```python
import torch

def _softmax(x, axis=-1):
    return torch.softmax(x, dim=axis)

def _gelu(x):
    return torch.nn.functional.gelu(x, approximate='tanh')

def _silu(x):
    return torch.nn.functional.silu(x)

def _sigmoid(x):
    return torch.sigmoid(x)

def _layernorm(x, axis=-1, eps=1e-05):
    m = x.mean(dim=axis, keepdim=True)
    v = x.var(dim=axis, keepdim=True, unbiased=False)
    return (x - m) / torch.sqrt(v + eps)

def _scatter_add(tgt, idx, src, axis=0):
    return tgt.clone().index_add_(axis, idx, src)

def _segment_sum(src, seg, n):
    out = torch.zeros((n,) + src.shape[1:], dtype=src.dtype)
    return out.index_add_(0, seg, src)

def _pad(x, pw):
    flat = tuple((v for pair in reversed(pw) for v in pair))
    return torch.nn.functional.pad(x, flat)
kernel_name = 'standalone__neighborhood_nat__vision'

def setup_inputs():

    _w = lambda a: (lambda t: t.to(torch.bfloat16) if t.is_floating_point() else t)(torch.as_tensor(a))
    H = W = 224
    C = 192
    return {'x': _w((lambda *s: torch.randn(*s, dtype=torch.bfloat16) * 0.2)(1, H, W, C)), 'wqkv': _w((lambda *s: torch.randn(*s, dtype=torch.bfloat16) * 0.2)(C, 3 * C)), 'wo': _w((lambda *s: torch.randn(*s, dtype=torch.bfloat16) * 0.05)(C, C))}

def reference(x, wqkv, wo):
    B, H, W, C = x.shape
    ks, dil = (7, 2)
    qkv = x @ wqkv
    q, k, v = (qkv[..., :C].clone(), qkv[..., C:2 * C].clone(), qkv[..., 2 * C:].clone())
    half = (ks - 1) // 2 * dil
    ir = torch.arange(H)
    ic = torch.arange(W)
    off = torch.arange(ks) * dil
    r0 = torch.clip(ir - half, 0, H - 1 - (ks - 1) * dil)
    c0 = torch.clip(ic - half, 0, W - 1 - (ks - 1) * dil)
    ri = r0[:, None] + off[None, :]
    ci = c0[:, None] + off[None, :]
    nidx = (ri[:, None, :, None] * W + ci[None, :, None, :]).reshape(1, H * W * ks * ks, 1)
    kf = k.reshape(B, H * W, C)
    vf = v.reshape(B, H * W, C)
    kn = (lambda x, i, axis: torch.take_along_dim(x, i, dim=axis))(kf, nidx, 1).reshape(B, H * W, ks * ks, C)
    vn = (lambda x, i, axis: torch.take_along_dim(x, i, dim=axis))(vf, nidx, 1).reshape(B, H * W, ks * ks, C)
    qf = q.reshape(B, H * W, C)
    scale = C ** (-0.5)
    logits = torch.einsum('bnc,bnkc->bnk', qf, kn) * scale
    p = _softmax(logits, axis=-1)
    o = torch.einsum('bnk,bnkc->bnc', p, vn) @ wo
    return o.reshape(B, H, W, C)
```

```cpp
#include <cuda_runtime.h>
#include <cuda_bf16.h>
#include <cuda.h>
#include <stdint.h>

#define NAT_P1 2
#define NAT_P2 4
#define NAT_H0 2
#define NAT_T0 2150
#define NAT_TD 1250
#define NAT_TW2 4500
#define NAT_TX2 3600
#define NAT_X1P 4
#define NAT_PK 3
#define NAT_HP 1800
#define NAT_PFD 700
#define NAT_XW 200
#define NAT_SU 8
#define NAT_TL 0
#define NAT_PW 0
#define NAT_WP 0
#define NAT_XF 1
#define NAT_SB 0
namespace nat {

constexpr int kW = 224, kC = 192;
constexpr int kCtas = 132;
constexpr int kTilesPerCta = 6;
constexpr float kAlpha = 0.07216878364870322f * 1.4426950408889634f;
constexpr uint32_t kChunkBytes = 13 * 1024;
constexpr uint32_t kWChunk = 192 * 128;
constexpr uint32_t kWBytes = 3 * kWChunk;
constexpr uint32_t kW1Off = 6 * kChunkBytes;
constexpr uint32_t kW2Off = kW1Off + kWBytes;
constexpr uint32_t kXOff = kW2Off + kWChunk;
constexpr uint32_t kOutOff = kW2Off;
constexpr uint32_t kBarOff = kW2Off + kWBytes;
constexpr uint32_t kProfOff = kBarOff + 208;
constexpr uint32_t kSmemBytes = kBarOff + 1024;

static_assert(kW1Off % 1024 == 0 && kW2Off % 1024 == 0 && kChunkBytes % 1024 == 0, "swizzle alignment");
static_assert(kSmemBytes <= 232448, "smem");

constexpr uint32_t kEmpty = 0xFFFFFFFFu;
#define NAT_R8(v) v, v, v, v, v, v, v, v
#define NAT_R2K(v) NAT_R8(NAT_R8(NAT_R8(v))), NAT_R8(NAT_R8(NAT_R8(v))), NAT_R8(NAT_R8(NAT_R8(v))), NAT_R8(NAT_R8(NAT_R8(v)))
#define NAT_IMG NAT_R8(NAT_R2K(kEmpty)), NAT_R2K(kEmpty)
__device__ __align__(1024) uint32_t g_wimg32[3 * kWBytes / 4] = {NAT_IMG, NAT_IMG, NAT_IMG};
static_assert(kWBytes / 4 == 9 * 2048, "initialiser");
__device__ __align__(128) uint32_t g_flag[96];
__device__ __forceinline__ uint32_t w2_offset() {
  uint32_t v;
  asm volatile("ld.relaxed.gpu.global.u32 %0, [%1];" : "=r"(v) : "l"(g_flag + 64) : "memory");
  return (1 + v) * kWBytes;
}

#define PROFS(id, wgid, slotid) do { } while (0)
#define PROF(wgid, slotid) do { } while (0)
#define PROF_DUMP(wgid) do { } while (0)

#define GT(slotid) do { } while (0)
#define GT_DUMP() do { } while (0)

__device__ __forceinline__ uint32_t smem_u32(const void* p) { return (uint32_t)__cvta_generic_to_shared(p); }

__device__ __forceinline__ void mbar_init(uint32_t bar, uint32_t count) {
  asm volatile("mbarrier.init.shared::cta.b64 [%0], %1;" ::"r"(bar), "r"(count) : "memory");
}
__device__ __forceinline__ void mbar_arrive(uint32_t bar) {
  asm volatile("mbarrier.arrive.shared::cta.b64 _, [%0];" ::"r"(bar) : "memory");
}
__device__ __forceinline__ void mbar_arrive_expect_tx(uint32_t bar, uint32_t bytes) {
  asm volatile("mbarrier.arrive.expect_tx.shared::cta.b64 _, [%0], %1;" ::"r"(bar), "r"(bytes) : "memory");
}
__device__ __forceinline__ void mbar_wait(uint32_t bar, uint32_t parity) {
  uint32_t ok;
  uint32_t it = 0;
  do {
    asm volatile(
        "{\n.reg .pred p;\n"
        "mbarrier.try_wait.parity.shared::cta.b64 p, [%1], %2;\n"
        "selp.u32 %0, 1, 0, p;\n}\n"
        : "=r"(ok)
        : "r"(bar), "r"(parity)
        : "memory");
    if (++it > (1u << 24)) break;
  } while (!ok);
}
__device__ __forceinline__ bool elect_one() {
  uint32_t r;
  asm volatile("{\n.reg .pred p;\nelect.sync _|p, 0xffffffff;\nselp.u32 %0, 1, 0, p;\n}\n" : "=r"(r));
  return r != 0;
}
__device__ __forceinline__ void nb_arrive(int id) { asm volatile("bar.arrive %0, 256;" ::"r"(id) : "memory"); }
__device__ __forceinline__ void nb_sync(int id) { asm volatile("bar.sync %0, 256;" ::"r"(id) : "memory"); }
__device__ __forceinline__ void nb_arrive_p(int id) { asm volatile("bar.arrive %0, 160;" ::"r"(id) : "memory"); }
__device__ __forceinline__ void nb_sync_p(int id) { asm volatile("bar.sync %0, 160;" ::"r"(id) : "memory"); }
__device__ __forceinline__ void fence_proxy_async() { asm volatile("fence.proxy.async.shared::cta;" ::: "memory"); }

__device__ __forceinline__ void tma_load_5d(uint32_t dst, const CUtensorMap* map, uint32_t bar, int c0, int c1, int c2,
                                            int c3, int c4) {
  asm volatile(
      "cp.async.bulk.tensor.5d.shared::cluster.global.tile.mbarrier::complete_tx::bytes "
      "[%0], [%1, {%3, %4, %5, %6, %7}], [%2];"
      ::"r"(dst), "l"((uint64_t)map), "r"(bar), "r"(c0), "r"(c1), "r"(c2), "r"(c3), "r"(c4)
      : "memory");
}
__device__ __forceinline__ void bulk_load(uint32_t dst, const void* src, uint32_t bytes, uint32_t bar) {
  asm volatile("cp.async.bulk.shared::cluster.global.mbarrier::complete_tx::bytes [%0], [%1], %2, [%3];"
               ::"r"(dst), "l"((uint64_t)src), "r"(bytes), "r"(bar)
               : "memory");
}

__device__ __forceinline__ void wg_fence() { asm volatile("wgmma.fence.sync.aligned;" ::: "memory"); }
__device__ __forceinline__ void wg_commit() { asm volatile("wgmma.commit_group.sync.aligned;" ::: "memory"); }
template <int N>
__device__ __forceinline__ void wg_wait() { asm volatile("wgmma.wait_group.sync.aligned %0;" ::"n"(N) : "memory"); }

template <int N>
__device__ __forceinline__ void fence_regs(float (&d)[N]) {
#pragma unroll
  for (int i = 0; i < N; i++) asm volatile("" : "+f"(d[i])::"memory");
}
template <int N>
__device__ __forceinline__ void keep_regs(uint32_t (&d)[N]) {
#pragma unroll
  for (int i = 0; i < N; i++) asm volatile("" : "+r"(d[i])::"memory");
}

__device__ __forceinline__ uint32_t pack_bf16(float lo, float hi) {
  uint32_t d;
  asm("cvt.rn.bf16x2.f32 %0, %1, %2;" : "=r"(d) : "f"(hi), "f"(lo));
  return d;
}
__device__ __forceinline__ float ex2(float x) {
  float y;
  asm("ex2.approx.ftz.f32 %0, %1;" : "=f"(y) : "f"(x));
  return y;
}
__device__ __forceinline__ float rcp_approx(float x) {
  float y;
  asm("rcp.approx.ftz.f32 %0, %1;" : "=f"(y) : "f"(x));
  return y;
}
__device__ __forceinline__ uint4 ldg128_nc(const void* p) {
  uint4 v;
  asm volatile("ld.global.nc.v4.u32 {%0,%1,%2,%3}, [%4];" : "=r"(v.x), "=r"(v.y), "=r"(v.z), "=r"(v.w) : "l"(p));
  return v;
}
__device__ __forceinline__ void stg128(void* p, uint32_t a, uint32_t b, uint32_t c, uint32_t d) {
  asm volatile("st.global.v4.u32 [%0], {%1,%2,%3,%4};" ::"l"(p), "r"(a), "r"(b), "r"(c), "r"(d) : "memory");
}

__device__ __forceinline__ long long clk64() {
  long long c;
  asm volatile("mov.u64 %0, %clock64;" : "=l"(c)::"memory");
  return c;
}
__device__ __forceinline__ void sched_fence() { while (clk64() < 0) { } }

__device__ __forceinline__ uint64_t make_desc(uint32_t addr, uint32_t lbo, uint32_t sbo, uint32_t mode = 1) {
  return (uint64_t)((addr & 0x3FFFF) >> 4) | ((uint64_t)(lbo >> 4) << 16) | ((uint64_t)(sbo >> 4) << 32) |
         ((uint64_t)mode << 62);
}

template <int OFF, int NN>
__device__ __forceinline__ void wg_m192(float (&d)[NN], uint64_t desc_a, uint64_t desc_b, int scale_d) {
  asm volatile(
      "{\n.reg .pred p;\nsetp.ne.b32 p, %98, 0;\n"
      "wgmma.mma_async.sync.aligned.m64n192k16.f32.bf16.bf16 "
      "{%0,%1,%2,%3,%4,%5,%6,%7,%8,%9,%10,%11,%12,%13,%14,%15,"
      "%16,%17,%18,%19,%20,%21,%22,%23,%24,%25,%26,%27,%28,%29,%30,%31,"
      "%32,%33,%34,%35,%36,%37,%38,%39,%40,%41,%42,%43,%44,%45,%46,%47,"
      "%48,%49,%50,%51,%52,%53,%54,%55,%56,%57,%58,%59,%60,%61,%62,%63,"
      "%64,%65,%66,%67,%68,%69,%70,%71,%72,%73,%74,%75,%76,%77,%78,%79,"
      "%80,%81,%82,%83,%84,%85,%86,%87,%88,%89,%90,%91,%92,%93,%94,%95}, "
      "%96, %97, p, 1, 1, 0, 0;\n}\n"
      : "+f"(d[OFF + 0]), "+f"(d[OFF + 1]), "+f"(d[OFF + 2]), "+f"(d[OFF + 3]), "+f"(d[OFF + 4]), "+f"(d[OFF + 5]),
        "+f"(d[OFF + 6]), "+f"(d[OFF + 7]), "+f"(d[OFF + 8]), "+f"(d[OFF + 9]), "+f"(d[OFF + 10]), "+f"(d[OFF + 11]),
        "+f"(d[OFF + 12]), "+f"(d[OFF + 13]), "+f"(d[OFF + 14]), "+f"(d[OFF + 15]), "+f"(d[OFF + 16]), "+f"(d[OFF + 17]),
        "+f"(d[OFF + 18]), "+f"(d[OFF + 19]), "+f"(d[OFF + 20]), "+f"(d[OFF + 21]), "+f"(d[OFF + 22]), "+f"(d[OFF + 23]),
        "+f"(d[OFF + 24]), "+f"(d[OFF + 25]), "+f"(d[OFF + 26]), "+f"(d[OFF + 27]), "+f"(d[OFF + 28]), "+f"(d[OFF + 29]),
        "+f"(d[OFF + 30]), "+f"(d[OFF + 31]), "+f"(d[OFF + 32]), "+f"(d[OFF + 33]), "+f"(d[OFF + 34]), "+f"(d[OFF + 35]),
        "+f"(d[OFF + 36]), "+f"(d[OFF + 37]), "+f"(d[OFF + 38]), "+f"(d[OFF + 39]), "+f"(d[OFF + 40]), "+f"(d[OFF + 41]),
        "+f"(d[OFF + 42]), "+f"(d[OFF + 43]), "+f"(d[OFF + 44]), "+f"(d[OFF + 45]), "+f"(d[OFF + 46]), "+f"(d[OFF + 47]),
        "+f"(d[OFF + 48]), "+f"(d[OFF + 49]), "+f"(d[OFF + 50]), "+f"(d[OFF + 51]), "+f"(d[OFF + 52]), "+f"(d[OFF + 53]),
        "+f"(d[OFF + 54]), "+f"(d[OFF + 55]), "+f"(d[OFF + 56]), "+f"(d[OFF + 57]), "+f"(d[OFF + 58]), "+f"(d[OFF + 59]),
        "+f"(d[OFF + 60]), "+f"(d[OFF + 61]), "+f"(d[OFF + 62]), "+f"(d[OFF + 63]), "+f"(d[OFF + 64]), "+f"(d[OFF + 65]),
        "+f"(d[OFF + 66]), "+f"(d[OFF + 67]), "+f"(d[OFF + 68]), "+f"(d[OFF + 69]), "+f"(d[OFF + 70]), "+f"(d[OFF + 71]),
        "+f"(d[OFF + 72]), "+f"(d[OFF + 73]), "+f"(d[OFF + 74]), "+f"(d[OFF + 75]), "+f"(d[OFF + 76]), "+f"(d[OFF + 77]),
        "+f"(d[OFF + 78]), "+f"(d[OFF + 79]), "+f"(d[OFF + 80]), "+f"(d[OFF + 81]), "+f"(d[OFF + 82]), "+f"(d[OFF + 83]),
        "+f"(d[OFF + 84]), "+f"(d[OFF + 85]), "+f"(d[OFF + 86]), "+f"(d[OFF + 87]), "+f"(d[OFF + 88]), "+f"(d[OFF + 89]),
        "+f"(d[OFF + 90]), "+f"(d[OFF + 91]), "+f"(d[OFF + 92]), "+f"(d[OFF + 93]), "+f"(d[OFF + 94]), "+f"(d[OFF + 95])
      : "l"(desc_a), "l"(desc_b), "r"(scale_d));
}

template <int OFF, int NN>
__device__ __forceinline__ void wg_m192z(float (&d)[NN], uint64_t desc_a, uint64_t desc_b, int scale_d) {
  asm volatile(
      "{\n.reg .pred p;\nsetp.ne.b32 p, %98, 0;\n"
      "wgmma.mma_async.sync.aligned.m64n192k16.f32.bf16.bf16 "
      "{%0,%1,%2,%3,%4,%5,%6,%7,%8,%9,%10,%11,%12,%13,%14,%15,"
      "%16,%17,%18,%19,%20,%21,%22,%23,%24,%25,%26,%27,%28,%29,%30,%31,"
      "%32,%33,%34,%35,%36,%37,%38,%39,%40,%41,%42,%43,%44,%45,%46,%47,"
      "%48,%49,%50,%51,%52,%53,%54,%55,%56,%57,%58,%59,%60,%61,%62,%63,"
      "%64,%65,%66,%67,%68,%69,%70,%71,%72,%73,%74,%75,%76,%77,%78,%79,"
      "%80,%81,%82,%83,%84,%85,%86,%87,%88,%89,%90,%91,%92,%93,%94,%95}, "
      "%96, %97, p, 1, 1, 0, 0;\n}\n"
      : "=f"(d[OFF + 0]), "=f"(d[OFF + 1]), "=f"(d[OFF + 2]), "=f"(d[OFF + 3]), "=f"(d[OFF + 4]), "=f"(d[OFF + 5]),
        "=f"(d[OFF + 6]), "=f"(d[OFF + 7]), "=f"(d[OFF + 8]), "=f"(d[OFF + 9]), "=f"(d[OFF + 10]), "=f"(d[OFF + 11]),
        "=f"(d[OFF + 12]), "=f"(d[OFF + 13]), "=f"(d[OFF + 14]), "=f"(d[OFF + 15]), "=f"(d[OFF + 16]), "=f"(d[OFF + 17]),
        "=f"(d[OFF + 18]), "=f"(d[OFF + 19]), "=f"(d[OFF + 20]), "=f"(d[OFF + 21]), "=f"(d[OFF + 22]), "=f"(d[OFF + 23]),
        "=f"(d[OFF + 24]), "=f"(d[OFF + 25]), "=f"(d[OFF + 26]), "=f"(d[OFF + 27]), "=f"(d[OFF + 28]), "=f"(d[OFF + 29]),
        "=f"(d[OFF + 30]), "=f"(d[OFF + 31]), "=f"(d[OFF + 32]), "=f"(d[OFF + 33]), "=f"(d[OFF + 34]), "=f"(d[OFF + 35]),
        "=f"(d[OFF + 36]), "=f"(d[OFF + 37]), "=f"(d[OFF + 38]), "=f"(d[OFF + 39]), "=f"(d[OFF + 40]), "=f"(d[OFF + 41]),
        "=f"(d[OFF + 42]), "=f"(d[OFF + 43]), "=f"(d[OFF + 44]), "=f"(d[OFF + 45]), "=f"(d[OFF + 46]), "=f"(d[OFF + 47]),
        "=f"(d[OFF + 48]), "=f"(d[OFF + 49]), "=f"(d[OFF + 50]), "=f"(d[OFF + 51]), "=f"(d[OFF + 52]), "=f"(d[OFF + 53]),
        "=f"(d[OFF + 54]), "=f"(d[OFF + 55]), "=f"(d[OFF + 56]), "=f"(d[OFF + 57]), "=f"(d[OFF + 58]), "=f"(d[OFF + 59]),
        "=f"(d[OFF + 60]), "=f"(d[OFF + 61]), "=f"(d[OFF + 62]), "=f"(d[OFF + 63]), "=f"(d[OFF + 64]), "=f"(d[OFF + 65]),
        "=f"(d[OFF + 66]), "=f"(d[OFF + 67]), "=f"(d[OFF + 68]), "=f"(d[OFF + 69]), "=f"(d[OFF + 70]), "=f"(d[OFF + 71]),
        "=f"(d[OFF + 72]), "=f"(d[OFF + 73]), "=f"(d[OFF + 74]), "=f"(d[OFF + 75]), "=f"(d[OFF + 76]), "=f"(d[OFF + 77]),
        "=f"(d[OFF + 78]), "=f"(d[OFF + 79]), "=f"(d[OFF + 80]), "=f"(d[OFF + 81]), "=f"(d[OFF + 82]), "=f"(d[OFF + 83]),
        "=f"(d[OFF + 84]), "=f"(d[OFF + 85]), "=f"(d[OFF + 86]), "=f"(d[OFF + 87]), "=f"(d[OFF + 88]), "=f"(d[OFF + 89]),
        "=f"(d[OFF + 90]), "=f"(d[OFF + 91]), "=f"(d[OFF + 92]), "=f"(d[OFF + 93]), "=f"(d[OFF + 94]), "=f"(d[OFF + 95])
      : "l"(desc_a), "l"(desc_b), "r"(scale_d));
}

template <int OFF, int NN>
__device__ __forceinline__ void wg_m192t(float (&d)[NN], uint64_t desc_a, uint64_t desc_b, int scale_d) {
  asm volatile(
      "{\n.reg .pred p;\nsetp.ne.b32 p, %98, 0;\n"
      "wgmma.mma_async.sync.aligned.m64n192k16.f32.bf16.bf16 "
      "{%0,%1,%2,%3,%4,%5,%6,%7,%8,%9,%10,%11,%12,%13,%14,%15,"
      "%16,%17,%18,%19,%20,%21,%22,%23,%24,%25,%26,%27,%28,%29,%30,%31,"
      "%32,%33,%34,%35,%36,%37,%38,%39,%40,%41,%42,%43,%44,%45,%46,%47,"
      "%48,%49,%50,%51,%52,%53,%54,%55,%56,%57,%58,%59,%60,%61,%62,%63,"
      "%64,%65,%66,%67,%68,%69,%70,%71,%72,%73,%74,%75,%76,%77,%78,%79,"
      "%80,%81,%82,%83,%84,%85,%86,%87,%88,%89,%90,%91,%92,%93,%94,%95}, "
      "%96, %97, p, 1, 1, 0, 1;\n}\n"
      : "+f"(d[OFF + 0]), "+f"(d[OFF + 1]), "+f"(d[OFF + 2]), "+f"(d[OFF + 3]), "+f"(d[OFF + 4]), "+f"(d[OFF + 5]),
        "+f"(d[OFF + 6]), "+f"(d[OFF + 7]), "+f"(d[OFF + 8]), "+f"(d[OFF + 9]), "+f"(d[OFF + 10]), "+f"(d[OFF + 11]),
        "+f"(d[OFF + 12]), "+f"(d[OFF + 13]), "+f"(d[OFF + 14]), "+f"(d[OFF + 15]), "+f"(d[OFF + 16]), "+f"(d[OFF + 17]),
        "+f"(d[OFF + 18]), "+f"(d[OFF + 19]), "+f"(d[OFF + 20]), "+f"(d[OFF + 21]), "+f"(d[OFF + 22]), "+f"(d[OFF + 23]),
        "+f"(d[OFF + 24]), "+f"(d[OFF + 25]), "+f"(d[OFF + 26]), "+f"(d[OFF + 27]), "+f"(d[OFF + 28]), "+f"(d[OFF + 29]),
        "+f"(d[OFF + 30]), "+f"(d[OFF + 31]), "+f"(d[OFF + 32]), "+f"(d[OFF + 33]), "+f"(d[OFF + 34]), "+f"(d[OFF + 35]),
        "+f"(d[OFF + 36]), "+f"(d[OFF + 37]), "+f"(d[OFF + 38]), "+f"(d[OFF + 39]), "+f"(d[OFF + 40]), "+f"(d[OFF + 41]),
        "+f"(d[OFF + 42]), "+f"(d[OFF + 43]), "+f"(d[OFF + 44]), "+f"(d[OFF + 45]), "+f"(d[OFF + 46]), "+f"(d[OFF + 47]),
        "+f"(d[OFF + 48]), "+f"(d[OFF + 49]), "+f"(d[OFF + 50]), "+f"(d[OFF + 51]), "+f"(d[OFF + 52]), "+f"(d[OFF + 53]),
        "+f"(d[OFF + 54]), "+f"(d[OFF + 55]), "+f"(d[OFF + 56]), "+f"(d[OFF + 57]), "+f"(d[OFF + 58]), "+f"(d[OFF + 59]),
        "+f"(d[OFF + 60]), "+f"(d[OFF + 61]), "+f"(d[OFF + 62]), "+f"(d[OFF + 63]), "+f"(d[OFF + 64]), "+f"(d[OFF + 65]),
        "+f"(d[OFF + 66]), "+f"(d[OFF + 67]), "+f"(d[OFF + 68]), "+f"(d[OFF + 69]), "+f"(d[OFF + 70]), "+f"(d[OFF + 71]),
        "+f"(d[OFF + 72]), "+f"(d[OFF + 73]), "+f"(d[OFF + 74]), "+f"(d[OFF + 75]), "+f"(d[OFF + 76]), "+f"(d[OFF + 77]),
        "+f"(d[OFF + 78]), "+f"(d[OFF + 79]), "+f"(d[OFF + 80]), "+f"(d[OFF + 81]), "+f"(d[OFF + 82]), "+f"(d[OFF + 83]),
        "+f"(d[OFF + 84]), "+f"(d[OFF + 85]), "+f"(d[OFF + 86]), "+f"(d[OFF + 87]), "+f"(d[OFF + 88]), "+f"(d[OFF + 89]),
        "+f"(d[OFF + 90]), "+f"(d[OFF + 91]), "+f"(d[OFF + 92]), "+f"(d[OFF + 93]), "+f"(d[OFF + 94]), "+f"(d[OFF + 95])
      : "l"(desc_a), "l"(desc_b), "r"(scale_d));
}

template <int OFF, int NN>
__device__ __forceinline__ void wg_m192tz(float (&d)[NN], uint64_t desc_a, uint64_t desc_b, int scale_d) {
  asm volatile(
      "{\n.reg .pred p;\nsetp.ne.b32 p, %98, 0;\n"
      "wgmma.mma_async.sync.aligned.m64n192k16.f32.bf16.bf16 "
      "{%0,%1,%2,%3,%4,%5,%6,%7,%8,%9,%10,%11,%12,%13,%14,%15,"
      "%16,%17,%18,%19,%20,%21,%22,%23,%24,%25,%26,%27,%28,%29,%30,%31,"
      "%32,%33,%34,%35,%36,%37,%38,%39,%40,%41,%42,%43,%44,%45,%46,%47,"
      "%48,%49,%50,%51,%52,%53,%54,%55,%56,%57,%58,%59,%60,%61,%62,%63,"
      "%64,%65,%66,%67,%68,%69,%70,%71,%72,%73,%74,%75,%76,%77,%78,%79,"
      "%80,%81,%82,%83,%84,%85,%86,%87,%88,%89,%90,%91,%92,%93,%94,%95}, "
      "%96, %97, p, 1, 1, 0, 1;\n}\n"
      : "=f"(d[OFF + 0]), "=f"(d[OFF + 1]), "=f"(d[OFF + 2]), "=f"(d[OFF + 3]), "=f"(d[OFF + 4]), "=f"(d[OFF + 5]),
        "=f"(d[OFF + 6]), "=f"(d[OFF + 7]), "=f"(d[OFF + 8]), "=f"(d[OFF + 9]), "=f"(d[OFF + 10]), "=f"(d[OFF + 11]),
        "=f"(d[OFF + 12]), "=f"(d[OFF + 13]), "=f"(d[OFF + 14]), "=f"(d[OFF + 15]), "=f"(d[OFF + 16]), "=f"(d[OFF + 17]),
        "=f"(d[OFF + 18]), "=f"(d[OFF + 19]), "=f"(d[OFF + 20]), "=f"(d[OFF + 21]), "=f"(d[OFF + 22]), "=f"(d[OFF + 23]),
        "=f"(d[OFF + 24]), "=f"(d[OFF + 25]), "=f"(d[OFF + 26]), "=f"(d[OFF + 27]), "=f"(d[OFF + 28]), "=f"(d[OFF + 29]),
        "=f"(d[OFF + 30]), "=f"(d[OFF + 31]), "=f"(d[OFF + 32]), "=f"(d[OFF + 33]), "=f"(d[OFF + 34]), "=f"(d[OFF + 35]),
        "=f"(d[OFF + 36]), "=f"(d[OFF + 37]), "=f"(d[OFF + 38]), "=f"(d[OFF + 39]), "=f"(d[OFF + 40]), "=f"(d[OFF + 41]),
        "=f"(d[OFF + 42]), "=f"(d[OFF + 43]), "=f"(d[OFF + 44]), "=f"(d[OFF + 45]), "=f"(d[OFF + 46]), "=f"(d[OFF + 47]),
        "=f"(d[OFF + 48]), "=f"(d[OFF + 49]), "=f"(d[OFF + 50]), "=f"(d[OFF + 51]), "=f"(d[OFF + 52]), "=f"(d[OFF + 53]),
        "=f"(d[OFF + 54]), "=f"(d[OFF + 55]), "=f"(d[OFF + 56]), "=f"(d[OFF + 57]), "=f"(d[OFF + 58]), "=f"(d[OFF + 59]),
        "=f"(d[OFF + 60]), "=f"(d[OFF + 61]), "=f"(d[OFF + 62]), "=f"(d[OFF + 63]), "=f"(d[OFF + 64]), "=f"(d[OFF + 65]),
        "=f"(d[OFF + 66]), "=f"(d[OFF + 67]), "=f"(d[OFF + 68]), "=f"(d[OFF + 69]), "=f"(d[OFF + 70]), "=f"(d[OFF + 71]),
        "=f"(d[OFF + 72]), "=f"(d[OFF + 73]), "=f"(d[OFF + 74]), "=f"(d[OFF + 75]), "=f"(d[OFF + 76]), "=f"(d[OFF + 77]),
        "=f"(d[OFF + 78]), "=f"(d[OFF + 79]), "=f"(d[OFF + 80]), "=f"(d[OFF + 81]), "=f"(d[OFF + 82]), "=f"(d[OFF + 83]),
        "=f"(d[OFF + 84]), "=f"(d[OFF + 85]), "=f"(d[OFF + 86]), "=f"(d[OFF + 87]), "=f"(d[OFF + 88]), "=f"(d[OFF + 89]),
        "=f"(d[OFF + 90]), "=f"(d[OFF + 91]), "=f"(d[OFF + 92]), "=f"(d[OFF + 93]), "=f"(d[OFF + 94]), "=f"(d[OFF + 95])
      : "l"(desc_a), "l"(desc_b), "r"(scale_d));
}

template <int OFF, int NN>
__device__ __forceinline__ void wg_d96(float (&d)[NN], uint32_t a0, uint32_t a1, uint32_t a2, uint32_t a3,
                                       uint64_t desc_b, int scale_d) {
  asm volatile(
      "{\n.reg .pred p;\nsetp.ne.b32 p, %53, 0;\n"
      "wgmma.mma_async.sync.aligned.m64n96k16.f32.bf16.bf16 "
      "{%0,%1,%2,%3,%4,%5,%6,%7,%8,%9,%10,%11,%12,%13,%14,%15,"
      "%16,%17,%18,%19,%20,%21,%22,%23,%24,%25,%26,%27,%28,%29,%30,%31,"
      "%32,%33,%34,%35,%36,%37,%38,%39,%40,%41,%42,%43,%44,%45,%46,%47}, "
      "{%48,%49,%50,%51}, %52, p, 1, 1, 0;\n}\n"
      : "+f"(d[OFF + 0]), "+f"(d[OFF + 1]), "+f"(d[OFF + 2]), "+f"(d[OFF + 3]), "+f"(d[OFF + 4]), "+f"(d[OFF + 5]),
        "+f"(d[OFF + 6]), "+f"(d[OFF + 7]), "+f"(d[OFF + 8]), "+f"(d[OFF + 9]), "+f"(d[OFF + 10]), "+f"(d[OFF + 11]),
        "+f"(d[OFF + 12]), "+f"(d[OFF + 13]), "+f"(d[OFF + 14]), "+f"(d[OFF + 15]), "+f"(d[OFF + 16]), "+f"(d[OFF + 17]),
        "+f"(d[OFF + 18]), "+f"(d[OFF + 19]), "+f"(d[OFF + 20]), "+f"(d[OFF + 21]), "+f"(d[OFF + 22]), "+f"(d[OFF + 23]),
        "+f"(d[OFF + 24]), "+f"(d[OFF + 25]), "+f"(d[OFF + 26]), "+f"(d[OFF + 27]), "+f"(d[OFF + 28]), "+f"(d[OFF + 29]),
        "+f"(d[OFF + 30]), "+f"(d[OFF + 31]), "+f"(d[OFF + 32]), "+f"(d[OFF + 33]), "+f"(d[OFF + 34]), "+f"(d[OFF + 35]),
        "+f"(d[OFF + 36]), "+f"(d[OFF + 37]), "+f"(d[OFF + 38]), "+f"(d[OFF + 39]), "+f"(d[OFF + 40]), "+f"(d[OFF + 41]),
        "+f"(d[OFF + 42]), "+f"(d[OFF + 43]), "+f"(d[OFF + 44]), "+f"(d[OFF + 45]), "+f"(d[OFF + 46]), "+f"(d[OFF + 47])
      : "r"(a0), "r"(a1), "r"(a2), "r"(a3), "l"(desc_b), "r"(scale_d));
}

template <int OFF, int NN>
__device__ __forceinline__ void wg_d96z(float (&d)[NN], uint32_t a0, uint32_t a1, uint32_t a2, uint32_t a3,
                                       uint64_t desc_b, int scale_d) {
  asm volatile(
      "{\n.reg .pred p;\nsetp.ne.b32 p, %53, 0;\n"
      "wgmma.mma_async.sync.aligned.m64n96k16.f32.bf16.bf16 "
      "{%0,%1,%2,%3,%4,%5,%6,%7,%8,%9,%10,%11,%12,%13,%14,%15,"
      "%16,%17,%18,%19,%20,%21,%22,%23,%24,%25,%26,%27,%28,%29,%30,%31,"
      "%32,%33,%34,%35,%36,%37,%38,%39,%40,%41,%42,%43,%44,%45,%46,%47}, "
      "{%48,%49,%50,%51}, %52, p, 1, 1, 0;\n}\n"
      : "=f"(d[OFF + 0]), "=f"(d[OFF + 1]), "=f"(d[OFF + 2]), "=f"(d[OFF + 3]), "=f"(d[OFF + 4]), "=f"(d[OFF + 5]),
        "=f"(d[OFF + 6]), "=f"(d[OFF + 7]), "=f"(d[OFF + 8]), "=f"(d[OFF + 9]), "=f"(d[OFF + 10]), "=f"(d[OFF + 11]),
        "=f"(d[OFF + 12]), "=f"(d[OFF + 13]), "=f"(d[OFF + 14]), "=f"(d[OFF + 15]), "=f"(d[OFF + 16]), "=f"(d[OFF + 17]),
        "=f"(d[OFF + 18]), "=f"(d[OFF + 19]), "=f"(d[OFF + 20]), "=f"(d[OFF + 21]), "=f"(d[OFF + 22]), "=f"(d[OFF + 23]),
        "=f"(d[OFF + 24]), "=f"(d[OFF + 25]), "=f"(d[OFF + 26]), "=f"(d[OFF + 27]), "=f"(d[OFF + 28]), "=f"(d[OFF + 29]),
        "=f"(d[OFF + 30]), "=f"(d[OFF + 31]), "=f"(d[OFF + 32]), "=f"(d[OFF + 33]), "=f"(d[OFF + 34]), "=f"(d[OFF + 35]),
        "=f"(d[OFF + 36]), "=f"(d[OFF + 37]), "=f"(d[OFF + 38]), "=f"(d[OFF + 39]), "=f"(d[OFF + 40]), "=f"(d[OFF + 41]),
        "=f"(d[OFF + 42]), "=f"(d[OFF + 43]), "=f"(d[OFF + 44]), "=f"(d[OFF + 45]), "=f"(d[OFF + 46]), "=f"(d[OFF + 47])
      : "r"(a0), "r"(a1), "r"(a2), "r"(a3), "l"(desc_b), "r"(scale_d));
}

template <int OFF, int NN>
__device__ __forceinline__ void wg_s104(float (&d)[NN], uint32_t a0, uint32_t a1, uint32_t a2, uint32_t a3,
                                       uint64_t desc_b, int scale_d, uint32_t meta) {
  asm volatile(
      "{\n.reg .pred p;\nsetp.ne.b32 p, %57, 0;\n"
      "wgmma.mma_async.sp.sync.aligned.m64n104k32.f32.bf16.bf16 "
      "{%0,%1,%2,%3,%4,%5,%6,%7,%8,%9,%10,%11,%12,%13,%14,%15,"
      "%16,%17,%18,%19,%20,%21,%22,%23,%24,%25,%26,%27,%28,%29,%30,%31,"
      "%32,%33,%34,%35,%36,%37,%38,%39,%40,%41,%42,%43,%44,%45,%46,%47,"
      "%48,%49,%50,%51}, "
      "{%52,%53,%54,%55}, %56, %58, 0, p, 1, 1, 0;\n}\n"
      : "+f"(d[OFF + 0]), "+f"(d[OFF + 1]), "+f"(d[OFF + 2]), "+f"(d[OFF + 3]), "+f"(d[OFF + 4]), "+f"(d[OFF + 5]),
        "+f"(d[OFF + 6]), "+f"(d[OFF + 7]), "+f"(d[OFF + 8]), "+f"(d[OFF + 9]), "+f"(d[OFF + 10]), "+f"(d[OFF + 11]),
        "+f"(d[OFF + 12]), "+f"(d[OFF + 13]), "+f"(d[OFF + 14]), "+f"(d[OFF + 15]), "+f"(d[OFF + 16]), "+f"(d[OFF + 17]),
        "+f"(d[OFF + 18]), "+f"(d[OFF + 19]), "+f"(d[OFF + 20]), "+f"(d[OFF + 21]), "+f"(d[OFF + 22]), "+f"(d[OFF + 23]),
        "+f"(d[OFF + 24]), "+f"(d[OFF + 25]), "+f"(d[OFF + 26]), "+f"(d[OFF + 27]), "+f"(d[OFF + 28]), "+f"(d[OFF + 29]),
        "+f"(d[OFF + 30]), "+f"(d[OFF + 31]), "+f"(d[OFF + 32]), "+f"(d[OFF + 33]), "+f"(d[OFF + 34]), "+f"(d[OFF + 35]),
        "+f"(d[OFF + 36]), "+f"(d[OFF + 37]), "+f"(d[OFF + 38]), "+f"(d[OFF + 39]), "+f"(d[OFF + 40]), "+f"(d[OFF + 41]),
        "+f"(d[OFF + 42]), "+f"(d[OFF + 43]), "+f"(d[OFF + 44]), "+f"(d[OFF + 45]), "+f"(d[OFF + 46]), "+f"(d[OFF + 47]),
        "+f"(d[OFF + 48]), "+f"(d[OFF + 49]), "+f"(d[OFF + 50]), "+f"(d[OFF + 51])
      : "r"(a0), "r"(a1), "r"(a2), "r"(a3), "l"(desc_b), "r"(scale_d), "r"(meta));
}

template <int OFF, int NN>
__device__ __forceinline__ void wg_s104z(float (&d)[NN], uint32_t a0, uint32_t a1, uint32_t a2, uint32_t a3,
                                       uint64_t desc_b, int scale_d, uint32_t meta) {
  asm volatile(
      "{\n.reg .pred p;\nsetp.ne.b32 p, %57, 0;\n"
      "wgmma.mma_async.sp.sync.aligned.m64n104k32.f32.bf16.bf16 "
      "{%0,%1,%2,%3,%4,%5,%6,%7,%8,%9,%10,%11,%12,%13,%14,%15,"
      "%16,%17,%18,%19,%20,%21,%22,%23,%24,%25,%26,%27,%28,%29,%30,%31,"
      "%32,%33,%34,%35,%36,%37,%38,%39,%40,%41,%42,%43,%44,%45,%46,%47,"
      "%48,%49,%50,%51}, "
      "{%52,%53,%54,%55}, %56, %58, 0, p, 1, 1, 0;\n}\n"
      : "=f"(d[OFF + 0]), "=f"(d[OFF + 1]), "=f"(d[OFF + 2]), "=f"(d[OFF + 3]), "=f"(d[OFF + 4]), "=f"(d[OFF + 5]),
        "=f"(d[OFF + 6]), "=f"(d[OFF + 7]), "=f"(d[OFF + 8]), "=f"(d[OFF + 9]), "=f"(d[OFF + 10]), "=f"(d[OFF + 11]),
        "=f"(d[OFF + 12]), "=f"(d[OFF + 13]), "=f"(d[OFF + 14]), "=f"(d[OFF + 15]), "=f"(d[OFF + 16]), "=f"(d[OFF + 17]),
        "=f"(d[OFF + 18]), "=f"(d[OFF + 19]), "=f"(d[OFF + 20]), "=f"(d[OFF + 21]), "=f"(d[OFF + 22]), "=f"(d[OFF + 23]),
        "=f"(d[OFF + 24]), "=f"(d[OFF + 25]), "=f"(d[OFF + 26]), "=f"(d[OFF + 27]), "=f"(d[OFF + 28]), "=f"(d[OFF + 29]),
        "=f"(d[OFF + 30]), "=f"(d[OFF + 31]), "=f"(d[OFF + 32]), "=f"(d[OFF + 33]), "=f"(d[OFF + 34]), "=f"(d[OFF + 35]),
        "=f"(d[OFF + 36]), "=f"(d[OFF + 37]), "=f"(d[OFF + 38]), "=f"(d[OFF + 39]), "=f"(d[OFF + 40]), "=f"(d[OFF + 41]),
        "=f"(d[OFF + 42]), "=f"(d[OFF + 43]), "=f"(d[OFF + 44]), "=f"(d[OFF + 45]), "=f"(d[OFF + 46]), "=f"(d[OFF + 47]),
        "=f"(d[OFF + 48]), "=f"(d[OFF + 49]), "=f"(d[OFF + 50]), "=f"(d[OFF + 51])
      : "r"(a0), "r"(a1), "r"(a2), "r"(a3), "l"(desc_b), "r"(scale_d), "r"(meta));
}

template <int OFF, int NN>
__device__ __forceinline__ void wg_s48(float (&d)[NN], uint32_t a0, uint32_t a1, uint32_t a2, uint32_t a3,
                                       uint64_t desc_b, int scale_d, uint32_t meta) {
  asm volatile(
      "{\n.reg .pred p;\nsetp.ne.b32 p, %29, 0;\n"
      "wgmma.mma_async.sp.sync.aligned.m64n48k32.f32.bf16.bf16 "
      "{%0,%1,%2,%3,%4,%5,%6,%7,%8,%9,%10,%11,%12,%13,%14,%15,"
      "%16,%17,%18,%19,%20,%21,%22,%23}, "
      "{%24,%25,%26,%27}, %28, %30, 0, p, 1, 1, 0;\n}\n"
      : "+f"(d[OFF + 0]), "+f"(d[OFF + 1]), "+f"(d[OFF + 2]), "+f"(d[OFF + 3]), "+f"(d[OFF + 4]), "+f"(d[OFF + 5]),
        "+f"(d[OFF + 6]), "+f"(d[OFF + 7]), "+f"(d[OFF + 8]), "+f"(d[OFF + 9]), "+f"(d[OFF + 10]), "+f"(d[OFF + 11]),
        "+f"(d[OFF + 12]), "+f"(d[OFF + 13]), "+f"(d[OFF + 14]), "+f"(d[OFF + 15]), "+f"(d[OFF + 16]), "+f"(d[OFF + 17]),
        "+f"(d[OFF + 18]), "+f"(d[OFF + 19]), "+f"(d[OFF + 20]), "+f"(d[OFF + 21]), "+f"(d[OFF + 22]), "+f"(d[OFF + 23])
      : "r"(a0), "r"(a1), "r"(a2), "r"(a3), "l"(desc_b), "r"(scale_d), "r"(meta));
}

template <int OFF, int NN>
__device__ __forceinline__ void wg_s48z(float (&d)[NN], uint32_t a0, uint32_t a1, uint32_t a2, uint32_t a3,
                                       uint64_t desc_b, int scale_d, uint32_t meta) {
  asm volatile(
      "{\n.reg .pred p;\nsetp.ne.b32 p, %29, 0;\n"
      "wgmma.mma_async.sp.sync.aligned.m64n48k32.f32.bf16.bf16 "
      "{%0,%1,%2,%3,%4,%5,%6,%7,%8,%9,%10,%11,%12,%13,%14,%15,"
      "%16,%17,%18,%19,%20,%21,%22,%23}, "
      "{%24,%25,%26,%27}, %28, %30, 0, p, 1, 1, 0;\n}\n"
      : "=f"(d[OFF + 0]), "=f"(d[OFF + 1]), "=f"(d[OFF + 2]), "=f"(d[OFF + 3]), "=f"(d[OFF + 4]), "=f"(d[OFF + 5]),
        "=f"(d[OFF + 6]), "=f"(d[OFF + 7]), "=f"(d[OFF + 8]), "=f"(d[OFF + 9]), "=f"(d[OFF + 10]), "=f"(d[OFF + 11]),
        "=f"(d[OFF + 12]), "=f"(d[OFF + 13]), "=f"(d[OFF + 14]), "=f"(d[OFF + 15]), "=f"(d[OFF + 16]), "=f"(d[OFF + 17]),
        "=f"(d[OFF + 18]), "=f"(d[OFF + 19]), "=f"(d[OFF + 20]), "=f"(d[OFF + 21]), "=f"(d[OFF + 22]), "=f"(d[OFF + 23])
      : "r"(a0), "r"(a1), "r"(a2), "r"(a3), "l"(desc_b), "r"(scale_d), "r"(meta));
}

template <int OFF, int NN>
__device__ __forceinline__ void wg_s56(float (&d)[NN], uint32_t a0, uint32_t a1, uint32_t a2, uint32_t a3,
                                       uint64_t desc_b, int scale_d, uint32_t meta) {
  asm volatile(
      "{\n.reg .pred p;\nsetp.ne.b32 p, %33, 0;\n"
      "wgmma.mma_async.sp.sync.aligned.m64n56k32.f32.bf16.bf16 "
      "{%0,%1,%2,%3,%4,%5,%6,%7,%8,%9,%10,%11,%12,%13,%14,%15,"
      "%16,%17,%18,%19,%20,%21,%22,%23,%24,%25,%26,%27}, "
      "{%28,%29,%30,%31}, %32, %34, 0, p, 1, 1, 0;\n}\n"
      : "+f"(d[OFF + 0]), "+f"(d[OFF + 1]), "+f"(d[OFF + 2]), "+f"(d[OFF + 3]), "+f"(d[OFF + 4]), "+f"(d[OFF + 5]),
        "+f"(d[OFF + 6]), "+f"(d[OFF + 7]), "+f"(d[OFF + 8]), "+f"(d[OFF + 9]), "+f"(d[OFF + 10]), "+f"(d[OFF + 11]),
        "+f"(d[OFF + 12]), "+f"(d[OFF + 13]), "+f"(d[OFF + 14]), "+f"(d[OFF + 15]), "+f"(d[OFF + 16]), "+f"(d[OFF + 17]),
        "+f"(d[OFF + 18]), "+f"(d[OFF + 19]), "+f"(d[OFF + 20]), "+f"(d[OFF + 21]), "+f"(d[OFF + 22]), "+f"(d[OFF + 23]),
        "+f"(d[OFF + 24]), "+f"(d[OFF + 25]), "+f"(d[OFF + 26]), "+f"(d[OFF + 27])
      : "r"(a0), "r"(a1), "r"(a2), "r"(a3), "l"(desc_b), "r"(scale_d), "r"(meta));
}

template <int OFF, int NN>
__device__ __forceinline__ void wg_s56z(float (&d)[NN], uint32_t a0, uint32_t a1, uint32_t a2, uint32_t a3,
                                       uint64_t desc_b, int scale_d, uint32_t meta) {
  asm volatile(
      "{\n.reg .pred p;\nsetp.ne.b32 p, %33, 0;\n"
      "wgmma.mma_async.sp.sync.aligned.m64n56k32.f32.bf16.bf16 "
      "{%0,%1,%2,%3,%4,%5,%6,%7,%8,%9,%10,%11,%12,%13,%14,%15,"
      "%16,%17,%18,%19,%20,%21,%22,%23,%24,%25,%26,%27}, "
      "{%28,%29,%30,%31}, %32, %34, 0, p, 1, 1, 0;\n}\n"
      : "=f"(d[OFF + 0]), "=f"(d[OFF + 1]), "=f"(d[OFF + 2]), "=f"(d[OFF + 3]), "=f"(d[OFF + 4]), "=f"(d[OFF + 5]),
        "=f"(d[OFF + 6]), "=f"(d[OFF + 7]), "=f"(d[OFF + 8]), "=f"(d[OFF + 9]), "=f"(d[OFF + 10]), "=f"(d[OFF + 11]),
        "=f"(d[OFF + 12]), "=f"(d[OFF + 13]), "=f"(d[OFF + 14]), "=f"(d[OFF + 15]), "=f"(d[OFF + 16]), "=f"(d[OFF + 17]),
        "=f"(d[OFF + 18]), "=f"(d[OFF + 19]), "=f"(d[OFF + 20]), "=f"(d[OFF + 21]), "=f"(d[OFF + 22]), "=f"(d[OFF + 23]),
        "=f"(d[OFF + 24]), "=f"(d[OFF + 25]), "=f"(d[OFF + 26]), "=f"(d[OFF + 27])
      : "r"(a0), "r"(a1), "r"(a2), "r"(a3), "l"(desc_b), "r"(scale_d), "r"(meta));
}

template <int OFF, int NN>
__device__ __forceinline__ void wg_s64t(float (&d)[NN], uint32_t a0, uint32_t a1, uint32_t a2, uint32_t a3,
                                       uint64_t desc_b, int scale_d, uint32_t meta) {
  asm volatile(
      "{\n.reg .pred p;\nsetp.ne.b32 p, %37, 0;\n"
      "wgmma.mma_async.sp.sync.aligned.m64n64k32.f32.bf16.bf16 "
      "{%0,%1,%2,%3,%4,%5,%6,%7,%8,%9,%10,%11,%12,%13,%14,%15,"
      "%16,%17,%18,%19,%20,%21,%22,%23,%24,%25,%26,%27,%28,%29,%30,%31}, "
      "{%32,%33,%34,%35}, %36, %38, 0, p, 1, 1, 1;\n}\n"
      : "+f"(d[OFF + 0]), "+f"(d[OFF + 1]), "+f"(d[OFF + 2]), "+f"(d[OFF + 3]), "+f"(d[OFF + 4]), "+f"(d[OFF + 5]),
        "+f"(d[OFF + 6]), "+f"(d[OFF + 7]), "+f"(d[OFF + 8]), "+f"(d[OFF + 9]), "+f"(d[OFF + 10]), "+f"(d[OFF + 11]),
        "+f"(d[OFF + 12]), "+f"(d[OFF + 13]), "+f"(d[OFF + 14]), "+f"(d[OFF + 15]), "+f"(d[OFF + 16]), "+f"(d[OFF + 17]),
        "+f"(d[OFF + 18]), "+f"(d[OFF + 19]), "+f"(d[OFF + 20]), "+f"(d[OFF + 21]), "+f"(d[OFF + 22]), "+f"(d[OFF + 23]),
        "+f"(d[OFF + 24]), "+f"(d[OFF + 25]), "+f"(d[OFF + 26]), "+f"(d[OFF + 27]), "+f"(d[OFF + 28]), "+f"(d[OFF + 29]),
        "+f"(d[OFF + 30]), "+f"(d[OFF + 31])
      : "r"(a0), "r"(a1), "r"(a2), "r"(a3), "l"(desc_b), "r"(scale_d), "r"(meta));
}

template <int OFF, int NN>
__device__ __forceinline__ void wg_s64t1(float (&d)[NN], uint32_t a0, uint32_t a1, uint32_t a2, uint32_t a3,
                                       uint64_t desc_b, int scale_d, uint32_t meta) {
  asm volatile(
      "{\n.reg .pred p;\nsetp.ne.b32 p, %37, 0;\n"
      "wgmma.mma_async.sp.sync.aligned.m64n64k32.f32.bf16.bf16 "
      "{%0,%1,%2,%3,%4,%5,%6,%7,%8,%9,%10,%11,%12,%13,%14,%15,"
      "%16,%17,%18,%19,%20,%21,%22,%23,%24,%25,%26,%27,%28,%29,%30,%31}, "
      "{%32,%33,%34,%35}, %36, %38, 1, p, 1, 1, 1;\n}\n"
      : "+f"(d[OFF + 0]), "+f"(d[OFF + 1]), "+f"(d[OFF + 2]), "+f"(d[OFF + 3]), "+f"(d[OFF + 4]), "+f"(d[OFF + 5]),
        "+f"(d[OFF + 6]), "+f"(d[OFF + 7]), "+f"(d[OFF + 8]), "+f"(d[OFF + 9]), "+f"(d[OFF + 10]), "+f"(d[OFF + 11]),
        "+f"(d[OFF + 12]), "+f"(d[OFF + 13]), "+f"(d[OFF + 14]), "+f"(d[OFF + 15]), "+f"(d[OFF + 16]), "+f"(d[OFF + 17]),
        "+f"(d[OFF + 18]), "+f"(d[OFF + 19]), "+f"(d[OFF + 20]), "+f"(d[OFF + 21]), "+f"(d[OFF + 22]), "+f"(d[OFF + 23]),
        "+f"(d[OFF + 24]), "+f"(d[OFF + 25]), "+f"(d[OFF + 26]), "+f"(d[OFF + 27]), "+f"(d[OFF + 28]), "+f"(d[OFF + 29]),
        "+f"(d[OFF + 30]), "+f"(d[OFF + 31])
      : "r"(a0), "r"(a1), "r"(a2), "r"(a3), "l"(desc_b), "r"(scale_d), "r"(meta));
}

template <int OFF, int NN>
__device__ __forceinline__ void wg_s64tz(float (&d)[NN], uint32_t a0, uint32_t a1, uint32_t a2, uint32_t a3,
                                       uint64_t desc_b, int scale_d, uint32_t meta) {
  asm volatile(
      "{\n.reg .pred p;\nsetp.ne.b32 p, %37, 0;\n"
      "wgmma.mma_async.sp.sync.aligned.m64n64k32.f32.bf16.bf16 "
      "{%0,%1,%2,%3,%4,%5,%6,%7,%8,%9,%10,%11,%12,%13,%14,%15,"
      "%16,%17,%18,%19,%20,%21,%22,%23,%24,%25,%26,%27,%28,%29,%30,%31}, "
      "{%32,%33,%34,%35}, %36, %38, 0, p, 1, 1, 1;\n}\n"
      : "=f"(d[OFF + 0]), "=f"(d[OFF + 1]), "=f"(d[OFF + 2]), "=f"(d[OFF + 3]), "=f"(d[OFF + 4]), "=f"(d[OFF + 5]),
        "=f"(d[OFF + 6]), "=f"(d[OFF + 7]), "=f"(d[OFF + 8]), "=f"(d[OFF + 9]), "=f"(d[OFF + 10]), "=f"(d[OFF + 11]),
        "=f"(d[OFF + 12]), "=f"(d[OFF + 13]), "=f"(d[OFF + 14]), "=f"(d[OFF + 15]), "=f"(d[OFF + 16]), "=f"(d[OFF + 17]),
        "=f"(d[OFF + 18]), "=f"(d[OFF + 19]), "=f"(d[OFF + 20]), "=f"(d[OFF + 21]), "=f"(d[OFF + 22]), "=f"(d[OFF + 23]),
        "=f"(d[OFF + 24]), "=f"(d[OFF + 25]), "=f"(d[OFF + 26]), "=f"(d[OFF + 27]), "=f"(d[OFF + 28]), "=f"(d[OFF + 29]),
        "=f"(d[OFF + 30]), "=f"(d[OFF + 31])
      : "r"(a0), "r"(a1), "r"(a2), "r"(a3), "l"(desc_b), "r"(scale_d), "r"(meta));
}

__device__ __forceinline__ int g2_inv(int ch) { return 32 * (ch >> 5) + 8 * ((ch >> 1) & 3) + 2 * ((ch >> 3) & 3) + (ch & 1); }
__host__ __device__ __forceinline__ uint32_t wimg_off(int n, int k) {
  return (uint32_t)(k >> 6) * kWChunk + (uint32_t)n * 128 + (uint32_t)((((k & 63) >> 3) ^ (n & 7)) << 4) + (k & 7) * 2;
}
__host__ __device__ constexpr int w2piece(int h, int c) { return c == 0 ? h : 1 + 2 * h + c; }
__device__ __forceinline__ uint32_t w2img_off(int n, int k) { return wimg_off(n % 96, k & 63) + w2piece(n >= 96, k >> 6) * (kWChunk / 2); }
__device__ __forceinline__ int qpix(int par, int t) {
  const int a = 2 * t + 13 * par - 6, b = t + 112 * par;
  return par ? min(a, b) : max(a, b);
}
__device__ __forceinline__ int woff(int par, int i, int r) {
  const int a = 99 * par + 6 - 8 * i;
  return par ? min(r, a) : max(r, a);
}

__device__ __forceinline__ void mma16816(float (&c)[4], uint32_t a0, uint32_t a1, uint32_t a2, uint32_t a3, uint32_t b0,
                                         uint32_t b1) {
  asm volatile(
      "mma.sync.aligned.m16n8k16.row.col.f32.bf16.bf16.f32 {%0,%1,%2,%3}, {%4,%5,%6,%7}, {%8,%9}, {%0,%1,%2,%3};"
      : "+f"(c[0]), "+f"(c[1]), "+f"(c[2]), "+f"(c[3])
      : "r"(a0), "r"(a1), "r"(a2), "r"(a3), "r"(b0), "r"(b1));
}

__device__ __forceinline__ void fold_w1(const int u, const __nv_bfloat16* __restrict__ wqkv, uint8_t* wimg) {
  const int g = (threadIdx.x >> 2) & 7, l = threadIdx.x & 3;
  const int m0 = (u / 12) * 16, s = u % 12;
  uint4 A[12], B[12];
  const __nv_bfloat16* arow = wqkv + (m0 + 4 * (g >> 1) + (g & 1)) * 576 + 192 + 8 * l;
  const __nv_bfloat16* brow = wqkv + (16 * s + 4 * (g >> 1) + (g & 1)) * 576 + 8 * l;
#pragma unroll
  for (int i = 0; i < 12; i++) {
    A[i] = ldg128_nc(arow + (i & 1) * 2 * 576 + 32 * (i >> 1));
    B[i] = ldg128_nc(brow + (i & 1) * 2 * 576 + 32 * (i >> 1));
  }
  sched_fence();
  uint8_t* dst = wimg + wimg_off(m0 + g, 16 * s + 4 * l);
  float acc[4][4];
#pragma unroll
  for (int j = 0; j < 16; j++) acc[j >> 2][j & 3] = 0.f;
#pragma unroll
  for (int i = 0; i < 6; i++) {
    const uint4 &a0 = A[2 * i], &a1 = A[2 * i + 1];
#pragma unroll
    for (int nb = 0; nb < 2; nb++) {
      mma16816(acc[2 * nb], a0.x, a1.x, a0.y, a1.y, B[2 * i + nb].x, B[2 * i + nb].y);
      mma16816(acc[2 * nb + 1], a0.z, a1.z, a0.w, a1.w, B[2 * i + nb].z, B[2 * i + nb].w);
    }
  }
#pragma unroll
  for (int j = 0; j < 2; j++) {
    const uint2 v = make_uint2(pack_bf16((acc[0][2 * j] + acc[1][2 * j]) * kAlpha, (acc[0][2 * j + 1] + acc[1][2 * j + 1]) * kAlpha),
                               pack_bf16((acc[2][2 * j] + acc[3][2 * j]) * kAlpha, (acc[2][2 * j + 1] + acc[3][2 * j + 1]) * kAlpha));
    asm volatile("st.relaxed.gpu.global.v2.u32 [%0], {%1,%2};" ::"l"(dst + j * 1024), "r"(v.x), "r"(v.y) : "memory");
  }
}
__device__ __forceinline__ void fold_w2(const int u, const __nv_bfloat16* __restrict__ wqkv, const __nv_bfloat16* __restrict__ wo,
                                        uint8_t* wimg) {
  const int g = (threadIdx.x >> 2) & 7, l = threadIdx.x & 3;
  const int m0 = (u / 12) * 32, n0 = (u % 12) * 16;
  uint4 S[12];
  uint32_t L[96];
  const __nv_bfloat16* brow = wqkv + (n0 + 4 * (g >> 1) + (g & 1)) * 576 + 384 + 8 * l;
#pragma unroll
  for (int i = 0; i < 12; i++) S[i] = ldg128_nc(brow + (i & 1) * 2 * 576 + 32 * (i >> 1));
  const __nv_bfloat16* acol = wo + (8 * l) * 192 + m0 + 4 * g;
#pragma unroll
  for (int c = 0; c < 48; c++)
    asm volatile("ld.global.nc.v2.u32 {%0,%1}, [%2];" : "=r"(L[2 * c]), "=r"(L[2 * c + 1]) : "l"(acol + (32 * (c >> 3) + (c & 7)) * 192));
  const uint32_t off = w2_offset();
  sched_fence();
  uint8_t* img = wimg + off;
  float acc[4][4];
#pragma unroll
  for (int j = 0; j < 16; j++) acc[j >> 2][j & 3] = 0.f;
#pragma unroll
  for (int i = 0; i < 6; i++) {
#pragma unroll
    for (int h = 0; h < 2; h++) {
      const uint4 &s0 = S[2 * i], &s1 = S[2 * i + 1];
#pragma unroll
      for (int mt = 0; mt < 2; mt++) {
        const uint32_t* a = L + 16 * i + 8 * h + mt;
        const uint32_t a0 = __byte_perm(a[0], a[2], 0x5410), a1 = __byte_perm(a[0], a[2], 0x7632);
        const uint32_t a2 = __byte_perm(a[4], a[6], 0x5410), a3 = __byte_perm(a[4], a[6], 0x7632);
        mma16816(acc[2 * mt], a0, a1, a2, a3, h ? s0.z : s0.x, h ? s0.w : s0.y);
        mma16816(acc[2 * mt + 1], a0, a1, a2, a3, h ? s1.z : s1.x, h ? s1.w : s1.y);
      }
    }
  }
#pragma unroll
  for (int j = 0; j < 4; j++) {
    const float(&c0)[4] = acc[j & 2];
    const float(&c1)[4] = acc[(j & 2) + 1];
    asm volatile("st.relaxed.gpu.global.v2.u32 [%0], {%1,%2};" ::"l"(img + w2img_off(g2_inv(m0 + 4 * g + j), n0 + 4 * l)),
                 "r"(pack_bf16(c0[2 * (j & 1)], c0[2 * (j & 1) + 1])), "r"(pack_bf16(c1[2 * (j & 1)], c1[2 * (j & 1) + 1])) : "memory");
  }
}

__global__ void __launch_bounds__(256) fold_kernel(const __nv_bfloat16* __restrict__ wqkv,
                                                   const __nv_bfloat16* __restrict__ wo, uint8_t* wimg) {
  const int u = blockIdx.x * 8 + (threadIdx.x >> 5);
  if (u < 144) fold_w1(u, wqkv, wimg);
  else fold_w2(u - 144, wqkv, wo, wimg);
}

struct TileCoord { int pr, pc, I, J, up, kind; };
struct TileTable { uint16_t e[kCtas * 6], g[6][8][2]; };
inline void make_tiles(TileTable& tt) {
  for (int tile = 0; tile < kCtas * 6; tile++) {
    const int b = tile / 6, k = tile - 6 * b;
    const int p = b < 128 ? (tile - 672) >> 1 : b - 80;
    const int strip = b < 112 ? b >> 1 : b >= 128 && k >= 2 ? (b & 1) * 27 + (b & 2) * 14 : p + (p < 26 ? 1 : 3);
    const int pr = strip >= 28, J = (strip - pr * 28) >> 1, pc = strip & 1, up = b < 112 ? b & 1 : pr;
    const int first = b < 112 ? 8 - 2 * pr - up : 13 * pr, step = b < 112 ? k : k & 1;
    const int I = up ? first - step : first + step;
    const int kind = b < 112 ? (J == 13 * pc ? 1 + pc : 0) : I == 13 * pr ? 4 + pr : 3;
    tt.e[tile] = (uint16_t)(I | J << 4 | pr << 8 | pc << 9 | up << 10 | kind << 11);
  }
  for (int kind = 0; kind < 6; kind++)
    for (int j = 0; j < 8; j++) {
      const int w = j >> 1, h = j & 1, e = kind % 3;
      auto off = [e](int t) { return e == 0 ? 2 * t : e == 1 ? t + (t == 7) : t + (t > 0); };
      tt.g[kind][j][0] = (uint16_t)(kind < 3 ? 3 * off(w + 4 * h) : 3 * (kW * off(2 * w) + 8 * h));
      tt.g[kind][j][1] = (uint16_t)(128 * (kind < 3 ? kind > 0 : 1 + off(2 * w + 1) - off(2 * w)));
    }
}
__device__ __forceinline__ int num_tiles() { return blockIdx.x < 128 ? 6 : 4; }
__device__ __forceinline__ TileCoord decode_tile(const TileTable& tt, int tile) {
  const uint32_t e = tt.e[tile];
  return TileCoord{(int)(e >> 8) & 1, (int)(e >> 9) & 1, (int)e & 15, (int)(e >> 4) & 15, (int)(e >> 10) & 1, (int)(e >> 11)};
}
__device__ __forceinline__ int halo_r0(const TileCoord& t) { return 8 * t.I + 6 * t.pr - 6; }
__device__ __forceinline__ int halo_c0(const TileCoord& t) { return min(max(8 * t.J + 6 * t.pc - 6, -3), 102); }

__device__ __forceinline__ uint32_t bar_full(uint32_t bars, int wg, int c) { return bars + (wg * 3 + c) * 8; }
__device__ __forceinline__ uint32_t bar_w1c(uint32_t bars, int c) { return bars + (6 + c) * 8; }
__device__ __forceinline__ uint32_t bar_w2(uint32_t bars) { return bars + 9 * 8; }
__device__ __forceinline__ uint32_t bar_x(uint32_t bars, int j) { return bars + (10 + j) * 8; }
__device__ __forceinline__ uint32_t bar_w1q(uint32_t bars) { return bars + 12 * 8; }
__device__ __forceinline__ uint32_t bar_xf(uint32_t bars) { return bars + 13 * 8; }
__device__ __forceinline__ uint32_t bar_w2m(uint32_t bars) { return bars + 14 * 8; }
__device__ __forceinline__ uint32_t bar_redo(uint32_t bars) { return bars + 15 * 8; }
__device__ __forceinline__ uint32_t bar_wok(uint32_t bars) { return bars + 16 * 8; }
__device__ __forceinline__ uint32_t bar_go(uint32_t bars, int j) { return bars + (17 + j) * 8; }
__device__ __forceinline__ uint32_t bar_raw(uint32_t bars) { return bars + 19 * 8; }
constexpr int kNumBars = 20;

__device__ __forceinline__ uint64_t wdesc(uint64_t d0, int s) { return d0 + (((s >> 2) * kWChunk + (s & 3) * 32) >> 4); }
__device__ __forceinline__ uint64_t w2desc(uint64_t d0, int i) { return d0 + ((w2piece(i / 12, i % 12 >> 2) * (kWChunk / 2) + (i & 3) * 32) >> 4); }

__device__ __forceinline__ int qrow(int w, int g) { return blockIdx.x < 112 ? g : 2 * w + (g & 1); }
__device__ __forceinline__ int qcol(int w, int g) { return blockIdx.x < 112 ? w : g >> 1; }
__device__ __forceinline__ bool edge_strip() {
  const int s = blockIdx.x >> 1;
  return s == 0 || s == 27 || s == 28 || s == 55;
}
template <int I0, int I1>
__device__ __forceinline__ void store_rows(bool on, __nv_bfloat16* pA, __nv_bfloat16* pB, const uint32_t (&a)[24], const uint32_t (&b)[24]) {
#pragma unroll
  for (int i = 2 * I0; i < 2 * I1; i++) {
    const uint32_t* v = (i & 1 ? b : a) + 4 * (i >> 1);
    asm volatile("{\n.reg .pred p;\nsetp.ne.u32 p, %5, 0;\n@p st.global.v4.u32 [%0], {%1,%2,%3,%4};\n}\n" ::"l"((i & 1 ? pB : pA) + 32 * (i >> 1)),
                 "r"(v[0]), "r"(v[1]), "r"(v[2]), "r"(v[3]), "r"((uint32_t)on) : "memory");
  }
}
template <int I0, int I1>
__device__ __forceinline__ void stage_out(uint32_t sts, const uint32_t (&a)[24], const uint32_t (&b)[24]) {
#pragma unroll
  for (int i = I0; i < I1; i++) {
    const uint32_t* v = (i < 6 ? a : b) + 4 * (i % 6);
    asm volatile("st.shared.v4.u32 [%0], {%1,%2,%3,%4};" ::"r"((sts ^ ((i & 1) << 6)) + (i / 6) * 12288 + (i % 6 >> 1) * 1024),
                 "r"(v[0]), "r"(v[1]), "r"(v[2]), "r"(v[3]) : "memory");
  }
}
__device__ __forceinline__ uint32_t now_ns() {
  uint32_t t;
  asm volatile("mov.u32 %0, %globaltimer_lo;" : "=r"(t)::"memory");
  return t;
}
__device__ __forceinline__ void wait_clock(uint32_t t_start, uint32_t t) {
  while (now_ns() - t_start < t) { }
}
#define NAT_PRED(f, m) ".reg .pred p;\n.reg .b32 t;\nand.b32 t, " f ", " m ";\nsetp.ne.u32 p, t, 0;\n"
constexpr uint32_t kHiV = 1, kHiU = 8, kColB = 0x20, kInV = 0x100, kInU = 0x1000, kColA = 0x10000;
template <uint32_t M>
__device__ __forceinline__ float pick(const float* a, const float* b, uint32_t f) {
  float d;
  asm("{\n" NAT_PRED("%5", "%6") "add.f32 %0, %1, %2;\n@p add.f32 %0, %3, %4;\n}\n"
      : "=&f"(d) : "f"(a[0]), "f"(a[2]), "f"(b[0]), "f"(b[2]), "r"(f), "n"(M));
  return d;
}
template <uint32_t M>
__device__ __forceinline__ float sel(float a, float b, uint32_t f) {
  float d;
  asm("{\n" NAT_PRED("%3", "%4") "selp.f32 %0, %1, %2, p;\n}\n" : "=f"(d) : "f"(a), "f"(b), "r"(f), "n"(M));
  return d;
}
template <uint32_t M>
__device__ __forceinline__ void max_if(float& m, float v, uint32_t f) {
  asm("{\n" NAT_PRED("%2", "%3") "@p max.f32 %0, %0, %1;\n}\n" : "+f"(m) : "f"(v), "r"(f), "n"(M));
}
template <uint32_t M>
__device__ __forceinline__ void add_if(float& m, float v, uint32_t f) {
  asm("{\n" NAT_PRED("%2", "%3") "@p add.f32 %0, %0, %1;\n}\n" : "+f"(m) : "f"(v), "r"(f), "n"(M));
}
__device__ __forceinline__ void pick_v(const float* a, float* v, uint32_t f) {
  v[0] = pick<kHiV>(a, a + 16, f), v[1] = pick<kHiV>(a + 1, a + 17, f);
  v[2] = pick<kHiV * 2>(a + 4, a + 20, f), v[3] = pick<kHiV * 2>(a + 5, a + 21, f);
  v[4] = pick<kHiV * 4>(a + 8, a + 24, f), v[5] = pick<kHiV * 4>(a + 9, a + 25, f);
  v[6] = a[12] + a[14], v[7] = a[13] + a[15];
}
__device__ __forceinline__ void pick_u(const float* a, float* v, uint32_t f) {
#pragma unroll
  for (int c = 0; c < 3; c++) v[2 * c] = pick<kHiU>(a + 4 * c, a + 4 * c + 12, f), v[2 * c + 1] = pick<kHiU * 2>(a + 4 * c + 1, a + 4 * c + 13, f);
}
__device__ __forceinline__ uint32_t sign_bytes(uint32_t v, uint32_t sel) {
  uint32_t d;
  asm("prmt.b32 %0, %1, %1, %2;" : "=r"(d) : "r"(v), "r"(sel));
  return d;
}
__device__ __forceinline__ float own_max(const float (&v)[14], uint32_t f) {
  float m = sel<kInV>(fmaxf(v[0], v[1]), -INFINITY, f), m2 = sel<kInV * 2>(fmaxf(v[2], v[3]), -INFINITY, f);
  max_if<kInV * 4>(m, fmaxf(v[4], v[5]), f);
  max_if<kInV * 8>(m2, fmaxf(v[6], v[7]), f);
  max_if<kInU>(m, fmaxf(fmaxf(v[8], v[10]), v[12]), f);
  max_if<kInU * 2>(m2, fmaxf(fmaxf(v[9], v[11]), v[13]), f);
  return fmaxf(m, m2);
}
__device__ __forceinline__ float quad_max(float m) {
  const float a = __shfl_xor_sync(0xffffffffu, m, 1), b = __shfl_xor_sync(0xffffffffu, m, 2), c = __shfl_xor_sync(0xffffffffu, m, 3);
  return fmaxf(fmaxf(m, a), fmaxf(b, c));
}
__device__ __forceinline__ float row_rcp(const float (&v)[14], uint32_t f) {
  float s = sel<kInV>(v[0] + v[1], 0.f, f), s2 = sel<kInV * 2>(v[2] + v[3], 0.f, f);
  add_if<kInV * 4>(s, v[4] + v[5], f);
  add_if<kInV * 8>(s2, v[6] + v[7], f);
  add_if<kInU>(s, v[8] + v[10] + v[12], f);
  add_if<kInU * 2>(s2, v[9] + v[11] + v[13], f);
  s += s2;
  const float a = __shfl_xor_sync(0xffffffffu, s, 1), b = __shfl_xor_sync(0xffffffffu, s, 2), c = __shfl_xor_sync(0xffffffffu, s, 3);
  return rcp_approx((s + a) + (b + c));
}
__device__ __forceinline__ void route(const float (&v)[14], float s, const uint32_t (&rt)[9], uint32_t (&p)[14]) {
#pragma unroll
  for (int i = 0; i < 7; i++) {
    const uint32_t u = pack_bf16(v[2 * i] * s, v[2 * i + 1] * s);
    if (i < 4) p[i] = u & rt[i];
    if (i < 3) p[i + 4] = u & rt[i + 4];
    if (i >= 4) {
      p[i + 3] = u & rt[7];
      p[i + 6] = u & rt[8];
    }
  }
}

template <int C>
__device__ __forceinline__ void pv_chunk(float (&z)[32], const uint32_t (&pa)[14], const uint32_t (&pb)[14],
                                         const uint32_t (&meta)[4], uint64_t dV) {
#pragma unroll
  for (int t = 0; t < 7; t++) {
    if (t & 1)
      wg_s64t1<0, 32>(z, pa[2 * t], pb[2 * t], pa[2 * t + 1], pb[2 * t + 1], dV + ((2 * C * kChunkBytes + t * 2048) >> 4), 1,
                      meta[t >> 1]);
    else if (t > 0)
      wg_s64t<0, 32>(z, pa[2 * t], pb[2 * t], pa[2 * t + 1], pb[2 * t + 1], dV + ((2 * C * kChunkBytes + t * 2048) >> 4), 1,
                     meta[t >> 1]);
    else
      wg_s64tz<0, 32>(z, pa[0], pb[0], pa[1], pb[1], dV + ((2 * C * kChunkBytes) >> 4), 0, meta[0]);
  }
}
template <int C>
__device__ __forceinline__ void pack_z(const float (&z)[32], uint32_t (&za)[24], uint32_t (&zb)[24]) {
#pragma unroll
  for (int j = 0; j < 8; j++) {
    za[8 * C + j] = pack_bf16(z[4 * j], z[4 * j + 1]);
    zb[8 * C + j] = pack_bf16(z[4 * j + 2], z[4 * j + 3]);
  }
}

template <int H>
__device__ __forceinline__ void pack_out(const float (&ac)[48], uint32_t (&oa)[24], uint32_t (&ob)[24]) {
#pragma unroll
  for (int j = 0; j < 12; j++) {
    oa[12 * H + j] = pack_bf16(ac[4 * j], ac[4 * j + 1]);
    ob[12 * H + j] = pack_bf16(ac[4 * j + 2], ac[4 * j + 3]);
  }
}
struct Maps { CUtensorMap v6, v2, v14, u8, px[8], wv, wo; };
__device__ __forceinline__ void tma_prefetch_5d(const CUtensorMap* map, int c0, int c1, int c2, int c3, int c4) {
  asm volatile("cp.async.bulk.prefetch.tensor.5d.L2.global.tile [%0, {%1, %2, %3, %4, %5}];" ::"l"((uint64_t)map), "r"(c0), "r"(c1),
               "r"(c2), "r"(c3), "r"(c4) : "memory");
}
__device__ __forceinline__ int first_line(const TileCoord tc) { return 3 * (qpix(tc.pr, 8 * tc.I) * kW + qpix(tc.pc, 8 * tc.J)); }
template <int MODE, int UNROLL, int I0 = 0, int I1 = 8>
__device__ __forceinline__ void move_px(const Maps& tm, const TileTable& tt, uint32_t buf, uint32_t bar, int line, int kind) {
#pragma unroll UNROLL
  for (int i = I0; i < I1; i++) {
    const int j = MODE == 2 ? 2 * (i & 3) + (i >> 2) : i;
    if (MODE == 2 || (i & 1) == 0 || kind != 0) {
      const CUtensorMap* map = (const CUtensorMap*)((const char*)(tm.px + (MODE & 2) * 2) + tt.g[kind][j][1]);
      const int ln = line + tt.g[kind][j][0];
      if (MODE == 0) tma_load_5d(buf + i * 3072, map, bar, 0, 0, 0, 0, ln);
      if (MODE == 1) tma_prefetch_5d(map, 0, 0, 0, 0, ln);
      if (MODE == 2)
        asm volatile("cp.async.bulk.tensor.5d.global.shared::cta.tile.bulk_group [%0, {%2, %2, %2, %2, %3}], [%1];" ::"l"((uint64_t)map),
                     "r"(buf + i * 3072), "r"(0), "r"(ln) : "memory");
      if (MODE == 2 && (i & 3) == 3) asm volatile("cp.async.bulk.commit_group;" ::: "memory");
    }
  }
}
__device__ __noinline__ bool refetch(uint32_t base, const uint8_t* src, bool gap) {
  constexpr uint32_t bars = 1024 + kBarOff, cnt = bars + 192;
#pragma unroll 1
  for (uint32_t o = 0; o < kWBytes && !gap; o += 2048) {
    uint32_t mx = 0;
#pragma unroll
    for (int i = 0; i < 4; i++) {
      uint4 v;
      asm volatile("ld.shared.v4.u32 {%0,%1,%2,%3}, [%4];" : "=r"(v.x), "=r"(v.y), "=r"(v.z), "=r"(v.w)
                   : "r"(base + o + i * 512 + (threadIdx.x & 31) * 16));
      mx = __vimax3_u32(__vimax3_u32(mx, v.x, v.y), v.z, v.w);
    }
    gap = __any_sync(0xffffffffu, mx == kEmpty);
  }
  uint32_t n;
  asm volatile("ld.shared.u32 %0, [%1];" : "=r"(n) : "r"(cnt) : "memory");
  if (!gap || __any_sync(0xffffffffu, n > (1u << 12))) return false;
  asm volatile("bar.sync 15, 128;" ::: "memory");
  if (threadIdx.x == 0) {
    asm volatile("st.shared.u32 [%0], %1;" ::"r"(cnt), "r"(n + 1) : "memory");
    mbar_arrive_expect_tx(bar_redo(bars), kWBytes);
    bulk_load(base, src, kWBytes, bar_redo(bars));
  }
  __syncwarp();
  mbar_wait(bar_redo(bars), n & 1);
  return true;
}
template <int H, int S0, int S1>
__device__ __forceinline__ void g2_steps(float (&ac)[48], const uint32_t (&za)[24], const uint32_t (&zb)[24], uint64_t dW2) {
#pragma unroll
  for (int s = S0; s < S1; s++) {
    if (s == 0) wg_d96z<0, 48>(ac, za[0], zb[0], za[1], zb[1], w2desc(dW2, 12 * H), 0);
    else wg_d96<0, 48>(ac, za[2 * s], zb[2 * s], za[2 * s + 1], zb[2 * s + 1], w2desc(dW2, 12 * H + s), 1);
  }
}

__device__ __forceinline__ void consumer(const int wg, __nv_bfloat16* out, const uint8_t* wimg, const uint32_t sbase,
                                         const uint32_t zero, const Maps& tm, const TileTable& tt) {
  const int tid = threadIdx.x & 127;
  const int w = __shfl_sync(0xffffffffu, tid >> 5, 0), lane = tid & 31, g = qrow(w, lane >> 2), qc = qcol(w, lane >> 2);
  const uint64_t dK = make_desc(sbase, 16, 1024);
  const uint64_t dV = make_desc(sbase, kChunkBytes, 512, 2);
  const uint64_t dW1 = make_desc(sbase + kW1Off, 16, 1024), dW2 = make_desc(sbase + kW2Off, 16, 1024);
  const uint32_t bars = sbase + kBarOff;
  int tile0 = blockIdx.x * kTilesPerCta;
  asm volatile("" : "+r"(tile0));
  const int nt = num_tiles();

  uint32_t pix = 0, geo[12] = {};
  const int l = lane & 3;
#pragma unroll 1
  for (int j = 4; j >= 0; j -= 2) {
    const TileCoord tc = decode_tile(tt, tile0 + wg + j);
    const uint32_t pr = qpix(tc.pr, 8 * tc.I + g) * kW;
    if (j == nt - 2) pix = (pr + qpix(tc.pc, 8 * tc.J + qc)) | (pr + qpix(tc.pc, 8 * tc.J + qc + 4)) << 16;
    const int d = 8 * tc.J + 6 * tc.pc - 6 - halo_c0(tc);
    const int ro = woff(tc.pr, tc.I, g), coA = woff(tc.pc, tc.J, qc) + d, coB = woff(tc.pc, tc.J, qc + 4) + d - 3;
#pragma unroll
    for (int i = 11; i >= 4; i--) geo[i] = geo[i - 4];
    const uint32_t lr = 0x1FCu << ro;
    const uint32_t lv = lr >> (2 + (l >> 1)), lu = lr >> (2 * l + 2 * tc.up);
    const uint32_t t = __byte_perm(lv, lu, wg ? 0x4501 : 0x5410);
    geo[0] = ((t & 0x15u) | (lv & 0x40u)) * 0x02082080u;
    geo[1] = ((t >> 8) & 0x15u) * 0x02082080u;
    geo[2] = __byte_perm(t << 7, t << 6, 0x7362);
    const int dr = (ro - 1) & 7;
    const uint32_t hiv = (((1u << ((ro - (l >> 1) + 1) >> 1)) - 1u) ^ (wg ? 7u : 0u)) & 7u, hiu = (t >> 24) & 3u;
    const uint32_t ca = (1u << coA) - 1u;
    geo[3] = hiv * kHiV | hiu * kHiU | ((((1u << coB) - 1u) >> (2 * (l & 1))) & 3u) * kColB |
             (15u & ~((uint32_t)((dr & 1) == (l >> 1)) << (dr >> 1))) * kInV | ((t >> 16 | t >> 24) & 3u) * kInU | ca * kColA |
             (ca >> ((0x49 >> (2 * l)) & 3) & 1u) << 19 | (uint32_t)(l == 3) << 20 | (0x55u & ((1u << (2 * coB)) - 1u)) << 24;
  }
  keep_regs(geo);
  const int so = (lane >> 3) | (lane & 4);
  uint32_t sts = sbase + kOutOff + w * 3072 + so * 128 + (((lane & 3) ^ so) << 4);
  __nv_bfloat16* poA = out + 8 * l + (pix & 0xFFFFu) * kC;
  __nv_bfloat16* poB = out + 8 * l + (pix >> 16) * kC;
  asm volatile("" : "+l"(poA), "+l"(poB), "+r"(sts));
  uint32_t oa[24], ob[24];
#pragma unroll
  for (int j = 0; j < 24; j++) oa[j] = ob[j] = 0u;
  keep_regs(oa);
  keep_regs(ob);
  PROF(wg, 0);
  if (threadIdx.x == 0) GT(1);

  for (int k = wg; k < nt; k += 2) {
    const uint32_t ph = (k >> 1) & 1;
    const int it = k >> 1;
    uint32_t qa[24], qb[24];
    uint32_t fl = geo[3];
    {
      float acc[96];
      const uint64_t dX = make_desc(sbase + (k == 0 ? kW2Off : kXOff), 16, 3072);
      if (k > 0) nb_sync(1 + (1 - wg));
      mbar_wait(bar_x(bars, k > 0), (k + (k > 0)) & 1);
      if (k < 2) PROF(wg, 1);
      PROFS(2, wg, 2 + it * 12);
      if (w == 0 && k < 2) GT(20 + wg);
#pragma unroll
      for (int s = 0; s < 12; s++) {
        if ((s & 3) == 0 && k == 0) {
          mbar_wait(bar_w1c(bars, s >> 2), 0);
          PROFS(17, wg, 50 + (s >> 2));
        }
        if ((s & 3) == 0) wg_fence();
        if (s == 0) wg_m192z<0, 96>(acc, dX, dW1, 0);
        else wg_m192<0, 96>(acc, dX + (((s >> 2) * 1024 + (s & 3) * 32) >> 4), wdesc(dW1, s), 1);
      }
      wg_commit();
      PROFS(13, wg, 13 + it * 12);
      wg_wait<0>();
      if (k > 0) nb_arrive_p(6);
      fence_regs(acc);
      PROFS(3, wg, 3 + it * 12);
#pragma unroll
      for (int j = 0; j < 24; j++) {
        qa[j] = pack_bf16(acc[4 * j], acc[4 * j + 1]);
        qb[j] = pack_bf16(acc[4 * j + 2], acc[4 * j + 3]);
      }
      keep_regs(qa);
      keep_regs(qb);
      sched_fence();
      if (k >= 2) {
        const uint32_t dst = k + 1 < nt ? sts : sts - 2 * kWChunk;
        nb_sync(11);
        stage_out<0, 6>(dst, oa, ob);
        nb_sync(12);
        stage_out<6, 12>(dst, oa, ob);
        fence_proxy_async();
        nb_arrive_p(10);
      }
    }

    float aE[52], aO[24], bO[52], bE[28];
    const uint32_t mq = 0xEEEE4444u | zero;
    PROFS(4, wg, 4 + it * 12);

    mbar_wait(bar_full(bars, wg, 0), ph);
    PROFS(14, wg, 40 + it * 3);
    if (w == 0 && k < 2) GT(22 + wg);
    if (k > 0) nb_sync(3 + (1 - wg));
    wg_fence();
#pragma unroll
    for (int ks = 0; ks < 6; ks++) {
      if (ks == NAT_P1) {
        mbar_wait(bar_full(bars, wg, 1), ph);
        PROFS(14, wg, 41 + it * 3);
        wg_fence();
      }
      if (ks == NAT_P2) {
        mbar_wait(bar_full(bars, wg, 2), ph);
        PROFS(14, wg, 42 + it * 3);
        wg_fence();
      }
      const uint64_t d = dK + ((ks * kChunkBytes) >> 4);
      if (ks == 0) wg_s104z<0, 52>(aE, qa[0], qa[1], qa[2], qa[3], d, 0, mq);
      else wg_s104<0, 52>(aE, qa[4 * ks], qa[4 * ks + 1], qa[4 * ks + 2], qa[4 * ks + 3], d, 1, mq);
    }
    wg_commit();
    wg_s48z<0, 24>(aO, qa[0], qa[1], qa[2], qa[3], dK + ((7 * 1024 + 64) >> 4), 0, mq);
#pragma unroll
    for (int ks = 1; ks < 6; ks++)
      wg_s48<0, 24>(aO, qa[4 * ks], qa[4 * ks + 1], qa[4 * ks + 2], qa[4 * ks + 3], dK + ((ks * kChunkBytes + 7 * 1024 + 64) >> 4), 1, mq);
    wg_commit();
    wg_s56z<0, 28>(bE, qb[0], qb[1], qb[2], qb[3], dK, 0, mq);
#pragma unroll
    for (int ks = 1; ks < 6; ks++) wg_s56<0, 28>(bE, qb[4 * ks], qb[4 * ks + 1], qb[4 * ks + 2], qb[4 * ks + 3], dK + ((ks * kChunkBytes) >> 4), 1, mq);
    wg_commit();
    wg_wait<2>();
    fence_regs(aE);
    PROFS(5, wg, 5 + it * 12);

    uint32_t pa[14], pb[14], meta[4];
    {
      float vA[14], vB[14];
      pick_v(aE, vA, fl);
      pick_u(aE + 28, vA + 8, fl);
      fence_regs(vA);
      if (k == 0) {
        if (__builtin_expect(__any_sync(0xffffffffu, vA[6] != vA[6]), 0)) {
          wg_wait<0>();
          fence_regs(aO);
          fence_regs(bE);
          if (refetch(sbase + kW1Off, wimg, false)) {
#pragma unroll
            for (int j = 0; j < 24; j++) oa[j] = ob[j] = 0u;
            k -= 2;
            continue;
          }
        }
        if (elect_one()) mbar_arrive(bar_xf(bars));
      }
      wg_fence();
      wg_s104z<0, 52>(bO, qb[0], qb[1], qb[2], qb[3], dK + 4, 0, mq);
#pragma unroll
      for (int ks = 1; ks < 6; ks++)
        wg_s104<0, 52>(bO, qb[4 * ks], qb[4 * ks + 1], qb[4 * ks + 2], qb[4 * ks + 3], dK + ((ks * kChunkBytes + 64) >> 4), 1, mq);
      wg_commit();
      if (k + 1 < nt) nb_arrive(1 + wg);
      uint32_t rt[9];
#pragma unroll
      for (int i = 0; i < 7; i++) rt[i] = sign_bytes(geo[i >> 2], 0x8888u + 0x1111u * (i & 3));
      rt[7] = sign_bytes(geo[2], 0x9988u);
      rt[8] = sign_bytes(geo[2], 0xBBAAu);
      keep_regs(rt);
      pa[13] = pb[13] = 0u;
      wg_wait<2>();
      keep_regs(qa);
      fence_regs(aO);
      float oA[6], eB[8];
      pick_u(aO, oA, fl);
      wg_wait<1>();
      fence_regs(bE);
      pick_v(bE, eB, fl);
      vA[8] = sel<kColA>(oA[0], vA[8], fl), vA[9] = sel<kColA>(oA[1], vA[9], fl);
      vA[10] = sel<kColA * 2>(oA[2], vA[10], fl), vA[11] = sel<kColA * 2>(oA[3], vA[11], fl);
      vA[12] = sel<kColA * 4>(oA[4], vA[12], fl), vA[13] = sel<kColA * 4>(oA[5], vA[13], fl);
      {
        const float m1 = __uint_as_float(0x88DD88DDu), m0 = __uint_as_float(0x88DDDD88u);
        meta[0] = 0xDD88DD88u ^ __byte_perm(fl, 0u, 0x3344);
        meta[1] = __float_as_uint(sel<kColA * 16>(sel<kColA>(m1, m0, fl), __uint_as_float(meta[0]), fl));
        meta[2] = __float_as_uint(sel<kColA * 8>(m1, m0, fl));
        meta[3] = __float_as_uint(sel<kColA * 4>(m1, m0, fl));
        keep_regs(meta);
      }
      float mA = own_max(vA, fl);
      fl |= __float_as_uint(eB[7]) & zero;
      fence_regs(eB);
      fence_regs(vA);
      asm volatile("" : "+f"(mA), "+r"(fl));
      sched_fence();
      wg_wait<0>();
      sched_fence();
      keep_regs(qb);
      fence_regs(bO);
      if (NAT_TL == 0 && k == 5) nb_arrive(11);
      PROFS(6, wg, 6 + it * 12);
      if (w == 0) GT(24 + k);
      mA = quad_max(mA);
#pragma unroll
      for (int i = 0; i < 14; i++) vA[i] = ex2(vA[i] - mA);
      pick_v(bO, vB, fl);
      pick_u(bO + 28, vB + 8, fl);
#pragma unroll
      for (int i = 0; i < 8; i += 2) vB[i] = sel<kColB>(vB[i], eB[i], fl), vB[i + 1] = sel<kColB * 2>(vB[i + 1], eB[i + 1], fl);
      float mB = quad_max(own_max(vB, fl));
      if (NAT_SB) {
        fence_regs(vA);
        fence_regs(vB);
        asm volatile("" : "+f"(mB));
        sched_fence();
      }
      if (NAT_TL == 1 && k == 5) nb_arrive(11);
      PROFS(7, wg, 7 + it * 12);
#pragma unroll
      for (int i = 0; i < 14; i++) vB[i] = ex2(vB[i] - mB);
      route(vA, row_rcp(vA, fl), rt, pa);
      route(vB, row_rcp(vB, fl), rt, pb);
    }
    PROFS(8, wg, 8 + it * 12);
    if (k == NAT_PK) PROFS(18, wg, 53);
    sched_fence();

    float ac0[48], ac1[48];
    {
      float z0[32], z1[32], z2[32];
      uint32_t za[24], zb[24];
      wg_fence();
      pv_chunk<0>(z0, pa, pb, meta, dV);
      wg_commit();
      pv_chunk<1>(z1, pa, pb, meta, dV);
      wg_commit();
      if (NAT_WP == 0 && k + 1 < nt) mbar_wait(k == 1 ? bar_wok(bars) : bar_w2(bars), k > 1 ? (k - 1) & 1 : 0);
      wg_wait<1>();
      if (k == NAT_PK) PROFS(18, wg, 54);
      if (k + 1 < nt) nb_arrive_p(7);
      if (NAT_WP == 0) wg_fence();
      pv_chunk<2>(z2, pa, pb, meta, dV);
      wg_commit();
      if (NAT_WP == 1 && k + 1 < nt) mbar_wait(k == 1 ? bar_wok(bars) : bar_w2(bars), k > 1 ? (k - 1) & 1 : 0);
      if (NAT_WP == 0) sched_fence();
      fence_regs(z0);
      pack_z<0>(z0, za, zb);
      sched_fence();
      wg_wait<1>();
      if (k == NAT_PK) PROFS(19, wg, 55);
      if (k + 1 < nt) nb_arrive_p(8);
      wg_fence();
      g2_steps<0, 0, 4>(ac0, za, zb, dW2);
      wg_commit();
      sched_fence();
      fence_regs(z1);
      pack_z<1>(z1, za, zb);
      sched_fence();
      wg_fence();
      g2_steps<1, 0, 4>(ac1, za, zb, dW2);
      wg_commit();
      wg_wait<2>();
      if (k + 1 < nt) nb_arrive_p(9);
      if (k == NAT_PK) PROFS(20, wg, 56);
      keep_regs(pa);
      keep_regs(pb);
      keep_regs(meta);
      sched_fence();
      if (k + 1 < nt) mbar_wait(bar_w2m(bars), k & 1);
      fence_regs(z2);
      pack_z<2>(z2, za, zb);
      keep_regs(za);
      keep_regs(zb);
      sched_fence();
      PROFS(9, wg, 9 + it * 12);
      wg_wait<1>();
      if (k > 0 && k + 1 < nt) nb_arrive(11);
      wg_fence();
      g2_steps<0, 4, 8>(ac0, za, zb, dW2);
      wg_commit();
      g2_steps<0, 8, 12>(ac0, za, zb, dW2);
      wg_commit();
      wg_wait<2>();
      if (k > 0 && k + 1 < nt) nb_arrive(12);
      g2_steps<1, 4, 8>(ac1, za, zb, dW2);
      wg_commit();
      wg_wait<2>();
      if (k + 2 < nt) nb_arrive_p(13);
      g2_steps<1, 8, 12>(ac1, za, zb, dW2);
      wg_commit();
      if (k + 1 < nt) nb_arrive(3 + wg);
      PROFS(10, wg, 10 + it * 12);
      const bool direct = k + 2 >= nt && (wg == 1 || nt < 6);
      wg_wait<2>();
      if (k + 2 < nt && (k > 0 || nt == 6)) nb_arrive_p(5);
      sched_fence();
      fence_regs(ac0);
      pack_out<0>(ac0, oa, ob);
      store_rows<0, 3>(direct, poA, poB, oa, ob);
      sched_fence();
      wg_wait<0>();
      fence_regs(ac1);
      PROFS(11, wg, 11 + it * 12);
      pack_out<1>(ac1, oa, ob);
      store_rows<3, 6>(direct, poA, poB, oa, ob);
      if (k == 0) {
        uint32_t m[2] = {oa[0], oa[1]};
#pragma unroll
        for (int i = 2; i < 24; i++) asm("max.NaN.bf16x2 %0, %0, %1;" : "+r"(m[i & 1]) : "r"(oa[i]));
        asm("max.NaN.bf16x2 %0, %0, %1;" : "+r"(m[0]) : "r"(m[1]));
        uint32_t nan;
        asm volatile("{\n.reg .pred p;\nsetp.ne.u32 p, %1, 0;\nbar.red.or.pred p, 15, 128, p;\nselp.u32 %0, 1, 0, p;\n}\n"
                     : "=r"(nan) : "r"(((m[0] & 0x7FFF7FFFu) + 0x007F007Fu) & 0x80008000u) : "memory");
        if (__builtin_expect(__any_sync(0xffffffffu, nan), 0)) {
          if (nt == 6) mbar_wait(bar_x(bars, 1), 1);
          for (bool first = true; __any_sync(0xffffffffu, refetch(sbase + kW2Off, wimg + w2_offset(), first)); first = false) { }
          wg_fence();
          g2_steps<0, 0, 12>(ac0, za, zb, dW2);
          g2_steps<1, 0, 12>(ac1, za, zb, dW2);
          wg_commit();
          wg_wait<0>();
          fence_regs(ac0);
          fence_regs(ac1);
          pack_out<0>(ac0, oa, ob);
          pack_out<1>(ac1, oa, ob);
          if (nt == 6) {
            asm volatile("bar.sync 15, 128;" ::: "memory");
            if (w == 0 && elect_one()) {
              const TileCoord tc = decode_tile(tt, tile0 + 2);
              mbar_arrive_expect_tx(bar_raw(bars), kWChunk);
              move_px<0, 1>(tm, tt, sbase + kXOff, bar_raw(bars), first_line(tc), tc.kind);
            }
            __syncwarp();
            mbar_wait(bar_raw(bars), 0);
          }
        }
        if (nt < 6) nb_arrive_p(5);
        if (elect_one()) mbar_arrive(bar_wok(bars));
      }
      keep_regs(za);
      keep_regs(zb);
#pragma unroll
      for (int i = 0; i < 8; i++) geo[i] = geo[i + 4];
      keep_regs(oa);
      keep_regs(ob);
      PROFS(12, wg, 12 + it * 12);
      sched_fence();
    }
  }
  if (wg == 0 && nt == 6) {
    if (NAT_TL < 2) nb_sync(11);
    stage_out<0, 12>(sts - kWChunk, oa, ob);
    fence_proxy_async();
    nb_arrive_p(6);
  }
  PROF(wg, 38);
  GT_DUMP();
  PROF_DUMP(wg);
}

struct HaloCols { int vj, vc, uj, uc; };
__device__ __forceinline__ HaloCols halo_cols(const TileCoord& tc) {
  const int c0 = halo_c0(tc);
  return HaloCols{c0 > 98, c0 > 98 ? 98 : c0 + 3, c0 < 0 ? -1 : 0, c0 < 0 ? 4 : c0};
}
__device__ __forceinline__ void load_halo(const Maps& tm, uint32_t sbase, uint32_t bars, const TileCoord tc, int k, int c) {
  const HaloCols hc = halo_cols(tc);
  const int h6 = halo_r0(tc) + (tc.up ? 0 : 8), h2 = halo_r0(tc) + 6, h8 = halo_r0(tc) + (tc.up ? 0 : 6), ch = 24 * tc.pc + 8 * c;
  uint32_t dv = sbase + 2 * c * kChunkBytes, du = dv + 7 * 1024;
  if (((k ^ tc.up) & 1) == 0) dv += 4 * 1024, du += 3 * 1024;
  const uint32_t bar = bar_full(bars, k & 1, c);
  mbar_arrive_expect_tx(bar, 14 * 1024);
  nb_sync_p(7 + c);
#pragma unroll
  for (int h = 0; h < 2; h++) {
    tma_load_5d(dv + h * kChunkBytes, &tm.v6, bar, ch + 4 * h, hc.vj, hc.vc, tc.pr, h6);
    tma_load_5d(du + h * kChunkBytes, &tm.u8, bar, ch + 4 * h, hc.uj, h8, tc.pr, hc.uc);
    tma_load_5d(sbase + (2 * c + h) * kChunkBytes + 3 * 1024, &tm.v2, bar, ch + 4 * h, hc.vj, hc.vc, tc.pr, h2);
  }
  PROFS(15, 2, k * 4 + c);
}
__device__ __forceinline__ void gather_px(const __nv_bfloat16* __restrict__ x, uint32_t buf, uint32_t bar, const TileCoord tc) {
  const int lane = threadIdx.x & 31, g = lane >> 3;
  uint32_t ro[4], co[4];
#pragma unroll
  for (int i = 0; i < 4; i++) {
    ro[i] = qpix(tc.pr, 8 * tc.I + 2 * i + (g & 1)) * (kW * kC * 2) + 16 * (lane & 7);
    co[i] = qpix(tc.pc, 8 * tc.J + 2 * i + (g >> 1)) * (kC * 2);
  }
  uint32_t dst = buf + g * 128 + (((lane & 7) ^ g) << 4);
  keep_regs(ro);
  keep_regs(co);
  sched_fence();
  nb_sync_p(13);
  nb_sync_p(5);
#pragma unroll
  for (int i = 0; i < 16; i++) {
    const char* src = (const char*)x + (ro[i >> 2] + co[i & 3]);
#pragma unroll
    for (int q = 0; q < 3; q++)
      asm volatile("cp.async.cg.shared.global [%0], [%1], 16;" ::"r"((dst ^ ((i & 1) * 576)) + (i >> 1) * 3072 + q * 1024), "l"(src + 128 * q) : "memory");
  }
  asm volatile("cp.async.wait_all;" ::: "memory");
  fence_proxy_async();
  __syncwarp();
  if (elect_one()) mbar_arrive(bar);
  __syncwarp();
}

__global__ void __launch_bounds__(384, 1)
nat_kernel(const __nv_bfloat16* __restrict__ x, __nv_bfloat16* out, const __nv_bfloat16* __restrict__ wqkv,
           const __nv_bfloat16* __restrict__ wo, uint8_t* wimg, const uint32_t zero,
           const __grid_constant__ Maps tm, const __grid_constant__ TileTable tt) {
  extern __shared__ uint8_t smem_raw[];
  constexpr uint32_t sbase = 1024;
  constexpr uint32_t bars = sbase + kBarOff;
  if (smem_u32(smem_raw) != sbase) __trap();
  const int tid = threadIdx.x;
  const uint32_t t_start = now_ns();
  if (tid == 0) GT(0);
  const int wid = __shfl_sync(0xffffffffu, tid >> 5, 0);
  if ((wid == 4 || (wid == 5 && blockIdx.x - 2 < 16)) && blockIdx.x < 128 && wqkv != nullptr) {
    fold_w1(blockIdx.x - 2 < 16 ? 2 * blockIdx.x + wid - 6 : blockIdx.x + (blockIdx.x < 2 ? 0 : 16), wqkv, wimg);
    if (wid == 4) asm volatile("bar.arrive 12, 64;" ::: "memory");
    if (tid == 128) GT(7);
  }
  if (wid == NAT_PW) {
    if (blockIdx.x >= 128) {
      asm volatile("prefetch.tensormap [%0];" ::"l"((uint64_t)&tm.wv) : "memory");
      asm volatile("prefetch.tensormap [%0];" ::"l"((uint64_t)&tm.wo) : "memory");
    }
    asm volatile("prefetch.tensormap [%0];" ::"l"((uint64_t)&tm.v14) : "memory");
    asm volatile("prefetch.tensormap [%0];" ::"l"((uint64_t)&tm.u8) : "memory");
    const CUtensorMap* px = tm.px + (blockIdx.x >= 112 ? 2 : edge_strip());
    asm volatile("prefetch.tensormap [%0];" ::"l"((uint64_t)px) : "memory");
    asm volatile("prefetch.tensormap [%0];" ::"l"((uint64_t)(px + 1)) : "memory");
    asm volatile("prefetch.tensormap [%0];" ::"l"((uint64_t)&tm.v6) : "memory");
    asm volatile("prefetch.tensormap [%0];" ::"l"((uint64_t)&tm.v2) : "memory");
    asm volatile("prefetch.tensormap [%0];" ::"l"((uint64_t)(px + 4)) : "memory");
    asm volatile("prefetch.tensormap [%0];" ::"l"((uint64_t)(px + 5)) : "memory");
  }
  if (wid >= 8) {
    asm volatile("setmaxnreg.dec.sync.aligned.u32 24;");
    const int c = wid & 3, lane = tid & 31;
    const int tile0 = blockIdx.x * kTilesPerCta, nt = num_tiles();
    uint32_t w2o = 0;
    if (c == 3) {
      asm volatile("bar.sync 13, 64;" ::: "memory");
      __nanosleep(NAT_TW2 - 2000);
      w2o = w2_offset();
      if (elect_one()) {
        mbar_arrive_expect_tx(bar_w2(bars), 2 * kWChunk);
        wait_clock(t_start, NAT_TW2);
        mbar_wait(bar_xf(bars), 0);
        bulk_load(sbase + kW2Off, wimg + w2o, kWChunk, bar_w2(bars));
        bulk_load(sbase + kW2Off + 2 * kWChunk, wimg + (w2o + 2 * kWChunk), kWChunk, bar_w2(bars));
      }
      __syncwarp();
      if (nt < 6) {
#pragma unroll 1
        for (int k = 2; k < 4; k++) {
          gather_px(x, sbase + kXOff, bar_x(bars, 1), decode_tile(tt, tile0 + k));
        }
      }
      if (wqkv == nullptr) return;
      mbar_wait(bar_wok(bars), 0);
      if (lane == 0) asm volatile("red.relaxed.gpu.global.add.u32 [%0], 1;" ::"l"(g_flag) : "memory");
      if (blockIdx.x >= 48) return;
      if (lane == 0) {
        uint32_t v, it = 0;
        do {
          __nanosleep(2000);
          asm volatile("ld.relaxed.gpu.global.u32 %0, [%1];" : "=r"(v) : "l"(g_flag) : "memory");
        } while (v < gridDim.x && ++it < (1u << 16));
      }
      __syncwarp();
#pragma unroll
      for (int i = 0; i < 6; i++)
        stg128(wimg + ((i < 3 ? 0u : 3 * kWBytes - w2o) + blockIdx.x * 1536 + (i % 3) * 512 + lane * 16), kEmpty, kEmpty, kEmpty, kEmpty);
      if (lane == 0 && atomicAdd(g_flag + 32, 1u) == 47) {
        g_flag[0] = g_flag[32] = 0;
        g_flag[64] = w2o == kWBytes;
      }
      return;
    }
    if (!elect_one()) return;
    if (c == 0) {
      for (int i = 0; i < kNumBars; i++) mbar_init(bars + i * 8, i == 13 || i == 16 ? 4 : 1);
      asm volatile("st.shared.v2.u32 [%0], {%1,%1};" ::"r"(bars + 192), "r"(0) : "memory");
      asm volatile("fence.mbarrier_init.release.cluster;" ::: "memory");
      if (blockIdx.x - 128 < 3 && wqkv != nullptr) {
        const int q = blockIdx.x & 3;
        mbar_arrive_expect_tx(bar_raw(bars), kWBytes + kWChunk);
#pragma unroll
        for (int j = 0; j < 6; j++)
          asm volatile("cp.async.bulk.tensor.2d.shared::cluster.global.tile.mbarrier::complete_tx::bytes [%0], [%1, {%3, %4}], [%2];" ::"r"(
                           j < 3 ? sbase + j * 8192 : sbase + kW2Off + (j - 3) * kWChunk),
                       "l"((uint64_t)(j < 3 ? &tm.wv : &tm.wo)), "r"(bar_raw(bars)), "r"(j < 3 ? 384 + 64 * j : 64 * (j - 3)), "r"(j < 3 ? 64 * q : 0) : "memory");
        asm volatile("bar.arrive 11, 160;" ::: "memory");
        w2o = w2_offset();
        asm volatile("bar.sync 10, 288;" ::: "memory");
#pragma unroll
        for (int h = 0; h < 2; h++)
          asm volatile("cp.async.bulk.global.shared::cta.bulk_group [%0], [%1], %2;" ::"l"(wimg + (w2o + w2piece(h, q) * (kWChunk / 2))),
                       "r"(sbase + kW1Off + h * (kWChunk / 2)), "r"(kWChunk / 2) : "memory");
        asm volatile("cp.async.bulk.commit_group;" ::: "memory");
        asm volatile("cp.async.bulk.wait_group.read 0;" ::: "memory");
        GT(31);
      }
      asm volatile("bar.arrive 0, 224;" ::: "memory");
      asm volatile("bar.arrive 14, 160;" ::: "memory");
      asm volatile("bar.arrive 13, 64;" ::: "memory");
      const TileCoord tc0 = decode_tile(tt, tile0);
      const HaloCols hc = halo_cols(tc0);
      const int h0 = halo_r0(tc0);
#pragma unroll
      for (int j = 0; j < 3; j++) mbar_arrive_expect_tx(bar_full(bars, 0, j), 2 * kChunkBytes);
      GT(17);
#pragma unroll 1
      for (int i = 0; i < 6; i++) {
        if (i == NAT_H0 || i == NAT_X1P) mbar_arrive(bar_go(bars, i != NAT_H0));
        if (i == NAT_H0) {
          wait_clock(t_start, NAT_HP);
#pragma unroll
          for (int q = 4 * NAT_H0; q < 24; q += 8) {
            tma_prefetch_5d(&tm.v6, 24 * tc0.pc + q, hc.vj, hc.vc, tc0.pr, h0 + (tc0.up ? 0 : 8));
            tma_prefetch_5d(&tm.u8, 24 * tc0.pc + q, hc.uj, h0 + (tc0.up ? 0 : 6), tc0.pr, hc.uc);
            if (blockIdx.x >= 112) tma_prefetch_5d(&tm.v2, 24 * tc0.pc + q, hc.vj, hc.vc, tc0.pr, h0 + 6);
          }
          mbar_wait(bar_w1q(bars), 0);
        }
        const uint32_t dst = sbase + i * kChunkBytes, bar = bar_full(bars, 0, i >> 1);
        const int ch = 24 * tc0.pc + 4 * i;
        tma_load_5d(dst, &tm.v14, bar, ch, hc.vj, hc.vc, tc0.pr, h0);
        tma_load_5d(dst + 7 * 1024, &tm.u8, bar, ch, hc.uj, h0 + (tc0.up ? 0 : -2), tc0.pr, hc.uc);
        tma_load_5d(dst + 10 * 1024, &tm.u8, bar, ch, hc.uj, h0 + (tc0.up ? 8 : 6), tc0.pr, hc.uc);
      }
      w2o = w2_offset();
    } else {
      asm volatile("bar.sync 0, 224;" ::: "memory");
      if (c == 2) {
        if (wqkv != nullptr && nt == 6) asm volatile("bar.sync 12, 64;" ::: "memory");
        const uint32_t c0 = clock();
        while ((uint32_t)clock() - c0 < NAT_TD) { }
        wait_clock(t_start, NAT_T0);
#pragma unroll
        for (int j = 0; j < 3; j++) {
          mbar_arrive_expect_tx(bar_w1c(bars, j), kWChunk);
          bulk_load(sbase + kW1Off + j * kWChunk, wimg + j * kWChunk, kWChunk, bar_w1c(bars, j));
        }
        mbar_arrive(bar_w1q(bars));
        GT(2);
      } else {
#pragma unroll 1
        for (int j = 0; j < 2; j++) {
          const TileCoord tc = decode_tile(tt, tile0 + j);
          const int line = first_line(tc);
          mbar_arrive_expect_tx(bar_x(bars, j), kWChunk);
          if (j == 1 || (tc.kind == 0 && NAT_XF == 0)) mbar_wait(bar_go(bars, j), 0);
          if (j == 0) GT(15);
          move_px<0, 2>(tm, tt, sbase + kW2Off + j * kWChunk, bar_x(bars, j), line, tc.kind);
          if (j == 0) GT(16);
        }
        w2o = w2_offset();
      }
    }
#pragma unroll 1
    for (int k = 1; k < nt; k++) {
      const TileCoord tn = decode_tile(tt, tile0 + k + 1);
      const int line = first_line(tn);
      if (c == 1) {
        nb_sync_p(6);
        bulk_load(sbase + kXOff, wimg + (w2o + kWChunk), kWChunk, bar_w2m(bars));
        mbar_arrive_expect_tx(bar_w2m(bars), kWChunk);
      }
      if (c == 2) {
        if (k == 1) wait_clock(t_start, NAT_TX2);
        else __nanosleep(NAT_PFD);
        if (k < 5 && nt == 6) move_px<1, 1>(tm, tt, 0, 0, line, tn.kind);
      }
      if (c == 2 && (blockIdx.x >= 112 || k == 5)) {
        const TileCoord tc = decode_tile(tt, tile0 + k);
        const HaloCols hc = halo_cols(tc);
        const int h8 = halo_r0(tc) + (tc.up ? 0 : 6);
#pragma unroll 1
        for (int q = 0; q < 24; q += 8) {
          tma_prefetch_5d(&tm.v6, 24 * tc.pc + q, hc.vj, hc.vc, tc.pr, h8);
          tma_prefetch_5d(&tm.v2, 24 * tc.pc + q, hc.vj, hc.vc, tc.pr, h8 + 6);
          tma_prefetch_5d(&tm.u8, 24 * tc.pc + q, hc.uj, h8, tc.pr, hc.uc);
        }
      }
      load_halo(tm, sbase, bars, decode_tile(tt, tile0 + k), k, c);
      if (c == 0 && k < 5 && nt == 6) {
        if (tn.kind == 0) {
#pragma unroll
          for (int j = 0; j < 4; j++) {
            if ((j & 1) == 0) nb_sync_p(j ? 5 : 13);
            tma_load_5d(sbase + kXOff + j * 6144, tm.px, bar_x(bars, 1), 0, 0, 0, 0, line + 6 * j);
          }
        } else {
          nb_sync_p(13);
          move_px<0, 4, 0, 4>(tm, tt, sbase + kXOff, bar_x(bars, 1), line, tn.kind);
          nb_sync_p(5);
          move_px<0, 4, 4, 8>(tm, tt, sbase + kXOff, bar_x(bars, 1), line, tn.kind);
        }
        mbar_arrive_expect_tx(bar_x(bars, 1), kWChunk);
        PROFS(16, 2, k * 4 + 3);
      }
      if (c == 0 && k >= 2) {
        const TileCoord tp = decode_tile(tt, tile0 + k - 2);
        const int lp = first_line(tp);
        nb_sync_p(10);
        if (NAT_XW == 1 && k < 5 && nt == 6) mbar_wait(bar_x(bars, 1), k & 1);
        if (NAT_XW > 1) __nanosleep(NAT_XW);
        if (k == NAT_PK) PROFS(22, 2, 0);
        move_px<2, NAT_SU>(tm, tt, sbase + kOutOff - (k + 1 < nt ? 0 : 2 * kWChunk), 0, lp, tp.kind);
        if (k + 1 == nt) break;
        if (k == NAT_PK) PROFS(22, 2, 1);
        asm volatile("cp.async.bulk.wait_group.read 1;" ::: "memory");
        if (k == NAT_PK) PROFS(22, 2, 2);
        bulk_load(sbase + kOutOff, wimg + w2o, kWChunk / 2, bar_w2(bars));
        asm volatile("cp.async.bulk.wait_group.read 0;" ::: "memory");
        if (k == NAT_PK) PROFS(22, 2, 3);
        bulk_load(sbase + kOutOff + kWChunk / 2, wimg + (w2o + kWChunk / 2), kWChunk / 2, bar_w2(bars));
        mbar_arrive_expect_tx(bar_w2(bars), kWChunk);
      }
    }
    if (c == 1 && nt == 6) {
      const TileCoord tp = decode_tile(tt, tile0 + 4);
      const int lp = first_line(tp);
      nb_sync_p(6);
      move_px<2, 1>(tm, tt, sbase + kOutOff - kWChunk, 0, lp, tp.kind);
    }
    asm volatile("cp.async.bulk.wait_group 0;" ::: "memory");
  } else {
    {
      if (blockIdx.x - 128 < 3 && wqkv != nullptr) {
        if (wid < 4) {
          asm volatile("bar.sync 11, 160;" ::: "memory");
          mbar_wait(bar_raw(bars), 0);
        } else if (wid < 6 && elect_one()) {
          asm volatile("cp.async.bulk.prefetch.L2.global [%0], %1;" ::"l"(wid == 4 ? wo : wqkv + (blockIdx.x & 3) * 64 * 576), "r"(kWBytes) : "memory");
        }
        __syncwarp();
        if (tid == 0) GT(7);
        float acc[96];
        wg_fence();
        wg_m192tz<0, 96>(acc, make_desc(sbase, 16, 1024), make_desc(sbase + kW2Off, kWChunk, 1024), 0);
#pragma unroll
        for (int s = 1; s < 12; s++)
          wg_m192t<0, 96>(acc, make_desc(sbase + (s >> 2) * 8192 + (s & 3) * 32, 16, 1024), make_desc(sbase + kW2Off + s * 2048, kWChunk, 1024), 1);
        wg_commit();
        wg_wait<0>();
        fence_regs(acc);
        if (tid == 0) GT(19);
        const int m = (tid >> 3) & 3;
#pragma unroll
        for (int j = 0; j < 24; j += 2) {
          const int n = g2_inv(8 * (j + (m >> 1)) + (tid & 7));
          asm volatile("stmatrix.sync.aligned.m8n8.x4.trans.shared.b16 [%0], {%1,%2,%3,%4};" ::"r"(
                           sbase + kW1Off + (wid >> 2) * kWChunk + n * 128 + (((2 * (wid & 3) + (m & 1)) ^ (n & 7)) << 4)),
                       "r"(pack_bf16(acc[4 * j], acc[4 * j + 1])), "r"(pack_bf16(acc[4 * j + 2], acc[4 * j + 3])),
                       "r"(pack_bf16(acc[4 * j + 4], acc[4 * j + 5])), "r"(pack_bf16(acc[4 * j + 6], acc[4 * j + 7])) : "memory");
        }
        fence_proxy_async();
        if (tid == 0) GT(18);
        asm volatile("bar.arrive 10, 288;" ::: "memory");
      }
    }
    __syncwarp();
    if (wid < 4) asm volatile("bar.sync 0, 224;" ::: "memory");
    else asm volatile("bar.sync 14, 160;" ::: "memory");
    asm volatile("setmaxnreg.inc.sync.aligned.u32 240;");
    consumer(wid >> 2, out, wimg, sbase, zero, tm, tt);
  }
}

}

typedef CUresult (*PFN_encodeTiled)(CUtensorMap*, CUtensorMapDataType, cuuint32_t, void*, const cuuint64_t*,
                                    const cuuint64_t*, const cuuint32_t*, const cuuint32_t*, CUtensorMapInterleave,
                                    CUtensorMapSwizzle, CUtensorMapL2promotion, CUtensorMapFloatOOBfill);

extern "C" void kernel_launch(void* const* d_in, const int* in_sizes, int n_in, void* d_out, int out_size) {
  const __nv_bfloat16* x = (const __nv_bfloat16*)d_in[0];
  const __nv_bfloat16* wqkv = (const __nv_bfloat16*)d_in[1];
  const __nv_bfloat16* wo = (const __nv_bfloat16*)d_in[2];
  __nv_bfloat16* out = (__nv_bfloat16*)d_out;

  static PFN_encodeTiled encode = nullptr;
  static int num_sms = 0;
  static uint8_t* wimg = nullptr;
  if (!encode) {
    void* fn = nullptr;
    cudaDriverEntryPointQueryResult qres;
    cudaGetDriverEntryPoint("cuTensorMapEncodeTiled", &fn, cudaEnableDefault, &qres);
    encode = (PFN_encodeTiled)fn;
    cudaFuncSetAttribute(nat::nat_kernel, cudaFuncAttributeMaxDynamicSharedMemorySize, nat::kSmemBytes);
    cudaGetSymbolAddress((void**)&wimg, nat::g_wimg32);
    int dev = 0;
    cudaGetDevice(&dev);
    cudaDeviceGetAttribute(&num_sms, cudaDevAttrMultiProcessorCount, dev);
  }
  nat::Maps tm;
  cuuint32_t estr[5] = {1, 1, 1, 1, 1};
  {
    cuuint64_t vdim[5] = {48, 2, 105, 2, 112}, udim[5] = {48, 2, 112, 2, 105};
    cuuint64_t vstr[4] = {7 * 768, 768, 224 * 384, 2 * 224 * 384}, ustr[4] = {7 * 768, 2 * 224 * 384, 224 * 384, 768};
    CUtensorMap* maps[4] = {&tm.v6, &tm.v2, &tm.v14, &tm.u8};
    for (int i = 0; i < 4; i++) {
      cuuint32_t box[5] = {4, 2, i < 3 ? 4u : 8u, 1, i == 0 ? 6u : i == 1 ? 2u : i == 2 ? 14u : 3u};
      encode(maps[i], CU_TENSOR_MAP_DATA_TYPE_UINT32, 5, (void*)x, i < 3 ? vdim : udim, i < 3 ? vstr : ustr, box, estr,
             CU_TENSOR_MAP_INTERLEAVE_16B, CU_TENSOR_MAP_SWIZZLE_128B, CU_TENSOR_MAP_L2_PROMOTION_L2_128B, CU_TENSOR_MAP_FLOAT_OOB_FILL_NONE);
    }
  }
  for (int i = 0; i < 8; i++) {
    const cuuint32_t row = 224 * 384, dr = (1u + (i & 1)) * row;
    const cuuint32_t shape[4][6] = {{8, 3, 2u - i, 2 * row, 128, 4 * 768}, {2, 4, 3, dr, 768, 128}, {4, 2, 3, 4 * row, 2 * row, 128}, {4, 2, 3, 768, dr, 128}};
    const cuuint32_t* sh = shape[i >> 1];
    cuuint64_t dim[5] = {64, sh[0], sh[1], sh[2], 224 * 224 * 3};
    cuuint64_t str[4] = {sh[3], sh[4], sh[5], 128};
    cuuint32_t box[5] = {64, sh[0], sh[1], sh[2], 1};
    encode(tm.px + i, CU_TENSOR_MAP_DATA_TYPE_BFLOAT16, 5, i < 4 ? (void*)x : (void*)out, dim, str, box, estr, CU_TENSOR_MAP_INTERLEAVE_NONE,
           CU_TENSOR_MAP_SWIZZLE_128B, i < 4 ? CU_TENSOR_MAP_L2_PROMOTION_L2_128B : CU_TENSOR_MAP_L2_PROMOTION_NONE,
           CU_TENSOR_MAP_FLOAT_OOB_FILL_NONE);
  }
  for (int i = 0; i < 2; i++) {
    cuuint64_t dim[2] = {i ? 192u : 576u, 192}, str[1] = {i ? 384u : 1152u};
    cuuint32_t box[2] = {64, i ? 192u : 64u};
    encode(i ? &tm.wo : &tm.wv, CU_TENSOR_MAP_DATA_TYPE_BFLOAT16, 2, i ? (void*)wo : (void*)wqkv, dim, str, box, estr,
           CU_TENSOR_MAP_INTERLEAVE_NONE, CU_TENSOR_MAP_SWIZZLE_128B, CU_TENSOR_MAP_L2_PROMOTION_L2_256B, CU_TENSOR_MAP_FLOAT_OOB_FILL_NONE);
  }
  nat::TileTable tt;
  nat::make_tiles(tt);
  const int grid = nat::kCtas;
  if (num_sms >= grid) {
    nat::nat_kernel<<<grid, 384, nat::kSmemBytes>>>(x, out, wqkv, wo, wimg, 0u, tm, tt);
  } else {
    nat::fold_kernel<<<27, 256>>>(wqkv, wo, wimg);
    nat::nat_kernel<<<grid, 384, nat::kSmemBytes>>>(x, out, nullptr, nullptr, wimg, 0u, tm, tt);
  }
}
```

```cpp
#include <cuda_runtime.h>
#include <cuda_bf16.h>
#include <cuda.h>
#include <stdint.h>

#define NAT_P1 2
#define NAT_P2 4
#define NAT_H0 2
#define NAT_T0 2150
#define NAT_TD 1250
#define NAT_TW2 4500
#define NAT_TX2 3600
#define NAT_X1P 4
#define NAT_PK 3
#define NAT_HP 1800
#define NAT_PFD 700
#define NAT_XW 200
#define NAT_SU 8
#define NAT_TL 0
#define NAT_PW 0
#define NAT_XF 1
#define NAT_RD 0
#define NAT_RP 0
#define NAT_SB 0
namespace nat {

constexpr int kW = 224, kC = 192;
constexpr int kCtas = 132;
constexpr int kTilesPerCta = 6;
constexpr float kAlpha = 0.07216878364870322f * 1.4426950408889634f;
constexpr uint32_t kChunkBytes = 13 * 1024;
constexpr uint32_t kWChunk = 192 * 128;
constexpr uint32_t kWBytes = 3 * kWChunk;
constexpr uint32_t kW1Off = 6 * kChunkBytes;
constexpr uint32_t kW2Off = kW1Off + kWBytes;
constexpr uint32_t kXOff = kW2Off + kWChunk;
constexpr uint32_t kBarOff = kW2Off + kWBytes;
constexpr uint32_t kProfOff = kBarOff + 208;
constexpr uint32_t kSmemBytes = kBarOff + 1024;

static_assert(kW1Off % 1024 == 0 && kW2Off % 1024 == 0 && kChunkBytes % 1024 == 0, "swizzle alignment");
static_assert(kSmemBytes <= 232448, "smem");

constexpr uint32_t kEmpty = 0xFFFFFFFFu;
#define NAT_R8(v) v, v, v, v, v, v, v, v
#define NAT_R2K(v) NAT_R8(NAT_R8(NAT_R8(v))), NAT_R8(NAT_R8(NAT_R8(v))), NAT_R8(NAT_R8(NAT_R8(v))), NAT_R8(NAT_R8(NAT_R8(v)))
#define NAT_IMG NAT_R8(NAT_R2K(kEmpty)), NAT_R2K(kEmpty)
__device__ __align__(1024) uint32_t g_wimg32[3 * kWBytes / 4] = {NAT_IMG, NAT_IMG, NAT_IMG};
static_assert(kWBytes / 4 == 9 * 2048, "initialiser");
__device__ __align__(128) uint32_t g_flag[96];
__device__ __forceinline__ uint32_t w2_offset() {
  uint32_t v;
  asm volatile("ld.relaxed.gpu.global.u32 %0, [%1];" : "=r"(v) : "l"(g_flag + 64) : "memory");
  return (1 + v) * kWBytes;
}

#define PROFS(id, wgid, slotid) do { } while (0)
#define PROF(wgid, slotid) do { } while (0)
#define PROF_DUMP(wgid) do { } while (0)

#define GT(slotid) do { } while (0)
#define GT_DUMP() do { } while (0)

__device__ __forceinline__ uint32_t smem_u32(const void* p) { return (uint32_t)__cvta_generic_to_shared(p); }

__device__ __forceinline__ void mbar_init(uint32_t bar, uint32_t count) {
  asm volatile("mbarrier.init.shared::cta.b64 [%0], %1;" ::"r"(bar), "r"(count) : "memory");
}
__device__ __forceinline__ void mbar_arrive(uint32_t bar) {
  asm volatile("mbarrier.arrive.shared::cta.b64 _, [%0];" ::"r"(bar) : "memory");
}
__device__ __forceinline__ void mbar_arrive_expect_tx(uint32_t bar, uint32_t bytes) {
  asm volatile("mbarrier.arrive.expect_tx.shared::cta.b64 _, [%0], %1;" ::"r"(bar), "r"(bytes) : "memory");
}
__device__ __forceinline__ void mbar_wait(uint32_t bar, uint32_t parity) {
  uint32_t ok;
  uint32_t it = 0;
  do {
    asm volatile(
        "{\n.reg .pred p;\n"
        "mbarrier.try_wait.parity.shared::cta.b64 p, [%1], %2;\n"
        "selp.u32 %0, 1, 0, p;\n}\n"
        : "=r"(ok)
        : "r"(bar), "r"(parity)
        : "memory");
    if (++it > (1u << 24)) break;
  } while (!ok);
}
__device__ __forceinline__ bool elect_one() {
  uint32_t r;
  asm volatile("{\n.reg .pred p;\nelect.sync _|p, 0xffffffff;\nselp.u32 %0, 1, 0, p;\n}\n" : "=r"(r));
  return r != 0;
}
__device__ __forceinline__ void nb_arrive(int id) { asm volatile("bar.arrive %0, 256;" ::"r"(id) : "memory"); }
__device__ __forceinline__ void nb_sync(int id) { asm volatile("bar.sync %0, 256;" ::"r"(id) : "memory"); }
__device__ __forceinline__ void nb_arrive_p(int id) { asm volatile("bar.arrive %0, 160;" ::"r"(id) : "memory"); }
__device__ __forceinline__ void nb_sync_p(int id) { asm volatile("bar.sync %0, 160;" ::"r"(id) : "memory"); }
__device__ __forceinline__ void fence_proxy_async() { asm volatile("fence.proxy.async.shared::cta;" ::: "memory"); }

__device__ __forceinline__ void tma_load_5d(uint32_t dst, const CUtensorMap* map, uint32_t bar, int c0, int c1, int c2,
                                            int c3, int c4) {
  asm volatile(
      "cp.async.bulk.tensor.5d.shared::cluster.global.tile.mbarrier::complete_tx::bytes "
      "[%0], [%1, {%3, %4, %5, %6, %7}], [%2];"
      ::"r"(dst), "l"((uint64_t)map), "r"(bar), "r"(c0), "r"(c1), "r"(c2), "r"(c3), "r"(c4)
      : "memory");
}
__device__ __forceinline__ void bulk_load(uint32_t dst, const void* src, uint32_t bytes, uint32_t bar) {
  asm volatile("cp.async.bulk.shared::cluster.global.mbarrier::complete_tx::bytes [%0], [%1], %2, [%3];"
               ::"r"(dst), "l"((uint64_t)src), "r"(bytes), "r"(bar)
               : "memory");
}

__device__ __forceinline__ void wg_fence() { asm volatile("wgmma.fence.sync.aligned;" ::: "memory"); }
__device__ __forceinline__ void wg_commit() { asm volatile("wgmma.commit_group.sync.aligned;" ::: "memory"); }
template <int N>
__device__ __forceinline__ void wg_wait() { asm volatile("wgmma.wait_group.sync.aligned %0;" ::"n"(N) : "memory"); }

template <int N>
__device__ __forceinline__ void fence_regs(float (&d)[N]) {
#pragma unroll
  for (int i = 0; i < N; i++) asm volatile("" : "+f"(d[i])::"memory");
}
template <int N>
__device__ __forceinline__ void keep_regs(uint32_t (&d)[N]) {
#pragma unroll
  for (int i = 0; i < N; i++) asm volatile("" : "+r"(d[i])::"memory");
}

__device__ __forceinline__ uint32_t pack_bf16(float lo, float hi) {
  uint32_t d;
  asm("cvt.rn.bf16x2.f32 %0, %1, %2;" : "=r"(d) : "f"(hi), "f"(lo));
  return d;
}
__device__ __forceinline__ float ex2(float x) {
  float y;
  asm("ex2.approx.ftz.f32 %0, %1;" : "=f"(y) : "f"(x));
  return y;
}
__device__ __forceinline__ float rcp_approx(float x) {
  float y;
  asm("rcp.approx.ftz.f32 %0, %1;" : "=f"(y) : "f"(x));
  return y;
}
__device__ __forceinline__ uint4 ldg128_nc(const void* p) {
  uint4 v;
  asm volatile("ld.global.nc.v4.u32 {%0,%1,%2,%3}, [%4];" : "=r"(v.x), "=r"(v.y), "=r"(v.z), "=r"(v.w) : "l"(p));
  return v;
}
__device__ __forceinline__ void stg128(void* p, uint32_t a, uint32_t b, uint32_t c, uint32_t d) {
  asm volatile("st.global.v4.u32 [%0], {%1,%2,%3,%4};" ::"l"(p), "r"(a), "r"(b), "r"(c), "r"(d) : "memory");
}

__device__ __forceinline__ long long clk64() {
  long long c;
  asm volatile("mov.u64 %0, %clock64;" : "=l"(c)::"memory");
  return c;
}
__device__ __forceinline__ void sched_fence() { while (clk64() < 0) { } }

__device__ __forceinline__ uint64_t make_desc(uint32_t addr, uint32_t lbo, uint32_t sbo, uint32_t mode = 1) {
  return (uint64_t)((addr & 0x3FFFF) >> 4) | ((uint64_t)(lbo >> 4) << 16) | ((uint64_t)(sbo >> 4) << 32) |
         ((uint64_t)mode << 62);
}

template <int OFF, int NN>
__device__ __forceinline__ void wg_m192(float (&d)[NN], uint64_t desc_a, uint64_t desc_b, int scale_d) {
  asm volatile(
      "{\n.reg .pred p;\nsetp.ne.b32 p, %98, 0;\n"
      "wgmma.mma_async.sync.aligned.m64n192k16.f32.bf16.bf16 "
      "{%0,%1,%2,%3,%4,%5,%6,%7,%8,%9,%10,%11,%12,%13,%14,%15,"
      "%16,%17,%18,%19,%20,%21,%22,%23,%24,%25,%26,%27,%28,%29,%30,%31,"
      "%32,%33,%34,%35,%36,%37,%38,%39,%40,%41,%42,%43,%44,%45,%46,%47,"
      "%48,%49,%50,%51,%52,%53,%54,%55,%56,%57,%58,%59,%60,%61,%62,%63,"
      "%64,%65,%66,%67,%68,%69,%70,%71,%72,%73,%74,%75,%76,%77,%78,%79,"
      "%80,%81,%82,%83,%84,%85,%86,%87,%88,%89,%90,%91,%92,%93,%94,%95}, "
      "%96, %97, p, 1, 1, 0, 0;\n}\n"
      : "+f"(d[OFF + 0]), "+f"(d[OFF + 1]), "+f"(d[OFF + 2]), "+f"(d[OFF + 3]), "+f"(d[OFF + 4]), "+f"(d[OFF + 5]),
        "+f"(d[OFF + 6]), "+f"(d[OFF + 7]), "+f"(d[OFF + 8]), "+f"(d[OFF + 9]), "+f"(d[OFF + 10]), "+f"(d[OFF + 11]),
        "+f"(d[OFF + 12]), "+f"(d[OFF + 13]), "+f"(d[OFF + 14]), "+f"(d[OFF + 15]), "+f"(d[OFF + 16]), "+f"(d[OFF + 17]),
        "+f"(d[OFF + 18]), "+f"(d[OFF + 19]), "+f"(d[OFF + 20]), "+f"(d[OFF + 21]), "+f"(d[OFF + 22]), "+f"(d[OFF + 23]),
        "+f"(d[OFF + 24]), "+f"(d[OFF + 25]), "+f"(d[OFF + 26]), "+f"(d[OFF + 27]), "+f"(d[OFF + 28]), "+f"(d[OFF + 29]),
        "+f"(d[OFF + 30]), "+f"(d[OFF + 31]), "+f"(d[OFF + 32]), "+f"(d[OFF + 33]), "+f"(d[OFF + 34]), "+f"(d[OFF + 35]),
        "+f"(d[OFF + 36]), "+f"(d[OFF + 37]), "+f"(d[OFF + 38]), "+f"(d[OFF + 39]), "+f"(d[OFF + 40]), "+f"(d[OFF + 41]),
        "+f"(d[OFF + 42]), "+f"(d[OFF + 43]), "+f"(d[OFF + 44]), "+f"(d[OFF + 45]), "+f"(d[OFF + 46]), "+f"(d[OFF + 47]),
        "+f"(d[OFF + 48]), "+f"(d[OFF + 49]), "+f"(d[OFF + 50]), "+f"(d[OFF + 51]), "+f"(d[OFF + 52]), "+f"(d[OFF + 53]),
        "+f"(d[OFF + 54]), "+f"(d[OFF + 55]), "+f"(d[OFF + 56]), "+f"(d[OFF + 57]), "+f"(d[OFF + 58]), "+f"(d[OFF + 59]),
        "+f"(d[OFF + 60]), "+f"(d[OFF + 61]), "+f"(d[OFF + 62]), "+f"(d[OFF + 63]), "+f"(d[OFF + 64]), "+f"(d[OFF + 65]),
        "+f"(d[OFF + 66]), "+f"(d[OFF + 67]), "+f"(d[OFF + 68]), "+f"(d[OFF + 69]), "+f"(d[OFF + 70]), "+f"(d[OFF + 71]),
        "+f"(d[OFF + 72]), "+f"(d[OFF + 73]), "+f"(d[OFF + 74]), "+f"(d[OFF + 75]), "+f"(d[OFF + 76]), "+f"(d[OFF + 77]),
        "+f"(d[OFF + 78]), "+f"(d[OFF + 79]), "+f"(d[OFF + 80]), "+f"(d[OFF + 81]), "+f"(d[OFF + 82]), "+f"(d[OFF + 83]),
        "+f"(d[OFF + 84]), "+f"(d[OFF + 85]), "+f"(d[OFF + 86]), "+f"(d[OFF + 87]), "+f"(d[OFF + 88]), "+f"(d[OFF + 89]),
        "+f"(d[OFF + 90]), "+f"(d[OFF + 91]), "+f"(d[OFF + 92]), "+f"(d[OFF + 93]), "+f"(d[OFF + 94]), "+f"(d[OFF + 95])
      : "l"(desc_a), "l"(desc_b), "r"(scale_d));
}

template <int OFF, int NN>
__device__ __forceinline__ void wg_m192z(float (&d)[NN], uint64_t desc_a, uint64_t desc_b, int scale_d) {
  asm volatile(
      "{\n.reg .pred p;\nsetp.ne.b32 p, %98, 0;\n"
      "wgmma.mma_async.sync.aligned.m64n192k16.f32.bf16.bf16 "
      "{%0,%1,%2,%3,%4,%5,%6,%7,%8,%9,%10,%11,%12,%13,%14,%15,"
      "%16,%17,%18,%19,%20,%21,%22,%23,%24,%25,%26,%27,%28,%29,%30,%31,"
      "%32,%33,%34,%35,%36,%37,%38,%39,%40,%41,%42,%43,%44,%45,%46,%47,"
      "%48,%49,%50,%51,%52,%53,%54,%55,%56,%57,%58,%59,%60,%61,%62,%63,"
      "%64,%65,%66,%67,%68,%69,%70,%71,%72,%73,%74,%75,%76,%77,%78,%79,"
      "%80,%81,%82,%83,%84,%85,%86,%87,%88,%89,%90,%91,%92,%93,%94,%95}, "
      "%96, %97, p, 1, 1, 0, 0;\n}\n"
      : "=f"(d[OFF + 0]), "=f"(d[OFF + 1]), "=f"(d[OFF + 2]), "=f"(d[OFF + 3]), "=f"(d[OFF + 4]), "=f"(d[OFF + 5]),
        "=f"(d[OFF + 6]), "=f"(d[OFF + 7]), "=f"(d[OFF + 8]), "=f"(d[OFF + 9]), "=f"(d[OFF + 10]), "=f"(d[OFF + 11]),
        "=f"(d[OFF + 12]), "=f"(d[OFF + 13]), "=f"(d[OFF + 14]), "=f"(d[OFF + 15]), "=f"(d[OFF + 16]), "=f"(d[OFF + 17]),
        "=f"(d[OFF + 18]), "=f"(d[OFF + 19]), "=f"(d[OFF + 20]), "=f"(d[OFF + 21]), "=f"(d[OFF + 22]), "=f"(d[OFF + 23]),
        "=f"(d[OFF + 24]), "=f"(d[OFF + 25]), "=f"(d[OFF + 26]), "=f"(d[OFF + 27]), "=f"(d[OFF + 28]), "=f"(d[OFF + 29]),
        "=f"(d[OFF + 30]), "=f"(d[OFF + 31]), "=f"(d[OFF + 32]), "=f"(d[OFF + 33]), "=f"(d[OFF + 34]), "=f"(d[OFF + 35]),
        "=f"(d[OFF + 36]), "=f"(d[OFF + 37]), "=f"(d[OFF + 38]), "=f"(d[OFF + 39]), "=f"(d[OFF + 40]), "=f"(d[OFF + 41]),
        "=f"(d[OFF + 42]), "=f"(d[OFF + 43]), "=f"(d[OFF + 44]), "=f"(d[OFF + 45]), "=f"(d[OFF + 46]), "=f"(d[OFF + 47]),
        "=f"(d[OFF + 48]), "=f"(d[OFF + 49]), "=f"(d[OFF + 50]), "=f"(d[OFF + 51]), "=f"(d[OFF + 52]), "=f"(d[OFF + 53]),
        "=f"(d[OFF + 54]), "=f"(d[OFF + 55]), "=f"(d[OFF + 56]), "=f"(d[OFF + 57]), "=f"(d[OFF + 58]), "=f"(d[OFF + 59]),
        "=f"(d[OFF + 60]), "=f"(d[OFF + 61]), "=f"(d[OFF + 62]), "=f"(d[OFF + 63]), "=f"(d[OFF + 64]), "=f"(d[OFF + 65]),
        "=f"(d[OFF + 66]), "=f"(d[OFF + 67]), "=f"(d[OFF + 68]), "=f"(d[OFF + 69]), "=f"(d[OFF + 70]), "=f"(d[OFF + 71]),
        "=f"(d[OFF + 72]), "=f"(d[OFF + 73]), "=f"(d[OFF + 74]), "=f"(d[OFF + 75]), "=f"(d[OFF + 76]), "=f"(d[OFF + 77]),
        "=f"(d[OFF + 78]), "=f"(d[OFF + 79]), "=f"(d[OFF + 80]), "=f"(d[OFF + 81]), "=f"(d[OFF + 82]), "=f"(d[OFF + 83]),
        "=f"(d[OFF + 84]), "=f"(d[OFF + 85]), "=f"(d[OFF + 86]), "=f"(d[OFF + 87]), "=f"(d[OFF + 88]), "=f"(d[OFF + 89]),
        "=f"(d[OFF + 90]), "=f"(d[OFF + 91]), "=f"(d[OFF + 92]), "=f"(d[OFF + 93]), "=f"(d[OFF + 94]), "=f"(d[OFF + 95])
      : "l"(desc_a), "l"(desc_b), "r"(scale_d));
}

template <int OFF, int NN>
__device__ __forceinline__ void wg_m192t(float (&d)[NN], uint64_t desc_a, uint64_t desc_b, int scale_d) {
  asm volatile(
      "{\n.reg .pred p;\nsetp.ne.b32 p, %98, 0;\n"
      "wgmma.mma_async.sync.aligned.m64n192k16.f32.bf16.bf16 "
      "{%0,%1,%2,%3,%4,%5,%6,%7,%8,%9,%10,%11,%12,%13,%14,%15,"
      "%16,%17,%18,%19,%20,%21,%22,%23,%24,%25,%26,%27,%28,%29,%30,%31,"
      "%32,%33,%34,%35,%36,%37,%38,%39,%40,%41,%42,%43,%44,%45,%46,%47,"
      "%48,%49,%50,%51,%52,%53,%54,%55,%56,%57,%58,%59,%60,%61,%62,%63,"
      "%64,%65,%66,%67,%68,%69,%70,%71,%72,%73,%74,%75,%76,%77,%78,%79,"
      "%80,%81,%82,%83,%84,%85,%86,%87,%88,%89,%90,%91,%92,%93,%94,%95}, "
      "%96, %97, p, 1, 1, 0, 1;\n}\n"
      : "+f"(d[OFF + 0]), "+f"(d[OFF + 1]), "+f"(d[OFF + 2]), "+f"(d[OFF + 3]), "+f"(d[OFF + 4]), "+f"(d[OFF + 5]),
        "+f"(d[OFF + 6]), "+f"(d[OFF + 7]), "+f"(d[OFF + 8]), "+f"(d[OFF + 9]), "+f"(d[OFF + 10]), "+f"(d[OFF + 11]),
        "+f"(d[OFF + 12]), "+f"(d[OFF + 13]), "+f"(d[OFF + 14]), "+f"(d[OFF + 15]), "+f"(d[OFF + 16]), "+f"(d[OFF + 17]),
        "+f"(d[OFF + 18]), "+f"(d[OFF + 19]), "+f"(d[OFF + 20]), "+f"(d[OFF + 21]), "+f"(d[OFF + 22]), "+f"(d[OFF + 23]),
        "+f"(d[OFF + 24]), "+f"(d[OFF + 25]), "+f"(d[OFF + 26]), "+f"(d[OFF + 27]), "+f"(d[OFF + 28]), "+f"(d[OFF + 29]),
        "+f"(d[OFF + 30]), "+f"(d[OFF + 31]), "+f"(d[OFF + 32]), "+f"(d[OFF + 33]), "+f"(d[OFF + 34]), "+f"(d[OFF + 35]),
        "+f"(d[OFF + 36]), "+f"(d[OFF + 37]), "+f"(d[OFF + 38]), "+f"(d[OFF + 39]), "+f"(d[OFF + 40]), "+f"(d[OFF + 41]),
        "+f"(d[OFF + 42]), "+f"(d[OFF + 43]), "+f"(d[OFF + 44]), "+f"(d[OFF + 45]), "+f"(d[OFF + 46]), "+f"(d[OFF + 47]),
        "+f"(d[OFF + 48]), "+f"(d[OFF + 49]), "+f"(d[OFF + 50]), "+f"(d[OFF + 51]), "+f"(d[OFF + 52]), "+f"(d[OFF + 53]),
        "+f"(d[OFF + 54]), "+f"(d[OFF + 55]), "+f"(d[OFF + 56]), "+f"(d[OFF + 57]), "+f"(d[OFF + 58]), "+f"(d[OFF + 59]),
        "+f"(d[OFF + 60]), "+f"(d[OFF + 61]), "+f"(d[OFF + 62]), "+f"(d[OFF + 63]), "+f"(d[OFF + 64]), "+f"(d[OFF + 65]),
        "+f"(d[OFF + 66]), "+f"(d[OFF + 67]), "+f"(d[OFF + 68]), "+f"(d[OFF + 69]), "+f"(d[OFF + 70]), "+f"(d[OFF + 71]),
        "+f"(d[OFF + 72]), "+f"(d[OFF + 73]), "+f"(d[OFF + 74]), "+f"(d[OFF + 75]), "+f"(d[OFF + 76]), "+f"(d[OFF + 77]),
        "+f"(d[OFF + 78]), "+f"(d[OFF + 79]), "+f"(d[OFF + 80]), "+f"(d[OFF + 81]), "+f"(d[OFF + 82]), "+f"(d[OFF + 83]),
        "+f"(d[OFF + 84]), "+f"(d[OFF + 85]), "+f"(d[OFF + 86]), "+f"(d[OFF + 87]), "+f"(d[OFF + 88]), "+f"(d[OFF + 89]),
        "+f"(d[OFF + 90]), "+f"(d[OFF + 91]), "+f"(d[OFF + 92]), "+f"(d[OFF + 93]), "+f"(d[OFF + 94]), "+f"(d[OFF + 95])
      : "l"(desc_a), "l"(desc_b), "r"(scale_d));
}

template <int OFF, int NN>
__device__ __forceinline__ void wg_m192tz(float (&d)[NN], uint64_t desc_a, uint64_t desc_b, int scale_d) {
  asm volatile(
      "{\n.reg .pred p;\nsetp.ne.b32 p, %98, 0;\n"
      "wgmma.mma_async.sync.aligned.m64n192k16.f32.bf16.bf16 "
      "{%0,%1,%2,%3,%4,%5,%6,%7,%8,%9,%10,%11,%12,%13,%14,%15,"
      "%16,%17,%18,%19,%20,%21,%22,%23,%24,%25,%26,%27,%28,%29,%30,%31,"
      "%32,%33,%34,%35,%36,%37,%38,%39,%40,%41,%42,%43,%44,%45,%46,%47,"
      "%48,%49,%50,%51,%52,%53,%54,%55,%56,%57,%58,%59,%60,%61,%62,%63,"
      "%64,%65,%66,%67,%68,%69,%70,%71,%72,%73,%74,%75,%76,%77,%78,%79,"
      "%80,%81,%82,%83,%84,%85,%86,%87,%88,%89,%90,%91,%92,%93,%94,%95}, "
      "%96, %97, p, 1, 1, 0, 1;\n}\n"
      : "=f"(d[OFF + 0]), "=f"(d[OFF + 1]), "=f"(d[OFF + 2]), "=f"(d[OFF + 3]), "=f"(d[OFF + 4]), "=f"(d[OFF + 5]),
        "=f"(d[OFF + 6]), "=f"(d[OFF + 7]), "=f"(d[OFF + 8]), "=f"(d[OFF + 9]), "=f"(d[OFF + 10]), "=f"(d[OFF + 11]),
        "=f"(d[OFF + 12]), "=f"(d[OFF + 13]), "=f"(d[OFF + 14]), "=f"(d[OFF + 15]), "=f"(d[OFF + 16]), "=f"(d[OFF + 17]),
        "=f"(d[OFF + 18]), "=f"(d[OFF + 19]), "=f"(d[OFF + 20]), "=f"(d[OFF + 21]), "=f"(d[OFF + 22]), "=f"(d[OFF + 23]),
        "=f"(d[OFF + 24]), "=f"(d[OFF + 25]), "=f"(d[OFF + 26]), "=f"(d[OFF + 27]), "=f"(d[OFF + 28]), "=f"(d[OFF + 29]),
        "=f"(d[OFF + 30]), "=f"(d[OFF + 31]), "=f"(d[OFF + 32]), "=f"(d[OFF + 33]), "=f"(d[OFF + 34]), "=f"(d[OFF + 35]),
        "=f"(d[OFF + 36]), "=f"(d[OFF + 37]), "=f"(d[OFF + 38]), "=f"(d[OFF + 39]), "=f"(d[OFF + 40]), "=f"(d[OFF + 41]),
        "=f"(d[OFF + 42]), "=f"(d[OFF + 43]), "=f"(d[OFF + 44]), "=f"(d[OFF + 45]), "=f"(d[OFF + 46]), "=f"(d[OFF + 47]),
        "=f"(d[OFF + 48]), "=f"(d[OFF + 49]), "=f"(d[OFF + 50]), "=f"(d[OFF + 51]), "=f"(d[OFF + 52]), "=f"(d[OFF + 53]),
        "=f"(d[OFF + 54]), "=f"(d[OFF + 55]), "=f"(d[OFF + 56]), "=f"(d[OFF + 57]), "=f"(d[OFF + 58]), "=f"(d[OFF + 59]),
        "=f"(d[OFF + 60]), "=f"(d[OFF + 61]), "=f"(d[OFF + 62]), "=f"(d[OFF + 63]), "=f"(d[OFF + 64]), "=f"(d[OFF + 65]),
        "=f"(d[OFF + 66]), "=f"(d[OFF + 67]), "=f"(d[OFF + 68]), "=f"(d[OFF + 69]), "=f"(d[OFF + 70]), "=f"(d[OFF + 71]),
        "=f"(d[OFF + 72]), "=f"(d[OFF + 73]), "=f"(d[OFF + 74]), "=f"(d[OFF + 75]), "=f"(d[OFF + 76]), "=f"(d[OFF + 77]),
        "=f"(d[OFF + 78]), "=f"(d[OFF + 79]), "=f"(d[OFF + 80]), "=f"(d[OFF + 81]), "=f"(d[OFF + 82]), "=f"(d[OFF + 83]),
        "=f"(d[OFF + 84]), "=f"(d[OFF + 85]), "=f"(d[OFF + 86]), "=f"(d[OFF + 87]), "=f"(d[OFF + 88]), "=f"(d[OFF + 89]),
        "=f"(d[OFF + 90]), "=f"(d[OFF + 91]), "=f"(d[OFF + 92]), "=f"(d[OFF + 93]), "=f"(d[OFF + 94]), "=f"(d[OFF + 95])
      : "l"(desc_a), "l"(desc_b), "r"(scale_d));
}

template <int OFF, int NN>
__device__ __forceinline__ void wg_d96(float (&d)[NN], uint32_t a0, uint32_t a1, uint32_t a2, uint32_t a3,
                                       uint64_t desc_b, int scale_d) {
  asm volatile(
      "{\n.reg .pred p;\nsetp.ne.b32 p, %53, 0;\n"
      "wgmma.mma_async.sync.aligned.m64n96k16.f32.bf16.bf16 "
      "{%0,%1,%2,%3,%4,%5,%6,%7,%8,%9,%10,%11,%12,%13,%14,%15,"
      "%16,%17,%18,%19,%20,%21,%22,%23,%24,%25,%26,%27,%28,%29,%30,%31,"
      "%32,%33,%34,%35,%36,%37,%38,%39,%40,%41,%42,%43,%44,%45,%46,%47}, "
      "{%48,%49,%50,%51}, %52, p, 1, 1, 0;\n}\n"
      : "+f"(d[OFF + 0]), "+f"(d[OFF + 1]), "+f"(d[OFF + 2]), "+f"(d[OFF + 3]), "+f"(d[OFF + 4]), "+f"(d[OFF + 5]),
        "+f"(d[OFF + 6]), "+f"(d[OFF + 7]), "+f"(d[OFF + 8]), "+f"(d[OFF + 9]), "+f"(d[OFF + 10]), "+f"(d[OFF + 11]),
        "+f"(d[OFF + 12]), "+f"(d[OFF + 13]), "+f"(d[OFF + 14]), "+f"(d[OFF + 15]), "+f"(d[OFF + 16]), "+f"(d[OFF + 17]),
        "+f"(d[OFF + 18]), "+f"(d[OFF + 19]), "+f"(d[OFF + 20]), "+f"(d[OFF + 21]), "+f"(d[OFF + 22]), "+f"(d[OFF + 23]),
        "+f"(d[OFF + 24]), "+f"(d[OFF + 25]), "+f"(d[OFF + 26]), "+f"(d[OFF + 27]), "+f"(d[OFF + 28]), "+f"(d[OFF + 29]),
        "+f"(d[OFF + 30]), "+f"(d[OFF + 31]), "+f"(d[OFF + 32]), "+f"(d[OFF + 33]), "+f"(d[OFF + 34]), "+f"(d[OFF + 35]),
        "+f"(d[OFF + 36]), "+f"(d[OFF + 37]), "+f"(d[OFF + 38]), "+f"(d[OFF + 39]), "+f"(d[OFF + 40]), "+f"(d[OFF + 41]),
        "+f"(d[OFF + 42]), "+f"(d[OFF + 43]), "+f"(d[OFF + 44]), "+f"(d[OFF + 45]), "+f"(d[OFF + 46]), "+f"(d[OFF + 47])
      : "r"(a0), "r"(a1), "r"(a2), "r"(a3), "l"(desc_b), "r"(scale_d));
}

template <int OFF, int NN>
__device__ __forceinline__ void wg_d96z(float (&d)[NN], uint32_t a0, uint32_t a1, uint32_t a2, uint32_t a3,
                                       uint64_t desc_b, int scale_d) {
  asm volatile(
      "{\n.reg .pred p;\nsetp.ne.b32 p, %53, 0;\n"
      "wgmma.mma_async.sync.aligned.m64n96k16.f32.bf16.bf16 "
      "{%0,%1,%2,%3,%4,%5,%6,%7,%8,%9,%10,%11,%12,%13,%14,%15,"
      "%16,%17,%18,%19,%20,%21,%22,%23,%24,%25,%26,%27,%28,%29,%30,%31,"
      "%32,%33,%34,%35,%36,%37,%38,%39,%40,%41,%42,%43,%44,%45,%46,%47}, "
      "{%48,%49,%50,%51}, %52, p, 1, 1, 0;\n}\n"
      : "=f"(d[OFF + 0]), "=f"(d[OFF + 1]), "=f"(d[OFF + 2]), "=f"(d[OFF + 3]), "=f"(d[OFF + 4]), "=f"(d[OFF + 5]),
        "=f"(d[OFF + 6]), "=f"(d[OFF + 7]), "=f"(d[OFF + 8]), "=f"(d[OFF + 9]), "=f"(d[OFF + 10]), "=f"(d[OFF + 11]),
        "=f"(d[OFF + 12]), "=f"(d[OFF + 13]), "=f"(d[OFF + 14]), "=f"(d[OFF + 15]), "=f"(d[OFF + 16]), "=f"(d[OFF + 17]),
        "=f"(d[OFF + 18]), "=f"(d[OFF + 19]), "=f"(d[OFF + 20]), "=f"(d[OFF + 21]), "=f"(d[OFF + 22]), "=f"(d[OFF + 23]),
        "=f"(d[OFF + 24]), "=f"(d[OFF + 25]), "=f"(d[OFF + 26]), "=f"(d[OFF + 27]), "=f"(d[OFF + 28]), "=f"(d[OFF + 29]),
        "=f"(d[OFF + 30]), "=f"(d[OFF + 31]), "=f"(d[OFF + 32]), "=f"(d[OFF + 33]), "=f"(d[OFF + 34]), "=f"(d[OFF + 35]),
        "=f"(d[OFF + 36]), "=f"(d[OFF + 37]), "=f"(d[OFF + 38]), "=f"(d[OFF + 39]), "=f"(d[OFF + 40]), "=f"(d[OFF + 41]),
        "=f"(d[OFF + 42]), "=f"(d[OFF + 43]), "=f"(d[OFF + 44]), "=f"(d[OFF + 45]), "=f"(d[OFF + 46]), "=f"(d[OFF + 47])
      : "r"(a0), "r"(a1), "r"(a2), "r"(a3), "l"(desc_b), "r"(scale_d));
}

template <int OFF, int NN>
__device__ __forceinline__ void wg_s104(float (&d)[NN], uint32_t a0, uint32_t a1, uint32_t a2, uint32_t a3,
                                       uint64_t desc_b, int scale_d, uint32_t meta) {
  asm volatile(
      "{\n.reg .pred p;\nsetp.ne.b32 p, %57, 0;\n"
      "wgmma.mma_async.sp.sync.aligned.m64n104k32.f32.bf16.bf16 "
      "{%0,%1,%2,%3,%4,%5,%6,%7,%8,%9,%10,%11,%12,%13,%14,%15,"
      "%16,%17,%18,%19,%20,%21,%22,%23,%24,%25,%26,%27,%28,%29,%30,%31,"
      "%32,%33,%34,%35,%36,%37,%38,%39,%40,%41,%42,%43,%44,%45,%46,%47,"
      "%48,%49,%50,%51}, "
      "{%52,%53,%54,%55}, %56, %58, 0, p, 1, 1, 0;\n}\n"
      : "+f"(d[OFF + 0]), "+f"(d[OFF + 1]), "+f"(d[OFF + 2]), "+f"(d[OFF + 3]), "+f"(d[OFF + 4]), "+f"(d[OFF + 5]),
        "+f"(d[OFF + 6]), "+f"(d[OFF + 7]), "+f"(d[OFF + 8]), "+f"(d[OFF + 9]), "+f"(d[OFF + 10]), "+f"(d[OFF + 11]),
        "+f"(d[OFF + 12]), "+f"(d[OFF + 13]), "+f"(d[OFF + 14]), "+f"(d[OFF + 15]), "+f"(d[OFF + 16]), "+f"(d[OFF + 17]),
        "+f"(d[OFF + 18]), "+f"(d[OFF + 19]), "+f"(d[OFF + 20]), "+f"(d[OFF + 21]), "+f"(d[OFF + 22]), "+f"(d[OFF + 23]),
        "+f"(d[OFF + 24]), "+f"(d[OFF + 25]), "+f"(d[OFF + 26]), "+f"(d[OFF + 27]), "+f"(d[OFF + 28]), "+f"(d[OFF + 29]),
        "+f"(d[OFF + 30]), "+f"(d[OFF + 31]), "+f"(d[OFF + 32]), "+f"(d[OFF + 33]), "+f"(d[OFF + 34]), "+f"(d[OFF + 35]),
        "+f"(d[OFF + 36]), "+f"(d[OFF + 37]), "+f"(d[OFF + 38]), "+f"(d[OFF + 39]), "+f"(d[OFF + 40]), "+f"(d[OFF + 41]),
        "+f"(d[OFF + 42]), "+f"(d[OFF + 43]), "+f"(d[OFF + 44]), "+f"(d[OFF + 45]), "+f"(d[OFF + 46]), "+f"(d[OFF + 47]),
        "+f"(d[OFF + 48]), "+f"(d[OFF + 49]), "+f"(d[OFF + 50]), "+f"(d[OFF + 51])
      : "r"(a0), "r"(a1), "r"(a2), "r"(a3), "l"(desc_b), "r"(scale_d), "r"(meta));
}

template <int OFF, int NN>
__device__ __forceinline__ void wg_s104z(float (&d)[NN], uint32_t a0, uint32_t a1, uint32_t a2, uint32_t a3,
                                       uint64_t desc_b, int scale_d, uint32_t meta) {
  asm volatile(
      "{\n.reg .pred p;\nsetp.ne.b32 p, %57, 0;\n"
      "wgmma.mma_async.sp.sync.aligned.m64n104k32.f32.bf16.bf16 "
      "{%0,%1,%2,%3,%4,%5,%6,%7,%8,%9,%10,%11,%12,%13,%14,%15,"
      "%16,%17,%18,%19,%20,%21,%22,%23,%24,%25,%26,%27,%28,%29,%30,%31,"
      "%32,%33,%34,%35,%36,%37,%38,%39,%40,%41,%42,%43,%44,%45,%46,%47,"
      "%48,%49,%50,%51}, "
      "{%52,%53,%54,%55}, %56, %58, 0, p, 1, 1, 0;\n}\n"
      : "=f"(d[OFF + 0]), "=f"(d[OFF + 1]), "=f"(d[OFF + 2]), "=f"(d[OFF + 3]), "=f"(d[OFF + 4]), "=f"(d[OFF + 5]),
        "=f"(d[OFF + 6]), "=f"(d[OFF + 7]), "=f"(d[OFF + 8]), "=f"(d[OFF + 9]), "=f"(d[OFF + 10]), "=f"(d[OFF + 11]),
        "=f"(d[OFF + 12]), "=f"(d[OFF + 13]), "=f"(d[OFF + 14]), "=f"(d[OFF + 15]), "=f"(d[OFF + 16]), "=f"(d[OFF + 17]),
        "=f"(d[OFF + 18]), "=f"(d[OFF + 19]), "=f"(d[OFF + 20]), "=f"(d[OFF + 21]), "=f"(d[OFF + 22]), "=f"(d[OFF + 23]),
        "=f"(d[OFF + 24]), "=f"(d[OFF + 25]), "=f"(d[OFF + 26]), "=f"(d[OFF + 27]), "=f"(d[OFF + 28]), "=f"(d[OFF + 29]),
        "=f"(d[OFF + 30]), "=f"(d[OFF + 31]), "=f"(d[OFF + 32]), "=f"(d[OFF + 33]), "=f"(d[OFF + 34]), "=f"(d[OFF + 35]),
        "=f"(d[OFF + 36]), "=f"(d[OFF + 37]), "=f"(d[OFF + 38]), "=f"(d[OFF + 39]), "=f"(d[OFF + 40]), "=f"(d[OFF + 41]),
        "=f"(d[OFF + 42]), "=f"(d[OFF + 43]), "=f"(d[OFF + 44]), "=f"(d[OFF + 45]), "=f"(d[OFF + 46]), "=f"(d[OFF + 47]),
        "=f"(d[OFF + 48]), "=f"(d[OFF + 49]), "=f"(d[OFF + 50]), "=f"(d[OFF + 51])
      : "r"(a0), "r"(a1), "r"(a2), "r"(a3), "l"(desc_b), "r"(scale_d), "r"(meta));
}

template <int OFF, int NN>
__device__ __forceinline__ void wg_s48(float (&d)[NN], uint32_t a0, uint32_t a1, uint32_t a2, uint32_t a3,
                                       uint64_t desc_b, int scale_d, uint32_t meta) {
  asm volatile(
      "{\n.reg .pred p;\nsetp.ne.b32 p, %29, 0;\n"
      "wgmma.mma_async.sp.sync.aligned.m64n48k32.f32.bf16.bf16 "
      "{%0,%1,%2,%3,%4,%5,%6,%7,%8,%9,%10,%11,%12,%13,%14,%15,"
      "%16,%17,%18,%19,%20,%21,%22,%23}, "
      "{%24,%25,%26,%27}, %28, %30, 0, p, 1, 1, 0;\n}\n"
      : "+f"(d[OFF + 0]), "+f"(d[OFF + 1]), "+f"(d[OFF + 2]), "+f"(d[OFF + 3]), "+f"(d[OFF + 4]), "+f"(d[OFF + 5]),
        "+f"(d[OFF + 6]), "+f"(d[OFF + 7]), "+f"(d[OFF + 8]), "+f"(d[OFF + 9]), "+f"(d[OFF + 10]), "+f"(d[OFF + 11]),
        "+f"(d[OFF + 12]), "+f"(d[OFF + 13]), "+f"(d[OFF + 14]), "+f"(d[OFF + 15]), "+f"(d[OFF + 16]), "+f"(d[OFF + 17]),
        "+f"(d[OFF + 18]), "+f"(d[OFF + 19]), "+f"(d[OFF + 20]), "+f"(d[OFF + 21]), "+f"(d[OFF + 22]), "+f"(d[OFF + 23])
      : "r"(a0), "r"(a1), "r"(a2), "r"(a3), "l"(desc_b), "r"(scale_d), "r"(meta));
}

template <int OFF, int NN>
__device__ __forceinline__ void wg_s48z(float (&d)[NN], uint32_t a0, uint32_t a1, uint32_t a2, uint32_t a3,
                                       uint64_t desc_b, int scale_d, uint32_t meta) {
  asm volatile(
      "{\n.reg .pred p;\nsetp.ne.b32 p, %29, 0;\n"
      "wgmma.mma_async.sp.sync.aligned.m64n48k32.f32.bf16.bf16 "
      "{%0,%1,%2,%3,%4,%5,%6,%7,%8,%9,%10,%11,%12,%13,%14,%15,"
      "%16,%17,%18,%19,%20,%21,%22,%23}, "
      "{%24,%25,%26,%27}, %28, %30, 0, p, 1, 1, 0;\n}\n"
      : "=f"(d[OFF + 0]), "=f"(d[OFF + 1]), "=f"(d[OFF + 2]), "=f"(d[OFF + 3]), "=f"(d[OFF + 4]), "=f"(d[OFF + 5]),
        "=f"(d[OFF + 6]), "=f"(d[OFF + 7]), "=f"(d[OFF + 8]), "=f"(d[OFF + 9]), "=f"(d[OFF + 10]), "=f"(d[OFF + 11]),
        "=f"(d[OFF + 12]), "=f"(d[OFF + 13]), "=f"(d[OFF + 14]), "=f"(d[OFF + 15]), "=f"(d[OFF + 16]), "=f"(d[OFF + 17]),
        "=f"(d[OFF + 18]), "=f"(d[OFF + 19]), "=f"(d[OFF + 20]), "=f"(d[OFF + 21]), "=f"(d[OFF + 22]), "=f"(d[OFF + 23])
      : "r"(a0), "r"(a1), "r"(a2), "r"(a3), "l"(desc_b), "r"(scale_d), "r"(meta));
}

template <int OFF, int NN>
__device__ __forceinline__ void wg_s56(float (&d)[NN], uint32_t a0, uint32_t a1, uint32_t a2, uint32_t a3,
                                       uint64_t desc_b, int scale_d, uint32_t meta) {
  asm volatile(
      "{\n.reg .pred p;\nsetp.ne.b32 p, %33, 0;\n"
      "wgmma.mma_async.sp.sync.aligned.m64n56k32.f32.bf16.bf16 "
      "{%0,%1,%2,%3,%4,%5,%6,%7,%8,%9,%10,%11,%12,%13,%14,%15,"
      "%16,%17,%18,%19,%20,%21,%22,%23,%24,%25,%26,%27}, "
      "{%28,%29,%30,%31}, %32, %34, 0, p, 1, 1, 0;\n}\n"
      : "+f"(d[OFF + 0]), "+f"(d[OFF + 1]), "+f"(d[OFF + 2]), "+f"(d[OFF + 3]), "+f"(d[OFF + 4]), "+f"(d[OFF + 5]),
        "+f"(d[OFF + 6]), "+f"(d[OFF + 7]), "+f"(d[OFF + 8]), "+f"(d[OFF + 9]), "+f"(d[OFF + 10]), "+f"(d[OFF + 11]),
        "+f"(d[OFF + 12]), "+f"(d[OFF + 13]), "+f"(d[OFF + 14]), "+f"(d[OFF + 15]), "+f"(d[OFF + 16]), "+f"(d[OFF + 17]),
        "+f"(d[OFF + 18]), "+f"(d[OFF + 19]), "+f"(d[OFF + 20]), "+f"(d[OFF + 21]), "+f"(d[OFF + 22]), "+f"(d[OFF + 23]),
        "+f"(d[OFF + 24]), "+f"(d[OFF + 25]), "+f"(d[OFF + 26]), "+f"(d[OFF + 27])
      : "r"(a0), "r"(a1), "r"(a2), "r"(a3), "l"(desc_b), "r"(scale_d), "r"(meta));
}

template <int OFF, int NN>
__device__ __forceinline__ void wg_s56z(float (&d)[NN], uint32_t a0, uint32_t a1, uint32_t a2, uint32_t a3,
                                       uint64_t desc_b, int scale_d, uint32_t meta) {
  asm volatile(
      "{\n.reg .pred p;\nsetp.ne.b32 p, %33, 0;\n"
      "wgmma.mma_async.sp.sync.aligned.m64n56k32.f32.bf16.bf16 "
      "{%0,%1,%2,%3,%4,%5,%6,%7,%8,%9,%10,%11,%12,%13,%14,%15,"
      "%16,%17,%18,%19,%20,%21,%22,%23,%24,%25,%26,%27}, "
      "{%28,%29,%30,%31}, %32, %34, 0, p, 1, 1, 0;\n}\n"
      : "=f"(d[OFF + 0]), "=f"(d[OFF + 1]), "=f"(d[OFF + 2]), "=f"(d[OFF + 3]), "=f"(d[OFF + 4]), "=f"(d[OFF + 5]),
        "=f"(d[OFF + 6]), "=f"(d[OFF + 7]), "=f"(d[OFF + 8]), "=f"(d[OFF + 9]), "=f"(d[OFF + 10]), "=f"(d[OFF + 11]),
        "=f"(d[OFF + 12]), "=f"(d[OFF + 13]), "=f"(d[OFF + 14]), "=f"(d[OFF + 15]), "=f"(d[OFF + 16]), "=f"(d[OFF + 17]),
        "=f"(d[OFF + 18]), "=f"(d[OFF + 19]), "=f"(d[OFF + 20]), "=f"(d[OFF + 21]), "=f"(d[OFF + 22]), "=f"(d[OFF + 23]),
        "=f"(d[OFF + 24]), "=f"(d[OFF + 25]), "=f"(d[OFF + 26]), "=f"(d[OFF + 27])
      : "r"(a0), "r"(a1), "r"(a2), "r"(a3), "l"(desc_b), "r"(scale_d), "r"(meta));
}

template <int OFF, int NN>
__device__ __forceinline__ void wg_s64t(float (&d)[NN], uint32_t a0, uint32_t a1, uint32_t a2, uint32_t a3,
                                       uint64_t desc_b, int scale_d, uint32_t meta) {
  asm volatile(
      "{\n.reg .pred p;\nsetp.ne.b32 p, %37, 0;\n"
      "wgmma.mma_async.sp.sync.aligned.m64n64k32.f32.bf16.bf16 "
      "{%0,%1,%2,%3,%4,%5,%6,%7,%8,%9,%10,%11,%12,%13,%14,%15,"
      "%16,%17,%18,%19,%20,%21,%22,%23,%24,%25,%26,%27,%28,%29,%30,%31}, "
      "{%32,%33,%34,%35}, %36, %38, 0, p, 1, 1, 1;\n}\n"
      : "+f"(d[OFF + 0]), "+f"(d[OFF + 1]), "+f"(d[OFF + 2]), "+f"(d[OFF + 3]), "+f"(d[OFF + 4]), "+f"(d[OFF + 5]),
        "+f"(d[OFF + 6]), "+f"(d[OFF + 7]), "+f"(d[OFF + 8]), "+f"(d[OFF + 9]), "+f"(d[OFF + 10]), "+f"(d[OFF + 11]),
        "+f"(d[OFF + 12]), "+f"(d[OFF + 13]), "+f"(d[OFF + 14]), "+f"(d[OFF + 15]), "+f"(d[OFF + 16]), "+f"(d[OFF + 17]),
        "+f"(d[OFF + 18]), "+f"(d[OFF + 19]), "+f"(d[OFF + 20]), "+f"(d[OFF + 21]), "+f"(d[OFF + 22]), "+f"(d[OFF + 23]),
        "+f"(d[OFF + 24]), "+f"(d[OFF + 25]), "+f"(d[OFF + 26]), "+f"(d[OFF + 27]), "+f"(d[OFF + 28]), "+f"(d[OFF + 29]),
        "+f"(d[OFF + 30]), "+f"(d[OFF + 31])
      : "r"(a0), "r"(a1), "r"(a2), "r"(a3), "l"(desc_b), "r"(scale_d), "r"(meta));
}

template <int OFF, int NN>
__device__ __forceinline__ void wg_s64t1(float (&d)[NN], uint32_t a0, uint32_t a1, uint32_t a2, uint32_t a3,
                                       uint64_t desc_b, int scale_d, uint32_t meta) {
  asm volatile(
      "{\n.reg .pred p;\nsetp.ne.b32 p, %37, 0;\n"
      "wgmma.mma_async.sp.sync.aligned.m64n64k32.f32.bf16.bf16 "
      "{%0,%1,%2,%3,%4,%5,%6,%7,%8,%9,%10,%11,%12,%13,%14,%15,"
      "%16,%17,%18,%19,%20,%21,%22,%23,%24,%25,%26,%27,%28,%29,%30,%31}, "
      "{%32,%33,%34,%35}, %36, %38, 1, p, 1, 1, 1;\n}\n"
      : "+f"(d[OFF + 0]), "+f"(d[OFF + 1]), "+f"(d[OFF + 2]), "+f"(d[OFF + 3]), "+f"(d[OFF + 4]), "+f"(d[OFF + 5]),
        "+f"(d[OFF + 6]), "+f"(d[OFF + 7]), "+f"(d[OFF + 8]), "+f"(d[OFF + 9]), "+f"(d[OFF + 10]), "+f"(d[OFF + 11]),
        "+f"(d[OFF + 12]), "+f"(d[OFF + 13]), "+f"(d[OFF + 14]), "+f"(d[OFF + 15]), "+f"(d[OFF + 16]), "+f"(d[OFF + 17]),
        "+f"(d[OFF + 18]), "+f"(d[OFF + 19]), "+f"(d[OFF + 20]), "+f"(d[OFF + 21]), "+f"(d[OFF + 22]), "+f"(d[OFF + 23]),
        "+f"(d[OFF + 24]), "+f"(d[OFF + 25]), "+f"(d[OFF + 26]), "+f"(d[OFF + 27]), "+f"(d[OFF + 28]), "+f"(d[OFF + 29]),
        "+f"(d[OFF + 30]), "+f"(d[OFF + 31])
      : "r"(a0), "r"(a1), "r"(a2), "r"(a3), "l"(desc_b), "r"(scale_d), "r"(meta));
}

template <int OFF, int NN>
__device__ __forceinline__ void wg_s64tz(float (&d)[NN], uint32_t a0, uint32_t a1, uint32_t a2, uint32_t a3,
                                       uint64_t desc_b, int scale_d, uint32_t meta) {
  asm volatile(
      "{\n.reg .pred p;\nsetp.ne.b32 p, %37, 0;\n"
      "wgmma.mma_async.sp.sync.aligned.m64n64k32.f32.bf16.bf16 "
      "{%0,%1,%2,%3,%4,%5,%6,%7,%8,%9,%10,%11,%12,%13,%14,%15,"
      "%16,%17,%18,%19,%20,%21,%22,%23,%24,%25,%26,%27,%28,%29,%30,%31}, "
      "{%32,%33,%34,%35}, %36, %38, 0, p, 1, 1, 1;\n}\n"
      : "=f"(d[OFF + 0]), "=f"(d[OFF + 1]), "=f"(d[OFF + 2]), "=f"(d[OFF + 3]), "=f"(d[OFF + 4]), "=f"(d[OFF + 5]),
        "=f"(d[OFF + 6]), "=f"(d[OFF + 7]), "=f"(d[OFF + 8]), "=f"(d[OFF + 9]), "=f"(d[OFF + 10]), "=f"(d[OFF + 11]),
        "=f"(d[OFF + 12]), "=f"(d[OFF + 13]), "=f"(d[OFF + 14]), "=f"(d[OFF + 15]), "=f"(d[OFF + 16]), "=f"(d[OFF + 17]),
        "=f"(d[OFF + 18]), "=f"(d[OFF + 19]), "=f"(d[OFF + 20]), "=f"(d[OFF + 21]), "=f"(d[OFF + 22]), "=f"(d[OFF + 23]),
        "=f"(d[OFF + 24]), "=f"(d[OFF + 25]), "=f"(d[OFF + 26]), "=f"(d[OFF + 27]), "=f"(d[OFF + 28]), "=f"(d[OFF + 29]),
        "=f"(d[OFF + 30]), "=f"(d[OFF + 31])
      : "r"(a0), "r"(a1), "r"(a2), "r"(a3), "l"(desc_b), "r"(scale_d), "r"(meta));
}

__device__ __forceinline__ int g2_inv(int ch) { return 32 * (ch >> 5) + 8 * ((ch >> 1) & 3) + 2 * ((ch >> 3) & 3) + (ch & 1); }
__host__ __device__ __forceinline__ uint32_t wimg_off(int n, int k) {
  return (uint32_t)(k >> 6) * kWChunk + (uint32_t)n * 128 + (uint32_t)((((k & 63) >> 3) ^ (n & 7)) << 4) + (k & 7) * 2;
}
__host__ __device__ constexpr int w2piece(int h, int c) { return c == 2 ? 2 + h : 4 * h + c; }
__device__ __forceinline__ uint32_t w2img_off(int n, int k) { return wimg_off(n % 96, k & 63) + w2piece(n >= 96, k >> 6) * (kWChunk / 2); }
__device__ __forceinline__ int qpix(int par, int t) {
  const int a = 2 * t + 13 * par - 6, b = t + 112 * par;
  return par ? min(a, b) : max(a, b);
}
__device__ __forceinline__ int woff(int par, int i, int r) {
  const int a = 99 * par + 6 - 8 * i;
  return par ? min(r, a) : max(r, a);
}

__device__ __forceinline__ void mma16816(float (&c)[4], uint32_t a0, uint32_t a1, uint32_t a2, uint32_t a3, uint32_t b0,
                                         uint32_t b1) {
  asm volatile(
      "mma.sync.aligned.m16n8k16.row.col.f32.bf16.bf16.f32 {%0,%1,%2,%3}, {%4,%5,%6,%7}, {%8,%9}, {%0,%1,%2,%3};"
      : "+f"(c[0]), "+f"(c[1]), "+f"(c[2]), "+f"(c[3])
      : "r"(a0), "r"(a1), "r"(a2), "r"(a3), "r"(b0), "r"(b1));
}

__device__ __forceinline__ void fold_w1(const int u, const __nv_bfloat16* __restrict__ wqkv, uint8_t* wimg) {
  const int g = (threadIdx.x >> 2) & 7, l = threadIdx.x & 3;
  const int m0 = (u / 12) * 16, s = u % 12;
  uint4 A[12], B[12];
  const __nv_bfloat16* arow = wqkv + (m0 + 4 * (g >> 1) + (g & 1)) * 576 + 192 + 8 * l;
  const __nv_bfloat16* brow = wqkv + (16 * s + 4 * (g >> 1) + (g & 1)) * 576 + 8 * l;
#pragma unroll
  for (int i = 0; i < 12; i++) {
    A[i] = ldg128_nc(arow + (i & 1) * 2 * 576 + 32 * (i >> 1));
    B[i] = ldg128_nc(brow + (i & 1) * 2 * 576 + 32 * (i >> 1));
  }
  sched_fence();
  uint8_t* dst = wimg + wimg_off(m0 + g, 16 * s + 4 * l);
  float acc[4][4];
#pragma unroll
  for (int j = 0; j < 16; j++) acc[j >> 2][j & 3] = 0.f;
#pragma unroll
  for (int i = 0; i < 6; i++) {
    const uint4 &a0 = A[2 * i], &a1 = A[2 * i + 1];
#pragma unroll
    for (int nb = 0; nb < 2; nb++) {
      mma16816(acc[2 * nb], a0.x, a1.x, a0.y, a1.y, B[2 * i + nb].x, B[2 * i + nb].y);
      mma16816(acc[2 * nb + 1], a0.z, a1.z, a0.w, a1.w, B[2 * i + nb].z, B[2 * i + nb].w);
    }
  }
#pragma unroll
  for (int j = 0; j < 2; j++) {
    const uint2 v = make_uint2(pack_bf16((acc[0][2 * j] + acc[1][2 * j]) * kAlpha, (acc[0][2 * j + 1] + acc[1][2 * j + 1]) * kAlpha),
                               pack_bf16((acc[2][2 * j] + acc[3][2 * j]) * kAlpha, (acc[2][2 * j + 1] + acc[3][2 * j + 1]) * kAlpha));
    asm volatile("st.relaxed.gpu.global.v2.u32 [%0], {%1,%2};" ::"l"(dst + j * 1024), "r"(v.x), "r"(v.y) : "memory");
  }
}
__device__ __forceinline__ void fold_w2(const int u, const __nv_bfloat16* __restrict__ wqkv, const __nv_bfloat16* __restrict__ wo,
                                        uint8_t* wimg) {
  const int g = (threadIdx.x >> 2) & 7, l = threadIdx.x & 3;
  const int m0 = (u / 12) * 32, n0 = (u % 12) * 16;
  uint4 S[12];
  uint32_t L[96];
  const __nv_bfloat16* brow = wqkv + (n0 + 4 * (g >> 1) + (g & 1)) * 576 + 384 + 8 * l;
#pragma unroll
  for (int i = 0; i < 12; i++) S[i] = ldg128_nc(brow + (i & 1) * 2 * 576 + 32 * (i >> 1));
  const __nv_bfloat16* acol = wo + (8 * l) * 192 + m0 + 4 * g;
#pragma unroll
  for (int c = 0; c < 48; c++)
    asm volatile("ld.global.nc.v2.u32 {%0,%1}, [%2];" : "=r"(L[2 * c]), "=r"(L[2 * c + 1]) : "l"(acol + (32 * (c >> 3) + (c & 7)) * 192));
  const uint32_t off = w2_offset();
  sched_fence();
  uint8_t* img = wimg + off;
  float acc[4][4];
#pragma unroll
  for (int j = 0; j < 16; j++) acc[j >> 2][j & 3] = 0.f;
#pragma unroll
  for (int i = 0; i < 6; i++) {
#pragma unroll
    for (int h = 0; h < 2; h++) {
      const uint4 &s0 = S[2 * i], &s1 = S[2 * i + 1];
#pragma unroll
      for (int mt = 0; mt < 2; mt++) {
        const uint32_t* a = L + 16 * i + 8 * h + mt;
        const uint32_t a0 = __byte_perm(a[0], a[2], 0x5410), a1 = __byte_perm(a[0], a[2], 0x7632);
        const uint32_t a2 = __byte_perm(a[4], a[6], 0x5410), a3 = __byte_perm(a[4], a[6], 0x7632);
        mma16816(acc[2 * mt], a0, a1, a2, a3, h ? s0.z : s0.x, h ? s0.w : s0.y);
        mma16816(acc[2 * mt + 1], a0, a1, a2, a3, h ? s1.z : s1.x, h ? s1.w : s1.y);
      }
    }
  }
#pragma unroll
  for (int j = 0; j < 4; j++) {
    const float(&c0)[4] = acc[j & 2];
    const float(&c1)[4] = acc[(j & 2) + 1];
    asm volatile("st.relaxed.gpu.global.v2.u32 [%0], {%1,%2};" ::"l"(img + w2img_off(g2_inv(m0 + 4 * g + j), n0 + 4 * l)),
                 "r"(pack_bf16(c0[2 * (j & 1)], c0[2 * (j & 1) + 1])), "r"(pack_bf16(c1[2 * (j & 1)], c1[2 * (j & 1) + 1])) : "memory");
  }
}

__global__ void __launch_bounds__(256) fold_kernel(const __nv_bfloat16* __restrict__ wqkv,
                                                   const __nv_bfloat16* __restrict__ wo, uint8_t* wimg) {
  const int u = blockIdx.x * 8 + (threadIdx.x >> 5);
  if (u < 144) fold_w1(u, wqkv, wimg);
  else fold_w2(u - 144, wqkv, wo, wimg);
}

struct TileCoord { int pr, pc, I, J, up, kind; };
struct TileTable { uint16_t e[kCtas * 6], g[6][8][2]; };
inline void make_tiles(TileTable& tt) {
  for (int tile = 0; tile < kCtas * 6; tile++) {
    const int b = tile / 6, k = tile - 6 * b;
    const int p = b < 128 ? (tile - 672) >> 1 : b - 80;
    const int strip = b < 112 ? b >> 1 : b >= 128 && k >= 2 ? (b & 1) * 27 + (b & 2) * 14 : p + (p < 26 ? 1 : 3);
    const int pr = strip >= 28, J = (strip - pr * 28) >> 1, pc = strip & 1, up = b < 112 ? b & 1 : pr;
    const int first = b < 112 ? 8 - 2 * pr - up : 13 * pr, step = b < 112 ? k : k & 1;
    const int I = up ? first - step : first + step;
    const int kind = b < 112 ? (J == 13 * pc ? 1 + pc : 0) : I == 13 * pr ? 4 + pr : 3;
    tt.e[tile] = (uint16_t)(I | J << 4 | pr << 8 | pc << 9 | up << 10 | kind << 11);
  }
  for (int kind = 0; kind < 6; kind++)
    for (int j = 0; j < 8; j++) {
      const int w = j >> 1, h = j & 1, e = kind % 3;
      auto off = [e](int t) { return e == 0 ? 2 * t : e == 1 ? t + (t == 7) : t + (t > 0); };
      tt.g[kind][j][0] = (uint16_t)(kind < 3 ? 3 * off(w + 4 * h) : 3 * (kW * off(2 * w) + 8 * h));
      tt.g[kind][j][1] = (uint16_t)(128 * (kind < 3 ? kind > 0 : 1 + off(2 * w + 1) - off(2 * w)));
    }
}
__device__ __forceinline__ int num_tiles() { return blockIdx.x < 128 ? 6 : 4; }
__device__ __forceinline__ TileCoord decode_tile(const TileTable& tt, int tile) {
  const uint32_t e = tt.e[tile];
  return TileCoord{(int)(e >> 8) & 1, (int)(e >> 9) & 1, (int)e & 15, (int)(e >> 4) & 15, (int)(e >> 10) & 1, (int)(e >> 11)};
}
__device__ __forceinline__ int halo_r0(const TileCoord& t) { return 8 * t.I + 6 * t.pr - 6; }
__device__ __forceinline__ int halo_c0(const TileCoord& t) { return min(max(8 * t.J + 6 * t.pc - 6, -3), 102); }

__device__ __forceinline__ uint32_t bar_full(uint32_t bars, int wg, int c) { return bars + (wg * 3 + c) * 8; }
__device__ __forceinline__ uint32_t bar_w1c(uint32_t bars, int c) { return bars + (6 + c) * 8; }
__device__ __forceinline__ uint32_t bar_w2(uint32_t bars) { return bars + 9 * 8; }
__device__ __forceinline__ uint32_t bar_x(uint32_t bars, int j) { return bars + (10 + j) * 8; }
__device__ __forceinline__ uint32_t bar_w1q(uint32_t bars) { return bars + 12 * 8; }
__device__ __forceinline__ uint32_t bar_xf(uint32_t bars) { return bars + 13 * 8; }
__device__ __forceinline__ uint32_t bar_w2m(uint32_t bars) { return bars + 14 * 8; }
__device__ __forceinline__ uint32_t bar_redo(uint32_t bars) { return bars + 15 * 8; }
__device__ __forceinline__ uint32_t bar_wok(uint32_t bars) { return bars + 16 * 8; }
__device__ __forceinline__ uint32_t bar_go(uint32_t bars, int j) { return bars + (17 + j) * 8; }
__device__ __forceinline__ uint32_t bar_raw(uint32_t bars) { return bars + 19 * 8; }
__device__ __forceinline__ uint32_t bar_w2a(uint32_t bars) { return bars + 20 * 8; }
constexpr int kNumBars = 21;

__device__ __forceinline__ uint64_t wdesc(uint64_t d0, int s) { return d0 + (((s >> 2) * kWChunk + (s & 3) * 32) >> 4); }

__device__ __forceinline__ int qrow(int w, int g) { return blockIdx.x < 112 ? g : 2 * w + (g & 1); }
__device__ __forceinline__ int qcol(int w, int g) { return blockIdx.x < 112 ? w : g >> 1; }
__device__ __forceinline__ uint32_t out_slot(int k, int nt) { return k + 1 < nt ? kW2Off + (~k & 1) * 2 * kWChunk : kW1Off + kWChunk; }
__device__ __forceinline__ bool edge_strip() {
  const int s = blockIdx.x >> 1;
  return s == 0 || s == 27 || s == 28 || s == 55;
}
template <int I0, int I1>
__device__ __forceinline__ void store_rows(bool on, __nv_bfloat16* pA, __nv_bfloat16* pB, const uint32_t (&a)[24], const uint32_t (&b)[24]) {
#pragma unroll
  for (int i = 2 * I0; i < 2 * I1; i++) {
    const uint32_t* v = (i & 1 ? b : a) + 4 * (i >> 1);
    asm volatile("{\n.reg .pred p;\nsetp.ne.u32 p, %5, 0;\n@p st.global.v4.u32 [%0], {%1,%2,%3,%4};\n}\n" ::"l"((i & 1 ? pB : pA) + 32 * (i >> 1)),
                 "r"(v[0]), "r"(v[1]), "r"(v[2]), "r"(v[3]), "r"((uint32_t)on) : "memory");
  }
}
template <int I0, int I1>
__device__ __forceinline__ void stage_out(uint32_t sts, int wg, const uint32_t (&a)[24], const uint32_t (&b)[24]) {
  const uint32_t e = sts, o = sts ^ 64;
  const uint32_t ad[4] = {wg ? o + 1024 : e, wg ? e + 2048 : o, wg ? e : o + 1024, wg ? o : e + 2048};
#pragma unroll
  for (int i = I0; i < I1; i++) {
    const uint32_t* v = (i < 6 ? a : b) + 4 * (i % 6);
    asm volatile("st.shared.v4.u32 [%0], {%1,%2,%3,%4};" ::"r"(ad[i % 6 / 3 * 2 + (i % 3 == 1)] + (i % 3 == 2) * 1024 + (i / 6) * 12288),
                 "r"(v[0]), "r"(v[1]), "r"(v[2]), "r"(v[3]) : "memory");
  }
}
__device__ __forceinline__ uint32_t now_ns() {
  uint32_t t;
  asm volatile("mov.u32 %0, %globaltimer_lo;" : "=r"(t)::"memory");
  return t;
}
__device__ __forceinline__ void wait_clock(uint32_t t_start, uint32_t t) {
  while (now_ns() - t_start < t) { }
}
#define NAT_PRED(f, m) ".reg .pred p;\n.reg .b32 t;\nand.b32 t, " f ", " m ";\nsetp.ne.u32 p, t, 0;\n"
constexpr uint32_t kHiV = 1, kHiU = 8, kColB = 0x20, kInV = 0x100, kInU = 0x1000, kColA = 0x10000;
template <uint32_t M>
__device__ __forceinline__ float pick(const float* a, const float* b, uint32_t f) {
  float d;
  asm("{\n" NAT_PRED("%5", "%6") "add.f32 %0, %1, %2;\n@p add.f32 %0, %3, %4;\n}\n"
      : "=&f"(d) : "f"(a[0]), "f"(a[2]), "f"(b[0]), "f"(b[2]), "r"(f), "n"(M));
  return d;
}
template <uint32_t M>
__device__ __forceinline__ float sel(float a, float b, uint32_t f) {
  float d;
  asm("{\n" NAT_PRED("%3", "%4") "selp.f32 %0, %1, %2, p;\n}\n" : "=f"(d) : "f"(a), "f"(b), "r"(f), "n"(M));
  return d;
}
template <uint32_t M>
__device__ __forceinline__ void max_if(float& m, float v, uint32_t f) {
  asm("{\n" NAT_PRED("%2", "%3") "@p max.f32 %0, %0, %1;\n}\n" : "+f"(m) : "f"(v), "r"(f), "n"(M));
}
template <uint32_t M>
__device__ __forceinline__ void add_if(float& m, float v, uint32_t f) {
  asm("{\n" NAT_PRED("%2", "%3") "@p add.f32 %0, %0, %1;\n}\n" : "+f"(m) : "f"(v), "r"(f), "n"(M));
}
__device__ __forceinline__ void pick_v(const float* a, float* v, uint32_t f) {
  v[0] = pick<kHiV>(a, a + 16, f), v[1] = pick<kHiV>(a + 1, a + 17, f);
  v[2] = pick<kHiV * 2>(a + 4, a + 20, f), v[3] = pick<kHiV * 2>(a + 5, a + 21, f);
  v[4] = pick<kHiV * 4>(a + 8, a + 24, f), v[5] = pick<kHiV * 4>(a + 9, a + 25, f);
  v[6] = a[12] + a[14], v[7] = a[13] + a[15];
}
__device__ __forceinline__ void pick_u(const float* a, float* v, uint32_t f) {
#pragma unroll
  for (int c = 0; c < 3; c++) v[2 * c] = pick<kHiU>(a + 4 * c, a + 4 * c + 12, f), v[2 * c + 1] = pick<kHiU * 2>(a + 4 * c + 1, a + 4 * c + 13, f);
}
__device__ __forceinline__ uint32_t sign_bytes(uint32_t v, uint32_t sel) {
  uint32_t d;
  asm("prmt.b32 %0, %1, %1, %2;" : "=r"(d) : "r"(v), "r"(sel));
  return d;
}
__device__ __forceinline__ float own_max(const float (&v)[14], uint32_t f) {
  float m = sel<kInV>(fmaxf(v[0], v[1]), -INFINITY, f), m2 = sel<kInV * 2>(fmaxf(v[2], v[3]), -INFINITY, f);
  max_if<kInV * 4>(m, fmaxf(v[4], v[5]), f);
  max_if<kInV * 8>(m2, fmaxf(v[6], v[7]), f);
  max_if<kInU>(m, fmaxf(fmaxf(v[8], v[10]), v[12]), f);
  max_if<kInU * 2>(m2, fmaxf(fmaxf(v[9], v[11]), v[13]), f);
  return fmaxf(m, m2);
}
__device__ __forceinline__ float quad_max(float m) {
  const float a = __shfl_xor_sync(0xffffffffu, m, 1), b = __shfl_xor_sync(0xffffffffu, m, 2), c = __shfl_xor_sync(0xffffffffu, m, 3);
  return fmaxf(fmaxf(m, a), fmaxf(b, c));
}
__device__ __forceinline__ float row_rcp(const float (&v)[14], uint32_t f) {
  float s = sel<kInV>(v[0] + v[1], 0.f, f), s2 = sel<kInV * 2>(v[2] + v[3], 0.f, f);
  add_if<kInV * 4>(s, v[4] + v[5], f);
  add_if<kInV * 8>(s2, v[6] + v[7], f);
  add_if<kInU>(s, v[8] + v[10] + v[12], f);
  add_if<kInU * 2>(s2, v[9] + v[11] + v[13], f);
  s += s2;
  const float a = __shfl_xor_sync(0xffffffffu, s, 1), b = __shfl_xor_sync(0xffffffffu, s, 2), c = __shfl_xor_sync(0xffffffffu, s, 3);
  return rcp_approx((s + a) + (b + c));
}
__device__ __forceinline__ void route(const float (&v)[14], float s, const uint32_t (&rt)[9], uint32_t (&p)[14]) {
#pragma unroll
  for (int i = 0; i < 7; i++) {
    const uint32_t u = pack_bf16(v[2 * i] * s, v[2 * i + 1] * s);
    if (i < 4) p[i] = u & rt[i];
    if (i < 3) p[i + 4] = u & rt[i + 4];
    if (i >= 4) {
      p[i + 3] = u & rt[7];
      p[i + 6] = u & rt[8];
    }
  }
}

template <int C, int T0 = 0, int T1 = 7>
__device__ __forceinline__ void pv_chunk(float (&z)[32], const uint32_t (&pa)[14], const uint32_t (&pb)[14],
                                         const uint32_t (&meta)[4], uint64_t dV) {
#pragma unroll
  for (int t = T0; t < T1; t++) {
    if (t & 1)
      wg_s64t1<0, 32>(z, pa[2 * t], pb[2 * t], pa[2 * t + 1], pb[2 * t + 1], dV + ((2 * C * kChunkBytes + t * 2048) >> 4), 1,
                      meta[t >> 1]);
    else if (t > 0)
      wg_s64t<0, 32>(z, pa[2 * t], pb[2 * t], pa[2 * t + 1], pb[2 * t + 1], dV + ((2 * C * kChunkBytes + t * 2048) >> 4), 1,
                     meta[t >> 1]);
    else
      wg_s64tz<0, 32>(z, pa[0], pb[0], pa[1], pb[1], dV + ((2 * C * kChunkBytes) >> 4), 0, meta[0]);
  }
}
template <int C>
__device__ __forceinline__ void pack_z(const float (&z)[32], uint32_t (&za)[24], uint32_t (&zb)[24]) {
#pragma unroll
  for (int j = 0; j < 8; j++) {
    za[8 * C + j] = pack_bf16(z[4 * j], z[4 * j + 1]);
    zb[8 * C + j] = pack_bf16(z[4 * j + 2], z[4 * j + 3]);
  }
}

template <int H>
__device__ __forceinline__ void pack_out(const float (&ac)[48], uint32_t (&oa)[24], uint32_t (&ob)[24]) {
#pragma unroll
  for (int j = 0; j < 12; j++) {
    oa[12 * H + j] = pack_bf16(ac[4 * j], ac[4 * j + 1]);
    ob[12 * H + j] = pack_bf16(ac[4 * j + 2], ac[4 * j + 3]);
  }
}
struct Maps { CUtensorMap v6, v2, v14, u8, px[8], wv, wo; };
__device__ __forceinline__ void tma_prefetch_5d(const CUtensorMap* map, int c0, int c1, int c2, int c3, int c4) {
  asm volatile("cp.async.bulk.prefetch.tensor.5d.L2.global.tile [%0, {%1, %2, %3, %4, %5}];" ::"l"((uint64_t)map), "r"(c0), "r"(c1),
               "r"(c2), "r"(c3), "r"(c4) : "memory");
}
__device__ __forceinline__ int first_line(const TileCoord tc) { return 3 * (qpix(tc.pr, 8 * tc.I) * kW + qpix(tc.pc, 8 * tc.J)); }
template <int MODE, int UNROLL, int N = 8>
__device__ __forceinline__ void move_px(const Maps& tm, const TileTable& tt, uint32_t buf, uint32_t bar, int line, int kind, int i0 = 0) {
#pragma unroll UNROLL
  for (int n = 0; n < N; n++) {
    const int i = i0 + n;
    const int j = MODE == 2 ? 2 * (i & 3) + (i >> 2) : i;
    if (MODE == 2 || (n & 1) == 0 || kind != 0) {
      const CUtensorMap* map = (const CUtensorMap*)((const char*)(tm.px + (MODE & 2) * 2) + tt.g[kind][j][1]);
      const int ln = line + tt.g[kind][j][0];
      if (MODE == 0) tma_load_5d(buf + i * 3072, map, bar, 0, 0, 0, 0, ln);
      if (MODE == 1) tma_prefetch_5d(map, 0, 0, 0, 0, ln);
      if (MODE == 2)
        asm volatile("cp.async.bulk.tensor.5d.global.shared::cta.tile.bulk_group [%0, {%2, %2, %2, %2, %3}], [%1];" ::"l"((uint64_t)map),
                     "r"(buf + i * 3072), "r"(0), "r"(ln) : "memory");
    }
  }
  if (MODE == 2) asm volatile("cp.async.bulk.commit_group;" ::: "memory");
}
__device__ __noinline__ bool refetch(uint32_t base, const uint8_t* src, bool gap) {
  constexpr uint32_t bars = 1024 + kBarOff, cnt = bars + 192;
#pragma unroll 1
  for (uint32_t o = 0; o < kWBytes && !gap; o += 2048) {
    uint32_t mx = 0;
#pragma unroll
    for (int i = 0; i < 4; i++) {
      uint4 v;
      asm volatile("ld.shared.v4.u32 {%0,%1,%2,%3}, [%4];" : "=r"(v.x), "=r"(v.y), "=r"(v.z), "=r"(v.w)
                   : "r"(base + o + i * 512 + (threadIdx.x & 31) * 16));
      mx = __vimax3_u32(__vimax3_u32(mx, v.x, v.y), v.z, v.w);
    }
    gap = __any_sync(0xffffffffu, mx == kEmpty);
  }
  uint32_t n;
  asm volatile("ld.shared.u32 %0, [%1];" : "=r"(n) : "r"(cnt) : "memory");
  if (!gap || __any_sync(0xffffffffu, n > (1u << 12))) return false;
  asm volatile("bar.sync 15, 128;" ::: "memory");
  if (threadIdx.x == 0) {
    asm volatile("st.shared.u32 [%0], %1;" ::"r"(cnt), "r"(n + 1) : "memory");
    mbar_arrive_expect_tx(bar_redo(bars), kWBytes);
    bulk_load(base, src, kWBytes, bar_redo(bars));
  }
  __syncwarp();
  mbar_wait(bar_redo(bars), n & 1);
  return true;
}
template <int S0, int S1, int Z>
__device__ __forceinline__ void g2_steps(float (&ac)[48], const uint32_t (&za)[24], const uint32_t (&zb)[24], uint64_t d) {
#pragma unroll
  for (int s = S0; s < S1; s++) {
    const uint64_t ds = d + (((s >> 2 & 1) * (kWChunk / 2) + (s & 3) * 32) >> 4);
    if (s == Z) wg_d96z<0, 48>(ac, za[2 * s], zb[2 * s], za[2 * s + 1], zb[2 * s + 1], ds, 0);
    else wg_d96<0, 48>(ac, za[2 * s], zb[2 * s], za[2 * s + 1], zb[2 * s + 1], ds, 1);
  }
}

__device__ __forceinline__ void consumer(const int wg, __nv_bfloat16* out, const uint8_t* wimg, const uint32_t sbase,
                                         const uint32_t zero, const Maps& tm, const TileTable& tt) {
  const int tid = threadIdx.x & 127;
  const int w = __shfl_sync(0xffffffffu, tid >> 5, 0), lane = tid & 31, g = qrow(w, lane >> 2), qc = qcol(w, lane >> 2);
  const uint64_t dK = make_desc(sbase, 16, 1024);
  const uint64_t dV = make_desc(sbase, kChunkBytes, 512, 2);
  const uint64_t dW1 = make_desc(sbase + kW1Off, 16, 1024);
  const uint64_t dX0 = make_desc(sbase + kW2Off + wg * 2 * kWChunk, 16, 1024), dY0 = make_desc(sbase + kW2Off + (1 - wg) * 2 * kWChunk, 16, 1024);
  const uint64_t dX2 = make_desc(sbase + kXOff + wg * (kWChunk / 2), 16, 1024), dY2 = make_desc(sbase + kXOff + (1 - wg) * (kWChunk / 2), 16, 1024);
  const uint32_t bars = sbase + kBarOff;
  int tile0 = blockIdx.x * kTilesPerCta;
  asm volatile("" : "+r"(tile0));
  const int nt = num_tiles();

  uint32_t pix = 0, geo[12] = {};
  const int l = lane & 3;
#pragma unroll 1
  for (int j = 4; j >= 0; j -= 2) {
    const TileCoord tc = decode_tile(tt, tile0 + wg + j);
    const uint32_t pr = qpix(tc.pr, 8 * tc.I + g) * kW;
    if (j == nt - 2) pix = (pr + qpix(tc.pc, 8 * tc.J + qc)) | (pr + qpix(tc.pc, 8 * tc.J + qc + 4)) << 16;
    const int d = 8 * tc.J + 6 * tc.pc - 6 - halo_c0(tc);
    const int ro = woff(tc.pr, tc.I, g), coA = woff(tc.pc, tc.J, qc) + d, coB = woff(tc.pc, tc.J, qc + 4) + d - 3;
#pragma unroll
    for (int i = 11; i >= 4; i--) geo[i] = geo[i - 4];
    const uint32_t lr = 0x1FCu << ro;
    const uint32_t lv = lr >> (2 + (l >> 1)), lu = lr >> (2 * l + 2 * tc.up);
    const uint32_t t = __byte_perm(lv, lu, wg ? 0x4501 : 0x5410);
    geo[0] = ((t & 0x15u) | (lv & 0x40u)) * 0x02082080u;
    geo[1] = ((t >> 8) & 0x15u) * 0x02082080u;
    geo[2] = __byte_perm(t << 7, t << 6, 0x7362);
    const int dr = (ro - 1) & 7;
    const uint32_t hiv = (((1u << ((ro - (l >> 1) + 1) >> 1)) - 1u) ^ (wg ? 7u : 0u)) & 7u, hiu = (t >> 24) & 3u;
    const uint32_t ca = (1u << coA) - 1u;
    geo[3] = hiv * kHiV | hiu * kHiU | ((((1u << coB) - 1u) >> (2 * (l & 1))) & 3u) * kColB |
             (15u & ~((uint32_t)((dr & 1) == (l >> 1)) << (dr >> 1))) * kInV | ((t >> 16 | t >> 24) & 3u) * kInU | ca * kColA |
             (ca >> ((0x49 >> (2 * l)) & 3) & 1u) << 19 | (uint32_t)(l == 3) << 20 | (0x55u & ((1u << (2 * coB)) - 1u)) << 24;
  }
  keep_regs(geo);
  const int so = (lane >> 3) | (lane & 4);
  uint32_t sts = sbase + w * 3072 + so * 128 + (((lane & 3) ^ so) << 4);
  __nv_bfloat16* poA = out + 8 * l + (pix & 0xFFFFu) * kC + 96 * wg;
  __nv_bfloat16* poB = out + 8 * l + (pix >> 16) * kC + 96 * wg;
  asm volatile("" : "+l"(poA), "+l"(poB), "+r"(sts));
  uint32_t oa[24], ob[24];
#pragma unroll
  for (int j = 0; j < 24; j++) oa[j] = ob[j] = 0u;
  keep_regs(oa);
  keep_regs(ob);
  PROF(wg, 0);
  if (threadIdx.x == 0) GT(1);

  for (int k = wg; k < nt; k += 2) {
    const uint32_t ph = (k >> 1) & 1;
    const int it = k >> 1;
    uint32_t qa[24], qb[24];
    uint32_t fl = geo[3];
    {
      float acc[96];
      const uint64_t dX = make_desc(sbase + kXOff + (k == 0 ? kWChunk : 0), 16, 3072);
      if (k > 0) nb_sync(1 + (1 - wg));
      mbar_wait(bar_x(bars, k > 0), (k + (k > 0)) & 1);
      if (k < 2) PROF(wg, 1);
      PROFS(2, wg, 2 + it * 12);
      if (w == 0 && k < 2) GT(20 + wg);
#pragma unroll
      for (int s = 0; s < 12; s++) {
        if ((s & 3) == 0 && k == 0) {
          mbar_wait(bar_w1c(bars, s >> 2), 0);
          PROFS(17, wg, 50 + (s >> 2));
        }
        if ((s & 3) == 0) wg_fence();
        if (s == 0) wg_m192z<0, 96>(acc, dX, dW1, 0);
        else wg_m192<0, 96>(acc, dX + (((s >> 2) * 1024 + (s & 3) * 32) >> 4), wdesc(dW1, s), 1);
      }
      wg_commit();
      PROFS(13, wg, 13 + it * 12);
      wg_wait<0>();
      if (k > 0) nb_arrive_p(6);
      fence_regs(acc);
      PROFS(3, wg, 3 + it * 12);
#pragma unroll
      for (int j = 0; j < 24; j++) {
        qa[j] = pack_bf16(acc[4 * j], acc[4 * j + 1]);
        qb[j] = pack_bf16(acc[4 * j + 2], acc[4 * j + 3]);
      }
      keep_regs(qa);
      keep_regs(qb);
      sched_fence();
      if (k >= 2) {
        const uint32_t dst = sts + out_slot(k, nt);
        nb_sync(11);
        stage_out<0, 6>(dst, wg, oa, ob);
        nb_sync(12);
        stage_out<6, 12>(dst, wg, oa, ob);
        fence_proxy_async();
        nb_arrive_p(10);
      }
    }

    float aE[52], aO[24], bO[52], bE[28];
    const uint32_t mq = 0xEEEE4444u | zero;
    PROFS(4, wg, 4 + it * 12);

    mbar_wait(bar_full(bars, wg, 0), ph);
    PROFS(14, wg, 40 + it * 3);
    if (w == 0 && k < 2) GT(22 + wg);
    if (k > 0) nb_sync(3 + (1 - wg));
    wg_fence();
#pragma unroll
    for (int ks = 0; ks < 6; ks++) {
      if (ks == NAT_P1) {
        mbar_wait(bar_full(bars, wg, 1), ph);
        PROFS(14, wg, 41 + it * 3);
        wg_fence();
      }
      if (ks == NAT_P2) {
        mbar_wait(bar_full(bars, wg, 2), ph);
        PROFS(14, wg, 42 + it * 3);
        wg_fence();
      }
      const uint64_t d = dK + ((ks * kChunkBytes) >> 4);
      if (ks == 0) wg_s104z<0, 52>(aE, qa[0], qa[1], qa[2], qa[3], d, 0, mq);
      else wg_s104<0, 52>(aE, qa[4 * ks], qa[4 * ks + 1], qa[4 * ks + 2], qa[4 * ks + 3], d, 1, mq);
    }
    wg_commit();
    wg_s48z<0, 24>(aO, qa[0], qa[1], qa[2], qa[3], dK + ((7 * 1024 + 64) >> 4), 0, mq);
#pragma unroll
    for (int ks = 1; ks < 6; ks++)
      wg_s48<0, 24>(aO, qa[4 * ks], qa[4 * ks + 1], qa[4 * ks + 2], qa[4 * ks + 3], dK + ((ks * kChunkBytes + 7 * 1024 + 64) >> 4), 1, mq);
    wg_commit();
    wg_s56z<0, 28>(bE, qb[0], qb[1], qb[2], qb[3], dK, 0, mq);
#pragma unroll
    for (int ks = 1; ks < 6; ks++) wg_s56<0, 28>(bE, qb[4 * ks], qb[4 * ks + 1], qb[4 * ks + 2], qb[4 * ks + 3], dK + ((ks * kChunkBytes) >> 4), 1, mq);
    wg_commit();
    wg_wait<2>();
    fence_regs(aE);
    PROFS(5, wg, 5 + it * 12);

    uint32_t pa[14], pb[14], meta[4];
    {
      float vA[14], vB[14];
      pick_v(aE, vA, fl);
      pick_u(aE + 28, vA + 8, fl);
      fence_regs(vA);
      if (k == 0) {
        if (__builtin_expect(__any_sync(0xffffffffu, vA[6] != vA[6]), 0)) {
          wg_wait<0>();
          fence_regs(aO);
          fence_regs(bE);
          if (refetch(sbase + kW1Off, wimg, false)) {
#pragma unroll
            for (int j = 0; j < 24; j++) oa[j] = ob[j] = 0u;
            k -= 2;
            continue;
          }
        }
        if (elect_one()) mbar_arrive(bar_xf(bars));
      }
      wg_fence();
      wg_s104z<0, 52>(bO, qb[0], qb[1], qb[2], qb[3], dK + 4, 0, mq);
#pragma unroll
      for (int ks = 1; ks < 6; ks++)
        wg_s104<0, 52>(bO, qb[4 * ks], qb[4 * ks + 1], qb[4 * ks + 2], qb[4 * ks + 3], dK + ((ks * kChunkBytes + 64) >> 4), 1, mq);
      wg_commit();
      if (k + 1 < nt) nb_arrive(1 + wg);
      uint32_t rt[9];
#pragma unroll
      for (int i = 0; i < 7; i++) rt[i] = sign_bytes(geo[i >> 2], 0x8888u + 0x1111u * (i & 3));
      rt[7] = sign_bytes(geo[2], 0x9988u);
      rt[8] = sign_bytes(geo[2], 0xBBAAu);
      keep_regs(rt);
      pa[13] = pb[13] = 0u;
      wg_wait<2>();
      keep_regs(qa);
      fence_regs(aO);
      float oA[6], eB[8];
      pick_u(aO, oA, fl);
      wg_wait<1>();
      fence_regs(bE);
      pick_v(bE, eB, fl);
      vA[8] = sel<kColA>(oA[0], vA[8], fl), vA[9] = sel<kColA>(oA[1], vA[9], fl);
      vA[10] = sel<kColA * 2>(oA[2], vA[10], fl), vA[11] = sel<kColA * 2>(oA[3], vA[11], fl);
      vA[12] = sel<kColA * 4>(oA[4], vA[12], fl), vA[13] = sel<kColA * 4>(oA[5], vA[13], fl);
      {
        const float m1 = __uint_as_float(0x88DD88DDu), m0 = __uint_as_float(0x88DDDD88u);
        meta[0] = 0xDD88DD88u ^ __byte_perm(fl, 0u, 0x3344);
        meta[1] = __float_as_uint(sel<kColA * 16>(sel<kColA>(m1, m0, fl), __uint_as_float(meta[0]), fl));
        meta[2] = __float_as_uint(sel<kColA * 8>(m1, m0, fl));
        meta[3] = __float_as_uint(sel<kColA * 4>(m1, m0, fl));
        keep_regs(meta);
      }
      float mA = own_max(vA, fl);
      fl |= __float_as_uint(eB[7]) & zero;
      fence_regs(eB);
      fence_regs(vA);
      asm volatile("" : "+f"(mA), "+r"(fl));
      sched_fence();
      wg_wait<0>();
      sched_fence();
      keep_regs(qb);
      fence_regs(bO);
      if (NAT_TL == 0 && k == 5) nb_arrive(11);
      PROFS(6, wg, 6 + it * 12);
      if (w == 0) GT(24 + k);
      mA = quad_max(mA);
#pragma unroll
      for (int i = 0; i < 14; i++) vA[i] = ex2(vA[i] - mA);
      pick_v(bO, vB, fl);
      pick_u(bO + 28, vB + 8, fl);
#pragma unroll
      for (int i = 0; i < 8; i += 2) vB[i] = sel<kColB>(vB[i], eB[i], fl), vB[i + 1] = sel<kColB * 2>(vB[i + 1], eB[i + 1], fl);
      float mB = quad_max(own_max(vB, fl));
      if (NAT_SB) {
        fence_regs(vA);
        fence_regs(vB);
        asm volatile("" : "+f"(mB));
        sched_fence();
      }
      if (NAT_TL == 1 && k == 5) nb_arrive(11);
      PROFS(7, wg, 7 + it * 12);
#pragma unroll
      for (int i = 0; i < 14; i++) vB[i] = ex2(vB[i] - mB);
      route(vA, row_rcp(vA, fl), rt, pa);
      route(vB, row_rcp(vB, fl), rt, pb);
    }
    PROFS(8, wg, 8 + it * 12);
    if (k == NAT_PK) PROFS(18, wg, 53);
    sched_fence();

    float ac0[48], ac1[48];
    {
      float z0[32], z1[32], z2[32];
      uint32_t za[24], zb[24];
      wg_fence();
      pv_chunk<0>(z0, pa, pb, meta, dV);
      wg_commit();
      pv_chunk<1>(z1, pa, pb, meta, dV);
      wg_commit();
      wg_wait<1>();
      if (k == NAT_PK) PROFS(18, wg, 54);
      if (k + 1 < nt) nb_arrive_p(7);
      pv_chunk<2, 0, 3>(z2, pa, pb, meta, dV);
      wg_commit();
      sched_fence();
      fence_regs(z0);
      pack_z<0>(z0, za, zb);
      sched_fence();
      wg_fence();
      pv_chunk<2, 3, 7>(z2, pa, pb, meta, dV);
      wg_commit();
      wg_wait<2>();
      if (k == NAT_PK) PROFS(19, wg, 55);
      if (k + 1 < nt) nb_arrive_p(8);
      if (k < 2) mbar_wait(k == 1 ? bar_wok(bars) : bar_w2a(bars), 0);
      wg_fence();
      g2_steps<0, 4, 0>(ac0, za, zb, dX0);
      wg_commit();
      sched_fence();
      fence_regs(z1);
      pack_z<1>(z1, za, zb);
      sched_fence();
      wg_fence();
      g2_steps<4, 8, 0>(ac0, za, zb, dX0);
      wg_commit();
      wg_wait<2>();
      if (k + 1 < nt) nb_arrive_p(9);
      if (k == NAT_PK) PROFS(20, wg, 56);
      keep_regs(pa);
      keep_regs(pb);
      keep_regs(meta);
      sched_fence();
      if (k + 1 < nt) mbar_wait(bar_w2m(bars), k & 1);
      fence_regs(z2);
      pack_z<2>(z2, za, zb);
      keep_regs(za);
      keep_regs(zb);
      sched_fence();
      PROFS(9, wg, 9 + it * 12);
      wg_fence();
      g2_steps<8, 12, 0>(ac0, za, zb, dX2);
      wg_commit();
      wg_wait<2>();
      if (k > 0 && k + 1 < nt) nb_arrive(11);
      g2_steps<8, 12, 8>(ac1, za, zb, dY2);
      wg_commit();
      wg_wait<2>();
      if (k > 0 && k + 1 < nt) nb_arrive(12);
      if (k != 1 && k + 1 < nt) mbar_wait(bar_w2(bars), k > 1 ? (k - 1) & 1 : 0);
      wg_fence();
      g2_steps<0, 4, 8>(ac1, za, zb, dY0);
      wg_commit();
      wg_wait<2>();
      if (k + 2 < nt) nb_arrive_p(13);
      g2_steps<4, 8, 8>(ac1, za, zb, dY0);
      wg_commit();
      if (k + 1 < nt) nb_arrive(3 + wg);
      PROFS(10, wg, 10 + it * 12);
      const bool direct = k + 2 >= nt && (wg == 1 || nt < 6);
      wg_wait<2>();
      if (k + 2 < nt && (k > 0 || nt == 6)) nb_arrive_p(5);
      sched_fence();
      fence_regs(ac0);
      pack_out<0>(ac0, oa, ob);
      store_rows<0, 3>(direct, poA, poB, oa, ob);
      __nv_bfloat16 *qA = poA - 192 * wg, *qB = poB - 192 * wg;
      sched_fence();
      wg_wait<0>();
      fence_regs(ac1);
      PROFS(11, wg, 11 + it * 12);
      pack_out<1>(ac1, oa, ob);
      asm volatile("" : "+l"(qA), "+l"(qB));
      store_rows<3, 6>(direct, qA, qB, oa, ob);
      if (k == 0) {
        uint32_t m[2] = {oa[0], oa[1]};
#pragma unroll
        for (int i = 2; i < 24; i++) asm("max.NaN.bf16x2 %0, %0, %1;" : "+r"(m[i & 1]) : "r"(oa[i]));
        asm("max.NaN.bf16x2 %0, %0, %1;" : "+r"(m[0]) : "r"(m[1]));
        uint32_t nan;
        asm volatile("{\n.reg .pred p;\nsetp.ne.u32 p, %1, 0;\nbar.red.or.pred p, 15, 128, p;\nselp.u32 %0, 1, 0, p;\n}\n"
                     : "=r"(nan) : "r"(((m[0] & 0x7FFF7FFFu) + 0x007F007Fu) & 0x80008000u) : "memory");
        if (__builtin_expect(__any_sync(0xffffffffu, nan), 0)) {
          if (nt == 6) mbar_wait(bar_x(bars, 1), 1);
          for (bool first = true; __any_sync(0xffffffffu, refetch(sbase + kW2Off, wimg + w2_offset(), first)); first = false) { }
          wg_fence();
          g2_steps<0, 8, 0>(ac0, za, zb, dX0);
          g2_steps<8, 12, 0>(ac0, za, zb, dX2);
          g2_steps<0, 8, 0>(ac1, za, zb, dY0);
          g2_steps<8, 12, 0>(ac1, za, zb, dY2);
          wg_commit();
          wg_wait<0>();
          fence_regs(ac0);
          fence_regs(ac1);
          pack_out<0>(ac0, oa, ob);
          pack_out<1>(ac1, oa, ob);
          if (nt == 6) {
            asm volatile("bar.sync 15, 128;" ::: "memory");
            if (w == 0 && elect_one()) {
              const TileCoord tc = decode_tile(tt, tile0 + 2);
              mbar_arrive_expect_tx(bar_raw(bars), kWChunk);
              move_px<0, 1>(tm, tt, sbase + kXOff, bar_raw(bars), first_line(tc), tc.kind);
            }
            __syncwarp();
            mbar_wait(bar_raw(bars), 0);
          }
        }
        if (nt < 6) nb_arrive_p(5);
        if (elect_one()) mbar_arrive(bar_wok(bars));
      }
      keep_regs(za);
      keep_regs(zb);
#pragma unroll
      for (int i = 0; i < 8; i++) geo[i] = geo[i + 4];
      keep_regs(oa);
      keep_regs(ob);
      PROFS(12, wg, 12 + it * 12);
      sched_fence();
    }
  }
  if (wg == 0 && nt == 6) {
    if (NAT_TL < 2) nb_sync(11);
    stage_out<0, 12>(sts + kW1Off, 0, oa, ob);
    fence_proxy_async();
    nb_arrive_p(6);
  }
  PROF(wg, 38);
  GT_DUMP();
  PROF_DUMP(wg);
}

struct HaloCols { int vj, vc, uj, uc; };
__device__ __forceinline__ HaloCols halo_cols(const TileCoord& tc) {
  const int c0 = halo_c0(tc);
  return HaloCols{c0 > 98, c0 > 98 ? 98 : c0 + 3, c0 < 0 ? -1 : 0, c0 < 0 ? 4 : c0};
}
__device__ __forceinline__ void load_halo(const Maps& tm, uint32_t sbase, uint32_t bars, const TileCoord tc, int k, int c) {
  const HaloCols hc = halo_cols(tc);
  const int h6 = halo_r0(tc) + (tc.up ? 0 : 8), h2 = halo_r0(tc) + 6, h8 = halo_r0(tc) + (tc.up ? 0 : 6), ch = 24 * tc.pc + 8 * c;
  uint32_t dv = sbase + 2 * c * kChunkBytes, du = dv + 7 * 1024;
  if (((k ^ tc.up) & 1) == 0) dv += 4 * 1024, du += 3 * 1024;
  const uint32_t bar = bar_full(bars, k & 1, c);
  mbar_arrive_expect_tx(bar, 14 * 1024);
  nb_sync_p(7 + c);
#pragma unroll
  for (int h = 0; h < 2; h++) {
    tma_load_5d(dv + h * kChunkBytes, &tm.v6, bar, ch + 4 * h, hc.vj, hc.vc, tc.pr, h6);
    tma_load_5d(du + h * kChunkBytes, &tm.u8, bar, ch + 4 * h, hc.uj, h8, tc.pr, hc.uc);
    tma_load_5d(sbase + (2 * c + h) * kChunkBytes + 3 * 1024, &tm.v2, bar, ch + 4 * h, hc.vj, hc.vc, tc.pr, h2);
  }
  PROFS(15, 2, k * 4 + c);
}
__device__ __forceinline__ void gather_px(const __nv_bfloat16* __restrict__ x, uint32_t buf, uint32_t bar, const TileCoord tc) {
  const int lane = threadIdx.x & 31, g = lane >> 3;
  uint32_t ro[4], co[4];
#pragma unroll
  for (int i = 0; i < 4; i++) {
    ro[i] = qpix(tc.pr, 8 * tc.I + 2 * i + (g & 1)) * (kW * kC * 2) + 16 * (lane & 7);
    co[i] = qpix(tc.pc, 8 * tc.J + 2 * i + (g >> 1)) * (kC * 2);
  }
  uint32_t dst = buf + g * 128 + (((lane & 7) ^ g) << 4);
  keep_regs(ro);
  keep_regs(co);
  sched_fence();
  nb_sync_p(13);
  nb_sync_p(5);
#pragma unroll
  for (int i = 0; i < 16; i++) {
    const char* src = (const char*)x + (ro[i >> 2] + co[i & 3]);
#pragma unroll
    for (int q = 0; q < 3; q++)
      asm volatile("cp.async.cg.shared.global [%0], [%1], 16;" ::"r"((dst ^ ((i & 1) * 576)) + (i >> 1) * 3072 + q * 1024), "l"(src + 128 * q) : "memory");
  }
  asm volatile("cp.async.wait_all;" ::: "memory");
  fence_proxy_async();
  __syncwarp();
  if (elect_one()) mbar_arrive(bar);
  __syncwarp();
}

__global__ void __launch_bounds__(384, 1)
nat_kernel(const __nv_bfloat16* __restrict__ x, __nv_bfloat16* out, const __nv_bfloat16* __restrict__ wqkv,
           const __nv_bfloat16* __restrict__ wo, uint8_t* wimg, const uint32_t zero,
           const __grid_constant__ Maps tm, const __grid_constant__ TileTable tt) {
  extern __shared__ uint8_t smem_raw[];
  constexpr uint32_t sbase = 1024;
  constexpr uint32_t bars = sbase + kBarOff;
  if (smem_u32(smem_raw) != sbase) __trap();
  const int tid = threadIdx.x;
  const uint32_t t_start = now_ns();
  if (tid == 0) GT(0);
  const int wid = __shfl_sync(0xffffffffu, tid >> 5, 0);
  if ((wid == 4 || (wid == 5 && blockIdx.x - 2 < 16)) && blockIdx.x < 128 && wqkv != nullptr) {
    fold_w1(blockIdx.x - 2 < 16 ? 2 * blockIdx.x + wid - 6 : blockIdx.x + (blockIdx.x < 2 ? 0 : 16), wqkv, wimg);
    if (wid == 4) asm volatile("bar.arrive 12, 64;" ::: "memory");
    if (tid == 128) GT(7);
  }
  if (wid == NAT_PW) {
    if (blockIdx.x >= 128) {
      asm volatile("prefetch.tensormap [%0];" ::"l"((uint64_t)&tm.wv) : "memory");
      asm volatile("prefetch.tensormap [%0];" ::"l"((uint64_t)&tm.wo) : "memory");
    }
    asm volatile("prefetch.tensormap [%0];" ::"l"((uint64_t)&tm.v14) : "memory");
    asm volatile("prefetch.tensormap [%0];" ::"l"((uint64_t)&tm.u8) : "memory");
    const CUtensorMap* px = tm.px + (blockIdx.x >= 112 ? 2 : edge_strip());
    asm volatile("prefetch.tensormap [%0];" ::"l"((uint64_t)px) : "memory");
    asm volatile("prefetch.tensormap [%0];" ::"l"((uint64_t)(px + 1)) : "memory");
    asm volatile("prefetch.tensormap [%0];" ::"l"((uint64_t)&tm.v6) : "memory");
    asm volatile("prefetch.tensormap [%0];" ::"l"((uint64_t)&tm.v2) : "memory");
    asm volatile("prefetch.tensormap [%0];" ::"l"((uint64_t)(px + 4)) : "memory");
    asm volatile("prefetch.tensormap [%0];" ::"l"((uint64_t)(px + 5)) : "memory");
  }
  if (wid >= 8) {
    asm volatile("setmaxnreg.dec.sync.aligned.u32 24;");
    const int c = wid & 3, lane = tid & 31;
    const int tile0 = blockIdx.x * kTilesPerCta, nt = num_tiles();
    uint32_t w2o = 0;
    if (c == 3) {
      asm volatile("bar.sync 13, 64;" ::: "memory");
      __nanosleep(NAT_TW2 - 2000);
      w2o = w2_offset();
      if (elect_one()) {
        mbar_arrive_expect_tx(bar_w2a(bars), kWChunk);
        mbar_arrive_expect_tx(bar_w2(bars), kWChunk);
        wait_clock(t_start, NAT_TW2);
        bulk_load(sbase + kW2Off, wimg + w2o, kWChunk, bar_w2a(bars));
        mbar_wait(bar_xf(bars), 0);
        bulk_load(sbase + kW2Off + 2 * kWChunk, wimg + (w2o + 2 * kWChunk), kWChunk, bar_w2(bars));
      }
      __syncwarp();
      if (nt < 6) {
#pragma unroll 1
        for (int k = 2; k < 4; k++) {
          gather_px(x, sbase + kXOff, bar_x(bars, 1), decode_tile(tt, tile0 + k));
        }
      }
      if (wqkv == nullptr) return;
      mbar_wait(bar_wok(bars), 0);
      if (lane == 0) asm volatile("red.relaxed.gpu.global.add.u32 [%0], 1;" ::"l"(g_flag) : "memory");
      if (blockIdx.x >= 48) return;
      if (lane == 0) {
        uint32_t v, it = 0;
        do {
          __nanosleep(2000);
          asm volatile("ld.relaxed.gpu.global.u32 %0, [%1];" : "=r"(v) : "l"(g_flag) : "memory");
        } while (v < gridDim.x && ++it < (1u << 16));
      }
      __syncwarp();
#pragma unroll
      for (int i = 0; i < 6; i++)
        stg128(wimg + ((i < 3 ? 0u : 3 * kWBytes - w2o) + blockIdx.x * 1536 + (i % 3) * 512 + lane * 16), kEmpty, kEmpty, kEmpty, kEmpty);
      if (lane == 0 && atomicAdd(g_flag + 32, 1u) == 47) {
        g_flag[0] = g_flag[32] = 0;
        g_flag[64] = w2o == kWBytes;
      }
      return;
    }
    if (!elect_one()) return;
    if (c == 0) {
      for (int i = 0; i < kNumBars; i++) mbar_init(bars + i * 8, i == 13 || i == 16 ? 4 : 1);
      asm volatile("st.shared.v2.u32 [%0], {%1,%1};" ::"r"(bars + 192), "r"(0) : "memory");
      asm volatile("fence.mbarrier_init.release.cluster;" ::: "memory");
      if (blockIdx.x - 128 < 3 && wqkv != nullptr) {
        const int q = blockIdx.x & 3;
        mbar_arrive_expect_tx(bar_raw(bars), kWBytes + kWChunk);
#pragma unroll
        for (int j = 0; j < 6; j++)
          asm volatile("cp.async.bulk.tensor.2d.shared::cluster.global.tile.mbarrier::complete_tx::bytes [%0], [%1, {%3, %4}], [%2];" ::"r"(
                           j < 3 ? sbase + j * 8192 : sbase + kW2Off + (j - 3) * kWChunk),
                       "l"((uint64_t)(j < 3 ? &tm.wv : &tm.wo)), "r"(bar_raw(bars)), "r"(j < 3 ? 384 + 64 * j : 64 * (j - 3)), "r"(j < 3 ? 64 * q : 0) : "memory");
        asm volatile("bar.arrive 11, 160;" ::: "memory");
        w2o = w2_offset();
        asm volatile("bar.sync 10, 288;" ::: "memory");
#pragma unroll
        for (int h = 0; h < 2; h++)
          asm volatile("cp.async.bulk.global.shared::cta.bulk_group [%0], [%1], %2;" ::"l"(wimg + (w2o + w2piece(h, q) * (kWChunk / 2))),
                       "r"(sbase + kW1Off + h * (kWChunk / 2)), "r"(kWChunk / 2) : "memory");
        asm volatile("cp.async.bulk.commit_group;" ::: "memory");
        asm volatile("cp.async.bulk.wait_group.read 0;" ::: "memory");
        GT(31);
      }
      asm volatile("bar.arrive 0, 224;" ::: "memory");
      asm volatile("bar.arrive 14, 160;" ::: "memory");
      asm volatile("bar.arrive 13, 64;" ::: "memory");
      const TileCoord tc0 = decode_tile(tt, tile0);
      const HaloCols hc = halo_cols(tc0);
      const int h0 = halo_r0(tc0);
#pragma unroll
      for (int j = 0; j < 3; j++) mbar_arrive_expect_tx(bar_full(bars, 0, j), 2 * kChunkBytes);
      GT(17);
#pragma unroll 1
      for (int i = 0; i < 6; i++) {
        if (i == NAT_H0 || i == NAT_X1P) mbar_arrive(bar_go(bars, i != NAT_H0));
        if (i == NAT_H0) {
          wait_clock(t_start, NAT_HP);
#pragma unroll
          for (int q = 4 * NAT_H0; q < 24; q += 8) {
            tma_prefetch_5d(&tm.v6, 24 * tc0.pc + q, hc.vj, hc.vc, tc0.pr, h0 + (tc0.up ? 0 : 8));
            tma_prefetch_5d(&tm.u8, 24 * tc0.pc + q, hc.uj, h0 + (tc0.up ? 0 : 6), tc0.pr, hc.uc);
            if (blockIdx.x >= 112) tma_prefetch_5d(&tm.v2, 24 * tc0.pc + q, hc.vj, hc.vc, tc0.pr, h0 + 6);
          }
          mbar_wait(bar_w1q(bars), 0);
        }
        const uint32_t dst = sbase + i * kChunkBytes, bar = bar_full(bars, 0, i >> 1);
        const int ch = 24 * tc0.pc + 4 * i;
        tma_load_5d(dst, &tm.v14, bar, ch, hc.vj, hc.vc, tc0.pr, h0);
        tma_load_5d(dst + 7 * 1024, &tm.u8, bar, ch, hc.uj, h0 + (tc0.up ? 0 : -2), tc0.pr, hc.uc);
        tma_load_5d(dst + 10 * 1024, &tm.u8, bar, ch, hc.uj, h0 + (tc0.up ? 8 : 6), tc0.pr, hc.uc);
      }
      w2o = w2_offset();
    } else {
      asm volatile("bar.sync 0, 224;" ::: "memory");
      if (c == 2) {
        if (wqkv != nullptr && nt == 6) asm volatile("bar.sync 12, 64;" ::: "memory");
        const uint32_t c0 = clock();
        while ((uint32_t)clock() - c0 < NAT_TD) { }
        wait_clock(t_start, NAT_T0);
#pragma unroll
        for (int j = 0; j < 3; j++) {
          mbar_arrive_expect_tx(bar_w1c(bars, j), kWChunk);
          bulk_load(sbase + kW1Off + j * kWChunk, wimg + j * kWChunk, kWChunk, bar_w1c(bars, j));
        }
        mbar_arrive(bar_w1q(bars));
        GT(2);
      } else {
#pragma unroll 1
        for (int j = 0; j < 2; j++) {
          const TileCoord tc = decode_tile(tt, tile0 + j);
          const int line = first_line(tc);
          mbar_arrive_expect_tx(bar_x(bars, j), kWChunk);
          if (j == 1 || (tc.kind == 0 && NAT_XF == 0)) mbar_wait(bar_go(bars, j), 0);
          if (j == 0) GT(15);
          move_px<0, 2>(tm, tt, sbase + kXOff + (1 - j) * kWChunk, bar_x(bars, j), line, tc.kind);
          if (j == 0) GT(16);
        }
        w2o = w2_offset();
      }
    }
#pragma unroll 1
    for (int k = 1; k < nt; k++) {
      const TileCoord tn = decode_tile(tt, tile0 + k + 1);
      const int line = first_line(tn);
      if (c == 1) {
        nb_sync_p(6);
        bulk_load(sbase + kXOff, wimg + (w2o + kWChunk), kWChunk, bar_w2m(bars));
        mbar_arrive_expect_tx(bar_w2m(bars), kWChunk);
      }
      if (c == 2) {
        if (k == 1) wait_clock(t_start, NAT_TX2);
        else __nanosleep(NAT_PFD);
        if (k < 5 && nt == 6) move_px<1, 1>(tm, tt, 0, 0, line, tn.kind);
      }
      if (c == 2 && (blockIdx.x >= 112 || k == 5)) {
        const TileCoord tc = decode_tile(tt, tile0 + k);
        const HaloCols hc = halo_cols(tc);
        const int h8 = halo_r0(tc) + (tc.up ? 0 : 6);
#pragma unroll 1
        for (int q = 0; q < 24; q += 8) {
          tma_prefetch_5d(&tm.v6, 24 * tc.pc + q, hc.vj, hc.vc, tc.pr, h8);
          tma_prefetch_5d(&tm.v2, 24 * tc.pc + q, hc.vj, hc.vc, tc.pr, h8 + 6);
          tma_prefetch_5d(&tm.u8, 24 * tc.pc + q, hc.uj, h8, tc.pr, hc.uc);
        }
      }
      load_halo(tm, sbase, bars, decode_tile(tt, tile0 + k), k, c);
      if (c == 0 && k >= 3 && NAT_RP == 1) {
        if (NAT_RD) __nanosleep(NAT_RD);
        asm volatile("cp.async.bulk.wait_group.read 0;" ::: "memory");
        bulk_load(sbase + out_slot(k - 1, nt), wimg + (w2o + out_slot(k - 1, nt) - kW2Off), kWChunk, bar_w2(bars));
        mbar_arrive_expect_tx(bar_w2(bars), kWChunk);
      }
      if (c == 0 && k < 5 && nt == 6) {
        const int f = ~k & 1;
        if (tn.kind == 0) {
#pragma unroll
          for (int j = 0; j < 4; j++) {
            if ((j & 1) == 0) nb_sync_p(j ? 5 : 13);
            tma_load_5d(sbase + kXOff + (j ^ 2 * f) * 6144, tm.px, bar_x(bars, 1), 0, 0, 0, 0, line + 6 * (j ^ 2 * f));
          }
        } else {
          nb_sync_p(13);
          move_px<0, 4, 4>(tm, tt, sbase + kXOff, bar_x(bars, 1), line, tn.kind, 4 * f);
          nb_sync_p(5);
          move_px<0, 4, 4>(tm, tt, sbase + kXOff, bar_x(bars, 1), line, tn.kind, 4 - 4 * f);
        }
        mbar_arrive_expect_tx(bar_x(bars, 1), kWChunk);
        PROFS(16, 2, k * 4 + 3);
      }
      if (c == 0 && k >= 2) {
        const TileCoord tp = decode_tile(tt, tile0 + k - 2);
        const int lp = first_line(tp);
        nb_sync_p(10);
        if (NAT_XW == 1 && k < 5 && nt == 6) mbar_wait(bar_x(bars, 1), k & 1);
        if (NAT_XW > 1) __nanosleep(NAT_XW);
        move_px<2, NAT_SU>(tm, tt, sbase + out_slot(k, nt), 0, lp, tp.kind);
        if (NAT_RP == 0 && k + 1 < nt) {
          asm volatile("cp.async.bulk.wait_group.read 0;" ::: "memory");
          bulk_load(sbase + out_slot(k, nt), wimg + (w2o + out_slot(k, nt) - kW2Off), kWChunk, bar_w2(bars));
          mbar_arrive_expect_tx(bar_w2(bars), kWChunk);
        }
      }
    }
    if (c == 1 && nt == 6) {
      const TileCoord tp = decode_tile(tt, tile0 + 4);
      const int lp = first_line(tp);
      nb_sync_p(6);
      move_px<2, 1>(tm, tt, sbase + kW1Off, 0, lp, tp.kind);
    }
    asm volatile("cp.async.bulk.wait_group 0;" ::: "memory");
  } else {
    {
      if (blockIdx.x - 128 < 3 && wqkv != nullptr) {
        if (wid < 4) {
          asm volatile("bar.sync 11, 160;" ::: "memory");
          mbar_wait(bar_raw(bars), 0);
        } else if (wid < 6 && elect_one()) {
          asm volatile("cp.async.bulk.prefetch.L2.global [%0], %1;" ::"l"(wid == 4 ? wo : wqkv + (blockIdx.x & 3) * 64 * 576), "r"(kWBytes) : "memory");
        }
        __syncwarp();
        if (tid == 0) GT(7);
        float acc[96];
        wg_fence();
        wg_m192tz<0, 96>(acc, make_desc(sbase, 16, 1024), make_desc(sbase + kW2Off, kWChunk, 1024), 0);
#pragma unroll
        for (int s = 1; s < 12; s++)
          wg_m192t<0, 96>(acc, make_desc(sbase + (s >> 2) * 8192 + (s & 3) * 32, 16, 1024), make_desc(sbase + kW2Off + s * 2048, kWChunk, 1024), 1);
        wg_commit();
        wg_wait<0>();
        fence_regs(acc);
        if (tid == 0) GT(19);
        const int m = (tid >> 3) & 3;
#pragma unroll
        for (int j = 0; j < 24; j += 2) {
          const int n = g2_inv(8 * (j + (m >> 1)) + (tid & 7));
          asm volatile("stmatrix.sync.aligned.m8n8.x4.trans.shared.b16 [%0], {%1,%2,%3,%4};" ::"r"(
                           sbase + kW1Off + (wid >> 2) * kWChunk + n * 128 + (((2 * (wid & 3) + (m & 1)) ^ (n & 7)) << 4)),
                       "r"(pack_bf16(acc[4 * j], acc[4 * j + 1])), "r"(pack_bf16(acc[4 * j + 2], acc[4 * j + 3])),
                       "r"(pack_bf16(acc[4 * j + 4], acc[4 * j + 5])), "r"(pack_bf16(acc[4 * j + 6], acc[4 * j + 7])) : "memory");
        }
        fence_proxy_async();
        if (tid == 0) GT(18);
        asm volatile("bar.arrive 10, 288;" ::: "memory");
      }
    }
    __syncwarp();
    if (wid < 4) asm volatile("bar.sync 0, 224;" ::: "memory");
    else asm volatile("bar.sync 14, 160;" ::: "memory");
    asm volatile("setmaxnreg.inc.sync.aligned.u32 240;");
    consumer(wid >> 2, out, wimg, sbase, zero, tm, tt);
  }
}

}

typedef CUresult (*PFN_encodeTiled)(CUtensorMap*, CUtensorMapDataType, cuuint32_t, void*, const cuuint64_t*,
                                    const cuuint64_t*, const cuuint32_t*, const cuuint32_t*, CUtensorMapInterleave,
                                    CUtensorMapSwizzle, CUtensorMapL2promotion, CUtensorMapFloatOOBfill);

extern "C" void kernel_launch(void* const* d_in, const int* in_sizes, int n_in, void* d_out, int out_size) {
  const __nv_bfloat16* x = (const __nv_bfloat16*)d_in[0];
  const __nv_bfloat16* wqkv = (const __nv_bfloat16*)d_in[1];
  const __nv_bfloat16* wo = (const __nv_bfloat16*)d_in[2];
  __nv_bfloat16* out = (__nv_bfloat16*)d_out;

  static PFN_encodeTiled encode = nullptr;
  static int num_sms = 0;
  static uint8_t* wimg = nullptr;
  if (!encode) {
    void* fn = nullptr;
    cudaDriverEntryPointQueryResult qres;
    cudaGetDriverEntryPoint("cuTensorMapEncodeTiled", &fn, cudaEnableDefault, &qres);
    encode = (PFN_encodeTiled)fn;
    cudaFuncSetAttribute(nat::nat_kernel, cudaFuncAttributeMaxDynamicSharedMemorySize, nat::kSmemBytes);
    cudaGetSymbolAddress((void**)&wimg, nat::g_wimg32);
    int dev = 0;
    cudaGetDevice(&dev);
    cudaDeviceGetAttribute(&num_sms, cudaDevAttrMultiProcessorCount, dev);
  }
  nat::Maps tm;
  cuuint32_t estr[5] = {1, 1, 1, 1, 1};
  {
    cuuint64_t vdim[5] = {48, 2, 105, 2, 112}, udim[5] = {48, 2, 112, 2, 105};
    cuuint64_t vstr[4] = {7 * 768, 768, 224 * 384, 2 * 224 * 384}, ustr[4] = {7 * 768, 2 * 224 * 384, 224 * 384, 768};
    CUtensorMap* maps[4] = {&tm.v6, &tm.v2, &tm.v14, &tm.u8};
    for (int i = 0; i < 4; i++) {
      cuuint32_t box[5] = {4, 2, i < 3 ? 4u : 8u, 1, i == 0 ? 6u : i == 1 ? 2u : i == 2 ? 14u : 3u};
      encode(maps[i], CU_TENSOR_MAP_DATA_TYPE_UINT32, 5, (void*)x, i < 3 ? vdim : udim, i < 3 ? vstr : ustr, box, estr,
             CU_TENSOR_MAP_INTERLEAVE_16B, CU_TENSOR_MAP_SWIZZLE_128B, CU_TENSOR_MAP_L2_PROMOTION_L2_128B, CU_TENSOR_MAP_FLOAT_OOB_FILL_NONE);
    }
  }
  for (int i = 0; i < 8; i++) {
    const cuuint32_t row = 224 * 384, dr = (1u + (i & 1)) * row;
    const cuuint32_t shape[4][6] = {{8, 3, 2u - i, 2 * row, 128, 4 * 768}, {2, 4, 3, dr, 768, 128}, {4, 2, 3, 4 * row, 2 * row, 128}, {4, 2, 3, 768, dr, 128}};
    const cuuint32_t* sh = shape[i >> 1];
    cuuint64_t dim[5] = {64, sh[0], sh[1], sh[2], 224 * 224 * 3};
    cuuint64_t str[4] = {sh[3], sh[4], sh[5], 128};
    cuuint32_t box[5] = {64, sh[0], sh[1], sh[2], 1};
    encode(tm.px + i, CU_TENSOR_MAP_DATA_TYPE_BFLOAT16, 5, i < 4 ? (void*)x : (void*)out, dim, str, box, estr, CU_TENSOR_MAP_INTERLEAVE_NONE,
           CU_TENSOR_MAP_SWIZZLE_128B, i < 4 ? CU_TENSOR_MAP_L2_PROMOTION_L2_128B : CU_TENSOR_MAP_L2_PROMOTION_NONE,
           CU_TENSOR_MAP_FLOAT_OOB_FILL_NONE);
  }
  for (int i = 0; i < 2; i++) {
    cuuint64_t dim[2] = {i ? 192u : 576u, 192}, str[1] = {i ? 384u : 1152u};
    cuuint32_t box[2] = {64, i ? 192u : 64u};
    encode(i ? &tm.wo : &tm.wv, CU_TENSOR_MAP_DATA_TYPE_BFLOAT16, 2, i ? (void*)wo : (void*)wqkv, dim, str, box, estr,
           CU_TENSOR_MAP_INTERLEAVE_NONE, CU_TENSOR_MAP_SWIZZLE_128B, CU_TENSOR_MAP_L2_PROMOTION_L2_256B, CU_TENSOR_MAP_FLOAT_OOB_FILL_NONE);
  }
  nat::TileTable tt;
  nat::make_tiles(tt);
  const int grid = nat::kCtas;
  if (num_sms >= grid) {
    nat::nat_kernel<<<grid, 384, nat::kSmemBytes>>>(x, out, wqkv, wo, wimg, 0u, tm, tt);
  } else {
    nat::fold_kernel<<<27, 256>>>(wqkv, wo, wimg);
    nat::nat_kernel<<<grid, 384, nat::kSmemBytes>>>(x, out, nullptr, nullptr, wimg, 0u, tm, tt);
  }
}
```

```cpp
#include <cuda_runtime.h>
#include <cuda_bf16.h>
#include <cuda.h>
#include <stdint.h>

#define NAT_P1 2
#define NAT_P2 4
#define NAT_H0 2
#define NAT_T0 2150
#define NAT_TD 1250
#define NAT_TW2 4500
#define NAT_TX2 3600
#define NAT_X1P 4
#define NAT_PK 3
#define NAT_HP 1800
#define NAT_PFD 700
#define NAT_XW 200
#define NAT_SU 8
#define NAT_TL 0
#define NAT_PW 0
#define NAT_XF 1
#define NAT_RD 0
#define NAT_RP 0
#define NAT_SP 9
#define NAT_OT 0
#define NAT_SB 0
namespace nat {

constexpr int kW = 224, kC = 192;
constexpr int kCtas = 132;
constexpr int kTilesPerCta = 6;
constexpr float kAlpha = 0.07216878364870322f * 1.4426950408889634f;
constexpr uint32_t kChunkBytes = 13 * 1024;
constexpr uint32_t kWChunk = 192 * 128;
constexpr uint32_t kWBytes = 3 * kWChunk;
constexpr uint32_t kW1Off = 6 * kChunkBytes;
constexpr uint32_t kW2Off = kW1Off + kWBytes;
constexpr uint32_t kXOff = kW2Off + kWChunk;
constexpr uint32_t kBarOff = kW2Off + kWBytes;
constexpr uint32_t kProfOff = kBarOff + 208;
constexpr uint32_t kSmemBytes = kBarOff + 1024;

static_assert(kW1Off % 1024 == 0 && kW2Off % 1024 == 0 && kChunkBytes % 1024 == 0, "swizzle alignment");
static_assert(kSmemBytes <= 232448, "smem");

constexpr uint32_t kEmpty = 0xFFFFFFFFu;
#define NAT_R8(v) v, v, v, v, v, v, v, v
#define NAT_R2K(v) NAT_R8(NAT_R8(NAT_R8(v))), NAT_R8(NAT_R8(NAT_R8(v))), NAT_R8(NAT_R8(NAT_R8(v))), NAT_R8(NAT_R8(NAT_R8(v)))
#define NAT_IMG NAT_R8(NAT_R2K(kEmpty)), NAT_R2K(kEmpty)
__device__ __align__(1024) uint32_t g_wimg32[3 * kWBytes / 4] = {NAT_IMG, NAT_IMG, NAT_IMG};
static_assert(kWBytes / 4 == 9 * 2048, "initialiser");
__device__ __align__(128) uint32_t g_flag[96];
__device__ __forceinline__ uint32_t w2_offset() {
  uint32_t v;
  asm volatile("ld.relaxed.gpu.global.u32 %0, [%1];" : "=r"(v) : "l"(g_flag + 64) : "memory");
  return (1 + v) * kWBytes;
}

#define PROFS(id, wgid, slotid) do { } while (0)
#define PROF(wgid, slotid) do { } while (0)
#define PROF_DUMP(wgid) do { } while (0)

#define GT(slotid) do { } while (0)
#define GT_DUMP() do { } while (0)

__device__ __forceinline__ uint32_t smem_u32(const void* p) { return (uint32_t)__cvta_generic_to_shared(p); }

__device__ __forceinline__ void mbar_init(uint32_t bar, uint32_t count) {
  asm volatile("mbarrier.init.shared::cta.b64 [%0], %1;" ::"r"(bar), "r"(count) : "memory");
}
__device__ __forceinline__ void mbar_arrive(uint32_t bar) {
  asm volatile("mbarrier.arrive.shared::cta.b64 _, [%0];" ::"r"(bar) : "memory");
}
__device__ __forceinline__ void mbar_arrive_expect_tx(uint32_t bar, uint32_t bytes) {
  asm volatile("mbarrier.arrive.expect_tx.shared::cta.b64 _, [%0], %1;" ::"r"(bar), "r"(bytes) : "memory");
}
__device__ __forceinline__ void mbar_wait(uint32_t bar, uint32_t parity) {
  uint32_t ok;
  uint32_t it = 0;
  do {
    asm volatile(
        "{\n.reg .pred p;\n"
        "mbarrier.try_wait.parity.shared::cta.b64 p, [%1], %2;\n"
        "selp.u32 %0, 1, 0, p;\n}\n"
        : "=r"(ok)
        : "r"(bar), "r"(parity)
        : "memory");
    if (++it > (1u << 24)) break;
  } while (!ok);
}
__device__ __forceinline__ uint32_t mbar_test(uint32_t bar, uint32_t parity) {
  uint32_t ok;
  asm volatile("{\n.reg .pred p;\nmbarrier.test_wait.parity.shared::cta.b64 p, [%1], %2;\nselp.u32 %0, 1, 0, p;\n}\n"
               : "=r"(ok) : "r"(bar), "r"(parity) : "memory");
  return ok;
}
__device__ __forceinline__ void mbar_wait_if(uint32_t ok, uint32_t bar, uint32_t parity) {
  if (!__all_sync(0xffffffffu, ok)) mbar_wait(bar, parity);
}
__device__ __forceinline__ bool elect_one() {
  uint32_t r;
  asm volatile("{\n.reg .pred p;\nelect.sync _|p, 0xffffffff;\nselp.u32 %0, 1, 0, p;\n}\n" : "=r"(r));
  return r != 0;
}
__device__ __forceinline__ void nb_arrive(int id) { asm volatile("bar.arrive %0, 256;" ::"r"(id) : "memory"); }
__device__ __forceinline__ void nb_sync(int id) { asm volatile("bar.sync %0, 256;" ::"r"(id) : "memory"); }
__device__ __forceinline__ void nb_arrive_p(int id) { asm volatile("bar.arrive %0, 160;" ::"r"(id) : "memory"); }
__device__ __forceinline__ void nb_sync_p(int id) { asm volatile("bar.sync %0, 160;" ::"r"(id) : "memory"); }
__device__ __forceinline__ void fence_proxy_async() { asm volatile("fence.proxy.async.shared::cta;" ::: "memory"); }

__device__ __forceinline__ void tma_load_5d(uint32_t dst, const CUtensorMap* map, uint32_t bar, int c0, int c1, int c2,
                                            int c3, int c4) {
  asm volatile(
      "cp.async.bulk.tensor.5d.shared::cluster.global.tile.mbarrier::complete_tx::bytes "
      "[%0], [%1, {%3, %4, %5, %6, %7}], [%2];"
      ::"r"(dst), "l"((uint64_t)map), "r"(bar), "r"(c0), "r"(c1), "r"(c2), "r"(c3), "r"(c4)
      : "memory");
}
__device__ __forceinline__ void bulk_load(uint32_t dst, const void* src, uint32_t bytes, uint32_t bar) {
  asm volatile("cp.async.bulk.shared::cluster.global.mbarrier::complete_tx::bytes [%0], [%1], %2, [%3];"
               ::"r"(dst), "l"((uint64_t)src), "r"(bytes), "r"(bar)
               : "memory");
}

__device__ __forceinline__ void wg_fence() { asm volatile("wgmma.fence.sync.aligned;" ::: "memory"); }
__device__ __forceinline__ void wg_commit() { asm volatile("wgmma.commit_group.sync.aligned;" ::: "memory"); }
template <int N>
__device__ __forceinline__ void wg_wait() { asm volatile("wgmma.wait_group.sync.aligned %0;" ::"n"(N) : "memory"); }

template <int N>
__device__ __forceinline__ void fence_regs(float (&d)[N]) {
#pragma unroll
  for (int i = 0; i < N; i++) asm volatile("" : "+f"(d[i])::"memory");
}
template <int N>
__device__ __forceinline__ void keep_regs(uint32_t (&d)[N]) {
#pragma unroll
  for (int i = 0; i < N; i++) asm volatile("" : "+r"(d[i])::"memory");
}

__device__ __forceinline__ uint32_t pack_bf16(float lo, float hi) {
  uint32_t d;
  asm("cvt.rn.bf16x2.f32 %0, %1, %2;" : "=r"(d) : "f"(hi), "f"(lo));
  return d;
}
__device__ __forceinline__ float ex2(float x) {
  float y;
  asm("ex2.approx.ftz.f32 %0, %1;" : "=f"(y) : "f"(x));
  return y;
}
__device__ __forceinline__ float rcp_approx(float x) {
  float y;
  asm("rcp.approx.ftz.f32 %0, %1;" : "=f"(y) : "f"(x));
  return y;
}
__device__ __forceinline__ uint4 ldg128_nc(const void* p) {
  uint4 v;
  asm volatile("ld.global.nc.v4.u32 {%0,%1,%2,%3}, [%4];" : "=r"(v.x), "=r"(v.y), "=r"(v.z), "=r"(v.w) : "l"(p));
  return v;
}
__device__ __forceinline__ void stg128(void* p, uint32_t a, uint32_t b, uint32_t c, uint32_t d) {
  asm volatile("st.global.v4.u32 [%0], {%1,%2,%3,%4};" ::"l"(p), "r"(a), "r"(b), "r"(c), "r"(d) : "memory");
}

__device__ __forceinline__ long long clk64() {
  long long c;
  asm volatile("mov.u64 %0, %clock64;" : "=l"(c)::"memory");
  return c;
}
__device__ __forceinline__ void sched_fence() { while (clk64() < 0) { } }

__device__ __forceinline__ uint64_t make_desc(uint32_t addr, uint32_t lbo, uint32_t sbo, uint32_t mode = 1) {
  return (uint64_t)((addr & 0x3FFFF) >> 4) | ((uint64_t)(lbo >> 4) << 16) | ((uint64_t)(sbo >> 4) << 32) |
         ((uint64_t)mode << 62);
}

template <int OFF, int NN>
__device__ __forceinline__ void wg_m192(float (&d)[NN], uint64_t desc_a, uint64_t desc_b, int scale_d) {
  asm volatile(
      "{\n.reg .pred p;\nsetp.ne.b32 p, %98, 0;\n"
      "wgmma.mma_async.sync.aligned.m64n192k16.f32.bf16.bf16 "
      "{%0,%1,%2,%3,%4,%5,%6,%7,%8,%9,%10,%11,%12,%13,%14,%15,"
      "%16,%17,%18,%19,%20,%21,%22,%23,%24,%25,%26,%27,%28,%29,%30,%31,"
      "%32,%33,%34,%35,%36,%37,%38,%39,%40,%41,%42,%43,%44,%45,%46,%47,"
      "%48,%49,%50,%51,%52,%53,%54,%55,%56,%57,%58,%59,%60,%61,%62,%63,"
      "%64,%65,%66,%67,%68,%69,%70,%71,%72,%73,%74,%75,%76,%77,%78,%79,"
      "%80,%81,%82,%83,%84,%85,%86,%87,%88,%89,%90,%91,%92,%93,%94,%95}, "
      "%96, %97, p, 1, 1, 0, 0;\n}\n"
      : "+f"(d[OFF + 0]), "+f"(d[OFF + 1]), "+f"(d[OFF + 2]), "+f"(d[OFF + 3]), "+f"(d[OFF + 4]), "+f"(d[OFF + 5]),
        "+f"(d[OFF + 6]), "+f"(d[OFF + 7]), "+f"(d[OFF + 8]), "+f"(d[OFF + 9]), "+f"(d[OFF + 10]), "+f"(d[OFF + 11]),
        "+f"(d[OFF + 12]), "+f"(d[OFF + 13]), "+f"(d[OFF + 14]), "+f"(d[OFF + 15]), "+f"(d[OFF + 16]), "+f"(d[OFF + 17]),
        "+f"(d[OFF + 18]), "+f"(d[OFF + 19]), "+f"(d[OFF + 20]), "+f"(d[OFF + 21]), "+f"(d[OFF + 22]), "+f"(d[OFF + 23]),
        "+f"(d[OFF + 24]), "+f"(d[OFF + 25]), "+f"(d[OFF + 26]), "+f"(d[OFF + 27]), "+f"(d[OFF + 28]), "+f"(d[OFF + 29]),
        "+f"(d[OFF + 30]), "+f"(d[OFF + 31]), "+f"(d[OFF + 32]), "+f"(d[OFF + 33]), "+f"(d[OFF + 34]), "+f"(d[OFF + 35]),
        "+f"(d[OFF + 36]), "+f"(d[OFF + 37]), "+f"(d[OFF + 38]), "+f"(d[OFF + 39]), "+f"(d[OFF + 40]), "+f"(d[OFF + 41]),
        "+f"(d[OFF + 42]), "+f"(d[OFF + 43]), "+f"(d[OFF + 44]), "+f"(d[OFF + 45]), "+f"(d[OFF + 46]), "+f"(d[OFF + 47]),
        "+f"(d[OFF + 48]), "+f"(d[OFF + 49]), "+f"(d[OFF + 50]), "+f"(d[OFF + 51]), "+f"(d[OFF + 52]), "+f"(d[OFF + 53]),
        "+f"(d[OFF + 54]), "+f"(d[OFF + 55]), "+f"(d[OFF + 56]), "+f"(d[OFF + 57]), "+f"(d[OFF + 58]), "+f"(d[OFF + 59]),
        "+f"(d[OFF + 60]), "+f"(d[OFF + 61]), "+f"(d[OFF + 62]), "+f"(d[OFF + 63]), "+f"(d[OFF + 64]), "+f"(d[OFF + 65]),
        "+f"(d[OFF + 66]), "+f"(d[OFF + 67]), "+f"(d[OFF + 68]), "+f"(d[OFF + 69]), "+f"(d[OFF + 70]), "+f"(d[OFF + 71]),
        "+f"(d[OFF + 72]), "+f"(d[OFF + 73]), "+f"(d[OFF + 74]), "+f"(d[OFF + 75]), "+f"(d[OFF + 76]), "+f"(d[OFF + 77]),
        "+f"(d[OFF + 78]), "+f"(d[OFF + 79]), "+f"(d[OFF + 80]), "+f"(d[OFF + 81]), "+f"(d[OFF + 82]), "+f"(d[OFF + 83]),
        "+f"(d[OFF + 84]), "+f"(d[OFF + 85]), "+f"(d[OFF + 86]), "+f"(d[OFF + 87]), "+f"(d[OFF + 88]), "+f"(d[OFF + 89]),
        "+f"(d[OFF + 90]), "+f"(d[OFF + 91]), "+f"(d[OFF + 92]), "+f"(d[OFF + 93]), "+f"(d[OFF + 94]), "+f"(d[OFF + 95])
      : "l"(desc_a), "l"(desc_b), "r"(scale_d));
}

template <int OFF, int NN>
__device__ __forceinline__ void wg_m192z(float (&d)[NN], uint64_t desc_a, uint64_t desc_b, int scale_d) {
  asm volatile(
      "{\n.reg .pred p;\nsetp.ne.b32 p, %98, 0;\n"
      "wgmma.mma_async.sync.aligned.m64n192k16.f32.bf16.bf16 "
      "{%0,%1,%2,%3,%4,%5,%6,%7,%8,%9,%10,%11,%12,%13,%14,%15,"
      "%16,%17,%18,%19,%20,%21,%22,%23,%24,%25,%26,%27,%28,%29,%30,%31,"
      "%32,%33,%34,%35,%36,%37,%38,%39,%40,%41,%42,%43,%44,%45,%46,%47,"
      "%48,%49,%50,%51,%52,%53,%54,%55,%56,%57,%58,%59,%60,%61,%62,%63,"
      "%64,%65,%66,%67,%68,%69,%70,%71,%72,%73,%74,%75,%76,%77,%78,%79,"
      "%80,%81,%82,%83,%84,%85,%86,%87,%88,%89,%90,%91,%92,%93,%94,%95}, "
      "%96, %97, p, 1, 1, 0, 0;\n}\n"
      : "=f"(d[OFF + 0]), "=f"(d[OFF + 1]), "=f"(d[OFF + 2]), "=f"(d[OFF + 3]), "=f"(d[OFF + 4]), "=f"(d[OFF + 5]),
        "=f"(d[OFF + 6]), "=f"(d[OFF + 7]), "=f"(d[OFF + 8]), "=f"(d[OFF + 9]), "=f"(d[OFF + 10]), "=f"(d[OFF + 11]),
        "=f"(d[OFF + 12]), "=f"(d[OFF + 13]), "=f"(d[OFF + 14]), "=f"(d[OFF + 15]), "=f"(d[OFF + 16]), "=f"(d[OFF + 17]),
        "=f"(d[OFF + 18]), "=f"(d[OFF + 19]), "=f"(d[OFF + 20]), "=f"(d[OFF + 21]), "=f"(d[OFF + 22]), "=f"(d[OFF + 23]),
        "=f"(d[OFF + 24]), "=f"(d[OFF + 25]), "=f"(d[OFF + 26]), "=f"(d[OFF + 27]), "=f"(d[OFF + 28]), "=f"(d[OFF + 29]),
        "=f"(d[OFF + 30]), "=f"(d[OFF + 31]), "=f"(d[OFF + 32]), "=f"(d[OFF + 33]), "=f"(d[OFF + 34]), "=f"(d[OFF + 35]),
        "=f"(d[OFF + 36]), "=f"(d[OFF + 37]), "=f"(d[OFF + 38]), "=f"(d[OFF + 39]), "=f"(d[OFF + 40]), "=f"(d[OFF + 41]),
        "=f"(d[OFF + 42]), "=f"(d[OFF + 43]), "=f"(d[OFF + 44]), "=f"(d[OFF + 45]), "=f"(d[OFF + 46]), "=f"(d[OFF + 47]),
        "=f"(d[OFF + 48]), "=f"(d[OFF + 49]), "=f"(d[OFF + 50]), "=f"(d[OFF + 51]), "=f"(d[OFF + 52]), "=f"(d[OFF + 53]),
        "=f"(d[OFF + 54]), "=f"(d[OFF + 55]), "=f"(d[OFF + 56]), "=f"(d[OFF + 57]), "=f"(d[OFF + 58]), "=f"(d[OFF + 59]),
        "=f"(d[OFF + 60]), "=f"(d[OFF + 61]), "=f"(d[OFF + 62]), "=f"(d[OFF + 63]), "=f"(d[OFF + 64]), "=f"(d[OFF + 65]),
        "=f"(d[OFF + 66]), "=f"(d[OFF + 67]), "=f"(d[OFF + 68]), "=f"(d[OFF + 69]), "=f"(d[OFF + 70]), "=f"(d[OFF + 71]),
        "=f"(d[OFF + 72]), "=f"(d[OFF + 73]), "=f"(d[OFF + 74]), "=f"(d[OFF + 75]), "=f"(d[OFF + 76]), "=f"(d[OFF + 77]),
        "=f"(d[OFF + 78]), "=f"(d[OFF + 79]), "=f"(d[OFF + 80]), "=f"(d[OFF + 81]), "=f"(d[OFF + 82]), "=f"(d[OFF + 83]),
        "=f"(d[OFF + 84]), "=f"(d[OFF + 85]), "=f"(d[OFF + 86]), "=f"(d[OFF + 87]), "=f"(d[OFF + 88]), "=f"(d[OFF + 89]),
        "=f"(d[OFF + 90]), "=f"(d[OFF + 91]), "=f"(d[OFF + 92]), "=f"(d[OFF + 93]), "=f"(d[OFF + 94]), "=f"(d[OFF + 95])
      : "l"(desc_a), "l"(desc_b), "r"(scale_d));
}

template <int OFF, int NN>
__device__ __forceinline__ void wg_m192t(float (&d)[NN], uint64_t desc_a, uint64_t desc_b, int scale_d) {
  asm volatile(
      "{\n.reg .pred p;\nsetp.ne.b32 p, %98, 0;\n"
      "wgmma.mma_async.sync.aligned.m64n192k16.f32.bf16.bf16 "
      "{%0,%1,%2,%3,%4,%5,%6,%7,%8,%9,%10,%11,%12,%13,%14,%15,"
      "%16,%17,%18,%19,%20,%21,%22,%23,%24,%25,%26,%27,%28,%29,%30,%31,"
      "%32,%33,%34,%35,%36,%37,%38,%39,%40,%41,%42,%43,%44,%45,%46,%47,"
      "%48,%49,%50,%51,%52,%53,%54,%55,%56,%57,%58,%59,%60,%61,%62,%63,"
      "%64,%65,%66,%67,%68,%69,%70,%71,%72,%73,%74,%75,%76,%77,%78,%79,"
      "%80,%81,%82,%83,%84,%85,%86,%87,%88,%89,%90,%91,%92,%93,%94,%95}, "
      "%96, %97, p, 1, 1, 0, 1;\n}\n"
      : "+f"(d[OFF + 0]), "+f"(d[OFF + 1]), "+f"(d[OFF + 2]), "+f"(d[OFF + 3]), "+f"(d[OFF + 4]), "+f"(d[OFF + 5]),
        "+f"(d[OFF + 6]), "+f"(d[OFF + 7]), "+f"(d[OFF + 8]), "+f"(d[OFF + 9]), "+f"(d[OFF + 10]), "+f"(d[OFF + 11]),
        "+f"(d[OFF + 12]), "+f"(d[OFF + 13]), "+f"(d[OFF + 14]), "+f"(d[OFF + 15]), "+f"(d[OFF + 16]), "+f"(d[OFF + 17]),
        "+f"(d[OFF + 18]), "+f"(d[OFF + 19]), "+f"(d[OFF + 20]), "+f"(d[OFF + 21]), "+f"(d[OFF + 22]), "+f"(d[OFF + 23]),
        "+f"(d[OFF + 24]), "+f"(d[OFF + 25]), "+f"(d[OFF + 26]), "+f"(d[OFF + 27]), "+f"(d[OFF + 28]), "+f"(d[OFF + 29]),
        "+f"(d[OFF + 30]), "+f"(d[OFF + 31]), "+f"(d[OFF + 32]), "+f"(d[OFF + 33]), "+f"(d[OFF + 34]), "+f"(d[OFF + 35]),
        "+f"(d[OFF + 36]), "+f"(d[OFF + 37]), "+f"(d[OFF + 38]), "+f"(d[OFF + 39]), "+f"(d[OFF + 40]), "+f"(d[OFF + 41]),
        "+f"(d[OFF + 42]), "+f"(d[OFF + 43]), "+f"(d[OFF + 44]), "+f"(d[OFF + 45]), "+f"(d[OFF + 46]), "+f"(d[OFF + 47]),
        "+f"(d[OFF + 48]), "+f"(d[OFF + 49]), "+f"(d[OFF + 50]), "+f"(d[OFF + 51]), "+f"(d[OFF + 52]), "+f"(d[OFF + 53]),
        "+f"(d[OFF + 54]), "+f"(d[OFF + 55]), "+f"(d[OFF + 56]), "+f"(d[OFF + 57]), "+f"(d[OFF + 58]), "+f"(d[OFF + 59]),
        "+f"(d[OFF + 60]), "+f"(d[OFF + 61]), "+f"(d[OFF + 62]), "+f"(d[OFF + 63]), "+f"(d[OFF + 64]), "+f"(d[OFF + 65]),
        "+f"(d[OFF + 66]), "+f"(d[OFF + 67]), "+f"(d[OFF + 68]), "+f"(d[OFF + 69]), "+f"(d[OFF + 70]), "+f"(d[OFF + 71]),
        "+f"(d[OFF + 72]), "+f"(d[OFF + 73]), "+f"(d[OFF + 74]), "+f"(d[OFF + 75]), "+f"(d[OFF + 76]), "+f"(d[OFF + 77]),
        "+f"(d[OFF + 78]), "+f"(d[OFF + 79]), "+f"(d[OFF + 80]), "+f"(d[OFF + 81]), "+f"(d[OFF + 82]), "+f"(d[OFF + 83]),
        "+f"(d[OFF + 84]), "+f"(d[OFF + 85]), "+f"(d[OFF + 86]), "+f"(d[OFF + 87]), "+f"(d[OFF + 88]), "+f"(d[OFF + 89]),
        "+f"(d[OFF + 90]), "+f"(d[OFF + 91]), "+f"(d[OFF + 92]), "+f"(d[OFF + 93]), "+f"(d[OFF + 94]), "+f"(d[OFF + 95])
      : "l"(desc_a), "l"(desc_b), "r"(scale_d));
}

template <int OFF, int NN>
__device__ __forceinline__ void wg_m192tz(float (&d)[NN], uint64_t desc_a, uint64_t desc_b, int scale_d) {
  asm volatile(
      "{\n.reg .pred p;\nsetp.ne.b32 p, %98, 0;\n"
      "wgmma.mma_async.sync.aligned.m64n192k16.f32.bf16.bf16 "
      "{%0,%1,%2,%3,%4,%5,%6,%7,%8,%9,%10,%11,%12,%13,%14,%15,"
      "%16,%17,%18,%19,%20,%21,%22,%23,%24,%25,%26,%27,%28,%29,%30,%31,"
      "%32,%33,%34,%35,%36,%37,%38,%39,%40,%41,%42,%43,%44,%45,%46,%47,"
      "%48,%49,%50,%51,%52,%53,%54,%55,%56,%57,%58,%59,%60,%61,%62,%63,"
      "%64,%65,%66,%67,%68,%69,%70,%71,%72,%73,%74,%75,%76,%77,%78,%79,"
      "%80,%81,%82,%83,%84,%85,%86,%87,%88,%89,%90,%91,%92,%93,%94,%95}, "
      "%96, %97, p, 1, 1, 0, 1;\n}\n"
      : "=f"(d[OFF + 0]), "=f"(d[OFF + 1]), "=f"(d[OFF + 2]), "=f"(d[OFF + 3]), "=f"(d[OFF + 4]), "=f"(d[OFF + 5]),
        "=f"(d[OFF + 6]), "=f"(d[OFF + 7]), "=f"(d[OFF + 8]), "=f"(d[OFF + 9]), "=f"(d[OFF + 10]), "=f"(d[OFF + 11]),
        "=f"(d[OFF + 12]), "=f"(d[OFF + 13]), "=f"(d[OFF + 14]), "=f"(d[OFF + 15]), "=f"(d[OFF + 16]), "=f"(d[OFF + 17]),
        "=f"(d[OFF + 18]), "=f"(d[OFF + 19]), "=f"(d[OFF + 20]), "=f"(d[OFF + 21]), "=f"(d[OFF + 22]), "=f"(d[OFF + 23]),
        "=f"(d[OFF + 24]), "=f"(d[OFF + 25]), "=f"(d[OFF + 26]), "=f"(d[OFF + 27]), "=f"(d[OFF + 28]), "=f"(d[OFF + 29]),
        "=f"(d[OFF + 30]), "=f"(d[OFF + 31]), "=f"(d[OFF + 32]), "=f"(d[OFF + 33]), "=f"(d[OFF + 34]), "=f"(d[OFF + 35]),
        "=f"(d[OFF + 36]), "=f"(d[OFF + 37]), "=f"(d[OFF + 38]), "=f"(d[OFF + 39]), "=f"(d[OFF + 40]), "=f"(d[OFF + 41]),
        "=f"(d[OFF + 42]), "=f"(d[OFF + 43]), "=f"(d[OFF + 44]), "=f"(d[OFF + 45]), "=f"(d[OFF + 46]), "=f"(d[OFF + 47]),
        "=f"(d[OFF + 48]), "=f"(d[OFF + 49]), "=f"(d[OFF + 50]), "=f"(d[OFF + 51]), "=f"(d[OFF + 52]), "=f"(d[OFF + 53]),
        "=f"(d[OFF + 54]), "=f"(d[OFF + 55]), "=f"(d[OFF + 56]), "=f"(d[OFF + 57]), "=f"(d[OFF + 58]), "=f"(d[OFF + 59]),
        "=f"(d[OFF + 60]), "=f"(d[OFF + 61]), "=f"(d[OFF + 62]), "=f"(d[OFF + 63]), "=f"(d[OFF + 64]), "=f"(d[OFF + 65]),
        "=f"(d[OFF + 66]), "=f"(d[OFF + 67]), "=f"(d[OFF + 68]), "=f"(d[OFF + 69]), "=f"(d[OFF + 70]), "=f"(d[OFF + 71]),
        "=f"(d[OFF + 72]), "=f"(d[OFF + 73]), "=f"(d[OFF + 74]), "=f"(d[OFF + 75]), "=f"(d[OFF + 76]), "=f"(d[OFF + 77]),
        "=f"(d[OFF + 78]), "=f"(d[OFF + 79]), "=f"(d[OFF + 80]), "=f"(d[OFF + 81]), "=f"(d[OFF + 82]), "=f"(d[OFF + 83]),
        "=f"(d[OFF + 84]), "=f"(d[OFF + 85]), "=f"(d[OFF + 86]), "=f"(d[OFF + 87]), "=f"(d[OFF + 88]), "=f"(d[OFF + 89]),
        "=f"(d[OFF + 90]), "=f"(d[OFF + 91]), "=f"(d[OFF + 92]), "=f"(d[OFF + 93]), "=f"(d[OFF + 94]), "=f"(d[OFF + 95])
      : "l"(desc_a), "l"(desc_b), "r"(scale_d));
}

template <int OFF, int NN>
__device__ __forceinline__ void wg_d96(float (&d)[NN], uint32_t a0, uint32_t a1, uint32_t a2, uint32_t a3,
                                       uint64_t desc_b, int scale_d) {
  asm volatile(
      "{\n.reg .pred p;\nsetp.ne.b32 p, %53, 0;\n"
      "wgmma.mma_async.sync.aligned.m64n96k16.f32.bf16.bf16 "
      "{%0,%1,%2,%3,%4,%5,%6,%7,%8,%9,%10,%11,%12,%13,%14,%15,"
      "%16,%17,%18,%19,%20,%21,%22,%23,%24,%25,%26,%27,%28,%29,%30,%31,"
      "%32,%33,%34,%35,%36,%37,%38,%39,%40,%41,%42,%43,%44,%45,%46,%47}, "
      "{%48,%49,%50,%51}, %52, p, 1, 1, 0;\n}\n"
      : "+f"(d[OFF + 0]), "+f"(d[OFF + 1]), "+f"(d[OFF + 2]), "+f"(d[OFF + 3]), "+f"(d[OFF + 4]), "+f"(d[OFF + 5]),
        "+f"(d[OFF + 6]), "+f"(d[OFF + 7]), "+f"(d[OFF + 8]), "+f"(d[OFF + 9]), "+f"(d[OFF + 10]), "+f"(d[OFF + 11]),
        "+f"(d[OFF + 12]), "+f"(d[OFF + 13]), "+f"(d[OFF + 14]), "+f"(d[OFF + 15]), "+f"(d[OFF + 16]), "+f"(d[OFF + 17]),
        "+f"(d[OFF + 18]), "+f"(d[OFF + 19]), "+f"(d[OFF + 20]), "+f"(d[OFF + 21]), "+f"(d[OFF + 22]), "+f"(d[OFF + 23]),
        "+f"(d[OFF + 24]), "+f"(d[OFF + 25]), "+f"(d[OFF + 26]), "+f"(d[OFF + 27]), "+f"(d[OFF + 28]), "+f"(d[OFF + 29]),
        "+f"(d[OFF + 30]), "+f"(d[OFF + 31]), "+f"(d[OFF + 32]), "+f"(d[OFF + 33]), "+f"(d[OFF + 34]), "+f"(d[OFF + 35]),
        "+f"(d[OFF + 36]), "+f"(d[OFF + 37]), "+f"(d[OFF + 38]), "+f"(d[OFF + 39]), "+f"(d[OFF + 40]), "+f"(d[OFF + 41]),
        "+f"(d[OFF + 42]), "+f"(d[OFF + 43]), "+f"(d[OFF + 44]), "+f"(d[OFF + 45]), "+f"(d[OFF + 46]), "+f"(d[OFF + 47])
      : "r"(a0), "r"(a1), "r"(a2), "r"(a3), "l"(desc_b), "r"(scale_d));
}

template <int OFF, int NN>
__device__ __forceinline__ void wg_d96z(float (&d)[NN], uint32_t a0, uint32_t a1, uint32_t a2, uint32_t a3,
                                       uint64_t desc_b, int scale_d) {
  asm volatile(
      "{\n.reg .pred p;\nsetp.ne.b32 p, %53, 0;\n"
      "wgmma.mma_async.sync.aligned.m64n96k16.f32.bf16.bf16 "
      "{%0,%1,%2,%3,%4,%5,%6,%7,%8,%9,%10,%11,%12,%13,%14,%15,"
      "%16,%17,%18,%19,%20,%21,%22,%23,%24,%25,%26,%27,%28,%29,%30,%31,"
      "%32,%33,%34,%35,%36,%37,%38,%39,%40,%41,%42,%43,%44,%45,%46,%47}, "
      "{%48,%49,%50,%51}, %52, p, 1, 1, 0;\n}\n"
      : "=f"(d[OFF + 0]), "=f"(d[OFF + 1]), "=f"(d[OFF + 2]), "=f"(d[OFF + 3]), "=f"(d[OFF + 4]), "=f"(d[OFF + 5]),
        "=f"(d[OFF + 6]), "=f"(d[OFF + 7]), "=f"(d[OFF + 8]), "=f"(d[OFF + 9]), "=f"(d[OFF + 10]), "=f"(d[OFF + 11]),
        "=f"(d[OFF + 12]), "=f"(d[OFF + 13]), "=f"(d[OFF + 14]), "=f"(d[OFF + 15]), "=f"(d[OFF + 16]), "=f"(d[OFF + 17]),
        "=f"(d[OFF + 18]), "=f"(d[OFF + 19]), "=f"(d[OFF + 20]), "=f"(d[OFF + 21]), "=f"(d[OFF + 22]), "=f"(d[OFF + 23]),
        "=f"(d[OFF + 24]), "=f"(d[OFF + 25]), "=f"(d[OFF + 26]), "=f"(d[OFF + 27]), "=f"(d[OFF + 28]), "=f"(d[OFF + 29]),
        "=f"(d[OFF + 30]), "=f"(d[OFF + 31]), "=f"(d[OFF + 32]), "=f"(d[OFF + 33]), "=f"(d[OFF + 34]), "=f"(d[OFF + 35]),
        "=f"(d[OFF + 36]), "=f"(d[OFF + 37]), "=f"(d[OFF + 38]), "=f"(d[OFF + 39]), "=f"(d[OFF + 40]), "=f"(d[OFF + 41]),
        "=f"(d[OFF + 42]), "=f"(d[OFF + 43]), "=f"(d[OFF + 44]), "=f"(d[OFF + 45]), "=f"(d[OFF + 46]), "=f"(d[OFF + 47])
      : "r"(a0), "r"(a1), "r"(a2), "r"(a3), "l"(desc_b), "r"(scale_d));
}

template <int OFF, int NN>
__device__ __forceinline__ void wg_s104(float (&d)[NN], uint32_t a0, uint32_t a1, uint32_t a2, uint32_t a3,
                                       uint64_t desc_b, int scale_d, uint32_t meta) {
  asm volatile(
      "{\n.reg .pred p;\nsetp.ne.b32 p, %57, 0;\n"
      "wgmma.mma_async.sp.sync.aligned.m64n104k32.f32.bf16.bf16 "
      "{%0,%1,%2,%3,%4,%5,%6,%7,%8,%9,%10,%11,%12,%13,%14,%15,"
      "%16,%17,%18,%19,%20,%21,%22,%23,%24,%25,%26,%27,%28,%29,%30,%31,"
      "%32,%33,%34,%35,%36,%37,%38,%39,%40,%41,%42,%43,%44,%45,%46,%47,"
      "%48,%49,%50,%51}, "
      "{%52,%53,%54,%55}, %56, %58, 0, p, 1, 1, 0;\n}\n"
      : "+f"(d[OFF + 0]), "+f"(d[OFF + 1]), "+f"(d[OFF + 2]), "+f"(d[OFF + 3]), "+f"(d[OFF + 4]), "+f"(d[OFF + 5]),
        "+f"(d[OFF + 6]), "+f"(d[OFF + 7]), "+f"(d[OFF + 8]), "+f"(d[OFF + 9]), "+f"(d[OFF + 10]), "+f"(d[OFF + 11]),
        "+f"(d[OFF + 12]), "+f"(d[OFF + 13]), "+f"(d[OFF + 14]), "+f"(d[OFF + 15]), "+f"(d[OFF + 16]), "+f"(d[OFF + 17]),
        "+f"(d[OFF + 18]), "+f"(d[OFF + 19]), "+f"(d[OFF + 20]), "+f"(d[OFF + 21]), "+f"(d[OFF + 22]), "+f"(d[OFF + 23]),
        "+f"(d[OFF + 24]), "+f"(d[OFF + 25]), "+f"(d[OFF + 26]), "+f"(d[OFF + 27]), "+f"(d[OFF + 28]), "+f"(d[OFF + 29]),
        "+f"(d[OFF + 30]), "+f"(d[OFF + 31]), "+f"(d[OFF + 32]), "+f"(d[OFF + 33]), "+f"(d[OFF + 34]), "+f"(d[OFF + 35]),
        "+f"(d[OFF + 36]), "+f"(d[OFF + 37]), "+f"(d[OFF + 38]), "+f"(d[OFF + 39]), "+f"(d[OFF + 40]), "+f"(d[OFF + 41]),
        "+f"(d[OFF + 42]), "+f"(d[OFF + 43]), "+f"(d[OFF + 44]), "+f"(d[OFF + 45]), "+f"(d[OFF + 46]), "+f"(d[OFF + 47]),
        "+f"(d[OFF + 48]), "+f"(d[OFF + 49]), "+f"(d[OFF + 50]), "+f"(d[OFF + 51])
      : "r"(a0), "r"(a1), "r"(a2), "r"(a3), "l"(desc_b), "r"(scale_d), "r"(meta));
}

template <int OFF, int NN>
__device__ __forceinline__ void wg_s104z(float (&d)[NN], uint32_t a0, uint32_t a1, uint32_t a2, uint32_t a3,
                                       uint64_t desc_b, int scale_d, uint32_t meta) {
  asm volatile(
      "{\n.reg .pred p;\nsetp.ne.b32 p, %57, 0;\n"
      "wgmma.mma_async.sp.sync.aligned.m64n104k32.f32.bf16.bf16 "
      "{%0,%1,%2,%3,%4,%5,%6,%7,%8,%9,%10,%11,%12,%13,%14,%15,"
      "%16,%17,%18,%19,%20,%21,%22,%23,%24,%25,%26,%27,%28,%29,%30,%31,"
      "%32,%33,%34,%35,%36,%37,%38,%39,%40,%41,%42,%43,%44,%45,%46,%47,"
      "%48,%49,%50,%51}, "
      "{%52,%53,%54,%55}, %56, %58, 0, p, 1, 1, 0;\n}\n"
      : "=f"(d[OFF + 0]), "=f"(d[OFF + 1]), "=f"(d[OFF + 2]), "=f"(d[OFF + 3]), "=f"(d[OFF + 4]), "=f"(d[OFF + 5]),
        "=f"(d[OFF + 6]), "=f"(d[OFF + 7]), "=f"(d[OFF + 8]), "=f"(d[OFF + 9]), "=f"(d[OFF + 10]), "=f"(d[OFF + 11]),
        "=f"(d[OFF + 12]), "=f"(d[OFF + 13]), "=f"(d[OFF + 14]), "=f"(d[OFF + 15]), "=f"(d[OFF + 16]), "=f"(d[OFF + 17]),
        "=f"(d[OFF + 18]), "=f"(d[OFF + 19]), "=f"(d[OFF + 20]), "=f"(d[OFF + 21]), "=f"(d[OFF + 22]), "=f"(d[OFF + 23]),
        "=f"(d[OFF + 24]), "=f"(d[OFF + 25]), "=f"(d[OFF + 26]), "=f"(d[OFF + 27]), "=f"(d[OFF + 28]), "=f"(d[OFF + 29]),
        "=f"(d[OFF + 30]), "=f"(d[OFF + 31]), "=f"(d[OFF + 32]), "=f"(d[OFF + 33]), "=f"(d[OFF + 34]), "=f"(d[OFF + 35]),
        "=f"(d[OFF + 36]), "=f"(d[OFF + 37]), "=f"(d[OFF + 38]), "=f"(d[OFF + 39]), "=f"(d[OFF + 40]), "=f"(d[OFF + 41]),
        "=f"(d[OFF + 42]), "=f"(d[OFF + 43]), "=f"(d[OFF + 44]), "=f"(d[OFF + 45]), "=f"(d[OFF + 46]), "=f"(d[OFF + 47]),
        "=f"(d[OFF + 48]), "=f"(d[OFF + 49]), "=f"(d[OFF + 50]), "=f"(d[OFF + 51])
      : "r"(a0), "r"(a1), "r"(a2), "r"(a3), "l"(desc_b), "r"(scale_d), "r"(meta));
}

template <int OFF, int NN>
__device__ __forceinline__ void wg_s48(float (&d)[NN], uint32_t a0, uint32_t a1, uint32_t a2, uint32_t a3,
                                       uint64_t desc_b, int scale_d, uint32_t meta) {
  asm volatile(
      "{\n.reg .pred p;\nsetp.ne.b32 p, %29, 0;\n"
      "wgmma.mma_async.sp.sync.aligned.m64n48k32.f32.bf16.bf16 "
      "{%0,%1,%2,%3,%4,%5,%6,%7,%8,%9,%10,%11,%12,%13,%14,%15,"
      "%16,%17,%18,%19,%20,%21,%22,%23}, "
      "{%24,%25,%26,%27}, %28, %30, 0, p, 1, 1, 0;\n}\n"
      : "+f"(d[OFF + 0]), "+f"(d[OFF + 1]), "+f"(d[OFF + 2]), "+f"(d[OFF + 3]), "+f"(d[OFF + 4]), "+f"(d[OFF + 5]),
        "+f"(d[OFF + 6]), "+f"(d[OFF + 7]), "+f"(d[OFF + 8]), "+f"(d[OFF + 9]), "+f"(d[OFF + 10]), "+f"(d[OFF + 11]),
        "+f"(d[OFF + 12]), "+f"(d[OFF + 13]), "+f"(d[OFF + 14]), "+f"(d[OFF + 15]), "+f"(d[OFF + 16]), "+f"(d[OFF + 17]),
        "+f"(d[OFF + 18]), "+f"(d[OFF + 19]), "+f"(d[OFF + 20]), "+f"(d[OFF + 21]), "+f"(d[OFF + 22]), "+f"(d[OFF + 23])
      : "r"(a0), "r"(a1), "r"(a2), "r"(a3), "l"(desc_b), "r"(scale_d), "r"(meta));
}

template <int OFF, int NN>
__device__ __forceinline__ void wg_s48z(float (&d)[NN], uint32_t a0, uint32_t a1, uint32_t a2, uint32_t a3,
                                       uint64_t desc_b, int scale_d, uint32_t meta) {
  asm volatile(
      "{\n.reg .pred p;\nsetp.ne.b32 p, %29, 0;\n"
      "wgmma.mma_async.sp.sync.aligned.m64n48k32.f32.bf16.bf16 "
      "{%0,%1,%2,%3,%4,%5,%6,%7,%8,%9,%10,%11,%12,%13,%14,%15,"
      "%16,%17,%18,%19,%20,%21,%22,%23}, "
      "{%24,%25,%26,%27}, %28, %30, 0, p, 1, 1, 0;\n}\n"
      : "=f"(d[OFF + 0]), "=f"(d[OFF + 1]), "=f"(d[OFF + 2]), "=f"(d[OFF + 3]), "=f"(d[OFF + 4]), "=f"(d[OFF + 5]),
        "=f"(d[OFF + 6]), "=f"(d[OFF + 7]), "=f"(d[OFF + 8]), "=f"(d[OFF + 9]), "=f"(d[OFF + 10]), "=f"(d[OFF + 11]),
        "=f"(d[OFF + 12]), "=f"(d[OFF + 13]), "=f"(d[OFF + 14]), "=f"(d[OFF + 15]), "=f"(d[OFF + 16]), "=f"(d[OFF + 17]),
        "=f"(d[OFF + 18]), "=f"(d[OFF + 19]), "=f"(d[OFF + 20]), "=f"(d[OFF + 21]), "=f"(d[OFF + 22]), "=f"(d[OFF + 23])
      : "r"(a0), "r"(a1), "r"(a2), "r"(a3), "l"(desc_b), "r"(scale_d), "r"(meta));
}

template <int OFF, int NN>
__device__ __forceinline__ void wg_s56(float (&d)[NN], uint32_t a0, uint32_t a1, uint32_t a2, uint32_t a3,
                                       uint64_t desc_b, int scale_d, uint32_t meta) {
  asm volatile(
      "{\n.reg .pred p;\nsetp.ne.b32 p, %33, 0;\n"
      "wgmma.mma_async.sp.sync.aligned.m64n56k32.f32.bf16.bf16 "
      "{%0,%1,%2,%3,%4,%5,%6,%7,%8,%9,%10,%11,%12,%13,%14,%15,"
      "%16,%17,%18,%19,%20,%21,%22,%23,%24,%25,%26,%27}, "
      "{%28,%29,%30,%31}, %32, %34, 0, p, 1, 1, 0;\n}\n"
      : "+f"(d[OFF + 0]), "+f"(d[OFF + 1]), "+f"(d[OFF + 2]), "+f"(d[OFF + 3]), "+f"(d[OFF + 4]), "+f"(d[OFF + 5]),
        "+f"(d[OFF + 6]), "+f"(d[OFF + 7]), "+f"(d[OFF + 8]), "+f"(d[OFF + 9]), "+f"(d[OFF + 10]), "+f"(d[OFF + 11]),
        "+f"(d[OFF + 12]), "+f"(d[OFF + 13]), "+f"(d[OFF + 14]), "+f"(d[OFF + 15]), "+f"(d[OFF + 16]), "+f"(d[OFF + 17]),
        "+f"(d[OFF + 18]), "+f"(d[OFF + 19]), "+f"(d[OFF + 20]), "+f"(d[OFF + 21]), "+f"(d[OFF + 22]), "+f"(d[OFF + 23]),
        "+f"(d[OFF + 24]), "+f"(d[OFF + 25]), "+f"(d[OFF + 26]), "+f"(d[OFF + 27])
      : "r"(a0), "r"(a1), "r"(a2), "r"(a3), "l"(desc_b), "r"(scale_d), "r"(meta));
}

template <int OFF, int NN>
__device__ __forceinline__ void wg_s56z(float (&d)[NN], uint32_t a0, uint32_t a1, uint32_t a2, uint32_t a3,
                                       uint64_t desc_b, int scale_d, uint32_t meta) {
  asm volatile(
      "{\n.reg .pred p;\nsetp.ne.b32 p, %33, 0;\n"
      "wgmma.mma_async.sp.sync.aligned.m64n56k32.f32.bf16.bf16 "
      "{%0,%1,%2,%3,%4,%5,%6,%7,%8,%9,%10,%11,%12,%13,%14,%15,"
      "%16,%17,%18,%19,%20,%21,%22,%23,%24,%25,%26,%27}, "
      "{%28,%29,%30,%31}, %32, %34, 0, p, 1, 1, 0;\n}\n"
      : "=f"(d[OFF + 0]), "=f"(d[OFF + 1]), "=f"(d[OFF + 2]), "=f"(d[OFF + 3]), "=f"(d[OFF + 4]), "=f"(d[OFF + 5]),
        "=f"(d[OFF + 6]), "=f"(d[OFF + 7]), "=f"(d[OFF + 8]), "=f"(d[OFF + 9]), "=f"(d[OFF + 10]), "=f"(d[OFF + 11]),
        "=f"(d[OFF + 12]), "=f"(d[OFF + 13]), "=f"(d[OFF + 14]), "=f"(d[OFF + 15]), "=f"(d[OFF + 16]), "=f"(d[OFF + 17]),
        "=f"(d[OFF + 18]), "=f"(d[OFF + 19]), "=f"(d[OFF + 20]), "=f"(d[OFF + 21]), "=f"(d[OFF + 22]), "=f"(d[OFF + 23]),
        "=f"(d[OFF + 24]), "=f"(d[OFF + 25]), "=f"(d[OFF + 26]), "=f"(d[OFF + 27])
      : "r"(a0), "r"(a1), "r"(a2), "r"(a3), "l"(desc_b), "r"(scale_d), "r"(meta));
}

template <int OFF, int NN>
__device__ __forceinline__ void wg_s64t(float (&d)[NN], uint32_t a0, uint32_t a1, uint32_t a2, uint32_t a3,
                                       uint64_t desc_b, int scale_d, uint32_t meta) {
  asm volatile(
      "{\n.reg .pred p;\nsetp.ne.b32 p, %37, 0;\n"
      "wgmma.mma_async.sp.sync.aligned.m64n64k32.f32.bf16.bf16 "
      "{%0,%1,%2,%3,%4,%5,%6,%7,%8,%9,%10,%11,%12,%13,%14,%15,"
      "%16,%17,%18,%19,%20,%21,%22,%23,%24,%25,%26,%27,%28,%29,%30,%31}, "
      "{%32,%33,%34,%35}, %36, %38, 0, p, 1, 1, 1;\n}\n"
      : "+f"(d[OFF + 0]), "+f"(d[OFF + 1]), "+f"(d[OFF + 2]), "+f"(d[OFF + 3]), "+f"(d[OFF + 4]), "+f"(d[OFF + 5]),
        "+f"(d[OFF + 6]), "+f"(d[OFF + 7]), "+f"(d[OFF + 8]), "+f"(d[OFF + 9]), "+f"(d[OFF + 10]), "+f"(d[OFF + 11]),
        "+f"(d[OFF + 12]), "+f"(d[OFF + 13]), "+f"(d[OFF + 14]), "+f"(d[OFF + 15]), "+f"(d[OFF + 16]), "+f"(d[OFF + 17]),
        "+f"(d[OFF + 18]), "+f"(d[OFF + 19]), "+f"(d[OFF + 20]), "+f"(d[OFF + 21]), "+f"(d[OFF + 22]), "+f"(d[OFF + 23]),
        "+f"(d[OFF + 24]), "+f"(d[OFF + 25]), "+f"(d[OFF + 26]), "+f"(d[OFF + 27]), "+f"(d[OFF + 28]), "+f"(d[OFF + 29]),
        "+f"(d[OFF + 30]), "+f"(d[OFF + 31])
      : "r"(a0), "r"(a1), "r"(a2), "r"(a3), "l"(desc_b), "r"(scale_d), "r"(meta));
}

template <int OFF, int NN>
__device__ __forceinline__ void wg_s64t1(float (&d)[NN], uint32_t a0, uint32_t a1, uint32_t a2, uint32_t a3,
                                       uint64_t desc_b, int scale_d, uint32_t meta) {
  asm volatile(
      "{\n.reg .pred p;\nsetp.ne.b32 p, %37, 0;\n"
      "wgmma.mma_async.sp.sync.aligned.m64n64k32.f32.bf16.bf16 "
      "{%0,%1,%2,%3,%4,%5,%6,%7,%8,%9,%10,%11,%12,%13,%14,%15,"
      "%16,%17,%18,%19,%20,%21,%22,%23,%24,%25,%26,%27,%28,%29,%30,%31}, "
      "{%32,%33,%34,%35}, %36, %38, 1, p, 1, 1, 1;\n}\n"
      : "+f"(d[OFF + 0]), "+f"(d[OFF + 1]), "+f"(d[OFF + 2]), "+f"(d[OFF + 3]), "+f"(d[OFF + 4]), "+f"(d[OFF + 5]),
        "+f"(d[OFF + 6]), "+f"(d[OFF + 7]), "+f"(d[OFF + 8]), "+f"(d[OFF + 9]), "+f"(d[OFF + 10]), "+f"(d[OFF + 11]),
        "+f"(d[OFF + 12]), "+f"(d[OFF + 13]), "+f"(d[OFF + 14]), "+f"(d[OFF + 15]), "+f"(d[OFF + 16]), "+f"(d[OFF + 17]),
        "+f"(d[OFF + 18]), "+f"(d[OFF + 19]), "+f"(d[OFF + 20]), "+f"(d[OFF + 21]), "+f"(d[OFF + 22]), "+f"(d[OFF + 23]),
        "+f"(d[OFF + 24]), "+f"(d[OFF + 25]), "+f"(d[OFF + 26]), "+f"(d[OFF + 27]), "+f"(d[OFF + 28]), "+f"(d[OFF + 29]),
        "+f"(d[OFF + 30]), "+f"(d[OFF + 31])
      : "r"(a0), "r"(a1), "r"(a2), "r"(a3), "l"(desc_b), "r"(scale_d), "r"(meta));
}

template <int OFF, int NN>
__device__ __forceinline__ void wg_s64tz(float (&d)[NN], uint32_t a0, uint32_t a1, uint32_t a2, uint32_t a3,
                                       uint64_t desc_b, int scale_d, uint32_t meta) {
  asm volatile(
      "{\n.reg .pred p;\nsetp.ne.b32 p, %37, 0;\n"
      "wgmma.mma_async.sp.sync.aligned.m64n64k32.f32.bf16.bf16 "
      "{%0,%1,%2,%3,%4,%5,%6,%7,%8,%9,%10,%11,%12,%13,%14,%15,"
      "%16,%17,%18,%19,%20,%21,%22,%23,%24,%25,%26,%27,%28,%29,%30,%31}, "
      "{%32,%33,%34,%35}, %36, %38, 0, p, 1, 1, 1;\n}\n"
      : "=f"(d[OFF + 0]), "=f"(d[OFF + 1]), "=f"(d[OFF + 2]), "=f"(d[OFF + 3]), "=f"(d[OFF + 4]), "=f"(d[OFF + 5]),
        "=f"(d[OFF + 6]), "=f"(d[OFF + 7]), "=f"(d[OFF + 8]), "=f"(d[OFF + 9]), "=f"(d[OFF + 10]), "=f"(d[OFF + 11]),
        "=f"(d[OFF + 12]), "=f"(d[OFF + 13]), "=f"(d[OFF + 14]), "=f"(d[OFF + 15]), "=f"(d[OFF + 16]), "=f"(d[OFF + 17]),
        "=f"(d[OFF + 18]), "=f"(d[OFF + 19]), "=f"(d[OFF + 20]), "=f"(d[OFF + 21]), "=f"(d[OFF + 22]), "=f"(d[OFF + 23]),
        "=f"(d[OFF + 24]), "=f"(d[OFF + 25]), "=f"(d[OFF + 26]), "=f"(d[OFF + 27]), "=f"(d[OFF + 28]), "=f"(d[OFF + 29]),
        "=f"(d[OFF + 30]), "=f"(d[OFF + 31])
      : "r"(a0), "r"(a1), "r"(a2), "r"(a3), "l"(desc_b), "r"(scale_d), "r"(meta));
}

__device__ __forceinline__ int g2_inv(int ch) { return 32 * (ch >> 5) + 8 * ((ch >> 1) & 3) + 2 * ((ch >> 3) & 3) + (ch & 1); }
__host__ __device__ __forceinline__ uint32_t wimg_off(int n, int k) {
  return (uint32_t)(k >> 6) * kWChunk + (uint32_t)n * 128 + (uint32_t)((((k & 63) >> 3) ^ (n & 7)) << 4) + (k & 7) * 2;
}
__host__ __device__ constexpr int w2piece(int h, int c) { return c == 2 ? 2 + h : 4 * h + c; }
__device__ __forceinline__ uint32_t w2img_off(int n, int k) { return wimg_off(n % 96, k & 63) + w2piece(n >= 96, k >> 6) * (kWChunk / 2); }
__device__ __forceinline__ int qpix(int par, int t) {
  const int a = 2 * t + 13 * par - 6, b = t + 112 * par;
  return par ? min(a, b) : max(a, b);
}
__device__ __forceinline__ int woff(int par, int i, int r) {
  const int a = 99 * par + 6 - 8 * i;
  return par ? min(r, a) : max(r, a);
}

__device__ __forceinline__ void mma16816(float (&c)[4], uint32_t a0, uint32_t a1, uint32_t a2, uint32_t a3, uint32_t b0,
                                         uint32_t b1) {
  asm volatile(
      "mma.sync.aligned.m16n8k16.row.col.f32.bf16.bf16.f32 {%0,%1,%2,%3}, {%4,%5,%6,%7}, {%8,%9}, {%0,%1,%2,%3};"
      : "+f"(c[0]), "+f"(c[1]), "+f"(c[2]), "+f"(c[3])
      : "r"(a0), "r"(a1), "r"(a2), "r"(a3), "r"(b0), "r"(b1));
}

__device__ __forceinline__ void fold_w1(const int u, const __nv_bfloat16* __restrict__ wqkv, uint8_t* wimg) {
  const int g = (threadIdx.x >> 2) & 7, l = threadIdx.x & 3;
  const int m0 = (u / 12) * 16, s = u % 12;
  uint4 A[12], B[12];
  const __nv_bfloat16* arow = wqkv + (m0 + 4 * (g >> 1) + (g & 1)) * 576 + 192 + 8 * l;
  const __nv_bfloat16* brow = wqkv + (16 * s + 4 * (g >> 1) + (g & 1)) * 576 + 8 * l;
#pragma unroll
  for (int i = 0; i < 12; i++) {
    A[i] = ldg128_nc(arow + (i & 1) * 2 * 576 + 32 * (i >> 1));
    B[i] = ldg128_nc(brow + (i & 1) * 2 * 576 + 32 * (i >> 1));
  }
  sched_fence();
  uint8_t* dst = wimg + wimg_off(m0 + g, 16 * s + 4 * l);
  float acc[4][4];
#pragma unroll
  for (int j = 0; j < 16; j++) acc[j >> 2][j & 3] = 0.f;
#pragma unroll
  for (int i = 0; i < 6; i++) {
    const uint4 &a0 = A[2 * i], &a1 = A[2 * i + 1];
#pragma unroll
    for (int nb = 0; nb < 2; nb++) {
      mma16816(acc[2 * nb], a0.x, a1.x, a0.y, a1.y, B[2 * i + nb].x, B[2 * i + nb].y);
      mma16816(acc[2 * nb + 1], a0.z, a1.z, a0.w, a1.w, B[2 * i + nb].z, B[2 * i + nb].w);
    }
  }
#pragma unroll
  for (int j = 0; j < 2; j++) {
    const uint2 v = make_uint2(pack_bf16((acc[0][2 * j] + acc[1][2 * j]) * kAlpha, (acc[0][2 * j + 1] + acc[1][2 * j + 1]) * kAlpha),
                               pack_bf16((acc[2][2 * j] + acc[3][2 * j]) * kAlpha, (acc[2][2 * j + 1] + acc[3][2 * j + 1]) * kAlpha));
    asm volatile("st.relaxed.gpu.global.v2.u32 [%0], {%1,%2};" ::"l"(dst + j * 1024), "r"(v.x), "r"(v.y) : "memory");
  }
}
__device__ __forceinline__ void fold_w2(const int u, const __nv_bfloat16* __restrict__ wqkv, const __nv_bfloat16* __restrict__ wo,
                                        uint8_t* wimg) {
  const int g = (threadIdx.x >> 2) & 7, l = threadIdx.x & 3;
  const int m0 = (u / 12) * 32, n0 = (u % 12) * 16;
  uint4 S[12];
  uint32_t L[96];
  const __nv_bfloat16* brow = wqkv + (n0 + 4 * (g >> 1) + (g & 1)) * 576 + 384 + 8 * l;
#pragma unroll
  for (int i = 0; i < 12; i++) S[i] = ldg128_nc(brow + (i & 1) * 2 * 576 + 32 * (i >> 1));
  const __nv_bfloat16* acol = wo + (8 * l) * 192 + m0 + 4 * g;
#pragma unroll
  for (int c = 0; c < 48; c++)
    asm volatile("ld.global.nc.v2.u32 {%0,%1}, [%2];" : "=r"(L[2 * c]), "=r"(L[2 * c + 1]) : "l"(acol + (32 * (c >> 3) + (c & 7)) * 192));
  const uint32_t off = w2_offset();
  sched_fence();
  uint8_t* img = wimg + off;
  float acc[4][4];
#pragma unroll
  for (int j = 0; j < 16; j++) acc[j >> 2][j & 3] = 0.f;
#pragma unroll
  for (int i = 0; i < 6; i++) {
#pragma unroll
    for (int h = 0; h < 2; h++) {
      const uint4 &s0 = S[2 * i], &s1 = S[2 * i + 1];
#pragma unroll
      for (int mt = 0; mt < 2; mt++) {
        const uint32_t* a = L + 16 * i + 8 * h + mt;
        const uint32_t a0 = __byte_perm(a[0], a[2], 0x5410), a1 = __byte_perm(a[0], a[2], 0x7632);
        const uint32_t a2 = __byte_perm(a[4], a[6], 0x5410), a3 = __byte_perm(a[4], a[6], 0x7632);
        mma16816(acc[2 * mt], a0, a1, a2, a3, h ? s0.z : s0.x, h ? s0.w : s0.y);
        mma16816(acc[2 * mt + 1], a0, a1, a2, a3, h ? s1.z : s1.x, h ? s1.w : s1.y);
      }
    }
  }
#pragma unroll
  for (int j = 0; j < 4; j++) {
    const float(&c0)[4] = acc[j & 2];
    const float(&c1)[4] = acc[(j & 2) + 1];
    asm volatile("st.relaxed.gpu.global.v2.u32 [%0], {%1,%2};" ::"l"(img + w2img_off(g2_inv(m0 + 4 * g + j), n0 + 4 * l)),
                 "r"(pack_bf16(c0[2 * (j & 1)], c0[2 * (j & 1) + 1])), "r"(pack_bf16(c1[2 * (j & 1)], c1[2 * (j & 1) + 1])) : "memory");
  }
}

__global__ void __launch_bounds__(256) fold_kernel(const __nv_bfloat16* __restrict__ wqkv,
                                                   const __nv_bfloat16* __restrict__ wo, uint8_t* wimg) {
  const int u = blockIdx.x * 8 + (threadIdx.x >> 5);
  if (u < 144) fold_w1(u, wqkv, wimg);
  else fold_w2(u - 144, wqkv, wo, wimg);
}

struct TileCoord { int pr, pc, I, J, up, kind; };
struct TileTable { uint16_t e[kCtas * 6], g[6][8][2]; };
inline void make_tiles(TileTable& tt) {
  for (int tile = 0; tile < kCtas * 6; tile++) {
    const int b = tile / 6, k = tile - 6 * b;
    const int p = b < 128 ? (tile - 672) >> 1 : b - 80;
    const int strip = b < 112 ? b >> 1 : b >= 128 && k >= 2 ? (b & 1) * 27 + (b & 2) * 14 : p + (p < 26 ? 1 : 3);
    const int pr = strip >= 28, J = (strip - pr * 28) >> 1, pc = strip & 1, up = b < 112 ? b & 1 : pr;
    const int first = b < 112 ? 8 - 2 * pr - up : 13 * pr, step = b < 112 ? k : k & 1;
    const int I = up ? first - step : first + step;
    const int kind = b < 112 ? (J == 13 * pc ? 1 + pc : 0) : I == 13 * pr ? 4 + pr : 3;
    tt.e[tile] = (uint16_t)(I | J << 4 | pr << 8 | pc << 9 | up << 10 | kind << 11);
  }
  for (int kind = 0; kind < 6; kind++)
    for (int j = 0; j < 8; j++) {
      const int w = j >> 1, h = j & 1, e = kind % 3;
      auto off = [e](int t) { return e == 0 ? 2 * t : e == 1 ? t + (t == 7) : t + (t > 0); };
      tt.g[kind][j][0] = (uint16_t)(kind < 3 ? 3 * off(w + 4 * h) : 3 * (kW * off(2 * w) + 8 * h));
      tt.g[kind][j][1] = (uint16_t)(128 * (kind < 3 ? kind > 0 : 1 + off(2 * w + 1) - off(2 * w)));
    }
}
__device__ __forceinline__ int num_tiles() { return blockIdx.x < 128 ? 6 : 4; }
__device__ __forceinline__ TileCoord decode_tile(const TileTable& tt, int tile) {
  const uint32_t e = tt.e[tile];
  return TileCoord{(int)(e >> 8) & 1, (int)(e >> 9) & 1, (int)e & 15, (int)(e >> 4) & 15, (int)(e >> 10) & 1, (int)(e >> 11)};
}
__device__ __forceinline__ int halo_r0(const TileCoord& t) { return 8 * t.I + 6 * t.pr - 6; }
__device__ __forceinline__ int halo_c0(const TileCoord& t) { return min(max(8 * t.J + 6 * t.pc - 6, -3), 102); }

__device__ __forceinline__ uint32_t bar_full(uint32_t bars, int wg, int c) { return bars + (wg * 3 + c) * 8; }
__device__ __forceinline__ uint32_t bar_w1c(uint32_t bars, int c) { return bars + (6 + c) * 8; }
__device__ __forceinline__ uint32_t bar_w2(uint32_t bars) { return bars + 9 * 8; }
__device__ __forceinline__ uint32_t bar_x(uint32_t bars, int j) { return bars + (10 + j) * 8; }
__device__ __forceinline__ uint32_t bar_w1q(uint32_t bars) { return bars + 12 * 8; }
__device__ __forceinline__ uint32_t bar_xf(uint32_t bars) { return bars + 13 * 8; }
__device__ __forceinline__ uint32_t bar_w2m(uint32_t bars) { return bars + 14 * 8; }
__device__ __forceinline__ uint32_t bar_redo(uint32_t bars) { return bars + 15 * 8; }
__device__ __forceinline__ uint32_t bar_wok(uint32_t bars) { return bars + 16 * 8; }
__device__ __forceinline__ uint32_t bar_go(uint32_t bars, int j) { return bars + (17 + j) * 8; }
__device__ __forceinline__ uint32_t bar_raw(uint32_t bars) { return bars + 19 * 8; }
__device__ __forceinline__ uint32_t bar_w2a(uint32_t bars) { return bars + 20 * 8; }
constexpr int kNumBars = 21;

__device__ __forceinline__ uint64_t wdesc(uint64_t d0, int s) { return d0 + (((s >> 2) * kWChunk + (s & 3) * 32) >> 4); }

__device__ __forceinline__ int qrow(int w, int g) { return blockIdx.x < 112 ? g : 2 * w + (g & 1); }
__device__ __forceinline__ int qcol(int w, int g) { return blockIdx.x < 112 ? w : g >> 1; }
__device__ __forceinline__ uint32_t out_slot(int k, int nt) { return k + 1 < nt ? kW2Off + (~k & 1) * 2 * kWChunk : kW1Off + kWChunk; }
__device__ __forceinline__ bool edge_strip() {
  const int s = blockIdx.x >> 1;
  return s == 0 || s == 27 || s == 28 || s == 55;
}
template <int I0, int I1>
__device__ __forceinline__ void store_rows(bool on, __nv_bfloat16* pA, __nv_bfloat16* pB, const uint32_t (&a)[24], const uint32_t (&b)[24]) {
#pragma unroll
  for (int i = 2 * I0; i < 2 * I1; i++) {
    const uint32_t* v = (i & 1 ? b : a) + 4 * (i >> 1);
    asm volatile("{\n.reg .pred p;\nsetp.ne.u32 p, %5, 0;\n@p st.global.v4.u32 [%0], {%1,%2,%3,%4};\n}\n" ::"l"((i & 1 ? pB : pA) + 32 * (i >> 1)),
                 "r"(v[0]), "r"(v[1]), "r"(v[2]), "r"(v[3]), "r"((uint32_t)on) : "memory");
  }
}
template <int I0, int I1>
__device__ __forceinline__ void stage_out(uint32_t sts, int wg, const uint32_t (&a)[24], const uint32_t (&b)[24]) {
  const uint32_t e = sts, o = sts ^ 64;
  const uint32_t ad[4] = {wg ? o + 1024 : e, wg ? e + 2048 : o, wg ? e : o + 1024, wg ? o : e + 2048};
#pragma unroll
  for (int i = I0; i < I1; i++) {
    const uint32_t* v = (i < 6 ? a : b) + 4 * (i % 6);
    asm volatile("st.shared.v4.u32 [%0], {%1,%2,%3,%4};" ::"r"(ad[i % 6 / 3 * 2 + (i % 3 == 1)] + (i % 3 == 2) * 1024 + (i / 6) * 12288),
                 "r"(v[0]), "r"(v[1]), "r"(v[2]), "r"(v[3]) : "memory");
  }
}
__device__ __forceinline__ uint32_t now_ns() {
  uint32_t t;
  asm volatile("mov.u32 %0, %globaltimer_lo;" : "=r"(t)::"memory");
  return t;
}
__device__ __forceinline__ void wait_clock(uint32_t t_start, uint32_t t) {
  while (now_ns() - t_start < t) { }
}
#define NAT_PRED(f, m) ".reg .pred p;\n.reg .b32 t;\nand.b32 t, " f ", " m ";\nsetp.ne.u32 p, t, 0;\n"
constexpr uint32_t kHiV = 1, kHiU = 8, kColB = 0x20, kInV = 0x100, kInU = 0x1000, kColA = 0x10000;
template <uint32_t M>
__device__ __forceinline__ float pick(const float* a, const float* b, uint32_t f) {
  float d;
  asm("{\n" NAT_PRED("%5", "%6") "add.f32 %0, %1, %2;\n@p add.f32 %0, %3, %4;\n}\n"
      : "=&f"(d) : "f"(a[0]), "f"(a[2]), "f"(b[0]), "f"(b[2]), "r"(f), "n"(M));
  return d;
}
template <uint32_t M>
__device__ __forceinline__ float sel(float a, float b, uint32_t f) {
  float d;
  asm("{\n" NAT_PRED("%3", "%4") "selp.f32 %0, %1, %2, p;\n}\n" : "=f"(d) : "f"(a), "f"(b), "r"(f), "n"(M));
  return d;
}
template <uint32_t M>
__device__ __forceinline__ void max_if(float& m, float v, uint32_t f) {
  asm("{\n" NAT_PRED("%2", "%3") "@p max.f32 %0, %0, %1;\n}\n" : "+f"(m) : "f"(v), "r"(f), "n"(M));
}
template <uint32_t M>
__device__ __forceinline__ void add_if(float& m, float v, uint32_t f) {
  asm("{\n" NAT_PRED("%2", "%3") "@p add.f32 %0, %0, %1;\n}\n" : "+f"(m) : "f"(v), "r"(f), "n"(M));
}
__device__ __forceinline__ void pick_v(const float* a, float* v, uint32_t f) {
  v[0] = pick<kHiV>(a, a + 16, f), v[1] = pick<kHiV>(a + 1, a + 17, f);
  v[2] = pick<kHiV * 2>(a + 4, a + 20, f), v[3] = pick<kHiV * 2>(a + 5, a + 21, f);
  v[4] = pick<kHiV * 4>(a + 8, a + 24, f), v[5] = pick<kHiV * 4>(a + 9, a + 25, f);
  v[6] = a[12] + a[14], v[7] = a[13] + a[15];
}
__device__ __forceinline__ void pick_u(const float* a, float* v, uint32_t f) {
#pragma unroll
  for (int c = 0; c < 3; c++) v[2 * c] = pick<kHiU>(a + 4 * c, a + 4 * c + 12, f), v[2 * c + 1] = pick<kHiU * 2>(a + 4 * c + 1, a + 4 * c + 13, f);
}
__device__ __forceinline__ uint32_t sign_bytes(uint32_t v, uint32_t sel) {
  uint32_t d;
  asm("prmt.b32 %0, %1, %1, %2;" : "=r"(d) : "r"(v), "r"(sel));
  return d;
}
__device__ __forceinline__ float own_max(const float (&v)[14], uint32_t f) {
  float m = sel<kInV>(fmaxf(v[0], v[1]), -INFINITY, f), m2 = sel<kInV * 2>(fmaxf(v[2], v[3]), -INFINITY, f);
  max_if<kInV * 4>(m, fmaxf(v[4], v[5]), f);
  max_if<kInV * 8>(m2, fmaxf(v[6], v[7]), f);
  max_if<kInU>(m, fmaxf(fmaxf(v[8], v[10]), v[12]), f);
  max_if<kInU * 2>(m2, fmaxf(fmaxf(v[9], v[11]), v[13]), f);
  return fmaxf(m, m2);
}
__device__ __forceinline__ float quad_max(float m) {
  const float a = __shfl_xor_sync(0xffffffffu, m, 1), b = __shfl_xor_sync(0xffffffffu, m, 2), c = __shfl_xor_sync(0xffffffffu, m, 3);
  return fmaxf(fmaxf(m, a), fmaxf(b, c));
}
__device__ __forceinline__ float row_rcp(const float (&v)[14], uint32_t f) {
  float s = sel<kInV>(v[0] + v[1], 0.f, f), s2 = sel<kInV * 2>(v[2] + v[3], 0.f, f);
  add_if<kInV * 4>(s, v[4] + v[5], f);
  add_if<kInV * 8>(s2, v[6] + v[7], f);
  add_if<kInU>(s, v[8] + v[10] + v[12], f);
  add_if<kInU * 2>(s2, v[9] + v[11] + v[13], f);
  s += s2;
  const float a = __shfl_xor_sync(0xffffffffu, s, 1), b = __shfl_xor_sync(0xffffffffu, s, 2), c = __shfl_xor_sync(0xffffffffu, s, 3);
  return rcp_approx((s + a) + (b + c));
}
__device__ __forceinline__ void route(const float (&v)[14], float s, const uint32_t (&rt)[9], uint32_t (&p)[14]) {
#pragma unroll
  for (int i = 0; i < 7; i++) {
    const uint32_t u = pack_bf16(v[2 * i] * s, v[2 * i + 1] * s);
    if (i < 4) p[i] = u & rt[i];
    if (i < 3) p[i + 4] = u & rt[i + 4];
    if (i >= 4) {
      p[i + 3] = u & rt[7];
      p[i + 6] = u & rt[8];
    }
  }
}

template <int C, int T0 = 0, int T1 = 7>
__device__ __forceinline__ void pv_chunk(float (&z)[32], const uint32_t (&pa)[14], const uint32_t (&pb)[14],
                                         const uint32_t (&meta)[4], uint64_t dV) {
#pragma unroll
  for (int t = T0; t < T1; t++) {
    if (t & 1)
      wg_s64t1<0, 32>(z, pa[2 * t], pb[2 * t], pa[2 * t + 1], pb[2 * t + 1], dV + ((2 * C * kChunkBytes + t * 2048) >> 4), 1,
                      meta[t >> 1]);
    else if (t > 0)
      wg_s64t<0, 32>(z, pa[2 * t], pb[2 * t], pa[2 * t + 1], pb[2 * t + 1], dV + ((2 * C * kChunkBytes + t * 2048) >> 4), 1,
                     meta[t >> 1]);
    else
      wg_s64tz<0, 32>(z, pa[0], pb[0], pa[1], pb[1], dV + ((2 * C * kChunkBytes) >> 4), 0, meta[0]);
  }
}
template <int C>
__device__ __forceinline__ void pack_z(const float (&z)[32], uint32_t (&za)[24], uint32_t (&zb)[24]) {
#pragma unroll
  for (int j = 0; j < 8; j++) {
    za[8 * C + j] = pack_bf16(z[4 * j], z[4 * j + 1]);
    zb[8 * C + j] = pack_bf16(z[4 * j + 2], z[4 * j + 3]);
  }
}

template <int H>
__device__ __forceinline__ void pack_out(const float (&ac)[48], uint32_t (&oa)[24], uint32_t (&ob)[24]) {
#pragma unroll
  for (int j = 0; j < 12; j++) {
    oa[12 * H + j] = pack_bf16(ac[4 * j], ac[4 * j + 1]);
    ob[12 * H + j] = pack_bf16(ac[4 * j + 2], ac[4 * j + 3]);
  }
}
struct Maps { CUtensorMap v6, v2, v14, u8, px[8], wv, wo; };
__device__ __forceinline__ void tma_prefetch_5d(const CUtensorMap* map, int c0, int c1, int c2, int c3, int c4) {
  asm volatile("cp.async.bulk.prefetch.tensor.5d.L2.global.tile [%0, {%1, %2, %3, %4, %5}];" ::"l"((uint64_t)map), "r"(c0), "r"(c1),
               "r"(c2), "r"(c3), "r"(c4) : "memory");
}
__device__ __forceinline__ int first_line(const TileCoord tc) { return 3 * (qpix(tc.pr, 8 * tc.I) * kW + qpix(tc.pc, 8 * tc.J)); }
template <int MODE, int UNROLL, int N = 8>
__device__ __forceinline__ void move_px(const Maps& tm, const TileTable& tt, uint32_t buf, uint32_t bar, int line, int kind, int i0 = 0) {
#pragma unroll UNROLL
  for (int n = 0; n < N; n++) {
    const int i = i0 + n;
    const int j = MODE == 2 ? 2 * (i & 3) + (i >> 2) : i;
    if (MODE == 2 || (n & 1) == 0 || kind != 0) {
      const CUtensorMap* map = (const CUtensorMap*)((const char*)(tm.px + (MODE & 2) * 2) + tt.g[kind][j][1]);
      const int ln = line + tt.g[kind][j][0];
      if (MODE == 0) tma_load_5d(buf + i * 3072, map, bar, 0, 0, 0, 0, ln);
      if (MODE == 1) tma_prefetch_5d(map, 0, 0, 0, 0, ln);
      if (MODE == 2)
        asm volatile("cp.async.bulk.tensor.5d.global.shared::cta.tile.bulk_group [%0, {%2, %2, %2, %2, %3}], [%1];" ::"l"((uint64_t)map),
                     "r"(buf + i * 3072), "r"(0), "r"(ln) : "memory");
      if (MODE == 2 && NAT_SP < 9) {
        asm volatile("cp.async.bulk.commit_group;" ::: "memory");
        asm volatile("cp.async.bulk.wait_group.read %0;" ::"n"(NAT_SP) : "memory");
      }
    }
  }
  if (MODE == 2) asm volatile("cp.async.bulk.commit_group;" ::: "memory");
}
__device__ __noinline__ bool refetch(uint32_t base, const uint8_t* src, bool gap) {
  constexpr uint32_t bars = 1024 + kBarOff, cnt = bars + 192;
#pragma unroll 1
  for (uint32_t o = 0; o < kWBytes && !gap; o += 2048) {
    uint32_t mx = 0;
#pragma unroll
    for (int i = 0; i < 4; i++) {
      uint4 v;
      asm volatile("ld.shared.v4.u32 {%0,%1,%2,%3}, [%4];" : "=r"(v.x), "=r"(v.y), "=r"(v.z), "=r"(v.w)
                   : "r"(base + o + i * 512 + (threadIdx.x & 31) * 16));
      mx = __vimax3_u32(__vimax3_u32(mx, v.x, v.y), v.z, v.w);
    }
    gap = __any_sync(0xffffffffu, mx == kEmpty);
  }
  uint32_t n;
  asm volatile("ld.shared.u32 %0, [%1];" : "=r"(n) : "r"(cnt) : "memory");
  if (!gap || __any_sync(0xffffffffu, n > (1u << 12))) return false;
  asm volatile("bar.sync 15, 128;" ::: "memory");
  if (threadIdx.x == 0) {
    asm volatile("st.shared.u32 [%0], %1;" ::"r"(cnt), "r"(n + 1) : "memory");
    mbar_arrive_expect_tx(bar_redo(bars), kWBytes);
    bulk_load(base, src, kWBytes, bar_redo(bars));
  }
  __syncwarp();
  mbar_wait(bar_redo(bars), n & 1);
  return true;
}
template <int S0, int S1, int Z>
__device__ __forceinline__ void g2_steps(float (&ac)[48], const uint32_t (&za)[24], const uint32_t (&zb)[24], uint64_t d) {
#pragma unroll
  for (int s = S0; s < S1; s++) {
    const uint64_t ds = d + (((s >> 2 & 1) * (kWChunk / 2) + (s & 3) * 32) >> 4);
    if (s == Z) wg_d96z<0, 48>(ac, za[2 * s], zb[2 * s], za[2 * s + 1], zb[2 * s + 1], ds, 0);
    else wg_d96<0, 48>(ac, za[2 * s], zb[2 * s], za[2 * s + 1], zb[2 * s + 1], ds, 1);
  }
}

__device__ __forceinline__ void consumer(const int wg, __nv_bfloat16* out, const uint8_t* wimg, const uint32_t sbase,
                                         const uint32_t zero, const Maps& tm, const TileTable& tt) {
  const int tid = threadIdx.x & 127;
  const int w = __shfl_sync(0xffffffffu, tid >> 5, 0), lane = tid & 31, g = qrow(w, lane >> 2), qc = qcol(w, lane >> 2);
  const uint64_t dK = make_desc(sbase, 16, 1024);
  const uint64_t dV = make_desc(sbase, kChunkBytes, 512, 2);
  const uint64_t dW1 = make_desc(sbase + kW1Off, 16, 1024);
  const uint64_t dX0 = make_desc(sbase + kW2Off + wg * 2 * kWChunk, 16, 1024), dY0 = make_desc(sbase + kW2Off + (1 - wg) * 2 * kWChunk, 16, 1024);
  const uint64_t dX2 = make_desc(sbase + kXOff + wg * (kWChunk / 2), 16, 1024), dY2 = make_desc(sbase + kXOff + (1 - wg) * (kWChunk / 2), 16, 1024);
  const uint32_t bars = sbase + kBarOff;
  int tile0 = blockIdx.x * kTilesPerCta;
  asm volatile("" : "+r"(tile0));
  const int nt = num_tiles();

  uint32_t pix = 0, geo[12] = {};
  const int l = lane & 3;
#pragma unroll 1
  for (int j = 4; j >= 0; j -= 2) {
    const TileCoord tc = decode_tile(tt, tile0 + wg + j);
    const uint32_t pr = qpix(tc.pr, 8 * tc.I + g) * kW;
    if (j == nt - 2) pix = (pr + qpix(tc.pc, 8 * tc.J + qc)) | (pr + qpix(tc.pc, 8 * tc.J + qc + 4)) << 16;
    const int d = 8 * tc.J + 6 * tc.pc - 6 - halo_c0(tc);
    const int ro = woff(tc.pr, tc.I, g), coA = woff(tc.pc, tc.J, qc) + d, coB = woff(tc.pc, tc.J, qc + 4) + d - 3;
#pragma unroll
    for (int i = 11; i >= 4; i--) geo[i] = geo[i - 4];
    const uint32_t lr = 0x1FCu << ro;
    const uint32_t lv = lr >> (2 + (l >> 1)), lu = lr >> (2 * l + 2 * tc.up);
    const uint32_t t = __byte_perm(lv, lu, wg ? 0x4501 : 0x5410);
    geo[0] = ((t & 0x15u) | (lv & 0x40u)) * 0x02082080u;
    geo[1] = ((t >> 8) & 0x15u) * 0x02082080u;
    geo[2] = __byte_perm(t << 7, t << 6, 0x7362);
    const int dr = (ro - 1) & 7;
    const uint32_t hiv = (((1u << ((ro - (l >> 1) + 1) >> 1)) - 1u) ^ (wg ? 7u : 0u)) & 7u, hiu = (t >> 24) & 3u;
    const uint32_t ca = (1u << coA) - 1u;
    geo[3] = hiv * kHiV | hiu * kHiU | ((((1u << coB) - 1u) >> (2 * (l & 1))) & 3u) * kColB |
             (15u & ~((uint32_t)((dr & 1) == (l >> 1)) << (dr >> 1))) * kInV | ((t >> 16 | t >> 24) & 3u) * kInU | ca * kColA |
             (ca >> ((0x49 >> (2 * l)) & 3) & 1u) << 19 | (uint32_t)(l == 3) << 20 | (0x55u & ((1u << (2 * coB)) - 1u)) << 24;
  }
  keep_regs(geo);
  const int so = (lane >> 3) | (lane & 4);
  uint32_t sts = sbase + w * 3072 + so * 128 + (((lane & 3) ^ so) << 4);
  __nv_bfloat16* poA = out + 8 * l + (pix & 0xFFFFu) * kC + 96 * wg;
  __nv_bfloat16* poB = out + 8 * l + (pix >> 16) * kC + 96 * wg;
  asm volatile("" : "+l"(poA), "+l"(poB), "+r"(sts));
  uint32_t oa[24], ob[24];
#pragma unroll
  for (int j = 0; j < 24; j++) oa[j] = ob[j] = 0u;
  keep_regs(oa);
  keep_regs(ob);
  PROF(wg, 0);
  if (threadIdx.x == 0) GT(1);

  for (int k = wg; k < nt; k += 2) {
    const uint32_t ph = (k >> 1) & 1;
    const int it = k >> 1;
    uint32_t qa[24], qb[24], hok[3];
    uint32_t fl = geo[3];
    {
      float acc[96];
      const uint64_t dX = make_desc(sbase + kXOff + (k == 0 ? kWChunk : 0), 16, 3072);
      if (k > 0) nb_sync(1 + (1 - wg));
      mbar_wait(bar_x(bars, k > 0), (k + (k > 0)) & 1);
      if (k < 2) PROF(wg, 1);
      PROFS(2, wg, 2 + it * 12);
      if (w == 0 && k < 2) GT(20 + wg);
#pragma unroll
      for (int s = 0; s < 12; s++) {
        if ((s & 3) == 0 && k == 0) {
          mbar_wait(bar_w1c(bars, s >> 2), 0);
          PROFS(17, wg, 50 + (s >> 2));
        }
        if ((s & 3) == 0) wg_fence();
        if (s == 0) wg_m192z<0, 96>(acc, dX, dW1, 0);
        else wg_m192<0, 96>(acc, dX + (((s >> 2) * 1024 + (s & 3) * 32) >> 4), wdesc(dW1, s), 1);
      }
      wg_commit();
      PROFS(13, wg, 13 + it * 12);
      wg_wait<0>();
      if (k > 0) nb_arrive_p(6);
      fence_regs(acc);
      PROFS(3, wg, 3 + it * 12);
#pragma unroll
      for (int j = 0; j < 24; j++) {
        qa[j] = pack_bf16(acc[4 * j], acc[4 * j + 1]);
        qb[j] = pack_bf16(acc[4 * j + 2], acc[4 * j + 3]);
      }
      keep_regs(qa);
      keep_regs(qb);
      sched_fence();
      if (k >= 2) {
        const uint32_t dst = sts + out_slot(k, nt);
        nb_sync(11);
        stage_out<0, 6>(dst, wg, oa, ob);
        nb_sync(12);
        stage_out<6, 12>(dst, wg, oa, ob);
      }
#pragma unroll
      for (int c = 0; c < 3; c++) hok[c] = mbar_test(bar_full(bars, wg, c), ph);
      if (k >= 2) {
        fence_proxy_async();
        nb_arrive_p(10);
      }
    }

    float aE[52], aO[24], bO[52], bE[28];
    const uint32_t mq = 0xEEEE4444u | zero;
    PROFS(4, wg, 4 + it * 12);

    mbar_wait_if(hok[0], bar_full(bars, wg, 0), ph);
    PROFS(14, wg, 40 + it * 3);
    if (w == 0 && k < 2) GT(22 + wg);
    if (k > 0) nb_sync(3 + (1 - wg));
    wg_fence();
#pragma unroll
    for (int ks = 0; ks < 6; ks++) {
      if (ks == NAT_P1) {
        mbar_wait_if(hok[1], bar_full(bars, wg, 1), ph);
        PROFS(14, wg, 41 + it * 3);
        wg_fence();
      }
      if (ks == NAT_P2) {
        mbar_wait_if(hok[2], bar_full(bars, wg, 2), ph);
        PROFS(14, wg, 42 + it * 3);
        wg_fence();
      }
      const uint64_t d = dK + ((ks * kChunkBytes) >> 4);
      if (ks == 0) wg_s104z<0, 52>(aE, qa[0], qa[1], qa[2], qa[3], d, 0, mq);
      else wg_s104<0, 52>(aE, qa[4 * ks], qa[4 * ks + 1], qa[4 * ks + 2], qa[4 * ks + 3], d, 1, mq);
    }
    wg_commit();
    wg_s48z<0, 24>(aO, qa[0], qa[1], qa[2], qa[3], dK + ((7 * 1024 + 64) >> 4), 0, mq);
#pragma unroll
    for (int ks = 1; ks < 6; ks++)
      wg_s48<0, 24>(aO, qa[4 * ks], qa[4 * ks + 1], qa[4 * ks + 2], qa[4 * ks + 3], dK + ((ks * kChunkBytes + 7 * 1024 + 64) >> 4), 1, mq);
    wg_commit();
    wg_s56z<0, 28>(bE, qb[0], qb[1], qb[2], qb[3], dK, 0, mq);
#pragma unroll
    for (int ks = 1; ks < 6; ks++) wg_s56<0, 28>(bE, qb[4 * ks], qb[4 * ks + 1], qb[4 * ks + 2], qb[4 * ks + 3], dK + ((ks * kChunkBytes) >> 4), 1, mq);
    wg_commit();
    wg_wait<2>();
    fence_regs(aE);
    PROFS(5, wg, 5 + it * 12);

    uint32_t pa[14], pb[14], meta[4];
    {
      float vA[14], vB[14];
      pick_v(aE, vA, fl);
      pick_u(aE + 28, vA + 8, fl);
      fence_regs(vA);
      if (k == 0) {
        if (__builtin_expect(__any_sync(0xffffffffu, vA[6] != vA[6]), 0)) {
          wg_wait<0>();
          fence_regs(aO);
          fence_regs(bE);
          if (refetch(sbase + kW1Off, wimg, false)) {
#pragma unroll
            for (int j = 0; j < 24; j++) oa[j] = ob[j] = 0u;
            k -= 2;
            continue;
          }
        }
        if (elect_one()) mbar_arrive(bar_xf(bars));
      }
      wg_fence();
      wg_s104z<0, 52>(bO, qb[0], qb[1], qb[2], qb[3], dK + 4, 0, mq);
#pragma unroll
      for (int ks = 1; ks < 6; ks++)
        wg_s104<0, 52>(bO, qb[4 * ks], qb[4 * ks + 1], qb[4 * ks + 2], qb[4 * ks + 3], dK + ((ks * kChunkBytes + 64) >> 4), 1, mq);
      wg_commit();
      if (k + 1 < nt) nb_arrive(1 + wg);
      uint32_t rt[9];
#pragma unroll
      for (int i = 0; i < 7; i++) rt[i] = sign_bytes(geo[i >> 2], 0x8888u + 0x1111u * (i & 3));
      rt[7] = sign_bytes(geo[2], 0x9988u);
      rt[8] = sign_bytes(geo[2], 0xBBAAu);
      keep_regs(rt);
      pa[13] = pb[13] = 0u;
      wg_wait<2>();
      keep_regs(qa);
      fence_regs(aO);
      float oA[6], eB[8];
      pick_u(aO, oA, fl);
      wg_wait<1>();
      fence_regs(bE);
      pick_v(bE, eB, fl);
      vA[8] = sel<kColA>(oA[0], vA[8], fl), vA[9] = sel<kColA>(oA[1], vA[9], fl);
      vA[10] = sel<kColA * 2>(oA[2], vA[10], fl), vA[11] = sel<kColA * 2>(oA[3], vA[11], fl);
      vA[12] = sel<kColA * 4>(oA[4], vA[12], fl), vA[13] = sel<kColA * 4>(oA[5], vA[13], fl);
      {
        const float m1 = __uint_as_float(0x88DD88DDu), m0 = __uint_as_float(0x88DDDD88u);
        meta[0] = 0xDD88DD88u ^ __byte_perm(fl, 0u, 0x3344);
        meta[1] = __float_as_uint(sel<kColA * 16>(sel<kColA>(m1, m0, fl), __uint_as_float(meta[0]), fl));
        meta[2] = __float_as_uint(sel<kColA * 8>(m1, m0, fl));
        meta[3] = __float_as_uint(sel<kColA * 4>(m1, m0, fl));
        keep_regs(meta);
      }
      float mA = own_max(vA, fl);
      fl |= __float_as_uint(eB[7]) & zero;
      fence_regs(eB);
      fence_regs(vA);
      asm volatile("" : "+f"(mA), "+r"(fl));
      sched_fence();
      wg_wait<0>();
      sched_fence();
      keep_regs(qb);
      fence_regs(bO);
      if (NAT_TL == 0 && k == 5) nb_arrive(11);
      PROFS(6, wg, 6 + it * 12);
      if (w == 0) GT(24 + k);
      mA = quad_max(mA);
#pragma unroll
      for (int i = 0; i < 14; i++) vA[i] = ex2(vA[i] - mA);
      pick_v(bO, vB, fl);
      pick_u(bO + 28, vB + 8, fl);
#pragma unroll
      for (int i = 0; i < 8; i += 2) vB[i] = sel<kColB>(vB[i], eB[i], fl), vB[i + 1] = sel<kColB * 2>(vB[i + 1], eB[i + 1], fl);
      float mB = quad_max(own_max(vB, fl));
      if (NAT_SB) {
        fence_regs(vA);
        fence_regs(vB);
        asm volatile("" : "+f"(mB));
        sched_fence();
      }
      if (NAT_TL == 1 && k == 5) nb_arrive(11);
      PROFS(7, wg, 7 + it * 12);
#pragma unroll
      for (int i = 0; i < 14; i++) vB[i] = ex2(vB[i] - mB);
      route(vA, row_rcp(vA, fl), rt, pa);
      route(vB, row_rcp(vB, fl), rt, pb);
    }
    PROFS(8, wg, 8 + it * 12);
    if (k == NAT_PK) PROFS(18, wg, 53);
    sched_fence();

    float ac0[48], ac1[48];
    {
      float z0[32], z1[32], z2[32];
      uint32_t za[24], zb[24];
      wg_fence();
      pv_chunk<0>(z0, pa, pb, meta, dV);
      wg_commit();
      pv_chunk<1>(z1, pa, pb, meta, dV);
      wg_commit();
      wg_wait<1>();
      if (k == NAT_PK) PROFS(18, wg, 54);
      if (k + 1 < nt) nb_arrive_p(7);
      pv_chunk<2, 0, 3>(z2, pa, pb, meta, dV);
      wg_commit();
      sched_fence();
      fence_regs(z0);
      pack_z<0>(z0, za, zb);
      sched_fence();
      wg_fence();
      pv_chunk<2, 3, 7>(z2, pa, pb, meta, dV);
      wg_commit();
      wg_wait<2>();
      if (k == NAT_PK) PROFS(19, wg, 55);
      if (k + 1 < nt) nb_arrive_p(8);
      if (k < 2) mbar_wait(k == 1 ? bar_wok(bars) : bar_w2a(bars), 0);
      wg_fence();
      g2_steps<0, 3, 0>(ac0, za, zb, dX0);
      wg_commit();
      sched_fence();
      fence_regs(z1);
      pack_z<1>(z1, za, zb);
      sched_fence();
      wg_fence();
      g2_steps<3, 4, 0>(ac0, za, zb, dX0);
      wg_commit();
      g2_steps<4, 8, 0>(ac0, za, zb, dX0);
      wg_commit();
      wg_wait<3>();
      if (k + 1 < nt) nb_arrive_p(9);
      if (k == NAT_PK) PROFS(20, wg, 56);
      keep_regs(pa);
      keep_regs(pb);
      keep_regs(meta);
      sched_fence();
      const uint32_t mok = mbar_test(bar_w2m(bars), k + 1 < nt ? k & 1 : ~k & 1);
      fence_regs(z2);
      pack_z<2>(z2, za, zb);
      keep_regs(za);
      keep_regs(zb);
      sched_fence();
      PROFS(9, wg, 9 + it * 12);
      wg_wait<1>();
      if (k > 0 && k + 1 < nt) nb_arrive(11);
      mbar_wait_if(mok, bar_w2m(bars), k & 1);
      wg_fence();
      g2_steps<8, 12, 0>(ac0, za, zb, dX2);
      wg_commit();
      g2_steps<8, 12, 8>(ac1, za, zb, dY2);
      wg_commit();
      wg_wait<2>();
      if (k > 0 && k + 1 < nt) nb_arrive(12);
      if (k != 1 && k + 1 < nt) mbar_wait(bar_w2(bars), k > 1 ? (k - 1) & 1 : 0);
      wg_fence();
      g2_steps<0, 4, 8>(ac1, za, zb, dY0);
      wg_commit();
      wg_wait<2>();
      if (k + 2 < nt) nb_arrive_p(13);
      g2_steps<4, 8, 8>(ac1, za, zb, dY0);
      wg_commit();
      if (k + 1 < nt) nb_arrive(3 + wg);
      PROFS(10, wg, 10 + it * 12);
      const bool direct = k + 2 >= nt && (wg == 1 || nt < 6);
      wg_wait<2>();
      if (k + 2 < nt && (k > 0 || nt == 6)) nb_arrive_p(5);
      sched_fence();
      fence_regs(ac0);
      pack_out<0>(ac0, oa, ob);
      store_rows<0, 3>(direct, poA, poB, oa, ob);
      __nv_bfloat16 *qA = poA - 192 * wg, *qB = poB - 192 * wg;
      sched_fence();
      wg_wait<0>();
      fence_regs(ac1);
      PROFS(11, wg, 11 + it * 12);
      pack_out<1>(ac1, oa, ob);
      asm volatile("" : "+l"(qA), "+l"(qB));
      store_rows<3, 6>(direct, qA, qB, oa, ob);
      if (k == 0) {
        uint32_t m[2] = {oa[0], oa[1]};
#pragma unroll
        for (int i = 2; i < 24; i++) asm("max.NaN.bf16x2 %0, %0, %1;" : "+r"(m[i & 1]) : "r"(oa[i]));
        asm("max.NaN.bf16x2 %0, %0, %1;" : "+r"(m[0]) : "r"(m[1]));
        uint32_t nan;
        asm volatile("{\n.reg .pred p;\nsetp.ne.u32 p, %1, 0;\nbar.red.or.pred p, 15, 128, p;\nselp.u32 %0, 1, 0, p;\n}\n"
                     : "=r"(nan) : "r"(((m[0] & 0x7FFF7FFFu) + 0x007F007Fu) & 0x80008000u) : "memory");
        if (__builtin_expect(__any_sync(0xffffffffu, nan), 0)) {
          if (nt == 6) mbar_wait(bar_x(bars, 1), 1);
          for (bool first = true; __any_sync(0xffffffffu, refetch(sbase + kW2Off, wimg + w2_offset(), first)); first = false) { }
          wg_fence();
          g2_steps<0, 8, 0>(ac0, za, zb, dX0);
          g2_steps<8, 12, 0>(ac0, za, zb, dX2);
          g2_steps<0, 8, 0>(ac1, za, zb, dY0);
          g2_steps<8, 12, 0>(ac1, za, zb, dY2);
          wg_commit();
          wg_wait<0>();
          fence_regs(ac0);
          fence_regs(ac1);
          pack_out<0>(ac0, oa, ob);
          pack_out<1>(ac1, oa, ob);
          if (nt == 6) {
            asm volatile("bar.sync 15, 128;" ::: "memory");
            if (w == 0 && elect_one()) {
              const TileCoord tc = decode_tile(tt, tile0 + 2);
              mbar_arrive_expect_tx(bar_raw(bars), kWChunk);
              move_px<0, 1>(tm, tt, sbase + kXOff, bar_raw(bars), first_line(tc), tc.kind);
            }
            __syncwarp();
            mbar_wait(bar_raw(bars), 0);
          }
        }
        if (nt < 6) nb_arrive_p(5);
        if (elect_one()) mbar_arrive(bar_wok(bars));
      }
      keep_regs(za);
      keep_regs(zb);
#pragma unroll
      for (int i = 0; i < 8; i++) geo[i] = geo[i + 4];
      keep_regs(oa);
      keep_regs(ob);
      PROFS(12, wg, 12 + it * 12);
      sched_fence();
    }
  }
  if (wg == 0 && nt == 6) {
    if (NAT_TL < 2) nb_sync(11);
    stage_out<0, 12>(sts + kW1Off, 0, oa, ob);
    fence_proxy_async();
    nb_arrive_p(6);
  }
  PROF(wg, 38);
  GT_DUMP();
  PROF_DUMP(wg);
}

struct HaloCols { int vj, vc, uj, uc; };
__device__ __forceinline__ HaloCols halo_cols(const TileCoord& tc) {
  const int c0 = halo_c0(tc);
  return HaloCols{c0 > 98, c0 > 98 ? 98 : c0 + 3, c0 < 0 ? -1 : 0, c0 < 0 ? 4 : c0};
}
__device__ __forceinline__ void load_halo(const Maps& tm, uint32_t sbase, uint32_t bars, const TileCoord tc, int k, int c) {
  const HaloCols hc = halo_cols(tc);
  const int h6 = halo_r0(tc) + (tc.up ? 0 : 8), h2 = halo_r0(tc) + 6, h8 = halo_r0(tc) + (tc.up ? 0 : 6), ch = 24 * tc.pc + 8 * c;
  uint32_t dv = sbase + 2 * c * kChunkBytes, du = dv + 7 * 1024;
  if (((k ^ tc.up) & 1) == 0) dv += 4 * 1024, du += 3 * 1024;
  const uint32_t bar = bar_full(bars, k & 1, c);
  mbar_arrive_expect_tx(bar, 14 * 1024);
  nb_sync_p(7 + c);
#pragma unroll
  for (int h = 0; h < 2; h++) {
    tma_load_5d(dv + h * kChunkBytes, &tm.v6, bar, ch + 4 * h, hc.vj, hc.vc, tc.pr, h6);
    tma_load_5d(du + h * kChunkBytes, &tm.u8, bar, ch + 4 * h, hc.uj, h8, tc.pr, hc.uc);
    tma_load_5d(sbase + (2 * c + h) * kChunkBytes + 3 * 1024, &tm.v2, bar, ch + 4 * h, hc.vj, hc.vc, tc.pr, h2);
  }
  PROFS(15, 2, k * 4 + c);
}
__device__ __forceinline__ void gather_px(const __nv_bfloat16* __restrict__ x, uint32_t buf, uint32_t bar, const TileCoord tc) {
  const int lane = threadIdx.x & 31, g = lane >> 3;
  uint32_t ro[4], co[4];
#pragma unroll
  for (int i = 0; i < 4; i++) {
    ro[i] = qpix(tc.pr, 8 * tc.I + 2 * i + (g & 1)) * (kW * kC * 2) + 16 * (lane & 7);
    co[i] = qpix(tc.pc, 8 * tc.J + 2 * i + (g >> 1)) * (kC * 2);
  }
  uint32_t dst = buf + g * 128 + (((lane & 7) ^ g) << 4);
  keep_regs(ro);
  keep_regs(co);
  sched_fence();
  nb_sync_p(13);
  nb_sync_p(5);
#pragma unroll
  for (int i = 0; i < 16; i++) {
    const char* src = (const char*)x + (ro[i >> 2] + co[i & 3]);
#pragma unroll
    for (int q = 0; q < 3; q++)
      asm volatile("cp.async.cg.shared.global [%0], [%1], 16;" ::"r"((dst ^ ((i & 1) * 576)) + (i >> 1) * 3072 + q * 1024), "l"(src + 128 * q) : "memory");
  }
  asm volatile("cp.async.wait_all;" ::: "memory");
  fence_proxy_async();
  __syncwarp();
  if (elect_one()) mbar_arrive(bar);
  __syncwarp();
}

__global__ void __launch_bounds__(384, 1)
nat_kernel(const __nv_bfloat16* __restrict__ x, __nv_bfloat16* out, const __nv_bfloat16* __restrict__ wqkv,
           const __nv_bfloat16* __restrict__ wo, uint8_t* wimg, const uint32_t zero,
           const __grid_constant__ Maps tm, const __grid_constant__ TileTable tt) {
  extern __shared__ uint8_t smem_raw[];
  constexpr uint32_t sbase = 1024;
  constexpr uint32_t bars = sbase + kBarOff;
  if (smem_u32(smem_raw) != sbase) __trap();
  const int tid = threadIdx.x;
  const uint32_t t_start = now_ns();
  if (tid == 0) GT(0);
  const int wid = __shfl_sync(0xffffffffu, tid >> 5, 0);
  if ((wid == 4 || (wid == 5 && blockIdx.x - 2 < 16)) && blockIdx.x < 128 && wqkv != nullptr) {
    fold_w1(blockIdx.x - 2 < 16 ? 2 * blockIdx.x + wid - 6 : blockIdx.x + (blockIdx.x < 2 ? 0 : 16), wqkv, wimg);
    if (wid == 4) asm volatile("bar.arrive 12, 64;" ::: "memory");
    if (tid == 128) GT(7);
  }
  if (wid == NAT_PW) {
    if (blockIdx.x >= 128) {
      asm volatile("prefetch.tensormap [%0];" ::"l"((uint64_t)&tm.wv) : "memory");
      asm volatile("prefetch.tensormap [%0];" ::"l"((uint64_t)&tm.wo) : "memory");
    }
    asm volatile("prefetch.tensormap [%0];" ::"l"((uint64_t)&tm.v14) : "memory");
    asm volatile("prefetch.tensormap [%0];" ::"l"((uint64_t)&tm.u8) : "memory");
    const CUtensorMap* px = tm.px + (blockIdx.x >= 112 ? 2 : edge_strip());
    asm volatile("prefetch.tensormap [%0];" ::"l"((uint64_t)px) : "memory");
    asm volatile("prefetch.tensormap [%0];" ::"l"((uint64_t)(px + 1)) : "memory");
    asm volatile("prefetch.tensormap [%0];" ::"l"((uint64_t)&tm.v6) : "memory");
    asm volatile("prefetch.tensormap [%0];" ::"l"((uint64_t)&tm.v2) : "memory");
    asm volatile("prefetch.tensormap [%0];" ::"l"((uint64_t)(px + 4)) : "memory");
    asm volatile("prefetch.tensormap [%0];" ::"l"((uint64_t)(px + 5)) : "memory");
  }
  if (wid >= 8) {
    asm volatile("setmaxnreg.dec.sync.aligned.u32 24;");
    const int c = wid & 3, lane = tid & 31;
    const int tile0 = blockIdx.x * kTilesPerCta, nt = num_tiles();
    uint32_t w2o = 0;
    if (c == 3) {
      asm volatile("bar.sync 13, 64;" ::: "memory");
      __nanosleep(NAT_TW2 - 2000);
      w2o = w2_offset();
      if (elect_one()) {
        mbar_arrive_expect_tx(bar_w2a(bars), kWChunk);
        mbar_arrive_expect_tx(bar_w2(bars), kWChunk);
        wait_clock(t_start, NAT_TW2);
        bulk_load(sbase + kW2Off, wimg + w2o, kWChunk, bar_w2a(bars));
        mbar_wait(bar_xf(bars), 0);
        bulk_load(sbase + kW2Off + 2 * kWChunk, wimg + (w2o + 2 * kWChunk), kWChunk, bar_w2(bars));
      }
      __syncwarp();
      if (nt < 6) {
#pragma unroll 1
        for (int k = 2; k < 4; k++) {
          gather_px(x, sbase + kXOff, bar_x(bars, 1), decode_tile(tt, tile0 + k));
        }
      }
      if (wqkv == nullptr) return;
      mbar_wait(bar_wok(bars), 0);
      if (lane == 0) asm volatile("red.relaxed.gpu.global.add.u32 [%0], 1;" ::"l"(g_flag) : "memory");
      if (blockIdx.x >= 48) return;
      if (lane == 0) {
        uint32_t v, it = 0;
        do {
          __nanosleep(2000);
          asm volatile("ld.relaxed.gpu.global.u32 %0, [%1];" : "=r"(v) : "l"(g_flag) : "memory");
        } while (v < gridDim.x && ++it < (1u << 16));
      }
      __syncwarp();
#pragma unroll
      for (int i = 0; i < 6; i++)
        stg128(wimg + ((i < 3 ? 0u : 3 * kWBytes - w2o) + blockIdx.x * 1536 + (i % 3) * 512 + lane * 16), kEmpty, kEmpty, kEmpty, kEmpty);
      if (lane == 0 && atomicAdd(g_flag + 32, 1u) == 47) {
        g_flag[0] = g_flag[32] = 0;
        g_flag[64] = w2o == kWBytes;
      }
      return;
    }
    if (!elect_one()) return;
    if (c == 0) {
      for (int i = 0; i < kNumBars; i++) mbar_init(bars + i * 8, i == 13 || i == 16 ? 4 : 1);
      asm volatile("st.shared.v2.u32 [%0], {%1,%1};" ::"r"(bars + 192), "r"(0) : "memory");
      asm volatile("fence.mbarrier_init.release.cluster;" ::: "memory");
      if (blockIdx.x - 128 < 3 && wqkv != nullptr) {
        const int q = blockIdx.x & 3;
        mbar_arrive_expect_tx(bar_raw(bars), kWBytes + kWChunk);
#pragma unroll
        for (int j = 0; j < 6; j++)
          asm volatile("cp.async.bulk.tensor.2d.shared::cluster.global.tile.mbarrier::complete_tx::bytes [%0], [%1, {%3, %4}], [%2];" ::"r"(
                           j < 3 ? sbase + j * 8192 : sbase + kW2Off + (j - 3) * kWChunk),
                       "l"((uint64_t)(j < 3 ? &tm.wv : &tm.wo)), "r"(bar_raw(bars)), "r"(j < 3 ? 384 + 64 * j : 64 * (j - 3)), "r"(j < 3 ? 64 * q : 0) : "memory");
        asm volatile("bar.arrive 11, 160;" ::: "memory");
        w2o = w2_offset();
        asm volatile("bar.sync 10, 288;" ::: "memory");
#pragma unroll
        for (int h = 0; h < 2; h++)
          asm volatile("cp.async.bulk.global.shared::cta.bulk_group [%0], [%1], %2;" ::"l"(wimg + (w2o + w2piece(h, q) * (kWChunk / 2))),
                       "r"(sbase + kW1Off + h * (kWChunk / 2)), "r"(kWChunk / 2) : "memory");
        asm volatile("cp.async.bulk.commit_group;" ::: "memory");
        asm volatile("cp.async.bulk.wait_group.read 0;" ::: "memory");
        GT(31);
      }
      asm volatile("bar.arrive 0, 224;" ::: "memory");
      asm volatile("bar.arrive 14, 160;" ::: "memory");
      asm volatile("bar.arrive 13, 64;" ::: "memory");
      const TileCoord tc0 = decode_tile(tt, tile0);
      const HaloCols hc = halo_cols(tc0);
      const int h0 = halo_r0(tc0);
#pragma unroll
      for (int j = 0; j < 3; j++) mbar_arrive_expect_tx(bar_full(bars, 0, j), 2 * kChunkBytes);
      GT(17);
#pragma unroll 1
      for (int i = 0; i < 6; i++) {
        if (i == NAT_H0 || i == NAT_X1P) mbar_arrive(bar_go(bars, i != NAT_H0));
        if (i == NAT_H0) {
          wait_clock(t_start, NAT_HP);
#pragma unroll
          for (int q = 4 * NAT_H0; q < 24; q += 8) {
            tma_prefetch_5d(&tm.v6, 24 * tc0.pc + q, hc.vj, hc.vc, tc0.pr, h0 + (tc0.up ? 0 : 8));
            tma_prefetch_5d(&tm.u8, 24 * tc0.pc + q, hc.uj, h0 + (tc0.up ? 0 : 6), tc0.pr, hc.uc);
            if (blockIdx.x >= 112) tma_prefetch_5d(&tm.v2, 24 * tc0.pc + q, hc.vj, hc.vc, tc0.pr, h0 + 6);
          }
          mbar_wait(bar_w1q(bars), 0);
        }
        const uint32_t dst = sbase + i * kChunkBytes, bar = bar_full(bars, 0, i >> 1);
        const int ch = 24 * tc0.pc + 4 * i;
        tma_load_5d(dst, &tm.v14, bar, ch, hc.vj, hc.vc, tc0.pr, h0);
        tma_load_5d(dst + 7 * 1024, &tm.u8, bar, ch, hc.uj, h0 + (tc0.up ? 0 : -2), tc0.pr, hc.uc);
        tma_load_5d(dst + 10 * 1024, &tm.u8, bar, ch, hc.uj, h0 + (tc0.up ? 8 : 6), tc0.pr, hc.uc);
      }
      w2o = w2_offset();
    } else {
      asm volatile("bar.sync 0, 224;" ::: "memory");
      if (c == 2) {
        if (wqkv != nullptr && nt == 6) asm volatile("bar.sync 12, 64;" ::: "memory");
        const uint32_t c0 = clock();
        while ((uint32_t)clock() - c0 < NAT_TD) { }
        wait_clock(t_start, NAT_T0);
#pragma unroll
        for (int j = 0; j < 3; j++) {
          mbar_arrive_expect_tx(bar_w1c(bars, j), kWChunk);
          bulk_load(sbase + kW1Off + j * kWChunk, wimg + j * kWChunk, kWChunk, bar_w1c(bars, j));
        }
        mbar_arrive(bar_w1q(bars));
        GT(2);
        if (NAT_OT == 2) w2o = w2_offset();
      } else {
#pragma unroll 1
        for (int j = 0; j < 2; j++) {
          const TileCoord tc = decode_tile(tt, tile0 + j);
          const int line = first_line(tc);
          mbar_arrive_expect_tx(bar_x(bars, j), kWChunk);
          if (j == 1 || (tc.kind == 0 && NAT_XF == 0)) mbar_wait(bar_go(bars, j), 0);
          if (j == 0) GT(15);
          move_px<0, 2>(tm, tt, sbase + kXOff + (1 - j) * kWChunk, bar_x(bars, j), line, tc.kind);
          if (j == 0) GT(16);
        }
        w2o = w2_offset();
      }
    }
#pragma unroll 1
    for (int k = 1; k < nt; k++) {
      const TileCoord tn = decode_tile(tt, tile0 + k + 1);
      const int line = first_line(tn);
      if (c == 1) {
        nb_sync_p(6);
        bulk_load(sbase + kXOff, wimg + (w2o + kWChunk), kWChunk, bar_w2m(bars));
        mbar_arrive_expect_tx(bar_w2m(bars), kWChunk);
      }
      if (c == 2 - NAT_OT) {
        if (k == 1) wait_clock(t_start, NAT_TX2);
        else if (NAT_OT == 0 || k == nt - 1 + (nt == 6)) __nanosleep(NAT_PFD);
        if (k < 5 && nt == 6) move_px<1, 1>(tm, tt, 0, 0, line, tn.kind);
      }
      if (c == 2 - NAT_OT && (blockIdx.x >= 112 || k == 5)) {
        const TileCoord tc = decode_tile(tt, tile0 + k);
        const HaloCols hc = halo_cols(tc);
        const int h8 = halo_r0(tc) + (tc.up ? 0 : 6);
#pragma unroll 1
        for (int q = 0; q < 24; q += 8) {
          tma_prefetch_5d(&tm.v6, 24 * tc.pc + q, hc.vj, hc.vc, tc.pr, h8);
          tma_prefetch_5d(&tm.v2, 24 * tc.pc + q, hc.vj, hc.vc, tc.pr, h8 + 6);
          tma_prefetch_5d(&tm.u8, 24 * tc.pc + q, hc.uj, h8, tc.pr, hc.uc);
        }
      }
      load_halo(tm, sbase, bars, decode_tile(tt, tile0 + k), k, c);
      if (c == 0 && k >= 3 && NAT_RP == 1) {
        if (NAT_RD) __nanosleep(NAT_RD);
        asm volatile("cp.async.bulk.wait_group.read 0;" ::: "memory");
        bulk_load(sbase + out_slot(k - 1, nt), wimg + (w2o + out_slot(k - 1, nt) - kW2Off), kWChunk, bar_w2(bars));
        mbar_arrive_expect_tx(bar_w2(bars), kWChunk);
      }
      if (c == 0 && k < 5 && nt == 6) {
        const int f = ~k & 1;
        if (tn.kind == 0) {
#pragma unroll
          for (int j = 0; j < 4; j++) {
            if ((j & 1) == 0) nb_sync_p(j ? 5 : 13);
            tma_load_5d(sbase + kXOff + (j ^ 2 * f) * 6144, tm.px, bar_x(bars, 1), 0, 0, 0, 0, line + 6 * (j ^ 2 * f));
          }
        } else {
          nb_sync_p(13);
          move_px<0, 4, 4>(tm, tt, sbase + kXOff, bar_x(bars, 1), line, tn.kind, 4 * f);
          nb_sync_p(5);
          move_px<0, 4, 4>(tm, tt, sbase + kXOff, bar_x(bars, 1), line, tn.kind, 4 - 4 * f);
        }
        mbar_arrive_expect_tx(bar_x(bars, 1), kWChunk);
        PROFS(16, 2, k * 4 + 3);
      }
      if (c == NAT_OT && k >= 2) {
        const TileCoord tp = decode_tile(tt, tile0 + k - 2);
        const int lp = first_line(tp);
        nb_sync_p(10);
        if (NAT_XW == 1 && k < 5 && nt == 6) mbar_wait(bar_x(bars, 1), k & 1);
        if (NAT_XW > 1) __nanosleep(NAT_XW);
        move_px<2, NAT_SU>(tm, tt, sbase + out_slot(k, nt), 0, lp, tp.kind);
        if (NAT_RP == 0 && k + 1 < nt) {
          asm volatile("cp.async.bulk.wait_group.read 0;" ::: "memory");
          bulk_load(sbase + out_slot(k, nt), wimg + (w2o + out_slot(k, nt) - kW2Off), kWChunk, bar_w2(bars));
          mbar_arrive_expect_tx(bar_w2(bars), kWChunk);
        }
      }
    }
    if (c == 1 && nt == 6) {
      const TileCoord tp = decode_tile(tt, tile0 + 4);
      const int lp = first_line(tp);
      nb_sync_p(6);
      move_px<2, 1>(tm, tt, sbase + kW1Off, 0, lp, tp.kind);
    }
    asm volatile("cp.async.bulk.wait_group 0;" ::: "memory");
  } else {
    {
      if (blockIdx.x - 128 < 3 && wqkv != nullptr) {
        if (wid < 4) {
          asm volatile("bar.sync 11, 160;" ::: "memory");
          mbar_wait(bar_raw(bars), 0);
        } else if (wid < 6 && elect_one()) {
          asm volatile("cp.async.bulk.prefetch.L2.global [%0], %1;" ::"l"(wid == 4 ? wo : wqkv + (blockIdx.x & 3) * 64 * 576), "r"(kWBytes) : "memory");
        }
        __syncwarp();
        if (tid == 0) GT(7);
        float acc[96];
        wg_fence();
        wg_m192tz<0, 96>(acc, make_desc(sbase, 16, 1024), make_desc(sbase + kW2Off, kWChunk, 1024), 0);
#pragma unroll
        for (int s = 1; s < 12; s++)
          wg_m192t<0, 96>(acc, make_desc(sbase + (s >> 2) * 8192 + (s & 3) * 32, 16, 1024), make_desc(sbase + kW2Off + s * 2048, kWChunk, 1024), 1);
        wg_commit();
        wg_wait<0>();
        fence_regs(acc);
        if (tid == 0) GT(19);
        const int m = (tid >> 3) & 3;
#pragma unroll
        for (int j = 0; j < 24; j += 2) {
          const int n = g2_inv(8 * (j + (m >> 1)) + (tid & 7));
          asm volatile("stmatrix.sync.aligned.m8n8.x4.trans.shared.b16 [%0], {%1,%2,%3,%4};" ::"r"(
                           sbase + kW1Off + (wid >> 2) * kWChunk + n * 128 + (((2 * (wid & 3) + (m & 1)) ^ (n & 7)) << 4)),
                       "r"(pack_bf16(acc[4 * j], acc[4 * j + 1])), "r"(pack_bf16(acc[4 * j + 2], acc[4 * j + 3])),
                       "r"(pack_bf16(acc[4 * j + 4], acc[4 * j + 5])), "r"(pack_bf16(acc[4 * j + 6], acc[4 * j + 7])) : "memory");
        }
        fence_proxy_async();
        if (tid == 0) GT(18);
        asm volatile("bar.arrive 10, 288;" ::: "memory");
      }
    }
    __syncwarp();
    if (wid < 4) asm volatile("bar.sync 0, 224;" ::: "memory");
    else asm volatile("bar.sync 14, 160;" ::: "memory");
    asm volatile("setmaxnreg.inc.sync.aligned.u32 240;");
    consumer(wid >> 2, out, wimg, sbase, zero, tm, tt);
  }
}

}

typedef CUresult (*PFN_encodeTiled)(CUtensorMap*, CUtensorMapDataType, cuuint32_t, void*, const cuuint64_t*,
                                    const cuuint64_t*, const cuuint32_t*, const cuuint32_t*, CUtensorMapInterleave,
                                    CUtensorMapSwizzle, CUtensorMapL2promotion, CUtensorMapFloatOOBfill);

extern "C" void kernel_launch(void* const* d_in, const int* in_sizes, int n_in, void* d_out, int out_size) {
  const __nv_bfloat16* x = (const __nv_bfloat16*)d_in[0];
  const __nv_bfloat16* wqkv = (const __nv_bfloat16*)d_in[1];
  const __nv_bfloat16* wo = (const __nv_bfloat16*)d_in[2];
  __nv_bfloat16* out = (__nv_bfloat16*)d_out;

  static PFN_encodeTiled encode = nullptr;
  static int num_sms = 0;
  static uint8_t* wimg = nullptr;
  if (!encode) {
    void* fn = nullptr;
    cudaDriverEntryPointQueryResult qres;
    cudaGetDriverEntryPoint("cuTensorMapEncodeTiled", &fn, cudaEnableDefault, &qres);
    encode = (PFN_encodeTiled)fn;
    cudaFuncSetAttribute(nat::nat_kernel, cudaFuncAttributeMaxDynamicSharedMemorySize, nat::kSmemBytes);
    cudaGetSymbolAddress((void**)&wimg, nat::g_wimg32);
    int dev = 0;
    cudaGetDevice(&dev);
    cudaDeviceGetAttribute(&num_sms, cudaDevAttrMultiProcessorCount, dev);
  }
  nat::Maps tm;
  cuuint32_t estr[5] = {1, 1, 1, 1, 1};
  {
    cuuint64_t vdim[5] = {48, 2, 105, 2, 112}, udim[5] = {48, 2, 112, 2, 105};
    cuuint64_t vstr[4] = {7 * 768, 768, 224 * 384, 2 * 224 * 384}, ustr[4] = {7 * 768, 2 * 224 * 384, 224 * 384, 768};
    CUtensorMap* maps[4] = {&tm.v6, &tm.v2, &tm.v14, &tm.u8};
    for (int i = 0; i < 4; i++) {
      cuuint32_t box[5] = {4, 2, i < 3 ? 4u : 8u, 1, i == 0 ? 6u : i == 1 ? 2u : i == 2 ? 14u : 3u};
      encode(maps[i], CU_TENSOR_MAP_DATA_TYPE_UINT32, 5, (void*)x, i < 3 ? vdim : udim, i < 3 ? vstr : ustr, box, estr,
             CU_TENSOR_MAP_INTERLEAVE_16B, CU_TENSOR_MAP_SWIZZLE_128B, CU_TENSOR_MAP_L2_PROMOTION_L2_128B, CU_TENSOR_MAP_FLOAT_OOB_FILL_NONE);
    }
  }
  for (int i = 0; i < 8; i++) {
    const cuuint32_t row = 224 * 384, dr = (1u + (i & 1)) * row;
    const cuuint32_t shape[4][6] = {{8, 3, 2u - i, 2 * row, 128, 4 * 768}, {2, 4, 3, dr, 768, 128}, {4, 2, 3, 4 * row, 2 * row, 128}, {4, 2, 3, 768, dr, 128}};
    const cuuint32_t* sh = shape[i >> 1];
    cuuint64_t dim[5] = {64, sh[0], sh[1], sh[2], 224 * 224 * 3};
    cuuint64_t str[4] = {sh[3], sh[4], sh[5], 128};
    cuuint32_t box[5] = {64, sh[0], sh[1], sh[2], 1};
    encode(tm.px + i, CU_TENSOR_MAP_DATA_TYPE_BFLOAT16, 5, i < 4 ? (void*)x : (void*)out, dim, str, box, estr, CU_TENSOR_MAP_INTERLEAVE_NONE,
           CU_TENSOR_MAP_SWIZZLE_128B, i < 4 ? CU_TENSOR_MAP_L2_PROMOTION_L2_128B : CU_TENSOR_MAP_L2_PROMOTION_NONE,
           CU_TENSOR_MAP_FLOAT_OOB_FILL_NONE);
  }
  for (int i = 0; i < 2; i++) {
    cuuint64_t dim[2] = {i ? 192u : 576u, 192}, str[1] = {i ? 384u : 1152u};
    cuuint32_t box[2] = {64, i ? 192u : 64u};
    encode(i ? &tm.wo : &tm.wv, CU_TENSOR_MAP_DATA_TYPE_BFLOAT16, 2, i ? (void*)wo : (void*)wqkv, dim, str, box, estr,
           CU_TENSOR_MAP_INTERLEAVE_NONE, CU_TENSOR_MAP_SWIZZLE_128B, CU_TENSOR_MAP_L2_PROMOTION_L2_256B, CU_TENSOR_MAP_FLOAT_OOB_FILL_NONE);
  }
  nat::TileTable tt;
  nat::make_tiles(tt);
  const int grid = nat::kCtas;
  if (num_sms >= grid) {
    nat::nat_kernel<<<grid, 384, nat::kSmemBytes>>>(x, out, wqkv, wo, wimg, 0u, tm, tt);
  } else {
    nat::fold_kernel<<<27, 256>>>(wqkv, wo, wimg);
    nat::nat_kernel<<<grid, 384, nat::kSmemBytes>>>(x, out, nullptr, nullptr, wimg, 0u, tm, tt);
  }
}
```

```cpp
#include <cuda_runtime.h>
#include <cuda_bf16.h>
#include <cuda.h>
#include <stdint.h>

#define NAT_P1 2
#define NAT_P2 4
#define NAT_H0 2
#define NAT_T0 2150
#define NAT_TD 1250
#define NAT_TW2 4500
#define NAT_TX2 3600
#define NAT_X1P 4
#define NAT_PK 3
#define NAT_HP 1800
#define NAT_PFD 700
#define NAT_XW 200
#define NAT_SU 8
#define NAT_D0 1
#define NAT_PW 0
#define NAT_XF 1
#define NAT_RD 0
#define NAT_RP 0
#define NAT_SP 9
#define NAT_OT 0
#define NAT_Q0 8
#define NAT_Q1 8
#define NAT_L2P CU_TENSOR_MAP_L2_PROMOTION_L2_128B
#define NAT_SB 0
namespace nat {

constexpr int kW = 224, kC = 192;
constexpr int kCtas = 132;
constexpr int kTilesPerCta = 6;
constexpr float kAlpha = 0.07216878364870322f * 1.4426950408889634f;
constexpr uint32_t kChunkBytes = 13 * 1024;
constexpr uint32_t kWChunk = 192 * 128;
constexpr uint32_t kWBytes = 3 * kWChunk;
constexpr uint32_t kW1Off = 6 * kChunkBytes;
constexpr uint32_t kW2Off = kW1Off + kWBytes;
constexpr uint32_t kXOff = kW2Off + kWChunk;
constexpr uint32_t kBarOff = kW2Off + kWBytes;
constexpr uint32_t kProfOff = kBarOff + 208;
constexpr uint32_t kSmemBytes = kBarOff + 1024;

static_assert(kW1Off % 1024 == 0 && kW2Off % 1024 == 0 && kChunkBytes % 1024 == 0, "swizzle alignment");
static_assert(kSmemBytes <= 232448, "smem");

constexpr uint32_t kEmpty = 0xFFFFFFFFu;
#define NAT_R8(v) v, v, v, v, v, v, v, v
#define NAT_R2K(v) NAT_R8(NAT_R8(NAT_R8(v))), NAT_R8(NAT_R8(NAT_R8(v))), NAT_R8(NAT_R8(NAT_R8(v))), NAT_R8(NAT_R8(NAT_R8(v)))
#define NAT_IMG NAT_R8(NAT_R2K(kEmpty)), NAT_R2K(kEmpty)
__device__ __align__(1024) uint32_t g_wimg32[3 * kWBytes / 4] = {NAT_IMG, NAT_IMG, NAT_IMG};
static_assert(kWBytes / 4 == 9 * 2048, "initialiser");
__device__ __align__(128) uint32_t g_flag[96];
__device__ __forceinline__ uint32_t w2_offset() {
  uint32_t v;
  asm volatile("ld.relaxed.gpu.global.u32 %0, [%1];" : "=r"(v) : "l"(g_flag + 64) : "memory");
  return (1 + v) * kWBytes;
}

#define PROFS(id, wgid, slotid) do { } while (0)
#define PROF(wgid, slotid) do { } while (0)
#define PROF_DUMP(wgid) do { } while (0)

#define GT(slotid) do { } while (0)
#define GT_DUMP() do { } while (0)

__device__ __forceinline__ uint32_t smem_u32(const void* p) { return (uint32_t)__cvta_generic_to_shared(p); }

__device__ __forceinline__ void mbar_init(uint32_t bar, uint32_t count) {
  asm volatile("mbarrier.init.shared::cta.b64 [%0], %1;" ::"r"(bar), "r"(count) : "memory");
}
__device__ __forceinline__ void mbar_arrive(uint32_t bar) {
  asm volatile("mbarrier.arrive.shared::cta.b64 _, [%0];" ::"r"(bar) : "memory");
}
__device__ __forceinline__ void mbar_arrive_expect_tx(uint32_t bar, uint32_t bytes) {
  asm volatile("mbarrier.arrive.expect_tx.shared::cta.b64 _, [%0], %1;" ::"r"(bar), "r"(bytes) : "memory");
}
__device__ __forceinline__ void mbar_wait(uint32_t bar, uint32_t parity) {
  uint32_t ok;
  uint32_t it = 0;
  do {
    asm volatile(
        "{\n.reg .pred p;\n"
        "mbarrier.try_wait.parity.shared::cta.b64 p, [%1], %2;\n"
        "selp.u32 %0, 1, 0, p;\n}\n"
        : "=r"(ok)
        : "r"(bar), "r"(parity)
        : "memory");
    if (++it > (1u << 24)) break;
  } while (!ok);
}
__device__ __forceinline__ uint32_t mbar_test(uint32_t bar, uint32_t parity) {
  uint32_t ok;
  asm volatile("{\n.reg .pred p;\nmbarrier.test_wait.parity.shared::cta.b64 p, [%1], %2;\nselp.u32 %0, 1, 0, p;\n}\n"
               : "=r"(ok) : "r"(bar), "r"(parity) : "memory");
  return ok;
}
__device__ __forceinline__ void mbar_wait_if(uint32_t ok, uint32_t bar, uint32_t parity) {
  if (!__all_sync(0xffffffffu, ok)) mbar_wait(bar, parity);
}
__device__ __forceinline__ bool elect_one() {
  uint32_t r;
  asm volatile("{\n.reg .pred p;\nelect.sync _|p, 0xffffffff;\nselp.u32 %0, 1, 0, p;\n}\n" : "=r"(r));
  return r != 0;
}
__device__ __forceinline__ void nb_arrive(int id) { asm volatile("bar.arrive %0, 256;" ::"r"(id) : "memory"); }
__device__ __forceinline__ void nb_sync(int id) { asm volatile("bar.sync %0, 256;" ::"r"(id) : "memory"); }
__device__ __forceinline__ void nb_arrive_p(int id) { asm volatile("bar.arrive %0, 160;" ::"r"(id) : "memory"); }
__device__ __forceinline__ void nb_sync_p(int id) { asm volatile("bar.sync %0, 160;" ::"r"(id) : "memory"); }
__device__ __forceinline__ void fence_proxy_async() { asm volatile("fence.proxy.async.shared::cta;" ::: "memory"); }

__device__ __forceinline__ void tma_load_5d(uint32_t dst, const CUtensorMap* map, uint32_t bar, int c0, int c1, int c2,
                                            int c3, int c4) {
  asm volatile(
      "cp.async.bulk.tensor.5d.shared::cluster.global.tile.mbarrier::complete_tx::bytes "
      "[%0], [%1, {%3, %4, %5, %6, %7}], [%2];"
      ::"r"(dst), "l"((uint64_t)map), "r"(bar), "r"(c0), "r"(c1), "r"(c2), "r"(c3), "r"(c4)
      : "memory");
}
__device__ __forceinline__ void bulk_load(uint32_t dst, const void* src, uint32_t bytes, uint32_t bar) {
  asm volatile("cp.async.bulk.shared::cluster.global.mbarrier::complete_tx::bytes [%0], [%1], %2, [%3];"
               ::"r"(dst), "l"((uint64_t)src), "r"(bytes), "r"(bar)
               : "memory");
}

__device__ __forceinline__ void wg_fence() { asm volatile("wgmma.fence.sync.aligned;" ::: "memory"); }
__device__ __forceinline__ void wg_commit() { asm volatile("wgmma.commit_group.sync.aligned;" ::: "memory"); }
template <int N>
__device__ __forceinline__ void wg_wait() { asm volatile("wgmma.wait_group.sync.aligned %0;" ::"n"(N) : "memory"); }

template <int N>
__device__ __forceinline__ void fence_regs(float (&d)[N]) {
#pragma unroll
  for (int i = 0; i < N; i++) asm volatile("" : "+f"(d[i])::"memory");
}
template <int N>
__device__ __forceinline__ void keep_regs(uint32_t (&d)[N]) {
#pragma unroll
  for (int i = 0; i < N; i++) asm volatile("" : "+r"(d[i])::"memory");
}

__device__ __forceinline__ uint32_t pack_bf16(float lo, float hi) {
  uint32_t d;
  asm("cvt.rn.bf16x2.f32 %0, %1, %2;" : "=r"(d) : "f"(hi), "f"(lo));
  return d;
}
__device__ __forceinline__ float ex2(float x) {
  float y;
  asm("ex2.approx.ftz.f32 %0, %1;" : "=f"(y) : "f"(x));
  return y;
}
__device__ __forceinline__ float rcp_approx(float x) {
  float y;
  asm("rcp.approx.ftz.f32 %0, %1;" : "=f"(y) : "f"(x));
  return y;
}
__device__ __forceinline__ uint4 ldg128_nc(const void* p) {
  uint4 v;
  asm volatile("ld.global.nc.v4.u32 {%0,%1,%2,%3}, [%4];" : "=r"(v.x), "=r"(v.y), "=r"(v.z), "=r"(v.w) : "l"(p));
  return v;
}
__device__ __forceinline__ void stg128(void* p, uint32_t a, uint32_t b, uint32_t c, uint32_t d) {
  asm volatile("st.global.v4.u32 [%0], {%1,%2,%3,%4};" ::"l"(p), "r"(a), "r"(b), "r"(c), "r"(d) : "memory");
}

__device__ __forceinline__ long long clk64() {
  long long c;
  asm volatile("mov.u64 %0, %clock64;" : "=l"(c)::"memory");
  return c;
}
__device__ __forceinline__ void sched_fence() { while (clk64() < 0) { } }

__device__ __forceinline__ uint64_t make_desc(uint32_t addr, uint32_t lbo, uint32_t sbo, uint32_t mode = 1) {
  return (uint64_t)((addr & 0x3FFFF) >> 4) | ((uint64_t)(lbo >> 4) << 16) | ((uint64_t)(sbo >> 4) << 32) |
         ((uint64_t)mode << 62);
}

template <int OFF, int NN>
__device__ __forceinline__ void wg_m192(float (&d)[NN], uint64_t desc_a, uint64_t desc_b, int scale_d) {
  asm volatile(
      "{\n.reg .pred p;\nsetp.ne.b32 p, %98, 0;\n"
      "wgmma.mma_async.sync.aligned.m64n192k16.f32.bf16.bf16 "
      "{%0,%1,%2,%3,%4,%5,%6,%7,%8,%9,%10,%11,%12,%13,%14,%15,"
      "%16,%17,%18,%19,%20,%21,%22,%23,%24,%25,%26,%27,%28,%29,%30,%31,"
      "%32,%33,%34,%35,%36,%37,%38,%39,%40,%41,%42,%43,%44,%45,%46,%47,"
      "%48,%49,%50,%51,%52,%53,%54,%55,%56,%57,%58,%59,%60,%61,%62,%63,"
      "%64,%65,%66,%67,%68,%69,%70,%71,%72,%73,%74,%75,%76,%77,%78,%79,"
      "%80,%81,%82,%83,%84,%85,%86,%87,%88,%89,%90,%91,%92,%93,%94,%95}, "
      "%96, %97, p, 1, 1, 0, 0;\n}\n"
      : "+f"(d[OFF + 0]), "+f"(d[OFF + 1]), "+f"(d[OFF + 2]), "+f"(d[OFF + 3]), "+f"(d[OFF + 4]), "+f"(d[OFF + 5]),
        "+f"(d[OFF + 6]), "+f"(d[OFF + 7]), "+f"(d[OFF + 8]), "+f"(d[OFF + 9]), "+f"(d[OFF + 10]), "+f"(d[OFF + 11]),
        "+f"(d[OFF + 12]), "+f"(d[OFF + 13]), "+f"(d[OFF + 14]), "+f"(d[OFF + 15]), "+f"(d[OFF + 16]), "+f"(d[OFF + 17]),
        "+f"(d[OFF + 18]), "+f"(d[OFF + 19]), "+f"(d[OFF + 20]), "+f"(d[OFF + 21]), "+f"(d[OFF + 22]), "+f"(d[OFF + 23]),
        "+f"(d[OFF + 24]), "+f"(d[OFF + 25]), "+f"(d[OFF + 26]), "+f"(d[OFF + 27]), "+f"(d[OFF + 28]), "+f"(d[OFF + 29]),
        "+f"(d[OFF + 30]), "+f"(d[OFF + 31]), "+f"(d[OFF + 32]), "+f"(d[OFF + 33]), "+f"(d[OFF + 34]), "+f"(d[OFF + 35]),
        "+f"(d[OFF + 36]), "+f"(d[OFF + 37]), "+f"(d[OFF + 38]), "+f"(d[OFF + 39]), "+f"(d[OFF + 40]), "+f"(d[OFF + 41]),
        "+f"(d[OFF + 42]), "+f"(d[OFF + 43]), "+f"(d[OFF + 44]), "+f"(d[OFF + 45]), "+f"(d[OFF + 46]), "+f"(d[OFF + 47]),
        "+f"(d[OFF + 48]), "+f"(d[OFF + 49]), "+f"(d[OFF + 50]), "+f"(d[OFF + 51]), "+f"(d[OFF + 52]), "+f"(d[OFF + 53]),
        "+f"(d[OFF + 54]), "+f"(d[OFF + 55]), "+f"(d[OFF + 56]), "+f"(d[OFF + 57]), "+f"(d[OFF + 58]), "+f"(d[OFF + 59]),
        "+f"(d[OFF + 60]), "+f"(d[OFF + 61]), "+f"(d[OFF + 62]), "+f"(d[OFF + 63]), "+f"(d[OFF + 64]), "+f"(d[OFF + 65]),
        "+f"(d[OFF + 66]), "+f"(d[OFF + 67]), "+f"(d[OFF + 68]), "+f"(d[OFF + 69]), "+f"(d[OFF + 70]), "+f"(d[OFF + 71]),
        "+f"(d[OFF + 72]), "+f"(d[OFF + 73]), "+f"(d[OFF + 74]), "+f"(d[OFF + 75]), "+f"(d[OFF + 76]), "+f"(d[OFF + 77]),
        "+f"(d[OFF + 78]), "+f"(d[OFF + 79]), "+f"(d[OFF + 80]), "+f"(d[OFF + 81]), "+f"(d[OFF + 82]), "+f"(d[OFF + 83]),
        "+f"(d[OFF + 84]), "+f"(d[OFF + 85]), "+f"(d[OFF + 86]), "+f"(d[OFF + 87]), "+f"(d[OFF + 88]), "+f"(d[OFF + 89]),
        "+f"(d[OFF + 90]), "+f"(d[OFF + 91]), "+f"(d[OFF + 92]), "+f"(d[OFF + 93]), "+f"(d[OFF + 94]), "+f"(d[OFF + 95])
      : "l"(desc_a), "l"(desc_b), "r"(scale_d));
}

template <int OFF, int NN>
__device__ __forceinline__ void wg_m192z(float (&d)[NN], uint64_t desc_a, uint64_t desc_b, int scale_d) {
  asm volatile(
      "{\n.reg .pred p;\nsetp.ne.b32 p, %98, 0;\n"
      "wgmma.mma_async.sync.aligned.m64n192k16.f32.bf16.bf16 "
      "{%0,%1,%2,%3,%4,%5,%6,%7,%8,%9,%10,%11,%12,%13,%14,%15,"
      "%16,%17,%18,%19,%20,%21,%22,%23,%24,%25,%26,%27,%28,%29,%30,%31,"
      "%32,%33,%34,%35,%36,%37,%38,%39,%40,%41,%42,%43,%44,%45,%46,%47,"
      "%48,%49,%50,%51,%52,%53,%54,%55,%56,%57,%58,%59,%60,%61,%62,%63,"
      "%64,%65,%66,%67,%68,%69,%70,%71,%72,%73,%74,%75,%76,%77,%78,%79,"
      "%80,%81,%82,%83,%84,%85,%86,%87,%88,%89,%90,%91,%92,%93,%94,%95}, "
      "%96, %97, p, 1, 1, 0, 0;\n}\n"
      : "=f"(d[OFF + 0]), "=f"(d[OFF + 1]), "=f"(d[OFF + 2]), "=f"(d[OFF + 3]), "=f"(d[OFF + 4]), "=f"(d[OFF + 5]),
        "=f"(d[OFF + 6]), "=f"(d[OFF + 7]), "=f"(d[OFF + 8]), "=f"(d[OFF + 9]), "=f"(d[OFF + 10]), "=f"(d[OFF + 11]),
        "=f"(d[OFF + 12]), "=f"(d[OFF + 13]), "=f"(d[OFF + 14]), "=f"(d[OFF + 15]), "=f"(d[OFF + 16]), "=f"(d[OFF + 17]),
        "=f"(d[OFF + 18]), "=f"(d[OFF + 19]), "=f"(d[OFF + 20]), "=f"(d[OFF + 21]), "=f"(d[OFF + 22]), "=f"(d[OFF + 23]),
        "=f"(d[OFF + 24]), "=f"(d[OFF + 25]), "=f"(d[OFF + 26]), "=f"(d[OFF + 27]), "=f"(d[OFF + 28]), "=f"(d[OFF + 29]),
        "=f"(d[OFF + 30]), "=f"(d[OFF + 31]), "=f"(d[OFF + 32]), "=f"(d[OFF + 33]), "=f"(d[OFF + 34]), "=f"(d[OFF + 35]),
        "=f"(d[OFF + 36]), "=f"(d[OFF + 37]), "=f"(d[OFF + 38]), "=f"(d[OFF + 39]), "=f"(d[OFF + 40]), "=f"(d[OFF + 41]),
        "=f"(d[OFF + 42]), "=f"(d[OFF + 43]), "=f"(d[OFF + 44]), "=f"(d[OFF + 45]), "=f"(d[OFF + 46]), "=f"(d[OFF + 47]),
        "=f"(d[OFF + 48]), "=f"(d[OFF + 49]), "=f"(d[OFF + 50]), "=f"(d[OFF + 51]), "=f"(d[OFF + 52]), "=f"(d[OFF + 53]),
        "=f"(d[OFF + 54]), "=f"(d[OFF + 55]), "=f"(d[OFF + 56]), "=f"(d[OFF + 57]), "=f"(d[OFF + 58]), "=f"(d[OFF + 59]),
        "=f"(d[OFF + 60]), "=f"(d[OFF + 61]), "=f"(d[OFF + 62]), "=f"(d[OFF + 63]), "=f"(d[OFF + 64]), "=f"(d[OFF + 65]),
        "=f"(d[OFF + 66]), "=f"(d[OFF + 67]), "=f"(d[OFF + 68]), "=f"(d[OFF + 69]), "=f"(d[OFF + 70]), "=f"(d[OFF + 71]),
        "=f"(d[OFF + 72]), "=f"(d[OFF + 73]), "=f"(d[OFF + 74]), "=f"(d[OFF + 75]), "=f"(d[OFF + 76]), "=f"(d[OFF + 77]),
        "=f"(d[OFF + 78]), "=f"(d[OFF + 79]), "=f"(d[OFF + 80]), "=f"(d[OFF + 81]), "=f"(d[OFF + 82]), "=f"(d[OFF + 83]),
        "=f"(d[OFF + 84]), "=f"(d[OFF + 85]), "=f"(d[OFF + 86]), "=f"(d[OFF + 87]), "=f"(d[OFF + 88]), "=f"(d[OFF + 89]),
        "=f"(d[OFF + 90]), "=f"(d[OFF + 91]), "=f"(d[OFF + 92]), "=f"(d[OFF + 93]), "=f"(d[OFF + 94]), "=f"(d[OFF + 95])
      : "l"(desc_a), "l"(desc_b), "r"(scale_d));
}

template <int OFF, int NN>
__device__ __forceinline__ void wg_m192t(float (&d)[NN], uint64_t desc_a, uint64_t desc_b, int scale_d) {
  asm volatile(
      "{\n.reg .pred p;\nsetp.ne.b32 p, %98, 0;\n"
      "wgmma.mma_async.sync.aligned.m64n192k16.f32.bf16.bf16 "
      "{%0,%1,%2,%3,%4,%5,%6,%7,%8,%9,%10,%11,%12,%13,%14,%15,"
      "%16,%17,%18,%19,%20,%21,%22,%23,%24,%25,%26,%27,%28,%29,%30,%31,"
      "%32,%33,%34,%35,%36,%37,%38,%39,%40,%41,%42,%43,%44,%45,%46,%47,"
      "%48,%49,%50,%51,%52,%53,%54,%55,%56,%57,%58,%59,%60,%61,%62,%63,"
      "%64,%65,%66,%67,%68,%69,%70,%71,%72,%73,%74,%75,%76,%77,%78,%79,"
      "%80,%81,%82,%83,%84,%85,%86,%87,%88,%89,%90,%91,%92,%93,%94,%95}, "
      "%96, %97, p, 1, 1, 0, 1;\n}\n"
      : "+f"(d[OFF + 0]), "+f"(d[OFF + 1]), "+f"(d[OFF + 2]), "+f"(d[OFF + 3]), "+f"(d[OFF + 4]), "+f"(d[OFF + 5]),
        "+f"(d[OFF + 6]), "+f"(d[OFF + 7]), "+f"(d[OFF + 8]), "+f"(d[OFF + 9]), "+f"(d[OFF + 10]), "+f"(d[OFF + 11]),
        "+f"(d[OFF + 12]), "+f"(d[OFF + 13]), "+f"(d[OFF + 14]), "+f"(d[OFF + 15]), "+f"(d[OFF + 16]), "+f"(d[OFF + 17]),
        "+f"(d[OFF + 18]), "+f"(d[OFF + 19]), "+f"(d[OFF + 20]), "+f"(d[OFF + 21]), "+f"(d[OFF + 22]), "+f"(d[OFF + 23]),
        "+f"(d[OFF + 24]), "+f"(d[OFF + 25]), "+f"(d[OFF + 26]), "+f"(d[OFF + 27]), "+f"(d[OFF + 28]), "+f"(d[OFF + 29]),
        "+f"(d[OFF + 30]), "+f"(d[OFF + 31]), "+f"(d[OFF + 32]), "+f"(d[OFF + 33]), "+f"(d[OFF + 34]), "+f"(d[OFF + 35]),
        "+f"(d[OFF + 36]), "+f"(d[OFF + 37]), "+f"(d[OFF + 38]), "+f"(d[OFF + 39]), "+f"(d[OFF + 40]), "+f"(d[OFF + 41]),
        "+f"(d[OFF + 42]), "+f"(d[OFF + 43]), "+f"(d[OFF + 44]), "+f"(d[OFF + 45]), "+f"(d[OFF + 46]), "+f"(d[OFF + 47]),
        "+f"(d[OFF + 48]), "+f"(d[OFF + 49]), "+f"(d[OFF + 50]), "+f"(d[OFF + 51]), "+f"(d[OFF + 52]), "+f"(d[OFF + 53]),
        "+f"(d[OFF + 54]), "+f"(d[OFF + 55]), "+f"(d[OFF + 56]), "+f"(d[OFF + 57]), "+f"(d[OFF + 58]), "+f"(d[OFF + 59]),
        "+f"(d[OFF + 60]), "+f"(d[OFF + 61]), "+f"(d[OFF + 62]), "+f"(d[OFF + 63]), "+f"(d[OFF + 64]), "+f"(d[OFF + 65]),
        "+f"(d[OFF + 66]), "+f"(d[OFF + 67]), "+f"(d[OFF + 68]), "+f"(d[OFF + 69]), "+f"(d[OFF + 70]), "+f"(d[OFF + 71]),
        "+f"(d[OFF + 72]), "+f"(d[OFF + 73]), "+f"(d[OFF + 74]), "+f"(d[OFF + 75]), "+f"(d[OFF + 76]), "+f"(d[OFF + 77]),
        "+f"(d[OFF + 78]), "+f"(d[OFF + 79]), "+f"(d[OFF + 80]), "+f"(d[OFF + 81]), "+f"(d[OFF + 82]), "+f"(d[OFF + 83]),
        "+f"(d[OFF + 84]), "+f"(d[OFF + 85]), "+f"(d[OFF + 86]), "+f"(d[OFF + 87]), "+f"(d[OFF + 88]), "+f"(d[OFF + 89]),
        "+f"(d[OFF + 90]), "+f"(d[OFF + 91]), "+f"(d[OFF + 92]), "+f"(d[OFF + 93]), "+f"(d[OFF + 94]), "+f"(d[OFF + 95])
      : "l"(desc_a), "l"(desc_b), "r"(scale_d));
}

template <int OFF, int NN>
__device__ __forceinline__ void wg_m192tz(float (&d)[NN], uint64_t desc_a, uint64_t desc_b, int scale_d) {
  asm volatile(
      "{\n.reg .pred p;\nsetp.ne.b32 p, %98, 0;\n"
      "wgmma.mma_async.sync.aligned.m64n192k16.f32.bf16.bf16 "
      "{%0,%1,%2,%3,%4,%5,%6,%7,%8,%9,%10,%11,%12,%13,%14,%15,"
      "%16,%17,%18,%19,%20,%21,%22,%23,%24,%25,%26,%27,%28,%29,%30,%31,"
      "%32,%33,%34,%35,%36,%37,%38,%39,%40,%41,%42,%43,%44,%45,%46,%47,"
      "%48,%49,%50,%51,%52,%53,%54,%55,%56,%57,%58,%59,%60,%61,%62,%63,"
      "%64,%65,%66,%67,%68,%69,%70,%71,%72,%73,%74,%75,%76,%77,%78,%79,"
      "%80,%81,%82,%83,%84,%85,%86,%87,%88,%89,%90,%91,%92,%93,%94,%95}, "
      "%96, %97, p, 1, 1, 0, 1;\n}\n"
      : "=f"(d[OFF + 0]), "=f"(d[OFF + 1]), "=f"(d[OFF + 2]), "=f"(d[OFF + 3]), "=f"(d[OFF + 4]), "=f"(d[OFF + 5]),
        "=f"(d[OFF + 6]), "=f"(d[OFF + 7]), "=f"(d[OFF + 8]), "=f"(d[OFF + 9]), "=f"(d[OFF + 10]), "=f"(d[OFF + 11]),
        "=f"(d[OFF + 12]), "=f"(d[OFF + 13]), "=f"(d[OFF + 14]), "=f"(d[OFF + 15]), "=f"(d[OFF + 16]), "=f"(d[OFF + 17]),
        "=f"(d[OFF + 18]), "=f"(d[OFF + 19]), "=f"(d[OFF + 20]), "=f"(d[OFF + 21]), "=f"(d[OFF + 22]), "=f"(d[OFF + 23]),
        "=f"(d[OFF + 24]), "=f"(d[OFF + 25]), "=f"(d[OFF + 26]), "=f"(d[OFF + 27]), "=f"(d[OFF + 28]), "=f"(d[OFF + 29]),
        "=f"(d[OFF + 30]), "=f"(d[OFF + 31]), "=f"(d[OFF + 32]), "=f"(d[OFF + 33]), "=f"(d[OFF + 34]), "=f"(d[OFF + 35]),
        "=f"(d[OFF + 36]), "=f"(d[OFF + 37]), "=f"(d[OFF + 38]), "=f"(d[OFF + 39]), "=f"(d[OFF + 40]), "=f"(d[OFF + 41]),
        "=f"(d[OFF + 42]), "=f"(d[OFF + 43]), "=f"(d[OFF + 44]), "=f"(d[OFF + 45]), "=f"(d[OFF + 46]), "=f"(d[OFF + 47]),
        "=f"(d[OFF + 48]), "=f"(d[OFF + 49]), "=f"(d[OFF + 50]), "=f"(d[OFF + 51]), "=f"(d[OFF + 52]), "=f"(d[OFF + 53]),
        "=f"(d[OFF + 54]), "=f"(d[OFF + 55]), "=f"(d[OFF + 56]), "=f"(d[OFF + 57]), "=f"(d[OFF + 58]), "=f"(d[OFF + 59]),
        "=f"(d[OFF + 60]), "=f"(d[OFF + 61]), "=f"(d[OFF + 62]), "=f"(d[OFF + 63]), "=f"(d[OFF + 64]), "=f"(d[OFF + 65]),
        "=f"(d[OFF + 66]), "=f"(d[OFF + 67]), "=f"(d[OFF + 68]), "=f"(d[OFF + 69]), "=f"(d[OFF + 70]), "=f"(d[OFF + 71]),
        "=f"(d[OFF + 72]), "=f"(d[OFF + 73]), "=f"(d[OFF + 74]), "=f"(d[OFF + 75]), "=f"(d[OFF + 76]), "=f"(d[OFF + 77]),
        "=f"(d[OFF + 78]), "=f"(d[OFF + 79]), "=f"(d[OFF + 80]), "=f"(d[OFF + 81]), "=f"(d[OFF + 82]), "=f"(d[OFF + 83]),
        "=f"(d[OFF + 84]), "=f"(d[OFF + 85]), "=f"(d[OFF + 86]), "=f"(d[OFF + 87]), "=f"(d[OFF + 88]), "=f"(d[OFF + 89]),
        "=f"(d[OFF + 90]), "=f"(d[OFF + 91]), "=f"(d[OFF + 92]), "=f"(d[OFF + 93]), "=f"(d[OFF + 94]), "=f"(d[OFF + 95])
      : "l"(desc_a), "l"(desc_b), "r"(scale_d));
}

template <int OFF, int NN>
__device__ __forceinline__ void wg_d96(float (&d)[NN], uint32_t a0, uint32_t a1, uint32_t a2, uint32_t a3,
                                       uint64_t desc_b, int scale_d) {
  asm volatile(
      "{\n.reg .pred p;\nsetp.ne.b32 p, %53, 0;\n"
      "wgmma.mma_async.sync.aligned.m64n96k16.f32.bf16.bf16 "
      "{%0,%1,%2,%3,%4,%5,%6,%7,%8,%9,%10,%11,%12,%13,%14,%15,"
      "%16,%17,%18,%19,%20,%21,%22,%23,%24,%25,%26,%27,%28,%29,%30,%31,"
      "%32,%33,%34,%35,%36,%37,%38,%39,%40,%41,%42,%43,%44,%45,%46,%47}, "
      "{%48,%49,%50,%51}, %52, p, 1, 1, 0;\n}\n"
      : "+f"(d[OFF + 0]), "+f"(d[OFF + 1]), "+f"(d[OFF + 2]), "+f"(d[OFF + 3]), "+f"(d[OFF + 4]), "+f"(d[OFF + 5]),
        "+f"(d[OFF + 6]), "+f"(d[OFF + 7]), "+f"(d[OFF + 8]), "+f"(d[OFF + 9]), "+f"(d[OFF + 10]), "+f"(d[OFF + 11]),
        "+f"(d[OFF + 12]), "+f"(d[OFF + 13]), "+f"(d[OFF + 14]), "+f"(d[OFF + 15]), "+f"(d[OFF + 16]), "+f"(d[OFF + 17]),
        "+f"(d[OFF + 18]), "+f"(d[OFF + 19]), "+f"(d[OFF + 20]), "+f"(d[OFF + 21]), "+f"(d[OFF + 22]), "+f"(d[OFF + 23]),
        "+f"(d[OFF + 24]), "+f"(d[OFF + 25]), "+f"(d[OFF + 26]), "+f"(d[OFF + 27]), "+f"(d[OFF + 28]), "+f"(d[OFF + 29]),
        "+f"(d[OFF + 30]), "+f"(d[OFF + 31]), "+f"(d[OFF + 32]), "+f"(d[OFF + 33]), "+f"(d[OFF + 34]), "+f"(d[OFF + 35]),
        "+f"(d[OFF + 36]), "+f"(d[OFF + 37]), "+f"(d[OFF + 38]), "+f"(d[OFF + 39]), "+f"(d[OFF + 40]), "+f"(d[OFF + 41]),
        "+f"(d[OFF + 42]), "+f"(d[OFF + 43]), "+f"(d[OFF + 44]), "+f"(d[OFF + 45]), "+f"(d[OFF + 46]), "+f"(d[OFF + 47])
      : "r"(a0), "r"(a1), "r"(a2), "r"(a3), "l"(desc_b), "r"(scale_d));
}

template <int OFF, int NN>
__device__ __forceinline__ void wg_d96z(float (&d)[NN], uint32_t a0, uint32_t a1, uint32_t a2, uint32_t a3,
                                       uint64_t desc_b, int scale_d) {
  asm volatile(
      "{\n.reg .pred p;\nsetp.ne.b32 p, %53, 0;\n"
      "wgmma.mma_async.sync.aligned.m64n96k16.f32.bf16.bf16 "
      "{%0,%1,%2,%3,%4,%5,%6,%7,%8,%9,%10,%11,%12,%13,%14,%15,"
      "%16,%17,%18,%19,%20,%21,%22,%23,%24,%25,%26,%27,%28,%29,%30,%31,"
      "%32,%33,%34,%35,%36,%37,%38,%39,%40,%41,%42,%43,%44,%45,%46,%47}, "
      "{%48,%49,%50,%51}, %52, p, 1, 1, 0;\n}\n"
      : "=f"(d[OFF + 0]), "=f"(d[OFF + 1]), "=f"(d[OFF + 2]), "=f"(d[OFF + 3]), "=f"(d[OFF + 4]), "=f"(d[OFF + 5]),
        "=f"(d[OFF + 6]), "=f"(d[OFF + 7]), "=f"(d[OFF + 8]), "=f"(d[OFF + 9]), "=f"(d[OFF + 10]), "=f"(d[OFF + 11]),
        "=f"(d[OFF + 12]), "=f"(d[OFF + 13]), "=f"(d[OFF + 14]), "=f"(d[OFF + 15]), "=f"(d[OFF + 16]), "=f"(d[OFF + 17]),
        "=f"(d[OFF + 18]), "=f"(d[OFF + 19]), "=f"(d[OFF + 20]), "=f"(d[OFF + 21]), "=f"(d[OFF + 22]), "=f"(d[OFF + 23]),
        "=f"(d[OFF + 24]), "=f"(d[OFF + 25]), "=f"(d[OFF + 26]), "=f"(d[OFF + 27]), "=f"(d[OFF + 28]), "=f"(d[OFF + 29]),
        "=f"(d[OFF + 30]), "=f"(d[OFF + 31]), "=f"(d[OFF + 32]), "=f"(d[OFF + 33]), "=f"(d[OFF + 34]), "=f"(d[OFF + 35]),
        "=f"(d[OFF + 36]), "=f"(d[OFF + 37]), "=f"(d[OFF + 38]), "=f"(d[OFF + 39]), "=f"(d[OFF + 40]), "=f"(d[OFF + 41]),
        "=f"(d[OFF + 42]), "=f"(d[OFF + 43]), "=f"(d[OFF + 44]), "=f"(d[OFF + 45]), "=f"(d[OFF + 46]), "=f"(d[OFF + 47])
      : "r"(a0), "r"(a1), "r"(a2), "r"(a3), "l"(desc_b), "r"(scale_d));
}

template <int OFF, int NN>
__device__ __forceinline__ void wg_s104(float (&d)[NN], uint32_t a0, uint32_t a1, uint32_t a2, uint32_t a3,
                                       uint64_t desc_b, int scale_d, uint32_t meta) {
  asm volatile(
      "{\n.reg .pred p;\nsetp.ne.b32 p, %57, 0;\n"
      "wgmma.mma_async.sp.sync.aligned.m64n104k32.f32.bf16.bf16 "
      "{%0,%1,%2,%3,%4,%5,%6,%7,%8,%9,%10,%11,%12,%13,%14,%15,"
      "%16,%17,%18,%19,%20,%21,%22,%23,%24,%25,%26,%27,%28,%29,%30,%31,"
      "%32,%33,%34,%35,%36,%37,%38,%39,%40,%41,%42,%43,%44,%45,%46,%47,"
      "%48,%49,%50,%51}, "
      "{%52,%53,%54,%55}, %56, %58, 0, p, 1, 1, 0;\n}\n"
      : "+f"(d[OFF + 0]), "+f"(d[OFF + 1]), "+f"(d[OFF + 2]), "+f"(d[OFF + 3]), "+f"(d[OFF + 4]), "+f"(d[OFF + 5]),
        "+f"(d[OFF + 6]), "+f"(d[OFF + 7]), "+f"(d[OFF + 8]), "+f"(d[OFF + 9]), "+f"(d[OFF + 10]), "+f"(d[OFF + 11]),
        "+f"(d[OFF + 12]), "+f"(d[OFF + 13]), "+f"(d[OFF + 14]), "+f"(d[OFF + 15]), "+f"(d[OFF + 16]), "+f"(d[OFF + 17]),
        "+f"(d[OFF + 18]), "+f"(d[OFF + 19]), "+f"(d[OFF + 20]), "+f"(d[OFF + 21]), "+f"(d[OFF + 22]), "+f"(d[OFF + 23]),
        "+f"(d[OFF + 24]), "+f"(d[OFF + 25]), "+f"(d[OFF + 26]), "+f"(d[OFF + 27]), "+f"(d[OFF + 28]), "+f"(d[OFF + 29]),
        "+f"(d[OFF + 30]), "+f"(d[OFF + 31]), "+f"(d[OFF + 32]), "+f"(d[OFF + 33]), "+f"(d[OFF + 34]), "+f"(d[OFF + 35]),
        "+f"(d[OFF + 36]), "+f"(d[OFF + 37]), "+f"(d[OFF + 38]), "+f"(d[OFF + 39]), "+f"(d[OFF + 40]), "+f"(d[OFF + 41]),
        "+f"(d[OFF + 42]), "+f"(d[OFF + 43]), "+f"(d[OFF + 44]), "+f"(d[OFF + 45]), "+f"(d[OFF + 46]), "+f"(d[OFF + 47]),
        "+f"(d[OFF + 48]), "+f"(d[OFF + 49]), "+f"(d[OFF + 50]), "+f"(d[OFF + 51])
      : "r"(a0), "r"(a1), "r"(a2), "r"(a3), "l"(desc_b), "r"(scale_d), "r"(meta));
}

template <int OFF, int NN>
__device__ __forceinline__ void wg_s104z(float (&d)[NN], uint32_t a0, uint32_t a1, uint32_t a2, uint32_t a3,
                                       uint64_t desc_b, int scale_d, uint32_t meta) {
  asm volatile(
      "{\n.reg .pred p;\nsetp.ne.b32 p, %57, 0;\n"
      "wgmma.mma_async.sp.sync.aligned.m64n104k32.f32.bf16.bf16 "
      "{%0,%1,%2,%3,%4,%5,%6,%7,%8,%9,%10,%11,%12,%13,%14,%15,"
      "%16,%17,%18,%19,%20,%21,%22,%23,%24,%25,%26,%27,%28,%29,%30,%31,"
      "%32,%33,%34,%35,%36,%37,%38,%39,%40,%41,%42,%43,%44,%45,%46,%47,"
      "%48,%49,%50,%51}, "
      "{%52,%53,%54,%55}, %56, %58, 0, p, 1, 1, 0;\n}\n"
      : "=f"(d[OFF + 0]), "=f"(d[OFF + 1]), "=f"(d[OFF + 2]), "=f"(d[OFF + 3]), "=f"(d[OFF + 4]), "=f"(d[OFF + 5]),
        "=f"(d[OFF + 6]), "=f"(d[OFF + 7]), "=f"(d[OFF + 8]), "=f"(d[OFF + 9]), "=f"(d[OFF + 10]), "=f"(d[OFF + 11]),
        "=f"(d[OFF + 12]), "=f"(d[OFF + 13]), "=f"(d[OFF + 14]), "=f"(d[OFF + 15]), "=f"(d[OFF + 16]), "=f"(d[OFF + 17]),
        "=f"(d[OFF + 18]), "=f"(d[OFF + 19]), "=f"(d[OFF + 20]), "=f"(d[OFF + 21]), "=f"(d[OFF + 22]), "=f"(d[OFF + 23]),
        "=f"(d[OFF + 24]), "=f"(d[OFF + 25]), "=f"(d[OFF + 26]), "=f"(d[OFF + 27]), "=f"(d[OFF + 28]), "=f"(d[OFF + 29]),
        "=f"(d[OFF + 30]), "=f"(d[OFF + 31]), "=f"(d[OFF + 32]), "=f"(d[OFF + 33]), "=f"(d[OFF + 34]), "=f"(d[OFF + 35]),
        "=f"(d[OFF + 36]), "=f"(d[OFF + 37]), "=f"(d[OFF + 38]), "=f"(d[OFF + 39]), "=f"(d[OFF + 40]), "=f"(d[OFF + 41]),
        "=f"(d[OFF + 42]), "=f"(d[OFF + 43]), "=f"(d[OFF + 44]), "=f"(d[OFF + 45]), "=f"(d[OFF + 46]), "=f"(d[OFF + 47]),
        "=f"(d[OFF + 48]), "=f"(d[OFF + 49]), "=f"(d[OFF + 50]), "=f"(d[OFF + 51])
      : "r"(a0), "r"(a1), "r"(a2), "r"(a3), "l"(desc_b), "r"(scale_d), "r"(meta));
}

template <int OFF, int NN>
__device__ __forceinline__ void wg_s48(float (&d)[NN], uint32_t a0, uint32_t a1, uint32_t a2, uint32_t a3,
                                       uint64_t desc_b, int scale_d, uint32_t meta) {
  asm volatile(
      "{\n.reg .pred p;\nsetp.ne.b32 p, %29, 0;\n"
      "wgmma.mma_async.sp.sync.aligned.m64n48k32.f32.bf16.bf16 "
      "{%0,%1,%2,%3,%4,%5,%6,%7,%8,%9,%10,%11,%12,%13,%14,%15,"
      "%16,%17,%18,%19,%20,%21,%22,%23}, "
      "{%24,%25,%26,%27}, %28, %30, 0, p, 1, 1, 0;\n}\n"
      : "+f"(d[OFF + 0]), "+f"(d[OFF + 1]), "+f"(d[OFF + 2]), "+f"(d[OFF + 3]), "+f"(d[OFF + 4]), "+f"(d[OFF + 5]),
        "+f"(d[OFF + 6]), "+f"(d[OFF + 7]), "+f"(d[OFF + 8]), "+f"(d[OFF + 9]), "+f"(d[OFF + 10]), "+f"(d[OFF + 11]),
        "+f"(d[OFF + 12]), "+f"(d[OFF + 13]), "+f"(d[OFF + 14]), "+f"(d[OFF + 15]), "+f"(d[OFF + 16]), "+f"(d[OFF + 17]),
        "+f"(d[OFF + 18]), "+f"(d[OFF + 19]), "+f"(d[OFF + 20]), "+f"(d[OFF + 21]), "+f"(d[OFF + 22]), "+f"(d[OFF + 23])
      : "r"(a0), "r"(a1), "r"(a2), "r"(a3), "l"(desc_b), "r"(scale_d), "r"(meta));
}

template <int OFF, int NN>
__device__ __forceinline__ void wg_s48z(float (&d)[NN], uint32_t a0, uint32_t a1, uint32_t a2, uint32_t a3,
                                       uint64_t desc_b, int scale_d, uint32_t meta) {
  asm volatile(
      "{\n.reg .pred p;\nsetp.ne.b32 p, %29, 0;\n"
      "wgmma.mma_async.sp.sync.aligned.m64n48k32.f32.bf16.bf16 "
      "{%0,%1,%2,%3,%4,%5,%6,%7,%8,%9,%10,%11,%12,%13,%14,%15,"
      "%16,%17,%18,%19,%20,%21,%22,%23}, "
      "{%24,%25,%26,%27}, %28, %30, 0, p, 1, 1, 0;\n}\n"
      : "=f"(d[OFF + 0]), "=f"(d[OFF + 1]), "=f"(d[OFF + 2]), "=f"(d[OFF + 3]), "=f"(d[OFF + 4]), "=f"(d[OFF + 5]),
        "=f"(d[OFF + 6]), "=f"(d[OFF + 7]), "=f"(d[OFF + 8]), "=f"(d[OFF + 9]), "=f"(d[OFF + 10]), "=f"(d[OFF + 11]),
        "=f"(d[OFF + 12]), "=f"(d[OFF + 13]), "=f"(d[OFF + 14]), "=f"(d[OFF + 15]), "=f"(d[OFF + 16]), "=f"(d[OFF + 17]),
        "=f"(d[OFF + 18]), "=f"(d[OFF + 19]), "=f"(d[OFF + 20]), "=f"(d[OFF + 21]), "=f"(d[OFF + 22]), "=f"(d[OFF + 23])
      : "r"(a0), "r"(a1), "r"(a2), "r"(a3), "l"(desc_b), "r"(scale_d), "r"(meta));
}

template <int OFF, int NN>
__device__ __forceinline__ void wg_s56(float (&d)[NN], uint32_t a0, uint32_t a1, uint32_t a2, uint32_t a3,
                                       uint64_t desc_b, int scale_d, uint32_t meta) {
  asm volatile(
      "{\n.reg .pred p;\nsetp.ne.b32 p, %33, 0;\n"
      "wgmma.mma_async.sp.sync.aligned.m64n56k32.f32.bf16.bf16 "
      "{%0,%1,%2,%3,%4,%5,%6,%7,%8,%9,%10,%11,%12,%13,%14,%15,"
      "%16,%17,%18,%19,%20,%21,%22,%23,%24,%25,%26,%27}, "
      "{%28,%29,%30,%31}, %32, %34, 0, p, 1, 1, 0;\n}\n"
      : "+f"(d[OFF + 0]), "+f"(d[OFF + 1]), "+f"(d[OFF + 2]), "+f"(d[OFF + 3]), "+f"(d[OFF + 4]), "+f"(d[OFF + 5]),
        "+f"(d[OFF + 6]), "+f"(d[OFF + 7]), "+f"(d[OFF + 8]), "+f"(d[OFF + 9]), "+f"(d[OFF + 10]), "+f"(d[OFF + 11]),
        "+f"(d[OFF + 12]), "+f"(d[OFF + 13]), "+f"(d[OFF + 14]), "+f"(d[OFF + 15]), "+f"(d[OFF + 16]), "+f"(d[OFF + 17]),
        "+f"(d[OFF + 18]), "+f"(d[OFF + 19]), "+f"(d[OFF + 20]), "+f"(d[OFF + 21]), "+f"(d[OFF + 22]), "+f"(d[OFF + 23]),
        "+f"(d[OFF + 24]), "+f"(d[OFF + 25]), "+f"(d[OFF + 26]), "+f"(d[OFF + 27])
      : "r"(a0), "r"(a1), "r"(a2), "r"(a3), "l"(desc_b), "r"(scale_d), "r"(meta));
}

template <int OFF, int NN>
__device__ __forceinline__ void wg_s56z(float (&d)[NN], uint32_t a0, uint32_t a1, uint32_t a2, uint32_t a3,
                                       uint64_t desc_b, int scale_d, uint32_t meta) {
  asm volatile(
      "{\n.reg .pred p;\nsetp.ne.b32 p, %33, 0;\n"
      "wgmma.mma_async.sp.sync.aligned.m64n56k32.f32.bf16.bf16 "
      "{%0,%1,%2,%3,%4,%5,%6,%7,%8,%9,%10,%11,%12,%13,%14,%15,"
      "%16,%17,%18,%19,%20,%21,%22,%23,%24,%25,%26,%27}, "
      "{%28,%29,%30,%31}, %32, %34, 0, p, 1, 1, 0;\n}\n"
      : "=f"(d[OFF + 0]), "=f"(d[OFF + 1]), "=f"(d[OFF + 2]), "=f"(d[OFF + 3]), "=f"(d[OFF + 4]), "=f"(d[OFF + 5]),
        "=f"(d[OFF + 6]), "=f"(d[OFF + 7]), "=f"(d[OFF + 8]), "=f"(d[OFF + 9]), "=f"(d[OFF + 10]), "=f"(d[OFF + 11]),
        "=f"(d[OFF + 12]), "=f"(d[OFF + 13]), "=f"(d[OFF + 14]), "=f"(d[OFF + 15]), "=f"(d[OFF + 16]), "=f"(d[OFF + 17]),
        "=f"(d[OFF + 18]), "=f"(d[OFF + 19]), "=f"(d[OFF + 20]), "=f"(d[OFF + 21]), "=f"(d[OFF + 22]), "=f"(d[OFF + 23]),
        "=f"(d[OFF + 24]), "=f"(d[OFF + 25]), "=f"(d[OFF + 26]), "=f"(d[OFF + 27])
      : "r"(a0), "r"(a1), "r"(a2), "r"(a3), "l"(desc_b), "r"(scale_d), "r"(meta));
}

template <int OFF, int NN>
__device__ __forceinline__ void wg_s64t(float (&d)[NN], uint32_t a0, uint32_t a1, uint32_t a2, uint32_t a3,
                                       uint64_t desc_b, int scale_d, uint32_t meta) {
  asm volatile(
      "{\n.reg .pred p;\nsetp.ne.b32 p, %37, 0;\n"
      "wgmma.mma_async.sp.sync.aligned.m64n64k32.f32.bf16.bf16 "
      "{%0,%1,%2,%3,%4,%5,%6,%7,%8,%9,%10,%11,%12,%13,%14,%15,"
      "%16,%17,%18,%19,%20,%21,%22,%23,%24,%25,%26,%27,%28,%29,%30,%31}, "
      "{%32,%33,%34,%35}, %36, %38, 0, p, 1, 1, 1;\n}\n"
      : "+f"(d[OFF + 0]), "+f"(d[OFF + 1]), "+f"(d[OFF + 2]), "+f"(d[OFF + 3]), "+f"(d[OFF + 4]), "+f"(d[OFF + 5]),
        "+f"(d[OFF + 6]), "+f"(d[OFF + 7]), "+f"(d[OFF + 8]), "+f"(d[OFF + 9]), "+f"(d[OFF + 10]), "+f"(d[OFF + 11]),
        "+f"(d[OFF + 12]), "+f"(d[OFF + 13]), "+f"(d[OFF + 14]), "+f"(d[OFF + 15]), "+f"(d[OFF + 16]), "+f"(d[OFF + 17]),
        "+f"(d[OFF + 18]), "+f"(d[OFF + 19]), "+f"(d[OFF + 20]), "+f"(d[OFF + 21]), "+f"(d[OFF + 22]), "+f"(d[OFF + 23]),
        "+f"(d[OFF + 24]), "+f"(d[OFF + 25]), "+f"(d[OFF + 26]), "+f"(d[OFF + 27]), "+f"(d[OFF + 28]), "+f"(d[OFF + 29]),
        "+f"(d[OFF + 30]), "+f"(d[OFF + 31])
      : "r"(a0), "r"(a1), "r"(a2), "r"(a3), "l"(desc_b), "r"(scale_d), "r"(meta));
}

template <int OFF, int NN>
__device__ __forceinline__ void wg_s64t1(float (&d)[NN], uint32_t a0, uint32_t a1, uint32_t a2, uint32_t a3,
                                       uint64_t desc_b, int scale_d, uint32_t meta) {
  asm volatile(
      "{\n.reg .pred p;\nsetp.ne.b32 p, %37, 0;\n"
      "wgmma.mma_async.sp.sync.aligned.m64n64k32.f32.bf16.bf16 "
      "{%0,%1,%2,%3,%4,%5,%6,%7,%8,%9,%10,%11,%12,%13,%14,%15,"
      "%16,%17,%18,%19,%20,%21,%22,%23,%24,%25,%26,%27,%28,%29,%30,%31}, "
      "{%32,%33,%34,%35}, %36, %38, 1, p, 1, 1, 1;\n}\n"
      : "+f"(d[OFF + 0]), "+f"(d[OFF + 1]), "+f"(d[OFF + 2]), "+f"(d[OFF + 3]), "+f"(d[OFF + 4]), "+f"(d[OFF + 5]),
        "+f"(d[OFF + 6]), "+f"(d[OFF + 7]), "+f"(d[OFF + 8]), "+f"(d[OFF + 9]), "+f"(d[OFF + 10]), "+f"(d[OFF + 11]),
        "+f"(d[OFF + 12]), "+f"(d[OFF + 13]), "+f"(d[OFF + 14]), "+f"(d[OFF + 15]), "+f"(d[OFF + 16]), "+f"(d[OFF + 17]),
        "+f"(d[OFF + 18]), "+f"(d[OFF + 19]), "+f"(d[OFF + 20]), "+f"(d[OFF + 21]), "+f"(d[OFF + 22]), "+f"(d[OFF + 23]),
        "+f"(d[OFF + 24]), "+f"(d[OFF + 25]), "+f"(d[OFF + 26]), "+f"(d[OFF + 27]), "+f"(d[OFF + 28]), "+f"(d[OFF + 29]),
        "+f"(d[OFF + 30]), "+f"(d[OFF + 31])
      : "r"(a0), "r"(a1), "r"(a2), "r"(a3), "l"(desc_b), "r"(scale_d), "r"(meta));
}

template <int OFF, int NN>
__device__ __forceinline__ void wg_s64tz(float (&d)[NN], uint32_t a0, uint32_t a1, uint32_t a2, uint32_t a3,
                                       uint64_t desc_b, int scale_d, uint32_t meta) {
  asm volatile(
      "{\n.reg .pred p;\nsetp.ne.b32 p, %37, 0;\n"
      "wgmma.mma_async.sp.sync.aligned.m64n64k32.f32.bf16.bf16 "
      "{%0,%1,%2,%3,%4,%5,%6,%7,%8,%9,%10,%11,%12,%13,%14,%15,"
      "%16,%17,%18,%19,%20,%21,%22,%23,%24,%25,%26,%27,%28,%29,%30,%31}, "
      "{%32,%33,%34,%35}, %36, %38, 0, p, 1, 1, 1;\n}\n"
      : "=f"(d[OFF + 0]), "=f"(d[OFF + 1]), "=f"(d[OFF + 2]), "=f"(d[OFF + 3]), "=f"(d[OFF + 4]), "=f"(d[OFF + 5]),
        "=f"(d[OFF + 6]), "=f"(d[OFF + 7]), "=f"(d[OFF + 8]), "=f"(d[OFF + 9]), "=f"(d[OFF + 10]), "=f"(d[OFF + 11]),
        "=f"(d[OFF + 12]), "=f"(d[OFF + 13]), "=f"(d[OFF + 14]), "=f"(d[OFF + 15]), "=f"(d[OFF + 16]), "=f"(d[OFF + 17]),
        "=f"(d[OFF + 18]), "=f"(d[OFF + 19]), "=f"(d[OFF + 20]), "=f"(d[OFF + 21]), "=f"(d[OFF + 22]), "=f"(d[OFF + 23]),
        "=f"(d[OFF + 24]), "=f"(d[OFF + 25]), "=f"(d[OFF + 26]), "=f"(d[OFF + 27]), "=f"(d[OFF + 28]), "=f"(d[OFF + 29]),
        "=f"(d[OFF + 30]), "=f"(d[OFF + 31])
      : "r"(a0), "r"(a1), "r"(a2), "r"(a3), "l"(desc_b), "r"(scale_d), "r"(meta));
}

__device__ __forceinline__ int g2_inv(int ch) { return 32 * (ch >> 5) + 8 * ((ch >> 1) & 3) + 2 * ((ch >> 3) & 3) + (ch & 1); }
__host__ __device__ __forceinline__ uint32_t wimg_off(int n, int k) {
  return (uint32_t)(k >> 6) * kWChunk + (uint32_t)n * 128 + (uint32_t)((((k & 63) >> 3) ^ (n & 7)) << 4) + (k & 7) * 2;
}
__host__ __device__ constexpr int w2piece(int h, int c) { return c == 2 ? 2 + h : 4 * h + c; }
__device__ __forceinline__ uint32_t w2img_off(int n, int k) { return wimg_off(n % 96, k & 63) + w2piece(n >= 96, k >> 6) * (kWChunk / 2); }
__device__ __forceinline__ int qpix(int par, int t) {
  const int a = 2 * t + 13 * par - 6, b = t + 112 * par;
  return par ? min(a, b) : max(a, b);
}
__device__ __forceinline__ int woff(int par, int i, int r) {
  const int a = 99 * par + 6 - 8 * i;
  return par ? min(r, a) : max(r, a);
}

__device__ __forceinline__ void mma16816(float (&c)[4], uint32_t a0, uint32_t a1, uint32_t a2, uint32_t a3, uint32_t b0,
                                         uint32_t b1) {
  asm volatile(
      "mma.sync.aligned.m16n8k16.row.col.f32.bf16.bf16.f32 {%0,%1,%2,%3}, {%4,%5,%6,%7}, {%8,%9}, {%0,%1,%2,%3};"
      : "+f"(c[0]), "+f"(c[1]), "+f"(c[2]), "+f"(c[3])
      : "r"(a0), "r"(a1), "r"(a2), "r"(a3), "r"(b0), "r"(b1));
}

__device__ __forceinline__ void fold_w1(const int u, const __nv_bfloat16* __restrict__ wqkv, uint8_t* wimg) {
  const int g = (threadIdx.x >> 2) & 7, l = threadIdx.x & 3;
  const int m0 = (u / 12) * 16, s = u % 12;
  uint4 A[12], B[12];
  const __nv_bfloat16* arow = wqkv + (m0 + 4 * (g >> 1) + (g & 1)) * 576 + 192 + 8 * l;
  const __nv_bfloat16* brow = wqkv + (16 * s + 4 * (g >> 1) + (g & 1)) * 576 + 8 * l;
#pragma unroll
  for (int i = 0; i < 12; i++) {
    A[i] = ldg128_nc(arow + (i & 1) * 2 * 576 + 32 * (i >> 1));
    B[i] = ldg128_nc(brow + (i & 1) * 2 * 576 + 32 * (i >> 1));
  }
  sched_fence();
  uint8_t* dst = wimg + wimg_off(m0 + g, 16 * s + 4 * l);
  float acc[4][4];
#pragma unroll
  for (int j = 0; j < 16; j++) acc[j >> 2][j & 3] = 0.f;
#pragma unroll
  for (int i = 0; i < 6; i++) {
    const uint4 &a0 = A[2 * i], &a1 = A[2 * i + 1];
#pragma unroll
    for (int nb = 0; nb < 2; nb++) {
      mma16816(acc[2 * nb], a0.x, a1.x, a0.y, a1.y, B[2 * i + nb].x, B[2 * i + nb].y);
      mma16816(acc[2 * nb + 1], a0.z, a1.z, a0.w, a1.w, B[2 * i + nb].z, B[2 * i + nb].w);
    }
  }
#pragma unroll
  for (int j = 0; j < 2; j++) {
    const uint2 v = make_uint2(pack_bf16((acc[0][2 * j] + acc[1][2 * j]) * kAlpha, (acc[0][2 * j + 1] + acc[1][2 * j + 1]) * kAlpha),
                               pack_bf16((acc[2][2 * j] + acc[3][2 * j]) * kAlpha, (acc[2][2 * j + 1] + acc[3][2 * j + 1]) * kAlpha));
    asm volatile("st.relaxed.gpu.global.v2.u32 [%0], {%1,%2};" ::"l"(dst + j * 1024), "r"(v.x), "r"(v.y) : "memory");
  }
}
__device__ __forceinline__ void fold_w2(const int u, const __nv_bfloat16* __restrict__ wqkv, const __nv_bfloat16* __restrict__ wo,
                                        uint8_t* wimg) {
  const int g = (threadIdx.x >> 2) & 7, l = threadIdx.x & 3;
  const int m0 = (u / 12) * 32, n0 = (u % 12) * 16;
  uint4 S[12];
  uint32_t L[96];
  const __nv_bfloat16* brow = wqkv + (n0 + 4 * (g >> 1) + (g & 1)) * 576 + 384 + 8 * l;
#pragma unroll
  for (int i = 0; i < 12; i++) S[i] = ldg128_nc(brow + (i & 1) * 2 * 576 + 32 * (i >> 1));
  const __nv_bfloat16* acol = wo + (8 * l) * 192 + m0 + 4 * g;
#pragma unroll
  for (int c = 0; c < 48; c++)
    asm volatile("ld.global.nc.v2.u32 {%0,%1}, [%2];" : "=r"(L[2 * c]), "=r"(L[2 * c + 1]) : "l"(acol + (32 * (c >> 3) + (c & 7)) * 192));
  const uint32_t off = w2_offset();
  sched_fence();
  uint8_t* img = wimg + off;
  float acc[4][4];
#pragma unroll
  for (int j = 0; j < 16; j++) acc[j >> 2][j & 3] = 0.f;
#pragma unroll
  for (int i = 0; i < 6; i++) {
#pragma unroll
    for (int h = 0; h < 2; h++) {
      const uint4 &s0 = S[2 * i], &s1 = S[2 * i + 1];
#pragma unroll
      for (int mt = 0; mt < 2; mt++) {
        const uint32_t* a = L + 16 * i + 8 * h + mt;
        const uint32_t a0 = __byte_perm(a[0], a[2], 0x5410), a1 = __byte_perm(a[0], a[2], 0x7632);
        const uint32_t a2 = __byte_perm(a[4], a[6], 0x5410), a3 = __byte_perm(a[4], a[6], 0x7632);
        mma16816(acc[2 * mt], a0, a1, a2, a3, h ? s0.z : s0.x, h ? s0.w : s0.y);
        mma16816(acc[2 * mt + 1], a0, a1, a2, a3, h ? s1.z : s1.x, h ? s1.w : s1.y);
      }
    }
  }
#pragma unroll
  for (int j = 0; j < 4; j++) {
    const float(&c0)[4] = acc[j & 2];
    const float(&c1)[4] = acc[(j & 2) + 1];
    asm volatile("st.relaxed.gpu.global.v2.u32 [%0], {%1,%2};" ::"l"(img + w2img_off(g2_inv(m0 + 4 * g + j), n0 + 4 * l)),
                 "r"(pack_bf16(c0[2 * (j & 1)], c0[2 * (j & 1) + 1])), "r"(pack_bf16(c1[2 * (j & 1)], c1[2 * (j & 1) + 1])) : "memory");
  }
}

__global__ void __launch_bounds__(256) fold_kernel(const __nv_bfloat16* __restrict__ wqkv,
                                                   const __nv_bfloat16* __restrict__ wo, uint8_t* wimg) {
  const int u = blockIdx.x * 8 + (threadIdx.x >> 5);
  if (u < 144) fold_w1(u, wqkv, wimg);
  else fold_w2(u - 144, wqkv, wo, wimg);
}

struct TileCoord { int pr, pc, I, J, up, kind; };
struct TileTable { uint16_t e[kCtas * 6], g[6][8][2]; };
inline void make_tiles(TileTable& tt) {
  for (int tile = 0; tile < kCtas * 6; tile++) {
    const int b = tile / 6, k = tile - 6 * b;
    const int p = b < 128 ? (tile - 672) >> 1 : b - 80;
    const int strip = b < 112 ? b >> 1 : b >= 128 && k >= 2 ? (b & 1) * 27 + (b & 2) * 14 : p + (p < 26 ? 1 : 3);
    const int pr = strip >= 28, J = (strip - pr * 28) >> 1, pc = strip & 1, up = b < 112 ? b & 1 : pr;
    const int first = b < 112 ? 8 - 2 * pr - up : 13 * pr, step = b < 112 ? k : k & 1;
    const int I = up ? first - step : first + step;
    const int kind = b < 112 ? (J == 13 * pc ? 1 + pc : 0) : I == 13 * pr ? 4 + pr : 3;
    tt.e[tile] = (uint16_t)(I | J << 4 | pr << 8 | pc << 9 | up << 10 | kind << 11);
  }
  for (int kind = 0; kind < 6; kind++)
    for (int j = 0; j < 8; j++) {
      const int w = j >> 1, h = j & 1, e = kind % 3;
      auto off = [e](int t) { return e == 0 ? 2 * t : e == 1 ? t + (t == 7) : t + (t > 0); };
      tt.g[kind][j][0] = (uint16_t)(kind < 3 ? 3 * off(w + 4 * h) : 3 * (kW * off(2 * w) + 8 * h));
      tt.g[kind][j][1] = (uint16_t)(128 * (kind < 3 ? kind > 0 : 1 + off(2 * w + 1) - off(2 * w)));
    }
}
__device__ __forceinline__ int num_tiles() { return blockIdx.x < 128 ? 6 : 4; }
__device__ __forceinline__ TileCoord decode_tile(const TileTable& tt, int tile) {
  const uint32_t e = tt.e[tile];
  return TileCoord{(int)(e >> 8) & 1, (int)(e >> 9) & 1, (int)e & 15, (int)(e >> 4) & 15, (int)(e >> 10) & 1, (int)(e >> 11)};
}
__device__ __forceinline__ int halo_r0(const TileCoord& t) { return 8 * t.I + 6 * t.pr - 6; }
__device__ __forceinline__ int halo_c0(const TileCoord& t) { return min(max(8 * t.J + 6 * t.pc - 6, -3), 102); }

__device__ __forceinline__ uint32_t bar_full(uint32_t bars, int wg, int c) { return bars + (wg * 3 + c) * 8; }
__device__ __forceinline__ uint32_t bar_w1c(uint32_t bars, int c) { return bars + (6 + c) * 8; }
__device__ __forceinline__ uint32_t bar_w2(uint32_t bars) { return bars + 9 * 8; }
__device__ __forceinline__ uint32_t bar_x(uint32_t bars, int j) { return bars + (10 + j) * 8; }
__device__ __forceinline__ uint32_t bar_w1q(uint32_t bars) { return bars + 12 * 8; }
__device__ __forceinline__ uint32_t bar_xf(uint32_t bars) { return bars + 13 * 8; }
__device__ __forceinline__ uint32_t bar_w2m(uint32_t bars) { return bars + 14 * 8; }
__device__ __forceinline__ uint32_t bar_redo(uint32_t bars) { return bars + 15 * 8; }
__device__ __forceinline__ uint32_t bar_wok(uint32_t bars) { return bars + 16 * 8; }
__device__ __forceinline__ uint32_t bar_go(uint32_t bars, int j) { return bars + (17 + j) * 8; }
__device__ __forceinline__ uint32_t bar_raw(uint32_t bars) { return bars + 19 * 8; }
__device__ __forceinline__ uint32_t bar_w2a(uint32_t bars) { return bars + 20 * 8; }
constexpr int kNumBars = 21;

__device__ __forceinline__ uint64_t wdesc(uint64_t d0, int s) { return d0 + (((s >> 2) * kWChunk + (s & 3) * 32) >> 4); }

__device__ __forceinline__ int qrow(int w, int g) { return blockIdx.x < 112 ? g : 2 * w + (g & 1); }
__device__ __forceinline__ int qcol(int w, int g) { return blockIdx.x < 112 ? w : g >> 1; }
__device__ __forceinline__ uint32_t out_slot(int k, int nt) { return k + 1 < nt ? kW2Off + (~k & 1) * 2 * kWChunk : kW1Off + kWChunk; }
__device__ __forceinline__ bool edge_strip() {
  const int s = blockIdx.x >> 1;
  return s == 0 || s == 27 || s == 28 || s == 55;
}
template <int I0, int I1>
__device__ __forceinline__ void store_rows(bool on, __nv_bfloat16* pA, __nv_bfloat16* pB, const uint32_t (&a)[24], const uint32_t (&b)[24]) {
#pragma unroll
  for (int i = 2 * I0; i < 2 * I1; i++) {
    const uint32_t* v = (i & 1 ? b : a) + 4 * (i >> 1);
    asm volatile("{\n.reg .pred p;\nsetp.ne.u32 p, %5, 0;\n@p st.global.v4.u32 [%0], {%1,%2,%3,%4};\n}\n" ::"l"((i & 1 ? pB : pA) + 32 * (i >> 1)),
                 "r"(v[0]), "r"(v[1]), "r"(v[2]), "r"(v[3]), "r"((uint32_t)on) : "memory");
  }
}
template <int I0, int I1>
__device__ __forceinline__ void stage_out(uint32_t sts, int wg, const uint32_t (&a)[24], const uint32_t (&b)[24]) {
  const uint32_t e = sts, o = sts ^ 64;
  const uint32_t ad[4] = {wg ? o + 1024 : e, wg ? e + 2048 : o, wg ? e : o + 1024, wg ? o : e + 2048};
#pragma unroll
  for (int i = I0; i < I1; i++) {
    const uint32_t* v = (i < 6 ? a : b) + 4 * (i % 6);
    asm volatile("st.shared.v4.u32 [%0], {%1,%2,%3,%4};" ::"r"(ad[i % 6 / 3 * 2 + (i % 3 == 1)] + (i % 3 == 2) * 1024 + (i / 6) * 12288),
                 "r"(v[0]), "r"(v[1]), "r"(v[2]), "r"(v[3]) : "memory");
  }
}
__device__ __forceinline__ uint32_t now_ns() {
  uint32_t t;
  asm volatile("mov.u32 %0, %globaltimer_lo;" : "=r"(t)::"memory");
  return t;
}
__device__ __forceinline__ void wait_clock(uint32_t t_start, uint32_t t) {
  while (now_ns() - t_start < t) { }
}
#define NAT_PRED(f, m) ".reg .pred p;\n.reg .b32 t;\nand.b32 t, " f ", " m ";\nsetp.ne.u32 p, t, 0;\n"
constexpr uint32_t kHiV = 1, kHiU = 8, kColB = 0x20, kInV = 0x100, kInU = 0x1000, kColA = 0x10000;
template <uint32_t M>
__device__ __forceinline__ float pick(const float* a, const float* b, uint32_t f) {
  float d;
  asm("{\n" NAT_PRED("%5", "%6") "add.f32 %0, %1, %2;\n@p add.f32 %0, %3, %4;\n}\n"
      : "=&f"(d) : "f"(a[0]), "f"(a[2]), "f"(b[0]), "f"(b[2]), "r"(f), "n"(M));
  return d;
}
template <uint32_t M>
__device__ __forceinline__ float sel(float a, float b, uint32_t f) {
  float d;
  asm("{\n" NAT_PRED("%3", "%4") "selp.f32 %0, %1, %2, p;\n}\n" : "=f"(d) : "f"(a), "f"(b), "r"(f), "n"(M));
  return d;
}
template <uint32_t M>
__device__ __forceinline__ void max_if(float& m, float v, uint32_t f) {
  asm("{\n" NAT_PRED("%2", "%3") "@p max.f32 %0, %0, %1;\n}\n" : "+f"(m) : "f"(v), "r"(f), "n"(M));
}
template <uint32_t M>
__device__ __forceinline__ void add_if(float& m, float v, uint32_t f) {
  asm("{\n" NAT_PRED("%2", "%3") "@p add.f32 %0, %0, %1;\n}\n" : "+f"(m) : "f"(v), "r"(f), "n"(M));
}
__device__ __forceinline__ void pick_v(const float* a, float* v, uint32_t f) {
  v[0] = pick<kHiV>(a, a + 16, f), v[1] = pick<kHiV>(a + 1, a + 17, f);
  v[2] = pick<kHiV * 2>(a + 4, a + 20, f), v[3] = pick<kHiV * 2>(a + 5, a + 21, f);
  v[4] = pick<kHiV * 4>(a + 8, a + 24, f), v[5] = pick<kHiV * 4>(a + 9, a + 25, f);
  v[6] = a[12] + a[14], v[7] = a[13] + a[15];
}
__device__ __forceinline__ void pick_u(const float* a, float* v, uint32_t f) {
#pragma unroll
  for (int c = 0; c < 3; c++) v[2 * c] = pick<kHiU>(a + 4 * c, a + 4 * c + 12, f), v[2 * c + 1] = pick<kHiU * 2>(a + 4 * c + 1, a + 4 * c + 13, f);
}
__device__ __forceinline__ uint32_t sign_bytes(uint32_t v, uint32_t sel) {
  uint32_t d;
  asm("prmt.b32 %0, %1, %1, %2;" : "=r"(d) : "r"(v), "r"(sel));
  return d;
}
__device__ __forceinline__ float own_max(const float (&v)[14], uint32_t f) {
  float m = sel<kInV>(fmaxf(v[0], v[1]), -INFINITY, f), m2 = sel<kInV * 2>(fmaxf(v[2], v[3]), -INFINITY, f);
  max_if<kInV * 4>(m, fmaxf(v[4], v[5]), f);
  max_if<kInV * 8>(m2, fmaxf(v[6], v[7]), f);
  max_if<kInU>(m, fmaxf(fmaxf(v[8], v[10]), v[12]), f);
  max_if<kInU * 2>(m2, fmaxf(fmaxf(v[9], v[11]), v[13]), f);
  return fmaxf(m, m2);
}
__device__ __forceinline__ float quad_max(float m) {
  const float a = __shfl_xor_sync(0xffffffffu, m, 1), b = __shfl_xor_sync(0xffffffffu, m, 2), c = __shfl_xor_sync(0xffffffffu, m, 3);
  return fmaxf(fmaxf(m, a), fmaxf(b, c));
}
__device__ __forceinline__ float row_rcp(const float (&v)[14], uint32_t f) {
  float s = sel<kInV>(v[0] + v[1], 0.f, f), s2 = sel<kInV * 2>(v[2] + v[3], 0.f, f);
  add_if<kInV * 4>(s, v[4] + v[5], f);
  add_if<kInV * 8>(s2, v[6] + v[7], f);
  add_if<kInU>(s, v[8] + v[10] + v[12], f);
  add_if<kInU * 2>(s2, v[9] + v[11] + v[13], f);
  s += s2;
  const float a = __shfl_xor_sync(0xffffffffu, s, 1), b = __shfl_xor_sync(0xffffffffu, s, 2), c = __shfl_xor_sync(0xffffffffu, s, 3);
  return rcp_approx((s + a) + (b + c));
}
__device__ __forceinline__ void route(const float (&v)[14], float s, const uint32_t (&rt)[9], uint32_t (&p)[14]) {
#pragma unroll
  for (int i = 0; i < 7; i++) {
    const uint32_t u = pack_bf16(v[2 * i] * s, v[2 * i + 1] * s);
    if (i < 4) p[i] = u & rt[i];
    if (i < 3) p[i + 4] = u & rt[i + 4];
    if (i >= 4) {
      p[i + 3] = u & rt[7];
      p[i + 6] = u & rt[8];
    }
  }
}

template <int C, int T0 = 0, int T1 = 7>
__device__ __forceinline__ void pv_chunk(float (&z)[32], const uint32_t (&pa)[14], const uint32_t (&pb)[14],
                                         const uint32_t (&meta)[4], uint64_t dV) {
#pragma unroll
  for (int t = T0; t < T1; t++) {
    if (t & 1)
      wg_s64t1<0, 32>(z, pa[2 * t], pb[2 * t], pa[2 * t + 1], pb[2 * t + 1], dV + ((2 * C * kChunkBytes + t * 2048) >> 4), 1,
                      meta[t >> 1]);
    else if (t > 0)
      wg_s64t<0, 32>(z, pa[2 * t], pb[2 * t], pa[2 * t + 1], pb[2 * t + 1], dV + ((2 * C * kChunkBytes + t * 2048) >> 4), 1,
                     meta[t >> 1]);
    else
      wg_s64tz<0, 32>(z, pa[0], pb[0], pa[1], pb[1], dV + ((2 * C * kChunkBytes) >> 4), 0, meta[0]);
  }
}
template <int C>
__device__ __forceinline__ void pack_z(const float (&z)[32], uint32_t (&za)[24], uint32_t (&zb)[24]) {
#pragma unroll
  for (int j = 0; j < 8; j++) {
    za[8 * C + j] = pack_bf16(z[4 * j], z[4 * j + 1]);
    zb[8 * C + j] = pack_bf16(z[4 * j + 2], z[4 * j + 3]);
  }
}

template <int H>
__device__ __forceinline__ void pack_out(const float (&ac)[48], uint32_t (&oa)[24], uint32_t (&ob)[24]) {
#pragma unroll
  for (int j = 0; j < 12; j++) {
    oa[12 * H + j] = pack_bf16(ac[4 * j], ac[4 * j + 1]);
    ob[12 * H + j] = pack_bf16(ac[4 * j + 2], ac[4 * j + 3]);
  }
}
struct Maps { CUtensorMap v6, v2, v14, u8, px[8], wv, wo; };
__device__ __forceinline__ void tma_prefetch_5d(const CUtensorMap* map, int c0, int c1, int c2, int c3, int c4) {
  asm volatile("cp.async.bulk.prefetch.tensor.5d.L2.global.tile [%0, {%1, %2, %3, %4, %5}];" ::"l"((uint64_t)map), "r"(c0), "r"(c1),
               "r"(c2), "r"(c3), "r"(c4) : "memory");
}
__device__ __forceinline__ int first_line(const TileCoord tc) { return 3 * (qpix(tc.pr, 8 * tc.I) * kW + qpix(tc.pc, 8 * tc.J)); }
template <int MODE, int UNROLL, int N = 8>
__device__ __forceinline__ void move_px(const Maps& tm, const TileTable& tt, uint32_t buf, uint32_t bar, int line, int kind, int i0 = 0) {
#pragma unroll UNROLL
  for (int n = 0; n < N; n++) {
    const int i = i0 + n;
    const int j = MODE == 2 ? 2 * (i & 3) + (i >> 2) : i;
    if (MODE == 2 || (n & 1) == 0 || kind != 0) {
      const CUtensorMap* map = (const CUtensorMap*)((const char*)(tm.px + (MODE & 2) * 2) + tt.g[kind][j][1]);
      const int ln = line + tt.g[kind][j][0];
      if (MODE == 0) tma_load_5d(buf + i * 3072, map, bar, 0, 0, 0, 0, ln);
      if (MODE == 1) tma_prefetch_5d(map, 0, 0, 0, 0, ln);
      if (MODE == 2)
        asm volatile("cp.async.bulk.tensor.5d.global.shared::cta.tile.bulk_group [%0, {%2, %2, %2, %2, %3}], [%1];" ::"l"((uint64_t)map),
                     "r"(buf + i * 3072), "r"(0), "r"(ln) : "memory");
      if (MODE == 2 && NAT_SP < 9) {
        asm volatile("cp.async.bulk.commit_group;" ::: "memory");
        asm volatile("cp.async.bulk.wait_group.read %0;" ::"n"(NAT_SP) : "memory");
      }
    }
  }
  if (MODE == 2) asm volatile("cp.async.bulk.commit_group;" ::: "memory");
}
__device__ __noinline__ bool refetch(uint32_t base, const uint8_t* src, bool gap) {
  constexpr uint32_t bars = 1024 + kBarOff, cnt = bars + 192;
#pragma unroll 1
  for (uint32_t o = 0; o < kWBytes && !gap; o += 2048) {
    uint32_t mx = 0;
#pragma unroll
    for (int i = 0; i < 4; i++) {
      uint4 v;
      asm volatile("ld.shared.v4.u32 {%0,%1,%2,%3}, [%4];" : "=r"(v.x), "=r"(v.y), "=r"(v.z), "=r"(v.w)
                   : "r"(base + o + i * 512 + (threadIdx.x & 31) * 16));
      mx = __vimax3_u32(__vimax3_u32(mx, v.x, v.y), v.z, v.w);
    }
    gap = __any_sync(0xffffffffu, mx == kEmpty);
  }
  uint32_t n;
  asm volatile("ld.shared.u32 %0, [%1];" : "=r"(n) : "r"(cnt) : "memory");
  if (!gap || __any_sync(0xffffffffu, n > (1u << 12))) return false;
  asm volatile("bar.sync 15, 128;" ::: "memory");
  if (threadIdx.x == 0) {
    asm volatile("st.shared.u32 [%0], %1;" ::"r"(cnt), "r"(n + 1) : "memory");
    mbar_arrive_expect_tx(bar_redo(bars), kWBytes);
    bulk_load(base, src, kWBytes, bar_redo(bars));
  }
  __syncwarp();
  mbar_wait(bar_redo(bars), n & 1);
  return true;
}
template <int S0, int S1, int Z>
__device__ __forceinline__ void g2_steps(float (&ac)[48], const uint32_t (&za)[24], const uint32_t (&zb)[24], uint64_t d) {
#pragma unroll
  for (int s = S0; s < S1; s++) {
    const uint64_t ds = d + (((s >> 2 & 1) * (kWChunk / 2) + (s & 3) * 32) >> 4);
    if (s == Z) wg_d96z<0, 48>(ac, za[2 * s], zb[2 * s], za[2 * s + 1], zb[2 * s + 1], ds, 0);
    else wg_d96<0, 48>(ac, za[2 * s], zb[2 * s], za[2 * s + 1], zb[2 * s + 1], ds, 1);
  }
}

__device__ __forceinline__ void consumer(const int wg, __nv_bfloat16* out, const uint8_t* wimg, const uint32_t sbase,
                                         const uint32_t zero, const Maps& tm, const TileTable& tt) {
  const int tid = threadIdx.x & 127;
  const int w = __shfl_sync(0xffffffffu, tid >> 5, 0), lane = tid & 31, g = qrow(w, lane >> 2), qc = qcol(w, lane >> 2);
  const uint64_t dK = make_desc(sbase, 16, 1024);
  const uint64_t dV = make_desc(sbase, kChunkBytes, 512, 2);
  const uint64_t dW1 = make_desc(sbase + kW1Off, 16, 1024);
  const uint64_t dX0 = make_desc(sbase + kW2Off + wg * 2 * kWChunk, 16, 1024), dY0 = make_desc(sbase + kW2Off + (1 - wg) * 2 * kWChunk, 16, 1024);
  const uint64_t dX2 = make_desc(sbase + kXOff + wg * (kWChunk / 2), 16, 1024), dY2 = make_desc(sbase + kXOff + (1 - wg) * (kWChunk / 2), 16, 1024);
  const uint32_t bars = sbase + kBarOff;
  int tile0 = blockIdx.x * kTilesPerCta;
  asm volatile("" : "+r"(tile0));
  const int nt = num_tiles();

  uint32_t pix = 0, geo[12] = {};
  const int l = lane & 3;
#pragma unroll 1
  for (int j = 4; j >= 0; j -= 2) {
    const TileCoord tc = decode_tile(tt, tile0 + wg + j);
    const uint32_t pr = qpix(tc.pr, 8 * tc.I + g) * kW;
    if (j == nt - 2) pix = (pr + qpix(tc.pc, 8 * tc.J + qc)) | (pr + qpix(tc.pc, 8 * tc.J + qc + 4)) << 16;
    const int d = 8 * tc.J + 6 * tc.pc - 6 - halo_c0(tc);
    const int ro = woff(tc.pr, tc.I, g), coA = woff(tc.pc, tc.J, qc) + d, coB = woff(tc.pc, tc.J, qc + 4) + d - 3;
#pragma unroll
    for (int i = 11; i >= 4; i--) geo[i] = geo[i - 4];
    const uint32_t lr = 0x1FCu << ro;
    const uint32_t lv = lr >> (2 + (l >> 1)), lu = lr >> (2 * l + 2 * tc.up);
    const uint32_t t = __byte_perm(lv, lu, wg ? 0x4501 : 0x5410);
    geo[0] = ((t & 0x15u) | (lv & 0x40u)) * 0x02082080u;
    geo[1] = ((t >> 8) & 0x15u) * 0x02082080u;
    geo[2] = __byte_perm(t << 7, t << 6, 0x7362);
    const int dr = (ro - 1) & 7;
    const uint32_t hiv = (((1u << ((ro - (l >> 1) + 1) >> 1)) - 1u) ^ (wg ? 7u : 0u)) & 7u, hiu = (t >> 24) & 3u;
    const uint32_t ca = (1u << coA) - 1u;
    geo[3] = hiv * kHiV | hiu * kHiU | ((((1u << coB) - 1u) >> (2 * (l & 1))) & 3u) * kColB |
             (15u & ~((uint32_t)((dr & 1) == (l >> 1)) << (dr >> 1))) * kInV | ((t >> 16 | t >> 24) & 3u) * kInU | ca * kColA |
             (ca >> ((0x49 >> (2 * l)) & 3) & 1u) << 19 | (uint32_t)(l == 3) << 20 | (0x55u & ((1u << (2 * coB)) - 1u)) << 24;
  }
  keep_regs(geo);
  const int so = (lane >> 3) | (lane & 4);
  uint32_t sts = sbase + w * 3072 + so * 128 + (((lane & 3) ^ so) << 4);
  __nv_bfloat16* poA = out + 8 * l + (pix & 0xFFFFu) * kC + 96 * wg;
  __nv_bfloat16* poB = out + 8 * l + (pix >> 16) * kC + 96 * wg;
  asm volatile("" : "+l"(poA), "+l"(poB), "+r"(sts));
  uint32_t oa[24], ob[24];
#pragma unroll
  for (int j = 0; j < 24; j++) oa[j] = ob[j] = 0u;
  keep_regs(oa);
  keep_regs(ob);
  PROF(wg, 0);
  if (threadIdx.x == 0) GT(1);

  for (int k = wg; k < nt; k += 2) {
    const uint32_t ph = (k >> 1) & 1;
    const int it = k >> 1;
    uint32_t qa[24], qb[24], hok[3];
    uint32_t fl = geo[3];
    {
      float acc[96];
      const uint64_t dX = make_desc(sbase + kXOff + (k == 0 ? kWChunk : 0), 16, 3072);
      if (k > 0) nb_sync(1 + (1 - wg));
      mbar_wait(bar_x(bars, k > 0), (k + (k > 0)) & 1);
      if (k < 2) PROF(wg, 1);
      PROFS(2, wg, 2 + it * 12);
      if (w == 0 && k < 2) GT(20 + wg);
#pragma unroll
      for (int s = 0; s < 12; s++) {
        if ((s & 3) == 0 && k == 0) {
          mbar_wait(bar_w1c(bars, s >> 2), 0);
          PROFS(17, wg, 50 + (s >> 2));
        }
        if ((s & 3) == 0) wg_fence();
        if (s == 0) wg_m192z<0, 96>(acc, dX, dW1, 0);
        else wg_m192<0, 96>(acc, dX + (((s >> 2) * 1024 + (s & 3) * 32) >> 4), wdesc(dW1, s), 1);
      }
      wg_commit();
      PROFS(13, wg, 13 + it * 12);
      wg_wait<0>();
      if (k > 0) nb_arrive_p(6);
      fence_regs(acc);
      PROFS(3, wg, 3 + it * 12);
#pragma unroll
      for (int j = 0; j < 24; j++) {
        qa[j] = pack_bf16(acc[4 * j], acc[4 * j + 1]);
        qb[j] = pack_bf16(acc[4 * j + 2], acc[4 * j + 3]);
      }
      keep_regs(qa);
      keep_regs(qb);
      sched_fence();
      if (k >= 2) {
        const uint32_t dst = sts + out_slot(k, nt);
        nb_sync(11);
        stage_out<0, 6>(dst, wg, oa, ob);
        nb_sync(12);
        stage_out<6, 12>(dst, wg, oa, ob);
      }
#pragma unroll
      for (int c = 0; c < 3; c++) hok[c] = mbar_test(bar_full(bars, wg, c), ph);
      if (k >= 2) {
        fence_proxy_async();
        nb_arrive_p(10);
      }
    }

    float aE[52], aO[24], bO[52], bE[28];
    const uint32_t mq = 0xEEEE4444u | zero;
    PROFS(4, wg, 4 + it * 12);

    mbar_wait_if(hok[0], bar_full(bars, wg, 0), ph);
    PROFS(14, wg, 40 + it * 3);
    if (w == 0 && k < 2) GT(22 + wg);
    if (k > 0) nb_sync(3 + (1 - wg));
    wg_fence();
#pragma unroll
    for (int ks = 0; ks < 6; ks++) {
      if (ks == NAT_P1) {
        mbar_wait_if(hok[1], bar_full(bars, wg, 1), ph);
        PROFS(14, wg, 41 + it * 3);
        wg_fence();
      }
      if (ks == NAT_P2) {
        mbar_wait_if(hok[2], bar_full(bars, wg, 2), ph);
        PROFS(14, wg, 42 + it * 3);
        wg_fence();
      }
      const uint64_t d = dK + ((ks * kChunkBytes) >> 4);
      if (ks == 0) wg_s104z<0, 52>(aE, qa[0], qa[1], qa[2], qa[3], d, 0, mq);
      else wg_s104<0, 52>(aE, qa[4 * ks], qa[4 * ks + 1], qa[4 * ks + 2], qa[4 * ks + 3], d, 1, mq);
    }
    wg_commit();
    wg_s48z<0, 24>(aO, qa[0], qa[1], qa[2], qa[3], dK + ((7 * 1024 + 64) >> 4), 0, mq);
#pragma unroll
    for (int ks = 1; ks < 6; ks++)
      wg_s48<0, 24>(aO, qa[4 * ks], qa[4 * ks + 1], qa[4 * ks + 2], qa[4 * ks + 3], dK + ((ks * kChunkBytes + 7 * 1024 + 64) >> 4), 1, mq);
    wg_commit();
    wg_s56z<0, 28>(bE, qb[0], qb[1], qb[2], qb[3], dK, 0, mq);
#pragma unroll
    for (int ks = 1; ks < 6; ks++) wg_s56<0, 28>(bE, qb[4 * ks], qb[4 * ks + 1], qb[4 * ks + 2], qb[4 * ks + 3], dK + ((ks * kChunkBytes) >> 4), 1, mq);
    wg_commit();
    wg_wait<2>();
    fence_regs(aE);
    PROFS(5, wg, 5 + it * 12);

    uint32_t pa[14], pb[14], meta[4];
    {
      float vA[14], vB[14];
      pick_v(aE, vA, fl);
      pick_u(aE + 28, vA + 8, fl);
      fence_regs(vA);
      if (k == 0) {
        if (__builtin_expect(__any_sync(0xffffffffu, vA[6] != vA[6]), 0)) {
          wg_wait<0>();
          fence_regs(aO);
          fence_regs(bE);
          if (refetch(sbase + kW1Off, wimg, false)) {
#pragma unroll
            for (int j = 0; j < 24; j++) oa[j] = ob[j] = 0u;
            k -= 2;
            continue;
          }
        }
        if (elect_one()) mbar_arrive(bar_xf(bars));
      }
      wg_fence();
      wg_s104z<0, 52>(bO, qb[0], qb[1], qb[2], qb[3], dK + 4, 0, mq);
#pragma unroll
      for (int ks = 1; ks < 6; ks++)
        wg_s104<0, 52>(bO, qb[4 * ks], qb[4 * ks + 1], qb[4 * ks + 2], qb[4 * ks + 3], dK + ((ks * kChunkBytes + 64) >> 4), 1, mq);
      wg_commit();
      if (k + 1 < nt) nb_arrive(1 + wg);
      uint32_t rt[9];
#pragma unroll
      for (int i = 0; i < 7; i++) rt[i] = sign_bytes(geo[i >> 2], 0x8888u + 0x1111u * (i & 3));
      rt[7] = sign_bytes(geo[2], 0x9988u);
      rt[8] = sign_bytes(geo[2], 0xBBAAu);
      keep_regs(rt);
      pa[13] = pb[13] = 0u;
      wg_wait<2>();
      keep_regs(qa);
      fence_regs(aO);
      float oA[6], eB[8];
      pick_u(aO, oA, fl);
      wg_wait<1>();
      fence_regs(bE);
      pick_v(bE, eB, fl);
      vA[8] = sel<kColA>(oA[0], vA[8], fl), vA[9] = sel<kColA>(oA[1], vA[9], fl);
      vA[10] = sel<kColA * 2>(oA[2], vA[10], fl), vA[11] = sel<kColA * 2>(oA[3], vA[11], fl);
      vA[12] = sel<kColA * 4>(oA[4], vA[12], fl), vA[13] = sel<kColA * 4>(oA[5], vA[13], fl);
      {
        const float m1 = __uint_as_float(0x88DD88DDu), m0 = __uint_as_float(0x88DDDD88u);
        meta[0] = 0xDD88DD88u ^ __byte_perm(fl, 0u, 0x3344);
        meta[1] = __float_as_uint(sel<kColA * 16>(sel<kColA>(m1, m0, fl), __uint_as_float(meta[0]), fl));
        meta[2] = __float_as_uint(sel<kColA * 8>(m1, m0, fl));
        meta[3] = __float_as_uint(sel<kColA * 4>(m1, m0, fl));
        keep_regs(meta);
      }
      float mA = own_max(vA, fl);
      fl |= __float_as_uint(eB[7]) & zero;
      fence_regs(eB);
      fence_regs(vA);
      asm volatile("" : "+f"(mA), "+r"(fl));
      sched_fence();
      wg_wait<0>();
      sched_fence();
      keep_regs(qb);
      fence_regs(bO);
      PROFS(6, wg, 6 + it * 12);
      if (w == 0) GT(24 + k);
      mA = quad_max(mA);
#pragma unroll
      for (int i = 0; i < 14; i++) vA[i] = ex2(vA[i] - mA);
      pick_v(bO, vB, fl);
      pick_u(bO + 28, vB + 8, fl);
#pragma unroll
      for (int i = 0; i < 8; i += 2) vB[i] = sel<kColB>(vB[i], eB[i], fl), vB[i + 1] = sel<kColB * 2>(vB[i + 1], eB[i + 1], fl);
      float mB = quad_max(own_max(vB, fl));
      if (NAT_SB) {
        fence_regs(vA);
        fence_regs(vB);
        asm volatile("" : "+f"(mB));
        sched_fence();
      }
      PROFS(7, wg, 7 + it * 12);
#pragma unroll
      for (int i = 0; i < 14; i++) vB[i] = ex2(vB[i] - mB);
      route(vA, row_rcp(vA, fl), rt, pa);
      route(vB, row_rcp(vB, fl), rt, pb);
    }
    PROFS(8, wg, 8 + it * 12);
    if (k == NAT_PK) PROFS(18, wg, 53);
    sched_fence();

    float ac0[48], ac1[48];
    {
      float z0[32], z1[32], z2[32];
      uint32_t za[24], zb[24];
      wg_fence();
      pv_chunk<0>(z0, pa, pb, meta, dV);
      wg_commit();
      pv_chunk<1>(z1, pa, pb, meta, dV);
      wg_commit();
      wg_wait<1>();
      if (k == NAT_PK) PROFS(18, wg, 54);
      if (k + 1 < nt) nb_arrive_p(7);
      pv_chunk<2, 0, 3>(z2, pa, pb, meta, dV);
      wg_commit();
      sched_fence();
      fence_regs(z0);
      pack_z<0>(z0, za, zb);
      sched_fence();
      wg_fence();
      pv_chunk<2, 3, 7>(z2, pa, pb, meta, dV);
      wg_commit();
      wg_wait<2>();
      if (k == NAT_PK) PROFS(19, wg, 55);
      if (k + 1 < nt) nb_arrive_p(8);
      if (k < 2) mbar_wait(k == 1 ? bar_wok(bars) : bar_w2a(bars), 0);
      wg_fence();
      g2_steps<0, 3, 0>(ac0, za, zb, dX0);
      wg_commit();
      sched_fence();
      fence_regs(z1);
      pack_z<1>(z1, za, zb);
      sched_fence();
      wg_fence();
      g2_steps<3, 4, 0>(ac0, za, zb, dX0);
      wg_commit();
      g2_steps<4, 8, 0>(ac0, za, zb, dX0);
      wg_commit();
      wg_wait<3>();
      if (k + 1 < nt) nb_arrive_p(9);
      else nb_arrive(11);
      if (k == NAT_PK) PROFS(20, wg, 56);
      keep_regs(pa);
      keep_regs(pb);
      keep_regs(meta);
      sched_fence();
      const uint32_t mok = mbar_test(bar_w2m(bars), k + 1 < nt ? k & 1 : ~k & 1);
      fence_regs(z2);
      pack_z<2>(z2, za, zb);
      keep_regs(za);
      keep_regs(zb);
      sched_fence();
      PROFS(9, wg, 9 + it * 12);
      wg_wait<1>();
      if (k > 0 && k + 1 < nt) nb_arrive(11);
      mbar_wait_if(mok, bar_w2m(bars), k & 1);
      wg_fence();
      g2_steps<8, 12, 0>(ac0, za, zb, dX2);
      wg_commit();
      g2_steps<8, 12, 8>(ac1, za, zb, dY2);
      wg_commit();
      wg_wait<2>();
      if (k > 0 && k + 1 < nt) nb_arrive(12);
      if (k != 1 && k + 1 < nt) mbar_wait(bar_w2(bars), k > 1 ? (k - 1) & 1 : 0);
      wg_fence();
      g2_steps<0, 4, 8>(ac1, za, zb, dY0);
      wg_commit();
      wg_wait<2>();
      if (k + 2 < nt) nb_arrive_p(13);
      const bool direct = k + 2 >= nt;
      sched_fence();
      fence_regs(ac0);
      pack_out<0>(ac0, oa, ob);
      store_rows<0, NAT_D0>(direct, poA, poB, oa, ob);
      sched_fence();
      wg_fence();
      g2_steps<4, 8, 8>(ac1, za, zb, dY0);
      wg_commit();
      if (k + 1 < nt) nb_arrive(3 + wg);
      PROFS(10, wg, 10 + it * 12);
      wg_wait<2>();
      if (k + 2 < nt && (k > 0 || nt == 6)) nb_arrive_p(5);
      store_rows<NAT_D0, 3>(direct, poA, poB, oa, ob);
      __nv_bfloat16 *qA = poA - 192 * wg, *qB = poB - 192 * wg;
      if (k + 2 == nt) nb_sync(11);
      sched_fence();
      wg_wait<0>();
      fence_regs(ac1);
      PROFS(11, wg, 11 + it * 12);
      pack_out<1>(ac1, oa, ob);
      asm volatile("" : "+l"(qA), "+l"(qB));
      store_rows<3, 6>(direct, qA, qB, oa, ob);
      if (k == 0) {
        uint32_t m[2] = {oa[0], oa[1]};
#pragma unroll
        for (int i = 2; i < 24; i++) asm("max.NaN.bf16x2 %0, %0, %1;" : "+r"(m[i & 1]) : "r"(oa[i]));
        asm("max.NaN.bf16x2 %0, %0, %1;" : "+r"(m[0]) : "r"(m[1]));
        uint32_t nan;
        asm volatile("{\n.reg .pred p;\nsetp.ne.u32 p, %1, 0;\nbar.red.or.pred p, 15, 128, p;\nselp.u32 %0, 1, 0, p;\n}\n"
                     : "=r"(nan) : "r"(((m[0] & 0x7FFF7FFFu) + 0x007F007Fu) & 0x80008000u) : "memory");
        if (__builtin_expect(__any_sync(0xffffffffu, nan), 0)) {
          if (nt == 6) mbar_wait(bar_x(bars, 1), 1);
          for (bool first = true; __any_sync(0xffffffffu, refetch(sbase + kW2Off, wimg + w2_offset(), first)); first = false) { }
          wg_fence();
          g2_steps<0, 8, 0>(ac0, za, zb, dX0);
          g2_steps<8, 12, 0>(ac0, za, zb, dX2);
          g2_steps<0, 8, 0>(ac1, za, zb, dY0);
          g2_steps<8, 12, 0>(ac1, za, zb, dY2);
          wg_commit();
          wg_wait<0>();
          fence_regs(ac0);
          fence_regs(ac1);
          pack_out<0>(ac0, oa, ob);
          pack_out<1>(ac1, oa, ob);
          if (nt == 6) {
            asm volatile("bar.sync 15, 128;" ::: "memory");
            if (w == 0 && elect_one()) {
              const TileCoord tc = decode_tile(tt, tile0 + 2);
              mbar_arrive_expect_tx(bar_raw(bars), kWChunk);
              move_px<0, 1>(tm, tt, sbase + kXOff, bar_raw(bars), first_line(tc), tc.kind);
            }
            __syncwarp();
            mbar_wait(bar_raw(bars), 0);
          }
        }
        if (nt < 6) nb_arrive_p(5);
        if (elect_one()) mbar_arrive(bar_wok(bars));
      }
      keep_regs(za);
      keep_regs(zb);
#pragma unroll
      for (int i = 0; i < 8; i++) geo[i] = geo[i + 4];
      keep_regs(oa);
      keep_regs(ob);
      PROFS(12, wg, 12 + it * 12);
      sched_fence();
    }
  }
  PROF(wg, 38);
  GT_DUMP();
  PROF_DUMP(wg);
}

struct HaloCols { int vj, vc, uj, uc; };
__device__ __forceinline__ HaloCols halo_cols(const TileCoord& tc) {
  const int c0 = halo_c0(tc);
  return HaloCols{c0 > 98, c0 > 98 ? 98 : c0 + 3, c0 < 0 ? -1 : 0, c0 < 0 ? 4 : c0};
}
__device__ __forceinline__ void load_halo(const Maps& tm, uint32_t sbase, uint32_t bars, const TileCoord tc, int k, int c) {
  const HaloCols hc = halo_cols(tc);
  const int h6 = halo_r0(tc) + (tc.up ? 0 : 8), h2 = halo_r0(tc) + 6, h8 = halo_r0(tc) + (tc.up ? 0 : 6), ch = 24 * tc.pc + 8 * c;
  uint32_t dv = sbase + 2 * c * kChunkBytes, du = dv + 7 * 1024;
  if (((k ^ tc.up) & 1) == 0) dv += 4 * 1024, du += 3 * 1024;
  const uint32_t bar = bar_full(bars, k & 1, c);
  mbar_arrive_expect_tx(bar, 14 * 1024);
  nb_sync_p(7 + c);
#pragma unroll
  for (int h = 0; h < 2; h++) {
    tma_load_5d(dv + h * kChunkBytes, &tm.v6, bar, ch + 4 * h, hc.vj, hc.vc, tc.pr, h6);
    tma_load_5d(du + h * kChunkBytes, &tm.u8, bar, ch + 4 * h, hc.uj, h8, tc.pr, hc.uc);
    tma_load_5d(sbase + (2 * c + h) * kChunkBytes + 3 * 1024, &tm.v2, bar, ch + 4 * h, hc.vj, hc.vc, tc.pr, h2);
  }
  PROFS(15, 2, k * 4 + c);
}
__device__ __forceinline__ void gather_px(const __nv_bfloat16* __restrict__ x, uint32_t buf, uint32_t bar, const TileCoord tc) {
  const int lane = threadIdx.x & 31, g = lane >> 3;
  uint32_t ro[4], co[4];
#pragma unroll
  for (int i = 0; i < 4; i++) {
    ro[i] = qpix(tc.pr, 8 * tc.I + 2 * i + (g & 1)) * (kW * kC * 2) + 16 * (lane & 7);
    co[i] = qpix(tc.pc, 8 * tc.J + 2 * i + (g >> 1)) * (kC * 2);
  }
  uint32_t dst = buf + g * 128 + (((lane & 7) ^ g) << 4);
  keep_regs(ro);
  keep_regs(co);
  sched_fence();
  nb_sync_p(13);
  nb_sync_p(5);
#pragma unroll
  for (int i = 0; i < 16; i++) {
    const char* src = (const char*)x + (ro[i >> 2] + co[i & 3]);
#pragma unroll
    for (int q = 0; q < 3; q++)
      asm volatile("cp.async.cg.shared.global [%0], [%1], 16;" ::"r"((dst ^ ((i & 1) * 576)) + (i >> 1) * 3072 + q * 1024), "l"(src + 128 * q) : "memory");
  }
  asm volatile("cp.async.wait_all;" ::: "memory");
  fence_proxy_async();
  __syncwarp();
  if (elect_one()) mbar_arrive(bar);
  __syncwarp();
}

__global__ void __launch_bounds__(384, 1)
nat_kernel(const __nv_bfloat16* __restrict__ x, __nv_bfloat16* out, const __nv_bfloat16* __restrict__ wqkv,
           const __nv_bfloat16* __restrict__ wo, uint8_t* wimg, const uint32_t zero,
           const __grid_constant__ Maps tm, const __grid_constant__ TileTable tt) {
  extern __shared__ uint8_t smem_raw[];
  constexpr uint32_t sbase = 1024;
  constexpr uint32_t bars = sbase + kBarOff;
  if (smem_u32(smem_raw) != sbase) __trap();
  const int tid = threadIdx.x;
  const uint32_t t_start = now_ns();
  if (tid == 0) GT(0);
  const int wid = __shfl_sync(0xffffffffu, tid >> 5, 0);
  if ((wid == 4 || (wid == 5 && blockIdx.x - 2 < 16)) && blockIdx.x < 128 && wqkv != nullptr) {
    fold_w1(blockIdx.x - 2 < 16 ? 2 * blockIdx.x + wid - 6 : blockIdx.x + (blockIdx.x < 2 ? 0 : 16), wqkv, wimg);
    if (wid == 4) asm volatile("bar.arrive 12, 64;" ::: "memory");
    if (tid == 128) GT(7);
  }
  if (wid == NAT_PW) {
    if (blockIdx.x >= 128) {
      asm volatile("prefetch.tensormap [%0];" ::"l"((uint64_t)&tm.wv) : "memory");
      asm volatile("prefetch.tensormap [%0];" ::"l"((uint64_t)&tm.wo) : "memory");
    }
    asm volatile("prefetch.tensormap [%0];" ::"l"((uint64_t)&tm.v14) : "memory");
    asm volatile("prefetch.tensormap [%0];" ::"l"((uint64_t)&tm.u8) : "memory");
    const CUtensorMap* px = tm.px + (blockIdx.x >= 112 ? 2 : edge_strip());
    asm volatile("prefetch.tensormap [%0];" ::"l"((uint64_t)px) : "memory");
    asm volatile("prefetch.tensormap [%0];" ::"l"((uint64_t)(px + 1)) : "memory");
    asm volatile("prefetch.tensormap [%0];" ::"l"((uint64_t)&tm.v6) : "memory");
    asm volatile("prefetch.tensormap [%0];" ::"l"((uint64_t)&tm.v2) : "memory");
    asm volatile("prefetch.tensormap [%0];" ::"l"((uint64_t)(px + 4)) : "memory");
    asm volatile("prefetch.tensormap [%0];" ::"l"((uint64_t)(px + 5)) : "memory");
  }
  if (wid >= 8) {
    asm volatile("setmaxnreg.dec.sync.aligned.u32 24;");
    const int c = wid & 3, lane = tid & 31;
    const int tile0 = blockIdx.x * kTilesPerCta, nt = num_tiles();
    uint32_t w2o = 0;
    if (c == 3) {
      asm volatile("bar.sync 13, 64;" ::: "memory");
      __nanosleep(NAT_TW2 - 2000);
      w2o = w2_offset();
      if (elect_one()) {
        mbar_arrive_expect_tx(bar_w2a(bars), kWChunk);
        mbar_arrive_expect_tx(bar_w2(bars), kWChunk);
        wait_clock(t_start, NAT_TW2);
        bulk_load(sbase + kW2Off, wimg + w2o, kWChunk, bar_w2a(bars));
        mbar_wait(bar_xf(bars), 0);
        bulk_load(sbase + kW2Off + 2 * kWChunk, wimg + (w2o + 2 * kWChunk), kWChunk, bar_w2(bars));
      }
      __syncwarp();
      if (nt < 6) {
#pragma unroll 1
        for (int k = 2; k < 4; k++) {
          gather_px(x, sbase + kXOff, bar_x(bars, 1), decode_tile(tt, tile0 + k));
        }
      }
      if (wqkv == nullptr) return;
      mbar_wait(bar_wok(bars), 0);
      if (lane == 0) asm volatile("red.relaxed.gpu.global.add.u32 [%0], 1;" ::"l"(g_flag) : "memory");
      if (blockIdx.x >= 48) return;
      if (lane == 0) {
        uint32_t v, it = 0;
        do {
          __nanosleep(2000);
          asm volatile("ld.relaxed.gpu.global.u32 %0, [%1];" : "=r"(v) : "l"(g_flag) : "memory");
        } while (v < gridDim.x && ++it < (1u << 16));
      }
      __syncwarp();
#pragma unroll
      for (int i = 0; i < 6; i++)
        stg128(wimg + ((i < 3 ? 0u : 3 * kWBytes - w2o) + blockIdx.x * 1536 + (i % 3) * 512 + lane * 16), kEmpty, kEmpty, kEmpty, kEmpty);
      if (lane == 0 && atomicAdd(g_flag + 32, 1u) == 47) {
        g_flag[0] = g_flag[32] = 0;
        g_flag[64] = w2o == kWBytes;
      }
      return;
    }
    if (!elect_one()) return;
    if (c == 0) {
      for (int i = 0; i < kNumBars; i++) mbar_init(bars + i * 8, i == 13 || i == 16 ? 4 : 1);
      asm volatile("st.shared.v2.u32 [%0], {%1,%1};" ::"r"(bars + 192), "r"(0) : "memory");
      asm volatile("fence.mbarrier_init.release.cluster;" ::: "memory");
      if (blockIdx.x - 128 < 3 && wqkv != nullptr) {
        const int q = blockIdx.x & 3;
        mbar_arrive_expect_tx(bar_raw(bars), kWBytes + kWChunk);
#pragma unroll
        for (int j = 0; j < 6; j++)
          asm volatile("cp.async.bulk.tensor.2d.shared::cluster.global.tile.mbarrier::complete_tx::bytes [%0], [%1, {%3, %4}], [%2];" ::"r"(
                           j < 3 ? sbase + j * 8192 : sbase + kW2Off + (j - 3) * kWChunk),
                       "l"((uint64_t)(j < 3 ? &tm.wv : &tm.wo)), "r"(bar_raw(bars)), "r"(j < 3 ? 384 + 64 * j : 64 * (j - 3)), "r"(j < 3 ? 64 * q : 0) : "memory");
        asm volatile("bar.arrive 11, 160;" ::: "memory");
        w2o = w2_offset();
        asm volatile("bar.sync 10, 288;" ::: "memory");
#pragma unroll
        for (int h = 0; h < 2; h++)
          asm volatile("cp.async.bulk.global.shared::cta.bulk_group [%0], [%1], %2;" ::"l"(wimg + (w2o + w2piece(h, q) * (kWChunk / 2))),
                       "r"(sbase + kW1Off + h * (kWChunk / 2)), "r"(kWChunk / 2) : "memory");
        asm volatile("cp.async.bulk.commit_group;" ::: "memory");
        asm volatile("cp.async.bulk.wait_group.read 0;" ::: "memory");
        GT(31);
      }
      asm volatile("bar.arrive 0, 224;" ::: "memory");
      asm volatile("bar.arrive 14, 160;" ::: "memory");
      asm volatile("bar.arrive 13, 64;" ::: "memory");
      const TileCoord tc0 = decode_tile(tt, tile0);
      const HaloCols hc = halo_cols(tc0);
      const int h0 = halo_r0(tc0);
#pragma unroll
      for (int j = 0; j < 3; j++) mbar_arrive_expect_tx(bar_full(bars, 0, j), 2 * kChunkBytes);
      GT(17);
#pragma unroll 1
      for (int i = 0; i < 6; i++) {
        if (i == NAT_H0 || i == NAT_X1P) mbar_arrive(bar_go(bars, i != NAT_H0));
        if (i == NAT_H0) {
          wait_clock(t_start, NAT_HP);
#pragma unroll
          for (int q = 4 * NAT_H0; q < 24; q += NAT_Q0) {
            tma_prefetch_5d(&tm.v6, 24 * tc0.pc + q, hc.vj, hc.vc, tc0.pr, h0 + (tc0.up ? 0 : 8));
            tma_prefetch_5d(&tm.u8, 24 * tc0.pc + q, hc.uj, h0 + (tc0.up ? 0 : 6), tc0.pr, hc.uc);
            if (blockIdx.x >= 112) tma_prefetch_5d(&tm.v2, 24 * tc0.pc + q, hc.vj, hc.vc, tc0.pr, h0 + 6);
          }
          mbar_wait(bar_w1q(bars), 0);
        }
        const uint32_t dst = sbase + i * kChunkBytes, bar = bar_full(bars, 0, i >> 1);
        const int ch = 24 * tc0.pc + 4 * i;
        tma_load_5d(dst, &tm.v14, bar, ch, hc.vj, hc.vc, tc0.pr, h0);
        tma_load_5d(dst + 7 * 1024, &tm.u8, bar, ch, hc.uj, h0 + (tc0.up ? 0 : -2), tc0.pr, hc.uc);
        tma_load_5d(dst + 10 * 1024, &tm.u8, bar, ch, hc.uj, h0 + (tc0.up ? 8 : 6), tc0.pr, hc.uc);
      }
      w2o = w2_offset();
    } else {
      asm volatile("bar.sync 0, 224;" ::: "memory");
      if (c == 2) {
        if (wqkv != nullptr && nt == 6) asm volatile("bar.sync 12, 64;" ::: "memory");
        const uint32_t c0 = clock();
        while ((uint32_t)clock() - c0 < NAT_TD) { }
        wait_clock(t_start, NAT_T0);
#pragma unroll
        for (int j = 0; j < 3; j++) {
          mbar_arrive_expect_tx(bar_w1c(bars, j), kWChunk);
          bulk_load(sbase + kW1Off + j * kWChunk, wimg + j * kWChunk, kWChunk, bar_w1c(bars, j));
        }
        mbar_arrive(bar_w1q(bars));
        GT(2);
        if (NAT_OT == 2) w2o = w2_offset();
      } else {
#pragma unroll 1
        for (int j = 0; j < 2; j++) {
          const TileCoord tc = decode_tile(tt, tile0 + j);
          const int line = first_line(tc);
          mbar_arrive_expect_tx(bar_x(bars, j), kWChunk);
          if (j == 1 || (tc.kind == 0 && NAT_XF == 0)) mbar_wait(bar_go(bars, j), 0);
          if (j == 0) GT(15);
          move_px<0, 2>(tm, tt, sbase + kXOff + (1 - j) * kWChunk, bar_x(bars, j), line, tc.kind);
          if (j == 0) GT(16);
        }
        w2o = w2_offset();
      }
    }
#pragma unroll 1
    for (int k = 1; k < nt; k++) {
      const TileCoord tn = decode_tile(tt, tile0 + k + 1);
      const int line = first_line(tn);
      if (c == 1) {
        nb_sync_p(6);
        bulk_load(sbase + kXOff, wimg + (w2o + kWChunk), kWChunk, bar_w2m(bars));
        mbar_arrive_expect_tx(bar_w2m(bars), kWChunk);
      }
      if (c == 2 - NAT_OT) {
        if (k == 1) wait_clock(t_start, NAT_TX2);
        else if (NAT_OT == 0 || k == nt - 1 + (nt == 6)) __nanosleep(NAT_PFD);
        if (k < 5 && nt == 6) move_px<1, 1>(tm, tt, 0, 0, line, tn.kind);
      }
      if (c == 2 - NAT_OT && (blockIdx.x >= 112 || k == 5)) {
        const TileCoord tc = decode_tile(tt, tile0 + k);
        const HaloCols hc = halo_cols(tc);
        const int h8 = halo_r0(tc) + (tc.up ? 0 : 6);
#pragma unroll 1
        for (int q = 0; q < 24; q += NAT_Q1) {
          tma_prefetch_5d(&tm.v6, 24 * tc.pc + q, hc.vj, hc.vc, tc.pr, h8);
          tma_prefetch_5d(&tm.v2, 24 * tc.pc + q, hc.vj, hc.vc, tc.pr, h8 + 6);
          tma_prefetch_5d(&tm.u8, 24 * tc.pc + q, hc.uj, h8, tc.pr, hc.uc);
        }
      }
      load_halo(tm, sbase, bars, decode_tile(tt, tile0 + k), k, c);
      if (c == 0 && k >= 3 && NAT_RP == 1) {
        if (NAT_RD) __nanosleep(NAT_RD);
        asm volatile("cp.async.bulk.wait_group.read 0;" ::: "memory");
        bulk_load(sbase + out_slot(k - 1, nt), wimg + (w2o + out_slot(k - 1, nt) - kW2Off), kWChunk, bar_w2(bars));
        mbar_arrive_expect_tx(bar_w2(bars), kWChunk);
      }
      if (c == 0 && k < 5 && nt == 6) {
        const int f = ~k & 1;
        if (tn.kind == 0) {
#pragma unroll
          for (int j = 0; j < 4; j++) {
            if ((j & 1) == 0) nb_sync_p(j ? 5 : 13);
            tma_load_5d(sbase + kXOff + (j ^ 2 * f) * 6144, tm.px, bar_x(bars, 1), 0, 0, 0, 0, line + 6 * (j ^ 2 * f));
          }
        } else {
          nb_sync_p(13);
          move_px<0, 4, 4>(tm, tt, sbase + kXOff, bar_x(bars, 1), line, tn.kind, 4 * f);
          nb_sync_p(5);
          move_px<0, 4, 4>(tm, tt, sbase + kXOff, bar_x(bars, 1), line, tn.kind, 4 - 4 * f);
        }
        mbar_arrive_expect_tx(bar_x(bars, 1), kWChunk);
        PROFS(16, 2, k * 4 + 3);
      }
      if (c == NAT_OT && k >= 2) {
        const TileCoord tp = decode_tile(tt, tile0 + k - 2);
        const int lp = first_line(tp);
        nb_sync_p(10);
        if (NAT_XW == 1 && k < 5 && nt == 6) mbar_wait(bar_x(bars, 1), k & 1);
        if (NAT_XW > 1) __nanosleep(NAT_XW);
        move_px<2, NAT_SU>(tm, tt, sbase + out_slot(k, nt), 0, lp, tp.kind);
        if (NAT_RP == 0 && k + 1 < nt) {
          asm volatile("cp.async.bulk.wait_group.read 0;" ::: "memory");
          bulk_load(sbase + out_slot(k, nt), wimg + (w2o + out_slot(k, nt) - kW2Off), kWChunk, bar_w2(bars));
          mbar_arrive_expect_tx(bar_w2(bars), kWChunk);
        }
      }
    }
    asm volatile("cp.async.bulk.wait_group 0;" ::: "memory");
  } else {
    {
      if (blockIdx.x - 128 < 3 && wqkv != nullptr) {
        if (wid < 4) {
          asm volatile("bar.sync 11, 160;" ::: "memory");
          mbar_wait(bar_raw(bars), 0);
        } else if (wid < 6 && elect_one()) {
          asm volatile("cp.async.bulk.prefetch.L2.global [%0], %1;" ::"l"(wid == 4 ? wo : wqkv + (blockIdx.x & 3) * 64 * 576), "r"(kWBytes) : "memory");
        }
        __syncwarp();
        if (tid == 0) GT(7);
        float acc[96];
        wg_fence();
        wg_m192tz<0, 96>(acc, make_desc(sbase, 16, 1024), make_desc(sbase + kW2Off, kWChunk, 1024), 0);
#pragma unroll
        for (int s = 1; s < 12; s++)
          wg_m192t<0, 96>(acc, make_desc(sbase + (s >> 2) * 8192 + (s & 3) * 32, 16, 1024), make_desc(sbase + kW2Off + s * 2048, kWChunk, 1024), 1);
        wg_commit();
        wg_wait<0>();
        fence_regs(acc);
        if (tid == 0) GT(19);
        const int m = (tid >> 3) & 3;
#pragma unroll
        for (int j = 0; j < 24; j += 2) {
          const int n = g2_inv(8 * (j + (m >> 1)) + (tid & 7));
          asm volatile("stmatrix.sync.aligned.m8n8.x4.trans.shared.b16 [%0], {%1,%2,%3,%4};" ::"r"(
                           sbase + kW1Off + (wid >> 2) * kWChunk + n * 128 + (((2 * (wid & 3) + (m & 1)) ^ (n & 7)) << 4)),
                       "r"(pack_bf16(acc[4 * j], acc[4 * j + 1])), "r"(pack_bf16(acc[4 * j + 2], acc[4 * j + 3])),
                       "r"(pack_bf16(acc[4 * j + 4], acc[4 * j + 5])), "r"(pack_bf16(acc[4 * j + 6], acc[4 * j + 7])) : "memory");
        }
        fence_proxy_async();
        if (tid == 0) GT(18);
        asm volatile("bar.arrive 10, 288;" ::: "memory");
      }
    }
    __syncwarp();
    if (wid < 4) asm volatile("bar.sync 0, 224;" ::: "memory");
    else asm volatile("bar.sync 14, 160;" ::: "memory");
    asm volatile("setmaxnreg.inc.sync.aligned.u32 240;");
    consumer(wid >> 2, out, wimg, sbase, zero, tm, tt);
  }
}

}

typedef CUresult (*PFN_encodeTiled)(CUtensorMap*, CUtensorMapDataType, cuuint32_t, void*, const cuuint64_t*,
                                    const cuuint64_t*, const cuuint32_t*, const cuuint32_t*, CUtensorMapInterleave,
                                    CUtensorMapSwizzle, CUtensorMapL2promotion, CUtensorMapFloatOOBfill);

extern "C" void kernel_launch(void* const* d_in, const int* in_sizes, int n_in, void* d_out, int out_size) {
  const __nv_bfloat16* x = (const __nv_bfloat16*)d_in[0];
  const __nv_bfloat16* wqkv = (const __nv_bfloat16*)d_in[1];
  const __nv_bfloat16* wo = (const __nv_bfloat16*)d_in[2];
  __nv_bfloat16* out = (__nv_bfloat16*)d_out;

  static PFN_encodeTiled encode = nullptr;
  static int num_sms = 0;
  static uint8_t* wimg = nullptr;
  if (!encode) {
    void* fn = nullptr;
    cudaDriverEntryPointQueryResult qres;
    cudaGetDriverEntryPoint("cuTensorMapEncodeTiled", &fn, cudaEnableDefault, &qres);
    encode = (PFN_encodeTiled)fn;
    cudaFuncSetAttribute(nat::nat_kernel, cudaFuncAttributeMaxDynamicSharedMemorySize, nat::kSmemBytes);
    cudaGetSymbolAddress((void**)&wimg, nat::g_wimg32);
    int dev = 0;
    cudaGetDevice(&dev);
    cudaDeviceGetAttribute(&num_sms, cudaDevAttrMultiProcessorCount, dev);
  }
  nat::Maps tm;
  cuuint32_t estr[5] = {1, 1, 1, 1, 1};
  {
    cuuint64_t vdim[5] = {48, 2, 105, 2, 112}, udim[5] = {48, 2, 112, 2, 105};
    cuuint64_t vstr[4] = {7 * 768, 768, 224 * 384, 2 * 224 * 384}, ustr[4] = {7 * 768, 2 * 224 * 384, 224 * 384, 768};
    CUtensorMap* maps[4] = {&tm.v6, &tm.v2, &tm.v14, &tm.u8};
    for (int i = 0; i < 4; i++) {
      cuuint32_t box[5] = {4, 2, i < 3 ? 4u : 8u, 1, i == 0 ? 6u : i == 1 ? 2u : i == 2 ? 14u : 3u};
      encode(maps[i], CU_TENSOR_MAP_DATA_TYPE_UINT32, 5, (void*)x, i < 3 ? vdim : udim, i < 3 ? vstr : ustr, box, estr,
             CU_TENSOR_MAP_INTERLEAVE_16B, CU_TENSOR_MAP_SWIZZLE_128B, NAT_L2P, CU_TENSOR_MAP_FLOAT_OOB_FILL_NONE);
    }
  }
  for (int i = 0; i < 8; i++) {
    const cuuint32_t row = 224 * 384, dr = (1u + (i & 1)) * row;
    const cuuint32_t shape[4][6] = {{8, 3, 2u - i, 2 * row, 128, 4 * 768}, {2, 4, 3, dr, 768, 128}, {4, 2, 3, 4 * row, 2 * row, 128}, {4, 2, 3, 768, dr, 128}};
    const cuuint32_t* sh = shape[i >> 1];
    cuuint64_t dim[5] = {64, sh[0], sh[1], sh[2], 224 * 224 * 3};
    cuuint64_t str[4] = {sh[3], sh[4], sh[5], 128};
    cuuint32_t box[5] = {64, sh[0], sh[1], sh[2], 1};
    encode(tm.px + i, CU_TENSOR_MAP_DATA_TYPE_BFLOAT16, 5, i < 4 ? (void*)x : (void*)out, dim, str, box, estr, CU_TENSOR_MAP_INTERLEAVE_NONE,
           CU_TENSOR_MAP_SWIZZLE_128B, i < 4 ? CU_TENSOR_MAP_L2_PROMOTION_L2_128B : CU_TENSOR_MAP_L2_PROMOTION_NONE,
           CU_TENSOR_MAP_FLOAT_OOB_FILL_NONE);
  }
  for (int i = 0; i < 2; i++) {
    cuuint64_t dim[2] = {i ? 192u : 576u, 192}, str[1] = {i ? 384u : 1152u};
    cuuint32_t box[2] = {64, i ? 192u : 64u};
    encode(i ? &tm.wo : &tm.wv, CU_TENSOR_MAP_DATA_TYPE_BFLOAT16, 2, i ? (void*)wo : (void*)wqkv, dim, str, box, estr,
           CU_TENSOR_MAP_INTERLEAVE_NONE, CU_TENSOR_MAP_SWIZZLE_128B, CU_TENSOR_MAP_L2_PROMOTION_L2_256B, CU_TENSOR_MAP_FLOAT_OOB_FILL_NONE);
  }
  nat::TileTable tt;
  nat::make_tiles(tt);
  const int grid = nat::kCtas;
  if (num_sms >= grid) {
    nat::nat_kernel<<<grid, 384, nat::kSmemBytes>>>(x, out, wqkv, wo, wimg, 0u, tm, tt);
  } else {
    nat::fold_kernel<<<27, 256>>>(wqkv, wo, wimg);
    nat::nat_kernel<<<grid, 384, nat::kSmemBytes>>>(x, out, nullptr, nullptr, wimg, 0u, tm, tt);
  }
}
```

```cpp
#include <cuda_runtime.h>
#include <cuda_bf16.h>
#include <cuda.h>
#include <stdint.h>

#define NAT_P1 2
#define NAT_P2 4
#define NAT_H0 2
#define NAT_T0 2150
#define NAT_TD 1250
#define NAT_TW2 4500
#define NAT_TX2 4000
#define NAT_X1P 5
#define NAT_PK 3
#define NAT_HP 1800
#define NAT_PFD 700
#define NAT_XW 200
#define NAT_SU 8
#define NAT_D0 1
#define NAT_RD 0
#define NAT_RP 0
#define NAT_SP 9
#define NAT_OT 0
#define NAT_L2P CU_TENSOR_MAP_L2_PROMOTION_L2_128B
#define NAT_TH 0
#define NAT_SB 0
namespace nat {

constexpr int kW = 224, kC = 192;
constexpr int kCtas = 132;
constexpr int kTilesPerCta = 6;
constexpr float kAlpha = 0.07216878364870322f * 1.4426950408889634f;
constexpr uint32_t kChunkBytes = 13 * 1024;
constexpr uint32_t kWChunk = 192 * 128;
constexpr uint32_t kWBytes = 3 * kWChunk;
constexpr uint32_t kW1Off = 6 * kChunkBytes;
constexpr uint32_t kW2Off = kW1Off + kWBytes;
constexpr uint32_t kXOff = kW2Off + kWChunk;
constexpr uint32_t kBarOff = kW2Off + kWBytes;
constexpr uint32_t kProfOff = kBarOff + 208;
constexpr uint32_t kSmemBytes = kBarOff + 1024;

static_assert(kW1Off % 1024 == 0 && kW2Off % 1024 == 0 && kChunkBytes % 1024 == 0, "swizzle alignment");
static_assert(kSmemBytes <= 232448, "smem");

constexpr uint32_t kEmpty = 0xFFFFFFFFu;
#define NAT_R8(v) v, v, v, v, v, v, v, v
#define NAT_R2K(v) NAT_R8(NAT_R8(NAT_R8(v))), NAT_R8(NAT_R8(NAT_R8(v))), NAT_R8(NAT_R8(NAT_R8(v))), NAT_R8(NAT_R8(NAT_R8(v)))
#define NAT_IMG NAT_R8(NAT_R2K(kEmpty)), NAT_R2K(kEmpty)
__device__ __align__(1024) uint32_t g_wimg32[3 * kWBytes / 4] = {NAT_IMG, NAT_IMG, NAT_IMG};
static_assert(kWBytes / 4 == 9 * 2048, "initialiser");
__device__ __align__(128) uint32_t g_flag[96];
__device__ __forceinline__ uint32_t w2_offset() {
  uint32_t v;
  asm volatile("ld.relaxed.gpu.global.u32 %0, [%1];" : "=r"(v) : "l"(g_flag + 64) : "memory");
  return (1 + v) * kWBytes;
}

#define PROFS(id, wgid, slotid) do { } while (0)
#define PROF(wgid, slotid) do { } while (0)
#define PROF_DUMP(wgid) do { } while (0)

#define GT(slotid) do { } while (0)
#define GT_DUMP() do { } while (0)

__device__ __forceinline__ uint32_t smem_u32(const void* p) { return (uint32_t)__cvta_generic_to_shared(p); }

__device__ __forceinline__ void mbar_init(uint32_t bar, uint32_t count) {
  asm volatile("mbarrier.init.shared::cta.b64 [%0], %1;" ::"r"(bar), "r"(count) : "memory");
}
__device__ __forceinline__ void mbar_arrive(uint32_t bar) {
  asm volatile("mbarrier.arrive.shared::cta.b64 _, [%0];" ::"r"(bar) : "memory");
}
__device__ __forceinline__ void mbar_arrive_expect_tx(uint32_t bar, uint32_t bytes) {
  asm volatile("mbarrier.arrive.expect_tx.shared::cta.b64 _, [%0], %1;" ::"r"(bar), "r"(bytes) : "memory");
}
__device__ __forceinline__ void mbar_wait(uint32_t bar, uint32_t parity) {
  uint32_t ok;
  uint32_t it = 0;
  do {
    asm volatile(
        "{\n.reg .pred p;\n"
        "mbarrier.try_wait.parity.shared::cta.b64 p, [%1], %2;\n"
        "selp.u32 %0, 1, 0, p;\n}\n"
        : "=r"(ok)
        : "r"(bar), "r"(parity)
        : "memory");
    if (++it > (1u << 24)) break;
  } while (!ok);
}
__device__ __forceinline__ uint32_t mbar_test(uint32_t bar, uint32_t parity) {
  uint32_t ok;
  asm volatile("{\n.reg .pred p;\nmbarrier.test_wait.parity.shared::cta.b64 p, [%1], %2;\nselp.u32 %0, 1, 0, p;\n}\n"
               : "=r"(ok) : "r"(bar), "r"(parity) : "memory");
  return ok;
}
__device__ __forceinline__ void mbar_wait_if(uint32_t ok, uint32_t bar, uint32_t parity) {
  if (!__all_sync(0xffffffffu, ok)) mbar_wait(bar, parity);
}
__device__ __forceinline__ bool elect_one() {
  uint32_t r;
  asm volatile("{\n.reg .pred p;\nelect.sync _|p, 0xffffffff;\nselp.u32 %0, 1, 0, p;\n}\n" : "=r"(r));
  return r != 0;
}
__device__ __forceinline__ void nb_arrive(int id) { asm volatile("bar.arrive %0, 256;" ::"r"(id) : "memory"); }
__device__ __forceinline__ void nb_sync(int id) { asm volatile("bar.sync %0, 256;" ::"r"(id) : "memory"); }
__device__ __forceinline__ void nb_arrive_p(int id) { asm volatile("bar.arrive %0, 160;" ::"r"(id) : "memory"); }
__device__ __forceinline__ void nb_sync_p(int id) { asm volatile("bar.sync %0, 160;" ::"r"(id) : "memory"); }
__device__ __forceinline__ void fence_proxy_async() { asm volatile("fence.proxy.async.shared::cta;" ::: "memory"); }

__device__ __forceinline__ void tma_load_5d(uint32_t dst, const CUtensorMap* map, uint32_t bar, int c0, int c1, int c2,
                                            int c3, int c4) {
  asm volatile(
      "cp.async.bulk.tensor.5d.shared::cluster.global.tile.mbarrier::complete_tx::bytes "
      "[%0], [%1, {%3, %4, %5, %6, %7}], [%2];"
      ::"r"(dst), "l"((uint64_t)map), "r"(bar), "r"(c0), "r"(c1), "r"(c2), "r"(c3), "r"(c4)
      : "memory");
}
__device__ __forceinline__ void bulk_load(uint32_t dst, const void* src, uint32_t bytes, uint32_t bar) {
  asm volatile("cp.async.bulk.shared::cluster.global.mbarrier::complete_tx::bytes [%0], [%1], %2, [%3];"
               ::"r"(dst), "l"((uint64_t)src), "r"(bytes), "r"(bar)
               : "memory");
}

__device__ __forceinline__ void wg_fence() { asm volatile("wgmma.fence.sync.aligned;" ::: "memory"); }
__device__ __forceinline__ void wg_commit() { asm volatile("wgmma.commit_group.sync.aligned;" ::: "memory"); }
template <int N>
__device__ __forceinline__ void wg_wait() { asm volatile("wgmma.wait_group.sync.aligned %0;" ::"n"(N) : "memory"); }

template <int N>
__device__ __forceinline__ void fence_regs(float (&d)[N]) {
#pragma unroll
  for (int i = 0; i < N; i++) asm volatile("" : "+f"(d[i])::"memory");
}
template <int N>
__device__ __forceinline__ void keep_regs(uint32_t (&d)[N]) {
#pragma unroll
  for (int i = 0; i < N; i++) asm volatile("" : "+r"(d[i])::"memory");
}

__device__ __forceinline__ uint32_t pack_bf16(float lo, float hi) {
  uint32_t d;
  asm("cvt.rn.bf16x2.f32 %0, %1, %2;" : "=r"(d) : "f"(hi), "f"(lo));
  return d;
}
__device__ __forceinline__ float ex2(float x) {
  float y;
  asm("ex2.approx.ftz.f32 %0, %1;" : "=f"(y) : "f"(x));
  return y;
}
__device__ __forceinline__ float rcp_approx(float x) {
  float y;
  asm("rcp.approx.ftz.f32 %0, %1;" : "=f"(y) : "f"(x));
  return y;
}
__device__ __forceinline__ uint4 ldg128_nc(const void* p) {
  uint4 v;
  asm volatile("ld.global.nc.v4.u32 {%0,%1,%2,%3}, [%4];" : "=r"(v.x), "=r"(v.y), "=r"(v.z), "=r"(v.w) : "l"(p));
  return v;
}
__device__ __forceinline__ void stg128(void* p, uint32_t a, uint32_t b, uint32_t c, uint32_t d) {
  asm volatile("st.global.v4.u32 [%0], {%1,%2,%3,%4};" ::"l"(p), "r"(a), "r"(b), "r"(c), "r"(d) : "memory");
}

__device__ __forceinline__ long long clk64() {
  long long c;
  asm volatile("mov.u64 %0, %clock64;" : "=l"(c)::"memory");
  return c;
}
__device__ __forceinline__ void sched_fence() { while (clk64() < 0) { } }

__device__ __forceinline__ uint64_t make_desc(uint32_t addr, uint32_t lbo, uint32_t sbo, uint32_t mode = 1) {
  return (uint64_t)((addr & 0x3FFFF) >> 4) | ((uint64_t)(lbo >> 4) << 16) | ((uint64_t)(sbo >> 4) << 32) |
         ((uint64_t)mode << 62);
}

template <int OFF, int NN>
__device__ __forceinline__ void wg_m192(float (&d)[NN], uint64_t desc_a, uint64_t desc_b, int scale_d) {
  asm volatile(
      "{\n.reg .pred p;\nsetp.ne.b32 p, %98, 0;\n"
      "wgmma.mma_async.sync.aligned.m64n192k16.f32.bf16.bf16 "
      "{%0,%1,%2,%3,%4,%5,%6,%7,%8,%9,%10,%11,%12,%13,%14,%15,"
      "%16,%17,%18,%19,%20,%21,%22,%23,%24,%25,%26,%27,%28,%29,%30,%31,"
      "%32,%33,%34,%35,%36,%37,%38,%39,%40,%41,%42,%43,%44,%45,%46,%47,"
      "%48,%49,%50,%51,%52,%53,%54,%55,%56,%57,%58,%59,%60,%61,%62,%63,"
      "%64,%65,%66,%67,%68,%69,%70,%71,%72,%73,%74,%75,%76,%77,%78,%79,"
      "%80,%81,%82,%83,%84,%85,%86,%87,%88,%89,%90,%91,%92,%93,%94,%95}, "
      "%96, %97, p, 1, 1, 0, 0;\n}\n"
      : "+f"(d[OFF + 0]), "+f"(d[OFF + 1]), "+f"(d[OFF + 2]), "+f"(d[OFF + 3]), "+f"(d[OFF + 4]), "+f"(d[OFF + 5]),
        "+f"(d[OFF + 6]), "+f"(d[OFF + 7]), "+f"(d[OFF + 8]), "+f"(d[OFF + 9]), "+f"(d[OFF + 10]), "+f"(d[OFF + 11]),
        "+f"(d[OFF + 12]), "+f"(d[OFF + 13]), "+f"(d[OFF + 14]), "+f"(d[OFF + 15]), "+f"(d[OFF + 16]), "+f"(d[OFF + 17]),
        "+f"(d[OFF + 18]), "+f"(d[OFF + 19]), "+f"(d[OFF + 20]), "+f"(d[OFF + 21]), "+f"(d[OFF + 22]), "+f"(d[OFF + 23]),
        "+f"(d[OFF + 24]), "+f"(d[OFF + 25]), "+f"(d[OFF + 26]), "+f"(d[OFF + 27]), "+f"(d[OFF + 28]), "+f"(d[OFF + 29]),
        "+f"(d[OFF + 30]), "+f"(d[OFF + 31]), "+f"(d[OFF + 32]), "+f"(d[OFF + 33]), "+f"(d[OFF + 34]), "+f"(d[OFF + 35]),
        "+f"(d[OFF + 36]), "+f"(d[OFF + 37]), "+f"(d[OFF + 38]), "+f"(d[OFF + 39]), "+f"(d[OFF + 40]), "+f"(d[OFF + 41]),
        "+f"(d[OFF + 42]), "+f"(d[OFF + 43]), "+f"(d[OFF + 44]), "+f"(d[OFF + 45]), "+f"(d[OFF + 46]), "+f"(d[OFF + 47]),
        "+f"(d[OFF + 48]), "+f"(d[OFF + 49]), "+f"(d[OFF + 50]), "+f"(d[OFF + 51]), "+f"(d[OFF + 52]), "+f"(d[OFF + 53]),
        "+f"(d[OFF + 54]), "+f"(d[OFF + 55]), "+f"(d[OFF + 56]), "+f"(d[OFF + 57]), "+f"(d[OFF + 58]), "+f"(d[OFF + 59]),
        "+f"(d[OFF + 60]), "+f"(d[OFF + 61]), "+f"(d[OFF + 62]), "+f"(d[OFF + 63]), "+f"(d[OFF + 64]), "+f"(d[OFF + 65]),
        "+f"(d[OFF + 66]), "+f"(d[OFF + 67]), "+f"(d[OFF + 68]), "+f"(d[OFF + 69]), "+f"(d[OFF + 70]), "+f"(d[OFF + 71]),
        "+f"(d[OFF + 72]), "+f"(d[OFF + 73]), "+f"(d[OFF + 74]), "+f"(d[OFF + 75]), "+f"(d[OFF + 76]), "+f"(d[OFF + 77]),
        "+f"(d[OFF + 78]), "+f"(d[OFF + 79]), "+f"(d[OFF + 80]), "+f"(d[OFF + 81]), "+f"(d[OFF + 82]), "+f"(d[OFF + 83]),
        "+f"(d[OFF + 84]), "+f"(d[OFF + 85]), "+f"(d[OFF + 86]), "+f"(d[OFF + 87]), "+f"(d[OFF + 88]), "+f"(d[OFF + 89]),
        "+f"(d[OFF + 90]), "+f"(d[OFF + 91]), "+f"(d[OFF + 92]), "+f"(d[OFF + 93]), "+f"(d[OFF + 94]), "+f"(d[OFF + 95])
      : "l"(desc_a), "l"(desc_b), "r"(scale_d));
}

template <int OFF, int NN>
__device__ __forceinline__ void wg_m192z(float (&d)[NN], uint64_t desc_a, uint64_t desc_b, int scale_d) {
  asm volatile(
      "{\n.reg .pred p;\nsetp.ne.b32 p, %98, 0;\n"
      "wgmma.mma_async.sync.aligned.m64n192k16.f32.bf16.bf16 "
      "{%0,%1,%2,%3,%4,%5,%6,%7,%8,%9,%10,%11,%12,%13,%14,%15,"
      "%16,%17,%18,%19,%20,%21,%22,%23,%24,%25,%26,%27,%28,%29,%30,%31,"
      "%32,%33,%34,%35,%36,%37,%38,%39,%40,%41,%42,%43,%44,%45,%46,%47,"
      "%48,%49,%50,%51,%52,%53,%54,%55,%56,%57,%58,%59,%60,%61,%62,%63,"
      "%64,%65,%66,%67,%68,%69,%70,%71,%72,%73,%74,%75,%76,%77,%78,%79,"
      "%80,%81,%82,%83,%84,%85,%86,%87,%88,%89,%90,%91,%92,%93,%94,%95}, "
      "%96, %97, p, 1, 1, 0, 0;\n}\n"
      : "=f"(d[OFF + 0]), "=f"(d[OFF + 1]), "=f"(d[OFF + 2]), "=f"(d[OFF + 3]), "=f"(d[OFF + 4]), "=f"(d[OFF + 5]),
        "=f"(d[OFF + 6]), "=f"(d[OFF + 7]), "=f"(d[OFF + 8]), "=f"(d[OFF + 9]), "=f"(d[OFF + 10]), "=f"(d[OFF + 11]),
        "=f"(d[OFF + 12]), "=f"(d[OFF + 13]), "=f"(d[OFF + 14]), "=f"(d[OFF + 15]), "=f"(d[OFF + 16]), "=f"(d[OFF + 17]),
        "=f"(d[OFF + 18]), "=f"(d[OFF + 19]), "=f"(d[OFF + 20]), "=f"(d[OFF + 21]), "=f"(d[OFF + 22]), "=f"(d[OFF + 23]),
        "=f"(d[OFF + 24]), "=f"(d[OFF + 25]), "=f"(d[OFF + 26]), "=f"(d[OFF + 27]), "=f"(d[OFF + 28]), "=f"(d[OFF + 29]),
        "=f"(d[OFF + 30]), "=f"(d[OFF + 31]), "=f"(d[OFF + 32]), "=f"(d[OFF + 33]), "=f"(d[OFF + 34]), "=f"(d[OFF + 35]),
        "=f"(d[OFF + 36]), "=f"(d[OFF + 37]), "=f"(d[OFF + 38]), "=f"(d[OFF + 39]), "=f"(d[OFF + 40]), "=f"(d[OFF + 41]),
        "=f"(d[OFF + 42]), "=f"(d[OFF + 43]), "=f"(d[OFF + 44]), "=f"(d[OFF + 45]), "=f"(d[OFF + 46]), "=f"(d[OFF + 47]),
        "=f"(d[OFF + 48]), "=f"(d[OFF + 49]), "=f"(d[OFF + 50]), "=f"(d[OFF + 51]), "=f"(d[OFF + 52]), "=f"(d[OFF + 53]),
        "=f"(d[OFF + 54]), "=f"(d[OFF + 55]), "=f"(d[OFF + 56]), "=f"(d[OFF + 57]), "=f"(d[OFF + 58]), "=f"(d[OFF + 59]),
        "=f"(d[OFF + 60]), "=f"(d[OFF + 61]), "=f"(d[OFF + 62]), "=f"(d[OFF + 63]), "=f"(d[OFF + 64]), "=f"(d[OFF + 65]),
        "=f"(d[OFF + 66]), "=f"(d[OFF + 67]), "=f"(d[OFF + 68]), "=f"(d[OFF + 69]), "=f"(d[OFF + 70]), "=f"(d[OFF + 71]),
        "=f"(d[OFF + 72]), "=f"(d[OFF + 73]), "=f"(d[OFF + 74]), "=f"(d[OFF + 75]), "=f"(d[OFF + 76]), "=f"(d[OFF + 77]),
        "=f"(d[OFF + 78]), "=f"(d[OFF + 79]), "=f"(d[OFF + 80]), "=f"(d[OFF + 81]), "=f"(d[OFF + 82]), "=f"(d[OFF + 83]),
        "=f"(d[OFF + 84]), "=f"(d[OFF + 85]), "=f"(d[OFF + 86]), "=f"(d[OFF + 87]), "=f"(d[OFF + 88]), "=f"(d[OFF + 89]),
        "=f"(d[OFF + 90]), "=f"(d[OFF + 91]), "=f"(d[OFF + 92]), "=f"(d[OFF + 93]), "=f"(d[OFF + 94]), "=f"(d[OFF + 95])
      : "l"(desc_a), "l"(desc_b), "r"(scale_d));
}

template <int OFF, int NN>
__device__ __forceinline__ void wg_m192t(float (&d)[NN], uint64_t desc_a, uint64_t desc_b, int scale_d) {
  asm volatile(
      "{\n.reg .pred p;\nsetp.ne.b32 p, %98, 0;\n"
      "wgmma.mma_async.sync.aligned.m64n192k16.f32.bf16.bf16 "
      "{%0,%1,%2,%3,%4,%5,%6,%7,%8,%9,%10,%11,%12,%13,%14,%15,"
      "%16,%17,%18,%19,%20,%21,%22,%23,%24,%25,%26,%27,%28,%29,%30,%31,"
      "%32,%33,%34,%35,%36,%37,%38,%39,%40,%41,%42,%43,%44,%45,%46,%47,"
      "%48,%49,%50,%51,%52,%53,%54,%55,%56,%57,%58,%59,%60,%61,%62,%63,"
      "%64,%65,%66,%67,%68,%69,%70,%71,%72,%73,%74,%75,%76,%77,%78,%79,"
      "%80,%81,%82,%83,%84,%85,%86,%87,%88,%89,%90,%91,%92,%93,%94,%95}, "
      "%96, %97, p, 1, 1, 0, 1;\n}\n"
      : "+f"(d[OFF + 0]), "+f"(d[OFF + 1]), "+f"(d[OFF + 2]), "+f"(d[OFF + 3]), "+f"(d[OFF + 4]), "+f"(d[OFF + 5]),
        "+f"(d[OFF + 6]), "+f"(d[OFF + 7]), "+f"(d[OFF + 8]), "+f"(d[OFF + 9]), "+f"(d[OFF + 10]), "+f"(d[OFF + 11]),
        "+f"(d[OFF + 12]), "+f"(d[OFF + 13]), "+f"(d[OFF + 14]), "+f"(d[OFF + 15]), "+f"(d[OFF + 16]), "+f"(d[OFF + 17]),
        "+f"(d[OFF + 18]), "+f"(d[OFF + 19]), "+f"(d[OFF + 20]), "+f"(d[OFF + 21]), "+f"(d[OFF + 22]), "+f"(d[OFF + 23]),
        "+f"(d[OFF + 24]), "+f"(d[OFF + 25]), "+f"(d[OFF + 26]), "+f"(d[OFF + 27]), "+f"(d[OFF + 28]), "+f"(d[OFF + 29]),
        "+f"(d[OFF + 30]), "+f"(d[OFF + 31]), "+f"(d[OFF + 32]), "+f"(d[OFF + 33]), "+f"(d[OFF + 34]), "+f"(d[OFF + 35]),
        "+f"(d[OFF + 36]), "+f"(d[OFF + 37]), "+f"(d[OFF + 38]), "+f"(d[OFF + 39]), "+f"(d[OFF + 40]), "+f"(d[OFF + 41]),
        "+f"(d[OFF + 42]), "+f"(d[OFF + 43]), "+f"(d[OFF + 44]), "+f"(d[OFF + 45]), "+f"(d[OFF + 46]), "+f"(d[OFF + 47]),
        "+f"(d[OFF + 48]), "+f"(d[OFF + 49]), "+f"(d[OFF + 50]), "+f"(d[OFF + 51]), "+f"(d[OFF + 52]), "+f"(d[OFF + 53]),
        "+f"(d[OFF + 54]), "+f"(d[OFF + 55]), "+f"(d[OFF + 56]), "+f"(d[OFF + 57]), "+f"(d[OFF + 58]), "+f"(d[OFF + 59]),
        "+f"(d[OFF + 60]), "+f"(d[OFF + 61]), "+f"(d[OFF + 62]), "+f"(d[OFF + 63]), "+f"(d[OFF + 64]), "+f"(d[OFF + 65]),
        "+f"(d[OFF + 66]), "+f"(d[OFF + 67]), "+f"(d[OFF + 68]), "+f"(d[OFF + 69]), "+f"(d[OFF + 70]), "+f"(d[OFF + 71]),
        "+f"(d[OFF + 72]), "+f"(d[OFF + 73]), "+f"(d[OFF + 74]), "+f"(d[OFF + 75]), "+f"(d[OFF + 76]), "+f"(d[OFF + 77]),
        "+f"(d[OFF + 78]), "+f"(d[OFF + 79]), "+f"(d[OFF + 80]), "+f"(d[OFF + 81]), "+f"(d[OFF + 82]), "+f"(d[OFF + 83]),
        "+f"(d[OFF + 84]), "+f"(d[OFF + 85]), "+f"(d[OFF + 86]), "+f"(d[OFF + 87]), "+f"(d[OFF + 88]), "+f"(d[OFF + 89]),
        "+f"(d[OFF + 90]), "+f"(d[OFF + 91]), "+f"(d[OFF + 92]), "+f"(d[OFF + 93]), "+f"(d[OFF + 94]), "+f"(d[OFF + 95])
      : "l"(desc_a), "l"(desc_b), "r"(scale_d));
}

template <int OFF, int NN>
__device__ __forceinline__ void wg_m192tz(float (&d)[NN], uint64_t desc_a, uint64_t desc_b, int scale_d) {
  asm volatile(
      "{\n.reg .pred p;\nsetp.ne.b32 p, %98, 0;\n"
      "wgmma.mma_async.sync.aligned.m64n192k16.f32.bf16.bf16 "
      "{%0,%1,%2,%3,%4,%5,%6,%7,%8,%9,%10,%11,%12,%13,%14,%15,"
      "%16,%17,%18,%19,%20,%21,%22,%23,%24,%25,%26,%27,%28,%29,%30,%31,"
      "%32,%33,%34,%35,%36,%37,%38,%39,%40,%41,%42,%43,%44,%45,%46,%47,"
      "%48,%49,%50,%51,%52,%53,%54,%55,%56,%57,%58,%59,%60,%61,%62,%63,"
      "%64,%65,%66,%67,%68,%69,%70,%71,%72,%73,%74,%75,%76,%77,%78,%79,"
      "%80,%81,%82,%83,%84,%85,%86,%87,%88,%89,%90,%91,%92,%93,%94,%95}, "
      "%96, %97, p, 1, 1, 0, 1;\n}\n"
      : "=f"(d[OFF + 0]), "=f"(d[OFF + 1]), "=f"(d[OFF + 2]), "=f"(d[OFF + 3]), "=f"(d[OFF + 4]), "=f"(d[OFF + 5]),
        "=f"(d[OFF + 6]), "=f"(d[OFF + 7]), "=f"(d[OFF + 8]), "=f"(d[OFF + 9]), "=f"(d[OFF + 10]), "=f"(d[OFF + 11]),
        "=f"(d[OFF + 12]), "=f"(d[OFF + 13]), "=f"(d[OFF + 14]), "=f"(d[OFF + 15]), "=f"(d[OFF + 16]), "=f"(d[OFF + 17]),
        "=f"(d[OFF + 18]), "=f"(d[OFF + 19]), "=f"(d[OFF + 20]), "=f"(d[OFF + 21]), "=f"(d[OFF + 22]), "=f"(d[OFF + 23]),
        "=f"(d[OFF + 24]), "=f"(d[OFF + 25]), "=f"(d[OFF + 26]), "=f"(d[OFF + 27]), "=f"(d[OFF + 28]), "=f"(d[OFF + 29]),
        "=f"(d[OFF + 30]), "=f"(d[OFF + 31]), "=f"(d[OFF + 32]), "=f"(d[OFF + 33]), "=f"(d[OFF + 34]), "=f"(d[OFF + 35]),
        "=f"(d[OFF + 36]), "=f"(d[OFF + 37]), "=f"(d[OFF + 38]), "=f"(d[OFF + 39]), "=f"(d[OFF + 40]), "=f"(d[OFF + 41]),
        "=f"(d[OFF + 42]), "=f"(d[OFF + 43]), "=f"(d[OFF + 44]), "=f"(d[OFF + 45]), "=f"(d[OFF + 46]), "=f"(d[OFF + 47]),
        "=f"(d[OFF + 48]), "=f"(d[OFF + 49]), "=f"(d[OFF + 50]), "=f"(d[OFF + 51]), "=f"(d[OFF + 52]), "=f"(d[OFF + 53]),
        "=f"(d[OFF + 54]), "=f"(d[OFF + 55]), "=f"(d[OFF + 56]), "=f"(d[OFF + 57]), "=f"(d[OFF + 58]), "=f"(d[OFF + 59]),
        "=f"(d[OFF + 60]), "=f"(d[OFF + 61]), "=f"(d[OFF + 62]), "=f"(d[OFF + 63]), "=f"(d[OFF + 64]), "=f"(d[OFF + 65]),
        "=f"(d[OFF + 66]), "=f"(d[OFF + 67]), "=f"(d[OFF + 68]), "=f"(d[OFF + 69]), "=f"(d[OFF + 70]), "=f"(d[OFF + 71]),
        "=f"(d[OFF + 72]), "=f"(d[OFF + 73]), "=f"(d[OFF + 74]), "=f"(d[OFF + 75]), "=f"(d[OFF + 76]), "=f"(d[OFF + 77]),
        "=f"(d[OFF + 78]), "=f"(d[OFF + 79]), "=f"(d[OFF + 80]), "=f"(d[OFF + 81]), "=f"(d[OFF + 82]), "=f"(d[OFF + 83]),
        "=f"(d[OFF + 84]), "=f"(d[OFF + 85]), "=f"(d[OFF + 86]), "=f"(d[OFF + 87]), "=f"(d[OFF + 88]), "=f"(d[OFF + 89]),
        "=f"(d[OFF + 90]), "=f"(d[OFF + 91]), "=f"(d[OFF + 92]), "=f"(d[OFF + 93]), "=f"(d[OFF + 94]), "=f"(d[OFF + 95])
      : "l"(desc_a), "l"(desc_b), "r"(scale_d));
}

template <int OFF, int NN>
__device__ __forceinline__ void wg_d96(float (&d)[NN], uint32_t a0, uint32_t a1, uint32_t a2, uint32_t a3,
                                       uint64_t desc_b, int scale_d) {
  asm volatile(
      "{\n.reg .pred p;\nsetp.ne.b32 p, %53, 0;\n"
      "wgmma.mma_async.sync.aligned.m64n96k16.f32.bf16.bf16 "
      "{%0,%1,%2,%3,%4,%5,%6,%7,%8,%9,%10,%11,%12,%13,%14,%15,"
      "%16,%17,%18,%19,%20,%21,%22,%23,%24,%25,%26,%27,%28,%29,%30,%31,"
      "%32,%33,%34,%35,%36,%37,%38,%39,%40,%41,%42,%43,%44,%45,%46,%47}, "
      "{%48,%49,%50,%51}, %52, p, 1, 1, 0;\n}\n"
      : "+f"(d[OFF + 0]), "+f"(d[OFF + 1]), "+f"(d[OFF + 2]), "+f"(d[OFF + 3]), "+f"(d[OFF + 4]), "+f"(d[OFF + 5]),
        "+f"(d[OFF + 6]), "+f"(d[OFF + 7]), "+f"(d[OFF + 8]), "+f"(d[OFF + 9]), "+f"(d[OFF + 10]), "+f"(d[OFF + 11]),
        "+f"(d[OFF + 12]), "+f"(d[OFF + 13]), "+f"(d[OFF + 14]), "+f"(d[OFF + 15]), "+f"(d[OFF + 16]), "+f"(d[OFF + 17]),
        "+f"(d[OFF + 18]), "+f"(d[OFF + 19]), "+f"(d[OFF + 20]), "+f"(d[OFF + 21]), "+f"(d[OFF + 22]), "+f"(d[OFF + 23]),
        "+f"(d[OFF + 24]), "+f"(d[OFF + 25]), "+f"(d[OFF + 26]), "+f"(d[OFF + 27]), "+f"(d[OFF + 28]), "+f"(d[OFF + 29]),
        "+f"(d[OFF + 30]), "+f"(d[OFF + 31]), "+f"(d[OFF + 32]), "+f"(d[OFF + 33]), "+f"(d[OFF + 34]), "+f"(d[OFF + 35]),
        "+f"(d[OFF + 36]), "+f"(d[OFF + 37]), "+f"(d[OFF + 38]), "+f"(d[OFF + 39]), "+f"(d[OFF + 40]), "+f"(d[OFF + 41]),
        "+f"(d[OFF + 42]), "+f"(d[OFF + 43]), "+f"(d[OFF + 44]), "+f"(d[OFF + 45]), "+f"(d[OFF + 46]), "+f"(d[OFF + 47])
      : "r"(a0), "r"(a1), "r"(a2), "r"(a3), "l"(desc_b), "r"(scale_d));
}

template <int OFF, int NN>
__device__ __forceinline__ void wg_d96z(float (&d)[NN], uint32_t a0, uint32_t a1, uint32_t a2, uint32_t a3,
                                       uint64_t desc_b, int scale_d) {
  asm volatile(
      "{\n.reg .pred p;\nsetp.ne.b32 p, %53, 0;\n"
      "wgmma.mma_async.sync.aligned.m64n96k16.f32.bf16.bf16 "
      "{%0,%1,%2,%3,%4,%5,%6,%7,%8,%9,%10,%11,%12,%13,%14,%15,"
      "%16,%17,%18,%19,%20,%21,%22,%23,%24,%25,%26,%27,%28,%29,%30,%31,"
      "%32,%33,%34,%35,%36,%37,%38,%39,%40,%41,%42,%43,%44,%45,%46,%47}, "
      "{%48,%49,%50,%51}, %52, p, 1, 1, 0;\n}\n"
      : "=f"(d[OFF + 0]), "=f"(d[OFF + 1]), "=f"(d[OFF + 2]), "=f"(d[OFF + 3]), "=f"(d[OFF + 4]), "=f"(d[OFF + 5]),
        "=f"(d[OFF + 6]), "=f"(d[OFF + 7]), "=f"(d[OFF + 8]), "=f"(d[OFF + 9]), "=f"(d[OFF + 10]), "=f"(d[OFF + 11]),
        "=f"(d[OFF + 12]), "=f"(d[OFF + 13]), "=f"(d[OFF + 14]), "=f"(d[OFF + 15]), "=f"(d[OFF + 16]), "=f"(d[OFF + 17]),
        "=f"(d[OFF + 18]), "=f"(d[OFF + 19]), "=f"(d[OFF + 20]), "=f"(d[OFF + 21]), "=f"(d[OFF + 22]), "=f"(d[OFF + 23]),
        "=f"(d[OFF + 24]), "=f"(d[OFF + 25]), "=f"(d[OFF + 26]), "=f"(d[OFF + 27]), "=f"(d[OFF + 28]), "=f"(d[OFF + 29]),
        "=f"(d[OFF + 30]), "=f"(d[OFF + 31]), "=f"(d[OFF + 32]), "=f"(d[OFF + 33]), "=f"(d[OFF + 34]), "=f"(d[OFF + 35]),
        "=f"(d[OFF + 36]), "=f"(d[OFF + 37]), "=f"(d[OFF + 38]), "=f"(d[OFF + 39]), "=f"(d[OFF + 40]), "=f"(d[OFF + 41]),
        "=f"(d[OFF + 42]), "=f"(d[OFF + 43]), "=f"(d[OFF + 44]), "=f"(d[OFF + 45]), "=f"(d[OFF + 46]), "=f"(d[OFF + 47])
      : "r"(a0), "r"(a1), "r"(a2), "r"(a3), "l"(desc_b), "r"(scale_d));
}

template <int OFF, int NN>
__device__ __forceinline__ void wg_s104(float (&d)[NN], uint32_t a0, uint32_t a1, uint32_t a2, uint32_t a3,
                                       uint64_t desc_b, int scale_d, uint32_t meta) {
  asm volatile(
      "{\n.reg .pred p;\nsetp.ne.b32 p, %57, 0;\n"
      "wgmma.mma_async.sp.sync.aligned.m64n104k32.f32.bf16.bf16 "
      "{%0,%1,%2,%3,%4,%5,%6,%7,%8,%9,%10,%11,%12,%13,%14,%15,"
      "%16,%17,%18,%19,%20,%21,%22,%23,%24,%25,%26,%27,%28,%29,%30,%31,"
      "%32,%33,%34,%35,%36,%37,%38,%39,%40,%41,%42,%43,%44,%45,%46,%47,"
      "%48,%49,%50,%51}, "
      "{%52,%53,%54,%55}, %56, %58, 0, p, 1, 1, 0;\n}\n"
      : "+f"(d[OFF + 0]), "+f"(d[OFF + 1]), "+f"(d[OFF + 2]), "+f"(d[OFF + 3]), "+f"(d[OFF + 4]), "+f"(d[OFF + 5]),
        "+f"(d[OFF + 6]), "+f"(d[OFF + 7]), "+f"(d[OFF + 8]), "+f"(d[OFF + 9]), "+f"(d[OFF + 10]), "+f"(d[OFF + 11]),
        "+f"(d[OFF + 12]), "+f"(d[OFF + 13]), "+f"(d[OFF + 14]), "+f"(d[OFF + 15]), "+f"(d[OFF + 16]), "+f"(d[OFF + 17]),
        "+f"(d[OFF + 18]), "+f"(d[OFF + 19]), "+f"(d[OFF + 20]), "+f"(d[OFF + 21]), "+f"(d[OFF + 22]), "+f"(d[OFF + 23]),
        "+f"(d[OFF + 24]), "+f"(d[OFF + 25]), "+f"(d[OFF + 26]), "+f"(d[OFF + 27]), "+f"(d[OFF + 28]), "+f"(d[OFF + 29]),
        "+f"(d[OFF + 30]), "+f"(d[OFF + 31]), "+f"(d[OFF + 32]), "+f"(d[OFF + 33]), "+f"(d[OFF + 34]), "+f"(d[OFF + 35]),
        "+f"(d[OFF + 36]), "+f"(d[OFF + 37]), "+f"(d[OFF + 38]), "+f"(d[OFF + 39]), "+f"(d[OFF + 40]), "+f"(d[OFF + 41]),
        "+f"(d[OFF + 42]), "+f"(d[OFF + 43]), "+f"(d[OFF + 44]), "+f"(d[OFF + 45]), "+f"(d[OFF + 46]), "+f"(d[OFF + 47]),
        "+f"(d[OFF + 48]), "+f"(d[OFF + 49]), "+f"(d[OFF + 50]), "+f"(d[OFF + 51])
      : "r"(a0), "r"(a1), "r"(a2), "r"(a3), "l"(desc_b), "r"(scale_d), "r"(meta));
}

template <int OFF, int NN>
__device__ __forceinline__ void wg_s104z(float (&d)[NN], uint32_t a0, uint32_t a1, uint32_t a2, uint32_t a3,
                                       uint64_t desc_b, int scale_d, uint32_t meta) {
  asm volatile(
      "{\n.reg .pred p;\nsetp.ne.b32 p, %57, 0;\n"
      "wgmma.mma_async.sp.sync.aligned.m64n104k32.f32.bf16.bf16 "
      "{%0,%1,%2,%3,%4,%5,%6,%7,%8,%9,%10,%11,%12,%13,%14,%15,"
      "%16,%17,%18,%19,%20,%21,%22,%23,%24,%25,%26,%27,%28,%29,%30,%31,"
      "%32,%33,%34,%35,%36,%37,%38,%39,%40,%41,%42,%43,%44,%45,%46,%47,"
      "%48,%49,%50,%51}, "
      "{%52,%53,%54,%55}, %56, %58, 0, p, 1, 1, 0;\n}\n"
      : "=f"(d[OFF + 0]), "=f"(d[OFF + 1]), "=f"(d[OFF + 2]), "=f"(d[OFF + 3]), "=f"(d[OFF + 4]), "=f"(d[OFF + 5]),
        "=f"(d[OFF + 6]), "=f"(d[OFF + 7]), "=f"(d[OFF + 8]), "=f"(d[OFF + 9]), "=f"(d[OFF + 10]), "=f"(d[OFF + 11]),
        "=f"(d[OFF + 12]), "=f"(d[OFF + 13]), "=f"(d[OFF + 14]), "=f"(d[OFF + 15]), "=f"(d[OFF + 16]), "=f"(d[OFF + 17]),
        "=f"(d[OFF + 18]), "=f"(d[OFF + 19]), "=f"(d[OFF + 20]), "=f"(d[OFF + 21]), "=f"(d[OFF + 22]), "=f"(d[OFF + 23]),
        "=f"(d[OFF + 24]), "=f"(d[OFF + 25]), "=f"(d[OFF + 26]), "=f"(d[OFF + 27]), "=f"(d[OFF + 28]), "=f"(d[OFF + 29]),
        "=f"(d[OFF + 30]), "=f"(d[OFF + 31]), "=f"(d[OFF + 32]), "=f"(d[OFF + 33]), "=f"(d[OFF + 34]), "=f"(d[OFF + 35]),
        "=f"(d[OFF + 36]), "=f"(d[OFF + 37]), "=f"(d[OFF + 38]), "=f"(d[OFF + 39]), "=f"(d[OFF + 40]), "=f"(d[OFF + 41]),
        "=f"(d[OFF + 42]), "=f"(d[OFF + 43]), "=f"(d[OFF + 44]), "=f"(d[OFF + 45]), "=f"(d[OFF + 46]), "=f"(d[OFF + 47]),
        "=f"(d[OFF + 48]), "=f"(d[OFF + 49]), "=f"(d[OFF + 50]), "=f"(d[OFF + 51])
      : "r"(a0), "r"(a1), "r"(a2), "r"(a3), "l"(desc_b), "r"(scale_d), "r"(meta));
}

template <int OFF, int NN>
__device__ __forceinline__ void wg_s48(float (&d)[NN], uint32_t a0, uint32_t a1, uint32_t a2, uint32_t a3,
                                       uint64_t desc_b, int scale_d, uint32_t meta) {
  asm volatile(
      "{\n.reg .pred p;\nsetp.ne.b32 p, %29, 0;\n"
      "wgmma.mma_async.sp.sync.aligned.m64n48k32.f32.bf16.bf16 "
      "{%0,%1,%2,%3,%4,%5,%6,%7,%8,%9,%10,%11,%12,%13,%14,%15,"
      "%16,%17,%18,%19,%20,%21,%22,%23}, "
      "{%24,%25,%26,%27}, %28, %30, 0, p, 1, 1, 0;\n}\n"
      : "+f"(d[OFF + 0]), "+f"(d[OFF + 1]), "+f"(d[OFF + 2]), "+f"(d[OFF + 3]), "+f"(d[OFF + 4]), "+f"(d[OFF + 5]),
        "+f"(d[OFF + 6]), "+f"(d[OFF + 7]), "+f"(d[OFF + 8]), "+f"(d[OFF + 9]), "+f"(d[OFF + 10]), "+f"(d[OFF + 11]),
        "+f"(d[OFF + 12]), "+f"(d[OFF + 13]), "+f"(d[OFF + 14]), "+f"(d[OFF + 15]), "+f"(d[OFF + 16]), "+f"(d[OFF + 17]),
        "+f"(d[OFF + 18]), "+f"(d[OFF + 19]), "+f"(d[OFF + 20]), "+f"(d[OFF + 21]), "+f"(d[OFF + 22]), "+f"(d[OFF + 23])
      : "r"(a0), "r"(a1), "r"(a2), "r"(a3), "l"(desc_b), "r"(scale_d), "r"(meta));
}

template <int OFF, int NN>
__device__ __forceinline__ void wg_s48z(float (&d)[NN], uint32_t a0, uint32_t a1, uint32_t a2, uint32_t a3,
                                       uint64_t desc_b, int scale_d, uint32_t meta) {
  asm volatile(
      "{\n.reg .pred p;\nsetp.ne.b32 p, %29, 0;\n"
      "wgmma.mma_async.sp.sync.aligned.m64n48k32.f32.bf16.bf16 "
      "{%0,%1,%2,%3,%4,%5,%6,%7,%8,%9,%10,%11,%12,%13,%14,%15,"
      "%16,%17,%18,%19,%20,%21,%22,%23}, "
      "{%24,%25,%26,%27}, %28, %30, 0, p, 1, 1, 0;\n}\n"
      : "=f"(d[OFF + 0]), "=f"(d[OFF + 1]), "=f"(d[OFF + 2]), "=f"(d[OFF + 3]), "=f"(d[OFF + 4]), "=f"(d[OFF + 5]),
        "=f"(d[OFF + 6]), "=f"(d[OFF + 7]), "=f"(d[OFF + 8]), "=f"(d[OFF + 9]), "=f"(d[OFF + 10]), "=f"(d[OFF + 11]),
        "=f"(d[OFF + 12]), "=f"(d[OFF + 13]), "=f"(d[OFF + 14]), "=f"(d[OFF + 15]), "=f"(d[OFF + 16]), "=f"(d[OFF + 17]),
        "=f"(d[OFF + 18]), "=f"(d[OFF + 19]), "=f"(d[OFF + 20]), "=f"(d[OFF + 21]), "=f"(d[OFF + 22]), "=f"(d[OFF + 23])
      : "r"(a0), "r"(a1), "r"(a2), "r"(a3), "l"(desc_b), "r"(scale_d), "r"(meta));
}

template <int OFF, int NN>
__device__ __forceinline__ void wg_s56(float (&d)[NN], uint32_t a0, uint32_t a1, uint32_t a2, uint32_t a3,
                                       uint64_t desc_b, int scale_d, uint32_t meta) {
  asm volatile(
      "{\n.reg .pred p;\nsetp.ne.b32 p, %33, 0;\n"
      "wgmma.mma_async.sp.sync.aligned.m64n56k32.f32.bf16.bf16 "
      "{%0,%1,%2,%3,%4,%5,%6,%7,%8,%9,%10,%11,%12,%13,%14,%15,"
      "%16,%17,%18,%19,%20,%21,%22,%23,%24,%25,%26,%27}, "
      "{%28,%29,%30,%31}, %32, %34, 0, p, 1, 1, 0;\n}\n"
      : "+f"(d[OFF + 0]), "+f"(d[OFF + 1]), "+f"(d[OFF + 2]), "+f"(d[OFF + 3]), "+f"(d[OFF + 4]), "+f"(d[OFF + 5]),
        "+f"(d[OFF + 6]), "+f"(d[OFF + 7]), "+f"(d[OFF + 8]), "+f"(d[OFF + 9]), "+f"(d[OFF + 10]), "+f"(d[OFF + 11]),
        "+f"(d[OFF + 12]), "+f"(d[OFF + 13]), "+f"(d[OFF + 14]), "+f"(d[OFF + 15]), "+f"(d[OFF + 16]), "+f"(d[OFF + 17]),
        "+f"(d[OFF + 18]), "+f"(d[OFF + 19]), "+f"(d[OFF + 20]), "+f"(d[OFF + 21]), "+f"(d[OFF + 22]), "+f"(d[OFF + 23]),
        "+f"(d[OFF + 24]), "+f"(d[OFF + 25]), "+f"(d[OFF + 26]), "+f"(d[OFF + 27])
      : "r"(a0), "r"(a1), "r"(a2), "r"(a3), "l"(desc_b), "r"(scale_d), "r"(meta));
}

template <int OFF, int NN>
__device__ __forceinline__ void wg_s56z(float (&d)[NN], uint32_t a0, uint32_t a1, uint32_t a2, uint32_t a3,
                                       uint64_t desc_b, int scale_d, uint32_t meta) {
  asm volatile(
      "{\n.reg .pred p;\nsetp.ne.b32 p, %33, 0;\n"
      "wgmma.mma_async.sp.sync.aligned.m64n56k32.f32.bf16.bf16 "
      "{%0,%1,%2,%3,%4,%5,%6,%7,%8,%9,%10,%11,%12,%13,%14,%15,"
      "%16,%17,%18,%19,%20,%21,%22,%23,%24,%25,%26,%27}, "
      "{%28,%29,%30,%31}, %32, %34, 0, p, 1, 1, 0;\n}\n"
      : "=f"(d[OFF + 0]), "=f"(d[OFF + 1]), "=f"(d[OFF + 2]), "=f"(d[OFF + 3]), "=f"(d[OFF + 4]), "=f"(d[OFF + 5]),
        "=f"(d[OFF + 6]), "=f"(d[OFF + 7]), "=f"(d[OFF + 8]), "=f"(d[OFF + 9]), "=f"(d[OFF + 10]), "=f"(d[OFF + 11]),
        "=f"(d[OFF + 12]), "=f"(d[OFF + 13]), "=f"(d[OFF + 14]), "=f"(d[OFF + 15]), "=f"(d[OFF + 16]), "=f"(d[OFF + 17]),
        "=f"(d[OFF + 18]), "=f"(d[OFF + 19]), "=f"(d[OFF + 20]), "=f"(d[OFF + 21]), "=f"(d[OFF + 22]), "=f"(d[OFF + 23]),
        "=f"(d[OFF + 24]), "=f"(d[OFF + 25]), "=f"(d[OFF + 26]), "=f"(d[OFF + 27])
      : "r"(a0), "r"(a1), "r"(a2), "r"(a3), "l"(desc_b), "r"(scale_d), "r"(meta));
}

template <int OFF, int NN>
__device__ __forceinline__ void wg_s64t(float (&d)[NN], uint32_t a0, uint32_t a1, uint32_t a2, uint32_t a3,
                                       uint64_t desc_b, int scale_d, uint32_t meta) {
  asm volatile(
      "{\n.reg .pred p;\nsetp.ne.b32 p, %37, 0;\n"
      "wgmma.mma_async.sp.sync.aligned.m64n64k32.f32.bf16.bf16 "
      "{%0,%1,%2,%3,%4,%5,%6,%7,%8,%9,%10,%11,%12,%13,%14,%15,"
      "%16,%17,%18,%19,%20,%21,%22,%23,%24,%25,%26,%27,%28,%29,%30,%31}, "
      "{%32,%33,%34,%35}, %36, %38, 0, p, 1, 1, 1;\n}\n"
      : "+f"(d[OFF + 0]), "+f"(d[OFF + 1]), "+f"(d[OFF + 2]), "+f"(d[OFF + 3]), "+f"(d[OFF + 4]), "+f"(d[OFF + 5]),
        "+f"(d[OFF + 6]), "+f"(d[OFF + 7]), "+f"(d[OFF + 8]), "+f"(d[OFF + 9]), "+f"(d[OFF + 10]), "+f"(d[OFF + 11]),
        "+f"(d[OFF + 12]), "+f"(d[OFF + 13]), "+f"(d[OFF + 14]), "+f"(d[OFF + 15]), "+f"(d[OFF + 16]), "+f"(d[OFF + 17]),
        "+f"(d[OFF + 18]), "+f"(d[OFF + 19]), "+f"(d[OFF + 20]), "+f"(d[OFF + 21]), "+f"(d[OFF + 22]), "+f"(d[OFF + 23]),
        "+f"(d[OFF + 24]), "+f"(d[OFF + 25]), "+f"(d[OFF + 26]), "+f"(d[OFF + 27]), "+f"(d[OFF + 28]), "+f"(d[OFF + 29]),
        "+f"(d[OFF + 30]), "+f"(d[OFF + 31])
      : "r"(a0), "r"(a1), "r"(a2), "r"(a3), "l"(desc_b), "r"(scale_d), "r"(meta));
}

template <int OFF, int NN>
__device__ __forceinline__ void wg_s64t1(float (&d)[NN], uint32_t a0, uint32_t a1, uint32_t a2, uint32_t a3,
                                       uint64_t desc_b, int scale_d, uint32_t meta) {
  asm volatile(
      "{\n.reg .pred p;\nsetp.ne.b32 p, %37, 0;\n"
      "wgmma.mma_async.sp.sync.aligned.m64n64k32.f32.bf16.bf16 "
      "{%0,%1,%2,%3,%4,%5,%6,%7,%8,%9,%10,%11,%12,%13,%14,%15,"
      "%16,%17,%18,%19,%20,%21,%22,%23,%24,%25,%26,%27,%28,%29,%30,%31}, "
      "{%32,%33,%34,%35}, %36, %38, 1, p, 1, 1, 1;\n}\n"
      : "+f"(d[OFF + 0]), "+f"(d[OFF + 1]), "+f"(d[OFF + 2]), "+f"(d[OFF + 3]), "+f"(d[OFF + 4]), "+f"(d[OFF + 5]),
        "+f"(d[OFF + 6]), "+f"(d[OFF + 7]), "+f"(d[OFF + 8]), "+f"(d[OFF + 9]), "+f"(d[OFF + 10]), "+f"(d[OFF + 11]),
        "+f"(d[OFF + 12]), "+f"(d[OFF + 13]), "+f"(d[OFF + 14]), "+f"(d[OFF + 15]), "+f"(d[OFF + 16]), "+f"(d[OFF + 17]),
        "+f"(d[OFF + 18]), "+f"(d[OFF + 19]), "+f"(d[OFF + 20]), "+f"(d[OFF + 21]), "+f"(d[OFF + 22]), "+f"(d[OFF + 23]),
        "+f"(d[OFF + 24]), "+f"(d[OFF + 25]), "+f"(d[OFF + 26]), "+f"(d[OFF + 27]), "+f"(d[OFF + 28]), "+f"(d[OFF + 29]),
        "+f"(d[OFF + 30]), "+f"(d[OFF + 31])
      : "r"(a0), "r"(a1), "r"(a2), "r"(a3), "l"(desc_b), "r"(scale_d), "r"(meta));
}

template <int OFF, int NN>
__device__ __forceinline__ void wg_s64tz(float (&d)[NN], uint32_t a0, uint32_t a1, uint32_t a2, uint32_t a3,
                                       uint64_t desc_b, int scale_d, uint32_t meta) {
  asm volatile(
      "{\n.reg .pred p;\nsetp.ne.b32 p, %37, 0;\n"
      "wgmma.mma_async.sp.sync.aligned.m64n64k32.f32.bf16.bf16 "
      "{%0,%1,%2,%3,%4,%5,%6,%7,%8,%9,%10,%11,%12,%13,%14,%15,"
      "%16,%17,%18,%19,%20,%21,%22,%23,%24,%25,%26,%27,%28,%29,%30,%31}, "
      "{%32,%33,%34,%35}, %36, %38, 0, p, 1, 1, 1;\n}\n"
      : "=f"(d[OFF + 0]), "=f"(d[OFF + 1]), "=f"(d[OFF + 2]), "=f"(d[OFF + 3]), "=f"(d[OFF + 4]), "=f"(d[OFF + 5]),
        "=f"(d[OFF + 6]), "=f"(d[OFF + 7]), "=f"(d[OFF + 8]), "=f"(d[OFF + 9]), "=f"(d[OFF + 10]), "=f"(d[OFF + 11]),
        "=f"(d[OFF + 12]), "=f"(d[OFF + 13]), "=f"(d[OFF + 14]), "=f"(d[OFF + 15]), "=f"(d[OFF + 16]), "=f"(d[OFF + 17]),
        "=f"(d[OFF + 18]), "=f"(d[OFF + 19]), "=f"(d[OFF + 20]), "=f"(d[OFF + 21]), "=f"(d[OFF + 22]), "=f"(d[OFF + 23]),
        "=f"(d[OFF + 24]), "=f"(d[OFF + 25]), "=f"(d[OFF + 26]), "=f"(d[OFF + 27]), "=f"(d[OFF + 28]), "=f"(d[OFF + 29]),
        "=f"(d[OFF + 30]), "=f"(d[OFF + 31])
      : "r"(a0), "r"(a1), "r"(a2), "r"(a3), "l"(desc_b), "r"(scale_d), "r"(meta));
}

__device__ __forceinline__ int g2_inv(int ch) { return 32 * (ch >> 5) + 8 * ((ch >> 1) & 3) + 2 * ((ch >> 3) & 3) + (ch & 1); }
__host__ __device__ __forceinline__ uint32_t wimg_off(int n, int k) {
  return (uint32_t)(k >> 6) * kWChunk + (uint32_t)n * 128 + (uint32_t)((((k & 63) >> 3) ^ (n & 7)) << 4) + (k & 7) * 2;
}
__host__ __device__ constexpr int w2piece(int h, int c) { return c == 2 ? 2 + h : 4 * h + c; }
__device__ __forceinline__ uint32_t w2img_off(int n, int k) { return wimg_off(n % 96, k & 63) + w2piece(n >= 96, k >> 6) * (kWChunk / 2); }
__device__ __forceinline__ int qpix(int par, int t) {
  const int a = 2 * t + 13 * par - 6, b = t + 112 * par;
  return par ? min(a, b) : max(a, b);
}
__device__ __forceinline__ int woff(int par, int i, int r) {
  const int a = 99 * par + 6 - 8 * i;
  return par ? min(r, a) : max(r, a);
}

__device__ __forceinline__ void mma16816(float (&c)[4], uint32_t a0, uint32_t a1, uint32_t a2, uint32_t a3, uint32_t b0,
                                         uint32_t b1) {
  asm volatile(
      "mma.sync.aligned.m16n8k16.row.col.f32.bf16.bf16.f32 {%0,%1,%2,%3}, {%4,%5,%6,%7}, {%8,%9}, {%0,%1,%2,%3};"
      : "+f"(c[0]), "+f"(c[1]), "+f"(c[2]), "+f"(c[3])
      : "r"(a0), "r"(a1), "r"(a2), "r"(a3), "r"(b0), "r"(b1));
}

__device__ __forceinline__ void fold_w1(const int u, const __nv_bfloat16* __restrict__ wqkv, uint8_t* wimg) {
  const int g = (threadIdx.x >> 2) & 7, l = threadIdx.x & 3;
  const int m0 = (u / 12) * 16, s = u % 12;
  uint4 A[12], B[12];
  const __nv_bfloat16* arow = wqkv + (m0 + 4 * (g >> 1) + (g & 1)) * 576 + 192 + 8 * l;
  const __nv_bfloat16* brow = wqkv + (16 * s + 4 * (g >> 1) + (g & 1)) * 576 + 8 * l;
#pragma unroll
  for (int i = 0; i < 12; i++) {
    A[i] = ldg128_nc(arow + (i & 1) * 2 * 576 + 32 * (i >> 1));
    B[i] = ldg128_nc(brow + (i & 1) * 2 * 576 + 32 * (i >> 1));
  }
  sched_fence();
  uint8_t* dst = wimg + wimg_off(m0 + g, 16 * s + 4 * l);
  float acc[4][4];
#pragma unroll
  for (int j = 0; j < 16; j++) acc[j >> 2][j & 3] = 0.f;
#pragma unroll
  for (int i = 0; i < 6; i++) {
    const uint4 &a0 = A[2 * i], &a1 = A[2 * i + 1];
#pragma unroll
    for (int nb = 0; nb < 2; nb++) {
      mma16816(acc[2 * nb], a0.x, a1.x, a0.y, a1.y, B[2 * i + nb].x, B[2 * i + nb].y);
      mma16816(acc[2 * nb + 1], a0.z, a1.z, a0.w, a1.w, B[2 * i + nb].z, B[2 * i + nb].w);
    }
  }
#pragma unroll
  for (int j = 0; j < 2; j++) {
    const uint2 v = make_uint2(pack_bf16((acc[0][2 * j] + acc[1][2 * j]) * kAlpha, (acc[0][2 * j + 1] + acc[1][2 * j + 1]) * kAlpha),
                               pack_bf16((acc[2][2 * j] + acc[3][2 * j]) * kAlpha, (acc[2][2 * j + 1] + acc[3][2 * j + 1]) * kAlpha));
    asm volatile("st.relaxed.gpu.global.v2.u32 [%0], {%1,%2};" ::"l"(dst + j * 1024), "r"(v.x), "r"(v.y) : "memory");
  }
}
__device__ __forceinline__ void fold_w2(const int u, const __nv_bfloat16* __restrict__ wqkv, const __nv_bfloat16* __restrict__ wo,
                                        uint8_t* wimg) {
  const int g = (threadIdx.x >> 2) & 7, l = threadIdx.x & 3;
  const int m0 = (u / 12) * 32, n0 = (u % 12) * 16;
  uint4 S[12];
  uint32_t L[96];
  const __nv_bfloat16* brow = wqkv + (n0 + 4 * (g >> 1) + (g & 1)) * 576 + 384 + 8 * l;
#pragma unroll
  for (int i = 0; i < 12; i++) S[i] = ldg128_nc(brow + (i & 1) * 2 * 576 + 32 * (i >> 1));
  const __nv_bfloat16* acol = wo + (8 * l) * 192 + m0 + 4 * g;
#pragma unroll
  for (int c = 0; c < 48; c++)
    asm volatile("ld.global.nc.v2.u32 {%0,%1}, [%2];" : "=r"(L[2 * c]), "=r"(L[2 * c + 1]) : "l"(acol + (32 * (c >> 3) + (c & 7)) * 192));
  const uint32_t off = w2_offset();
  sched_fence();
  uint8_t* img = wimg + off;
  float acc[4][4];
#pragma unroll
  for (int j = 0; j < 16; j++) acc[j >> 2][j & 3] = 0.f;
#pragma unroll
  for (int i = 0; i < 6; i++) {
#pragma unroll
    for (int h = 0; h < 2; h++) {
      const uint4 &s0 = S[2 * i], &s1 = S[2 * i + 1];
#pragma unroll
      for (int mt = 0; mt < 2; mt++) {
        const uint32_t* a = L + 16 * i + 8 * h + mt;
        const uint32_t a0 = __byte_perm(a[0], a[2], 0x5410), a1 = __byte_perm(a[0], a[2], 0x7632);
        const uint32_t a2 = __byte_perm(a[4], a[6], 0x5410), a3 = __byte_perm(a[4], a[6], 0x7632);
        mma16816(acc[2 * mt], a0, a1, a2, a3, h ? s0.z : s0.x, h ? s0.w : s0.y);
        mma16816(acc[2 * mt + 1], a0, a1, a2, a3, h ? s1.z : s1.x, h ? s1.w : s1.y);
      }
    }
  }
#pragma unroll
  for (int j = 0; j < 4; j++) {
    const float(&c0)[4] = acc[j & 2];
    const float(&c1)[4] = acc[(j & 2) + 1];
    asm volatile("st.relaxed.gpu.global.v2.u32 [%0], {%1,%2};" ::"l"(img + w2img_off(g2_inv(m0 + 4 * g + j), n0 + 4 * l)),
                 "r"(pack_bf16(c0[2 * (j & 1)], c0[2 * (j & 1) + 1])), "r"(pack_bf16(c1[2 * (j & 1)], c1[2 * (j & 1) + 1])) : "memory");
  }
}

__global__ void __launch_bounds__(256) fold_kernel(const __nv_bfloat16* __restrict__ wqkv,
                                                   const __nv_bfloat16* __restrict__ wo, uint8_t* wimg) {
  const int u = blockIdx.x * 8 + (threadIdx.x >> 5);
  if (u < 144) fold_w1(u, wqkv, wimg);
  else fold_w2(u - 144, wqkv, wo, wimg);
}

struct TileCoord { int pr, pc, I, J, up, kind; };
struct TileTable { uint16_t e[kCtas * 6], g[6][8][2]; };
inline void make_tiles(TileTable& tt) {
  for (int tile = 0; tile < kCtas * 6; tile++) {
    const int b = tile / 6, k = tile - 6 * b;
    const int p = b < 128 ? (tile - 672) >> 1 : b - 80;
    const int strip = b < 112 ? b >> 1 : b >= 128 && k >= 2 ? (b & 1) * 27 + (b & 2) * 14 : p + (p < 26 ? 1 : 3);
    const int pr = strip >= 28, J = (strip - pr * 28) >> 1, pc = strip & 1, up = b < 112 ? b & 1 : pr;
    const int first = b < 112 ? 8 - 2 * pr - up : 13 * pr, step = b < 112 ? k : k & 1;
    const int I = up ? first - step : first + step;
    const int kind = b < 112 ? (J == 13 * pc ? 1 + pc : 0) : I == 13 * pr ? 4 + pr : 3;
    tt.e[tile] = (uint16_t)(I | J << 4 | pr << 8 | pc << 9 | up << 10 | kind << 11);
  }
  for (int kind = 0; kind < 6; kind++)
    for (int j = 0; j < 8; j++) {
      const int w = j >> 1, h = j & 1, e = kind % 3;
      auto off = [e](int t) { return e == 0 ? 2 * t : e == 1 ? t + (t == 7) : t + (t > 0); };
      tt.g[kind][j][0] = (uint16_t)(kind < 3 ? 3 * off(w + 4 * h) : 3 * (kW * off(2 * w) + 8 * h));
      tt.g[kind][j][1] = (uint16_t)(128 * (kind < 3 ? kind > 0 : 1 + off(2 * w + 1) - off(2 * w)));
    }
}
__device__ __forceinline__ int num_tiles() { return blockIdx.x < 128 ? 6 : 4; }
__device__ __forceinline__ TileCoord decode_tile(const TileTable& tt, int tile) {
  const uint32_t e = tt.e[tile];
  return TileCoord{(int)(e >> 8) & 1, (int)(e >> 9) & 1, (int)e & 15, (int)(e >> 4) & 15, (int)(e >> 10) & 1, (int)(e >> 11)};
}
__device__ __forceinline__ int halo_r0(const TileCoord& t) { return 8 * t.I + 6 * t.pr - 6; }
__device__ __forceinline__ int halo_c0(const TileCoord& t) { return min(max(8 * t.J + 6 * t.pc - 6, -3), 102); }

__device__ __forceinline__ uint32_t bar_full(uint32_t bars, int wg, int c) { return bars + (wg * 3 + c) * 8; }
__device__ __forceinline__ uint32_t bar_w1c(uint32_t bars, int c) { return bars + (6 + c) * 8; }
__device__ __forceinline__ uint32_t bar_w2(uint32_t bars) { return bars + 9 * 8; }
__device__ __forceinline__ uint32_t bar_x(uint32_t bars, int j) { return bars + (10 + j) * 8; }
__device__ __forceinline__ uint32_t bar_w1q(uint32_t bars) { return bars + 12 * 8; }
__device__ __forceinline__ uint32_t bar_xf(uint32_t bars) { return bars + 13 * 8; }
__device__ __forceinline__ uint32_t bar_w2m(uint32_t bars) { return bars + 14 * 8; }
__device__ __forceinline__ uint32_t bar_redo(uint32_t bars) { return bars + 15 * 8; }
__device__ __forceinline__ uint32_t bar_wok(uint32_t bars) { return bars + 16 * 8; }
__device__ __forceinline__ uint32_t bar_go(uint32_t bars) { return bars + 17 * 8; }
__device__ __forceinline__ uint32_t bar_raw(uint32_t bars) { return bars + 19 * 8; }
__device__ __forceinline__ uint32_t bar_w2a(uint32_t bars) { return bars + 20 * 8; }
constexpr int kNumBars = 21;

__device__ __forceinline__ uint64_t wdesc(uint64_t d0, int s) { return d0 + (((s >> 2) * kWChunk + (s & 3) * 32) >> 4); }

__device__ __forceinline__ int qrow(int w, int g) { return blockIdx.x < 112 ? g : 2 * w + (g & 1); }
__device__ __forceinline__ int qcol(int w, int g) { return blockIdx.x < 112 ? w : g >> 1; }
__device__ __forceinline__ uint32_t out_slot(int k, int nt) { return k + 1 < nt ? kW2Off + (~k & 1) * 2 * kWChunk : kW1Off + kWChunk; }
__device__ __forceinline__ bool edge_strip() {
  const int s = blockIdx.x >> 1;
  return s == 0 || s == 27 || s == 28 || s == 55;
}
template <int I0, int I1>
__device__ __forceinline__ void store_rows(bool on, __nv_bfloat16* pA, __nv_bfloat16* pB, const uint32_t (&a)[24], const uint32_t (&b)[24]) {
#pragma unroll
  for (int i = 2 * I0; i < 2 * I1; i++) {
    const uint32_t* v = (i & 1 ? b : a) + 4 * (i >> 1);
    asm volatile("{\n.reg .pred p;\nsetp.ne.u32 p, %5, 0;\n@p st.global.v4.u32 [%0], {%1,%2,%3,%4};\n}\n" ::"l"((i & 1 ? pB : pA) + 32 * (i >> 1)),
                 "r"(v[0]), "r"(v[1]), "r"(v[2]), "r"(v[3]), "r"((uint32_t)on) : "memory");
  }
}
template <int I0, int I1>
__device__ __forceinline__ void stage_out(uint32_t sts, int wg, const uint32_t (&a)[24], const uint32_t (&b)[24]) {
  const uint32_t e = sts, o = sts ^ 64;
  const uint32_t ad[4] = {wg ? o + 1024 : e, wg ? e + 2048 : o, wg ? e : o + 1024, wg ? o : e + 2048};
#pragma unroll
  for (int i = I0; i < I1; i++) {
    const uint32_t* v = (i < 6 ? a : b) + 4 * (i % 6);
    asm volatile("st.shared.v4.u32 [%0], {%1,%2,%3,%4};" ::"r"(ad[i % 6 / 3 * 2 + (i % 3 == 1)] + (i % 3 == 2) * 1024 + (i / 6) * 12288),
                 "r"(v[0]), "r"(v[1]), "r"(v[2]), "r"(v[3]) : "memory");
  }
}
__device__ __forceinline__ uint32_t now_ns() {
  uint32_t t;
  asm volatile("mov.u32 %0, %globaltimer_lo;" : "=r"(t)::"memory");
  return t;
}
__device__ __forceinline__ void wait_clock(uint32_t t_start, uint32_t t) {
  while (now_ns() - t_start < t) { }
}
#define NAT_PRED(f, m) ".reg .pred p;\n.reg .b32 t;\nand.b32 t, " f ", " m ";\nsetp.ne.u32 p, t, 0;\n"
constexpr uint32_t kHiV = 1, kHiU = 8, kColB = 0x20, kInV = 0x100, kInU = 0x1000, kColA = 0x10000;
template <uint32_t M>
__device__ __forceinline__ float pick(const float* a, const float* b, uint32_t f) {
  float d;
  asm("{\n" NAT_PRED("%5", "%6") "add.f32 %0, %1, %2;\n@p add.f32 %0, %3, %4;\n}\n"
      : "=&f"(d) : "f"(a[0]), "f"(a[2]), "f"(b[0]), "f"(b[2]), "r"(f), "n"(M));
  return d;
}
template <uint32_t M>
__device__ __forceinline__ float sel(float a, float b, uint32_t f) {
  float d;
  asm("{\n" NAT_PRED("%3", "%4") "selp.f32 %0, %1, %2, p;\n}\n" : "=f"(d) : "f"(a), "f"(b), "r"(f), "n"(M));
  return d;
}
template <uint32_t M>
__device__ __forceinline__ void max_if(float& m, float v, uint32_t f) {
  asm("{\n" NAT_PRED("%2", "%3") "@p max.f32 %0, %0, %1;\n}\n" : "+f"(m) : "f"(v), "r"(f), "n"(M));
}
template <uint32_t M>
__device__ __forceinline__ void add_if(float& m, float v, uint32_t f) {
  asm("{\n" NAT_PRED("%2", "%3") "@p add.f32 %0, %0, %1;\n}\n" : "+f"(m) : "f"(v), "r"(f), "n"(M));
}
__device__ __forceinline__ void pick_v(const float* a, float* v, uint32_t f) {
  v[0] = pick<kHiV>(a, a + 16, f), v[1] = pick<kHiV>(a + 1, a + 17, f);
  v[2] = pick<kHiV * 2>(a + 4, a + 20, f), v[3] = pick<kHiV * 2>(a + 5, a + 21, f);
  v[4] = pick<kHiV * 4>(a + 8, a + 24, f), v[5] = pick<kHiV * 4>(a + 9, a + 25, f);
  v[6] = a[12] + a[14], v[7] = a[13] + a[15];
}
__device__ __forceinline__ void pick_u(const float* a, float* v, uint32_t f) {
#pragma unroll
  for (int c = 0; c < 3; c++) v[2 * c] = pick<kHiU>(a + 4 * c, a + 4 * c + 12, f), v[2 * c + 1] = pick<kHiU * 2>(a + 4 * c + 1, a + 4 * c + 13, f);
}
__device__ __forceinline__ uint32_t sign_bytes(uint32_t v, uint32_t sel) {
  uint32_t d;
  asm("prmt.b32 %0, %1, %1, %2;" : "=r"(d) : "r"(v), "r"(sel));
  return d;
}
__device__ __forceinline__ float own_max(const float (&v)[14], uint32_t f) {
  float m = sel<kInV>(fmaxf(v[0], v[1]), -INFINITY, f), m2 = sel<kInV * 2>(fmaxf(v[2], v[3]), -INFINITY, f);
  max_if<kInV * 4>(m, fmaxf(v[4], v[5]), f);
  max_if<kInV * 8>(m2, fmaxf(v[6], v[7]), f);
  max_if<kInU>(m, fmaxf(fmaxf(v[8], v[10]), v[12]), f);
  max_if<kInU * 2>(m2, fmaxf(fmaxf(v[9], v[11]), v[13]), f);
  return fmaxf(m, m2);
}
__device__ __forceinline__ float quad_max(float m) {
  const float a = __shfl_xor_sync(0xffffffffu, m, 1), b = __shfl_xor_sync(0xffffffffu, m, 2), c = __shfl_xor_sync(0xffffffffu, m, 3);
  return fmaxf(fmaxf(m, a), fmaxf(b, c));
}
__device__ __forceinline__ float row_rcp(const float (&v)[14], uint32_t f) {
  float s = sel<kInV>(v[0] + v[1], 0.f, f), s2 = sel<kInV * 2>(v[2] + v[3], 0.f, f);
  add_if<kInV * 4>(s, v[4] + v[5], f);
  add_if<kInV * 8>(s2, v[6] + v[7], f);
  add_if<kInU>(s, v[8] + v[10] + v[12], f);
  add_if<kInU * 2>(s2, v[9] + v[11] + v[13], f);
  s += s2;
  const float a = __shfl_xor_sync(0xffffffffu, s, 1), b = __shfl_xor_sync(0xffffffffu, s, 2), c = __shfl_xor_sync(0xffffffffu, s, 3);
  return rcp_approx((s + a) + (b + c));
}
__device__ __forceinline__ void route(const float (&v)[14], float s, const uint32_t (&rt)[9], uint32_t (&p)[14]) {
#pragma unroll
  for (int i = 0; i < 7; i++) {
    const uint32_t u = pack_bf16(v[2 * i] * s, v[2 * i + 1] * s);
    if (i < 4) p[i] = u & rt[i];
    if (i < 3) p[i + 4] = u & rt[i + 4];
    if (i >= 4) {
      p[i + 3] = u & rt[7];
      p[i + 6] = u & rt[8];
    }
  }
}

template <int C, int T0 = 0, int T1 = 7>
__device__ __forceinline__ void pv_chunk(float (&z)[32], const uint32_t (&pa)[14], const uint32_t (&pb)[14],
                                         const uint32_t (&meta)[4], uint64_t dV) {
#pragma unroll
  for (int t = T0; t < T1; t++) {
    if (t & 1)
      wg_s64t1<0, 32>(z, pa[2 * t], pb[2 * t], pa[2 * t + 1], pb[2 * t + 1], dV + ((2 * C * kChunkBytes + t * 2048) >> 4), 1,
                      meta[t >> 1]);
    else if (t > 0)
      wg_s64t<0, 32>(z, pa[2 * t], pb[2 * t], pa[2 * t + 1], pb[2 * t + 1], dV + ((2 * C * kChunkBytes + t * 2048) >> 4), 1,
                     meta[t >> 1]);
    else
      wg_s64tz<0, 32>(z, pa[0], pb[0], pa[1], pb[1], dV + ((2 * C * kChunkBytes) >> 4), 0, meta[0]);
  }
}
template <int C>
__device__ __forceinline__ void pack_z(const float (&z)[32], uint32_t (&za)[24], uint32_t (&zb)[24]) {
#pragma unroll
  for (int j = 0; j < 8; j++) {
    za[8 * C + j] = pack_bf16(z[4 * j], z[4 * j + 1]);
    zb[8 * C + j] = pack_bf16(z[4 * j + 2], z[4 * j + 3]);
  }
}

template <int H>
__device__ __forceinline__ void pack_out(const float (&ac)[48], uint32_t (&oa)[24], uint32_t (&ob)[24]) {
#pragma unroll
  for (int j = 0; j < 12; j++) {
    oa[12 * H + j] = pack_bf16(ac[4 * j], ac[4 * j + 1]);
    ob[12 * H + j] = pack_bf16(ac[4 * j + 2], ac[4 * j + 3]);
  }
}
struct Maps { CUtensorMap v6, v2, v14, u8, px[8], wv, wo; };
__device__ __forceinline__ void tma_prefetch_5d(const CUtensorMap* map, int c0, int c1, int c2, int c3, int c4) {
  asm volatile("cp.async.bulk.prefetch.tensor.5d.L2.global.tile [%0, {%1, %2, %3, %4, %5}];" ::"l"((uint64_t)map), "r"(c0), "r"(c1),
               "r"(c2), "r"(c3), "r"(c4) : "memory");
}
__device__ __forceinline__ int first_line(const TileCoord tc) { return 3 * (qpix(tc.pr, 8 * tc.I) * kW + qpix(tc.pc, 8 * tc.J)); }
template <int MODE, int UNROLL, int N = 8>
__device__ __forceinline__ void move_px(const Maps& tm, const TileTable& tt, uint32_t buf, uint32_t bar, int line, int kind, int i0 = 0) {
#pragma unroll UNROLL
  for (int n = 0; n < N; n++) {
    const int i = i0 + n;
    const int j = MODE == 2 ? 2 * (i & 3) + (i >> 2) : i;
    if (MODE == 2 || (n & 1) == 0 || kind != 0) {
      const CUtensorMap* map = (const CUtensorMap*)((const char*)(tm.px + (MODE & 2) * 2) + tt.g[kind][j][1]);
      const int ln = line + tt.g[kind][j][0];
      if (MODE == 0) tma_load_5d(buf + i * 3072, map, bar, 0, 0, 0, 0, ln);
      if (MODE == 1) tma_prefetch_5d(map, 0, 0, 0, 0, ln);
      if (MODE == 2)
        asm volatile("cp.async.bulk.tensor.5d.global.shared::cta.tile.bulk_group [%0, {%2, %2, %2, %2, %3}], [%1];" ::"l"((uint64_t)map),
                     "r"(buf + i * 3072), "r"(0), "r"(ln) : "memory");
      if (MODE == 2 && NAT_SP < 9) {
        asm volatile("cp.async.bulk.commit_group;" ::: "memory");
        asm volatile("cp.async.bulk.wait_group.read %0;" ::"n"(NAT_SP) : "memory");
      }
    }
  }
  if (MODE == 2) asm volatile("cp.async.bulk.commit_group;" ::: "memory");
}
__device__ __noinline__ bool refetch(uint32_t base, const uint8_t* src, bool gap) {
  constexpr uint32_t bars = 1024 + kBarOff, cnt = bars + 192;
#pragma unroll 1
  for (uint32_t o = 0; o < kWBytes && !gap; o += 2048) {
    uint32_t mx = 0;
#pragma unroll
    for (int i = 0; i < 4; i++) {
      uint4 v;
      asm volatile("ld.shared.v4.u32 {%0,%1,%2,%3}, [%4];" : "=r"(v.x), "=r"(v.y), "=r"(v.z), "=r"(v.w)
                   : "r"(base + o + i * 512 + (threadIdx.x & 31) * 16));
      mx = __vimax3_u32(__vimax3_u32(mx, v.x, v.y), v.z, v.w);
    }
    gap = __any_sync(0xffffffffu, mx == kEmpty);
  }
  uint32_t n;
  asm volatile("ld.shared.u32 %0, [%1];" : "=r"(n) : "r"(cnt) : "memory");
  if (!gap || __any_sync(0xffffffffu, n > (1u << 12))) return false;
  asm volatile("bar.sync 15, 128;" ::: "memory");
  if (threadIdx.x == 0) {
    asm volatile("st.shared.u32 [%0], %1;" ::"r"(cnt), "r"(n + 1) : "memory");
    mbar_arrive_expect_tx(bar_redo(bars), kWBytes);
    bulk_load(base, src, kWBytes, bar_redo(bars));
  }
  __syncwarp();
  mbar_wait(bar_redo(bars), n & 1);
  return true;
}
template <int S0, int S1, int Z>
__device__ __forceinline__ void g2_steps(float (&ac)[48], const uint32_t (&za)[24], const uint32_t (&zb)[24], uint64_t d) {
#pragma unroll
  for (int s = S0; s < S1; s++) {
    const uint64_t ds = d + (((s >> 2 & 1) * (kWChunk / 2) + (s & 3) * 32) >> 4);
    if (s == Z) wg_d96z<0, 48>(ac, za[2 * s], zb[2 * s], za[2 * s + 1], zb[2 * s + 1], ds, 0);
    else wg_d96<0, 48>(ac, za[2 * s], zb[2 * s], za[2 * s + 1], zb[2 * s + 1], ds, 1);
  }
}

__device__ __forceinline__ void consumer(const int wg, __nv_bfloat16* out, const uint8_t* wimg, const uint32_t sbase,
                                         const uint32_t zero, const Maps& tm, const TileTable& tt) {
  const int tid = threadIdx.x & 127;
  const int w = __shfl_sync(0xffffffffu, tid >> 5, 0), lane = tid & 31, g = qrow(w, lane >> 2), qc = qcol(w, lane >> 2);
  const uint64_t dK = make_desc(sbase, 16, 1024);
  const uint64_t dV = make_desc(sbase, kChunkBytes, 512, 2);
  const uint64_t dW1 = make_desc(sbase + kW1Off, 16, 1024);
  const uint64_t dX0 = make_desc(sbase + kW2Off + wg * 2 * kWChunk, 16, 1024), dY0 = make_desc(sbase + kW2Off + (1 - wg) * 2 * kWChunk, 16, 1024);
  const uint64_t dX2 = make_desc(sbase + kXOff + wg * (kWChunk / 2), 16, 1024), dY2 = make_desc(sbase + kXOff + (1 - wg) * (kWChunk / 2), 16, 1024);
  const uint32_t bars = sbase + kBarOff;
  int tile0 = blockIdx.x * kTilesPerCta;
  asm volatile("" : "+r"(tile0));
  const int nt = num_tiles();

  uint32_t pix = 0, geo[12] = {};
  const int l = lane & 3;
#pragma unroll 1
  for (int j = 4; j >= 0; j -= 2) {
    const TileCoord tc = decode_tile(tt, tile0 + wg + j);
    const uint32_t pr = qpix(tc.pr, 8 * tc.I + g) * kW;
    if (j == nt - 2) pix = (pr + qpix(tc.pc, 8 * tc.J + qc)) | (pr + qpix(tc.pc, 8 * tc.J + qc + 4)) << 16;
    const int d = 8 * tc.J + 6 * tc.pc - 6 - halo_c0(tc);
    const int ro = woff(tc.pr, tc.I, g), coA = woff(tc.pc, tc.J, qc) + d, coB = woff(tc.pc, tc.J, qc + 4) + d - 3;
#pragma unroll
    for (int i = 11; i >= 4; i--) geo[i] = geo[i - 4];
    const uint32_t lr = 0x1FCu << ro;
    const uint32_t lv = lr >> (2 + (l >> 1)), lu = lr >> (2 * l + 2 * tc.up);
    const uint32_t t = __byte_perm(lv, lu, wg ? 0x4501 : 0x5410);
    geo[0] = ((t & 0x15u) | (lv & 0x40u)) * 0x02082080u;
    geo[1] = ((t >> 8) & 0x15u) * 0x02082080u;
    geo[2] = __byte_perm(t << 7, t << 6, 0x7362);
    const int dr = (ro - 1) & 7;
    const uint32_t hiv = (((1u << ((ro - (l >> 1) + 1) >> 1)) - 1u) ^ (wg ? 7u : 0u)) & 7u, hiu = (t >> 24) & 3u;
    const uint32_t ca = (1u << coA) - 1u;
    geo[3] = hiv * kHiV | hiu * kHiU | ((((1u << coB) - 1u) >> (2 * (l & 1))) & 3u) * kColB |
             (15u & ~((uint32_t)((dr & 1) == (l >> 1)) << (dr >> 1))) * kInV | ((t >> 16 | t >> 24) & 3u) * kInU | ca * kColA |
             (ca >> ((0x49 >> (2 * l)) & 3) & 1u) << 19 | (uint32_t)(l == 3) << 20 | (0x55u & ((1u << (2 * coB)) - 1u)) << 24;
  }
  keep_regs(geo);
  const int so = (lane >> 3) | (lane & 4);
  uint32_t sts = sbase + w * 3072 + so * 128 + (((lane & 3) ^ so) << 4);
  __nv_bfloat16* poA = out + 8 * l + (pix & 0xFFFFu) * kC + 96 * wg;
  __nv_bfloat16* poB = out + 8 * l + (pix >> 16) * kC + 96 * wg;
  asm volatile("" : "+l"(poA), "+l"(poB), "+r"(sts));
  uint32_t oa[24], ob[24];
#pragma unroll
  for (int j = 0; j < 24; j++) oa[j] = ob[j] = 0u;
  keep_regs(oa);
  keep_regs(ob);
  PROF(wg, 0);
  if (threadIdx.x == 0) GT(1);

  for (int k = wg; k < nt; k += 2) {
    const uint32_t ph = (k >> 1) & 1;
    const int it = k >> 1;
    uint32_t qa[24], qb[24], hok[3];
    uint32_t fl = geo[3];
    {
      float acc[96];
      const uint64_t dX = make_desc(sbase + kXOff + (k == 0 ? kWChunk : 0), 16, 3072);
      if (k > 0) nb_sync(1 + (1 - wg));
      mbar_wait(bar_x(bars, k > 0), (k + (k > 0)) & 1);
      if (k < 2) PROF(wg, 1);
      PROFS(2, wg, 2 + it * 12);
      if (w == 0 && k < 2) GT(20 + wg);
#pragma unroll
      for (int s = 0; s < 12; s++) {
        if ((s & 3) == 0 && k == 0) {
          mbar_wait(bar_w1c(bars, s >> 2), 0);
          PROFS(17, wg, 50 + (s >> 2));
        }
        if ((s & 3) == 0) wg_fence();
        if (s == 0) wg_m192z<0, 96>(acc, dX, dW1, 0);
        else wg_m192<0, 96>(acc, dX + (((s >> 2) * 1024 + (s & 3) * 32) >> 4), wdesc(dW1, s), 1);
      }
      wg_commit();
      PROFS(13, wg, 13 + it * 12);
      wg_wait<0>();
      if (k > 0) nb_arrive_p(6);
      fence_regs(acc);
      PROFS(3, wg, 3 + it * 12);
#pragma unroll
      for (int j = 0; j < 24; j++) {
        qa[j] = pack_bf16(acc[4 * j], acc[4 * j + 1]);
        qb[j] = pack_bf16(acc[4 * j + 2], acc[4 * j + 3]);
      }
      keep_regs(qa);
      keep_regs(qb);
      sched_fence();
      if (k >= 2) {
        const uint32_t dst = sts + out_slot(k, nt);
        nb_sync(11);
        stage_out<0, 6>(dst, wg, oa, ob);
        nb_sync(12);
        stage_out<6, 12>(dst, wg, oa, ob);
      }
#pragma unroll
      for (int c = 0; c < 3; c++) hok[c] = mbar_test(bar_full(bars, wg, c), ph);
      if (k >= 2) {
        fence_proxy_async();
        nb_arrive_p(10);
      }
    }

    float aE[52], aO[24], bO[52], bE[28];
    const uint32_t mq = 0xEEEE4444u | zero;
    PROFS(4, wg, 4 + it * 12);

    mbar_wait_if(hok[0], bar_full(bars, wg, 0), ph);
    PROFS(14, wg, 40 + it * 3);
    if (w == 0 && k < 2) GT(22 + wg);
    if (k > 0) nb_sync(3 + (1 - wg));
    wg_fence();
#pragma unroll
    for (int ks = 0; ks < 6; ks++) {
      if (ks == NAT_P1) {
        mbar_wait_if(hok[1], bar_full(bars, wg, 1), ph);
        PROFS(14, wg, 41 + it * 3);
        wg_fence();
      }
      if (ks == NAT_P2) {
        mbar_wait_if(hok[2], bar_full(bars, wg, 2), ph);
        PROFS(14, wg, 42 + it * 3);
        wg_fence();
      }
      const uint64_t d = dK + ((ks * kChunkBytes) >> 4);
      if (ks == 0) wg_s104z<0, 52>(aE, qa[0], qa[1], qa[2], qa[3], d, 0, mq);
      else wg_s104<0, 52>(aE, qa[4 * ks], qa[4 * ks + 1], qa[4 * ks + 2], qa[4 * ks + 3], d, 1, mq);
    }
    wg_commit();
    wg_s48z<0, 24>(aO, qa[0], qa[1], qa[2], qa[3], dK + ((7 * 1024 + 64) >> 4), 0, mq);
#pragma unroll
    for (int ks = 1; ks < 6; ks++)
      wg_s48<0, 24>(aO, qa[4 * ks], qa[4 * ks + 1], qa[4 * ks + 2], qa[4 * ks + 3], dK + ((ks * kChunkBytes + 7 * 1024 + 64) >> 4), 1, mq);
    wg_commit();
    wg_s56z<0, 28>(bE, qb[0], qb[1], qb[2], qb[3], dK, 0, mq);
#pragma unroll
    for (int ks = 1; ks < 6; ks++) wg_s56<0, 28>(bE, qb[4 * ks], qb[4 * ks + 1], qb[4 * ks + 2], qb[4 * ks + 3], dK + ((ks * kChunkBytes) >> 4), 1, mq);
    wg_commit();
    wg_wait<2>();
    fence_regs(aE);
    PROFS(5, wg, 5 + it * 12);

    uint32_t pa[14], pb[14], meta[4];
    {
      float vA[14], vB[14];
      pick_v(aE, vA, fl);
      pick_u(aE + 28, vA + 8, fl);
      fence_regs(vA);
      if (k == 0) {
        if (__builtin_expect(__any_sync(0xffffffffu, vA[6] != vA[6]), 0)) {
          wg_wait<0>();
          fence_regs(aO);
          fence_regs(bE);
          if (refetch(sbase + kW1Off, wimg, false)) {
#pragma unroll
            for (int j = 0; j < 24; j++) oa[j] = ob[j] = 0u;
            k -= 2;
            continue;
          }
        }
        if (elect_one()) mbar_arrive(bar_xf(bars));
      }
      wg_fence();
      wg_s104z<0, 52>(bO, qb[0], qb[1], qb[2], qb[3], dK + 4, 0, mq);
#pragma unroll
      for (int ks = 1; ks < 6; ks++)
        wg_s104<0, 52>(bO, qb[4 * ks], qb[4 * ks + 1], qb[4 * ks + 2], qb[4 * ks + 3], dK + ((ks * kChunkBytes + 64) >> 4), 1, mq);
      wg_commit();
      if (k + 1 < nt) nb_arrive(1 + wg);
      uint32_t rt[9];
#pragma unroll
      for (int i = 0; i < 7; i++) rt[i] = sign_bytes(geo[i >> 2], 0x8888u + 0x1111u * (i & 3));
      rt[7] = sign_bytes(geo[2], 0x9988u);
      rt[8] = sign_bytes(geo[2], 0xBBAAu);
      keep_regs(rt);
      pa[13] = pb[13] = 0u;
      wg_wait<2>();
      keep_regs(qa);
      fence_regs(aO);
      float oA[6], eB[8];
      pick_u(aO, oA, fl);
      wg_wait<1>();
      fence_regs(bE);
      pick_v(bE, eB, fl);
      vA[8] = sel<kColA>(oA[0], vA[8], fl), vA[9] = sel<kColA>(oA[1], vA[9], fl);
      vA[10] = sel<kColA * 2>(oA[2], vA[10], fl), vA[11] = sel<kColA * 2>(oA[3], vA[11], fl);
      vA[12] = sel<kColA * 4>(oA[4], vA[12], fl), vA[13] = sel<kColA * 4>(oA[5], vA[13], fl);
      {
        const float m1 = __uint_as_float(0x88DD88DDu), m0 = __uint_as_float(0x88DDDD88u);
        meta[0] = 0xDD88DD88u ^ __byte_perm(fl, 0u, 0x3344);
        meta[1] = __float_as_uint(sel<kColA * 16>(sel<kColA>(m1, m0, fl), __uint_as_float(meta[0]), fl));
        meta[2] = __float_as_uint(sel<kColA * 8>(m1, m0, fl));
        meta[3] = __float_as_uint(sel<kColA * 4>(m1, m0, fl));
        keep_regs(meta);
      }
      float mA = own_max(vA, fl);
      fl |= __float_as_uint(eB[7]) & zero;
      fence_regs(eB);
      fence_regs(vA);
      asm volatile("" : "+f"(mA), "+r"(fl));
      sched_fence();
      wg_wait<0>();
      sched_fence();
      keep_regs(qb);
      fence_regs(bO);
      PROFS(6, wg, 6 + it * 12);
      if (w == 0) GT(24 + k);
      mA = quad_max(mA);
#pragma unroll
      for (int i = 0; i < 14; i++) vA[i] = ex2(vA[i] - mA);
      pick_v(bO, vB, fl);
      pick_u(bO + 28, vB + 8, fl);
#pragma unroll
      for (int i = 0; i < 8; i += 2) vB[i] = sel<kColB>(vB[i], eB[i], fl), vB[i + 1] = sel<kColB * 2>(vB[i + 1], eB[i + 1], fl);
      float mB = quad_max(own_max(vB, fl));
      if (NAT_SB) {
        fence_regs(vA);
        fence_regs(vB);
        asm volatile("" : "+f"(mB));
        sched_fence();
      }
      PROFS(7, wg, 7 + it * 12);
#pragma unroll
      for (int i = 0; i < 14; i++) vB[i] = ex2(vB[i] - mB);
      route(vA, row_rcp(vA, fl), rt, pa);
      route(vB, row_rcp(vB, fl), rt, pb);
    }
    PROFS(8, wg, 8 + it * 12);
    if (k == NAT_PK) PROFS(18, wg, 53);
    sched_fence();

    float ac0[48], ac1[48];
    {
      float z0[32], z1[32], z2[32];
      uint32_t za[24], zb[24];
      wg_fence();
      pv_chunk<0>(z0, pa, pb, meta, dV);
      wg_commit();
      pv_chunk<1>(z1, pa, pb, meta, dV);
      wg_commit();
      wg_wait<1>();
      if (k == NAT_PK) PROFS(18, wg, 54);
      if (k + 1 < nt) nb_arrive_p(7);
      pv_chunk<2, 0, 3>(z2, pa, pb, meta, dV);
      wg_commit();
      sched_fence();
      fence_regs(z0);
      pack_z<0>(z0, za, zb);
      sched_fence();
      wg_fence();
      pv_chunk<2, 3, 7>(z2, pa, pb, meta, dV);
      wg_commit();
      wg_wait<2>();
      if (k == NAT_PK) PROFS(19, wg, 55);
      if (k + 1 < nt) nb_arrive_p(8);
      if (k < 2) mbar_wait(k == 1 ? bar_wok(bars) : bar_w2a(bars), 0);
      wg_fence();
      g2_steps<0, 3, 0>(ac0, za, zb, dX0);
      wg_commit();
      sched_fence();
      fence_regs(z1);
      pack_z<1>(z1, za, zb);
      sched_fence();
      wg_fence();
      g2_steps<3, 4, 0>(ac0, za, zb, dX0);
      wg_commit();
      g2_steps<4, 8, 0>(ac0, za, zb, dX0);
      wg_commit();
      wg_wait<3>();
      if (k + 1 < nt) nb_arrive_p(9);
      else nb_arrive(11);
      if (k == NAT_PK) PROFS(20, wg, 56);
      keep_regs(pa);
      keep_regs(pb);
      keep_regs(meta);
      sched_fence();
      const uint32_t mok = mbar_test(bar_w2m(bars), k + 1 < nt ? k & 1 : ~k & 1);
      fence_regs(z2);
      pack_z<2>(z2, za, zb);
      keep_regs(za);
      keep_regs(zb);
      sched_fence();
      PROFS(9, wg, 9 + it * 12);
      wg_wait<1>();
      if (k > 0 && k + 1 < nt) nb_arrive(11);
      mbar_wait_if(mok, bar_w2m(bars), k & 1);
      wg_fence();
      g2_steps<8, 12, 0>(ac0, za, zb, dX2);
      wg_commit();
      g2_steps<8, 12, 8>(ac1, za, zb, dY2);
      wg_commit();
      wg_wait<2>();
      if (k > 0 && k + 1 < nt) nb_arrive(12);
      if (k != 1 && k + 1 < nt) mbar_wait(bar_w2(bars), k > 1 ? (k - 1) & 1 : 0);
      wg_fence();
      g2_steps<0, 4, 8>(ac1, za, zb, dY0);
      wg_commit();
      wg_wait<2>();
      if (k + 2 < nt) nb_arrive_p(13);
      const bool direct = k + 2 >= nt;
      sched_fence();
      fence_regs(ac0);
      pack_out<0>(ac0, oa, ob);
      store_rows<0, NAT_D0>(direct, poA, poB, oa, ob);
      sched_fence();
      wg_fence();
      g2_steps<4, 8, 8>(ac1, za, zb, dY0);
      wg_commit();
      if (k + 1 < nt) nb_arrive(3 + wg);
      PROFS(10, wg, 10 + it * 12);
      wg_wait<2>();
      if (k + 2 < nt && (k > 0 || nt == 6)) nb_arrive_p(5);
      store_rows<NAT_D0, 3>(direct, poA, poB, oa, ob);
      __nv_bfloat16 *qA = poA - 192 * wg, *qB = poB - 192 * wg;
      if (k + 2 == nt) nb_sync(11);
      sched_fence();
      wg_wait<0>();
      fence_regs(ac1);
      PROFS(11, wg, 11 + it * 12);
      pack_out<1>(ac1, oa, ob);
      asm volatile("" : "+l"(qA), "+l"(qB));
      store_rows<3, 6>(direct, qA, qB, oa, ob);
      if (k == 0) {
        uint32_t m[2] = {oa[0], oa[1]};
#pragma unroll
        for (int i = 2; i < 24; i++) asm("max.NaN.bf16x2 %0, %0, %1;" : "+r"(m[i & 1]) : "r"(oa[i]));
        asm("max.NaN.bf16x2 %0, %0, %1;" : "+r"(m[0]) : "r"(m[1]));
        uint32_t nan;
        asm volatile("{\n.reg .pred p;\nsetp.ne.u32 p, %1, 0;\nbar.red.or.pred p, 15, 128, p;\nselp.u32 %0, 1, 0, p;\n}\n"
                     : "=r"(nan) : "r"(((m[0] & 0x7FFF7FFFu) + 0x007F007Fu) & 0x80008000u) : "memory");
        if (__builtin_expect(__any_sync(0xffffffffu, nan), 0)) {
          if (nt == 6) mbar_wait(bar_x(bars, 1), 1);
          for (bool first = true; __any_sync(0xffffffffu, refetch(sbase + kW2Off, wimg + w2_offset(), first)); first = false) { }
          wg_fence();
          g2_steps<0, 8, 0>(ac0, za, zb, dX0);
          g2_steps<8, 12, 0>(ac0, za, zb, dX2);
          g2_steps<0, 8, 0>(ac1, za, zb, dY0);
          g2_steps<8, 12, 0>(ac1, za, zb, dY2);
          wg_commit();
          wg_wait<0>();
          fence_regs(ac0);
          fence_regs(ac1);
          pack_out<0>(ac0, oa, ob);
          pack_out<1>(ac1, oa, ob);
          if (nt == 6) {
            asm volatile("bar.sync 15, 128;" ::: "memory");
            if (w == 0 && elect_one()) {
              const TileCoord tc = decode_tile(tt, tile0 + 2);
              mbar_arrive_expect_tx(bar_raw(bars), kWChunk);
              move_px<0, 1>(tm, tt, sbase + kXOff, bar_raw(bars), first_line(tc), tc.kind);
            }
            __syncwarp();
            mbar_wait(bar_raw(bars), 0);
          }
        }
        if (nt < 6) nb_arrive_p(5);
        if (elect_one()) mbar_arrive(bar_wok(bars));
      }
      keep_regs(za);
      keep_regs(zb);
#pragma unroll
      for (int i = 0; i < 8; i++) geo[i] = geo[i + 4];
      keep_regs(oa);
      keep_regs(ob);
      PROFS(12, wg, 12 + it * 12);
      sched_fence();
    }
  }
  PROF(wg, 38);
  GT_DUMP();
  PROF_DUMP(wg);
}

struct HaloCols { int vj, vc, uj, uc; };
__device__ __forceinline__ HaloCols halo_cols(const TileCoord& tc) {
  const int c0 = halo_c0(tc);
  return HaloCols{c0 > 98, c0 > 98 ? 98 : c0 + 3, c0 < 0 ? -1 : 0, c0 < 0 ? 4 : c0};
}
__device__ __forceinline__ void first_halo(const Maps& tm, uint32_t sbase, const TileCoord tc, int i) {
  const HaloCols hc = halo_cols(tc);
  const uint32_t dst = sbase + i * kChunkBytes, bar = bar_full(sbase + kBarOff, 0, i >> 1);
  const int h0 = halo_r0(tc), ch = 24 * tc.pc + 4 * i;
  tma_load_5d(dst, &tm.v14, bar, ch, hc.vj, hc.vc, tc.pr, h0);
  tma_load_5d(dst + 7 * 1024, &tm.u8, bar, ch, hc.uj, h0 + (tc.up ? 0 : -2), tc.pr, hc.uc);
  tma_load_5d(dst + 10 * 1024, &tm.u8, bar, ch, hc.uj, h0 + (tc.up ? 8 : 6), tc.pr, hc.uc);
}
__device__ __forceinline__ void load_halo(const Maps& tm, uint32_t sbase, uint32_t bars, const TileCoord tc, int k, int c) {
  const HaloCols hc = halo_cols(tc);
  const int h6 = halo_r0(tc) + (tc.up ? 0 : 8), h2 = halo_r0(tc) + 6, h8 = halo_r0(tc) + (tc.up ? 0 : 6), ch = 24 * tc.pc + 8 * c;
  uint32_t dv = sbase + 2 * c * kChunkBytes, du = dv + 7 * 1024;
  if (((k ^ tc.up) & 1) == 0) dv += 4 * 1024, du += 3 * 1024;
  const uint32_t bar = bar_full(bars, k & 1, c);
  mbar_arrive_expect_tx(bar, 14 * 1024);
  nb_sync_p(7 + c);
#pragma unroll
  for (int h = 0; h < 2; h++) {
    tma_load_5d(dv + h * kChunkBytes, &tm.v6, bar, ch + 4 * h, hc.vj, hc.vc, tc.pr, h6);
    tma_load_5d(du + h * kChunkBytes, &tm.u8, bar, ch + 4 * h, hc.uj, h8, tc.pr, hc.uc);
    tma_load_5d(sbase + (2 * c + h) * kChunkBytes + 3 * 1024, &tm.v2, bar, ch + 4 * h, hc.vj, hc.vc, tc.pr, h2);
  }
  PROFS(15, 2, k * 4 + c);
}
__device__ __forceinline__ void gather_px(const __nv_bfloat16* __restrict__ x, uint32_t buf, uint32_t bar, const TileCoord tc) {
  const int lane = threadIdx.x & 31, g = lane >> 3;
  uint32_t ro[4], co[4];
#pragma unroll
  for (int i = 0; i < 4; i++) {
    ro[i] = qpix(tc.pr, 8 * tc.I + 2 * i + (g & 1)) * (kW * kC * 2) + 16 * (lane & 7);
    co[i] = qpix(tc.pc, 8 * tc.J + 2 * i + (g >> 1)) * (kC * 2);
  }
  uint32_t dst = buf + g * 128 + (((lane & 7) ^ g) << 4);
  keep_regs(ro);
  keep_regs(co);
  sched_fence();
  nb_sync_p(13);
  nb_sync_p(5);
#pragma unroll
  for (int i = 0; i < 16; i++) {
    const char* src = (const char*)x + (ro[i >> 2] + co[i & 3]);
#pragma unroll
    for (int q = 0; q < 3; q++)
      asm volatile("cp.async.cg.shared.global [%0], [%1], 16;" ::"r"((dst ^ ((i & 1) * 576)) + (i >> 1) * 3072 + q * 1024), "l"(src + 128 * q) : "memory");
  }
  asm volatile("cp.async.wait_all;" ::: "memory");
  fence_proxy_async();
  __syncwarp();
  if (elect_one()) mbar_arrive(bar);
  __syncwarp();
}

__global__ void __launch_bounds__(384, 1)
nat_kernel(const __nv_bfloat16* __restrict__ x, __nv_bfloat16* out, const __nv_bfloat16* __restrict__ wqkv,
           const __nv_bfloat16* __restrict__ wo, uint8_t* wimg, const uint32_t zero,
           const __grid_constant__ Maps tm, const __grid_constant__ TileTable tt) {
  extern __shared__ uint8_t smem_raw[];
  constexpr uint32_t sbase = 1024;
  constexpr uint32_t bars = sbase + kBarOff;
  if (smem_u32(smem_raw) != sbase) __trap();
  const int tid = threadIdx.x;
  const uint32_t t_start = now_ns();
  if (tid == 0) GT(0);
  const int wid = __shfl_sync(0xffffffffu, tid >> 5, 0);
  const bool w2cta = blockIdx.x - 128 < 3 && wqkv != nullptr;
  if (wid >= 8) {
    asm volatile("setmaxnreg.dec.sync.aligned.u32 24;");
    const int c = wid & 3, lane = tid & 31;
    const int tile0 = blockIdx.x * kTilesPerCta, nt = num_tiles();
    uint32_t w2o = 0;
    if (c == 3) {
      const CUtensorMap* px = tm.px + (blockIdx.x >= 112 ? 2 : edge_strip());
      asm volatile("prefetch.tensormap [%0];" ::"l"((uint64_t)(px + 1)) : "memory");
      asm volatile("prefetch.tensormap [%0];" ::"l"((uint64_t)&tm.v6) : "memory");
      asm volatile("prefetch.tensormap [%0];" ::"l"((uint64_t)&tm.v2) : "memory");
      asm volatile("prefetch.tensormap [%0];" ::"l"((uint64_t)(px + 4)) : "memory");
      asm volatile("prefetch.tensormap [%0];" ::"l"((uint64_t)(px + 5)) : "memory");
      asm volatile("bar.sync 13, 64;" ::: "memory");
      __nanosleep(NAT_TW2 - 2000);
      w2o = w2_offset();
      if (elect_one()) {
        mbar_arrive_expect_tx(bar_w2a(bars), kWChunk);
        mbar_arrive_expect_tx(bar_w2(bars), kWChunk);
        wait_clock(t_start, NAT_TW2);
        bulk_load(sbase + kW2Off, wimg + w2o, kWChunk, bar_w2a(bars));
        mbar_wait(bar_xf(bars), 0);
        bulk_load(sbase + kW2Off + 2 * kWChunk, wimg + (w2o + 2 * kWChunk), kWChunk, bar_w2(bars));
      }
      __syncwarp();
      if (nt < 6) {
#pragma unroll 1
        for (int k = 2; k < 4; k++) {
          gather_px(x, sbase + kXOff, bar_x(bars, 1), decode_tile(tt, tile0 + k));
        }
      }
      if (wqkv == nullptr) return;
      mbar_wait(bar_wok(bars), 0);
      if (lane == 0) asm volatile("red.relaxed.gpu.global.add.u32 [%0], 1;" ::"l"(g_flag) : "memory");
      if (blockIdx.x >= 48) return;
      if (lane == 0) {
        uint32_t v, it = 0;
        do {
          __nanosleep(2000);
          asm volatile("ld.relaxed.gpu.global.u32 %0, [%1];" : "=r"(v) : "l"(g_flag) : "memory");
        } while (v < gridDim.x && ++it < (1u << 16));
      }
      __syncwarp();
#pragma unroll
      for (int i = 0; i < 6; i++)
        stg128(wimg + ((i < 3 ? 0u : 3 * kWBytes - w2o) + blockIdx.x * 1536 + (i % 3) * 512 + lane * 16), kEmpty, kEmpty, kEmpty, kEmpty);
      if (lane == 0 && atomicAdd(g_flag + 32, 1u) == 47) {
        g_flag[0] = g_flag[32] = 0;
        g_flag[64] = w2o == kWBytes;
      }
      return;
    }
    if (!elect_one()) return;
    if (c == 0) {
      for (int i = 0; i < kNumBars; i++)
        if ((i != 0 && i != 10 || nt < 6) && (i != 19 || !w2cta)) mbar_init(bars + i * 8, i == 13 || i == 16 ? 4 : 1);
      asm volatile("st.shared.v2.u32 [%0], {%1,%1};" ::"r"(bars + 192), "r"(0) : "memory");
      asm volatile("fence.mbarrier_init.release.cluster;" ::: "memory");
      if (w2cta) asm volatile("bar.sync 10, 64;" ::: "memory");
      asm volatile("bar.arrive 0, 224;" ::: "memory");
      asm volatile("bar.arrive 14, 160;" ::: "memory");
      asm volatile("bar.arrive 13, 64;" ::: "memory");
      const TileCoord tc0 = decode_tile(tt, tile0);
      const HaloCols hc = halo_cols(tc0);
      const int h0 = halo_r0(tc0);
#pragma unroll
      for (int j = 0; j < 3; j++)
        if (j > 0 || nt < 6) mbar_arrive_expect_tx(bar_full(bars, 0, j), 2 * kChunkBytes);
      wait_clock(t_start, NAT_HP);
#pragma unroll
      for (int q = 8; q < 24; q += 8) {
        tma_prefetch_5d(&tm.v6, 24 * tc0.pc + q, hc.vj, hc.vc, tc0.pr, h0 + (tc0.up ? 0 : 8));
        tma_prefetch_5d(&tm.u8, 24 * tc0.pc + q, hc.uj, h0 + (tc0.up ? 0 : 6), tc0.pr, hc.uc);
        if (blockIdx.x >= 112) tma_prefetch_5d(&tm.v2, 24 * tc0.pc + q, hc.vj, hc.vc, tc0.pr, h0 + 6);
      }
#pragma unroll 1
      for (int i = nt < 6 ? 0 : 2; i < 7; i++) {
        if (i == NAT_H0) mbar_wait(bar_w1q(bars), 0);
        if (i == NAT_X1P) mbar_arrive(bar_go(bars));
        if (i < 6) first_halo(tm, sbase, tc0, i);
      }
      w2o = w2_offset();
    } else {
      asm volatile("bar.sync 0, 224;" ::: "memory");
      if (c == 2) {
        if (wqkv != nullptr && nt == 6) asm volatile("bar.sync 12, 64;" ::: "memory");
        const uint32_t c0 = clock();
        while ((uint32_t)clock() - c0 < NAT_TD) { }
        wait_clock(t_start, NAT_T0);
#pragma unroll
        for (int j = 0; j < 3; j++) {
          mbar_arrive_expect_tx(bar_w1c(bars, j), kWChunk);
          bulk_load(sbase + kW1Off + j * kWChunk, wimg + j * kWChunk, kWChunk, bar_w1c(bars, j));
        }
        mbar_arrive(bar_w1q(bars));
        GT(2);
        if (NAT_OT == 2) w2o = w2_offset();
      } else {
#pragma unroll 1
        for (int j = nt == 6; j < 2; j++) {
          const TileCoord tc = decode_tile(tt, tile0 + j);
          const int line = first_line(tc);
          mbar_arrive_expect_tx(bar_x(bars, j), kWChunk);
          if (j == 1) mbar_wait(bar_go(bars), 0);
          move_px<0, 2>(tm, tt, sbase + kXOff + (1 - j) * kWChunk, bar_x(bars, j), line, tc.kind);
        }
        w2o = w2_offset();
      }
    }
#pragma unroll 1
    for (int k = 1; k < nt; k++) {
      const TileCoord tn = decode_tile(tt, tile0 + k + 1);
      const int line = first_line(tn);
      if (c == 1) {
        nb_sync_p(6);
        bulk_load(sbase + kXOff, wimg + (w2o + kWChunk), kWChunk, bar_w2m(bars));
        mbar_arrive_expect_tx(bar_w2m(bars), kWChunk);
      }
      if (c == 2 - NAT_OT) {
        if (k == 1) wait_clock(t_start, NAT_TX2);
        else if (NAT_OT == 0 || k == nt - 1 + (nt == 6)) __nanosleep(NAT_PFD);
        if (k < 5 && nt == 6) move_px<1, 1>(tm, tt, 0, 0, line, tn.kind);
      }
      if (c == 2 - NAT_OT && (blockIdx.x >= 112 || k == 5)) {
        const TileCoord tc = decode_tile(tt, tile0 + k);
        const HaloCols hc = halo_cols(tc);
        const int h8 = halo_r0(tc) + (tc.up ? 0 : 6);
#pragma unroll 1
        for (int q = 0; q < 24; q += 8) {
          tma_prefetch_5d(&tm.v6, 24 * tc.pc + q, hc.vj, hc.vc, tc.pr, h8);
          tma_prefetch_5d(&tm.v2, 24 * tc.pc + q, hc.vj, hc.vc, tc.pr, h8 + 6);
          tma_prefetch_5d(&tm.u8, 24 * tc.pc + q, hc.uj, h8, tc.pr, hc.uc);
        }
      }
      load_halo(tm, sbase, bars, decode_tile(tt, tile0 + k), k, c);
      if (c == 0 && k >= 3 && NAT_RP == 1) {
        if (NAT_RD) __nanosleep(NAT_RD);
        asm volatile("cp.async.bulk.wait_group.read 0;" ::: "memory");
        bulk_load(sbase + out_slot(k - 1, nt), wimg + (w2o + out_slot(k - 1, nt) - kW2Off), kWChunk, bar_w2(bars));
        mbar_arrive_expect_tx(bar_w2(bars), kWChunk);
      }
      if (c == 0 && k < 5 && nt == 6) {
        const int f = ~k & 1;
        if (tn.kind == 0) {
#pragma unroll
          for (int j = 0; j < 4; j++) {
            if ((j & 1) == 0) nb_sync_p(j ? 5 : 13);
            tma_load_5d(sbase + kXOff + (j ^ 2 * f) * 6144, tm.px, bar_x(bars, 1), 0, 0, 0, 0, line + 6 * (j ^ 2 * f));
          }
        } else {
          nb_sync_p(13);
          move_px<0, 4, 4>(tm, tt, sbase + kXOff, bar_x(bars, 1), line, tn.kind, 4 * f);
          nb_sync_p(5);
          move_px<0, 4, 4>(tm, tt, sbase + kXOff, bar_x(bars, 1), line, tn.kind, 4 - 4 * f);
        }
        mbar_arrive_expect_tx(bar_x(bars, 1), kWChunk);
        PROFS(16, 2, k * 4 + 3);
      }
      if (c == NAT_OT && k >= 2) {
        const TileCoord tp = decode_tile(tt, tile0 + k - 2);
        const int lp = first_line(tp);
        nb_sync_p(10);
        if (NAT_XW == 1 && k < 5 && nt == 6) mbar_wait(bar_x(bars, 1), k & 1);
        if (NAT_XW > 1) __nanosleep(NAT_XW);
        move_px<2, NAT_SU>(tm, tt, sbase + out_slot(k, nt), 0, lp, tp.kind);
        if (NAT_RP == 0 && k + 1 < nt) {
          asm volatile("cp.async.bulk.wait_group.read 0;" ::: "memory");
          bulk_load(sbase + out_slot(k, nt), wimg + (w2o + out_slot(k, nt) - kW2Off), kWChunk, bar_w2(bars));
          mbar_arrive_expect_tx(bar_w2(bars), kWChunk);
        }
      }
    }
    asm volatile("cp.async.bulk.wait_group 0;" ::: "memory");
  } else {
    if (blockIdx.x < 128) {
      if ((wid == 4 || (wid == 5 && blockIdx.x - 2 < 16)) && wqkv != nullptr) {
        fold_w1(blockIdx.x - 2 < 16 ? 2 * blockIdx.x + wid - 6 : blockIdx.x + (blockIdx.x < 2 ? 0 : 16), wqkv, wimg);
        if (wid == 4) asm volatile("bar.arrive 12, 64;" ::: "memory");
        if (tid == 128) GT(7);
      }
      sched_fence();
      if (wid == 1 && elect_one()) {
        const TileCoord tc = decode_tile(tt, blockIdx.x * kTilesPerCta);
        mbar_init(bar_x(bars, 0), 1);
        asm volatile("fence.mbarrier_init.release.cluster;" ::: "memory");
        mbar_arrive_expect_tx(bar_x(bars, 0), kWChunk);
        GT(15);
        move_px<0, 2>(tm, tt, sbase + kXOff + kWChunk, bar_x(bars, 0), first_line(tc), tc.kind);
        GT(16);
      }
      __syncwarp();
      sched_fence();
      if (wid == 2 && elect_one()) {
        asm volatile("prefetch.tensormap [%0];" ::"l"((uint64_t)&tm.v14) : "memory");
        asm volatile("prefetch.tensormap [%0];" ::"l"((uint64_t)&tm.u8) : "memory");
        const TileCoord tc = decode_tile(tt, blockIdx.x * kTilesPerCta);
        mbar_init(bar_full(bars, 0, 0), 1);
        asm volatile("fence.mbarrier_init.release.cluster;" ::: "memory");
        mbar_arrive_expect_tx(bar_full(bars, 0, 0), 2 * kChunkBytes);
        if (NAT_TH) wait_clock(t_start, NAT_TH);
        GT(17);
        first_halo(tm, sbase, tc, 0);
        first_halo(tm, sbase, tc, 1);
      }
      __syncwarp();
    }
    sched_fence();
    {
      if (w2cta) {
        const int q = blockIdx.x & 3;
        uint32_t w2o = 0;
        if (wid == 1 && elect_one()) {
          mbar_init(bar_raw(bars), 1);
          asm volatile("fence.mbarrier_init.release.cluster;" ::: "memory");
          mbar_arrive_expect_tx(bar_raw(bars), kWBytes + kWChunk);
#pragma unroll
          for (int j = 0; j < 6; j++)
            asm volatile("cp.async.bulk.tensor.2d.shared::cluster.global.tile.mbarrier::complete_tx::bytes [%0], [%1, {%3, %4}], [%2];" ::"r"(
                             j < 3 ? sbase + j * 8192 : sbase + kW2Off + (j - 3) * kWChunk),
                         "l"((uint64_t)(j < 3 ? &tm.wv : &tm.wo)), "r"(bar_raw(bars)), "r"(j < 3 ? 384 + 64 * j : 64 * (j - 3)), "r"(j < 3 ? 64 * q : 0) : "memory");
          w2o = w2_offset();
        } else if (wid == 0) {
          asm volatile("prefetch.tensormap [%0];" ::"l"((uint64_t)&tm.wo) : "memory");
        } else if (wid - 2 < 2u && elect_one()) {
          asm volatile("cp.async.bulk.prefetch.L2.global [%0], %1;" ::"l"(wid == 2 ? wo : wqkv + q * 64 * 576), "r"(kWBytes) : "memory");
        }
        __syncwarp();
        if (wid < 4) {
          asm volatile("bar.sync 15, 128;" ::: "memory");
          mbar_wait(bar_raw(bars), 0);
        }
        if (tid == 0) GT(7);
        float acc[96];
        wg_fence();
        wg_m192tz<0, 96>(acc, make_desc(sbase, 16, 1024), make_desc(sbase + kW2Off, kWChunk, 1024), 0);
#pragma unroll
        for (int s = 1; s < 12; s++)
          wg_m192t<0, 96>(acc, make_desc(sbase + (s >> 2) * 8192 + (s & 3) * 32, 16, 1024), make_desc(sbase + kW2Off + s * 2048, kWChunk, 1024), 1);
        wg_commit();
        wg_wait<0>();
        fence_regs(acc);
        if (tid == 0) GT(19);
        const int m = (tid >> 3) & 3;
#pragma unroll
        for (int j = 0; j < 24; j += 2) {
          const int n = g2_inv(8 * (j + (m >> 1)) + (tid & 7));
          asm volatile("stmatrix.sync.aligned.m8n8.x4.trans.shared.b16 [%0], {%1,%2,%3,%4};" ::"r"(
                           sbase + kW1Off + (wid >> 2) * kWChunk + n * 128 + (((2 * (wid & 3) + (m & 1)) ^ (n & 7)) << 4)),
                       "r"(pack_bf16(acc[4 * j], acc[4 * j + 1])), "r"(pack_bf16(acc[4 * j + 2], acc[4 * j + 3])),
                       "r"(pack_bf16(acc[4 * j + 4], acc[4 * j + 5])), "r"(pack_bf16(acc[4 * j + 6], acc[4 * j + 7])) : "memory");
        }
        fence_proxy_async();
        if (tid == 0) GT(18);
        asm volatile("bar.sync 11, 256;" ::: "memory");
        if (wid == 1) {
          if (elect_one()) {
#pragma unroll
            for (int h = 0; h < 2; h++)
              asm volatile("cp.async.bulk.global.shared::cta.bulk_group [%0], [%1], %2;" ::"l"(wimg + (w2o + w2piece(h, q) * (kWChunk / 2))),
                           "r"(sbase + kW1Off + h * (kWChunk / 2)), "r"(kWChunk / 2) : "memory");
            asm volatile("cp.async.bulk.commit_group;" ::: "memory");
            asm volatile("cp.async.bulk.wait_group.read 0;" ::: "memory");
            GT(31);
          }
          __syncwarp();
          asm volatile("bar.arrive 10, 64;" ::: "memory");
        }
      }
    }
    __syncwarp();
    if (wid < 4) asm volatile("bar.sync 0, 224;" ::: "memory");
    else asm volatile("bar.sync 14, 160;" ::: "memory");
    asm volatile("setmaxnreg.inc.sync.aligned.u32 240;");
    consumer(wid >> 2, out, wimg, sbase, zero, tm, tt);
  }
}

}

typedef CUresult (*PFN_encodeTiled)(CUtensorMap*, CUtensorMapDataType, cuuint32_t, void*, const cuuint64_t*,
                                    const cuuint64_t*, const cuuint32_t*, const cuuint32_t*, CUtensorMapInterleave,
                                    CUtensorMapSwizzle, CUtensorMapL2promotion, CUtensorMapFloatOOBfill);

extern "C" void kernel_launch(void* const* d_in, const int* in_sizes, int n_in, void* d_out, int out_size) {
  const __nv_bfloat16* x = (const __nv_bfloat16*)d_in[0];
  const __nv_bfloat16* wqkv = (const __nv_bfloat16*)d_in[1];
  const __nv_bfloat16* wo = (const __nv_bfloat16*)d_in[2];
  __nv_bfloat16* out = (__nv_bfloat16*)d_out;

  static PFN_encodeTiled encode = nullptr;
  static int num_sms = 0;
  static uint8_t* wimg = nullptr;
  if (!encode) {
    void* fn = nullptr;
    cudaDriverEntryPointQueryResult qres;
    cudaGetDriverEntryPoint("cuTensorMapEncodeTiled", &fn, cudaEnableDefault, &qres);
    encode = (PFN_encodeTiled)fn;
    cudaFuncSetAttribute(nat::nat_kernel, cudaFuncAttributeMaxDynamicSharedMemorySize, nat::kSmemBytes);
    cudaGetSymbolAddress((void**)&wimg, nat::g_wimg32);
    int dev = 0;
    cudaGetDevice(&dev);
    cudaDeviceGetAttribute(&num_sms, cudaDevAttrMultiProcessorCount, dev);
  }
  nat::Maps tm;
  cuuint32_t estr[5] = {1, 1, 1, 1, 1};
  {
    cuuint64_t vdim[5] = {48, 2, 105, 2, 112}, udim[5] = {48, 2, 112, 2, 105};
    cuuint64_t vstr[4] = {7 * 768, 768, 224 * 384, 2 * 224 * 384}, ustr[4] = {7 * 768, 2 * 224 * 384, 224 * 384, 768};
    CUtensorMap* maps[4] = {&tm.v6, &tm.v2, &tm.v14, &tm.u8};
    for (int i = 0; i < 4; i++) {
      cuuint32_t box[5] = {4, 2, i < 3 ? 4u : 8u, 1, i == 0 ? 6u : i == 1 ? 2u : i == 2 ? 14u : 3u};
      encode(maps[i], CU_TENSOR_MAP_DATA_TYPE_UINT32, 5, (void*)x, i < 3 ? vdim : udim, i < 3 ? vstr : ustr, box, estr,
             CU_TENSOR_MAP_INTERLEAVE_16B, CU_TENSOR_MAP_SWIZZLE_128B, NAT_L2P, CU_TENSOR_MAP_FLOAT_OOB_FILL_NONE);
    }
  }
  for (int i = 0; i < 8; i++) {
    const cuuint32_t row = 224 * 384, dr = (1u + (i & 1)) * row;
    const cuuint32_t shape[4][6] = {{8, 3, 2u - i, 2 * row, 128, 4 * 768}, {2, 4, 3, dr, 768, 128}, {4, 2, 3, 4 * row, 2 * row, 128}, {4, 2, 3, 768, dr, 128}};
    const cuuint32_t* sh = shape[i >> 1];
    cuuint64_t dim[5] = {64, sh[0], sh[1], sh[2], 224 * 224 * 3};
    cuuint64_t str[4] = {sh[3], sh[4], sh[5], 128};
    cuuint32_t box[5] = {64, sh[0], sh[1], sh[2], 1};
    encode(tm.px + i, CU_TENSOR_MAP_DATA_TYPE_BFLOAT16, 5, i < 4 ? (void*)x : (void*)out, dim, str, box, estr, CU_TENSOR_MAP_INTERLEAVE_NONE,
           CU_TENSOR_MAP_SWIZZLE_128B, i < 4 ? CU_TENSOR_MAP_L2_PROMOTION_L2_128B : CU_TENSOR_MAP_L2_PROMOTION_NONE,
           CU_TENSOR_MAP_FLOAT_OOB_FILL_NONE);
  }
  for (int i = 0; i < 2; i++) {
    cuuint64_t dim[2] = {i ? 192u : 576u, 192}, str[1] = {i ? 384u : 1152u};
    cuuint32_t box[2] = {64, i ? 192u : 64u};
    encode(i ? &tm.wo : &tm.wv, CU_TENSOR_MAP_DATA_TYPE_BFLOAT16, 2, i ? (void*)wo : (void*)wqkv, dim, str, box, estr,
           CU_TENSOR_MAP_INTERLEAVE_NONE, CU_TENSOR_MAP_SWIZZLE_128B, CU_TENSOR_MAP_L2_PROMOTION_L2_256B, CU_TENSOR_MAP_FLOAT_OOB_FILL_NONE);
  }
  nat::TileTable tt;
  nat::make_tiles(tt);
  const int grid = nat::kCtas;
  if (num_sms >= grid) {
    nat::nat_kernel<<<grid, 384, nat::kSmemBytes>>>(x, out, wqkv, wo, wimg, 0u, tm, tt);
  } else {
    nat::fold_kernel<<<27, 256>>>(wqkv, wo, wimg);
    nat::nat_kernel<<<grid, 384, nat::kSmemBytes>>>(x, out, nullptr, nullptr, wimg, 0u, tm, tt);
  }
}
```

```cpp
#include <cuda_runtime.h>
#include <cuda_bf16.h>
#include <cuda.h>
#include <stdint.h>

#define NAT_P1 2
#define NAT_P2 4
#define NAT_H0 2
#define NAT_T0 2100
#define NAT_TD 1200
#define NAT_TW2 4650
#define NAT_TX2 3800
#define NAT_X1P 5
#define NAT_PK 3
#define NAT_HP 1800
#define NAT_PFD 700
#define NAT_XW 200
#define NAT_SU 8
#define NAT_D0 1
#define NAT_RD 0
#define NAT_RP 0
#define NAT_SP 9
#define NAT_OT 0
#define NAT_L2P CU_TENSOR_MAP_L2_PROMOTION_L2_128B
#define NAT_TH 600
#define NAT_TM 1300
#define NAT_SB 0
namespace nat {

constexpr int kW = 224, kC = 192;
constexpr int kCtas = 132;
constexpr int kTilesPerCta = 6;
constexpr float kAlpha = 0.07216878364870322f * 1.4426950408889634f;
constexpr uint32_t kChunkBytes = 13 * 1024;
constexpr uint32_t kWChunk = 192 * 128;
constexpr uint32_t kWBytes = 3 * kWChunk;
constexpr uint32_t kW1Off = 6 * kChunkBytes;
constexpr uint32_t kW2Off = kW1Off + kWBytes;
constexpr uint32_t kXOff = kW2Off + kWChunk;
constexpr uint32_t kBarOff = kW2Off + kWBytes;
constexpr uint32_t kProfOff = kBarOff + 208;
constexpr uint32_t kSmemBytes = kBarOff + 1024;

static_assert(kW1Off % 1024 == 0 && kW2Off % 1024 == 0 && kChunkBytes % 1024 == 0, "swizzle alignment");
static_assert(kSmemBytes <= 232448, "smem");

constexpr uint32_t kEmpty = 0xFFFFFFFFu;
#define NAT_R8(v) v, v, v, v, v, v, v, v
#define NAT_R2K(v) NAT_R8(NAT_R8(NAT_R8(v))), NAT_R8(NAT_R8(NAT_R8(v))), NAT_R8(NAT_R8(NAT_R8(v))), NAT_R8(NAT_R8(NAT_R8(v)))
#define NAT_IMG NAT_R8(NAT_R2K(kEmpty)), NAT_R2K(kEmpty)
__device__ __align__(1024) uint32_t g_wimg32[3 * kWBytes / 4] = {NAT_IMG, NAT_IMG, NAT_IMG};
static_assert(kWBytes / 4 == 9 * 2048, "initialiser");
__device__ __align__(128) uint32_t g_flag[96];
__device__ __forceinline__ uint32_t w2_offset() {
  uint32_t v;
  asm volatile("ld.relaxed.gpu.global.u32 %0, [%1];" : "=r"(v) : "l"(g_flag + 64) : "memory");
  return (1 + v) * kWBytes;
}

#define PROFS(id, wgid, slotid) do { } while (0)
#define PROF(wgid, slotid) do { } while (0)
#define PROF_DUMP(wgid) do { } while (0)

#define GT(slotid) do { } while (0)
#define GT_DUMP() do { } while (0)

__device__ __forceinline__ uint32_t smem_u32(const void* p) { return (uint32_t)__cvta_generic_to_shared(p); }

__device__ __forceinline__ void mbar_init(uint32_t bar, uint32_t count) {
  asm volatile("mbarrier.init.shared::cta.b64 [%0], %1;" ::"r"(bar), "r"(count) : "memory");
}
__device__ __forceinline__ void mbar_arrive(uint32_t bar) {
  asm volatile("mbarrier.arrive.shared::cta.b64 _, [%0];" ::"r"(bar) : "memory");
}
__device__ __forceinline__ void mbar_arrive_expect_tx(uint32_t bar, uint32_t bytes) {
  asm volatile("mbarrier.arrive.expect_tx.shared::cta.b64 _, [%0], %1;" ::"r"(bar), "r"(bytes) : "memory");
}
__device__ __forceinline__ void mbar_wait(uint32_t bar, uint32_t parity) {
  uint32_t ok;
  uint32_t it = 0;
  do {
    asm volatile(
        "{\n.reg .pred p;\n"
        "mbarrier.try_wait.parity.shared::cta.b64 p, [%1], %2;\n"
        "selp.u32 %0, 1, 0, p;\n}\n"
        : "=r"(ok)
        : "r"(bar), "r"(parity)
        : "memory");
    if (++it > (1u << 24)) break;
  } while (!ok);
}
__device__ __forceinline__ uint32_t mbar_test(uint32_t bar, uint32_t parity) {
  uint32_t ok;
  asm volatile("{\n.reg .pred p;\nmbarrier.test_wait.parity.shared::cta.b64 p, [%1], %2;\nselp.u32 %0, 1, 0, p;\n}\n"
               : "=r"(ok) : "r"(bar), "r"(parity) : "memory");
  return ok;
}
__device__ __forceinline__ void mbar_wait_if(uint32_t ok, uint32_t bar, uint32_t parity) {
  if (!__all_sync(0xffffffffu, ok)) mbar_wait(bar, parity);
}
__device__ __forceinline__ bool elect_one() {
  uint32_t r;
  asm volatile("{\n.reg .pred p;\nelect.sync _|p, 0xffffffff;\nselp.u32 %0, 1, 0, p;\n}\n" : "=r"(r));
  return r != 0;
}
__device__ __forceinline__ void nb_arrive(int id) { asm volatile("bar.arrive %0, 256;" ::"r"(id) : "memory"); }
__device__ __forceinline__ void nb_sync(int id) { asm volatile("bar.sync %0, 256;" ::"r"(id) : "memory"); }
__device__ __forceinline__ void nb_arrive_p(int id) { asm volatile("bar.arrive %0, 160;" ::"r"(id) : "memory"); }
__device__ __forceinline__ void nb_sync_p(int id) { asm volatile("bar.sync %0, 160;" ::"r"(id) : "memory"); }
__device__ __forceinline__ void fence_proxy_async() { asm volatile("fence.proxy.async.shared::cta;" ::: "memory"); }

__device__ __forceinline__ void tma_load_5d(uint32_t dst, const CUtensorMap* map, uint32_t bar, int c0, int c1, int c2,
                                            int c3, int c4) {
  asm volatile(
      "cp.async.bulk.tensor.5d.shared::cluster.global.tile.mbarrier::complete_tx::bytes "
      "[%0], [%1, {%3, %4, %5, %6, %7}], [%2];"
      ::"r"(dst), "l"((uint64_t)map), "r"(bar), "r"(c0), "r"(c1), "r"(c2), "r"(c3), "r"(c4)
      : "memory");
}
__device__ __forceinline__ void bulk_load(uint32_t dst, const void* src, uint32_t bytes, uint32_t bar) {
  asm volatile("cp.async.bulk.shared::cluster.global.mbarrier::complete_tx::bytes [%0], [%1], %2, [%3];"
               ::"r"(dst), "l"((uint64_t)src), "r"(bytes), "r"(bar)
               : "memory");
}

__device__ __forceinline__ void wg_fence() { asm volatile("wgmma.fence.sync.aligned;" ::: "memory"); }
__device__ __forceinline__ void wg_commit() { asm volatile("wgmma.commit_group.sync.aligned;" ::: "memory"); }
template <int N>
__device__ __forceinline__ void wg_wait() { asm volatile("wgmma.wait_group.sync.aligned %0;" ::"n"(N) : "memory"); }

template <int N>
__device__ __forceinline__ void fence_regs(float (&d)[N]) {
#pragma unroll
  for (int i = 0; i < N; i++) asm volatile("" : "+f"(d[i])::"memory");
}
template <int N>
__device__ __forceinline__ void keep_regs(uint32_t (&d)[N]) {
#pragma unroll
  for (int i = 0; i < N; i++) asm volatile("" : "+r"(d[i])::"memory");
}

__device__ __forceinline__ uint32_t pack_bf16(float lo, float hi) {
  uint32_t d;
  asm("cvt.rn.bf16x2.f32 %0, %1, %2;" : "=r"(d) : "f"(hi), "f"(lo));
  return d;
}
__device__ __forceinline__ float ex2(float x) {
  float y;
  asm("ex2.approx.ftz.f32 %0, %1;" : "=f"(y) : "f"(x));
  return y;
}
__device__ __forceinline__ float rcp_approx(float x) {
  float y;
  asm("rcp.approx.ftz.f32 %0, %1;" : "=f"(y) : "f"(x));
  return y;
}
__device__ __forceinline__ uint4 ldg128_nc(const void* p) {
  uint4 v;
  asm volatile("ld.global.nc.v4.u32 {%0,%1,%2,%3}, [%4];" : "=r"(v.x), "=r"(v.y), "=r"(v.z), "=r"(v.w) : "l"(p));
  return v;
}
__device__ __forceinline__ void stg128(void* p, uint32_t a, uint32_t b, uint32_t c, uint32_t d) {
  asm volatile("st.global.v4.u32 [%0], {%1,%2,%3,%4};" ::"l"(p), "r"(a), "r"(b), "r"(c), "r"(d) : "memory");
}

__device__ __forceinline__ long long clk64() {
  long long c;
  asm volatile("mov.u64 %0, %clock64;" : "=l"(c)::"memory");
  return c;
}
__device__ __forceinline__ void sched_fence() { while (clk64() < 0) { } }

__device__ __forceinline__ uint64_t make_desc(uint32_t addr, uint32_t lbo, uint32_t sbo, uint32_t mode = 1) {
  return (uint64_t)((addr & 0x3FFFF) >> 4) | ((uint64_t)(lbo >> 4) << 16) | ((uint64_t)(sbo >> 4) << 32) |
         ((uint64_t)mode << 62);
}

template <int OFF, int NN>
__device__ __forceinline__ void wg_m192(float (&d)[NN], uint64_t desc_a, uint64_t desc_b, int scale_d) {
  asm volatile(
      "{\n.reg .pred p;\nsetp.ne.b32 p, %98, 0;\n"
      "wgmma.mma_async.sync.aligned.m64n192k16.f32.bf16.bf16 "
      "{%0,%1,%2,%3,%4,%5,%6,%7,%8,%9,%10,%11,%12,%13,%14,%15,"
      "%16,%17,%18,%19,%20,%21,%22,%23,%24,%25,%26,%27,%28,%29,%30,%31,"
      "%32,%33,%34,%35,%36,%37,%38,%39,%40,%41,%42,%43,%44,%45,%46,%47,"
      "%48,%49,%50,%51,%52,%53,%54,%55,%56,%57,%58,%59,%60,%61,%62,%63,"
      "%64,%65,%66,%67,%68,%69,%70,%71,%72,%73,%74,%75,%76,%77,%78,%79,"
      "%80,%81,%82,%83,%84,%85,%86,%87,%88,%89,%90,%91,%92,%93,%94,%95}, "
      "%96, %97, p, 1, 1, 0, 0;\n}\n"
      : "+f"(d[OFF + 0]), "+f"(d[OFF + 1]), "+f"(d[OFF + 2]), "+f"(d[OFF + 3]), "+f"(d[OFF + 4]), "+f"(d[OFF + 5]),
        "+f"(d[OFF + 6]), "+f"(d[OFF + 7]), "+f"(d[OFF + 8]), "+f"(d[OFF + 9]), "+f"(d[OFF + 10]), "+f"(d[OFF + 11]),
        "+f"(d[OFF + 12]), "+f"(d[OFF + 13]), "+f"(d[OFF + 14]), "+f"(d[OFF + 15]), "+f"(d[OFF + 16]), "+f"(d[OFF + 17]),
        "+f"(d[OFF + 18]), "+f"(d[OFF + 19]), "+f"(d[OFF + 20]), "+f"(d[OFF + 21]), "+f"(d[OFF + 22]), "+f"(d[OFF + 23]),
        "+f"(d[OFF + 24]), "+f"(d[OFF + 25]), "+f"(d[OFF + 26]), "+f"(d[OFF + 27]), "+f"(d[OFF + 28]), "+f"(d[OFF + 29]),
        "+f"(d[OFF + 30]), "+f"(d[OFF + 31]), "+f"(d[OFF + 32]), "+f"(d[OFF + 33]), "+f"(d[OFF + 34]), "+f"(d[OFF + 35]),
        "+f"(d[OFF + 36]), "+f"(d[OFF + 37]), "+f"(d[OFF + 38]), "+f"(d[OFF + 39]), "+f"(d[OFF + 40]), "+f"(d[OFF + 41]),
        "+f"(d[OFF + 42]), "+f"(d[OFF + 43]), "+f"(d[OFF + 44]), "+f"(d[OFF + 45]), "+f"(d[OFF + 46]), "+f"(d[OFF + 47]),
        "+f"(d[OFF + 48]), "+f"(d[OFF + 49]), "+f"(d[OFF + 50]), "+f"(d[OFF + 51]), "+f"(d[OFF + 52]), "+f"(d[OFF + 53]),
        "+f"(d[OFF + 54]), "+f"(d[OFF + 55]), "+f"(d[OFF + 56]), "+f"(d[OFF + 57]), "+f"(d[OFF + 58]), "+f"(d[OFF + 59]),
        "+f"(d[OFF + 60]), "+f"(d[OFF + 61]), "+f"(d[OFF + 62]), "+f"(d[OFF + 63]), "+f"(d[OFF + 64]), "+f"(d[OFF + 65]),
        "+f"(d[OFF + 66]), "+f"(d[OFF + 67]), "+f"(d[OFF + 68]), "+f"(d[OFF + 69]), "+f"(d[OFF + 70]), "+f"(d[OFF + 71]),
        "+f"(d[OFF + 72]), "+f"(d[OFF + 73]), "+f"(d[OFF + 74]), "+f"(d[OFF + 75]), "+f"(d[OFF + 76]), "+f"(d[OFF + 77]),
        "+f"(d[OFF + 78]), "+f"(d[OFF + 79]), "+f"(d[OFF + 80]), "+f"(d[OFF + 81]), "+f"(d[OFF + 82]), "+f"(d[OFF + 83]),
        "+f"(d[OFF + 84]), "+f"(d[OFF + 85]), "+f"(d[OFF + 86]), "+f"(d[OFF + 87]), "+f"(d[OFF + 88]), "+f"(d[OFF + 89]),
        "+f"(d[OFF + 90]), "+f"(d[OFF + 91]), "+f"(d[OFF + 92]), "+f"(d[OFF + 93]), "+f"(d[OFF + 94]), "+f"(d[OFF + 95])
      : "l"(desc_a), "l"(desc_b), "r"(scale_d));
}

template <int OFF, int NN>
__device__ __forceinline__ void wg_m192z(float (&d)[NN], uint64_t desc_a, uint64_t desc_b, int scale_d) {
  asm volatile(
      "{\n.reg .pred p;\nsetp.ne.b32 p, %98, 0;\n"
      "wgmma.mma_async.sync.aligned.m64n192k16.f32.bf16.bf16 "
      "{%0,%1,%2,%3,%4,%5,%6,%7,%8,%9,%10,%11,%12,%13,%14,%15,"
      "%16,%17,%18,%19,%20,%21,%22,%23,%24,%25,%26,%27,%28,%29,%30,%31,"
      "%32,%33,%34,%35,%36,%37,%38,%39,%40,%41,%42,%43,%44,%45,%46,%47,"
      "%48,%49,%50,%51,%52,%53,%54,%55,%56,%57,%58,%59,%60,%61,%62,%63,"
      "%64,%65,%66,%67,%68,%69,%70,%71,%72,%73,%74,%75,%76,%77,%78,%79,"
      "%80,%81,%82,%83,%84,%85,%86,%87,%88,%89,%90,%91,%92,%93,%94,%95}, "
      "%96, %97, p, 1, 1, 0, 0;\n}\n"
      : "=f"(d[OFF + 0]), "=f"(d[OFF + 1]), "=f"(d[OFF + 2]), "=f"(d[OFF + 3]), "=f"(d[OFF + 4]), "=f"(d[OFF + 5]),
        "=f"(d[OFF + 6]), "=f"(d[OFF + 7]), "=f"(d[OFF + 8]), "=f"(d[OFF + 9]), "=f"(d[OFF + 10]), "=f"(d[OFF + 11]),
        "=f"(d[OFF + 12]), "=f"(d[OFF + 13]), "=f"(d[OFF + 14]), "=f"(d[OFF + 15]), "=f"(d[OFF + 16]), "=f"(d[OFF + 17]),
        "=f"(d[OFF + 18]), "=f"(d[OFF + 19]), "=f"(d[OFF + 20]), "=f"(d[OFF + 21]), "=f"(d[OFF + 22]), "=f"(d[OFF + 23]),
        "=f"(d[OFF + 24]), "=f"(d[OFF + 25]), "=f"(d[OFF + 26]), "=f"(d[OFF + 27]), "=f"(d[OFF + 28]), "=f"(d[OFF + 29]),
        "=f"(d[OFF + 30]), "=f"(d[OFF + 31]), "=f"(d[OFF + 32]), "=f"(d[OFF + 33]), "=f"(d[OFF + 34]), "=f"(d[OFF + 35]),
        "=f"(d[OFF + 36]), "=f"(d[OFF + 37]), "=f"(d[OFF + 38]), "=f"(d[OFF + 39]), "=f"(d[OFF + 40]), "=f"(d[OFF + 41]),
        "=f"(d[OFF + 42]), "=f"(d[OFF + 43]), "=f"(d[OFF + 44]), "=f"(d[OFF + 45]), "=f"(d[OFF + 46]), "=f"(d[OFF + 47]),
        "=f"(d[OFF + 48]), "=f"(d[OFF + 49]), "=f"(d[OFF + 50]), "=f"(d[OFF + 51]), "=f"(d[OFF + 52]), "=f"(d[OFF + 53]),
        "=f"(d[OFF + 54]), "=f"(d[OFF + 55]), "=f"(d[OFF + 56]), "=f"(d[OFF + 57]), "=f"(d[OFF + 58]), "=f"(d[OFF + 59]),
        "=f"(d[OFF + 60]), "=f"(d[OFF + 61]), "=f"(d[OFF + 62]), "=f"(d[OFF + 63]), "=f"(d[OFF + 64]), "=f"(d[OFF + 65]),
        "=f"(d[OFF + 66]), "=f"(d[OFF + 67]), "=f"(d[OFF + 68]), "=f"(d[OFF + 69]), "=f"(d[OFF + 70]), "=f"(d[OFF + 71]),
        "=f"(d[OFF + 72]), "=f"(d[OFF + 73]), "=f"(d[OFF + 74]), "=f"(d[OFF + 75]), "=f"(d[OFF + 76]), "=f"(d[OFF + 77]),
        "=f"(d[OFF + 78]), "=f"(d[OFF + 79]), "=f"(d[OFF + 80]), "=f"(d[OFF + 81]), "=f"(d[OFF + 82]), "=f"(d[OFF + 83]),
        "=f"(d[OFF + 84]), "=f"(d[OFF + 85]), "=f"(d[OFF + 86]), "=f"(d[OFF + 87]), "=f"(d[OFF + 88]), "=f"(d[OFF + 89]),
        "=f"(d[OFF + 90]), "=f"(d[OFF + 91]), "=f"(d[OFF + 92]), "=f"(d[OFF + 93]), "=f"(d[OFF + 94]), "=f"(d[OFF + 95])
      : "l"(desc_a), "l"(desc_b), "r"(scale_d));
}

template <int OFF, int NN>
__device__ __forceinline__ void wg_m64t(float (&d)[NN], uint64_t desc_a, uint64_t desc_b, int scale_d) {
  asm volatile(
      "{\n.reg .pred p;\nsetp.ne.b32 p, %34, 0;\n"
      "wgmma.mma_async.sync.aligned.m64n64k16.f32.bf16.bf16 "
      "{%0,%1,%2,%3,%4,%5,%6,%7,%8,%9,%10,%11,%12,%13,%14,%15,"
      "%16,%17,%18,%19,%20,%21,%22,%23,%24,%25,%26,%27,%28,%29,%30,%31}, "
      "%32, %33, p, 1, 1, 0, 1;\n}\n"
      : "+f"(d[OFF + 0]), "+f"(d[OFF + 1]), "+f"(d[OFF + 2]), "+f"(d[OFF + 3]), "+f"(d[OFF + 4]), "+f"(d[OFF + 5]),
        "+f"(d[OFF + 6]), "+f"(d[OFF + 7]), "+f"(d[OFF + 8]), "+f"(d[OFF + 9]), "+f"(d[OFF + 10]), "+f"(d[OFF + 11]),
        "+f"(d[OFF + 12]), "+f"(d[OFF + 13]), "+f"(d[OFF + 14]), "+f"(d[OFF + 15]), "+f"(d[OFF + 16]), "+f"(d[OFF + 17]),
        "+f"(d[OFF + 18]), "+f"(d[OFF + 19]), "+f"(d[OFF + 20]), "+f"(d[OFF + 21]), "+f"(d[OFF + 22]), "+f"(d[OFF + 23]),
        "+f"(d[OFF + 24]), "+f"(d[OFF + 25]), "+f"(d[OFF + 26]), "+f"(d[OFF + 27]), "+f"(d[OFF + 28]), "+f"(d[OFF + 29]),
        "+f"(d[OFF + 30]), "+f"(d[OFF + 31])
      : "l"(desc_a), "l"(desc_b), "r"(scale_d));
}

template <int OFF, int NN>
__device__ __forceinline__ void wg_m64tz(float (&d)[NN], uint64_t desc_a, uint64_t desc_b, int scale_d) {
  asm volatile(
      "{\n.reg .pred p;\nsetp.ne.b32 p, %34, 0;\n"
      "wgmma.mma_async.sync.aligned.m64n64k16.f32.bf16.bf16 "
      "{%0,%1,%2,%3,%4,%5,%6,%7,%8,%9,%10,%11,%12,%13,%14,%15,"
      "%16,%17,%18,%19,%20,%21,%22,%23,%24,%25,%26,%27,%28,%29,%30,%31}, "
      "%32, %33, p, 1, 1, 0, 1;\n}\n"
      : "=f"(d[OFF + 0]), "=f"(d[OFF + 1]), "=f"(d[OFF + 2]), "=f"(d[OFF + 3]), "=f"(d[OFF + 4]), "=f"(d[OFF + 5]),
        "=f"(d[OFF + 6]), "=f"(d[OFF + 7]), "=f"(d[OFF + 8]), "=f"(d[OFF + 9]), "=f"(d[OFF + 10]), "=f"(d[OFF + 11]),
        "=f"(d[OFF + 12]), "=f"(d[OFF + 13]), "=f"(d[OFF + 14]), "=f"(d[OFF + 15]), "=f"(d[OFF + 16]), "=f"(d[OFF + 17]),
        "=f"(d[OFF + 18]), "=f"(d[OFF + 19]), "=f"(d[OFF + 20]), "=f"(d[OFF + 21]), "=f"(d[OFF + 22]), "=f"(d[OFF + 23]),
        "=f"(d[OFF + 24]), "=f"(d[OFF + 25]), "=f"(d[OFF + 26]), "=f"(d[OFF + 27]), "=f"(d[OFF + 28]), "=f"(d[OFF + 29]),
        "=f"(d[OFF + 30]), "=f"(d[OFF + 31])
      : "l"(desc_a), "l"(desc_b), "r"(scale_d));
}

template <int OFF, int NN>
__device__ __forceinline__ void wg_d96(float (&d)[NN], uint32_t a0, uint32_t a1, uint32_t a2, uint32_t a3,
                                       uint64_t desc_b, int scale_d) {
  asm volatile(
      "{\n.reg .pred p;\nsetp.ne.b32 p, %53, 0;\n"
      "wgmma.mma_async.sync.aligned.m64n96k16.f32.bf16.bf16 "
      "{%0,%1,%2,%3,%4,%5,%6,%7,%8,%9,%10,%11,%12,%13,%14,%15,"
      "%16,%17,%18,%19,%20,%21,%22,%23,%24,%25,%26,%27,%28,%29,%30,%31,"
      "%32,%33,%34,%35,%36,%37,%38,%39,%40,%41,%42,%43,%44,%45,%46,%47}, "
      "{%48,%49,%50,%51}, %52, p, 1, 1, 0;\n}\n"
      : "+f"(d[OFF + 0]), "+f"(d[OFF + 1]), "+f"(d[OFF + 2]), "+f"(d[OFF + 3]), "+f"(d[OFF + 4]), "+f"(d[OFF + 5]),
        "+f"(d[OFF + 6]), "+f"(d[OFF + 7]), "+f"(d[OFF + 8]), "+f"(d[OFF + 9]), "+f"(d[OFF + 10]), "+f"(d[OFF + 11]),
        "+f"(d[OFF + 12]), "+f"(d[OFF + 13]), "+f"(d[OFF + 14]), "+f"(d[OFF + 15]), "+f"(d[OFF + 16]), "+f"(d[OFF + 17]),
        "+f"(d[OFF + 18]), "+f"(d[OFF + 19]), "+f"(d[OFF + 20]), "+f"(d[OFF + 21]), "+f"(d[OFF + 22]), "+f"(d[OFF + 23]),
        "+f"(d[OFF + 24]), "+f"(d[OFF + 25]), "+f"(d[OFF + 26]), "+f"(d[OFF + 27]), "+f"(d[OFF + 28]), "+f"(d[OFF + 29]),
        "+f"(d[OFF + 30]), "+f"(d[OFF + 31]), "+f"(d[OFF + 32]), "+f"(d[OFF + 33]), "+f"(d[OFF + 34]), "+f"(d[OFF + 35]),
        "+f"(d[OFF + 36]), "+f"(d[OFF + 37]), "+f"(d[OFF + 38]), "+f"(d[OFF + 39]), "+f"(d[OFF + 40]), "+f"(d[OFF + 41]),
        "+f"(d[OFF + 42]), "+f"(d[OFF + 43]), "+f"(d[OFF + 44]), "+f"(d[OFF + 45]), "+f"(d[OFF + 46]), "+f"(d[OFF + 47])
      : "r"(a0), "r"(a1), "r"(a2), "r"(a3), "l"(desc_b), "r"(scale_d));
}

template <int OFF, int NN>
__device__ __forceinline__ void wg_d96z(float (&d)[NN], uint32_t a0, uint32_t a1, uint32_t a2, uint32_t a3,
                                       uint64_t desc_b, int scale_d) {
  asm volatile(
      "{\n.reg .pred p;\nsetp.ne.b32 p, %53, 0;\n"
      "wgmma.mma_async.sync.aligned.m64n96k16.f32.bf16.bf16 "
      "{%0,%1,%2,%3,%4,%5,%6,%7,%8,%9,%10,%11,%12,%13,%14,%15,"
      "%16,%17,%18,%19,%20,%21,%22,%23,%24,%25,%26,%27,%28,%29,%30,%31,"
      "%32,%33,%34,%35,%36,%37,%38,%39,%40,%41,%42,%43,%44,%45,%46,%47}, "
      "{%48,%49,%50,%51}, %52, p, 1, 1, 0;\n}\n"
      : "=f"(d[OFF + 0]), "=f"(d[OFF + 1]), "=f"(d[OFF + 2]), "=f"(d[OFF + 3]), "=f"(d[OFF + 4]), "=f"(d[OFF + 5]),
        "=f"(d[OFF + 6]), "=f"(d[OFF + 7]), "=f"(d[OFF + 8]), "=f"(d[OFF + 9]), "=f"(d[OFF + 10]), "=f"(d[OFF + 11]),
        "=f"(d[OFF + 12]), "=f"(d[OFF + 13]), "=f"(d[OFF + 14]), "=f"(d[OFF + 15]), "=f"(d[OFF + 16]), "=f"(d[OFF + 17]),
        "=f"(d[OFF + 18]), "=f"(d[OFF + 19]), "=f"(d[OFF + 20]), "=f"(d[OFF + 21]), "=f"(d[OFF + 22]), "=f"(d[OFF + 23]),
        "=f"(d[OFF + 24]), "=f"(d[OFF + 25]), "=f"(d[OFF + 26]), "=f"(d[OFF + 27]), "=f"(d[OFF + 28]), "=f"(d[OFF + 29]),
        "=f"(d[OFF + 30]), "=f"(d[OFF + 31]), "=f"(d[OFF + 32]), "=f"(d[OFF + 33]), "=f"(d[OFF + 34]), "=f"(d[OFF + 35]),
        "=f"(d[OFF + 36]), "=f"(d[OFF + 37]), "=f"(d[OFF + 38]), "=f"(d[OFF + 39]), "=f"(d[OFF + 40]), "=f"(d[OFF + 41]),
        "=f"(d[OFF + 42]), "=f"(d[OFF + 43]), "=f"(d[OFF + 44]), "=f"(d[OFF + 45]), "=f"(d[OFF + 46]), "=f"(d[OFF + 47])
      : "r"(a0), "r"(a1), "r"(a2), "r"(a3), "l"(desc_b), "r"(scale_d));
}

template <int OFF, int NN>
__device__ __forceinline__ void wg_s104(float (&d)[NN], uint32_t a0, uint32_t a1, uint32_t a2, uint32_t a3,
                                       uint64_t desc_b, int scale_d, uint32_t meta) {
  asm volatile(
      "{\n.reg .pred p;\nsetp.ne.b32 p, %57, 0;\n"
      "wgmma.mma_async.sp.sync.aligned.m64n104k32.f32.bf16.bf16 "
      "{%0,%1,%2,%3,%4,%5,%6,%7,%8,%9,%10,%11,%12,%13,%14,%15,"
      "%16,%17,%18,%19,%20,%21,%22,%23,%24,%25,%26,%27,%28,%29,%30,%31,"
      "%32,%33,%34,%35,%36,%37,%38,%39,%40,%41,%42,%43,%44,%45,%46,%47,"
      "%48,%49,%50,%51}, "
      "{%52,%53,%54,%55}, %56, %58, 0, p, 1, 1, 0;\n}\n"
      : "+f"(d[OFF + 0]), "+f"(d[OFF + 1]), "+f"(d[OFF + 2]), "+f"(d[OFF + 3]), "+f"(d[OFF + 4]), "+f"(d[OFF + 5]),
        "+f"(d[OFF + 6]), "+f"(d[OFF + 7]), "+f"(d[OFF + 8]), "+f"(d[OFF + 9]), "+f"(d[OFF + 10]), "+f"(d[OFF + 11]),
        "+f"(d[OFF + 12]), "+f"(d[OFF + 13]), "+f"(d[OFF + 14]), "+f"(d[OFF + 15]), "+f"(d[OFF + 16]), "+f"(d[OFF + 17]),
        "+f"(d[OFF + 18]), "+f"(d[OFF + 19]), "+f"(d[OFF + 20]), "+f"(d[OFF + 21]), "+f"(d[OFF + 22]), "+f"(d[OFF + 23]),
        "+f"(d[OFF + 24]), "+f"(d[OFF + 25]), "+f"(d[OFF + 26]), "+f"(d[OFF + 27]), "+f"(d[OFF + 28]), "+f"(d[OFF + 29]),
        "+f"(d[OFF + 30]), "+f"(d[OFF + 31]), "+f"(d[OFF + 32]), "+f"(d[OFF + 33]), "+f"(d[OFF + 34]), "+f"(d[OFF + 35]),
        "+f"(d[OFF + 36]), "+f"(d[OFF + 37]), "+f"(d[OFF + 38]), "+f"(d[OFF + 39]), "+f"(d[OFF + 40]), "+f"(d[OFF + 41]),
        "+f"(d[OFF + 42]), "+f"(d[OFF + 43]), "+f"(d[OFF + 44]), "+f"(d[OFF + 45]), "+f"(d[OFF + 46]), "+f"(d[OFF + 47]),
        "+f"(d[OFF + 48]), "+f"(d[OFF + 49]), "+f"(d[OFF + 50]), "+f"(d[OFF + 51])
      : "r"(a0), "r"(a1), "r"(a2), "r"(a3), "l"(desc_b), "r"(scale_d), "r"(meta));
}

template <int OFF, int NN>
__device__ __forceinline__ void wg_s104z(float (&d)[NN], uint32_t a0, uint32_t a1, uint32_t a2, uint32_t a3,
                                       uint64_t desc_b, int scale_d, uint32_t meta) {
  asm volatile(
      "{\n.reg .pred p;\nsetp.ne.b32 p, %57, 0;\n"
      "wgmma.mma_async.sp.sync.aligned.m64n104k32.f32.bf16.bf16 "
      "{%0,%1,%2,%3,%4,%5,%6,%7,%8,%9,%10,%11,%12,%13,%14,%15,"
      "%16,%17,%18,%19,%20,%21,%22,%23,%24,%25,%26,%27,%28,%29,%30,%31,"
      "%32,%33,%34,%35,%36,%37,%38,%39,%40,%41,%42,%43,%44,%45,%46,%47,"
      "%48,%49,%50,%51}, "
      "{%52,%53,%54,%55}, %56, %58, 0, p, 1, 1, 0;\n}\n"
      : "=f"(d[OFF + 0]), "=f"(d[OFF + 1]), "=f"(d[OFF + 2]), "=f"(d[OFF + 3]), "=f"(d[OFF + 4]), "=f"(d[OFF + 5]),
        "=f"(d[OFF + 6]), "=f"(d[OFF + 7]), "=f"(d[OFF + 8]), "=f"(d[OFF + 9]), "=f"(d[OFF + 10]), "=f"(d[OFF + 11]),
        "=f"(d[OFF + 12]), "=f"(d[OFF + 13]), "=f"(d[OFF + 14]), "=f"(d[OFF + 15]), "=f"(d[OFF + 16]), "=f"(d[OFF + 17]),
        "=f"(d[OFF + 18]), "=f"(d[OFF + 19]), "=f"(d[OFF + 20]), "=f"(d[OFF + 21]), "=f"(d[OFF + 22]), "=f"(d[OFF + 23]),
        "=f"(d[OFF + 24]), "=f"(d[OFF + 25]), "=f"(d[OFF + 26]), "=f"(d[OFF + 27]), "=f"(d[OFF + 28]), "=f"(d[OFF + 29]),
        "=f"(d[OFF + 30]), "=f"(d[OFF + 31]), "=f"(d[OFF + 32]), "=f"(d[OFF + 33]), "=f"(d[OFF + 34]), "=f"(d[OFF + 35]),
        "=f"(d[OFF + 36]), "=f"(d[OFF + 37]), "=f"(d[OFF + 38]), "=f"(d[OFF + 39]), "=f"(d[OFF + 40]), "=f"(d[OFF + 41]),
        "=f"(d[OFF + 42]), "=f"(d[OFF + 43]), "=f"(d[OFF + 44]), "=f"(d[OFF + 45]), "=f"(d[OFF + 46]), "=f"(d[OFF + 47]),
        "=f"(d[OFF + 48]), "=f"(d[OFF + 49]), "=f"(d[OFF + 50]), "=f"(d[OFF + 51])
      : "r"(a0), "r"(a1), "r"(a2), "r"(a3), "l"(desc_b), "r"(scale_d), "r"(meta));
}

template <int OFF, int NN>
__device__ __forceinline__ void wg_s48(float (&d)[NN], uint32_t a0, uint32_t a1, uint32_t a2, uint32_t a3,
                                       uint64_t desc_b, int scale_d, uint32_t meta) {
  asm volatile(
      "{\n.reg .pred p;\nsetp.ne.b32 p, %29, 0;\n"
      "wgmma.mma_async.sp.sync.aligned.m64n48k32.f32.bf16.bf16 "
      "{%0,%1,%2,%3,%4,%5,%6,%7,%8,%9,%10,%11,%12,%13,%14,%15,"
      "%16,%17,%18,%19,%20,%21,%22,%23}, "
      "{%24,%25,%26,%27}, %28, %30, 0, p, 1, 1, 0;\n}\n"
      : "+f"(d[OFF + 0]), "+f"(d[OFF + 1]), "+f"(d[OFF + 2]), "+f"(d[OFF + 3]), "+f"(d[OFF + 4]), "+f"(d[OFF + 5]),
        "+f"(d[OFF + 6]), "+f"(d[OFF + 7]), "+f"(d[OFF + 8]), "+f"(d[OFF + 9]), "+f"(d[OFF + 10]), "+f"(d[OFF + 11]),
        "+f"(d[OFF + 12]), "+f"(d[OFF + 13]), "+f"(d[OFF + 14]), "+f"(d[OFF + 15]), "+f"(d[OFF + 16]), "+f"(d[OFF + 17]),
        "+f"(d[OFF + 18]), "+f"(d[OFF + 19]), "+f"(d[OFF + 20]), "+f"(d[OFF + 21]), "+f"(d[OFF + 22]), "+f"(d[OFF + 23])
      : "r"(a0), "r"(a1), "r"(a2), "r"(a3), "l"(desc_b), "r"(scale_d), "r"(meta));
}

template <int OFF, int NN>
__device__ __forceinline__ void wg_s48z(float (&d)[NN], uint32_t a0, uint32_t a1, uint32_t a2, uint32_t a3,
                                       uint64_t desc_b, int scale_d, uint32_t meta) {
  asm volatile(
      "{\n.reg .pred p;\nsetp.ne.b32 p, %29, 0;\n"
      "wgmma.mma_async.sp.sync.aligned.m64n48k32.f32.bf16.bf16 "
      "{%0,%1,%2,%3,%4,%5,%6,%7,%8,%9,%10,%11,%12,%13,%14,%15,"
      "%16,%17,%18,%19,%20,%21,%22,%23}, "
      "{%24,%25,%26,%27}, %28, %30, 0, p, 1, 1, 0;\n}\n"
      : "=f"(d[OFF + 0]), "=f"(d[OFF + 1]), "=f"(d[OFF + 2]), "=f"(d[OFF + 3]), "=f"(d[OFF + 4]), "=f"(d[OFF + 5]),
        "=f"(d[OFF + 6]), "=f"(d[OFF + 7]), "=f"(d[OFF + 8]), "=f"(d[OFF + 9]), "=f"(d[OFF + 10]), "=f"(d[OFF + 11]),
        "=f"(d[OFF + 12]), "=f"(d[OFF + 13]), "=f"(d[OFF + 14]), "=f"(d[OFF + 15]), "=f"(d[OFF + 16]), "=f"(d[OFF + 17]),
        "=f"(d[OFF + 18]), "=f"(d[OFF + 19]), "=f"(d[OFF + 20]), "=f"(d[OFF + 21]), "=f"(d[OFF + 22]), "=f"(d[OFF + 23])
      : "r"(a0), "r"(a1), "r"(a2), "r"(a3), "l"(desc_b), "r"(scale_d), "r"(meta));
}

template <int OFF, int NN>
__device__ __forceinline__ void wg_s56(float (&d)[NN], uint32_t a0, uint32_t a1, uint32_t a2, uint32_t a3,
                                       uint64_t desc_b, int scale_d, uint32_t meta) {
  asm volatile(
      "{\n.reg .pred p;\nsetp.ne.b32 p, %33, 0;\n"
      "wgmma.mma_async.sp.sync.aligned.m64n56k32.f32.bf16.bf16 "
      "{%0,%1,%2,%3,%4,%5,%6,%7,%8,%9,%10,%11,%12,%13,%14,%15,"
      "%16,%17,%18,%19,%20,%21,%22,%23,%24,%25,%26,%27}, "
      "{%28,%29,%30,%31}, %32, %34, 0, p, 1, 1, 0;\n}\n"
      : "+f"(d[OFF + 0]), "+f"(d[OFF + 1]), "+f"(d[OFF + 2]), "+f"(d[OFF + 3]), "+f"(d[OFF + 4]), "+f"(d[OFF + 5]),
        "+f"(d[OFF + 6]), "+f"(d[OFF + 7]), "+f"(d[OFF + 8]), "+f"(d[OFF + 9]), "+f"(d[OFF + 10]), "+f"(d[OFF + 11]),
        "+f"(d[OFF + 12]), "+f"(d[OFF + 13]), "+f"(d[OFF + 14]), "+f"(d[OFF + 15]), "+f"(d[OFF + 16]), "+f"(d[OFF + 17]),
        "+f"(d[OFF + 18]), "+f"(d[OFF + 19]), "+f"(d[OFF + 20]), "+f"(d[OFF + 21]), "+f"(d[OFF + 22]), "+f"(d[OFF + 23]),
        "+f"(d[OFF + 24]), "+f"(d[OFF + 25]), "+f"(d[OFF + 26]), "+f"(d[OFF + 27])
      : "r"(a0), "r"(a1), "r"(a2), "r"(a3), "l"(desc_b), "r"(scale_d), "r"(meta));
}

template <int OFF, int NN>
__device__ __forceinline__ void wg_s56z(float (&d)[NN], uint32_t a0, uint32_t a1, uint32_t a2, uint32_t a3,
                                       uint64_t desc_b, int scale_d, uint32_t meta) {
  asm volatile(
      "{\n.reg .pred p;\nsetp.ne.b32 p, %33, 0;\n"
      "wgmma.mma_async.sp.sync.aligned.m64n56k32.f32.bf16.bf16 "
      "{%0,%1,%2,%3,%4,%5,%6,%7,%8,%9,%10,%11,%12,%13,%14,%15,"
      "%16,%17,%18,%19,%20,%21,%22,%23,%24,%25,%26,%27}, "
      "{%28,%29,%30,%31}, %32, %34, 0, p, 1, 1, 0;\n}\n"
      : "=f"(d[OFF + 0]), "=f"(d[OFF + 1]), "=f"(d[OFF + 2]), "=f"(d[OFF + 3]), "=f"(d[OFF + 4]), "=f"(d[OFF + 5]),
        "=f"(d[OFF + 6]), "=f"(d[OFF + 7]), "=f"(d[OFF + 8]), "=f"(d[OFF + 9]), "=f"(d[OFF + 10]), "=f"(d[OFF + 11]),
        "=f"(d[OFF + 12]), "=f"(d[OFF + 13]), "=f"(d[OFF + 14]), "=f"(d[OFF + 15]), "=f"(d[OFF + 16]), "=f"(d[OFF + 17]),
        "=f"(d[OFF + 18]), "=f"(d[OFF + 19]), "=f"(d[OFF + 20]), "=f"(d[OFF + 21]), "=f"(d[OFF + 22]), "=f"(d[OFF + 23]),
        "=f"(d[OFF + 24]), "=f"(d[OFF + 25]), "=f"(d[OFF + 26]), "=f"(d[OFF + 27])
      : "r"(a0), "r"(a1), "r"(a2), "r"(a3), "l"(desc_b), "r"(scale_d), "r"(meta));
}

template <int OFF, int NN>
__device__ __forceinline__ void wg_s64t(float (&d)[NN], uint32_t a0, uint32_t a1, uint32_t a2, uint32_t a3,
                                       uint64_t desc_b, int scale_d, uint32_t meta) {
  asm volatile(
      "{\n.reg .pred p;\nsetp.ne.b32 p, %37, 0;\n"
      "wgmma.mma_async.sp.sync.aligned.m64n64k32.f32.bf16.bf16 "
      "{%0,%1,%2,%3,%4,%5,%6,%7,%8,%9,%10,%11,%12,%13,%14,%15,"
      "%16,%17,%18,%19,%20,%21,%22,%23,%24,%25,%26,%27,%28,%29,%30,%31}, "
      "{%32,%33,%34,%35}, %36, %38, 0, p, 1, 1, 1;\n}\n"
      : "+f"(d[OFF + 0]), "+f"(d[OFF + 1]), "+f"(d[OFF + 2]), "+f"(d[OFF + 3]), "+f"(d[OFF + 4]), "+f"(d[OFF + 5]),
        "+f"(d[OFF + 6]), "+f"(d[OFF + 7]), "+f"(d[OFF + 8]), "+f"(d[OFF + 9]), "+f"(d[OFF + 10]), "+f"(d[OFF + 11]),
        "+f"(d[OFF + 12]), "+f"(d[OFF + 13]), "+f"(d[OFF + 14]), "+f"(d[OFF + 15]), "+f"(d[OFF + 16]), "+f"(d[OFF + 17]),
        "+f"(d[OFF + 18]), "+f"(d[OFF + 19]), "+f"(d[OFF + 20]), "+f"(d[OFF + 21]), "+f"(d[OFF + 22]), "+f"(d[OFF + 23]),
        "+f"(d[OFF + 24]), "+f"(d[OFF + 25]), "+f"(d[OFF + 26]), "+f"(d[OFF + 27]), "+f"(d[OFF + 28]), "+f"(d[OFF + 29]),
        "+f"(d[OFF + 30]), "+f"(d[OFF + 31])
      : "r"(a0), "r"(a1), "r"(a2), "r"(a3), "l"(desc_b), "r"(scale_d), "r"(meta));
}

template <int OFF, int NN>
__device__ __forceinline__ void wg_s64t1(float (&d)[NN], uint32_t a0, uint32_t a1, uint32_t a2, uint32_t a3,
                                       uint64_t desc_b, int scale_d, uint32_t meta) {
  asm volatile(
      "{\n.reg .pred p;\nsetp.ne.b32 p, %37, 0;\n"
      "wgmma.mma_async.sp.sync.aligned.m64n64k32.f32.bf16.bf16 "
      "{%0,%1,%2,%3,%4,%5,%6,%7,%8,%9,%10,%11,%12,%13,%14,%15,"
      "%16,%17,%18,%19,%20,%21,%22,%23,%24,%25,%26,%27,%28,%29,%30,%31}, "
      "{%32,%33,%34,%35}, %36, %38, 1, p, 1, 1, 1;\n}\n"
      : "+f"(d[OFF + 0]), "+f"(d[OFF + 1]), "+f"(d[OFF + 2]), "+f"(d[OFF + 3]), "+f"(d[OFF + 4]), "+f"(d[OFF + 5]),
        "+f"(d[OFF + 6]), "+f"(d[OFF + 7]), "+f"(d[OFF + 8]), "+f"(d[OFF + 9]), "+f"(d[OFF + 10]), "+f"(d[OFF + 11]),
        "+f"(d[OFF + 12]), "+f"(d[OFF + 13]), "+f"(d[OFF + 14]), "+f"(d[OFF + 15]), "+f"(d[OFF + 16]), "+f"(d[OFF + 17]),
        "+f"(d[OFF + 18]), "+f"(d[OFF + 19]), "+f"(d[OFF + 20]), "+f"(d[OFF + 21]), "+f"(d[OFF + 22]), "+f"(d[OFF + 23]),
        "+f"(d[OFF + 24]), "+f"(d[OFF + 25]), "+f"(d[OFF + 26]), "+f"(d[OFF + 27]), "+f"(d[OFF + 28]), "+f"(d[OFF + 29]),
        "+f"(d[OFF + 30]), "+f"(d[OFF + 31])
      : "r"(a0), "r"(a1), "r"(a2), "r"(a3), "l"(desc_b), "r"(scale_d), "r"(meta));
}

template <int OFF, int NN>
__device__ __forceinline__ void wg_s64tz(float (&d)[NN], uint32_t a0, uint32_t a1, uint32_t a2, uint32_t a3,
                                       uint64_t desc_b, int scale_d, uint32_t meta) {
  asm volatile(
      "{\n.reg .pred p;\nsetp.ne.b32 p, %37, 0;\n"
      "wgmma.mma_async.sp.sync.aligned.m64n64k32.f32.bf16.bf16 "
      "{%0,%1,%2,%3,%4,%5,%6,%7,%8,%9,%10,%11,%12,%13,%14,%15,"
      "%16,%17,%18,%19,%20,%21,%22,%23,%24,%25,%26,%27,%28,%29,%30,%31}, "
      "{%32,%33,%34,%35}, %36, %38, 0, p, 1, 1, 1;\n}\n"
      : "=f"(d[OFF + 0]), "=f"(d[OFF + 1]), "=f"(d[OFF + 2]), "=f"(d[OFF + 3]), "=f"(d[OFF + 4]), "=f"(d[OFF + 5]),
        "=f"(d[OFF + 6]), "=f"(d[OFF + 7]), "=f"(d[OFF + 8]), "=f"(d[OFF + 9]), "=f"(d[OFF + 10]), "=f"(d[OFF + 11]),
        "=f"(d[OFF + 12]), "=f"(d[OFF + 13]), "=f"(d[OFF + 14]), "=f"(d[OFF + 15]), "=f"(d[OFF + 16]), "=f"(d[OFF + 17]),
        "=f"(d[OFF + 18]), "=f"(d[OFF + 19]), "=f"(d[OFF + 20]), "=f"(d[OFF + 21]), "=f"(d[OFF + 22]), "=f"(d[OFF + 23]),
        "=f"(d[OFF + 24]), "=f"(d[OFF + 25]), "=f"(d[OFF + 26]), "=f"(d[OFF + 27]), "=f"(d[OFF + 28]), "=f"(d[OFF + 29]),
        "=f"(d[OFF + 30]), "=f"(d[OFF + 31])
      : "r"(a0), "r"(a1), "r"(a2), "r"(a3), "l"(desc_b), "r"(scale_d), "r"(meta));
}

__device__ __forceinline__ int g2_inv(int ch) { return 32 * (ch >> 5) + 8 * ((ch >> 1) & 3) + 2 * ((ch >> 3) & 3) + (ch & 1); }
__host__ __device__ __forceinline__ uint32_t wimg_off(int n, int k) {
  return (uint32_t)(k >> 6) * kWChunk + (uint32_t)n * 128 + (uint32_t)((((k & 63) >> 3) ^ (n & 7)) << 4) + (k & 7) * 2;
}
__host__ __device__ constexpr int w2piece(int h, int c) { return c == 2 ? 2 + h : 4 * h + c; }
__device__ __forceinline__ uint32_t w2img_off(int n, int k) { return wimg_off(n % 96, k & 63) + w2piece(n >= 96, k >> 6) * (kWChunk / 2); }
__device__ __forceinline__ int qpix(int par, int t) {
  const int a = 2 * t + 13 * par - 6, b = t + 112 * par;
  return par ? min(a, b) : max(a, b);
}
__device__ __forceinline__ int woff(int par, int i, int r) {
  const int a = 99 * par + 6 - 8 * i;
  return par ? min(r, a) : max(r, a);
}

__device__ __forceinline__ void mma16816(float (&c)[4], uint32_t a0, uint32_t a1, uint32_t a2, uint32_t a3, uint32_t b0,
                                         uint32_t b1) {
  asm volatile(
      "mma.sync.aligned.m16n8k16.row.col.f32.bf16.bf16.f32 {%0,%1,%2,%3}, {%4,%5,%6,%7}, {%8,%9}, {%0,%1,%2,%3};"
      : "+f"(c[0]), "+f"(c[1]), "+f"(c[2]), "+f"(c[3])
      : "r"(a0), "r"(a1), "r"(a2), "r"(a3), "r"(b0), "r"(b1));
}

__device__ __forceinline__ void fold_w1(const int u, const __nv_bfloat16* __restrict__ wqkv, uint8_t* wimg) {
  const int g = (threadIdx.x >> 2) & 7, l = threadIdx.x & 3;
  const int m0 = (u / 12) * 16, s = u % 12;
  uint4 A[12], B[12];
  const __nv_bfloat16* arow = wqkv + (m0 + 4 * (g >> 1) + (g & 1)) * 576 + 192 + 8 * l;
  const __nv_bfloat16* brow = wqkv + (16 * s + 4 * (g >> 1) + (g & 1)) * 576 + 8 * l;
#pragma unroll
  for (int i = 0; i < 12; i++) {
    A[i] = ldg128_nc(arow + (i & 1) * 2 * 576 + 32 * (i >> 1));
    B[i] = ldg128_nc(brow + (i & 1) * 2 * 576 + 32 * (i >> 1));
  }
  sched_fence();
  uint8_t* dst = wimg + wimg_off(m0 + g, 16 * s + 4 * l);
  float acc[4][4];
#pragma unroll
  for (int j = 0; j < 16; j++) acc[j >> 2][j & 3] = 0.f;
#pragma unroll
  for (int i = 0; i < 6; i++) {
    const uint4 &a0 = A[2 * i], &a1 = A[2 * i + 1];
#pragma unroll
    for (int nb = 0; nb < 2; nb++) {
      mma16816(acc[2 * nb], a0.x, a1.x, a0.y, a1.y, B[2 * i + nb].x, B[2 * i + nb].y);
      mma16816(acc[2 * nb + 1], a0.z, a1.z, a0.w, a1.w, B[2 * i + nb].z, B[2 * i + nb].w);
    }
  }
#pragma unroll
  for (int j = 0; j < 2; j++) {
    const uint2 v = make_uint2(pack_bf16((acc[0][2 * j] + acc[1][2 * j]) * kAlpha, (acc[0][2 * j + 1] + acc[1][2 * j + 1]) * kAlpha),
                               pack_bf16((acc[2][2 * j] + acc[3][2 * j]) * kAlpha, (acc[2][2 * j + 1] + acc[3][2 * j + 1]) * kAlpha));
    asm volatile("st.relaxed.gpu.global.v2.u32 [%0], {%1,%2};" ::"l"(dst + j * 1024), "r"(v.x), "r"(v.y) : "memory");
  }
}
__device__ __forceinline__ void fold_w2(const int u, const __nv_bfloat16* __restrict__ wqkv, const __nv_bfloat16* __restrict__ wo,
                                        uint8_t* wimg) {
  const int g = (threadIdx.x >> 2) & 7, l = threadIdx.x & 3;
  const int m0 = (u / 12) * 32, n0 = (u % 12) * 16;
  uint4 S[12];
  uint32_t L[96];
  const __nv_bfloat16* brow = wqkv + (n0 + 4 * (g >> 1) + (g & 1)) * 576 + 384 + 8 * l;
#pragma unroll
  for (int i = 0; i < 12; i++) S[i] = ldg128_nc(brow + (i & 1) * 2 * 576 + 32 * (i >> 1));
  const __nv_bfloat16* acol = wo + (8 * l) * 192 + m0 + 4 * g;
#pragma unroll
  for (int c = 0; c < 48; c++)
    asm volatile("ld.global.nc.v2.u32 {%0,%1}, [%2];" : "=r"(L[2 * c]), "=r"(L[2 * c + 1]) : "l"(acol + (32 * (c >> 3) + (c & 7)) * 192));
  const uint32_t off = w2_offset();
  sched_fence();
  uint8_t* img = wimg + off;
  float acc[4][4];
#pragma unroll
  for (int j = 0; j < 16; j++) acc[j >> 2][j & 3] = 0.f;
#pragma unroll
  for (int i = 0; i < 6; i++) {
#pragma unroll
    for (int h = 0; h < 2; h++) {
      const uint4 &s0 = S[2 * i], &s1 = S[2 * i + 1];
#pragma unroll
      for (int mt = 0; mt < 2; mt++) {
        const uint32_t* a = L + 16 * i + 8 * h + mt;
        const uint32_t a0 = __byte_perm(a[0], a[2], 0x5410), a1 = __byte_perm(a[0], a[2], 0x7632);
        const uint32_t a2 = __byte_perm(a[4], a[6], 0x5410), a3 = __byte_perm(a[4], a[6], 0x7632);
        mma16816(acc[2 * mt], a0, a1, a2, a3, h ? s0.z : s0.x, h ? s0.w : s0.y);
        mma16816(acc[2 * mt + 1], a0, a1, a2, a3, h ? s1.z : s1.x, h ? s1.w : s1.y);
      }
    }
  }
#pragma unroll
  for (int j = 0; j < 4; j++) {
    const float(&c0)[4] = acc[j & 2];
    const float(&c1)[4] = acc[(j & 2) + 1];
    asm volatile("st.relaxed.gpu.global.v2.u32 [%0], {%1,%2};" ::"l"(img + w2img_off(g2_inv(m0 + 4 * g + j), n0 + 4 * l)),
                 "r"(pack_bf16(c0[2 * (j & 1)], c0[2 * (j & 1) + 1])), "r"(pack_bf16(c1[2 * (j & 1)], c1[2 * (j & 1) + 1])) : "memory");
  }
}

__global__ void __launch_bounds__(256) fold_kernel(const __nv_bfloat16* __restrict__ wqkv,
                                                   const __nv_bfloat16* __restrict__ wo, uint8_t* wimg) {
  const int u = blockIdx.x * 8 + (threadIdx.x >> 5);
  if (u < 144) fold_w1(u, wqkv, wimg);
  else fold_w2(u - 144, wqkv, wo, wimg);
}

struct TileCoord { int pr, pc, I, J, up, kind; };
struct TileTable { uint16_t e[kCtas * 6], g[6][8][2]; };
inline void make_tiles(TileTable& tt) {
  for (int tile = 0; tile < kCtas * 6; tile++) {
    const int b = tile / 6, k = tile - 6 * b;
    const int p = b < 128 ? (tile - 672) >> 1 : b - 80;
    const int strip = b < 112 ? b >> 1 : b >= 128 && k >= 2 ? (b & 1) * 27 + (b & 2) * 14 : p + (p < 26 ? 1 : 3);
    const int pr = strip >= 28, J = (strip - pr * 28) >> 1, pc = strip & 1, up = b < 112 ? b & 1 : pr;
    const int first = b < 112 ? 8 - 2 * pr - up : 13 * pr, step = b < 112 ? k : k & 1;
    const int I = up ? first - step : first + step;
    const int kind = b < 112 ? (J == 13 * pc ? 1 + pc : 0) : I == 13 * pr ? 4 + pr : 3;
    tt.e[tile] = (uint16_t)(I | J << 4 | pr << 8 | pc << 9 | up << 10 | kind << 11);
  }
  for (int kind = 0; kind < 6; kind++)
    for (int j = 0; j < 8; j++) {
      const int w = j >> 1, h = j & 1, e = kind % 3;
      auto off = [e](int t) { return e == 0 ? 2 * t : e == 1 ? t + (t == 7) : t + (t > 0); };
      tt.g[kind][j][0] = (uint16_t)(kind < 3 ? 3 * off(w + 4 * h) : 3 * (kW * off(2 * w) + 8 * h));
      tt.g[kind][j][1] = (uint16_t)(128 * (kind < 3 ? kind > 0 : 1 + off(2 * w + 1) - off(2 * w)));
    }
}
__device__ __forceinline__ int num_tiles() { return blockIdx.x < 128 ? 6 : 4; }
__device__ __forceinline__ TileCoord decode_tile(const TileTable& tt, int tile) {
  const uint32_t e = tt.e[tile];
  return TileCoord{(int)(e >> 8) & 1, (int)(e >> 9) & 1, (int)e & 15, (int)(e >> 4) & 15, (int)(e >> 10) & 1, (int)(e >> 11)};
}
__device__ __forceinline__ int halo_r0(const TileCoord& t) { return 8 * t.I + 6 * t.pr - 6; }
__device__ __forceinline__ int halo_c0(const TileCoord& t) { return min(max(8 * t.J + 6 * t.pc - 6, -3), 102); }

__device__ __forceinline__ uint32_t bar_full(uint32_t bars, int wg, int c) { return bars + (wg * 3 + c) * 8; }
__device__ __forceinline__ uint32_t bar_w1c(uint32_t bars, int c) { return bars + (6 + c) * 8; }
__device__ __forceinline__ uint32_t bar_w2(uint32_t bars) { return bars + 9 * 8; }
__device__ __forceinline__ uint32_t bar_x(uint32_t bars, int j) { return bars + (10 + j) * 8; }
__device__ __forceinline__ uint32_t bar_w1q(uint32_t bars) { return bars + 12 * 8; }
__device__ __forceinline__ uint32_t bar_xf(uint32_t bars) { return bars + 13 * 8; }
__device__ __forceinline__ uint32_t bar_w2m(uint32_t bars) { return bars + 14 * 8; }
__device__ __forceinline__ uint32_t bar_redo(uint32_t bars) { return bars + 15 * 8; }
__device__ __forceinline__ uint32_t bar_wok(uint32_t bars) { return bars + 16 * 8; }
__device__ __forceinline__ uint32_t bar_go(uint32_t bars) { return bars + 17 * 8; }
__device__ __forceinline__ uint32_t bar_raw(uint32_t bars, int j = 0) { return bars + (21 + j) * 8; }
__device__ __forceinline__ uint32_t bar_w2a(uint32_t bars) { return bars + 20 * 8; }
constexpr int kNumBars = 22;

__device__ __forceinline__ uint64_t wdesc(uint64_t d0, int s) { return d0 + (((s >> 2) * kWChunk + (s & 3) * 32) >> 4); }

__device__ __forceinline__ int qrow(int w, int g) { return blockIdx.x < 112 ? g : 2 * w + (g & 1); }
__device__ __forceinline__ int qcol(int w, int g) { return blockIdx.x < 112 ? w : g >> 1; }
__device__ __forceinline__ uint32_t out_slot(int k, int nt) { return k + 1 < nt ? kW2Off + (~k & 1) * 2 * kWChunk : kW1Off + kWChunk; }
__device__ __forceinline__ bool edge_strip() {
  const int s = blockIdx.x >> 1;
  return s == 0 || s == 27 || s == 28 || s == 55;
}
template <int I0, int I1>
__device__ __forceinline__ void store_rows(bool on, __nv_bfloat16* pA, __nv_bfloat16* pB, const uint32_t (&a)[24], const uint32_t (&b)[24]) {
#pragma unroll
  for (int i = 2 * I0; i < 2 * I1; i++) {
    const uint32_t* v = (i & 1 ? b : a) + 4 * (i >> 1);
    asm volatile("{\n.reg .pred p;\nsetp.ne.u32 p, %5, 0;\n@p st.global.v4.u32 [%0], {%1,%2,%3,%4};\n}\n" ::"l"((i & 1 ? pB : pA) + 32 * (i >> 1)),
                 "r"(v[0]), "r"(v[1]), "r"(v[2]), "r"(v[3]), "r"((uint32_t)on) : "memory");
  }
}
template <int I0, int I1>
__device__ __forceinline__ void stage_out(uint32_t sts, int wg, const uint32_t (&a)[24], const uint32_t (&b)[24]) {
  const uint32_t e = sts, o = sts ^ 64;
  const uint32_t ad[4] = {wg ? o + 1024 : e, wg ? e + 2048 : o, wg ? e : o + 1024, wg ? o : e + 2048};
#pragma unroll
  for (int i = I0; i < I1; i++) {
    const uint32_t* v = (i < 6 ? a : b) + 4 * (i % 6);
    asm volatile("st.shared.v4.u32 [%0], {%1,%2,%3,%4};" ::"r"(ad[i % 6 / 3 * 2 + (i % 3 == 1)] + (i % 3 == 2) * 1024 + (i / 6) * 12288),
                 "r"(v[0]), "r"(v[1]), "r"(v[2]), "r"(v[3]) : "memory");
  }
}
__device__ __forceinline__ uint32_t now_ns() {
  uint32_t t;
  asm volatile("mov.u32 %0, %globaltimer_lo;" : "=r"(t)::"memory");
  return t;
}
__device__ __forceinline__ void wait_clock(uint32_t t_start, uint32_t t) {
  while (now_ns() - t_start < t) { }
}
#define NAT_PRED(f, m) ".reg .pred p;\n.reg .b32 t;\nand.b32 t, " f ", " m ";\nsetp.ne.u32 p, t, 0;\n"
constexpr uint32_t kHiV = 1, kHiU = 8, kColB = 0x20, kInV = 0x100, kInU = 0x1000, kColA = 0x10000;
template <uint32_t M>
__device__ __forceinline__ float pick(const float* a, const float* b, uint32_t f) {
  float d;
  asm("{\n" NAT_PRED("%5", "%6") "add.f32 %0, %1, %2;\n@p add.f32 %0, %3, %4;\n}\n"
      : "=&f"(d) : "f"(a[0]), "f"(a[2]), "f"(b[0]), "f"(b[2]), "r"(f), "n"(M));
  return d;
}
template <uint32_t M>
__device__ __forceinline__ float sel(float a, float b, uint32_t f) {
  float d;
  asm("{\n" NAT_PRED("%3", "%4") "selp.f32 %0, %1, %2, p;\n}\n" : "=f"(d) : "f"(a), "f"(b), "r"(f), "n"(M));
  return d;
}
template <uint32_t M>
__device__ __forceinline__ void max_if(float& m, float v, uint32_t f) {
  asm("{\n" NAT_PRED("%2", "%3") "@p max.f32 %0, %0, %1;\n}\n" : "+f"(m) : "f"(v), "r"(f), "n"(M));
}
template <uint32_t M>
__device__ __forceinline__ void add_if(float& m, float v, uint32_t f) {
  asm("{\n" NAT_PRED("%2", "%3") "@p add.f32 %0, %0, %1;\n}\n" : "+f"(m) : "f"(v), "r"(f), "n"(M));
}
__device__ __forceinline__ void pick_v(const float* a, float* v, uint32_t f) {
  v[0] = pick<kHiV>(a, a + 16, f), v[1] = pick<kHiV>(a + 1, a + 17, f);
  v[2] = pick<kHiV * 2>(a + 4, a + 20, f), v[3] = pick<kHiV * 2>(a + 5, a + 21, f);
  v[4] = pick<kHiV * 4>(a + 8, a + 24, f), v[5] = pick<kHiV * 4>(a + 9, a + 25, f);
  v[6] = a[12] + a[14], v[7] = a[13] + a[15];
}
__device__ __forceinline__ void pick_u(const float* a, float* v, uint32_t f) {
#pragma unroll
  for (int c = 0; c < 3; c++) v[2 * c] = pick<kHiU>(a + 4 * c, a + 4 * c + 12, f), v[2 * c + 1] = pick<kHiU * 2>(a + 4 * c + 1, a + 4 * c + 13, f);
}
__device__ __forceinline__ uint32_t sign_bytes(uint32_t v, uint32_t sel) {
  uint32_t d;
  asm("prmt.b32 %0, %1, %1, %2;" : "=r"(d) : "r"(v), "r"(sel));
  return d;
}
__device__ __forceinline__ float own_max(const float (&v)[14], uint32_t f) {
  float m = sel<kInV>(fmaxf(v[0], v[1]), -INFINITY, f), m2 = sel<kInV * 2>(fmaxf(v[2], v[3]), -INFINITY, f);
  max_if<kInV * 4>(m, fmaxf(v[4], v[5]), f);
  max_if<kInV * 8>(m2, fmaxf(v[6], v[7]), f);
  max_if<kInU>(m, fmaxf(fmaxf(v[8], v[10]), v[12]), f);
  max_if<kInU * 2>(m2, fmaxf(fmaxf(v[9], v[11]), v[13]), f);
  return fmaxf(m, m2);
}
__device__ __forceinline__ float quad_max(float m) {
  const float a = __shfl_xor_sync(0xffffffffu, m, 1), b = __shfl_xor_sync(0xffffffffu, m, 2), c = __shfl_xor_sync(0xffffffffu, m, 3);
  return fmaxf(fmaxf(m, a), fmaxf(b, c));
}
__device__ __forceinline__ float row_rcp(const float (&v)[14], uint32_t f) {
  float s = sel<kInV>(v[0] + v[1], 0.f, f), s2 = sel<kInV * 2>(v[2] + v[3], 0.f, f);
  add_if<kInV * 4>(s, v[4] + v[5], f);
  add_if<kInV * 8>(s2, v[6] + v[7], f);
  add_if<kInU>(s, v[8] + v[10] + v[12], f);
  add_if<kInU * 2>(s2, v[9] + v[11] + v[13], f);
  s += s2;
  const float a = __shfl_xor_sync(0xffffffffu, s, 1), b = __shfl_xor_sync(0xffffffffu, s, 2), c = __shfl_xor_sync(0xffffffffu, s, 3);
  return rcp_approx((s + a) + (b + c));
}
__device__ __forceinline__ void route(const float (&v)[14], float s, const uint32_t (&rt)[9], uint32_t (&p)[14]) {
#pragma unroll
  for (int i = 0; i < 7; i++) {
    const uint32_t u = pack_bf16(v[2 * i] * s, v[2 * i + 1] * s);
    if (i < 4) p[i] = u & rt[i];
    if (i < 3) p[i + 4] = u & rt[i + 4];
    if (i >= 4) {
      p[i + 3] = u & rt[7];
      p[i + 6] = u & rt[8];
    }
  }
}

template <int C, int T0 = 0, int T1 = 7>
__device__ __forceinline__ void pv_chunk(float (&z)[32], const uint32_t (&pa)[14], const uint32_t (&pb)[14],
                                         const uint32_t (&meta)[4], uint64_t dV) {
#pragma unroll
  for (int t = T0; t < T1; t++) {
    if (t & 1)
      wg_s64t1<0, 32>(z, pa[2 * t], pb[2 * t], pa[2 * t + 1], pb[2 * t + 1], dV + ((2 * C * kChunkBytes + t * 2048) >> 4), 1,
                      meta[t >> 1]);
    else if (t > 0)
      wg_s64t<0, 32>(z, pa[2 * t], pb[2 * t], pa[2 * t + 1], pb[2 * t + 1], dV + ((2 * C * kChunkBytes + t * 2048) >> 4), 1,
                     meta[t >> 1]);
    else
      wg_s64tz<0, 32>(z, pa[0], pb[0], pa[1], pb[1], dV + ((2 * C * kChunkBytes) >> 4), 0, meta[0]);
  }
}
template <int C>
__device__ __forceinline__ void pack_z(const float (&z)[32], uint32_t (&za)[24], uint32_t (&zb)[24]) {
#pragma unroll
  for (int j = 0; j < 8; j++) {
    za[8 * C + j] = pack_bf16(z[4 * j], z[4 * j + 1]);
    zb[8 * C + j] = pack_bf16(z[4 * j + 2], z[4 * j + 3]);
  }
}

template <int H>
__device__ __forceinline__ void pack_out(const float (&ac)[48], uint32_t (&oa)[24], uint32_t (&ob)[24]) {
#pragma unroll
  for (int j = 0; j < 12; j++) {
    oa[12 * H + j] = pack_bf16(ac[4 * j], ac[4 * j + 1]);
    ob[12 * H + j] = pack_bf16(ac[4 * j + 2], ac[4 * j + 3]);
  }
}
struct Maps { CUtensorMap v6, v2, v14, u8, px[8], wv, wo; };
__device__ __forceinline__ void tma_prefetch_5d(const CUtensorMap* map, int c0, int c1, int c2, int c3, int c4) {
  asm volatile("cp.async.bulk.prefetch.tensor.5d.L2.global.tile [%0, {%1, %2, %3, %4, %5}];" ::"l"((uint64_t)map), "r"(c0), "r"(c1),
               "r"(c2), "r"(c3), "r"(c4) : "memory");
}
__device__ __forceinline__ int first_line(const TileCoord tc) { return 3 * (qpix(tc.pr, 8 * tc.I) * kW + qpix(tc.pc, 8 * tc.J)); }
template <int MODE, int UNROLL, int N = 8>
__device__ __forceinline__ void move_px(const Maps& tm, const TileTable& tt, uint32_t buf, uint32_t bar, int line, int kind, int i0 = 0) {
#pragma unroll UNROLL
  for (int n = 0; n < N; n++) {
    const int i = i0 + n;
    const int j = MODE == 2 ? 2 * (i & 3) + (i >> 2) : i;
    if (MODE == 2 || (n & 1) == 0 || kind != 0) {
      const CUtensorMap* map = (const CUtensorMap*)((const char*)(tm.px + (MODE & 2) * 2) + tt.g[kind][j][1]);
      const int ln = line + tt.g[kind][j][0];
      if (MODE == 0) tma_load_5d(buf + i * 3072, map, bar, 0, 0, 0, 0, ln);
      if (MODE == 1) tma_prefetch_5d(map, 0, 0, 0, 0, ln);
      if (MODE == 2)
        asm volatile("cp.async.bulk.tensor.5d.global.shared::cta.tile.bulk_group [%0, {%2, %2, %2, %2, %3}], [%1];" ::"l"((uint64_t)map),
                     "r"(buf + i * 3072), "r"(0), "r"(ln) : "memory");
      if (MODE == 2 && NAT_SP < 9) {
        asm volatile("cp.async.bulk.commit_group;" ::: "memory");
        asm volatile("cp.async.bulk.wait_group.read %0;" ::"n"(NAT_SP) : "memory");
      }
    }
  }
  if (MODE == 2) asm volatile("cp.async.bulk.commit_group;" ::: "memory");
}
__device__ __noinline__ bool refetch(uint32_t base, const uint8_t* src, bool gap) {
  constexpr uint32_t bars = 1024 + kBarOff, cnt = bars + 192;
#pragma unroll 1
  for (uint32_t o = 0; o < kWBytes && !gap; o += 2048) {
    uint32_t mx = 0;
#pragma unroll
    for (int i = 0; i < 4; i++) {
      uint4 v;
      asm volatile("ld.shared.v4.u32 {%0,%1,%2,%3}, [%4];" : "=r"(v.x), "=r"(v.y), "=r"(v.z), "=r"(v.w)
                   : "r"(base + o + i * 512 + (threadIdx.x & 31) * 16));
      mx = __vimax3_u32(__vimax3_u32(mx, v.x, v.y), v.z, v.w);
    }
    gap = __any_sync(0xffffffffu, mx == kEmpty);
  }
  uint32_t n;
  asm volatile("ld.shared.u32 %0, [%1];" : "=r"(n) : "r"(cnt) : "memory");
  if (!gap || __any_sync(0xffffffffu, n > (1u << 12))) return false;
  asm volatile("bar.sync 15, 128;" ::: "memory");
  if (threadIdx.x == 0) {
    asm volatile("st.shared.u32 [%0], %1;" ::"r"(cnt), "r"(n + 1) : "memory");
    mbar_arrive_expect_tx(bar_redo(bars), kWBytes);
    bulk_load(base, src, kWBytes, bar_redo(bars));
  }
  __syncwarp();
  mbar_wait(bar_redo(bars), n & 1);
  return true;
}
template <int S0, int S1, int Z>
__device__ __forceinline__ void g2_steps(float (&ac)[48], const uint32_t (&za)[24], const uint32_t (&zb)[24], uint64_t d) {
#pragma unroll
  for (int s = S0; s < S1; s++) {
    const uint64_t ds = d + (((s >> 2 & 1) * (kWChunk / 2) + (s & 3) * 32) >> 4);
    if (s == Z) wg_d96z<0, 48>(ac, za[2 * s], zb[2 * s], za[2 * s + 1], zb[2 * s + 1], ds, 0);
    else wg_d96<0, 48>(ac, za[2 * s], zb[2 * s], za[2 * s + 1], zb[2 * s + 1], ds, 1);
  }
}

__device__ __forceinline__ void consumer(const int wg, __nv_bfloat16* out, const uint8_t* wimg, const uint32_t sbase,
                                         const uint32_t zero, const Maps& tm, const TileTable& tt) {
  const int tid = threadIdx.x & 127;
  const int w = __shfl_sync(0xffffffffu, tid >> 5, 0), lane = tid & 31, g = qrow(w, lane >> 2), qc = qcol(w, lane >> 2);
  const uint64_t dK = make_desc(sbase, 16, 1024);
  const uint64_t dV = make_desc(sbase, kChunkBytes, 512, 2);
  const uint64_t dW1 = make_desc(sbase + kW1Off, 16, 1024);
  const uint64_t dX0 = make_desc(sbase + kW2Off + wg * 2 * kWChunk, 16, 1024), dY0 = make_desc(sbase + kW2Off + (1 - wg) * 2 * kWChunk, 16, 1024);
  const uint64_t dX2 = make_desc(sbase + kXOff + wg * (kWChunk / 2), 16, 1024), dY2 = make_desc(sbase + kXOff + (1 - wg) * (kWChunk / 2), 16, 1024);
  const uint32_t bars = sbase + kBarOff;
  int tile0 = blockIdx.x * kTilesPerCta;
  asm volatile("" : "+r"(tile0));
  const int nt = num_tiles();

  uint32_t pix = 0, geo[12] = {};
  const int l = lane & 3;
#pragma unroll 1
  for (int j = 4; j >= 0; j -= 2) {
    const TileCoord tc = decode_tile(tt, tile0 + wg + j);
    const uint32_t pr = qpix(tc.pr, 8 * tc.I + g) * kW;
    if (j == nt - 2) pix = (pr + qpix(tc.pc, 8 * tc.J + qc)) | (pr + qpix(tc.pc, 8 * tc.J + qc + 4)) << 16;
    const int d = 8 * tc.J + 6 * tc.pc - 6 - halo_c0(tc);
    const int ro = woff(tc.pr, tc.I, g), coA = woff(tc.pc, tc.J, qc) + d, coB = woff(tc.pc, tc.J, qc + 4) + d - 3;
#pragma unroll
    for (int i = 11; i >= 4; i--) geo[i] = geo[i - 4];
    const uint32_t lr = 0x1FCu << ro;
    const uint32_t lv = lr >> (2 + (l >> 1)), lu = lr >> (2 * l + 2 * tc.up);
    const uint32_t t = __byte_perm(lv, lu, wg ? 0x4501 : 0x5410);
    geo[0] = ((t & 0x15u) | (lv & 0x40u)) * 0x02082080u;
    geo[1] = ((t >> 8) & 0x15u) * 0x02082080u;
    geo[2] = __byte_perm(t << 7, t << 6, 0x7362);
    const int dr = (ro - 1) & 7;
    const uint32_t hiv = (((1u << ((ro - (l >> 1) + 1) >> 1)) - 1u) ^ (wg ? 7u : 0u)) & 7u, hiu = (t >> 24) & 3u;
    const uint32_t ca = (1u << coA) - 1u;
    geo[3] = hiv * kHiV | hiu * kHiU | ((((1u << coB) - 1u) >> (2 * (l & 1))) & 3u) * kColB |
             (15u & ~((uint32_t)((dr & 1) == (l >> 1)) << (dr >> 1))) * kInV | ((t >> 16 | t >> 24) & 3u) * kInU | ca * kColA |
             (ca >> ((0x49 >> (2 * l)) & 3) & 1u) << 19 | (uint32_t)(l == 3) << 20 | (0x55u & ((1u << (2 * coB)) - 1u)) << 24;
  }
  keep_regs(geo);
  const int so = (lane >> 3) | (lane & 4);
  uint32_t sts = sbase + w * 3072 + so * 128 + (((lane & 3) ^ so) << 4);
  __nv_bfloat16* poA = out + 8 * l + (pix & 0xFFFFu) * kC + 96 * wg;
  __nv_bfloat16* poB = out + 8 * l + (pix >> 16) * kC + 96 * wg;
  asm volatile("" : "+l"(poA), "+l"(poB), "+r"(sts));
  uint32_t oa[24], ob[24];
#pragma unroll
  for (int j = 0; j < 24; j++) oa[j] = ob[j] = 0u;
  keep_regs(oa);
  keep_regs(ob);
  PROF(wg, 0);
  if (threadIdx.x == 0) GT(1);

  for (int k = wg; k < nt; k += 2) {
    const uint32_t ph = (k >> 1) & 1;
    const int it = k >> 1;
    uint32_t qa[24], qb[24], hok[3];
    uint32_t fl = geo[3];
    {
      float acc[96];
      const uint64_t dX = make_desc(sbase + kXOff + (k == 0 ? kWChunk : 0), 16, 3072);
      if (k > 0) nb_sync(1 + (1 - wg));
      mbar_wait(bar_x(bars, k > 0), (k + (k > 0)) & 1);
      if (k < 2) PROF(wg, 1);
      PROFS(2, wg, 2 + it * 12);
      if (w == 0 && k < 2) GT(20 + wg);
#pragma unroll
      for (int s = 0; s < 12; s++) {
        if ((s & 3) == 0 && k == 0) {
          mbar_wait(bar_w1c(bars, s >> 2), 0);
          PROFS(17, wg, 50 + (s >> 2));
        }
        if ((s & 3) == 0) wg_fence();
        if (s == 0) wg_m192z<0, 96>(acc, dX, dW1, 0);
        else wg_m192<0, 96>(acc, dX + (((s >> 2) * 1024 + (s & 3) * 32) >> 4), wdesc(dW1, s), 1);
      }
      wg_commit();
      PROFS(13, wg, 13 + it * 12);
      wg_wait<0>();
      if (k > 0) nb_arrive_p(6);
      fence_regs(acc);
      PROFS(3, wg, 3 + it * 12);
#pragma unroll
      for (int j = 0; j < 24; j++) {
        qa[j] = pack_bf16(acc[4 * j], acc[4 * j + 1]);
        qb[j] = pack_bf16(acc[4 * j + 2], acc[4 * j + 3]);
      }
      keep_regs(qa);
      keep_regs(qb);
      sched_fence();
      if (k >= 2) {
        const uint32_t dst = sts + out_slot(k, nt);
        nb_sync(11);
        stage_out<0, 6>(dst, wg, oa, ob);
        nb_sync(12);
        stage_out<6, 12>(dst, wg, oa, ob);
      }
#pragma unroll
      for (int c = 0; c < 3; c++) hok[c] = mbar_test(bar_full(bars, wg, c), ph);
      if (k >= 2) {
        fence_proxy_async();
        nb_arrive_p(10);
      }
    }

    float aE[52], aO[24], bO[52], bE[28];
    const uint32_t mq = 0xEEEE4444u | zero;
    PROFS(4, wg, 4 + it * 12);

    mbar_wait_if(hok[0], bar_full(bars, wg, 0), ph);
    PROFS(14, wg, 40 + it * 3);
    if (w == 0 && k < 2) GT(22 + wg);
    if (k > 0) nb_sync(3 + (1 - wg));
    wg_fence();
#pragma unroll
    for (int ks = 0; ks < 6; ks++) {
      if (ks == NAT_P1) {
        mbar_wait_if(hok[1], bar_full(bars, wg, 1), ph);
        PROFS(14, wg, 41 + it * 3);
        wg_fence();
      }
      if (ks == NAT_P2) {
        mbar_wait_if(hok[2], bar_full(bars, wg, 2), ph);
        PROFS(14, wg, 42 + it * 3);
        wg_fence();
      }
      const uint64_t d = dK + ((ks * kChunkBytes) >> 4);
      if (ks == 0) wg_s104z<0, 52>(aE, qa[0], qa[1], qa[2], qa[3], d, 0, mq);
      else wg_s104<0, 52>(aE, qa[4 * ks], qa[4 * ks + 1], qa[4 * ks + 2], qa[4 * ks + 3], d, 1, mq);
    }
    wg_commit();
    wg_s48z<0, 24>(aO, qa[0], qa[1], qa[2], qa[3], dK + ((7 * 1024 + 64) >> 4), 0, mq);
#pragma unroll
    for (int ks = 1; ks < 6; ks++)
      wg_s48<0, 24>(aO, qa[4 * ks], qa[4 * ks + 1], qa[4 * ks + 2], qa[4 * ks + 3], dK + ((ks * kChunkBytes + 7 * 1024 + 64) >> 4), 1, mq);
    wg_commit();
    wg_s56z<0, 28>(bE, qb[0], qb[1], qb[2], qb[3], dK, 0, mq);
#pragma unroll
    for (int ks = 1; ks < 6; ks++) wg_s56<0, 28>(bE, qb[4 * ks], qb[4 * ks + 1], qb[4 * ks + 2], qb[4 * ks + 3], dK + ((ks * kChunkBytes) >> 4), 1, mq);
    wg_commit();
    wg_wait<2>();
    fence_regs(aE);
    PROFS(5, wg, 5 + it * 12);

    uint32_t pa[14], pb[14], meta[4];
    {
      float vA[14], vB[14];
      pick_v(aE, vA, fl);
      pick_u(aE + 28, vA + 8, fl);
      fence_regs(vA);
      if (k == 0) {
        if (__builtin_expect(__any_sync(0xffffffffu, vA[6] != vA[6]), 0)) {
          wg_wait<0>();
          fence_regs(aO);
          fence_regs(bE);
          if (refetch(sbase + kW1Off, wimg, false)) {
#pragma unroll
            for (int j = 0; j < 24; j++) oa[j] = ob[j] = 0u;
            k -= 2;
            continue;
          }
        }
        if (elect_one()) mbar_arrive(bar_xf(bars));
      }
      wg_fence();
      wg_s104z<0, 52>(bO, qb[0], qb[1], qb[2], qb[3], dK + 4, 0, mq);
#pragma unroll
      for (int ks = 1; ks < 6; ks++)
        wg_s104<0, 52>(bO, qb[4 * ks], qb[4 * ks + 1], qb[4 * ks + 2], qb[4 * ks + 3], dK + ((ks * kChunkBytes + 64) >> 4), 1, mq);
      wg_commit();
      if (k + 1 < nt) nb_arrive(1 + wg);
      uint32_t rt[9];
#pragma unroll
      for (int i = 0; i < 7; i++) rt[i] = sign_bytes(geo[i >> 2], 0x8888u + 0x1111u * (i & 3));
      rt[7] = sign_bytes(geo[2], 0x9988u);
      rt[8] = sign_bytes(geo[2], 0xBBAAu);
      keep_regs(rt);
      pa[13] = pb[13] = 0u;
      wg_wait<2>();
      keep_regs(qa);
      fence_regs(aO);
      float oA[6], eB[8];
      pick_u(aO, oA, fl);
      wg_wait<1>();
      fence_regs(bE);
      pick_v(bE, eB, fl);
      vA[8] = sel<kColA>(oA[0], vA[8], fl), vA[9] = sel<kColA>(oA[1], vA[9], fl);
      vA[10] = sel<kColA * 2>(oA[2], vA[10], fl), vA[11] = sel<kColA * 2>(oA[3], vA[11], fl);
      vA[12] = sel<kColA * 4>(oA[4], vA[12], fl), vA[13] = sel<kColA * 4>(oA[5], vA[13], fl);
      {
        const float m1 = __uint_as_float(0x88DD88DDu), m0 = __uint_as_float(0x88DDDD88u);
        meta[0] = 0xDD88DD88u ^ __byte_perm(fl, 0u, 0x3344);
        meta[1] = __float_as_uint(sel<kColA * 16>(sel<kColA>(m1, m0, fl), __uint_as_float(meta[0]), fl));
        meta[2] = __float_as_uint(sel<kColA * 8>(m1, m0, fl));
        meta[3] = __float_as_uint(sel<kColA * 4>(m1, m0, fl));
        keep_regs(meta);
      }
      float mA = own_max(vA, fl);
      fl |= __float_as_uint(eB[7]) & zero;
      fence_regs(eB);
      fence_regs(vA);
      asm volatile("" : "+f"(mA), "+r"(fl));
      sched_fence();
      wg_wait<0>();
      sched_fence();
      keep_regs(qb);
      fence_regs(bO);
      PROFS(6, wg, 6 + it * 12);
      if (w == 0) GT(24 + k);
      mA = quad_max(mA);
#pragma unroll
      for (int i = 0; i < 14; i++) vA[i] = ex2(vA[i] - mA);
      pick_v(bO, vB, fl);
      pick_u(bO + 28, vB + 8, fl);
#pragma unroll
      for (int i = 0; i < 8; i += 2) vB[i] = sel<kColB>(vB[i], eB[i], fl), vB[i + 1] = sel<kColB * 2>(vB[i + 1], eB[i + 1], fl);
      float mB = quad_max(own_max(vB, fl));
      if (NAT_SB) {
        fence_regs(vA);
        fence_regs(vB);
        asm volatile("" : "+f"(mB));
        sched_fence();
      }
      PROFS(7, wg, 7 + it * 12);
#pragma unroll
      for (int i = 0; i < 14; i++) vB[i] = ex2(vB[i] - mB);
      route(vA, row_rcp(vA, fl), rt, pa);
      route(vB, row_rcp(vB, fl), rt, pb);
    }
    PROFS(8, wg, 8 + it * 12);
    if (k == NAT_PK) PROFS(18, wg, 53);
    sched_fence();

    float ac0[48], ac1[48];
    {
      float z0[32], z1[32], z2[32];
      uint32_t za[24], zb[24];
      wg_fence();
      pv_chunk<0>(z0, pa, pb, meta, dV);
      wg_commit();
      pv_chunk<1>(z1, pa, pb, meta, dV);
      wg_commit();
      wg_wait<1>();
      if (k == NAT_PK) PROFS(18, wg, 54);
      if (k + 1 < nt) nb_arrive_p(7);
      pv_chunk<2, 0, 3>(z2, pa, pb, meta, dV);
      wg_commit();
      sched_fence();
      fence_regs(z0);
      pack_z<0>(z0, za, zb);
      sched_fence();
      wg_fence();
      pv_chunk<2, 3, 7>(z2, pa, pb, meta, dV);
      wg_commit();
      wg_wait<2>();
      if (k == NAT_PK) PROFS(19, wg, 55);
      if (k + 1 < nt) nb_arrive_p(8);
      if (k < 2) mbar_wait(k == 1 ? bar_wok(bars) : bar_w2a(bars), 0);
      wg_fence();
      g2_steps<0, 3, 0>(ac0, za, zb, dX0);
      wg_commit();
      sched_fence();
      fence_regs(z1);
      pack_z<1>(z1, za, zb);
      sched_fence();
      wg_fence();
      g2_steps<3, 4, 0>(ac0, za, zb, dX0);
      wg_commit();
      g2_steps<4, 8, 0>(ac0, za, zb, dX0);
      wg_commit();
      wg_wait<3>();
      if (k + 1 < nt) nb_arrive_p(9);
      else nb_arrive(11);
      if (k == NAT_PK) PROFS(20, wg, 56);
      keep_regs(pa);
      keep_regs(pb);
      keep_regs(meta);
      sched_fence();
      const uint32_t mok = mbar_test(bar_w2m(bars), k + 1 < nt ? k & 1 : ~k & 1);
      fence_regs(z2);
      pack_z<2>(z2, za, zb);
      keep_regs(za);
      keep_regs(zb);
      sched_fence();
      PROFS(9, wg, 9 + it * 12);
      wg_wait<1>();
      if (k > 0 && k + 1 < nt) nb_arrive(11);
      mbar_wait_if(mok, bar_w2m(bars), k & 1);
      wg_fence();
      g2_steps<8, 12, 0>(ac0, za, zb, dX2);
      wg_commit();
      g2_steps<8, 12, 8>(ac1, za, zb, dY2);
      wg_commit();
      wg_wait<2>();
      if (k > 0 && k + 1 < nt) nb_arrive(12);
      if (k != 1 && k + 1 < nt) mbar_wait(bar_w2(bars), k > 1 ? (k - 1) & 1 : 0);
      wg_fence();
      g2_steps<0, 4, 8>(ac1, za, zb, dY0);
      wg_commit();
      wg_wait<2>();
      if (k + 2 < nt) nb_arrive_p(13);
      const bool direct = k + 2 >= nt;
      sched_fence();
      fence_regs(ac0);
      pack_out<0>(ac0, oa, ob);
      store_rows<0, NAT_D0>(direct, poA, poB, oa, ob);
      sched_fence();
      wg_fence();
      g2_steps<4, 8, 8>(ac1, za, zb, dY0);
      wg_commit();
      if (k + 1 < nt) nb_arrive(3 + wg);
      PROFS(10, wg, 10 + it * 12);
      wg_wait<2>();
      if (k + 2 < nt && (k > 0 || nt == 6)) nb_arrive_p(5);
      store_rows<NAT_D0, 3>(direct, poA, poB, oa, ob);
      __nv_bfloat16 *qA = poA - 192 * wg, *qB = poB - 192 * wg;
      if (k + 2 == nt) nb_sync(11);
      sched_fence();
      wg_wait<0>();
      fence_regs(ac1);
      pack_out<1>(ac1, oa, ob);
      asm volatile("" : "+l"(qA), "+l"(qB));
      store_rows<3, 6>(direct, qA, qB, oa, ob);
      if (k == 0) {
        uint32_t m[2] = {oa[0], oa[1]};
#pragma unroll
        for (int i = 2; i < 24; i++) asm("max.NaN.bf16x2 %0, %0, %1;" : "+r"(m[i & 1]) : "r"(oa[i]));
        asm("max.NaN.bf16x2 %0, %0, %1;" : "+r"(m[0]) : "r"(m[1]));
        uint32_t nan;
        asm volatile("{\n.reg .pred p;\nsetp.ne.u32 p, %1, 0;\nbar.red.or.pred p, 15, 128, p;\nselp.u32 %0, 1, 0, p;\n}\n"
                     : "=r"(nan) : "r"(((m[0] & 0x7FFF7FFFu) + 0x007F007Fu) & 0x80008000u) : "memory");
        if (__builtin_expect(__any_sync(0xffffffffu, nan), 0)) {
          if (nt == 6) mbar_wait(bar_x(bars, 1), 1);
          for (bool first = true; __any_sync(0xffffffffu, refetch(sbase + kW2Off, wimg + w2_offset(), first)); first = false) { }
          wg_fence();
          g2_steps<0, 8, 0>(ac0, za, zb, dX0);
          g2_steps<8, 12, 0>(ac0, za, zb, dX2);
          g2_steps<0, 8, 0>(ac1, za, zb, dY0);
          g2_steps<8, 12, 0>(ac1, za, zb, dY2);
          wg_commit();
          wg_wait<0>();
          fence_regs(ac0);
          fence_regs(ac1);
          pack_out<0>(ac0, oa, ob);
          pack_out<1>(ac1, oa, ob);
          if (nt == 6) {
            asm volatile("bar.sync 15, 128;" ::: "memory");
            if (w == 0 && elect_one()) {
              const TileCoord tc = decode_tile(tt, tile0 + 2);
              mbar_arrive_expect_tx(bar_raw(bars), kWChunk);
              move_px<0, 1>(tm, tt, sbase + kXOff, bar_raw(bars), first_line(tc), tc.kind);
            }
            __syncwarp();
            mbar_wait(bar_raw(bars), 0);
          }
        }
        if (nt < 6) nb_arrive_p(5);
        if (elect_one()) mbar_arrive(bar_wok(bars));
      }
      keep_regs(za);
      keep_regs(zb);
#pragma unroll
      for (int i = 0; i < 8; i++) geo[i] = geo[i + 4];
      keep_regs(oa);
      keep_regs(ob);
      PROFS(12, wg, 12 + it * 12);
      sched_fence();
    }
  }
  PROF(wg, 38);
  GT_DUMP();
  PROF_DUMP(wg);
}

struct HaloCols { int vj, vc, uj, uc; };
__device__ __forceinline__ HaloCols halo_cols(const TileCoord& tc) {
  const int c0 = halo_c0(tc);
  return HaloCols{c0 > 98, c0 > 98 ? 98 : c0 + 3, c0 < 0 ? -1 : 0, c0 < 0 ? 4 : c0};
}
__device__ __forceinline__ void first_halo(const Maps& tm, uint32_t sbase, const TileCoord tc, int i) {
  const HaloCols hc = halo_cols(tc);
  const uint32_t dst = sbase + i * kChunkBytes, bar = bar_full(sbase + kBarOff, 0, i >> 1);
  const int h0 = halo_r0(tc), ch = 24 * tc.pc + 4 * i;
  tma_load_5d(dst, &tm.v14, bar, ch, hc.vj, hc.vc, tc.pr, h0);
  tma_load_5d(dst + 7 * 1024, &tm.u8, bar, ch, hc.uj, h0 + (tc.up ? 0 : -2), tc.pr, hc.uc);
  tma_load_5d(dst + 10 * 1024, &tm.u8, bar, ch, hc.uj, h0 + (tc.up ? 8 : 6), tc.pr, hc.uc);
}
__device__ __forceinline__ void load_halo(const Maps& tm, uint32_t sbase, uint32_t bars, const TileCoord tc, int k, int c) {
  const HaloCols hc = halo_cols(tc);
  const int h6 = halo_r0(tc) + (tc.up ? 0 : 8), h2 = halo_r0(tc) + 6, h8 = halo_r0(tc) + (tc.up ? 0 : 6), ch = 24 * tc.pc + 8 * c;
  uint32_t dv = sbase + 2 * c * kChunkBytes, du = dv + 7 * 1024;
  if (((k ^ tc.up) & 1) == 0) dv += 4 * 1024, du += 3 * 1024;
  const uint32_t bar = bar_full(bars, k & 1, c);
  mbar_arrive_expect_tx(bar, 14 * 1024);
  nb_sync_p(7 + c);
#pragma unroll
  for (int h = 0; h < 2; h++) {
    tma_load_5d(dv + h * kChunkBytes, &tm.v6, bar, ch + 4 * h, hc.vj, hc.vc, tc.pr, h6);
    tma_load_5d(du + h * kChunkBytes, &tm.u8, bar, ch + 4 * h, hc.uj, h8, tc.pr, hc.uc);
    tma_load_5d(sbase + (2 * c + h) * kChunkBytes + 3 * 1024, &tm.v2, bar, ch + 4 * h, hc.vj, hc.vc, tc.pr, h2);
  }
  PROFS(15, 2, k * 4 + c);
}
__device__ __forceinline__ void gather_px(const __nv_bfloat16* __restrict__ x, uint32_t buf, uint32_t bar, const TileCoord tc) {
  const int lane = threadIdx.x & 31, g = lane >> 3;
  uint32_t ro[4], co[4];
#pragma unroll
  for (int i = 0; i < 4; i++) {
    ro[i] = qpix(tc.pr, 8 * tc.I + 2 * i + (g & 1)) * (kW * kC * 2) + 16 * (lane & 7);
    co[i] = qpix(tc.pc, 8 * tc.J + 2 * i + (g >> 1)) * (kC * 2);
  }
  uint32_t dst = buf + g * 128 + (((lane & 7) ^ g) << 4);
  keep_regs(ro);
  keep_regs(co);
  sched_fence();
  nb_sync_p(13);
  nb_sync_p(5);
#pragma unroll
  for (int i = 0; i < 16; i++) {
    const char* src = (const char*)x + (ro[i >> 2] + co[i & 3]);
#pragma unroll
    for (int q = 0; q < 3; q++)
      asm volatile("cp.async.cg.shared.global [%0], [%1], 16;" ::"r"((dst ^ ((i & 1) * 576)) + (i >> 1) * 3072 + q * 1024), "l"(src + 128 * q) : "memory");
  }
  asm volatile("cp.async.wait_all;" ::: "memory");
  fence_proxy_async();
  __syncwarp();
  if (elect_one()) mbar_arrive(bar);
  __syncwarp();
}

__global__ void __launch_bounds__(384, 1)
nat_kernel(const __nv_bfloat16* __restrict__ x, __nv_bfloat16* out, const __nv_bfloat16* __restrict__ wqkv,
           const __nv_bfloat16* __restrict__ wo, uint8_t* wimg, const uint32_t zero,
           const __grid_constant__ Maps tm, const __grid_constant__ TileTable tt) {
  extern __shared__ uint8_t smem_raw[];
  constexpr uint32_t sbase = 1024;
  constexpr uint32_t bars = sbase + kBarOff;
  if (smem_u32(smem_raw) != sbase) __trap();
  const int tid = threadIdx.x;
  const uint32_t t_start = now_ns();
  if (tid == 0) GT(0);
  const int wid = __shfl_sync(0xffffffffu, tid >> 5, 0);
  const bool w2cta = blockIdx.x - 128 < 3 && wqkv != nullptr;
  if (wid >= 8) {
    asm volatile("setmaxnreg.dec.sync.aligned.u32 24;");
    const int c = wid & 3, lane = tid & 31;
    const int tile0 = blockIdx.x * kTilesPerCta, nt = num_tiles();
    uint32_t w2o = 0;
    if (c == 3) {
      asm volatile("bar.sync 13, 128;" ::: "memory");
      if (elect_one()) wait_clock(t_start, NAT_TM);
      __syncwarp();
      const CUtensorMap* px = tm.px + (blockIdx.x >= 112 ? 2 : edge_strip());
      asm volatile("prefetch.tensormap [%0];" ::"l"((uint64_t)&tm.v6) : "memory");
      asm volatile("prefetch.tensormap [%0];" ::"l"((uint64_t)&tm.v2) : "memory");
      asm volatile("prefetch.tensormap [%0];" ::"l"((uint64_t)(px + 4)) : "memory");
      asm volatile("prefetch.tensormap [%0];" ::"l"((uint64_t)(px + 5)) : "memory");
      __nanosleep(NAT_TW2 - 2800);
      w2o = w2_offset();
      if (elect_one()) {
        mbar_arrive_expect_tx(bar_w2a(bars), kWChunk);
        mbar_arrive_expect_tx(bar_w2(bars), kWChunk);
        wait_clock(t_start, NAT_TW2);
        bulk_load(sbase + kW2Off, wimg + w2o, kWChunk, bar_w2a(bars));
        mbar_wait(bar_xf(bars), 0);
        bulk_load(sbase + kW2Off + 2 * kWChunk, wimg + (w2o + 2 * kWChunk), kWChunk, bar_w2(bars));
      }
      __syncwarp();
      if (nt < 6) {
#pragma unroll 1
        for (int k = 2; k < 4; k++) {
          gather_px(x, sbase + kXOff, bar_x(bars, 1), decode_tile(tt, tile0 + k));
        }
      }
      if (wqkv == nullptr) return;
      mbar_wait(bar_wok(bars), 0);
      if (lane == 0) asm volatile("red.relaxed.gpu.global.add.u32 [%0], 1;" ::"l"(g_flag) : "memory");
      if (blockIdx.x >= 48) return;
      if (lane == 0) {
        uint32_t v, it = 0;
        do {
          __nanosleep(2000);
          asm volatile("ld.relaxed.gpu.global.u32 %0, [%1];" : "=r"(v) : "l"(g_flag) : "memory");
        } while (v < gridDim.x && ++it < (1u << 16));
      }
      __syncwarp();
#pragma unroll
      for (int i = 0; i < 6; i++)
        stg128(wimg + ((i < 3 ? 0u : 3 * kWBytes - w2o) + blockIdx.x * 1536 + (i % 3) * 512 + lane * 16), kEmpty, kEmpty, kEmpty, kEmpty);
      if (lane == 0 && atomicAdd(g_flag + 32, 1u) == 47) {
        g_flag[0] = g_flag[32] = 0;
        g_flag[64] = w2o == kWBytes;
      }
      return;
    }
    if (!elect_one()) return;
    if (c == 0) {
      for (int i = 0; i < kNumBars; i++)
        if ((i != 0 && i != 10 || nt < 6) && (i != 21 || !w2cta)) mbar_init(bars + i * 8, i == 13 || i == 16 ? 4 : 1);
      asm volatile("st.shared.v2.u32 [%0], {%1,%1};" ::"r"(bars + 192), "r"(0) : "memory");
      asm volatile("fence.mbarrier_init.release.cluster;" ::: "memory");
      if (w2cta) asm volatile("bar.sync 10, 64;" ::: "memory");
      asm volatile("bar.arrive 0, 160;" ::: "memory");
      asm volatile("bar.arrive 14, 160;" ::: "memory");
      asm volatile("bar.arrive 13, 128;" ::: "memory");
      const TileCoord tc0 = decode_tile(tt, tile0);
      const HaloCols hc = halo_cols(tc0);
      const int h0 = halo_r0(tc0);
#pragma unroll
      for (int j = 0; j < 3; j++)
        if (j > 0 || nt < 6) mbar_arrive_expect_tx(bar_full(bars, 0, j), 2 * kChunkBytes);
      wait_clock(t_start, NAT_HP);
#pragma unroll
      for (int q = 8; q < 24; q += 8) {
        tma_prefetch_5d(&tm.v6, 24 * tc0.pc + q, hc.vj, hc.vc, tc0.pr, h0 + (tc0.up ? 0 : 8));
        tma_prefetch_5d(&tm.u8, 24 * tc0.pc + q, hc.uj, h0 + (tc0.up ? 0 : 6), tc0.pr, hc.uc);
        if (blockIdx.x >= 112) tma_prefetch_5d(&tm.v2, 24 * tc0.pc + q, hc.vj, hc.vc, tc0.pr, h0 + 6);
      }
#pragma unroll 1
      for (int i = nt < 6 ? 0 : 2; i < 7; i++) {
        if (i == NAT_H0) mbar_wait(bar_w1q(bars), 0);
        if (i == NAT_X1P) mbar_arrive(bar_go(bars));
        if (i < 6) first_halo(tm, sbase, tc0, i);
      }
      w2o = w2_offset();
    } else {
      asm volatile("bar.sync 13, 128;" ::: "memory");
      if (c == 2) {
        if (wqkv != nullptr && nt == 6) asm volatile("bar.sync 12, 64;" ::: "memory");
        const uint32_t c0 = clock();
        while ((uint32_t)clock() - c0 < NAT_TD) { }
        wait_clock(t_start, NAT_T0);
#pragma unroll
        for (int j = 0; j < 3; j++) {
          mbar_arrive_expect_tx(bar_w1c(bars, j), kWChunk);
          bulk_load(sbase + kW1Off + j * kWChunk, wimg + j * kWChunk, kWChunk, bar_w1c(bars, j));
        }
        mbar_arrive(bar_w1q(bars));
        GT(2);
        if (NAT_OT == 2) w2o = w2_offset();
      } else {
#pragma unroll 1
        for (int j = nt == 6; j < 2; j++) {
          const TileCoord tc = decode_tile(tt, tile0 + j);
          const int line = first_line(tc);
          mbar_arrive_expect_tx(bar_x(bars, j), kWChunk);
          if (j == 1) mbar_wait(bar_go(bars), 0);
          move_px<0, 2>(tm, tt, sbase + kXOff + (1 - j) * kWChunk, bar_x(bars, j), line, tc.kind);
        }
        w2o = w2_offset();
      }
    }
#pragma unroll 1
    for (int k = 1; k < nt; k++) {
      const TileCoord tn = decode_tile(tt, tile0 + k + 1);
      const int line = first_line(tn);
      if (c == 1) {
        nb_sync_p(6);
        bulk_load(sbase + kXOff, wimg + (w2o + kWChunk), kWChunk, bar_w2m(bars));
        mbar_arrive_expect_tx(bar_w2m(bars), kWChunk);
      }
      if (c == 2 - NAT_OT) {
        if (k == 1) wait_clock(t_start, NAT_TX2);
        else if (NAT_OT == 0 || k == nt - 1 + (nt == 6)) __nanosleep(NAT_PFD);
        if (k < 5 && nt == 6) move_px<1, 1>(tm, tt, 0, 0, line, tn.kind);
      }
      if (c == 2 - NAT_OT && (blockIdx.x >= 112 || k == 5)) {
        const TileCoord tc = decode_tile(tt, tile0 + k);
        const HaloCols hc = halo_cols(tc);
        const int h8 = halo_r0(tc) + (tc.up ? 0 : 6);
#pragma unroll 1
        for (int q = 0; q < 24; q += 8) {
          tma_prefetch_5d(&tm.v6, 24 * tc.pc + q, hc.vj, hc.vc, tc.pr, h8);
          tma_prefetch_5d(&tm.v2, 24 * tc.pc + q, hc.vj, hc.vc, tc.pr, h8 + 6);
          tma_prefetch_5d(&tm.u8, 24 * tc.pc + q, hc.uj, h8, tc.pr, hc.uc);
        }
      }
      load_halo(tm, sbase, bars, decode_tile(tt, tile0 + k), k, c);
      if (c == 0 && k >= 3 && NAT_RP == 1) {
        if (NAT_RD) __nanosleep(NAT_RD);
        asm volatile("cp.async.bulk.wait_group.read 0;" ::: "memory");
        bulk_load(sbase + out_slot(k - 1, nt), wimg + (w2o + out_slot(k - 1, nt) - kW2Off), kWChunk, bar_w2(bars));
        mbar_arrive_expect_tx(bar_w2(bars), kWChunk);
      }
      if (c == 0 && k < 5 && nt == 6) {
        const int f = ~k & 1;
        if (tn.kind == 0) {
#pragma unroll
          for (int j = 0; j < 4; j++) {
            if ((j & 1) == 0) nb_sync_p(j ? 5 : 13);
            tma_load_5d(sbase + kXOff + (j ^ 2 * f) * 6144, tm.px, bar_x(bars, 1), 0, 0, 0, 0, line + 6 * (j ^ 2 * f));
          }
        } else {
          nb_sync_p(13);
          move_px<0, 4, 4>(tm, tt, sbase + kXOff, bar_x(bars, 1), line, tn.kind, 4 * f);
          nb_sync_p(5);
          move_px<0, 4, 4>(tm, tt, sbase + kXOff, bar_x(bars, 1), line, tn.kind, 4 - 4 * f);
        }
        mbar_arrive_expect_tx(bar_x(bars, 1), kWChunk);
        PROFS(16, 2, k * 4 + 3);
      }
      if (c == NAT_OT && k >= 2) {
        const TileCoord tp = decode_tile(tt, tile0 + k - 2);
        const int lp = first_line(tp);
        nb_sync_p(10);
        if (NAT_XW == 1 && k < 5 && nt == 6) mbar_wait(bar_x(bars, 1), k & 1);
        if (NAT_XW > 1) __nanosleep(NAT_XW);
        move_px<2, NAT_SU>(tm, tt, sbase + out_slot(k, nt), 0, lp, tp.kind);
        if (NAT_RP == 0 && k + 1 < nt) {
          asm volatile("cp.async.bulk.wait_group.read 0;" ::: "memory");
          bulk_load(sbase + out_slot(k, nt), wimg + (w2o + out_slot(k, nt) - kW2Off), kWChunk, bar_w2(bars));
          mbar_arrive_expect_tx(bar_w2(bars), kWChunk);
        }
      }
    }
    asm volatile("cp.async.bulk.wait_group 0;" ::: "memory");
  } else {
    if (blockIdx.x < 128) {
      if ((wid == 4 || (wid == 5 && blockIdx.x - 2 < 16)) && wqkv != nullptr) {
        fold_w1(blockIdx.x - 2 < 16 ? 2 * blockIdx.x + wid - 6 : blockIdx.x + (blockIdx.x < 2 ? 0 : 16), wqkv, wimg);
        if (wid == 4) asm volatile("bar.arrive 12, 64;" ::: "memory");
        if (tid == 128) GT(7);
      }
      sched_fence();
      if (wid == 1 && elect_one()) {
        const TileCoord tc = decode_tile(tt, blockIdx.x * kTilesPerCta);
        mbar_init(bar_x(bars, 0), 1);
        asm volatile("fence.mbarrier_init.release.cluster;" ::: "memory");
        mbar_arrive_expect_tx(bar_x(bars, 0), kWChunk);
        GT(15);
        move_px<0, 2>(tm, tt, sbase + kXOff + kWChunk, bar_x(bars, 0), first_line(tc), tc.kind);
        GT(16);
      }
      __syncwarp();
      sched_fence();
      if (wid == 2 && elect_one()) {
        const TileCoord tc = decode_tile(tt, blockIdx.x * kTilesPerCta);
        mbar_init(bar_full(bars, 0, 0), 1);
        asm volatile("fence.mbarrier_init.release.cluster;" ::: "memory");
        mbar_arrive_expect_tx(bar_full(bars, 0, 0), 2 * kChunkBytes);
        if (NAT_TH) wait_clock(t_start, NAT_TH);
        asm volatile("prefetch.tensormap [%0];" ::"l"((uint64_t)&tm.u8) : "memory");
        GT(17);
        first_halo(tm, sbase, tc, 0);
        first_halo(tm, sbase, tc, 1);
      }
      __syncwarp();
    }
    sched_fence();
    {
      if (w2cta) {
        const int q = blockIdx.x & 3;
        uint32_t w2o = 0;
        if (wid == 1 && elect_one()) {
          asm volatile("prefetch.tensormap [%0];" ::"l"((uint64_t)&tm.wo) : "memory");
#pragma unroll
          for (int j = 0; j < 3; j++) mbar_init(bar_raw(bars, j), 1);
          asm volatile("fence.mbarrier_init.release.cluster;" ::: "memory");
#pragma unroll
          for (int j = 0; j < 6; j++)
            asm volatile("cp.async.bulk.tensor.2d.shared::cluster.global.tile.mbarrier::complete_tx::bytes [%0], [%1, {%3, %4}], [%2];" ::"r"(
                             j < 3 ? sbase + j * 8192 : sbase + kW2Off + (j - 3) * kWChunk),
                         "l"((uint64_t)(j < 3 ? &tm.wv : &tm.wo)), "r"(bar_raw(bars, j < 3 ? 0 : j - 3)),
                         "r"(j < 3 ? 384 + 64 * j : 64 * (j - 3)), "r"(j < 3 ? 64 * q : 0) : "memory");
#pragma unroll
          for (int j = 0; j < 3; j++) mbar_arrive_expect_tx(bar_raw(bars, j), j ? kWChunk : 2 * kWChunk);
          w2o = w2_offset();
        }
        __syncwarp();
#pragma unroll 1
        for (int r = 0; r < 3; r++) {
          const int blk = 2 * r - 2 + (wid >> 2);
          if (blk < 3) {
            if (r > 0) {
              mbar_wait(bar_raw(bars, 0), 0);
              mbar_wait(bar_raw(bars, blk), 0);
            }
            if (tid == 0 && r == 1) GT(7);
            float acc[32];
            const uint64_t db = make_desc(sbase + kW2Off + max(blk, 0) * kWChunk, kWChunk, 1024);
            wg_fence();
            wg_m64tz<0, 32>(acc, make_desc(sbase, 16, 1024), db, 0);
#pragma unroll
            for (int s = 1; s < 12; s++) wg_m64t<0, 32>(acc, make_desc(sbase + (s >> 2) * 8192 + (s & 3) * 32, 16, 1024), db + s * 128, 1);
            wg_commit();
            wg_wait<0>();
            fence_regs(acc);
            if (tid == 0) GT(19);
            const int m = (tid >> 3) & 3;
#pragma unroll
            for (int j = 0; j < 8; j += 2) {
              const int n = g2_inv(8 * (j + (m >> 1)) + (tid & 7));
              asm volatile("stmatrix.sync.aligned.m8n8.x4.trans.shared.b16 [%0], {%1,%2,%3,%4};" ::"r"(
                               sbase + kW1Off + (blk + 2) * 8192 + n * 128 + (((2 * (wid & 3) + (m & 1)) ^ (n & 7)) << 4)),
                           "r"(pack_bf16(acc[4 * j], acc[4 * j + 1])), "r"(pack_bf16(acc[4 * j + 2], acc[4 * j + 3])),
                           "r"(pack_bf16(acc[4 * j + 4], acc[4 * j + 5])), "r"(pack_bf16(acc[4 * j + 6], acc[4 * j + 7])) : "memory");
            }
            fence_proxy_async();
          }
          if (tid == 0) GT(18);
          asm volatile("bar.sync 11, 256;" ::: "memory");
          if (wid == 1 && elect_one()) {
            asm volatile("{\n.reg .pred p;\nsetp.ne.s32 p, %3, 0;\n@p cp.async.bulk.global.shared::cta.bulk_group [%0], [%1], %2;\n}\n" ::"l"(
                             wimg + (w2o + w2piece(r >> 1, q) * (kWChunk / 2))),
                         "r"(sbase + kW1Off + 16384 + (r >> 1) * (kWChunk / 2)), "r"(kWChunk / 2), "r"(r) : "memory");
            asm volatile("cp.async.bulk.commit_group;" ::: "memory");
          }
          __syncwarp();
        }
        if (wid == 1) {
          if (elect_one()) asm volatile("cp.async.bulk.wait_group.read 0;" ::: "memory");
          if (tid == 32) GT(31);
          __syncwarp();
          asm volatile("bar.arrive 10, 64;" ::: "memory");
        }
      }
    }
    __syncwarp();
    if (wid < 4) asm volatile("bar.sync 0, 160;" ::: "memory");
    else asm volatile("bar.sync 14, 160;" ::: "memory");
    asm volatile("setmaxnreg.inc.sync.aligned.u32 240;");
    consumer(wid >> 2, out, wimg, sbase, zero, tm, tt);
  }
}

}

typedef CUresult (*PFN_encodeTiled)(CUtensorMap*, CUtensorMapDataType, cuuint32_t, void*, const cuuint64_t*,
                                    const cuuint64_t*, const cuuint32_t*, const cuuint32_t*, CUtensorMapInterleave,
                                    CUtensorMapSwizzle, CUtensorMapL2promotion, CUtensorMapFloatOOBfill);

extern "C" void kernel_launch(void* const* d_in, const int* in_sizes, int n_in, void* d_out, int out_size) {
  const __nv_bfloat16* x = (const __nv_bfloat16*)d_in[0];
  const __nv_bfloat16* wqkv = (const __nv_bfloat16*)d_in[1];
  const __nv_bfloat16* wo = (const __nv_bfloat16*)d_in[2];
  __nv_bfloat16* out = (__nv_bfloat16*)d_out;

  static PFN_encodeTiled encode = nullptr;
  static int num_sms = 0;
  static uint8_t* wimg = nullptr;
  if (!encode) {
    void* fn = nullptr;
    cudaDriverEntryPointQueryResult qres;
    cudaGetDriverEntryPoint("cuTensorMapEncodeTiled", &fn, cudaEnableDefault, &qres);
    encode = (PFN_encodeTiled)fn;
    cudaFuncSetAttribute(nat::nat_kernel, cudaFuncAttributeMaxDynamicSharedMemorySize, nat::kSmemBytes);
    cudaGetSymbolAddress((void**)&wimg, nat::g_wimg32);
    int dev = 0;
    cudaGetDevice(&dev);
    cudaDeviceGetAttribute(&num_sms, cudaDevAttrMultiProcessorCount, dev);
  }
  nat::Maps tm;
  cuuint32_t estr[5] = {1, 1, 1, 1, 1};
  {
    cuuint64_t vdim[5] = {48, 2, 105, 2, 112}, udim[5] = {48, 2, 112, 2, 105};
    cuuint64_t vstr[4] = {7 * 768, 768, 224 * 384, 2 * 224 * 384}, ustr[4] = {7 * 768, 2 * 224 * 384, 224 * 384, 768};
    CUtensorMap* maps[4] = {&tm.v6, &tm.v2, &tm.v14, &tm.u8};
    for (int i = 0; i < 4; i++) {
      cuuint32_t box[5] = {4, 2, i < 3 ? 4u : 8u, 1, i == 0 ? 6u : i == 1 ? 2u : i == 2 ? 14u : 3u};
      encode(maps[i], CU_TENSOR_MAP_DATA_TYPE_UINT32, 5, (void*)x, i < 3 ? vdim : udim, i < 3 ? vstr : ustr, box, estr,
             CU_TENSOR_MAP_INTERLEAVE_16B, CU_TENSOR_MAP_SWIZZLE_128B, NAT_L2P, CU_TENSOR_MAP_FLOAT_OOB_FILL_NONE);
    }
  }
  for (int i = 0; i < 8; i++) {
    const cuuint32_t row = 224 * 384, dr = (1u + (i & 1)) * row;
    const cuuint32_t shape[4][6] = {{8, 3, 2u - i, 2 * row, 128, 4 * 768}, {2, 4, 3, dr, 768, 128}, {4, 2, 3, 4 * row, 2 * row, 128}, {4, 2, 3, 768, dr, 128}};
    const cuuint32_t* sh = shape[i >> 1];
    cuuint64_t dim[5] = {64, sh[0], sh[1], sh[2], 224 * 224 * 3};
    cuuint64_t str[4] = {sh[3], sh[4], sh[5], 128};
    cuuint32_t box[5] = {64, sh[0], sh[1], sh[2], 1};
    encode(tm.px + i, CU_TENSOR_MAP_DATA_TYPE_BFLOAT16, 5, i < 4 ? (void*)x : (void*)out, dim, str, box, estr, CU_TENSOR_MAP_INTERLEAVE_NONE,
           CU_TENSOR_MAP_SWIZZLE_128B, i < 4 ? CU_TENSOR_MAP_L2_PROMOTION_L2_128B : CU_TENSOR_MAP_L2_PROMOTION_NONE,
           CU_TENSOR_MAP_FLOAT_OOB_FILL_NONE);
  }
  for (int i = 0; i < 2; i++) {
    cuuint64_t dim[2] = {i ? 192u : 576u, 192}, str[1] = {i ? 384u : 1152u};
    cuuint32_t box[2] = {64, i ? 192u : 64u};
    encode(i ? &tm.wo : &tm.wv, CU_TENSOR_MAP_DATA_TYPE_BFLOAT16, 2, i ? (void*)wo : (void*)wqkv, dim, str, box, estr,
           CU_TENSOR_MAP_INTERLEAVE_NONE, CU_TENSOR_MAP_SWIZZLE_128B, CU_TENSOR_MAP_L2_PROMOTION_L2_256B, CU_TENSOR_MAP_FLOAT_OOB_FILL_NONE);
  }
  nat::TileTable tt;
  nat::make_tiles(tt);
  const int grid = nat::kCtas;
  if (num_sms >= grid) {
    nat::nat_kernel<<<grid, 384, nat::kSmemBytes>>>(x, out, wqkv, wo, wimg, 0u, tm, tt);
  } else {
    nat::fold_kernel<<<27, 256>>>(wqkv, wo, wimg);
    nat::nat_kernel<<<grid, 384, nat::kSmemBytes>>>(x, out, nullptr, nullptr, wimg, 0u, tm, tt);
  }
}
```

```cpp
#include <cuda_runtime.h>
#include <cuda_bf16.h>
#include <cuda.h>
#include <stdint.h>

#define NAT_P1 2
#define NAT_P2 4
#define NAT_H0 2
#define NAT_T0 2100
#define NAT_TD 1200
#define NAT_TW2 4650
#define NAT_TX2 3800
#define NAT_X1P 5
#define NAT_PK 3
#define NAT_HP 1800
#define NAT_PFD 700
#define NAT_XW 200
#define NAT_SU 8
#define NAT_D0 1
#define NAT_RD 0
#define NAT_RP 0
#define NAT_SP 9
#define NAT_OT 0
#define NAT_L2P CU_TENSOR_MAP_L2_PROMOTION_L2_128B
#define NAT_TH 600
#define NAT_TM 1300
#define NAT_A5 1
#define NAT_D1 2
#define NAT_SB 0
namespace nat {

constexpr int kW = 224, kC = 192;
constexpr int kCtas = 132;
constexpr int kTilesPerCta = 6;
constexpr float kAlpha = 0.07216878364870322f * 1.4426950408889634f;
constexpr uint32_t kChunkBytes = 13 * 1024;
constexpr uint32_t kWChunk = 192 * 128;
constexpr uint32_t kWBytes = 3 * kWChunk;
constexpr uint32_t kW1Off = 6 * kChunkBytes;
constexpr uint32_t kW2Off = kW1Off + kWBytes;
constexpr uint32_t kXOff = kW2Off + kWChunk;
constexpr uint32_t kBarOff = kW2Off + kWBytes;
constexpr uint32_t kProfOff = kBarOff + 208;
constexpr uint32_t kSmemBytes = kBarOff + 1024;

static_assert(kW1Off % 1024 == 0 && kW2Off % 1024 == 0 && kChunkBytes % 1024 == 0, "swizzle alignment");
static_assert(kSmemBytes <= 232448, "smem");

constexpr uint32_t kEmpty = 0xFFFFFFFFu;
#define NAT_R8(v) v, v, v, v, v, v, v, v
#define NAT_R2K(v) NAT_R8(NAT_R8(NAT_R8(v))), NAT_R8(NAT_R8(NAT_R8(v))), NAT_R8(NAT_R8(NAT_R8(v))), NAT_R8(NAT_R8(NAT_R8(v)))
#define NAT_IMG NAT_R8(NAT_R2K(kEmpty)), NAT_R2K(kEmpty)
__device__ __align__(1024) uint32_t g_wimg32[3 * kWBytes / 4] = {NAT_IMG, NAT_IMG, NAT_IMG};
static_assert(kWBytes / 4 == 9 * 2048, "initialiser");
__device__ __align__(128) uint32_t g_flag[96];
__device__ __forceinline__ uint32_t w2_offset() {
  uint32_t v;
  asm volatile("ld.relaxed.gpu.global.u32 %0, [%1];" : "=r"(v) : "l"(g_flag + 64) : "memory");
  return (1 + v) * kWBytes;
}

#define PROFS(id, wgid, slotid) do { } while (0)
#define PROF(wgid, slotid) do { } while (0)
#define PROF_DUMP(wgid) do { } while (0)

#define GT(slotid) do { } while (0)
#define GT_DUMP() do { } while (0)

__device__ __forceinline__ uint32_t smem_u32(const void* p) { return (uint32_t)__cvta_generic_to_shared(p); }

__device__ __forceinline__ void mbar_init(uint32_t bar, uint32_t count) {
  asm volatile("mbarrier.init.shared::cta.b64 [%0], %1;" ::"r"(bar), "r"(count) : "memory");
}
__device__ __forceinline__ void mbar_arrive(uint32_t bar) {
  asm volatile("mbarrier.arrive.shared::cta.b64 _, [%0];" ::"r"(bar) : "memory");
}
__device__ __forceinline__ void mbar_arrive_expect_tx(uint32_t bar, uint32_t bytes) {
  asm volatile("mbarrier.arrive.expect_tx.shared::cta.b64 _, [%0], %1;" ::"r"(bar), "r"(bytes) : "memory");
}
__device__ __forceinline__ void mbar_wait(uint32_t bar, uint32_t parity) {
  uint32_t ok;
  uint32_t it = 0;
  do {
    asm volatile(
        "{\n.reg .pred p;\n"
        "mbarrier.try_wait.parity.shared::cta.b64 p, [%1], %2;\n"
        "selp.u32 %0, 1, 0, p;\n}\n"
        : "=r"(ok)
        : "r"(bar), "r"(parity)
        : "memory");
    if (++it > (1u << 24)) break;
  } while (!ok);
}
__device__ __forceinline__ uint32_t mbar_test(uint32_t bar, uint32_t parity) {
  uint32_t ok;
  asm volatile("{\n.reg .pred p;\nmbarrier.test_wait.parity.shared::cta.b64 p, [%1], %2;\nselp.u32 %0, 1, 0, p;\n}\n"
               : "=r"(ok) : "r"(bar), "r"(parity) : "memory");
  return ok;
}
__device__ __forceinline__ void mbar_wait_if(uint32_t ok, uint32_t bar, uint32_t parity) {
  if (!__all_sync(0xffffffffu, ok)) mbar_wait(bar, parity);
}
__device__ __forceinline__ bool elect_one() {
  uint32_t r;
  asm volatile("{\n.reg .pred p;\nelect.sync _|p, 0xffffffff;\nselp.u32 %0, 1, 0, p;\n}\n" : "=r"(r));
  return r != 0;
}
__device__ __forceinline__ void nb_arrive(int id) { asm volatile("bar.arrive %0, 256;" ::"r"(id) : "memory"); }
__device__ __forceinline__ void nb_sync(int id) { asm volatile("bar.sync %0, 256;" ::"r"(id) : "memory"); }
__device__ __forceinline__ void nb_arrive_p(int id) { asm volatile("bar.arrive %0, 160;" ::"r"(id) : "memory"); }
__device__ __forceinline__ void nb_sync_p(int id) { asm volatile("bar.sync %0, 160;" ::"r"(id) : "memory"); }
__device__ __forceinline__ void fence_proxy_async() { asm volatile("fence.proxy.async.shared::cta;" ::: "memory"); }

__device__ __forceinline__ void tma_load_5d(uint32_t dst, const CUtensorMap* map, uint32_t bar, int c0, int c1, int c2,
                                            int c3, int c4) {
  asm volatile(
      "cp.async.bulk.tensor.5d.shared::cluster.global.tile.mbarrier::complete_tx::bytes "
      "[%0], [%1, {%3, %4, %5, %6, %7}], [%2];"
      ::"r"(dst), "l"((uint64_t)map), "r"(bar), "r"(c0), "r"(c1), "r"(c2), "r"(c3), "r"(c4)
      : "memory");
}
__device__ __forceinline__ void bulk_load(uint32_t dst, const void* src, uint32_t bytes, uint32_t bar) {
  asm volatile("cp.async.bulk.shared::cluster.global.mbarrier::complete_tx::bytes [%0], [%1], %2, [%3];"
               ::"r"(dst), "l"((uint64_t)src), "r"(bytes), "r"(bar)
               : "memory");
}

__device__ __forceinline__ void wg_fence() { asm volatile("wgmma.fence.sync.aligned;" ::: "memory"); }
__device__ __forceinline__ void wg_commit() { asm volatile("wgmma.commit_group.sync.aligned;" ::: "memory"); }
template <int N>
__device__ __forceinline__ void wg_wait() { asm volatile("wgmma.wait_group.sync.aligned %0;" ::"n"(N) : "memory"); }

template <int N>
__device__ __forceinline__ void fence_regs(float (&d)[N]) {
#pragma unroll
  for (int i = 0; i < N; i++) asm volatile("" : "+f"(d[i])::"memory");
}
template <int N>
__device__ __forceinline__ void keep_regs(uint32_t (&d)[N]) {
#pragma unroll
  for (int i = 0; i < N; i++) asm volatile("" : "+r"(d[i])::"memory");
}

__device__ __forceinline__ uint32_t pack_bf16(float lo, float hi) {
  uint32_t d;
  asm("cvt.rn.bf16x2.f32 %0, %1, %2;" : "=r"(d) : "f"(hi), "f"(lo));
  return d;
}
__device__ __forceinline__ float ex2(float x) {
  float y;
  asm("ex2.approx.ftz.f32 %0, %1;" : "=f"(y) : "f"(x));
  return y;
}
__device__ __forceinline__ float rcp_approx(float x) {
  float y;
  asm("rcp.approx.ftz.f32 %0, %1;" : "=f"(y) : "f"(x));
  return y;
}
__device__ __forceinline__ uint4 ldg128_nc(const void* p) {
  uint4 v;
  asm volatile("ld.global.nc.v4.u32 {%0,%1,%2,%3}, [%4];" : "=r"(v.x), "=r"(v.y), "=r"(v.z), "=r"(v.w) : "l"(p));
  return v;
}
__device__ __forceinline__ void stg128(void* p, uint32_t a, uint32_t b, uint32_t c, uint32_t d) {
  asm volatile("st.global.v4.u32 [%0], {%1,%2,%3,%4};" ::"l"(p), "r"(a), "r"(b), "r"(c), "r"(d) : "memory");
}

__device__ __forceinline__ long long clk64() {
  long long c;
  asm volatile("mov.u64 %0, %clock64;" : "=l"(c)::"memory");
  return c;
}
__device__ __forceinline__ void sched_fence() { while (clk64() < 0) { } }

__device__ __forceinline__ uint64_t make_desc(uint32_t addr, uint32_t lbo, uint32_t sbo, uint32_t mode = 1) {
  return (uint64_t)((addr & 0x3FFFF) >> 4) | ((uint64_t)(lbo >> 4) << 16) | ((uint64_t)(sbo >> 4) << 32) |
         ((uint64_t)mode << 62);
}

template <int OFF, int NN>
__device__ __forceinline__ void wg_m192(float (&d)[NN], uint64_t desc_a, uint64_t desc_b, int scale_d) {
  asm volatile(
      "{\n.reg .pred p;\nsetp.ne.b32 p, %98, 0;\n"
      "wgmma.mma_async.sync.aligned.m64n192k16.f32.bf16.bf16 "
      "{%0,%1,%2,%3,%4,%5,%6,%7,%8,%9,%10,%11,%12,%13,%14,%15,"
      "%16,%17,%18,%19,%20,%21,%22,%23,%24,%25,%26,%27,%28,%29,%30,%31,"
      "%32,%33,%34,%35,%36,%37,%38,%39,%40,%41,%42,%43,%44,%45,%46,%47,"
      "%48,%49,%50,%51,%52,%53,%54,%55,%56,%57,%58,%59,%60,%61,%62,%63,"
      "%64,%65,%66,%67,%68,%69,%70,%71,%72,%73,%74,%75,%76,%77,%78,%79,"
      "%80,%81,%82,%83,%84,%85,%86,%87,%88,%89,%90,%91,%92,%93,%94,%95}, "
      "%96, %97, p, 1, 1, 0, 0;\n}\n"
      : "+f"(d[OFF + 0]), "+f"(d[OFF + 1]), "+f"(d[OFF + 2]), "+f"(d[OFF + 3]), "+f"(d[OFF + 4]), "+f"(d[OFF + 5]),
        "+f"(d[OFF + 6]), "+f"(d[OFF + 7]), "+f"(d[OFF + 8]), "+f"(d[OFF + 9]), "+f"(d[OFF + 10]), "+f"(d[OFF + 11]),
        "+f"(d[OFF + 12]), "+f"(d[OFF + 13]), "+f"(d[OFF + 14]), "+f"(d[OFF + 15]), "+f"(d[OFF + 16]), "+f"(d[OFF + 17]),
        "+f"(d[OFF + 18]), "+f"(d[OFF + 19]), "+f"(d[OFF + 20]), "+f"(d[OFF + 21]), "+f"(d[OFF + 22]), "+f"(d[OFF + 23]),
        "+f"(d[OFF + 24]), "+f"(d[OFF + 25]), "+f"(d[OFF + 26]), "+f"(d[OFF + 27]), "+f"(d[OFF + 28]), "+f"(d[OFF + 29]),
        "+f"(d[OFF + 30]), "+f"(d[OFF + 31]), "+f"(d[OFF + 32]), "+f"(d[OFF + 33]), "+f"(d[OFF + 34]), "+f"(d[OFF + 35]),
        "+f"(d[OFF + 36]), "+f"(d[OFF + 37]), "+f"(d[OFF + 38]), "+f"(d[OFF + 39]), "+f"(d[OFF + 40]), "+f"(d[OFF + 41]),
        "+f"(d[OFF + 42]), "+f"(d[OFF + 43]), "+f"(d[OFF + 44]), "+f"(d[OFF + 45]), "+f"(d[OFF + 46]), "+f"(d[OFF + 47]),
        "+f"(d[OFF + 48]), "+f"(d[OFF + 49]), "+f"(d[OFF + 50]), "+f"(d[OFF + 51]), "+f"(d[OFF + 52]), "+f"(d[OFF + 53]),
        "+f"(d[OFF + 54]), "+f"(d[OFF + 55]), "+f"(d[OFF + 56]), "+f"(d[OFF + 57]), "+f"(d[OFF + 58]), "+f"(d[OFF + 59]),
        "+f"(d[OFF + 60]), "+f"(d[OFF + 61]), "+f"(d[OFF + 62]), "+f"(d[OFF + 63]), "+f"(d[OFF + 64]), "+f"(d[OFF + 65]),
        "+f"(d[OFF + 66]), "+f"(d[OFF + 67]), "+f"(d[OFF + 68]), "+f"(d[OFF + 69]), "+f"(d[OFF + 70]), "+f"(d[OFF + 71]),
        "+f"(d[OFF + 72]), "+f"(d[OFF + 73]), "+f"(d[OFF + 74]), "+f"(d[OFF + 75]), "+f"(d[OFF + 76]), "+f"(d[OFF + 77]),
        "+f"(d[OFF + 78]), "+f"(d[OFF + 79]), "+f"(d[OFF + 80]), "+f"(d[OFF + 81]), "+f"(d[OFF + 82]), "+f"(d[OFF + 83]),
        "+f"(d[OFF + 84]), "+f"(d[OFF + 85]), "+f"(d[OFF + 86]), "+f"(d[OFF + 87]), "+f"(d[OFF + 88]), "+f"(d[OFF + 89]),
        "+f"(d[OFF + 90]), "+f"(d[OFF + 91]), "+f"(d[OFF + 92]), "+f"(d[OFF + 93]), "+f"(d[OFF + 94]), "+f"(d[OFF + 95])
      : "l"(desc_a), "l"(desc_b), "r"(scale_d));
}

template <int OFF, int NN>
__device__ __forceinline__ void wg_m192z(float (&d)[NN], uint64_t desc_a, uint64_t desc_b, int scale_d) {
  asm volatile(
      "{\n.reg .pred p;\nsetp.ne.b32 p, %98, 0;\n"
      "wgmma.mma_async.sync.aligned.m64n192k16.f32.bf16.bf16 "
      "{%0,%1,%2,%3,%4,%5,%6,%7,%8,%9,%10,%11,%12,%13,%14,%15,"
      "%16,%17,%18,%19,%20,%21,%22,%23,%24,%25,%26,%27,%28,%29,%30,%31,"
      "%32,%33,%34,%35,%36,%37,%38,%39,%40,%41,%42,%43,%44,%45,%46,%47,"
      "%48,%49,%50,%51,%52,%53,%54,%55,%56,%57,%58,%59,%60,%61,%62,%63,"
      "%64,%65,%66,%67,%68,%69,%70,%71,%72,%73,%74,%75,%76,%77,%78,%79,"
      "%80,%81,%82,%83,%84,%85,%86,%87,%88,%89,%90,%91,%92,%93,%94,%95}, "
      "%96, %97, p, 1, 1, 0, 0;\n}\n"
      : "=f"(d[OFF + 0]), "=f"(d[OFF + 1]), "=f"(d[OFF + 2]), "=f"(d[OFF + 3]), "=f"(d[OFF + 4]), "=f"(d[OFF + 5]),
        "=f"(d[OFF + 6]), "=f"(d[OFF + 7]), "=f"(d[OFF + 8]), "=f"(d[OFF + 9]), "=f"(d[OFF + 10]), "=f"(d[OFF + 11]),
        "=f"(d[OFF + 12]), "=f"(d[OFF + 13]), "=f"(d[OFF + 14]), "=f"(d[OFF + 15]), "=f"(d[OFF + 16]), "=f"(d[OFF + 17]),
        "=f"(d[OFF + 18]), "=f"(d[OFF + 19]), "=f"(d[OFF + 20]), "=f"(d[OFF + 21]), "=f"(d[OFF + 22]), "=f"(d[OFF + 23]),
        "=f"(d[OFF + 24]), "=f"(d[OFF + 25]), "=f"(d[OFF + 26]), "=f"(d[OFF + 27]), "=f"(d[OFF + 28]), "=f"(d[OFF + 29]),
        "=f"(d[OFF + 30]), "=f"(d[OFF + 31]), "=f"(d[OFF + 32]), "=f"(d[OFF + 33]), "=f"(d[OFF + 34]), "=f"(d[OFF + 35]),
        "=f"(d[OFF + 36]), "=f"(d[OFF + 37]), "=f"(d[OFF + 38]), "=f"(d[OFF + 39]), "=f"(d[OFF + 40]), "=f"(d[OFF + 41]),
        "=f"(d[OFF + 42]), "=f"(d[OFF + 43]), "=f"(d[OFF + 44]), "=f"(d[OFF + 45]), "=f"(d[OFF + 46]), "=f"(d[OFF + 47]),
        "=f"(d[OFF + 48]), "=f"(d[OFF + 49]), "=f"(d[OFF + 50]), "=f"(d[OFF + 51]), "=f"(d[OFF + 52]), "=f"(d[OFF + 53]),
        "=f"(d[OFF + 54]), "=f"(d[OFF + 55]), "=f"(d[OFF + 56]), "=f"(d[OFF + 57]), "=f"(d[OFF + 58]), "=f"(d[OFF + 59]),
        "=f"(d[OFF + 60]), "=f"(d[OFF + 61]), "=f"(d[OFF + 62]), "=f"(d[OFF + 63]), "=f"(d[OFF + 64]), "=f"(d[OFF + 65]),
        "=f"(d[OFF + 66]), "=f"(d[OFF + 67]), "=f"(d[OFF + 68]), "=f"(d[OFF + 69]), "=f"(d[OFF + 70]), "=f"(d[OFF + 71]),
        "=f"(d[OFF + 72]), "=f"(d[OFF + 73]), "=f"(d[OFF + 74]), "=f"(d[OFF + 75]), "=f"(d[OFF + 76]), "=f"(d[OFF + 77]),
        "=f"(d[OFF + 78]), "=f"(d[OFF + 79]), "=f"(d[OFF + 80]), "=f"(d[OFF + 81]), "=f"(d[OFF + 82]), "=f"(d[OFF + 83]),
        "=f"(d[OFF + 84]), "=f"(d[OFF + 85]), "=f"(d[OFF + 86]), "=f"(d[OFF + 87]), "=f"(d[OFF + 88]), "=f"(d[OFF + 89]),
        "=f"(d[OFF + 90]), "=f"(d[OFF + 91]), "=f"(d[OFF + 92]), "=f"(d[OFF + 93]), "=f"(d[OFF + 94]), "=f"(d[OFF + 95])
      : "l"(desc_a), "l"(desc_b), "r"(scale_d));
}

template <int OFF, int NN>
__device__ __forceinline__ void wg_m64t(float (&d)[NN], uint64_t desc_a, uint64_t desc_b, int scale_d) {
  asm volatile(
      "{\n.reg .pred p;\nsetp.ne.b32 p, %34, 0;\n"
      "wgmma.mma_async.sync.aligned.m64n64k16.f32.bf16.bf16 "
      "{%0,%1,%2,%3,%4,%5,%6,%7,%8,%9,%10,%11,%12,%13,%14,%15,"
      "%16,%17,%18,%19,%20,%21,%22,%23,%24,%25,%26,%27,%28,%29,%30,%31}, "
      "%32, %33, p, 1, 1, 0, 1;\n}\n"
      : "+f"(d[OFF + 0]), "+f"(d[OFF + 1]), "+f"(d[OFF + 2]), "+f"(d[OFF + 3]), "+f"(d[OFF + 4]), "+f"(d[OFF + 5]),
        "+f"(d[OFF + 6]), "+f"(d[OFF + 7]), "+f"(d[OFF + 8]), "+f"(d[OFF + 9]), "+f"(d[OFF + 10]), "+f"(d[OFF + 11]),
        "+f"(d[OFF + 12]), "+f"(d[OFF + 13]), "+f"(d[OFF + 14]), "+f"(d[OFF + 15]), "+f"(d[OFF + 16]), "+f"(d[OFF + 17]),
        "+f"(d[OFF + 18]), "+f"(d[OFF + 19]), "+f"(d[OFF + 20]), "+f"(d[OFF + 21]), "+f"(d[OFF + 22]), "+f"(d[OFF + 23]),
        "+f"(d[OFF + 24]), "+f"(d[OFF + 25]), "+f"(d[OFF + 26]), "+f"(d[OFF + 27]), "+f"(d[OFF + 28]), "+f"(d[OFF + 29]),
        "+f"(d[OFF + 30]), "+f"(d[OFF + 31])
      : "l"(desc_a), "l"(desc_b), "r"(scale_d));
}

template <int OFF, int NN>
__device__ __forceinline__ void wg_m64tz(float (&d)[NN], uint64_t desc_a, uint64_t desc_b, int scale_d) {
  asm volatile(
      "{\n.reg .pred p;\nsetp.ne.b32 p, %34, 0;\n"
      "wgmma.mma_async.sync.aligned.m64n64k16.f32.bf16.bf16 "
      "{%0,%1,%2,%3,%4,%5,%6,%7,%8,%9,%10,%11,%12,%13,%14,%15,"
      "%16,%17,%18,%19,%20,%21,%22,%23,%24,%25,%26,%27,%28,%29,%30,%31}, "
      "%32, %33, p, 1, 1, 0, 1;\n}\n"
      : "=f"(d[OFF + 0]), "=f"(d[OFF + 1]), "=f"(d[OFF + 2]), "=f"(d[OFF + 3]), "=f"(d[OFF + 4]), "=f"(d[OFF + 5]),
        "=f"(d[OFF + 6]), "=f"(d[OFF + 7]), "=f"(d[OFF + 8]), "=f"(d[OFF + 9]), "=f"(d[OFF + 10]), "=f"(d[OFF + 11]),
        "=f"(d[OFF + 12]), "=f"(d[OFF + 13]), "=f"(d[OFF + 14]), "=f"(d[OFF + 15]), "=f"(d[OFF + 16]), "=f"(d[OFF + 17]),
        "=f"(d[OFF + 18]), "=f"(d[OFF + 19]), "=f"(d[OFF + 20]), "=f"(d[OFF + 21]), "=f"(d[OFF + 22]), "=f"(d[OFF + 23]),
        "=f"(d[OFF + 24]), "=f"(d[OFF + 25]), "=f"(d[OFF + 26]), "=f"(d[OFF + 27]), "=f"(d[OFF + 28]), "=f"(d[OFF + 29]),
        "=f"(d[OFF + 30]), "=f"(d[OFF + 31])
      : "l"(desc_a), "l"(desc_b), "r"(scale_d));
}

template <int OFF, int NN>
__device__ __forceinline__ void wg_d96(float (&d)[NN], uint32_t a0, uint32_t a1, uint32_t a2, uint32_t a3,
                                       uint64_t desc_b, int scale_d) {
  asm volatile(
      "{\n.reg .pred p;\nsetp.ne.b32 p, %53, 0;\n"
      "wgmma.mma_async.sync.aligned.m64n96k16.f32.bf16.bf16 "
      "{%0,%1,%2,%3,%4,%5,%6,%7,%8,%9,%10,%11,%12,%13,%14,%15,"
      "%16,%17,%18,%19,%20,%21,%22,%23,%24,%25,%26,%27,%28,%29,%30,%31,"
      "%32,%33,%34,%35,%36,%37,%38,%39,%40,%41,%42,%43,%44,%45,%46,%47}, "
      "{%48,%49,%50,%51}, %52, p, 1, 1, 0;\n}\n"
      : "+f"(d[OFF + 0]), "+f"(d[OFF + 1]), "+f"(d[OFF + 2]), "+f"(d[OFF + 3]), "+f"(d[OFF + 4]), "+f"(d[OFF + 5]),
        "+f"(d[OFF + 6]), "+f"(d[OFF + 7]), "+f"(d[OFF + 8]), "+f"(d[OFF + 9]), "+f"(d[OFF + 10]), "+f"(d[OFF + 11]),
        "+f"(d[OFF + 12]), "+f"(d[OFF + 13]), "+f"(d[OFF + 14]), "+f"(d[OFF + 15]), "+f"(d[OFF + 16]), "+f"(d[OFF + 17]),
        "+f"(d[OFF + 18]), "+f"(d[OFF + 19]), "+f"(d[OFF + 20]), "+f"(d[OFF + 21]), "+f"(d[OFF + 22]), "+f"(d[OFF + 23]),
        "+f"(d[OFF + 24]), "+f"(d[OFF + 25]), "+f"(d[OFF + 26]), "+f"(d[OFF + 27]), "+f"(d[OFF + 28]), "+f"(d[OFF + 29]),
        "+f"(d[OFF + 30]), "+f"(d[OFF + 31]), "+f"(d[OFF + 32]), "+f"(d[OFF + 33]), "+f"(d[OFF + 34]), "+f"(d[OFF + 35]),
        "+f"(d[OFF + 36]), "+f"(d[OFF + 37]), "+f"(d[OFF + 38]), "+f"(d[OFF + 39]), "+f"(d[OFF + 40]), "+f"(d[OFF + 41]),
        "+f"(d[OFF + 42]), "+f"(d[OFF + 43]), "+f"(d[OFF + 44]), "+f"(d[OFF + 45]), "+f"(d[OFF + 46]), "+f"(d[OFF + 47])
      : "r"(a0), "r"(a1), "r"(a2), "r"(a3), "l"(desc_b), "r"(scale_d));
}

template <int OFF, int NN>
__device__ __forceinline__ void wg_d96z(float (&d)[NN], uint32_t a0, uint32_t a1, uint32_t a2, uint32_t a3,
                                       uint64_t desc_b, int scale_d) {
  asm volatile(
      "{\n.reg .pred p;\nsetp.ne.b32 p, %53, 0;\n"
      "wgmma.mma_async.sync.aligned.m64n96k16.f32.bf16.bf16 "
      "{%0,%1,%2,%3,%4,%5,%6,%7,%8,%9,%10,%11,%12,%13,%14,%15,"
      "%16,%17,%18,%19,%20,%21,%22,%23,%24,%25,%26,%27,%28,%29,%30,%31,"
      "%32,%33,%34,%35,%36,%37,%38,%39,%40,%41,%42,%43,%44,%45,%46,%47}, "
      "{%48,%49,%50,%51}, %52, p, 1, 1, 0;\n}\n"
      : "=f"(d[OFF + 0]), "=f"(d[OFF + 1]), "=f"(d[OFF + 2]), "=f"(d[OFF + 3]), "=f"(d[OFF + 4]), "=f"(d[OFF + 5]),
        "=f"(d[OFF + 6]), "=f"(d[OFF + 7]), "=f"(d[OFF + 8]), "=f"(d[OFF + 9]), "=f"(d[OFF + 10]), "=f"(d[OFF + 11]),
        "=f"(d[OFF + 12]), "=f"(d[OFF + 13]), "=f"(d[OFF + 14]), "=f"(d[OFF + 15]), "=f"(d[OFF + 16]), "=f"(d[OFF + 17]),
        "=f"(d[OFF + 18]), "=f"(d[OFF + 19]), "=f"(d[OFF + 20]), "=f"(d[OFF + 21]), "=f"(d[OFF + 22]), "=f"(d[OFF + 23]),
        "=f"(d[OFF + 24]), "=f"(d[OFF + 25]), "=f"(d[OFF + 26]), "=f"(d[OFF + 27]), "=f"(d[OFF + 28]), "=f"(d[OFF + 29]),
        "=f"(d[OFF + 30]), "=f"(d[OFF + 31]), "=f"(d[OFF + 32]), "=f"(d[OFF + 33]), "=f"(d[OFF + 34]), "=f"(d[OFF + 35]),
        "=f"(d[OFF + 36]), "=f"(d[OFF + 37]), "=f"(d[OFF + 38]), "=f"(d[OFF + 39]), "=f"(d[OFF + 40]), "=f"(d[OFF + 41]),
        "=f"(d[OFF + 42]), "=f"(d[OFF + 43]), "=f"(d[OFF + 44]), "=f"(d[OFF + 45]), "=f"(d[OFF + 46]), "=f"(d[OFF + 47])
      : "r"(a0), "r"(a1), "r"(a2), "r"(a3), "l"(desc_b), "r"(scale_d));
}

template <int OFF, int NN>
__device__ __forceinline__ void wg_s104(float (&d)[NN], uint32_t a0, uint32_t a1, uint32_t a2, uint32_t a3,
                                       uint64_t desc_b, int scale_d, uint32_t meta) {
  asm volatile(
      "{\n.reg .pred p;\nsetp.ne.b32 p, %57, 0;\n"
      "wgmma.mma_async.sp.sync.aligned.m64n104k32.f32.bf16.bf16 "
      "{%0,%1,%2,%3,%4,%5,%6,%7,%8,%9,%10,%11,%12,%13,%14,%15,"
      "%16,%17,%18,%19,%20,%21,%22,%23,%24,%25,%26,%27,%28,%29,%30,%31,"
      "%32,%33,%34,%35,%36,%37,%38,%39,%40,%41,%42,%43,%44,%45,%46,%47,"
      "%48,%49,%50,%51}, "
      "{%52,%53,%54,%55}, %56, %58, 0, p, 1, 1, 0;\n}\n"
      : "+f"(d[OFF + 0]), "+f"(d[OFF + 1]), "+f"(d[OFF + 2]), "+f"(d[OFF + 3]), "+f"(d[OFF + 4]), "+f"(d[OFF + 5]),
        "+f"(d[OFF + 6]), "+f"(d[OFF + 7]), "+f"(d[OFF + 8]), "+f"(d[OFF + 9]), "+f"(d[OFF + 10]), "+f"(d[OFF + 11]),
        "+f"(d[OFF + 12]), "+f"(d[OFF + 13]), "+f"(d[OFF + 14]), "+f"(d[OFF + 15]), "+f"(d[OFF + 16]), "+f"(d[OFF + 17]),
        "+f"(d[OFF + 18]), "+f"(d[OFF + 19]), "+f"(d[OFF + 20]), "+f"(d[OFF + 21]), "+f"(d[OFF + 22]), "+f"(d[OFF + 23]),
        "+f"(d[OFF + 24]), "+f"(d[OFF + 25]), "+f"(d[OFF + 26]), "+f"(d[OFF + 27]), "+f"(d[OFF + 28]), "+f"(d[OFF + 29]),
        "+f"(d[OFF + 30]), "+f"(d[OFF + 31]), "+f"(d[OFF + 32]), "+f"(d[OFF + 33]), "+f"(d[OFF + 34]), "+f"(d[OFF + 35]),
        "+f"(d[OFF + 36]), "+f"(d[OFF + 37]), "+f"(d[OFF + 38]), "+f"(d[OFF + 39]), "+f"(d[OFF + 40]), "+f"(d[OFF + 41]),
        "+f"(d[OFF + 42]), "+f"(d[OFF + 43]), "+f"(d[OFF + 44]), "+f"(d[OFF + 45]), "+f"(d[OFF + 46]), "+f"(d[OFF + 47]),
        "+f"(d[OFF + 48]), "+f"(d[OFF + 49]), "+f"(d[OFF + 50]), "+f"(d[OFF + 51])
      : "r"(a0), "r"(a1), "r"(a2), "r"(a3), "l"(desc_b), "r"(scale_d), "r"(meta));
}

template <int OFF, int NN>
__device__ __forceinline__ void wg_s104z(float (&d)[NN], uint32_t a0, uint32_t a1, uint32_t a2, uint32_t a3,
                                       uint64_t desc_b, int scale_d, uint32_t meta) {
  asm volatile(
      "{\n.reg .pred p;\nsetp.ne.b32 p, %57, 0;\n"
      "wgmma.mma_async.sp.sync.aligned.m64n104k32.f32.bf16.bf16 "
      "{%0,%1,%2,%3,%4,%5,%6,%7,%8,%9,%10,%11,%12,%13,%14,%15,"
      "%16,%17,%18,%19,%20,%21,%22,%23,%24,%25,%26,%27,%28,%29,%30,%31,"
      "%32,%33,%34,%35,%36,%37,%38,%39,%40,%41,%42,%43,%44,%45,%46,%47,"
      "%48,%49,%50,%51}, "
      "{%52,%53,%54,%55}, %56, %58, 0, p, 1, 1, 0;\n}\n"
      : "=f"(d[OFF + 0]), "=f"(d[OFF + 1]), "=f"(d[OFF + 2]), "=f"(d[OFF + 3]), "=f"(d[OFF + 4]), "=f"(d[OFF + 5]),
        "=f"(d[OFF + 6]), "=f"(d[OFF + 7]), "=f"(d[OFF + 8]), "=f"(d[OFF + 9]), "=f"(d[OFF + 10]), "=f"(d[OFF + 11]),
        "=f"(d[OFF + 12]), "=f"(d[OFF + 13]), "=f"(d[OFF + 14]), "=f"(d[OFF + 15]), "=f"(d[OFF + 16]), "=f"(d[OFF + 17]),
        "=f"(d[OFF + 18]), "=f"(d[OFF + 19]), "=f"(d[OFF + 20]), "=f"(d[OFF + 21]), "=f"(d[OFF + 22]), "=f"(d[OFF + 23]),
        "=f"(d[OFF + 24]), "=f"(d[OFF + 25]), "=f"(d[OFF + 26]), "=f"(d[OFF + 27]), "=f"(d[OFF + 28]), "=f"(d[OFF + 29]),
        "=f"(d[OFF + 30]), "=f"(d[OFF + 31]), "=f"(d[OFF + 32]), "=f"(d[OFF + 33]), "=f"(d[OFF + 34]), "=f"(d[OFF + 35]),
        "=f"(d[OFF + 36]), "=f"(d[OFF + 37]), "=f"(d[OFF + 38]), "=f"(d[OFF + 39]), "=f"(d[OFF + 40]), "=f"(d[OFF + 41]),
        "=f"(d[OFF + 42]), "=f"(d[OFF + 43]), "=f"(d[OFF + 44]), "=f"(d[OFF + 45]), "=f"(d[OFF + 46]), "=f"(d[OFF + 47]),
        "=f"(d[OFF + 48]), "=f"(d[OFF + 49]), "=f"(d[OFF + 50]), "=f"(d[OFF + 51])
      : "r"(a0), "r"(a1), "r"(a2), "r"(a3), "l"(desc_b), "r"(scale_d), "r"(meta));
}

template <int OFF, int NN>
__device__ __forceinline__ void wg_s48(float (&d)[NN], uint32_t a0, uint32_t a1, uint32_t a2, uint32_t a3,
                                       uint64_t desc_b, int scale_d, uint32_t meta) {
  asm volatile(
      "{\n.reg .pred p;\nsetp.ne.b32 p, %29, 0;\n"
      "wgmma.mma_async.sp.sync.aligned.m64n48k32.f32.bf16.bf16 "
      "{%0,%1,%2,%3,%4,%5,%6,%7,%8,%9,%10,%11,%12,%13,%14,%15,"
      "%16,%17,%18,%19,%20,%21,%22,%23}, "
      "{%24,%25,%26,%27}, %28, %30, 0, p, 1, 1, 0;\n}\n"
      : "+f"(d[OFF + 0]), "+f"(d[OFF + 1]), "+f"(d[OFF + 2]), "+f"(d[OFF + 3]), "+f"(d[OFF + 4]), "+f"(d[OFF + 5]),
        "+f"(d[OFF + 6]), "+f"(d[OFF + 7]), "+f"(d[OFF + 8]), "+f"(d[OFF + 9]), "+f"(d[OFF + 10]), "+f"(d[OFF + 11]),
        "+f"(d[OFF + 12]), "+f"(d[OFF + 13]), "+f"(d[OFF + 14]), "+f"(d[OFF + 15]), "+f"(d[OFF + 16]), "+f"(d[OFF + 17]),
        "+f"(d[OFF + 18]), "+f"(d[OFF + 19]), "+f"(d[OFF + 20]), "+f"(d[OFF + 21]), "+f"(d[OFF + 22]), "+f"(d[OFF + 23])
      : "r"(a0), "r"(a1), "r"(a2), "r"(a3), "l"(desc_b), "r"(scale_d), "r"(meta));
}

template <int OFF, int NN>
__device__ __forceinline__ void wg_s48z(float (&d)[NN], uint32_t a0, uint32_t a1, uint32_t a2, uint32_t a3,
                                       uint64_t desc_b, int scale_d, uint32_t meta) {
  asm volatile(
      "{\n.reg .pred p;\nsetp.ne.b32 p, %29, 0;\n"
      "wgmma.mma_async.sp.sync.aligned.m64n48k32.f32.bf16.bf16 "
      "{%0,%1,%2,%3,%4,%5,%6,%7,%8,%9,%10,%11,%12,%13,%14,%15,"
      "%16,%17,%18,%19,%20,%21,%22,%23}, "
      "{%24,%25,%26,%27}, %28, %30, 0, p, 1, 1, 0;\n}\n"
      : "=f"(d[OFF + 0]), "=f"(d[OFF + 1]), "=f"(d[OFF + 2]), "=f"(d[OFF + 3]), "=f"(d[OFF + 4]), "=f"(d[OFF + 5]),
        "=f"(d[OFF + 6]), "=f"(d[OFF + 7]), "=f"(d[OFF + 8]), "=f"(d[OFF + 9]), "=f"(d[OFF + 10]), "=f"(d[OFF + 11]),
        "=f"(d[OFF + 12]), "=f"(d[OFF + 13]), "=f"(d[OFF + 14]), "=f"(d[OFF + 15]), "=f"(d[OFF + 16]), "=f"(d[OFF + 17]),
        "=f"(d[OFF + 18]), "=f"(d[OFF + 19]), "=f"(d[OFF + 20]), "=f"(d[OFF + 21]), "=f"(d[OFF + 22]), "=f"(d[OFF + 23])
      : "r"(a0), "r"(a1), "r"(a2), "r"(a3), "l"(desc_b), "r"(scale_d), "r"(meta));
}

template <int OFF, int NN>
__device__ __forceinline__ void wg_s56(float (&d)[NN], uint32_t a0, uint32_t a1, uint32_t a2, uint32_t a3,
                                       uint64_t desc_b, int scale_d, uint32_t meta) {
  asm volatile(
      "{\n.reg .pred p;\nsetp.ne.b32 p, %33, 0;\n"
      "wgmma.mma_async.sp.sync.aligned.m64n56k32.f32.bf16.bf16 "
      "{%0,%1,%2,%3,%4,%5,%6,%7,%8,%9,%10,%11,%12,%13,%14,%15,"
      "%16,%17,%18,%19,%20,%21,%22,%23,%24,%25,%26,%27}, "
      "{%28,%29,%30,%31}, %32, %34, 0, p, 1, 1, 0;\n}\n"
      : "+f"(d[OFF + 0]), "+f"(d[OFF + 1]), "+f"(d[OFF + 2]), "+f"(d[OFF + 3]), "+f"(d[OFF + 4]), "+f"(d[OFF + 5]),
        "+f"(d[OFF + 6]), "+f"(d[OFF + 7]), "+f"(d[OFF + 8]), "+f"(d[OFF + 9]), "+f"(d[OFF + 10]), "+f"(d[OFF + 11]),
        "+f"(d[OFF + 12]), "+f"(d[OFF + 13]), "+f"(d[OFF + 14]), "+f"(d[OFF + 15]), "+f"(d[OFF + 16]), "+f"(d[OFF + 17]),
        "+f"(d[OFF + 18]), "+f"(d[OFF + 19]), "+f"(d[OFF + 20]), "+f"(d[OFF + 21]), "+f"(d[OFF + 22]), "+f"(d[OFF + 23]),
        "+f"(d[OFF + 24]), "+f"(d[OFF + 25]), "+f"(d[OFF + 26]), "+f"(d[OFF + 27])
      : "r"(a0), "r"(a1), "r"(a2), "r"(a3), "l"(desc_b), "r"(scale_d), "r"(meta));
}

template <int OFF, int NN>
__device__ __forceinline__ void wg_s56z(float (&d)[NN], uint32_t a0, uint32_t a1, uint32_t a2, uint32_t a3,
                                       uint64_t desc_b, int scale_d, uint32_t meta) {
  asm volatile(
      "{\n.reg .pred p;\nsetp.ne.b32 p, %33, 0;\n"
      "wgmma.mma_async.sp.sync.aligned.m64n56k32.f32.bf16.bf16 "
      "{%0,%1,%2,%3,%4,%5,%6,%7,%8,%9,%10,%11,%12,%13,%14,%15,"
      "%16,%17,%18,%19,%20,%21,%22,%23,%24,%25,%26,%27}, "
      "{%28,%29,%30,%31}, %32, %34, 0, p, 1, 1, 0;\n}\n"
      : "=f"(d[OFF + 0]), "=f"(d[OFF + 1]), "=f"(d[OFF + 2]), "=f"(d[OFF + 3]), "=f"(d[OFF + 4]), "=f"(d[OFF + 5]),
        "=f"(d[OFF + 6]), "=f"(d[OFF + 7]), "=f"(d[OFF + 8]), "=f"(d[OFF + 9]), "=f"(d[OFF + 10]), "=f"(d[OFF + 11]),
        "=f"(d[OFF + 12]), "=f"(d[OFF + 13]), "=f"(d[OFF + 14]), "=f"(d[OFF + 15]), "=f"(d[OFF + 16]), "=f"(d[OFF + 17]),
        "=f"(d[OFF + 18]), "=f"(d[OFF + 19]), "=f"(d[OFF + 20]), "=f"(d[OFF + 21]), "=f"(d[OFF + 22]), "=f"(d[OFF + 23]),
        "=f"(d[OFF + 24]), "=f"(d[OFF + 25]), "=f"(d[OFF + 26]), "=f"(d[OFF + 27])
      : "r"(a0), "r"(a1), "r"(a2), "r"(a3), "l"(desc_b), "r"(scale_d), "r"(meta));
}

template <int OFF, int NN>
__device__ __forceinline__ void wg_s64t(float (&d)[NN], uint32_t a0, uint32_t a1, uint32_t a2, uint32_t a3,
                                       uint64_t desc_b, int scale_d, uint32_t meta) {
  asm volatile(
      "{\n.reg .pred p;\nsetp.ne.b32 p, %37, 0;\n"
      "wgmma.mma_async.sp.sync.aligned.m64n64k32.f32.bf16.bf16 "
      "{%0,%1,%2,%3,%4,%5,%6,%7,%8,%9,%10,%11,%12,%13,%14,%15,"
      "%16,%17,%18,%19,%20,%21,%22,%23,%24,%25,%26,%27,%28,%29,%30,%31}, "
      "{%32,%33,%34,%35}, %36, %38, 0, p, 1, 1, 1;\n}\n"
      : "+f"(d[OFF + 0]), "+f"(d[OFF + 1]), "+f"(d[OFF + 2]), "+f"(d[OFF + 3]), "+f"(d[OFF + 4]), "+f"(d[OFF + 5]),
        "+f"(d[OFF + 6]), "+f"(d[OFF + 7]), "+f"(d[OFF + 8]), "+f"(d[OFF + 9]), "+f"(d[OFF + 10]), "+f"(d[OFF + 11]),
        "+f"(d[OFF + 12]), "+f"(d[OFF + 13]), "+f"(d[OFF + 14]), "+f"(d[OFF + 15]), "+f"(d[OFF + 16]), "+f"(d[OFF + 17]),
        "+f"(d[OFF + 18]), "+f"(d[OFF + 19]), "+f"(d[OFF + 20]), "+f"(d[OFF + 21]), "+f"(d[OFF + 22]), "+f"(d[OFF + 23]),
        "+f"(d[OFF + 24]), "+f"(d[OFF + 25]), "+f"(d[OFF + 26]), "+f"(d[OFF + 27]), "+f"(d[OFF + 28]), "+f"(d[OFF + 29]),
        "+f"(d[OFF + 30]), "+f"(d[OFF + 31])
      : "r"(a0), "r"(a1), "r"(a2), "r"(a3), "l"(desc_b), "r"(scale_d), "r"(meta));
}

template <int OFF, int NN>
__device__ __forceinline__ void wg_s64t1(float (&d)[NN], uint32_t a0, uint32_t a1, uint32_t a2, uint32_t a3,
                                       uint64_t desc_b, int scale_d, uint32_t meta) {
  asm volatile(
      "{\n.reg .pred p;\nsetp.ne.b32 p, %37, 0;\n"
      "wgmma.mma_async.sp.sync.aligned.m64n64k32.f32.bf16.bf16 "
      "{%0,%1,%2,%3,%4,%5,%6,%7,%8,%9,%10,%11,%12,%13,%14,%15,"
      "%16,%17,%18,%19,%20,%21,%22,%23,%24,%25,%26,%27,%28,%29,%30,%31}, "
      "{%32,%33,%34,%35}, %36, %38, 1, p, 1, 1, 1;\n}\n"
      : "+f"(d[OFF + 0]), "+f"(d[OFF + 1]), "+f"(d[OFF + 2]), "+f"(d[OFF + 3]), "+f"(d[OFF + 4]), "+f"(d[OFF + 5]),
        "+f"(d[OFF + 6]), "+f"(d[OFF + 7]), "+f"(d[OFF + 8]), "+f"(d[OFF + 9]), "+f"(d[OFF + 10]), "+f"(d[OFF + 11]),
        "+f"(d[OFF + 12]), "+f"(d[OFF + 13]), "+f"(d[OFF + 14]), "+f"(d[OFF + 15]), "+f"(d[OFF + 16]), "+f"(d[OFF + 17]),
        "+f"(d[OFF + 18]), "+f"(d[OFF + 19]), "+f"(d[OFF + 20]), "+f"(d[OFF + 21]), "+f"(d[OFF + 22]), "+f"(d[OFF + 23]),
        "+f"(d[OFF + 24]), "+f"(d[OFF + 25]), "+f"(d[OFF + 26]), "+f"(d[OFF + 27]), "+f"(d[OFF + 28]), "+f"(d[OFF + 29]),
        "+f"(d[OFF + 30]), "+f"(d[OFF + 31])
      : "r"(a0), "r"(a1), "r"(a2), "r"(a3), "l"(desc_b), "r"(scale_d), "r"(meta));
}

template <int OFF, int NN>
__device__ __forceinline__ void wg_s64tz(float (&d)[NN], uint32_t a0, uint32_t a1, uint32_t a2, uint32_t a3,
                                       uint64_t desc_b, int scale_d, uint32_t meta) {
  asm volatile(
      "{\n.reg .pred p;\nsetp.ne.b32 p, %37, 0;\n"
      "wgmma.mma_async.sp.sync.aligned.m64n64k32.f32.bf16.bf16 "
      "{%0,%1,%2,%3,%4,%5,%6,%7,%8,%9,%10,%11,%12,%13,%14,%15,"
      "%16,%17,%18,%19,%20,%21,%22,%23,%24,%25,%26,%27,%28,%29,%30,%31}, "
      "{%32,%33,%34,%35}, %36, %38, 0, p, 1, 1, 1;\n}\n"
      : "=f"(d[OFF + 0]), "=f"(d[OFF + 1]), "=f"(d[OFF + 2]), "=f"(d[OFF + 3]), "=f"(d[OFF + 4]), "=f"(d[OFF + 5]),
        "=f"(d[OFF + 6]), "=f"(d[OFF + 7]), "=f"(d[OFF + 8]), "=f"(d[OFF + 9]), "=f"(d[OFF + 10]), "=f"(d[OFF + 11]),
        "=f"(d[OFF + 12]), "=f"(d[OFF + 13]), "=f"(d[OFF + 14]), "=f"(d[OFF + 15]), "=f"(d[OFF + 16]), "=f"(d[OFF + 17]),
        "=f"(d[OFF + 18]), "=f"(d[OFF + 19]), "=f"(d[OFF + 20]), "=f"(d[OFF + 21]), "=f"(d[OFF + 22]), "=f"(d[OFF + 23]),
        "=f"(d[OFF + 24]), "=f"(d[OFF + 25]), "=f"(d[OFF + 26]), "=f"(d[OFF + 27]), "=f"(d[OFF + 28]), "=f"(d[OFF + 29]),
        "=f"(d[OFF + 30]), "=f"(d[OFF + 31])
      : "r"(a0), "r"(a1), "r"(a2), "r"(a3), "l"(desc_b), "r"(scale_d), "r"(meta));
}

__device__ __forceinline__ int g2_inv(int ch) { return 32 * (ch >> 5) + 8 * ((ch >> 1) & 3) + 2 * ((ch >> 3) & 3) + (ch & 1); }
__host__ __device__ __forceinline__ uint32_t wimg_off(int n, int k) {
  return (uint32_t)(k >> 6) * kWChunk + (uint32_t)n * 128 + (uint32_t)((((k & 63) >> 3) ^ (n & 7)) << 4) + (k & 7) * 2;
}
__host__ __device__ constexpr int w2piece(int h, int c) { return c == 2 ? 2 + h : 4 * h + c; }
__device__ __forceinline__ uint32_t w2img_off(int n, int k) { return wimg_off(n % 96, k & 63) + w2piece(n >= 96, k >> 6) * (kWChunk / 2); }
__device__ __forceinline__ int qpix(int par, int t) {
  const int a = 2 * t + 13 * par - 6, b = t + 112 * par;
  return par ? min(a, b) : max(a, b);
}
__device__ __forceinline__ int woff(int par, int i, int r) {
  const int a = 99 * par + 6 - 8 * i;
  return par ? min(r, a) : max(r, a);
}

__device__ __forceinline__ void mma16816(float (&c)[4], uint32_t a0, uint32_t a1, uint32_t a2, uint32_t a3, uint32_t b0,
                                         uint32_t b1) {
  asm volatile(
      "mma.sync.aligned.m16n8k16.row.col.f32.bf16.bf16.f32 {%0,%1,%2,%3}, {%4,%5,%6,%7}, {%8,%9}, {%0,%1,%2,%3};"
      : "+f"(c[0]), "+f"(c[1]), "+f"(c[2]), "+f"(c[3])
      : "r"(a0), "r"(a1), "r"(a2), "r"(a3), "r"(b0), "r"(b1));
}

__device__ __forceinline__ void fold_w1(const int u, const __nv_bfloat16* __restrict__ wqkv, uint8_t* wimg) {
  const int g = (threadIdx.x >> 2) & 7, l = threadIdx.x & 3;
  const int m0 = (u / 12) * 16, s = u % 12;
  uint4 A[12], B[12];
  const __nv_bfloat16* arow = wqkv + (m0 + 4 * (g >> 1) + (g & 1)) * 576 + 192 + 8 * l;
  const __nv_bfloat16* brow = wqkv + (16 * s + 4 * (g >> 1) + (g & 1)) * 576 + 8 * l;
#pragma unroll
  for (int i = 0; i < 12; i++) {
    A[i] = ldg128_nc(arow + (i & 1) * 2 * 576 + 32 * (i >> 1));
    B[i] = ldg128_nc(brow + (i & 1) * 2 * 576 + 32 * (i >> 1));
  }
  sched_fence();
  uint8_t* dst = wimg + wimg_off(m0 + g, 16 * s + 4 * l);
  float acc[4][4];
#pragma unroll
  for (int j = 0; j < 16; j++) acc[j >> 2][j & 3] = 0.f;
#pragma unroll
  for (int i = 0; i < 6; i++) {
    const uint4 &a0 = A[2 * i], &a1 = A[2 * i + 1];
#pragma unroll
    for (int nb = 0; nb < 2; nb++) {
      mma16816(acc[2 * nb], a0.x, a1.x, a0.y, a1.y, B[2 * i + nb].x, B[2 * i + nb].y);
      mma16816(acc[2 * nb + 1], a0.z, a1.z, a0.w, a1.w, B[2 * i + nb].z, B[2 * i + nb].w);
    }
  }
#pragma unroll
  for (int j = 0; j < 2; j++) {
    const uint2 v = make_uint2(pack_bf16((acc[0][2 * j] + acc[1][2 * j]) * kAlpha, (acc[0][2 * j + 1] + acc[1][2 * j + 1]) * kAlpha),
                               pack_bf16((acc[2][2 * j] + acc[3][2 * j]) * kAlpha, (acc[2][2 * j + 1] + acc[3][2 * j + 1]) * kAlpha));
    asm volatile("st.relaxed.gpu.global.v2.u32 [%0], {%1,%2};" ::"l"(dst + j * 1024), "r"(v.x), "r"(v.y) : "memory");
  }
}
__device__ __forceinline__ void fold_w2(const int u, const __nv_bfloat16* __restrict__ wqkv, const __nv_bfloat16* __restrict__ wo,
                                        uint8_t* wimg) {
  const int g = (threadIdx.x >> 2) & 7, l = threadIdx.x & 3;
  const int m0 = (u / 12) * 32, n0 = (u % 12) * 16;
  uint4 S[12];
  uint32_t L[96];
  const __nv_bfloat16* brow = wqkv + (n0 + 4 * (g >> 1) + (g & 1)) * 576 + 384 + 8 * l;
#pragma unroll
  for (int i = 0; i < 12; i++) S[i] = ldg128_nc(brow + (i & 1) * 2 * 576 + 32 * (i >> 1));
  const __nv_bfloat16* acol = wo + (8 * l) * 192 + m0 + 4 * g;
#pragma unroll
  for (int c = 0; c < 48; c++)
    asm volatile("ld.global.nc.v2.u32 {%0,%1}, [%2];" : "=r"(L[2 * c]), "=r"(L[2 * c + 1]) : "l"(acol + (32 * (c >> 3) + (c & 7)) * 192));
  const uint32_t off = w2_offset();
  sched_fence();
  uint8_t* img = wimg + off;
  float acc[4][4];
#pragma unroll
  for (int j = 0; j < 16; j++) acc[j >> 2][j & 3] = 0.f;
#pragma unroll
  for (int i = 0; i < 6; i++) {
#pragma unroll
    for (int h = 0; h < 2; h++) {
      const uint4 &s0 = S[2 * i], &s1 = S[2 * i + 1];
#pragma unroll
      for (int mt = 0; mt < 2; mt++) {
        const uint32_t* a = L + 16 * i + 8 * h + mt;
        const uint32_t a0 = __byte_perm(a[0], a[2], 0x5410), a1 = __byte_perm(a[0], a[2], 0x7632);
        const uint32_t a2 = __byte_perm(a[4], a[6], 0x5410), a3 = __byte_perm(a[4], a[6], 0x7632);
        mma16816(acc[2 * mt], a0, a1, a2, a3, h ? s0.z : s0.x, h ? s0.w : s0.y);
        mma16816(acc[2 * mt + 1], a0, a1, a2, a3, h ? s1.z : s1.x, h ? s1.w : s1.y);
      }
    }
  }
#pragma unroll
  for (int j = 0; j < 4; j++) {
    const float(&c0)[4] = acc[j & 2];
    const float(&c1)[4] = acc[(j & 2) + 1];
    asm volatile("st.relaxed.gpu.global.v2.u32 [%0], {%1,%2};" ::"l"(img + w2img_off(g2_inv(m0 + 4 * g + j), n0 + 4 * l)),
                 "r"(pack_bf16(c0[2 * (j & 1)], c0[2 * (j & 1) + 1])), "r"(pack_bf16(c1[2 * (j & 1)], c1[2 * (j & 1) + 1])) : "memory");
  }
}

__global__ void __launch_bounds__(256) fold_kernel(const __nv_bfloat16* __restrict__ wqkv,
                                                   const __nv_bfloat16* __restrict__ wo, uint8_t* wimg) {
  const int u = blockIdx.x * 8 + (threadIdx.x >> 5);
  if (u < 144) fold_w1(u, wqkv, wimg);
  else fold_w2(u - 144, wqkv, wo, wimg);
}

struct TileCoord { int pr, pc, I, J, up, kind; };
struct TileTable { uint16_t e[kCtas * 6], g[6][8][2]; };
inline void make_tiles(TileTable& tt) {
  for (int tile = 0; tile < kCtas * 6; tile++) {
    const int b = tile / 6, k = tile - 6 * b;
    const int p = b < 128 ? (tile - 672) >> 1 : b - 80;
    const int strip = b < 112 ? b >> 1 : b >= 128 && k >= 2 ? (b & 1) * 27 + (b & 2) * 14 : p + (p < 26 ? 1 : 3);
    const int pr = strip >= 28, J = (strip - pr * 28) >> 1, pc = strip & 1, up = b < 112 ? b & 1 : pr;
    const int first = b < 112 ? 8 - 2 * pr - up : 13 * pr, step = b < 112 ? k : k & 1;
    const int I = up ? first - step : first + step;
    const int kind = b < 112 ? (J == 13 * pc ? 1 + pc : 0) : I == 13 * pr ? 4 + pr : b >= 128 && k >= 2 ? 3 : 0;
    tt.e[tile] = (uint16_t)(I | J << 4 | pr << 8 | pc << 9 | up << 10 | kind << 11);
  }
  for (int kind = 0; kind < 6; kind++)
    for (int j = 0; j < 8; j++) {
      const int w = j >> 1, h = j & 1, e = kind % 3;
      auto off = [e](int t) { return e == 0 ? 2 * t : e == 1 ? t + (t == 7) : t + (t > 0); };
      tt.g[kind][j][0] = (uint16_t)(kind < 3 ? 3 * off(w + 4 * h) : 3 * (kW * off(2 * w) + 8 * h));
      tt.g[kind][j][1] = (uint16_t)(128 * (kind < 3 ? kind > 0 : 1 + off(2 * w + 1) - off(2 * w)));
    }
}
__device__ __forceinline__ int num_tiles() { return blockIdx.x < 128 ? 6 : 4; }
__device__ __forceinline__ TileCoord decode_tile(const TileTable& tt, int tile) {
  const uint32_t e = tt.e[tile];
  return TileCoord{(int)(e >> 8) & 1, (int)(e >> 9) & 1, (int)e & 15, (int)(e >> 4) & 15, (int)(e >> 10) & 1, (int)(e >> 11)};
}
__device__ __forceinline__ int halo_r0(const TileCoord& t) { return 8 * t.I + 6 * t.pr - 6; }
__device__ __forceinline__ int halo_c0(const TileCoord& t) { return min(max(8 * t.J + 6 * t.pc - 6, -3), 102); }

__device__ __forceinline__ uint32_t bar_full(uint32_t bars, int wg, int c) { return bars + (wg * 3 + c) * 8; }
__device__ __forceinline__ uint32_t bar_w1c(uint32_t bars, int c) { return bars + (6 + c) * 8; }
__device__ __forceinline__ uint32_t bar_w2(uint32_t bars) { return bars + 9 * 8; }
__device__ __forceinline__ uint32_t bar_x(uint32_t bars, int j) { return bars + (10 + j) * 8; }
__device__ __forceinline__ uint32_t bar_w1q(uint32_t bars) { return bars + 12 * 8; }
__device__ __forceinline__ uint32_t bar_xf(uint32_t bars) { return bars + 13 * 8; }
__device__ __forceinline__ uint32_t bar_w2m(uint32_t bars) { return bars + 14 * 8; }
__device__ __forceinline__ uint32_t bar_redo(uint32_t bars) { return bars + 15 * 8; }
__device__ __forceinline__ uint32_t bar_wok(uint32_t bars) { return bars + 16 * 8; }
__device__ __forceinline__ uint32_t bar_go(uint32_t bars) { return bars + 17 * 8; }
__device__ __forceinline__ uint32_t bar_raw(uint32_t bars, int j = 0) { return bars + (21 + j) * 8; }
__device__ __forceinline__ uint32_t bar_w2a(uint32_t bars) { return bars + 20 * 8; }
constexpr int kNumBars = 22;

__device__ __forceinline__ uint64_t wdesc(uint64_t d0, int s) { return d0 + (((s >> 2) * kWChunk + (s & 3) * 32) >> 4); }

__device__ __forceinline__ uint32_t out_slot(int k, int nt) { return k + 1 < nt ? kW2Off + (~k & 1) * 2 * kWChunk : kW1Off + kWChunk; }
__device__ __forceinline__ bool edge_strip() {
  const int s = blockIdx.x >> 1;
  return s == 0 || s == 27 || s == 28 || s == 55;
}
template <int I0, int I1>
__device__ __forceinline__ void store_rows(bool on, __nv_bfloat16* pA, __nv_bfloat16* pB, const uint32_t (&a)[24], const uint32_t (&b)[24]) {
#pragma unroll
  for (int i = 2 * I0; i < 2 * I1; i++) {
    const uint32_t* v = (i & 1 ? b : a) + 4 * (i >> 1);
    asm volatile("{\n.reg .pred p;\nsetp.ne.u32 p, %5, 0;\n@p st.global.v4.u32 [%0], {%1,%2,%3,%4};\n}\n" ::"l"((i & 1 ? pB : pA) + 32 * (i >> 1)),
                 "r"(v[0]), "r"(v[1]), "r"(v[2]), "r"(v[3]), "r"((uint32_t)on) : "memory");
  }
}
template <int I0, int I1>
__device__ __forceinline__ void stage_out(uint32_t sts, int wg, const uint32_t (&a)[24], const uint32_t (&b)[24]) {
  const uint32_t e = sts, o = sts ^ 64;
  const uint32_t ad[4] = {wg ? o + 1024 : e, wg ? e + 2048 : o, wg ? e : o + 1024, wg ? o : e + 2048};
#pragma unroll
  for (int i = I0; i < I1; i++) {
    const uint32_t* v = (i < 6 ? a : b) + 4 * (i % 6);
    asm volatile("st.shared.v4.u32 [%0], {%1,%2,%3,%4};" ::"r"(ad[i % 6 / 3 * 2 + (i % 3 == 1)] + (i % 3 == 2) * 1024 + (i / 6) * 12288),
                 "r"(v[0]), "r"(v[1]), "r"(v[2]), "r"(v[3]) : "memory");
  }
}
__device__ __forceinline__ uint32_t now_ns() {
  uint32_t t;
  asm volatile("mov.u32 %0, %globaltimer_lo;" : "=r"(t)::"memory");
  return t;
}
__device__ __forceinline__ void wait_clock(uint32_t t_start, uint32_t t) {
  while (now_ns() - t_start < t) { }
}
#define NAT_PRED(f, m) ".reg .pred p;\n.reg .b32 t;\nand.b32 t, " f ", " m ";\nsetp.ne.u32 p, t, 0;\n"
constexpr uint32_t kHiV = 1, kHiU = 8, kColB = 0x20, kInV = 0x100, kInU = 0x1000, kColA = 0x10000;
template <uint32_t M>
__device__ __forceinline__ float pick(const float* a, const float* b, uint32_t f) {
  float d;
  asm("{\n" NAT_PRED("%5", "%6") "add.f32 %0, %1, %2;\n@p add.f32 %0, %3, %4;\n}\n"
      : "=&f"(d) : "f"(a[0]), "f"(a[2]), "f"(b[0]), "f"(b[2]), "r"(f), "n"(M));
  return d;
}
template <uint32_t M>
__device__ __forceinline__ float sel(float a, float b, uint32_t f) {
  float d;
  asm("{\n" NAT_PRED("%3", "%4") "selp.f32 %0, %1, %2, p;\n}\n" : "=f"(d) : "f"(a), "f"(b), "r"(f), "n"(M));
  return d;
}
template <uint32_t M>
__device__ __forceinline__ void max_if(float& m, float v, uint32_t f) {
  asm("{\n" NAT_PRED("%2", "%3") "@p max.f32 %0, %0, %1;\n}\n" : "+f"(m) : "f"(v), "r"(f), "n"(M));
}
template <uint32_t M>
__device__ __forceinline__ void add_if(float& m, float v, uint32_t f) {
  asm("{\n" NAT_PRED("%2", "%3") "@p add.f32 %0, %0, %1;\n}\n" : "+f"(m) : "f"(v), "r"(f), "n"(M));
}
__device__ __forceinline__ void pick_v(const float* a, float* v, uint32_t f) {
  v[0] = pick<kHiV>(a, a + 16, f), v[1] = pick<kHiV>(a + 1, a + 17, f);
  v[2] = pick<kHiV * 2>(a + 4, a + 20, f), v[3] = pick<kHiV * 2>(a + 5, a + 21, f);
  v[4] = pick<kHiV * 4>(a + 8, a + 24, f), v[5] = pick<kHiV * 4>(a + 9, a + 25, f);
  v[6] = a[12] + a[14], v[7] = a[13] + a[15];
}
__device__ __forceinline__ void pick_u(const float* a, float* v, uint32_t f) {
#pragma unroll
  for (int c = 0; c < 3; c++) v[2 * c] = pick<kHiU>(a + 4 * c, a + 4 * c + 12, f), v[2 * c + 1] = pick<kHiU * 2>(a + 4 * c + 1, a + 4 * c + 13, f);
}
__device__ __forceinline__ uint32_t sign_bytes(uint32_t v, uint32_t sel) {
  uint32_t d;
  asm("prmt.b32 %0, %1, %1, %2;" : "=r"(d) : "r"(v), "r"(sel));
  return d;
}
__device__ __forceinline__ float own_max(const float (&v)[14], uint32_t f) {
  float m = sel<kInV>(fmaxf(v[0], v[1]), -INFINITY, f), m2 = sel<kInV * 2>(fmaxf(v[2], v[3]), -INFINITY, f);
  max_if<kInV * 4>(m, fmaxf(v[4], v[5]), f);
  max_if<kInV * 8>(m2, fmaxf(v[6], v[7]), f);
  max_if<kInU>(m, fmaxf(fmaxf(v[8], v[10]), v[12]), f);
  max_if<kInU * 2>(m2, fmaxf(fmaxf(v[9], v[11]), v[13]), f);
  return fmaxf(m, m2);
}
__device__ __forceinline__ float quad_max(float m) {
  const float a = __shfl_xor_sync(0xffffffffu, m, 1), b = __shfl_xor_sync(0xffffffffu, m, 2), c = __shfl_xor_sync(0xffffffffu, m, 3);
  return fmaxf(fmaxf(m, a), fmaxf(b, c));
}
__device__ __forceinline__ float row_rcp(const float (&v)[14], uint32_t f) {
  float s = sel<kInV>(v[0] + v[1], 0.f, f), s2 = sel<kInV * 2>(v[2] + v[3], 0.f, f);
  add_if<kInV * 4>(s, v[4] + v[5], f);
  add_if<kInV * 8>(s2, v[6] + v[7], f);
  add_if<kInU>(s, v[8] + v[10] + v[12], f);
  add_if<kInU * 2>(s2, v[9] + v[11] + v[13], f);
  s += s2;
  const float a = __shfl_xor_sync(0xffffffffu, s, 1), b = __shfl_xor_sync(0xffffffffu, s, 2), c = __shfl_xor_sync(0xffffffffu, s, 3);
  return rcp_approx((s + a) + (b + c));
}
__device__ __forceinline__ void route(const float (&v)[14], float s, const uint32_t (&rt)[9], uint32_t (&p)[14]) {
#pragma unroll
  for (int i = 0; i < 7; i++) {
    const uint32_t u = pack_bf16(v[2 * i] * s, v[2 * i + 1] * s);
    if (i < 4) p[i] = u & rt[i];
    if (i < 3) p[i + 4] = u & rt[i + 4];
    if (i >= 4) {
      p[i + 3] = u & rt[7];
      p[i + 6] = u & rt[8];
    }
  }
}

template <int C, int T0 = 0, int T1 = 7>
__device__ __forceinline__ void pv_chunk(float (&z)[32], const uint32_t (&pa)[14], const uint32_t (&pb)[14],
                                         const uint32_t (&meta)[4], uint64_t dV) {
#pragma unroll
  for (int t = T0; t < T1; t++) {
    if (t & 1)
      wg_s64t1<0, 32>(z, pa[2 * t], pb[2 * t], pa[2 * t + 1], pb[2 * t + 1], dV + ((2 * C * kChunkBytes + t * 2048) >> 4), 1,
                      meta[t >> 1]);
    else if (t > 0)
      wg_s64t<0, 32>(z, pa[2 * t], pb[2 * t], pa[2 * t + 1], pb[2 * t + 1], dV + ((2 * C * kChunkBytes + t * 2048) >> 4), 1,
                     meta[t >> 1]);
    else
      wg_s64tz<0, 32>(z, pa[0], pb[0], pa[1], pb[1], dV + ((2 * C * kChunkBytes) >> 4), 0, meta[0]);
  }
}
template <int C>
__device__ __forceinline__ void pack_z(const float (&z)[32], uint32_t (&za)[24], uint32_t (&zb)[24]) {
#pragma unroll
  for (int j = 0; j < 8; j++) {
    za[8 * C + j] = pack_bf16(z[4 * j], z[4 * j + 1]);
    zb[8 * C + j] = pack_bf16(z[4 * j + 2], z[4 * j + 3]);
  }
}

template <int H>
__device__ __forceinline__ void pack_out(const float (&ac)[48], uint32_t (&oa)[24], uint32_t (&ob)[24]) {
#pragma unroll
  for (int j = 0; j < 12; j++) {
    oa[12 * H + j] = pack_bf16(ac[4 * j], ac[4 * j + 1]);
    ob[12 * H + j] = pack_bf16(ac[4 * j + 2], ac[4 * j + 3]);
  }
}
struct Maps { CUtensorMap v6, v2, v14, u8, px[8], wv, wo; };
__device__ __forceinline__ void tma_prefetch_5d(const CUtensorMap* map, int c0, int c1, int c2, int c3, int c4) {
  asm volatile("cp.async.bulk.prefetch.tensor.5d.L2.global.tile [%0, {%1, %2, %3, %4, %5}];" ::"l"((uint64_t)map), "r"(c0), "r"(c1),
               "r"(c2), "r"(c3), "r"(c4) : "memory");
}
__device__ __forceinline__ int first_line(const TileCoord tc) { return 3 * (qpix(tc.pr, 8 * tc.I) * kW + qpix(tc.pc, 8 * tc.J)); }
template <int MODE, int UNROLL, int N = 8>
__device__ __forceinline__ void move_px(const Maps& tm, const TileTable& tt, uint32_t buf, uint32_t bar, int line, int kind, int i0 = 0) {
#pragma unroll UNROLL
  for (int n = 0; n < N; n++) {
    const int i = i0 + n;
    const int j = MODE == 2 ? 2 * (i & 3) + (i >> 2) : i;
    if (MODE == 2 || (n & 1) == 0 || kind != 0) {
      const CUtensorMap* map = (const CUtensorMap*)((const char*)(tm.px + (MODE & 2) * 2) + tt.g[kind][j][1]);
      const int ln = line + tt.g[kind][j][0];
      if (MODE == 0) tma_load_5d(buf + i * 3072, map, bar, 0, 0, 0, 0, ln);
      if (MODE == 1) tma_prefetch_5d(map, 0, 0, 0, 0, ln);
      if (MODE == 2)
        asm volatile("cp.async.bulk.tensor.5d.global.shared::cta.tile.bulk_group [%0, {%2, %2, %2, %2, %3}], [%1];" ::"l"((uint64_t)map),
                     "r"(buf + i * 3072), "r"(0), "r"(ln) : "memory");
      if (MODE == 2 && NAT_SP < 9) {
        asm volatile("cp.async.bulk.commit_group;" ::: "memory");
        asm volatile("cp.async.bulk.wait_group.read %0;" ::"n"(NAT_SP) : "memory");
      }
    }
  }
  if (MODE == 2) asm volatile("cp.async.bulk.commit_group;" ::: "memory");
}
__device__ __noinline__ bool refetch(uint32_t base, const uint8_t* src, bool gap) {
  constexpr uint32_t bars = 1024 + kBarOff, cnt = bars + 192;
#pragma unroll 1
  for (uint32_t o = 0; o < kWBytes && !gap; o += 2048) {
    uint32_t mx = 0;
#pragma unroll
    for (int i = 0; i < 4; i++) {
      uint4 v;
      asm volatile("ld.shared.v4.u32 {%0,%1,%2,%3}, [%4];" : "=r"(v.x), "=r"(v.y), "=r"(v.z), "=r"(v.w)
                   : "r"(base + o + i * 512 + (threadIdx.x & 31) * 16));
      mx = __vimax3_u32(__vimax3_u32(mx, v.x, v.y), v.z, v.w);
    }
    gap = __any_sync(0xffffffffu, mx == kEmpty);
  }
  uint32_t n;
  asm volatile("ld.shared.u32 %0, [%1];" : "=r"(n) : "r"(cnt) : "memory");
  if (!gap || __any_sync(0xffffffffu, n > (1u << 12))) return false;
  asm volatile("bar.sync 15, 128;" ::: "memory");
  if (threadIdx.x == 0) {
    asm volatile("st.shared.u32 [%0], %1;" ::"r"(cnt), "r"(n + 1) : "memory");
    mbar_arrive_expect_tx(bar_redo(bars), kWBytes);
    bulk_load(base, src, kWBytes, bar_redo(bars));
  }
  __syncwarp();
  mbar_wait(bar_redo(bars), n & 1);
  return true;
}
template <int S0, int S1, int Z>
__device__ __forceinline__ void g2_steps(float (&ac)[48], const uint32_t (&za)[24], const uint32_t (&zb)[24], uint64_t d) {
#pragma unroll
  for (int s = S0; s < S1; s++) {
    const uint64_t ds = d + (((s >> 2 & 1) * (kWChunk / 2) + (s & 3) * 32) >> 4);
    if (s == Z) wg_d96z<0, 48>(ac, za[2 * s], zb[2 * s], za[2 * s + 1], zb[2 * s + 1], ds, 0);
    else wg_d96<0, 48>(ac, za[2 * s], zb[2 * s], za[2 * s + 1], zb[2 * s + 1], ds, 1);
  }
}

__device__ __forceinline__ void consumer(const int wg, __nv_bfloat16* out, const uint8_t* wimg, const uint32_t sbase,
                                         const uint32_t zero, const Maps& tm, const TileTable& tt) {
  const int tid = threadIdx.x & 127;
  const int w = __shfl_sync(0xffffffffu, tid >> 5, 0), lane = tid & 31;
  const uint64_t dK = make_desc(sbase, 16, 1024);
  const uint64_t dV = make_desc(sbase, kChunkBytes, 512, 2);
  const uint64_t dW1 = make_desc(sbase + kW1Off, 16, 1024);
  const uint64_t dX0 = make_desc(sbase + kW2Off + wg * 2 * kWChunk, 16, 1024), dY0 = make_desc(sbase + kW2Off + (1 - wg) * 2 * kWChunk, 16, 1024);
  const uint64_t dX2 = make_desc(sbase + kXOff + wg * (kWChunk / 2), 16, 1024), dY2 = make_desc(sbase + kXOff + (1 - wg) * (kWChunk / 2), 16, 1024);
  const uint32_t bars = sbase + kBarOff;
  int tile0 = blockIdx.x * kTilesPerCta;
  asm volatile("" : "+r"(tile0));
  const int nt = num_tiles();

  uint32_t pix = 0, geo[12] = {};
  const int l = lane & 3;
#pragma unroll 1
  for (int j = 4; j >= 0; j -= 2) {
    const TileCoord tc = decode_tile(tt, tile0 + wg + j);
    const int g = tc.kind < 3 ? lane >> 2 : 2 * w + ((lane >> 2) & 1), qc = tc.kind < 3 ? w : lane >> 3;
    const uint32_t pr = qpix(tc.pr, 8 * tc.I + g) * kW;
    if (j == nt - 2) pix = (pr + qpix(tc.pc, 8 * tc.J + qc)) | (pr + qpix(tc.pc, 8 * tc.J + qc + 4)) << 16;
    const int d = 8 * tc.J + 6 * tc.pc - 6 - halo_c0(tc);
    const int ro = woff(tc.pr, tc.I, g), coA = woff(tc.pc, tc.J, qc) + d, coB = woff(tc.pc, tc.J, qc + 4) + d - 3;
#pragma unroll
    for (int i = 11; i >= 4; i--) geo[i] = geo[i - 4];
    const uint32_t lr = 0x1FCu << ro;
    const uint32_t lv = lr >> (2 + (l >> 1)), lu = lr >> (2 * l + 2 * tc.up);
    const uint32_t t = __byte_perm(lv, lu, wg ? 0x4501 : 0x5410);
    geo[0] = ((t & 0x15u) | (lv & 0x40u)) * 0x02082080u;
    geo[1] = ((t >> 8) & 0x15u) * 0x02082080u;
    geo[2] = __byte_perm(t << 7, t << 6, 0x7362);
    const int dr = (ro - 1) & 7;
    const uint32_t hiv = (((1u << ((ro - (l >> 1) + 1) >> 1)) - 1u) ^ (wg ? 7u : 0u)) & 7u, hiu = (t >> 24) & 3u;
    const uint32_t ca = (1u << coA) - 1u;
    geo[3] = hiv * kHiV | hiu * kHiU | ((((1u << coB) - 1u) >> (2 * (l & 1))) & 3u) * kColB |
             (15u & ~((uint32_t)((dr & 1) == (l >> 1)) << (dr >> 1))) * kInV | ((t >> 16 | t >> 24) & 3u) * kInU | ca * kColA |
             (ca >> ((0x49 >> (2 * l)) & 3) & 1u) << 19 | (uint32_t)(l == 3) << 20 | (0x55u & ((1u << (2 * coB)) - 1u)) << 24;
  }
  keep_regs(geo);
  const int so = (lane >> 3) | (lane & 4);
  uint32_t sts = sbase + w * 3072 + so * 128 + (((lane & 3) ^ so) << 4);
  __nv_bfloat16* poA = out + 8 * l + (pix & 0xFFFFu) * kC + 96 * wg;
  __nv_bfloat16* poB = out + 8 * l + (pix >> 16) * kC + 96 * wg;
  asm volatile("" : "+l"(poA), "+l"(poB), "+r"(sts));
  uint32_t oa[24], ob[24];
#pragma unroll
  for (int j = 0; j < 24; j++) oa[j] = ob[j] = 0u;
  keep_regs(oa);
  keep_regs(ob);
  PROF(wg, 0);
  if (threadIdx.x == 0) GT(1);

  for (int k = wg; k < nt; k += 2) {
    const uint32_t ph = (k >> 1) & 1;
    const int it = k >> 1;
    uint32_t qa[24], qb[24], hok[3];
    uint32_t fl = geo[3];
    {
      float acc[96];
      const uint64_t dX = make_desc(sbase + kXOff + (k == 0 ? kWChunk : 0), 16, 3072);
      if (k > 0) nb_sync(1 + (1 - wg));
      mbar_wait(bar_x(bars, k > 0), (k + (k > 0)) & 1);
      if (k < 2) PROF(wg, 1);
      PROFS(2, wg, 2 + it * 12);
      if (w == 0 && k < 2) GT(20 + wg);
#pragma unroll
      for (int s = 0; s < 12; s++) {
        if ((s & 3) == 0 && k == 0) {
          mbar_wait(bar_w1c(bars, s >> 2), 0);
          PROFS(17, wg, 50 + (s >> 2));
        }
        if ((s & 3) == 0) wg_fence();
        if (s == 0) wg_m192z<0, 96>(acc, dX, dW1, 0);
        else wg_m192<0, 96>(acc, dX + (((s >> 2) * 1024 + (s & 3) * 32) >> 4), wdesc(dW1, s), 1);
      }
      wg_commit();
      PROFS(13, wg, 13 + it * 12);
      wg_wait<0>();
      if (k > 0) nb_arrive_p(6);
      fence_regs(acc);
      PROFS(3, wg, 3 + it * 12);
#pragma unroll
      for (int j = 0; j < 24; j++) {
        qa[j] = pack_bf16(acc[4 * j], acc[4 * j + 1]);
        qb[j] = pack_bf16(acc[4 * j + 2], acc[4 * j + 3]);
      }
      keep_regs(qa);
      keep_regs(qb);
      sched_fence();
      if (k >= 2) {
        const uint32_t dst = sts + out_slot(k, nt);
        nb_sync(11);
        stage_out<0, 6>(dst, wg, oa, ob);
        nb_sync(12);
        stage_out<6, 12>(dst, wg, oa, ob);
      }
#pragma unroll
      for (int c = 0; c < 3; c++) hok[c] = mbar_test(bar_full(bars, wg, c), ph);
      if (k >= 2) {
        fence_proxy_async();
        nb_arrive_p(10);
      }
    }

    float aE[52], aO[24], bO[52], bE[28];
    const uint32_t mq = 0xEEEE4444u | zero;
    PROFS(4, wg, 4 + it * 12);

    mbar_wait_if(hok[0], bar_full(bars, wg, 0), ph);
    PROFS(14, wg, 40 + it * 3);
    if (w == 0 && k < 2) GT(22 + wg);
    if (k > 0) nb_sync(3 + (1 - wg));
    wg_fence();
#pragma unroll
    for (int ks = 0; ks < 6; ks++) {
      if (ks == NAT_P1) {
        mbar_wait_if(hok[1], bar_full(bars, wg, 1), ph);
        PROFS(14, wg, 41 + it * 3);
        wg_fence();
      }
      if (ks == NAT_P2) {
        mbar_wait_if(hok[2], bar_full(bars, wg, 2), ph);
        PROFS(14, wg, 42 + it * 3);
        wg_fence();
      }
      const uint64_t d = dK + ((ks * kChunkBytes) >> 4);
      if (ks == 0) wg_s104z<0, 52>(aE, qa[0], qa[1], qa[2], qa[3], d, 0, mq);
      else wg_s104<0, 52>(aE, qa[4 * ks], qa[4 * ks + 1], qa[4 * ks + 2], qa[4 * ks + 3], d, 1, mq);
    }
    wg_commit();
    wg_s48z<0, 24>(aO, qa[0], qa[1], qa[2], qa[3], dK + ((7 * 1024 + 64) >> 4), 0, mq);
#pragma unroll
    for (int ks = 1; ks < 6; ks++)
      wg_s48<0, 24>(aO, qa[4 * ks], qa[4 * ks + 1], qa[4 * ks + 2], qa[4 * ks + 3], dK + ((ks * kChunkBytes + 7 * 1024 + 64) >> 4), 1, mq);
    wg_commit();
    wg_s56z<0, 28>(bE, qb[0], qb[1], qb[2], qb[3], dK, 0, mq);
#pragma unroll
    for (int ks = 1; ks < 6; ks++) wg_s56<0, 28>(bE, qb[4 * ks], qb[4 * ks + 1], qb[4 * ks + 2], qb[4 * ks + 3], dK + ((ks * kChunkBytes) >> 4), 1, mq);
    wg_commit();
    wg_wait<2>();
    fence_regs(aE);
    PROFS(5, wg, 5 + it * 12);

    uint32_t pa[14], pb[14], meta[4];
    {
      float vA[14], vB[14];
      pick_v(aE, vA, fl);
      pick_u(aE + 28, vA + 8, fl);
      fence_regs(vA);
      if (k == 0) {
        if (__builtin_expect(__any_sync(0xffffffffu, vA[6] != vA[6]), 0)) {
          wg_wait<0>();
          fence_regs(aO);
          fence_regs(bE);
          if (refetch(sbase + kW1Off, wimg, false)) {
#pragma unroll
            for (int j = 0; j < 24; j++) oa[j] = ob[j] = 0u;
            k -= 2;
            continue;
          }
        }
        if (elect_one()) mbar_arrive(bar_xf(bars));
      }
      wg_fence();
      wg_s104z<0, 52>(bO, qb[0], qb[1], qb[2], qb[3], dK + 4, 0, mq);
#pragma unroll
      for (int ks = 1; ks < 6; ks++)
        wg_s104<0, 52>(bO, qb[4 * ks], qb[4 * ks + 1], qb[4 * ks + 2], qb[4 * ks + 3], dK + ((ks * kChunkBytes + 64) >> 4), 1, mq);
      wg_commit();
      if (k + 1 < nt) nb_arrive(1 + wg);
      uint32_t rt[9];
#pragma unroll
      for (int i = 0; i < 7; i++) rt[i] = sign_bytes(geo[i >> 2], 0x8888u + 0x1111u * (i & 3));
      rt[7] = sign_bytes(geo[2], 0x9988u);
      rt[8] = sign_bytes(geo[2], 0xBBAAu);
      keep_regs(rt);
      pa[13] = pb[13] = 0u;
      wg_wait<2>();
      keep_regs(qa);
      fence_regs(aO);
      float oA[6], eB[8];
      pick_u(aO, oA, fl);
      wg_wait<1>();
      fence_regs(bE);
      pick_v(bE, eB, fl);
      vA[8] = sel<kColA>(oA[0], vA[8], fl), vA[9] = sel<kColA>(oA[1], vA[9], fl);
      vA[10] = sel<kColA * 2>(oA[2], vA[10], fl), vA[11] = sel<kColA * 2>(oA[3], vA[11], fl);
      vA[12] = sel<kColA * 4>(oA[4], vA[12], fl), vA[13] = sel<kColA * 4>(oA[5], vA[13], fl);
      {
        const float m1 = __uint_as_float(0x88DD88DDu), m0 = __uint_as_float(0x88DDDD88u);
        meta[0] = 0xDD88DD88u ^ __byte_perm(fl, 0u, 0x3344);
        meta[1] = __float_as_uint(sel<kColA * 16>(sel<kColA>(m1, m0, fl), __uint_as_float(meta[0]), fl));
        meta[2] = __float_as_uint(sel<kColA * 8>(m1, m0, fl));
        meta[3] = __float_as_uint(sel<kColA * 4>(m1, m0, fl));
        keep_regs(meta);
      }
      float mA = own_max(vA, fl);
      fl |= __float_as_uint(eB[7]) & zero;
      fence_regs(eB);
      fence_regs(vA);
      asm volatile("" : "+f"(mA), "+r"(fl));
      sched_fence();
      wg_wait<0>();
      sched_fence();
      keep_regs(qb);
      fence_regs(bO);
      PROFS(6, wg, 6 + it * 12);
      if (w == 0) GT(24 + k);
      mA = quad_max(mA);
#pragma unroll
      for (int i = 0; i < 14; i++) vA[i] = ex2(vA[i] - mA);
      pick_v(bO, vB, fl);
      pick_u(bO + 28, vB + 8, fl);
#pragma unroll
      for (int i = 0; i < 8; i += 2) vB[i] = sel<kColB>(vB[i], eB[i], fl), vB[i + 1] = sel<kColB * 2>(vB[i + 1], eB[i + 1], fl);
      float mB = quad_max(own_max(vB, fl));
      if (NAT_SB) {
        fence_regs(vA);
        fence_regs(vB);
        asm volatile("" : "+f"(mB));
        sched_fence();
      }
      PROFS(7, wg, 7 + it * 12);
#pragma unroll
      for (int i = 0; i < 14; i++) vB[i] = ex2(vB[i] - mB);
      route(vA, row_rcp(vA, fl), rt, pa);
      route(vB, row_rcp(vB, fl), rt, pb);
    }
    PROFS(8, wg, 8 + it * 12);
    if (k == NAT_PK) PROFS(18, wg, 53);
    sched_fence();

    float ac0[48], ac1[48];
    {
      float z0[32], z1[32], z2[32];
      uint32_t za[24], zb[24];
      wg_fence();
      pv_chunk<0>(z0, pa, pb, meta, dV);
      wg_commit();
      pv_chunk<1>(z1, pa, pb, meta, dV);
      wg_commit();
      wg_wait<1>();
      if (k == NAT_PK) PROFS(18, wg, 54);
      if (k + 1 < nt) nb_arrive_p(7);
      pv_chunk<2, 0, 3>(z2, pa, pb, meta, dV);
      wg_commit();
      sched_fence();
      fence_regs(z0);
      pack_z<0>(z0, za, zb);
      sched_fence();
      wg_fence();
      pv_chunk<2, 3, 7>(z2, pa, pb, meta, dV);
      wg_commit();
      wg_wait<2>();
      if (k == NAT_PK) PROFS(19, wg, 55);
      if (k + 1 < nt) nb_arrive_p(8);
      if (k < 2) mbar_wait(k == 1 ? bar_wok(bars) : bar_w2a(bars), 0);
      wg_fence();
      g2_steps<0, 3, 0>(ac0, za, zb, dX0);
      wg_commit();
      sched_fence();
      fence_regs(z1);
      pack_z<1>(z1, za, zb);
      sched_fence();
      wg_fence();
      g2_steps<3, 4, 0>(ac0, za, zb, dX0);
      wg_commit();
      g2_steps<4, 8, 0>(ac0, za, zb, dX0);
      wg_commit();
      wg_wait<3>();
      if (k + 1 < nt) nb_arrive_p(9);
      else nb_arrive(11);
      if (k == NAT_PK) PROFS(20, wg, 56);
      keep_regs(pa);
      keep_regs(pb);
      keep_regs(meta);
      sched_fence();
      const uint32_t mok = mbar_test(bar_w2m(bars), k + 1 < nt ? k & 1 : ~k & 1);
      fence_regs(z2);
      pack_z<2>(z2, za, zb);
      keep_regs(za);
      keep_regs(zb);
      sched_fence();
      PROFS(9, wg, 9 + it * 12);
      wg_wait<1>();
      if (k > 0 && k + 1 < nt) nb_arrive(11);
      mbar_wait_if(mok, bar_w2m(bars), k & 1);
      wg_fence();
      g2_steps<8, 12, 0>(ac0, za, zb, dX2);
      wg_commit();
      g2_steps<8, 12, 8>(ac1, za, zb, dY2);
      wg_commit();
      wg_wait<2>();
      if (k > 0 && k + 1 < nt) nb_arrive(12);
      if (k != 1 && k + 1 < nt) mbar_wait(bar_w2(bars), k > 1 ? (k - 1) & 1 : 0);
      wg_fence();
      g2_steps<0, 4, 8>(ac1, za, zb, dY0);
      wg_commit();
      wg_wait<2>();
      if (k + 2 < nt) nb_arrive_p(13);
      const bool direct = k + 2 >= nt;
      sched_fence();
      fence_regs(ac0);
      pack_out<0>(ac0, oa, ob);
      store_rows<0, NAT_D0>(direct, poA, poB, oa, ob);
      sched_fence();
      if (NAT_A5) {
        wg_wait<1>();
        if (k + 2 < nt && (k > 0 || nt == 6)) nb_arrive_p(5);
      }
      wg_fence();
      g2_steps<4, 8, 8>(ac1, za, zb, dY0);
      wg_commit();
      if (k + 1 < nt) nb_arrive(3 + wg);
      PROFS(10, wg, 10 + it * 12);
      if (!NAT_A5) {
        wg_wait<2>();
        if (k + 2 < nt && (k > 0 || nt == 6)) nb_arrive_p(5);
      }
      if (NAT_D1 < 3 && k + 2 == nt) {
        store_rows<NAT_D0, NAT_D1>(true, poA, poB, oa, ob);
        nb_sync(11);
        store_rows<NAT_D1, 3>(true, poA, poB, oa, ob);
      } else
      store_rows<NAT_D0, 3>(direct, poA, poB, oa, ob);
      __nv_bfloat16 *qA = poA - 192 * wg, *qB = poB - 192 * wg;
      if (NAT_D1 == 3 && k + 2 == nt) nb_sync(11);
      sched_fence();
      wg_wait<0>();
      fence_regs(ac1);
      pack_out<1>(ac1, oa, ob);
      asm volatile("" : "+l"(qA), "+l"(qB));
      store_rows<3, 6>(direct, qA, qB, oa, ob);
      if (k == 0) {
        uint32_t m[2] = {oa[0], oa[1]};
#pragma unroll
        for (int i = 2; i < 24; i++) asm("max.NaN.bf16x2 %0, %0, %1;" : "+r"(m[i & 1]) : "r"(oa[i]));
        asm("max.NaN.bf16x2 %0, %0, %1;" : "+r"(m[0]) : "r"(m[1]));
        uint32_t nan;
        asm volatile("{\n.reg .pred p;\nsetp.ne.u32 p, %1, 0;\nbar.red.or.pred p, 15, 128, p;\nselp.u32 %0, 1, 0, p;\n}\n"
                     : "=r"(nan) : "r"(((m[0] & 0x7FFF7FFFu) + 0x007F007Fu) & 0x80008000u) : "memory");
        if (__builtin_expect(__any_sync(0xffffffffu, nan), 0)) {
          if (nt == 6) mbar_wait(bar_x(bars, 1), 1);
          for (bool first = true; __any_sync(0xffffffffu, refetch(sbase + kW2Off, wimg + w2_offset(), first)); first = false) { }
          wg_fence();
          g2_steps<0, 8, 0>(ac0, za, zb, dX0);
          g2_steps<8, 12, 0>(ac0, za, zb, dX2);
          g2_steps<0, 8, 0>(ac1, za, zb, dY0);
          g2_steps<8, 12, 0>(ac1, za, zb, dY2);
          wg_commit();
          wg_wait<0>();
          fence_regs(ac0);
          fence_regs(ac1);
          pack_out<0>(ac0, oa, ob);
          pack_out<1>(ac1, oa, ob);
          if (nt == 6) {
            asm volatile("bar.sync 15, 128;" ::: "memory");
            if (w == 0 && elect_one()) {
              const TileCoord tc = decode_tile(tt, tile0 + 2);
              mbar_arrive_expect_tx(bar_raw(bars), kWChunk);
              move_px<0, 1>(tm, tt, sbase + kXOff, bar_raw(bars), first_line(tc), tc.kind);
            }
            __syncwarp();
            mbar_wait(bar_raw(bars), 0);
          }
        }
        if (nt < 6) nb_arrive_p(5);
        if (elect_one()) mbar_arrive(bar_wok(bars));
      }
      keep_regs(za);
      keep_regs(zb);
#pragma unroll
      for (int i = 0; i < 8; i++) geo[i] = geo[i + 4];
      keep_regs(oa);
      keep_regs(ob);
      PROFS(12, wg, 12 + it * 12);
      sched_fence();
    }
  }
  PROF(wg, 38);
  GT_DUMP();
  PROF_DUMP(wg);
}

struct HaloCols { int vj, vc, uj, uc; };
__device__ __forceinline__ HaloCols halo_cols(const TileCoord& tc) {
  const int c0 = halo_c0(tc);
  return HaloCols{c0 > 98, c0 > 98 ? 98 : c0 + 3, c0 < 0 ? -1 : 0, c0 < 0 ? 4 : c0};
}
__device__ __forceinline__ void first_halo(const Maps& tm, uint32_t sbase, const TileCoord tc, int i) {
  const HaloCols hc = halo_cols(tc);
  const uint32_t dst = sbase + i * kChunkBytes, bar = bar_full(sbase + kBarOff, 0, i >> 1);
  const int h0 = halo_r0(tc), ch = 24 * tc.pc + 4 * i;
  tma_load_5d(dst, &tm.v14, bar, ch, hc.vj, hc.vc, tc.pr, h0);
  tma_load_5d(dst + 7 * 1024, &tm.u8, bar, ch, hc.uj, h0 + (tc.up ? 0 : -2), tc.pr, hc.uc);
  tma_load_5d(dst + 10 * 1024, &tm.u8, bar, ch, hc.uj, h0 + (tc.up ? 8 : 6), tc.pr, hc.uc);
}
__device__ __forceinline__ void load_halo(const Maps& tm, uint32_t sbase, uint32_t bars, const TileCoord tc, int k, int c) {
  const HaloCols hc = halo_cols(tc);
  const int h6 = halo_r0(tc) + (tc.up ? 0 : 8), h2 = halo_r0(tc) + 6, h8 = halo_r0(tc) + (tc.up ? 0 : 6), ch = 24 * tc.pc + 8 * c;
  uint32_t dv = sbase + 2 * c * kChunkBytes, du = dv + 7 * 1024;
  if (((k ^ tc.up) & 1) == 0) dv += 4 * 1024, du += 3 * 1024;
  const uint32_t bar = bar_full(bars, k & 1, c);
  mbar_arrive_expect_tx(bar, 14 * 1024);
  nb_sync_p(7 + c);
#pragma unroll
  for (int h = 0; h < 2; h++) {
    tma_load_5d(dv + h * kChunkBytes, &tm.v6, bar, ch + 4 * h, hc.vj, hc.vc, tc.pr, h6);
    tma_load_5d(du + h * kChunkBytes, &tm.u8, bar, ch + 4 * h, hc.uj, h8, tc.pr, hc.uc);
    tma_load_5d(sbase + (2 * c + h) * kChunkBytes + 3 * 1024, &tm.v2, bar, ch + 4 * h, hc.vj, hc.vc, tc.pr, h2);
  }
  PROFS(15, 2, k * 4 + c);
}
__device__ __forceinline__ void gather_px(const __nv_bfloat16* __restrict__ x, uint32_t buf, uint32_t bar, const TileCoord tc) {
  const int lane = threadIdx.x & 31, g = lane >> 3;
  uint32_t ro[4], co[4];
#pragma unroll
  for (int i = 0; i < 4; i++) {
    ro[i] = qpix(tc.pr, 8 * tc.I + 2 * i + (g & 1)) * (kW * kC * 2) + 16 * (lane & 7);
    co[i] = qpix(tc.pc, 8 * tc.J + 2 * i + (g >> 1)) * (kC * 2);
  }
  uint32_t dst = buf + g * 128 + (((lane & 7) ^ g) << 4);
  keep_regs(ro);
  keep_regs(co);
  sched_fence();
  nb_sync_p(13);
  nb_sync_p(5);
#pragma unroll
  for (int i = 0; i < 16; i++) {
    const char* src = (const char*)x + (ro[i >> 2] + co[i & 3]);
#pragma unroll
    for (int q = 0; q < 3; q++)
      asm volatile("cp.async.cg.shared.global [%0], [%1], 16;" ::"r"((dst ^ ((i & 1) * 576)) + (i >> 1) * 3072 + q * 1024), "l"(src + 128 * q) : "memory");
  }
  asm volatile("cp.async.wait_all;" ::: "memory");
  fence_proxy_async();
  __syncwarp();
  if (elect_one()) mbar_arrive(bar);
  __syncwarp();
}

__global__ void __launch_bounds__(384, 1)
nat_kernel(const __nv_bfloat16* __restrict__ x, __nv_bfloat16* out, const __nv_bfloat16* __restrict__ wqkv,
           const __nv_bfloat16* __restrict__ wo, uint8_t* wimg, const uint32_t zero,
           const __grid_constant__ Maps tm, const __grid_constant__ TileTable tt) {
  extern __shared__ uint8_t smem_raw[];
  constexpr uint32_t sbase = 1024;
  constexpr uint32_t bars = sbase + kBarOff;
  if (smem_u32(smem_raw) != sbase) __trap();
  const int tid = threadIdx.x;
  const uint32_t t_start = now_ns();
  if (tid == 0) GT(0);
  const int wid = __shfl_sync(0xffffffffu, tid >> 5, 0);
  const bool w2cta = blockIdx.x - 128 < 3 && wqkv != nullptr;
  if (wid >= 8) {
    asm volatile("setmaxnreg.dec.sync.aligned.u32 24;");
    const int c = wid & 3, lane = tid & 31;
    const int tile0 = blockIdx.x * kTilesPerCta, nt = num_tiles();
    uint32_t w2o = 0;
    if (c == 3) {
      asm volatile("bar.sync 13, 128;" ::: "memory");
      if (elect_one()) wait_clock(t_start, NAT_TM);
      __syncwarp();
      const CUtensorMap* px = tm.px + (blockIdx.x >= 112 ? 2 : edge_strip());
      asm volatile("prefetch.tensormap [%0];" ::"l"((uint64_t)&tm.v6) : "memory");
      asm volatile("prefetch.tensormap [%0];" ::"l"((uint64_t)&tm.v2) : "memory");
      asm volatile("prefetch.tensormap [%0];" ::"l"((uint64_t)(px + 4)) : "memory");
      asm volatile("prefetch.tensormap [%0];" ::"l"((uint64_t)(px + 5)) : "memory");
      if (blockIdx.x >= 112) {
        asm volatile("prefetch.tensormap [%0];" ::"l"((uint64_t)tm.px) : "memory");
        asm volatile("prefetch.tensormap [%0];" ::"l"((uint64_t)(tm.px + 4)) : "memory");
      }
      __nanosleep(NAT_TW2 - 2800);
      w2o = w2_offset();
      if (elect_one()) {
        mbar_arrive_expect_tx(bar_w2a(bars), kWChunk);
        mbar_arrive_expect_tx(bar_w2(bars), kWChunk);
        wait_clock(t_start, NAT_TW2);
        bulk_load(sbase + kW2Off, wimg + w2o, kWChunk, bar_w2a(bars));
        mbar_wait(bar_xf(bars), 0);
        bulk_load(sbase + kW2Off + 2 * kWChunk, wimg + (w2o + 2 * kWChunk), kWChunk, bar_w2(bars));
      }
      __syncwarp();
      if (nt < 6) {
#pragma unroll 1
        for (int k = 2; k < 4; k++) {
          gather_px(x, sbase + kXOff, bar_x(bars, 1), decode_tile(tt, tile0 + k));
        }
      }
      if (wqkv == nullptr) return;
      mbar_wait(bar_wok(bars), 0);
      if (lane == 0) asm volatile("red.relaxed.gpu.global.add.u32 [%0], 1;" ::"l"(g_flag) : "memory");
      if (blockIdx.x >= 48) return;
      if (lane == 0) {
        uint32_t v, it = 0;
        do {
          __nanosleep(2000);
          asm volatile("ld.relaxed.gpu.global.u32 %0, [%1];" : "=r"(v) : "l"(g_flag) : "memory");
        } while (v < gridDim.x && ++it < (1u << 16));
      }
      __syncwarp();
#pragma unroll
      for (int i = 0; i < 6; i++)
        stg128(wimg + ((i < 3 ? 0u : 3 * kWBytes - w2o) + blockIdx.x * 1536 + (i % 3) * 512 + lane * 16), kEmpty, kEmpty, kEmpty, kEmpty);
      if (lane == 0 && atomicAdd(g_flag + 32, 1u) == 47) {
        g_flag[0] = g_flag[32] = 0;
        g_flag[64] = w2o == kWBytes;
      }
      return;
    }
    if (!elect_one()) return;
    if (c == 0) {
      for (int i = 0; i < kNumBars; i++)
        if ((i != 0 && i != 10 || nt < 6) && (i != 21 || !w2cta)) mbar_init(bars + i * 8, i == 13 || i == 16 ? 4 : 1);
      asm volatile("st.shared.v2.u32 [%0], {%1,%1};" ::"r"(bars + 192), "r"(0) : "memory");
      asm volatile("fence.mbarrier_init.release.cluster;" ::: "memory");
      if (w2cta) asm volatile("bar.sync 10, 64;" ::: "memory");
      asm volatile("bar.arrive 0, 160;" ::: "memory");
      asm volatile("bar.arrive 14, 160;" ::: "memory");
      asm volatile("bar.arrive 13, 128;" ::: "memory");
      const TileCoord tc0 = decode_tile(tt, tile0);
      const HaloCols hc = halo_cols(tc0);
      const int h0 = halo_r0(tc0);
#pragma unroll
      for (int j = 0; j < 3; j++)
        if (j > 0 || nt < 6) mbar_arrive_expect_tx(bar_full(bars, 0, j), 2 * kChunkBytes);
      wait_clock(t_start, NAT_HP);
#pragma unroll
      for (int q = 8; q < 24; q += 8) {
        tma_prefetch_5d(&tm.v6, 24 * tc0.pc + q, hc.vj, hc.vc, tc0.pr, h0 + (tc0.up ? 0 : 8));
        tma_prefetch_5d(&tm.u8, 24 * tc0.pc + q, hc.uj, h0 + (tc0.up ? 0 : 6), tc0.pr, hc.uc);
        if (blockIdx.x >= 112) tma_prefetch_5d(&tm.v2, 24 * tc0.pc + q, hc.vj, hc.vc, tc0.pr, h0 + 6);
      }
#pragma unroll 1
      for (int i = nt < 6 ? 0 : 2; i < 7; i++) {
        if (i == NAT_H0) mbar_wait(bar_w1q(bars), 0);
        if (i == NAT_X1P) mbar_arrive(bar_go(bars));
        if (i < 6) first_halo(tm, sbase, tc0, i);
      }
      w2o = w2_offset();
    } else {
      asm volatile("bar.sync 13, 128;" ::: "memory");
      if (c == 2) {
        if (wqkv != nullptr && nt == 6) asm volatile("bar.sync 12, 64;" ::: "memory");
        const uint32_t c0 = clock();
        while ((uint32_t)clock() - c0 < NAT_TD) { }
        wait_clock(t_start, NAT_T0);
#pragma unroll
        for (int j = 0; j < 3; j++) {
          mbar_arrive_expect_tx(bar_w1c(bars, j), kWChunk);
          bulk_load(sbase + kW1Off + j * kWChunk, wimg + j * kWChunk, kWChunk, bar_w1c(bars, j));
        }
        mbar_arrive(bar_w1q(bars));
        GT(2);
        if (NAT_OT == 2) w2o = w2_offset();
      } else {
#pragma unroll 1
        for (int j = nt == 6; j < 2; j++) {
          const TileCoord tc = decode_tile(tt, tile0 + j);
          const int line = first_line(tc);
          mbar_arrive_expect_tx(bar_x(bars, j), kWChunk);
          if (j == 1) mbar_wait(bar_go(bars), 0);
          move_px<0, 2>(tm, tt, sbase + kXOff + (1 - j) * kWChunk, bar_x(bars, j), line, tc.kind);
        }
        w2o = w2_offset();
      }
    }
#pragma unroll 1
    for (int k = 1; k < nt; k++) {
      const TileCoord tn = decode_tile(tt, tile0 + k + 1);
      const int line = first_line(tn);
      if (c == 1) {
        nb_sync_p(6);
        bulk_load(sbase + kXOff, wimg + (w2o + kWChunk), kWChunk, bar_w2m(bars));
        mbar_arrive_expect_tx(bar_w2m(bars), kWChunk);
      }
      if (c == 2 - NAT_OT) {
        if (k == 1) wait_clock(t_start, NAT_TX2);
        else if (NAT_OT == 0 || k == nt - 1 + (nt == 6)) __nanosleep(NAT_PFD);
        if (k < 5 && nt == 6) move_px<1, 1>(tm, tt, 0, 0, line, tn.kind);
      }
      if (c == 2 - NAT_OT && (blockIdx.x >= 112 || k == 5)) {
        const TileCoord tc = decode_tile(tt, tile0 + k);
        const HaloCols hc = halo_cols(tc);
        const int h8 = halo_r0(tc) + (tc.up ? 0 : 6);
#pragma unroll 1
        for (int q = 0; q < 24; q += 8) {
          tma_prefetch_5d(&tm.v6, 24 * tc.pc + q, hc.vj, hc.vc, tc.pr, h8);
          tma_prefetch_5d(&tm.v2, 24 * tc.pc + q, hc.vj, hc.vc, tc.pr, h8 + 6);
          tma_prefetch_5d(&tm.u8, 24 * tc.pc + q, hc.uj, h8, tc.pr, hc.uc);
        }
      }
      load_halo(tm, sbase, bars, decode_tile(tt, tile0 + k), k, c);
      if (c == 0 && k >= 3 && NAT_RP == 1) {
        if (NAT_RD) __nanosleep(NAT_RD);
        asm volatile("cp.async.bulk.wait_group.read 0;" ::: "memory");
        bulk_load(sbase + out_slot(k - 1, nt), wimg + (w2o + out_slot(k - 1, nt) - kW2Off), kWChunk, bar_w2(bars));
        mbar_arrive_expect_tx(bar_w2(bars), kWChunk);
      }
      if (c == 0 && k < 5 && nt == 6) {
        const int f = ~k & 1;
        if (tn.kind == 0) {
#pragma unroll
          for (int j = 0; j < 4; j++) {
            if ((j & 1) == 0) nb_sync_p(j ? 5 : 13);
            tma_load_5d(sbase + kXOff + (j ^ 2 * f) * 6144, tm.px, bar_x(bars, 1), 0, 0, 0, 0, line + 6 * (j ^ 2 * f));
          }
        } else {
          nb_sync_p(13);
          move_px<0, 4, 4>(tm, tt, sbase + kXOff, bar_x(bars, 1), line, tn.kind, 4 * f);
          nb_sync_p(5);
          move_px<0, 4, 4>(tm, tt, sbase + kXOff, bar_x(bars, 1), line, tn.kind, 4 - 4 * f);
        }
        mbar_arrive_expect_tx(bar_x(bars, 1), kWChunk);
        PROFS(16, 2, k * 4 + 3);
      }
      if (c == NAT_OT && k >= 2) {
        const TileCoord tp = decode_tile(tt, tile0 + k - 2);
        const int lp = first_line(tp);
        nb_sync_p(10);
        if (NAT_XW == 1 && k < 5 && nt == 6) mbar_wait(bar_x(bars, 1), k & 1);
        if (NAT_XW > 1) __nanosleep(NAT_XW);
        move_px<2, NAT_SU>(tm, tt, sbase + out_slot(k, nt), 0, lp, tp.kind);
        if (NAT_RP == 0 && k + 1 < nt) {
          asm volatile("cp.async.bulk.wait_group.read 0;" ::: "memory");
          bulk_load(sbase + out_slot(k, nt), wimg + (w2o + out_slot(k, nt) - kW2Off), kWChunk, bar_w2(bars));
          mbar_arrive_expect_tx(bar_w2(bars), kWChunk);
        }
      }
    }
    asm volatile("cp.async.bulk.wait_group 0;" ::: "memory");
  } else {
    if (blockIdx.x < 128) {
      if ((wid == 4 || (wid == 5 && blockIdx.x - 2 < 16)) && wqkv != nullptr) {
        fold_w1(blockIdx.x - 2 < 16 ? 2 * blockIdx.x + wid - 6 : blockIdx.x + (blockIdx.x < 2 ? 0 : 16), wqkv, wimg);
        if (wid == 4) asm volatile("bar.arrive 12, 64;" ::: "memory");
        if (tid == 128) GT(7);
      }
      sched_fence();
      if (wid == 1 && elect_one()) {
        const TileCoord tc = decode_tile(tt, blockIdx.x * kTilesPerCta);
        mbar_init(bar_x(bars, 0), 1);
        asm volatile("fence.mbarrier_init.release.cluster;" ::: "memory");
        mbar_arrive_expect_tx(bar_x(bars, 0), kWChunk);
        GT(15);
        move_px<0, 2>(tm, tt, sbase + kXOff + kWChunk, bar_x(bars, 0), first_line(tc), tc.kind);
        GT(16);
      }
      __syncwarp();
      sched_fence();
      if (wid == 2 && elect_one()) {
        const TileCoord tc = decode_tile(tt, blockIdx.x * kTilesPerCta);
        mbar_init(bar_full(bars, 0, 0), 1);
        asm volatile("fence.mbarrier_init.release.cluster;" ::: "memory");
        mbar_arrive_expect_tx(bar_full(bars, 0, 0), 2 * kChunkBytes);
        if (NAT_TH) wait_clock(t_start, NAT_TH);
        asm volatile("prefetch.tensormap [%0];" ::"l"((uint64_t)&tm.u8) : "memory");
        GT(17);
        first_halo(tm, sbase, tc, 0);
        first_halo(tm, sbase, tc, 1);
      }
      __syncwarp();
    }
    sched_fence();
    {
      if (w2cta) {
        const int q = blockIdx.x & 3;
        uint32_t w2o = 0;
        if (wid == 1 && elect_one()) {
          asm volatile("prefetch.tensormap [%0];" ::"l"((uint64_t)&tm.wo) : "memory");
#pragma unroll
          for (int j = 0; j < 3; j++) mbar_init(bar_raw(bars, j), 1);
          asm volatile("fence.mbarrier_init.release.cluster;" ::: "memory");
#pragma unroll
          for (int j = 0; j < 6; j++)
            asm volatile("cp.async.bulk.tensor.2d.shared::cluster.global.tile.mbarrier::complete_tx::bytes [%0], [%1, {%3, %4}], [%2];" ::"r"(
                             j < 3 ? sbase + j * 8192 : sbase + kW2Off + (j - 3) * kWChunk),
                         "l"((uint64_t)(j < 3 ? &tm.wv : &tm.wo)), "r"(bar_raw(bars, j < 3 ? 0 : j - 3)),
                         "r"(j < 3 ? 384 + 64 * j : 64 * (j - 3)), "r"(j < 3 ? 64 * q : 0) : "memory");
#pragma unroll
          for (int j = 0; j < 3; j++) mbar_arrive_expect_tx(bar_raw(bars, j), j ? kWChunk : 2 * kWChunk);
          w2o = w2_offset();
        }
        __syncwarp();
#pragma unroll 1
        for (int r = 0; r < 3; r++) {
          const int blk = 2 * r - 2 + (wid >> 2);
          if (blk < 3) {
            if (r > 0) {
              mbar_wait(bar_raw(bars, 0), 0);
              mbar_wait(bar_raw(bars, blk), 0);
            }
            if (tid == 0 && r == 1) GT(7);
            float acc[32];
            const uint64_t db = make_desc(sbase + kW2Off + max(blk, 0) * kWChunk, kWChunk, 1024);
            wg_fence();
            wg_m64tz<0, 32>(acc, make_desc(sbase, 16, 1024), db, 0);
#pragma unroll
            for (int s = 1; s < 12; s++) wg_m64t<0, 32>(acc, make_desc(sbase + (s >> 2) * 8192 + (s & 3) * 32, 16, 1024), db + s * 128, 1);
            wg_commit();
            wg_wait<0>();
            fence_regs(acc);
            if (tid == 0) GT(19);
            const int m = (tid >> 3) & 3;
#pragma unroll
            for (int j = 0; j < 8; j += 2) {
              const int n = g2_inv(8 * (j + (m >> 1)) + (tid & 7));
              asm volatile("stmatrix.sync.aligned.m8n8.x4.trans.shared.b16 [%0], {%1,%2,%3,%4};" ::"r"(
                               sbase + kW1Off + (blk + 2) * 8192 + n * 128 + (((2 * (wid & 3) + (m & 1)) ^ (n & 7)) << 4)),
                           "r"(pack_bf16(acc[4 * j], acc[4 * j + 1])), "r"(pack_bf16(acc[4 * j + 2], acc[4 * j + 3])),
                           "r"(pack_bf16(acc[4 * j + 4], acc[4 * j + 5])), "r"(pack_bf16(acc[4 * j + 6], acc[4 * j + 7])) : "memory");
            }
            fence_proxy_async();
          }
          if (tid == 0) GT(18);
          asm volatile("bar.sync 11, 256;" ::: "memory");
          if (wid == 1 && elect_one()) {
            asm volatile("{\n.reg .pred p;\nsetp.ne.s32 p, %3, 0;\n@p cp.async.bulk.global.shared::cta.bulk_group [%0], [%1], %2;\n}\n" ::"l"(
                             wimg + (w2o + w2piece(r >> 1, q) * (kWChunk / 2))),
                         "r"(sbase + kW1Off + 16384 + (r >> 1) * (kWChunk / 2)), "r"(kWChunk / 2), "r"(r) : "memory");
            asm volatile("cp.async.bulk.commit_group;" ::: "memory");
          }
          __syncwarp();
        }
        if (wid == 1) {
          if (elect_one()) asm volatile("cp.async.bulk.wait_group.read 0;" ::: "memory");
          if (tid == 32) GT(31);
          __syncwarp();
          asm volatile("bar.arrive 10, 64;" ::: "memory");
        }
      }
    }
    __syncwarp();
    if (wid < 4) asm volatile("bar.sync 0, 160;" ::: "memory");
    else asm volatile("bar.sync 14, 160;" ::: "memory");
    asm volatile("setmaxnreg.inc.sync.aligned.u32 240;");
    consumer(wid >> 2, out, wimg, sbase, zero, tm, tt);
  }
}

}

typedef CUresult (*PFN_encodeTiled)(CUtensorMap*, CUtensorMapDataType, cuuint32_t, void*, const cuuint64_t*,
                                    const cuuint64_t*, const cuuint32_t*, const cuuint32_t*, CUtensorMapInterleave,
                                    CUtensorMapSwizzle, CUtensorMapL2promotion, CUtensorMapFloatOOBfill);

extern "C" void kernel_launch(void* const* d_in, const int* in_sizes, int n_in, void* d_out, int out_size) {
  const __nv_bfloat16* x = (const __nv_bfloat16*)d_in[0];
  const __nv_bfloat16* wqkv = (const __nv_bfloat16*)d_in[1];
  const __nv_bfloat16* wo = (const __nv_bfloat16*)d_in[2];
  __nv_bfloat16* out = (__nv_bfloat16*)d_out;

  static PFN_encodeTiled encode = nullptr;
  static int num_sms = 0;
  static uint8_t* wimg = nullptr;
  if (!encode) {
    void* fn = nullptr;
    cudaDriverEntryPointQueryResult qres;
    cudaGetDriverEntryPoint("cuTensorMapEncodeTiled", &fn, cudaEnableDefault, &qres);
    encode = (PFN_encodeTiled)fn;
    cudaFuncSetAttribute(nat::nat_kernel, cudaFuncAttributeMaxDynamicSharedMemorySize, nat::kSmemBytes);
    cudaGetSymbolAddress((void**)&wimg, nat::g_wimg32);
    int dev = 0;
    cudaGetDevice(&dev);
    cudaDeviceGetAttribute(&num_sms, cudaDevAttrMultiProcessorCount, dev);
  }
  nat::Maps tm;
  cuuint32_t estr[5] = {1, 1, 1, 1, 1};
  {
    cuuint64_t vdim[5] = {48, 2, 105, 2, 112}, udim[5] = {48, 2, 112, 2, 105};
    cuuint64_t vstr[4] = {7 * 768, 768, 224 * 384, 2 * 224 * 384}, ustr[4] = {7 * 768, 2 * 224 * 384, 224 * 384, 768};
    CUtensorMap* maps[4] = {&tm.v6, &tm.v2, &tm.v14, &tm.u8};
    for (int i = 0; i < 4; i++) {
      cuuint32_t box[5] = {4, 2, i < 3 ? 4u : 8u, 1, i == 0 ? 6u : i == 1 ? 2u : i == 2 ? 14u : 3u};
      encode(maps[i], CU_TENSOR_MAP_DATA_TYPE_UINT32, 5, (void*)x, i < 3 ? vdim : udim, i < 3 ? vstr : ustr, box, estr,
             CU_TENSOR_MAP_INTERLEAVE_16B, CU_TENSOR_MAP_SWIZZLE_128B, NAT_L2P, CU_TENSOR_MAP_FLOAT_OOB_FILL_NONE);
    }
  }
  for (int i = 0; i < 8; i++) {
    const cuuint32_t row = 224 * 384, dr = (1u + (i & 1)) * row;
    const cuuint32_t shape[4][6] = {{8, 3, 2u - i, 2 * row, 128, 4 * 768}, {2, 4, 3, dr, 768, 128}, {4, 2, 3, 4 * row, 2 * row, 128}, {4, 2, 3, 768, dr, 128}};
    const cuuint32_t* sh = shape[i >> 1];
    cuuint64_t dim[5] = {64, sh[0], sh[1], sh[2], 224 * 224 * 3};
    cuuint64_t str[4] = {sh[3], sh[4], sh[5], 128};
    cuuint32_t box[5] = {64, sh[0], sh[1], sh[2], 1};
    encode(tm.px + i, CU_TENSOR_MAP_DATA_TYPE_BFLOAT16, 5, i < 4 ? (void*)x : (void*)out, dim, str, box, estr, CU_TENSOR_MAP_INTERLEAVE_NONE,
           CU_TENSOR_MAP_SWIZZLE_128B, i < 4 ? CU_TENSOR_MAP_L2_PROMOTION_L2_128B : CU_TENSOR_MAP_L2_PROMOTION_NONE,
           CU_TENSOR_MAP_FLOAT_OOB_FILL_NONE);
  }
  for (int i = 0; i < 2; i++) {
    cuuint64_t dim[2] = {i ? 192u : 576u, 192}, str[1] = {i ? 384u : 1152u};
    cuuint32_t box[2] = {64, i ? 192u : 64u};
    encode(i ? &tm.wo : &tm.wv, CU_TENSOR_MAP_DATA_TYPE_BFLOAT16, 2, i ? (void*)wo : (void*)wqkv, dim, str, box, estr,
           CU_TENSOR_MAP_INTERLEAVE_NONE, CU_TENSOR_MAP_SWIZZLE_128B, CU_TENSOR_MAP_L2_PROMOTION_L2_256B, CU_TENSOR_MAP_FLOAT_OOB_FILL_NONE);
  }
  nat::TileTable tt;
  nat::make_tiles(tt);
  const int grid = nat::kCtas;
  if (num_sms >= grid) {
    nat::nat_kernel<<<grid, 384, nat::kSmemBytes>>>(x, out, wqkv, wo, wimg, 0u, tm, tt);
  } else {
    nat::fold_kernel<<<27, 256>>>(wqkv, wo, wimg);
    nat::nat_kernel<<<grid, 384, nat::kSmemBytes>>>(x, out, nullptr, nullptr, wimg, 0u, tm, tt);
  }
}
```

```cpp
#include <cuda_runtime.h>
#include <cuda_bf16.h>
#include <cuda.h>
#include <stdint.h>

#define NAT_P1 2
#define NAT_P2 4
#define NAT_H0 2
#define NAT_T0 2100
#define NAT_TD 1200
#define NAT_TW2 4650
#define NAT_TX2 3800
#define NAT_X1P 5
#define NAT_PK 3
#define NAT_HP 1800
#define NAT_PFD 700
#define NAT_XW 200
#define NAT_SU 8
#define NAT_D0 1
#define NAT_TH 600
#define NAT_TM 1300
#define NAT_SB 0
namespace nat {

constexpr int kW = 224, kC = 192;
constexpr int kCtas = 132;
constexpr int kTilesPerCta = 6;
constexpr float kAlpha = 0.07216878364870322f * 1.4426950408889634f;
constexpr uint32_t kChunkBytes = 13 * 1024;
constexpr uint32_t kWChunk = 192 * 128;
constexpr uint32_t kWBytes = 3 * kWChunk;
constexpr uint32_t kW1Off = 6 * kChunkBytes;
constexpr uint32_t kW2Off = kW1Off + kWBytes;
constexpr uint32_t kXOff = kW2Off + kWChunk;
constexpr uint32_t kBarOff = kW2Off + kWBytes;
constexpr uint32_t kProfOff = kBarOff + 208;
constexpr uint32_t kSmemBytes = kBarOff + 1024;

static_assert(kW1Off % 1024 == 0 && kW2Off % 1024 == 0 && kChunkBytes % 1024 == 0, "swizzle alignment");
static_assert(kSmemBytes <= 232448, "smem");

constexpr uint32_t kEmpty = 0xFFFFFFFFu;
#define NAT_R8(v) v, v, v, v, v, v, v, v
#define NAT_R2K(v) NAT_R8(NAT_R8(NAT_R8(v))), NAT_R8(NAT_R8(NAT_R8(v))), NAT_R8(NAT_R8(NAT_R8(v))), NAT_R8(NAT_R8(NAT_R8(v)))
#define NAT_IMG NAT_R8(NAT_R2K(kEmpty)), NAT_R2K(kEmpty)
__device__ __align__(1024) uint32_t g_wimg32[3 * kWBytes / 4] = {NAT_IMG, NAT_IMG, NAT_IMG};
static_assert(kWBytes / 4 == 9 * 2048, "initialiser");
__device__ __align__(128) uint32_t g_flag[96];
__device__ __forceinline__ uint32_t w2_offset() {
  uint32_t v;
  asm volatile("ld.relaxed.gpu.global.u32 %0, [%1];" : "=r"(v) : "l"(g_flag + 64) : "memory");
  return (1 + v) * kWBytes;
}

#define PROFS(id, wgid, slotid) do { } while (0)
#define PROF(wgid, slotid) do { } while (0)
#define PROF_DUMP(wgid) do { } while (0)

#define GT(slotid) do { } while (0)
#define GT_DUMP() do { } while (0)

__device__ __forceinline__ uint32_t smem_u32(const void* p) { return (uint32_t)__cvta_generic_to_shared(p); }

__device__ __forceinline__ void mbar_init(uint32_t bar, uint32_t count) {
  asm volatile("mbarrier.init.shared::cta.b64 [%0], %1;" ::"r"(bar), "r"(count) : "memory");
}
__device__ __forceinline__ void mbar_arrive(uint32_t bar) {
  asm volatile("mbarrier.arrive.shared::cta.b64 _, [%0];" ::"r"(bar) : "memory");
}
__device__ __forceinline__ void mbar_arrive_expect_tx(uint32_t bar, uint32_t bytes) {
  asm volatile("mbarrier.arrive.expect_tx.shared::cta.b64 _, [%0], %1;" ::"r"(bar), "r"(bytes) : "memory");
}
__device__ __forceinline__ void mbar_wait(uint32_t bar, uint32_t parity) {
  uint32_t ok;
  uint32_t it = 0;
  do {
    asm volatile(
        "{\n.reg .pred p;\n"
        "mbarrier.try_wait.parity.shared::cta.b64 p, [%1], %2;\n"
        "selp.u32 %0, 1, 0, p;\n}\n"
        : "=r"(ok)
        : "r"(bar), "r"(parity)
        : "memory");
    if (++it > (1u << 24)) break;
  } while (!ok);
}
__device__ __forceinline__ uint32_t mbar_test(uint32_t bar, uint32_t parity) {
  uint32_t ok;
  asm volatile("{\n.reg .pred p;\nmbarrier.test_wait.parity.shared::cta.b64 p, [%1], %2;\nselp.u32 %0, 1, 0, p;\n}\n"
               : "=r"(ok) : "r"(bar), "r"(parity) : "memory");
  return ok;
}
__device__ __forceinline__ void mbar_wait_if(uint32_t ok, uint32_t bar, uint32_t parity) {
  if (!__all_sync(0xffffffffu, ok)) mbar_wait(bar, parity);
}
__device__ __forceinline__ bool elect_one() {
  uint32_t r;
  asm volatile("{\n.reg .pred p;\nelect.sync _|p, 0xffffffff;\nselp.u32 %0, 1, 0, p;\n}\n" : "=r"(r));
  return r != 0;
}
__device__ __forceinline__ void nb_arrive(int id) { asm volatile("bar.arrive %0, 256;" ::"r"(id) : "memory"); }
__device__ __forceinline__ void nb_sync(int id) { asm volatile("bar.sync %0, 256;" ::"r"(id) : "memory"); }
__device__ __forceinline__ void nb_arrive_p(int id) { asm volatile("bar.arrive %0, 160;" ::"r"(id) : "memory"); }
__device__ __forceinline__ void nb_sync_p(int id) { asm volatile("bar.sync %0, 160;" ::"r"(id) : "memory"); }
__device__ __forceinline__ void fence_proxy_async() { asm volatile("fence.proxy.async.shared::cta;" ::: "memory"); }

__device__ __forceinline__ void tma_load_5d(uint32_t dst, const CUtensorMap* map, uint32_t bar, int c0, int c1, int c2,
                                            int c3, int c4) {
  asm volatile(
      "cp.async.bulk.tensor.5d.shared::cluster.global.tile.mbarrier::complete_tx::bytes "
      "[%0], [%1, {%3, %4, %5, %6, %7}], [%2];"
      ::"r"(dst), "l"((uint64_t)map), "r"(bar), "r"(c0), "r"(c1), "r"(c2), "r"(c3), "r"(c4)
      : "memory");
}
__device__ __forceinline__ void bulk_load(uint32_t dst, const void* src, uint32_t bytes, uint32_t bar) {
  asm volatile("cp.async.bulk.shared::cluster.global.mbarrier::complete_tx::bytes [%0], [%1], %2, [%3];"
               ::"r"(dst), "l"((uint64_t)src), "r"(bytes), "r"(bar)
               : "memory");
}

__device__ __forceinline__ void wg_fence() { asm volatile("wgmma.fence.sync.aligned;" ::: "memory"); }
__device__ __forceinline__ void wg_commit() { asm volatile("wgmma.commit_group.sync.aligned;" ::: "memory"); }
template <int N>
__device__ __forceinline__ void wg_wait() { asm volatile("wgmma.wait_group.sync.aligned %0;" ::"n"(N) : "memory"); }

template <int N>
__device__ __forceinline__ void fence_regs(float (&d)[N]) {
#pragma unroll
  for (int i = 0; i < N; i++) asm volatile("" : "+f"(d[i])::"memory");
}
template <int N>
__device__ __forceinline__ void keep_regs(uint32_t (&d)[N]) {
#pragma unroll
  for (int i = 0; i < N; i++) asm volatile("" : "+r"(d[i])::"memory");
}

__device__ __forceinline__ uint32_t pack_bf16(float lo, float hi) {
  uint32_t d;
  asm("cvt.rn.bf16x2.f32 %0, %1, %2;" : "=r"(d) : "f"(hi), "f"(lo));
  return d;
}
__device__ __forceinline__ float ex2(float x) {
  float y;
  asm("ex2.approx.ftz.f32 %0, %1;" : "=f"(y) : "f"(x));
  return y;
}
__device__ __forceinline__ float rcp_approx(float x) {
  float y;
  asm("rcp.approx.ftz.f32 %0, %1;" : "=f"(y) : "f"(x));
  return y;
}
__device__ __forceinline__ uint4 ldg128_nc(const void* p) {
  uint4 v;
  asm volatile("ld.global.nc.v4.u32 {%0,%1,%2,%3}, [%4];" : "=r"(v.x), "=r"(v.y), "=r"(v.z), "=r"(v.w) : "l"(p));
  return v;
}
__device__ __forceinline__ void stg128(void* p, uint32_t a, uint32_t b, uint32_t c, uint32_t d) {
  asm volatile("st.global.v4.u32 [%0], {%1,%2,%3,%4};" ::"l"(p), "r"(a), "r"(b), "r"(c), "r"(d) : "memory");
}

__device__ __forceinline__ long long clk64() {
  long long c;
  asm volatile("mov.u64 %0, %clock64;" : "=l"(c)::"memory");
  return c;
}
__device__ __forceinline__ void sched_fence() { while (clk64() < 0) { } }

__device__ __forceinline__ uint64_t make_desc(uint32_t addr, uint32_t lbo, uint32_t sbo, uint32_t mode = 1) {
  return (uint64_t)((addr & 0x3FFFF) >> 4) | ((uint64_t)(lbo >> 4) << 16) | ((uint64_t)(sbo >> 4) << 32) |
         ((uint64_t)mode << 62);
}

template <int OFF, int NN>
__device__ __forceinline__ void wg_m192(float (&d)[NN], uint64_t desc_a, uint64_t desc_b, int scale_d) {
  asm volatile(
      "{\n.reg .pred p;\nsetp.ne.b32 p, %98, 0;\n"
      "wgmma.mma_async.sync.aligned.m64n192k16.f32.bf16.bf16 "
      "{%0,%1,%2,%3,%4,%5,%6,%7,%8,%9,%10,%11,%12,%13,%14,%15,"
      "%16,%17,%18,%19,%20,%21,%22,%23,%24,%25,%26,%27,%28,%29,%30,%31,"
      "%32,%33,%34,%35,%36,%37,%38,%39,%40,%41,%42,%43,%44,%45,%46,%47,"
      "%48,%49,%50,%51,%52,%53,%54,%55,%56,%57,%58,%59,%60,%61,%62,%63,"
      "%64,%65,%66,%67,%68,%69,%70,%71,%72,%73,%74,%75,%76,%77,%78,%79,"
      "%80,%81,%82,%83,%84,%85,%86,%87,%88,%89,%90,%91,%92,%93,%94,%95}, "
      "%96, %97, p, 1, 1, 0, 0;\n}\n"
      : "+f"(d[OFF + 0]), "+f"(d[OFF + 1]), "+f"(d[OFF + 2]), "+f"(d[OFF + 3]), "+f"(d[OFF + 4]), "+f"(d[OFF + 5]),
        "+f"(d[OFF + 6]), "+f"(d[OFF + 7]), "+f"(d[OFF + 8]), "+f"(d[OFF + 9]), "+f"(d[OFF + 10]), "+f"(d[OFF + 11]),
        "+f"(d[OFF + 12]), "+f"(d[OFF + 13]), "+f"(d[OFF + 14]), "+f"(d[OFF + 15]), "+f"(d[OFF + 16]), "+f"(d[OFF + 17]),
        "+f"(d[OFF + 18]), "+f"(d[OFF + 19]), "+f"(d[OFF + 20]), "+f"(d[OFF + 21]), "+f"(d[OFF + 22]), "+f"(d[OFF + 23]),
        "+f"(d[OFF + 24]), "+f"(d[OFF + 25]), "+f"(d[OFF + 26]), "+f"(d[OFF + 27]), "+f"(d[OFF + 28]), "+f"(d[OFF + 29]),
        "+f"(d[OFF + 30]), "+f"(d[OFF + 31]), "+f"(d[OFF + 32]), "+f"(d[OFF + 33]), "+f"(d[OFF + 34]), "+f"(d[OFF + 35]),
        "+f"(d[OFF + 36]), "+f"(d[OFF + 37]), "+f"(d[OFF + 38]), "+f"(d[OFF + 39]), "+f"(d[OFF + 40]), "+f"(d[OFF + 41]),
        "+f"(d[OFF + 42]), "+f"(d[OFF + 43]), "+f"(d[OFF + 44]), "+f"(d[OFF + 45]), "+f"(d[OFF + 46]), "+f"(d[OFF + 47]),
        "+f"(d[OFF + 48]), "+f"(d[OFF + 49]), "+f"(d[OFF + 50]), "+f"(d[OFF + 51]), "+f"(d[OFF + 52]), "+f"(d[OFF + 53]),
        "+f"(d[OFF + 54]), "+f"(d[OFF + 55]), "+f"(d[OFF + 56]), "+f"(d[OFF + 57]), "+f"(d[OFF + 58]), "+f"(d[OFF + 59]),
        "+f"(d[OFF + 60]), "+f"(d[OFF + 61]), "+f"(d[OFF + 62]), "+f"(d[OFF + 63]), "+f"(d[OFF + 64]), "+f"(d[OFF + 65]),
        "+f"(d[OFF + 66]), "+f"(d[OFF + 67]), "+f"(d[OFF + 68]), "+f"(d[OFF + 69]), "+f"(d[OFF + 70]), "+f"(d[OFF + 71]),
        "+f"(d[OFF + 72]), "+f"(d[OFF + 73]), "+f"(d[OFF + 74]), "+f"(d[OFF + 75]), "+f"(d[OFF + 76]), "+f"(d[OFF + 77]),
        "+f"(d[OFF + 78]), "+f"(d[OFF + 79]), "+f"(d[OFF + 80]), "+f"(d[OFF + 81]), "+f"(d[OFF + 82]), "+f"(d[OFF + 83]),
        "+f"(d[OFF + 84]), "+f"(d[OFF + 85]), "+f"(d[OFF + 86]), "+f"(d[OFF + 87]), "+f"(d[OFF + 88]), "+f"(d[OFF + 89]),
        "+f"(d[OFF + 90]), "+f"(d[OFF + 91]), "+f"(d[OFF + 92]), "+f"(d[OFF + 93]), "+f"(d[OFF + 94]), "+f"(d[OFF + 95])
      : "l"(desc_a), "l"(desc_b), "r"(scale_d));
}

template <int OFF, int NN>
__device__ __forceinline__ void wg_m192z(float (&d)[NN], uint64_t desc_a, uint64_t desc_b, int scale_d) {
  asm volatile(
      "{\n.reg .pred p;\nsetp.ne.b32 p, %98, 0;\n"
      "wgmma.mma_async.sync.aligned.m64n192k16.f32.bf16.bf16 "
      "{%0,%1,%2,%3,%4,%5,%6,%7,%8,%9,%10,%11,%12,%13,%14,%15,"
      "%16,%17,%18,%19,%20,%21,%22,%23,%24,%25,%26,%27,%28,%29,%30,%31,"
      "%32,%33,%34,%35,%36,%37,%38,%39,%40,%41,%42,%43,%44,%45,%46,%47,"
      "%48,%49,%50,%51,%52,%53,%54,%55,%56,%57,%58,%59,%60,%61,%62,%63,"
      "%64,%65,%66,%67,%68,%69,%70,%71,%72,%73,%74,%75,%76,%77,%78,%79,"
      "%80,%81,%82,%83,%84,%85,%86,%87,%88,%89,%90,%91,%92,%93,%94,%95}, "
      "%96, %97, p, 1, 1, 0, 0;\n}\n"
      : "=f"(d[OFF + 0]), "=f"(d[OFF + 1]), "=f"(d[OFF + 2]), "=f"(d[OFF + 3]), "=f"(d[OFF + 4]), "=f"(d[OFF + 5]),
        "=f"(d[OFF + 6]), "=f"(d[OFF + 7]), "=f"(d[OFF + 8]), "=f"(d[OFF + 9]), "=f"(d[OFF + 10]), "=f"(d[OFF + 11]),
        "=f"(d[OFF + 12]), "=f"(d[OFF + 13]), "=f"(d[OFF + 14]), "=f"(d[OFF + 15]), "=f"(d[OFF + 16]), "=f"(d[OFF + 17]),
        "=f"(d[OFF + 18]), "=f"(d[OFF + 19]), "=f"(d[OFF + 20]), "=f"(d[OFF + 21]), "=f"(d[OFF + 22]), "=f"(d[OFF + 23]),
        "=f"(d[OFF + 24]), "=f"(d[OFF + 25]), "=f"(d[OFF + 26]), "=f"(d[OFF + 27]), "=f"(d[OFF + 28]), "=f"(d[OFF + 29]),
        "=f"(d[OFF + 30]), "=f"(d[OFF + 31]), "=f"(d[OFF + 32]), "=f"(d[OFF + 33]), "=f"(d[OFF + 34]), "=f"(d[OFF + 35]),
        "=f"(d[OFF + 36]), "=f"(d[OFF + 37]), "=f"(d[OFF + 38]), "=f"(d[OFF + 39]), "=f"(d[OFF + 40]), "=f"(d[OFF + 41]),
        "=f"(d[OFF + 42]), "=f"(d[OFF + 43]), "=f"(d[OFF + 44]), "=f"(d[OFF + 45]), "=f"(d[OFF + 46]), "=f"(d[OFF + 47]),
        "=f"(d[OFF + 48]), "=f"(d[OFF + 49]), "=f"(d[OFF + 50]), "=f"(d[OFF + 51]), "=f"(d[OFF + 52]), "=f"(d[OFF + 53]),
        "=f"(d[OFF + 54]), "=f"(d[OFF + 55]), "=f"(d[OFF + 56]), "=f"(d[OFF + 57]), "=f"(d[OFF + 58]), "=f"(d[OFF + 59]),
        "=f"(d[OFF + 60]), "=f"(d[OFF + 61]), "=f"(d[OFF + 62]), "=f"(d[OFF + 63]), "=f"(d[OFF + 64]), "=f"(d[OFF + 65]),
        "=f"(d[OFF + 66]), "=f"(d[OFF + 67]), "=f"(d[OFF + 68]), "=f"(d[OFF + 69]), "=f"(d[OFF + 70]), "=f"(d[OFF + 71]),
        "=f"(d[OFF + 72]), "=f"(d[OFF + 73]), "=f"(d[OFF + 74]), "=f"(d[OFF + 75]), "=f"(d[OFF + 76]), "=f"(d[OFF + 77]),
        "=f"(d[OFF + 78]), "=f"(d[OFF + 79]), "=f"(d[OFF + 80]), "=f"(d[OFF + 81]), "=f"(d[OFF + 82]), "=f"(d[OFF + 83]),
        "=f"(d[OFF + 84]), "=f"(d[OFF + 85]), "=f"(d[OFF + 86]), "=f"(d[OFF + 87]), "=f"(d[OFF + 88]), "=f"(d[OFF + 89]),
        "=f"(d[OFF + 90]), "=f"(d[OFF + 91]), "=f"(d[OFF + 92]), "=f"(d[OFF + 93]), "=f"(d[OFF + 94]), "=f"(d[OFF + 95])
      : "l"(desc_a), "l"(desc_b), "r"(scale_d));
}

template <int OFF, int NN>
__device__ __forceinline__ void wg_m64t(float (&d)[NN], uint64_t desc_a, uint64_t desc_b, int scale_d) {
  asm volatile(
      "{\n.reg .pred p;\nsetp.ne.b32 p, %34, 0;\n"
      "wgmma.mma_async.sync.aligned.m64n64k16.f32.bf16.bf16 "
      "{%0,%1,%2,%3,%4,%5,%6,%7,%8,%9,%10,%11,%12,%13,%14,%15,"
      "%16,%17,%18,%19,%20,%21,%22,%23,%24,%25,%26,%27,%28,%29,%30,%31}, "
      "%32, %33, p, 1, 1, 0, 1;\n}\n"
      : "+f"(d[OFF + 0]), "+f"(d[OFF + 1]), "+f"(d[OFF + 2]), "+f"(d[OFF + 3]), "+f"(d[OFF + 4]), "+f"(d[OFF + 5]),
        "+f"(d[OFF + 6]), "+f"(d[OFF + 7]), "+f"(d[OFF + 8]), "+f"(d[OFF + 9]), "+f"(d[OFF + 10]), "+f"(d[OFF + 11]),
        "+f"(d[OFF + 12]), "+f"(d[OFF + 13]), "+f"(d[OFF + 14]), "+f"(d[OFF + 15]), "+f"(d[OFF + 16]), "+f"(d[OFF + 17]),
        "+f"(d[OFF + 18]), "+f"(d[OFF + 19]), "+f"(d[OFF + 20]), "+f"(d[OFF + 21]), "+f"(d[OFF + 22]), "+f"(d[OFF + 23]),
        "+f"(d[OFF + 24]), "+f"(d[OFF + 25]), "+f"(d[OFF + 26]), "+f"(d[OFF + 27]), "+f"(d[OFF + 28]), "+f"(d[OFF + 29]),
        "+f"(d[OFF + 30]), "+f"(d[OFF + 31])
      : "l"(desc_a), "l"(desc_b), "r"(scale_d));
}

template <int OFF, int NN>
__device__ __forceinline__ void wg_m64tz(float (&d)[NN], uint64_t desc_a, uint64_t desc_b, int scale_d) {
  asm volatile(
      "{\n.reg .pred p;\nsetp.ne.b32 p, %34, 0;\n"
      "wgmma.mma_async.sync.aligned.m64n64k16.f32.bf16.bf16 "
      "{%0,%1,%2,%3,%4,%5,%6,%7,%8,%9,%10,%11,%12,%13,%14,%15,"
      "%16,%17,%18,%19,%20,%21,%22,%23,%24,%25,%26,%27,%28,%29,%30,%31}, "
      "%32, %33, p, 1, 1, 0, 1;\n}\n"
      : "=f"(d[OFF + 0]), "=f"(d[OFF + 1]), "=f"(d[OFF + 2]), "=f"(d[OFF + 3]), "=f"(d[OFF + 4]), "=f"(d[OFF + 5]),
        "=f"(d[OFF + 6]), "=f"(d[OFF + 7]), "=f"(d[OFF + 8]), "=f"(d[OFF + 9]), "=f"(d[OFF + 10]), "=f"(d[OFF + 11]),
        "=f"(d[OFF + 12]), "=f"(d[OFF + 13]), "=f"(d[OFF + 14]), "=f"(d[OFF + 15]), "=f"(d[OFF + 16]), "=f"(d[OFF + 17]),
        "=f"(d[OFF + 18]), "=f"(d[OFF + 19]), "=f"(d[OFF + 20]), "=f"(d[OFF + 21]), "=f"(d[OFF + 22]), "=f"(d[OFF + 23]),
        "=f"(d[OFF + 24]), "=f"(d[OFF + 25]), "=f"(d[OFF + 26]), "=f"(d[OFF + 27]), "=f"(d[OFF + 28]), "=f"(d[OFF + 29]),
        "=f"(d[OFF + 30]), "=f"(d[OFF + 31])
      : "l"(desc_a), "l"(desc_b), "r"(scale_d));
}

template <int OFF, int NN>
__device__ __forceinline__ void wg_d96(float (&d)[NN], uint32_t a0, uint32_t a1, uint32_t a2, uint32_t a3,
                                       uint64_t desc_b, int scale_d) {
  asm volatile(
      "{\n.reg .pred p;\nsetp.ne.b32 p, %53, 0;\n"
      "wgmma.mma_async.sync.aligned.m64n96k16.f32.bf16.bf16 "
      "{%0,%1,%2,%3,%4,%5,%6,%7,%8,%9,%10,%11,%12,%13,%14,%15,"
      "%16,%17,%18,%19,%20,%21,%22,%23,%24,%25,%26,%27,%28,%29,%30,%31,"
      "%32,%33,%34,%35,%36,%37,%38,%39,%40,%41,%42,%43,%44,%45,%46,%47}, "
      "{%48,%49,%50,%51}, %52, p, 1, 1, 0;\n}\n"
      : "+f"(d[OFF + 0]), "+f"(d[OFF + 1]), "+f"(d[OFF + 2]), "+f"(d[OFF + 3]), "+f"(d[OFF + 4]), "+f"(d[OFF + 5]),
        "+f"(d[OFF + 6]), "+f"(d[OFF + 7]), "+f"(d[OFF + 8]), "+f"(d[OFF + 9]), "+f"(d[OFF + 10]), "+f"(d[OFF + 11]),
        "+f"(d[OFF + 12]), "+f"(d[OFF + 13]), "+f"(d[OFF + 14]), "+f"(d[OFF + 15]), "+f"(d[OFF + 16]), "+f"(d[OFF + 17]),
        "+f"(d[OFF + 18]), "+f"(d[OFF + 19]), "+f"(d[OFF + 20]), "+f"(d[OFF + 21]), "+f"(d[OFF + 22]), "+f"(d[OFF + 23]),
        "+f"(d[OFF + 24]), "+f"(d[OFF + 25]), "+f"(d[OFF + 26]), "+f"(d[OFF + 27]), "+f"(d[OFF + 28]), "+f"(d[OFF + 29]),
        "+f"(d[OFF + 30]), "+f"(d[OFF + 31]), "+f"(d[OFF + 32]), "+f"(d[OFF + 33]), "+f"(d[OFF + 34]), "+f"(d[OFF + 35]),
        "+f"(d[OFF + 36]), "+f"(d[OFF + 37]), "+f"(d[OFF + 38]), "+f"(d[OFF + 39]), "+f"(d[OFF + 40]), "+f"(d[OFF + 41]),
        "+f"(d[OFF + 42]), "+f"(d[OFF + 43]), "+f"(d[OFF + 44]), "+f"(d[OFF + 45]), "+f"(d[OFF + 46]), "+f"(d[OFF + 47])
      : "r"(a0), "r"(a1), "r"(a2), "r"(a3), "l"(desc_b), "r"(scale_d));
}

template <int OFF, int NN>
__device__ __forceinline__ void wg_d96z(float (&d)[NN], uint32_t a0, uint32_t a1, uint32_t a2, uint32_t a3,
                                       uint64_t desc_b, int scale_d) {
  asm volatile(
      "{\n.reg .pred p;\nsetp.ne.b32 p, %53, 0;\n"
      "wgmma.mma_async.sync.aligned.m64n96k16.f32.bf16.bf16 "
      "{%0,%1,%2,%3,%4,%5,%6,%7,%8,%9,%10,%11,%12,%13,%14,%15,"
      "%16,%17,%18,%19,%20,%21,%22,%23,%24,%25,%26,%27,%28,%29,%30,%31,"
      "%32,%33,%34,%35,%36,%37,%38,%39,%40,%41,%42,%43,%44,%45,%46,%47}, "
      "{%48,%49,%50,%51}, %52, p, 1, 1, 0;\n}\n"
      : "=f"(d[OFF + 0]), "=f"(d[OFF + 1]), "=f"(d[OFF + 2]), "=f"(d[OFF + 3]), "=f"(d[OFF + 4]), "=f"(d[OFF + 5]),
        "=f"(d[OFF + 6]), "=f"(d[OFF + 7]), "=f"(d[OFF + 8]), "=f"(d[OFF + 9]), "=f"(d[OFF + 10]), "=f"(d[OFF + 11]),
        "=f"(d[OFF + 12]), "=f"(d[OFF + 13]), "=f"(d[OFF + 14]), "=f"(d[OFF + 15]), "=f"(d[OFF + 16]), "=f"(d[OFF + 17]),
        "=f"(d[OFF + 18]), "=f"(d[OFF + 19]), "=f"(d[OFF + 20]), "=f"(d[OFF + 21]), "=f"(d[OFF + 22]), "=f"(d[OFF + 23]),
        "=f"(d[OFF + 24]), "=f"(d[OFF + 25]), "=f"(d[OFF + 26]), "=f"(d[OFF + 27]), "=f"(d[OFF + 28]), "=f"(d[OFF + 29]),
        "=f"(d[OFF + 30]), "=f"(d[OFF + 31]), "=f"(d[OFF + 32]), "=f"(d[OFF + 33]), "=f"(d[OFF + 34]), "=f"(d[OFF + 35]),
        "=f"(d[OFF + 36]), "=f"(d[OFF + 37]), "=f"(d[OFF + 38]), "=f"(d[OFF + 39]), "=f"(d[OFF + 40]), "=f"(d[OFF + 41]),
        "=f"(d[OFF + 42]), "=f"(d[OFF + 43]), "=f"(d[OFF + 44]), "=f"(d[OFF + 45]), "=f"(d[OFF + 46]), "=f"(d[OFF + 47])
      : "r"(a0), "r"(a1), "r"(a2), "r"(a3), "l"(desc_b), "r"(scale_d));
}

template <int OFF, int NN>
__device__ __forceinline__ void wg_s104(float (&d)[NN], uint32_t a0, uint32_t a1, uint32_t a2, uint32_t a3,
                                       uint64_t desc_b, int scale_d, uint32_t meta) {
  asm volatile(
      "{\n.reg .pred p;\nsetp.ne.b32 p, %57, 0;\n"
      "wgmma.mma_async.sp.sync.aligned.m64n104k32.f32.bf16.bf16 "
      "{%0,%1,%2,%3,%4,%5,%6,%7,%8,%9,%10,%11,%12,%13,%14,%15,"
      "%16,%17,%18,%19,%20,%21,%22,%23,%24,%25,%26,%27,%28,%29,%30,%31,"
      "%32,%33,%34,%35,%36,%37,%38,%39,%40,%41,%42,%43,%44,%45,%46,%47,"
      "%48,%49,%50,%51}, "
      "{%52,%53,%54,%55}, %56, %58, 0, p, 1, 1, 0;\n}\n"
      : "+f"(d[OFF + 0]), "+f"(d[OFF + 1]), "+f"(d[OFF + 2]), "+f"(d[OFF + 3]), "+f"(d[OFF + 4]), "+f"(d[OFF + 5]),
        "+f"(d[OFF + 6]), "+f"(d[OFF + 7]), "+f"(d[OFF + 8]), "+f"(d[OFF + 9]), "+f"(d[OFF + 10]), "+f"(d[OFF + 11]),
        "+f"(d[OFF + 12]), "+f"(d[OFF + 13]), "+f"(d[OFF + 14]), "+f"(d[OFF + 15]), "+f"(d[OFF + 16]), "+f"(d[OFF + 17]),
        "+f"(d[OFF + 18]), "+f"(d[OFF + 19]), "+f"(d[OFF + 20]), "+f"(d[OFF + 21]), "+f"(d[OFF + 22]), "+f"(d[OFF + 23]),
        "+f"(d[OFF + 24]), "+f"(d[OFF + 25]), "+f"(d[OFF + 26]), "+f"(d[OFF + 27]), "+f"(d[OFF + 28]), "+f"(d[OFF + 29]),
        "+f"(d[OFF + 30]), "+f"(d[OFF + 31]), "+f"(d[OFF + 32]), "+f"(d[OFF + 33]), "+f"(d[OFF + 34]), "+f"(d[OFF + 35]),
        "+f"(d[OFF + 36]), "+f"(d[OFF + 37]), "+f"(d[OFF + 38]), "+f"(d[OFF + 39]), "+f"(d[OFF + 40]), "+f"(d[OFF + 41]),
        "+f"(d[OFF + 42]), "+f"(d[OFF + 43]), "+f"(d[OFF + 44]), "+f"(d[OFF + 45]), "+f"(d[OFF + 46]), "+f"(d[OFF + 47]),
        "+f"(d[OFF + 48]), "+f"(d[OFF + 49]), "+f"(d[OFF + 50]), "+f"(d[OFF + 51])
      : "r"(a0), "r"(a1), "r"(a2), "r"(a3), "l"(desc_b), "r"(scale_d), "r"(meta));
}

template <int OFF, int NN>
__device__ __forceinline__ void wg_s104z(float (&d)[NN], uint32_t a0, uint32_t a1, uint32_t a2, uint32_t a3,
                                       uint64_t desc_b, int scale_d, uint32_t meta) {
  asm volatile(
      "{\n.reg .pred p;\nsetp.ne.b32 p, %57, 0;\n"
      "wgmma.mma_async.sp.sync.aligned.m64n104k32.f32.bf16.bf16 "
      "{%0,%1,%2,%3,%4,%5,%6,%7,%8,%9,%10,%11,%12,%13,%14,%15,"
      "%16,%17,%18,%19,%20,%21,%22,%23,%24,%25,%26,%27,%28,%29,%30,%31,"
      "%32,%33,%34,%35,%36,%37,%38,%39,%40,%41,%42,%43,%44,%45,%46,%47,"
      "%48,%49,%50,%51}, "
      "{%52,%53,%54,%55}, %56, %58, 0, p, 1, 1, 0;\n}\n"
      : "=f"(d[OFF + 0]), "=f"(d[OFF + 1]), "=f"(d[OFF + 2]), "=f"(d[OFF + 3]), "=f"(d[OFF + 4]), "=f"(d[OFF + 5]),
        "=f"(d[OFF + 6]), "=f"(d[OFF + 7]), "=f"(d[OFF + 8]), "=f"(d[OFF + 9]), "=f"(d[OFF + 10]), "=f"(d[OFF + 11]),
        "=f"(d[OFF + 12]), "=f"(d[OFF + 13]), "=f"(d[OFF + 14]), "=f"(d[OFF + 15]), "=f"(d[OFF + 16]), "=f"(d[OFF + 17]),
        "=f"(d[OFF + 18]), "=f"(d[OFF + 19]), "=f"(d[OFF + 20]), "=f"(d[OFF + 21]), "=f"(d[OFF + 22]), "=f"(d[OFF + 23]),
        "=f"(d[OFF + 24]), "=f"(d[OFF + 25]), "=f"(d[OFF + 26]), "=f"(d[OFF + 27]), "=f"(d[OFF + 28]), "=f"(d[OFF + 29]),
        "=f"(d[OFF + 30]), "=f"(d[OFF + 31]), "=f"(d[OFF + 32]), "=f"(d[OFF + 33]), "=f"(d[OFF + 34]), "=f"(d[OFF + 35]),
        "=f"(d[OFF + 36]), "=f"(d[OFF + 37]), "=f"(d[OFF + 38]), "=f"(d[OFF + 39]), "=f"(d[OFF + 40]), "=f"(d[OFF + 41]),
        "=f"(d[OFF + 42]), "=f"(d[OFF + 43]), "=f"(d[OFF + 44]), "=f"(d[OFF + 45]), "=f"(d[OFF + 46]), "=f"(d[OFF + 47]),
        "=f"(d[OFF + 48]), "=f"(d[OFF + 49]), "=f"(d[OFF + 50]), "=f"(d[OFF + 51])
      : "r"(a0), "r"(a1), "r"(a2), "r"(a3), "l"(desc_b), "r"(scale_d), "r"(meta));
}

template <int OFF, int NN>
__device__ __forceinline__ void wg_s48(float (&d)[NN], uint32_t a0, uint32_t a1, uint32_t a2, uint32_t a3,
                                       uint64_t desc_b, int scale_d, uint32_t meta) {
  asm volatile(
      "{\n.reg .pred p;\nsetp.ne.b32 p, %29, 0;\n"
      "wgmma.mma_async.sp.sync.aligned.m64n48k32.f32.bf16.bf16 "
      "{%0,%1,%2,%3,%4,%5,%6,%7,%8,%9,%10,%11,%12,%13,%14,%15,"
      "%16,%17,%18,%19,%20,%21,%22,%23}, "
      "{%24,%25,%26,%27}, %28, %30, 0, p, 1, 1, 0;\n}\n"
      : "+f"(d[OFF + 0]), "+f"(d[OFF + 1]), "+f"(d[OFF + 2]), "+f"(d[OFF + 3]), "+f"(d[OFF + 4]), "+f"(d[OFF + 5]),
        "+f"(d[OFF + 6]), "+f"(d[OFF + 7]), "+f"(d[OFF + 8]), "+f"(d[OFF + 9]), "+f"(d[OFF + 10]), "+f"(d[OFF + 11]),
        "+f"(d[OFF + 12]), "+f"(d[OFF + 13]), "+f"(d[OFF + 14]), "+f"(d[OFF + 15]), "+f"(d[OFF + 16]), "+f"(d[OFF + 17]),
        "+f"(d[OFF + 18]), "+f"(d[OFF + 19]), "+f"(d[OFF + 20]), "+f"(d[OFF + 21]), "+f"(d[OFF + 22]), "+f"(d[OFF + 23])
      : "r"(a0), "r"(a1), "r"(a2), "r"(a3), "l"(desc_b), "r"(scale_d), "r"(meta));
}

template <int OFF, int NN>
__device__ __forceinline__ void wg_s48z(float (&d)[NN], uint32_t a0, uint32_t a1, uint32_t a2, uint32_t a3,
                                       uint64_t desc_b, int scale_d, uint32_t meta) {
  asm volatile(
      "{\n.reg .pred p;\nsetp.ne.b32 p, %29, 0;\n"
      "wgmma.mma_async.sp.sync.aligned.m64n48k32.f32.bf16.bf16 "
      "{%0,%1,%2,%3,%4,%5,%6,%7,%8,%9,%10,%11,%12,%13,%14,%15,"
      "%16,%17,%18,%19,%20,%21,%22,%23}, "
      "{%24,%25,%26,%27}, %28, %30, 0, p, 1, 1, 0;\n}\n"
      : "=f"(d[OFF + 0]), "=f"(d[OFF + 1]), "=f"(d[OFF + 2]), "=f"(d[OFF + 3]), "=f"(d[OFF + 4]), "=f"(d[OFF + 5]),
        "=f"(d[OFF + 6]), "=f"(d[OFF + 7]), "=f"(d[OFF + 8]), "=f"(d[OFF + 9]), "=f"(d[OFF + 10]), "=f"(d[OFF + 11]),
        "=f"(d[OFF + 12]), "=f"(d[OFF + 13]), "=f"(d[OFF + 14]), "=f"(d[OFF + 15]), "=f"(d[OFF + 16]), "=f"(d[OFF + 17]),
        "=f"(d[OFF + 18]), "=f"(d[OFF + 19]), "=f"(d[OFF + 20]), "=f"(d[OFF + 21]), "=f"(d[OFF + 22]), "=f"(d[OFF + 23])
      : "r"(a0), "r"(a1), "r"(a2), "r"(a3), "l"(desc_b), "r"(scale_d), "r"(meta));
}

template <int OFF, int NN>
__device__ __forceinline__ void wg_s56(float (&d)[NN], uint32_t a0, uint32_t a1, uint32_t a2, uint32_t a3,
                                       uint64_t desc_b, int scale_d, uint32_t meta) {
  asm volatile(
      "{\n.reg .pred p;\nsetp.ne.b32 p, %33, 0;\n"
      "wgmma.mma_async.sp.sync.aligned.m64n56k32.f32.bf16.bf16 "
      "{%0,%1,%2,%3,%4,%5,%6,%7,%8,%9,%10,%11,%12,%13,%14,%15,"
      "%16,%17,%18,%19,%20,%21,%22,%23,%24,%25,%26,%27}, "
      "{%28,%29,%30,%31}, %32, %34, 0, p, 1, 1, 0;\n}\n"
      : "+f"(d[OFF + 0]), "+f"(d[OFF + 1]), "+f"(d[OFF + 2]), "+f"(d[OFF + 3]), "+f"(d[OFF + 4]), "+f"(d[OFF + 5]),
        "+f"(d[OFF + 6]), "+f"(d[OFF + 7]), "+f"(d[OFF + 8]), "+f"(d[OFF + 9]), "+f"(d[OFF + 10]), "+f"(d[OFF + 11]),
        "+f"(d[OFF + 12]), "+f"(d[OFF + 13]), "+f"(d[OFF + 14]), "+f"(d[OFF + 15]), "+f"(d[OFF + 16]), "+f"(d[OFF + 17]),
        "+f"(d[OFF + 18]), "+f"(d[OFF + 19]), "+f"(d[OFF + 20]), "+f"(d[OFF + 21]), "+f"(d[OFF + 22]), "+f"(d[OFF + 23]),
        "+f"(d[OFF + 24]), "+f"(d[OFF + 25]), "+f"(d[OFF + 26]), "+f"(d[OFF + 27])
      : "r"(a0), "r"(a1), "r"(a2), "r"(a3), "l"(desc_b), "r"(scale_d), "r"(meta));
}

template <int OFF, int NN>
__device__ __forceinline__ void wg_s56z(float (&d)[NN], uint32_t a0, uint32_t a1, uint32_t a2, uint32_t a3,
                                       uint64_t desc_b, int scale_d, uint32_t meta) {
  asm volatile(
      "{\n.reg .pred p;\nsetp.ne.b32 p, %33, 0;\n"
      "wgmma.mma_async.sp.sync.aligned.m64n56k32.f32.bf16.bf16 "
      "{%0,%1,%2,%3,%4,%5,%6,%7,%8,%9,%10,%11,%12,%13,%14,%15,"
      "%16,%17,%18,%19,%20,%21,%22,%23,%24,%25,%26,%27}, "
      "{%28,%29,%30,%31}, %32, %34, 0, p, 1, 1, 0;\n}\n"
      : "=f"(d[OFF + 0]), "=f"(d[OFF + 1]), "=f"(d[OFF + 2]), "=f"(d[OFF + 3]), "=f"(d[OFF + 4]), "=f"(d[OFF + 5]),
        "=f"(d[OFF + 6]), "=f"(d[OFF + 7]), "=f"(d[OFF + 8]), "=f"(d[OFF + 9]), "=f"(d[OFF + 10]), "=f"(d[OFF + 11]),
        "=f"(d[OFF + 12]), "=f"(d[OFF + 13]), "=f"(d[OFF + 14]), "=f"(d[OFF + 15]), "=f"(d[OFF + 16]), "=f"(d[OFF + 17]),
        "=f"(d[OFF + 18]), "=f"(d[OFF + 19]), "=f"(d[OFF + 20]), "=f"(d[OFF + 21]), "=f"(d[OFF + 22]), "=f"(d[OFF + 23]),
        "=f"(d[OFF + 24]), "=f"(d[OFF + 25]), "=f"(d[OFF + 26]), "=f"(d[OFF + 27])
      : "r"(a0), "r"(a1), "r"(a2), "r"(a3), "l"(desc_b), "r"(scale_d), "r"(meta));
}

template <int OFF, int NN>
__device__ __forceinline__ void wg_s64t(float (&d)[NN], uint32_t a0, uint32_t a1, uint32_t a2, uint32_t a3,
                                       uint64_t desc_b, int scale_d, uint32_t meta) {
  asm volatile(
      "{\n.reg .pred p;\nsetp.ne.b32 p, %37, 0;\n"
      "wgmma.mma_async.sp.sync.aligned.m64n64k32.f32.bf16.bf16 "
      "{%0,%1,%2,%3,%4,%5,%6,%7,%8,%9,%10,%11,%12,%13,%14,%15,"
      "%16,%17,%18,%19,%20,%21,%22,%23,%24,%25,%26,%27,%28,%29,%30,%31}, "
      "{%32,%33,%34,%35}, %36, %38, 0, p, 1, 1, 1;\n}\n"
      : "+f"(d[OFF + 0]), "+f"(d[OFF + 1]), "+f"(d[OFF + 2]), "+f"(d[OFF + 3]), "+f"(d[OFF + 4]), "+f"(d[OFF + 5]),
        "+f"(d[OFF + 6]), "+f"(d[OFF + 7]), "+f"(d[OFF + 8]), "+f"(d[OFF + 9]), "+f"(d[OFF + 10]), "+f"(d[OFF + 11]),
        "+f"(d[OFF + 12]), "+f"(d[OFF + 13]), "+f"(d[OFF + 14]), "+f"(d[OFF + 15]), "+f"(d[OFF + 16]), "+f"(d[OFF + 17]),
        "+f"(d[OFF + 18]), "+f"(d[OFF + 19]), "+f"(d[OFF + 20]), "+f"(d[OFF + 21]), "+f"(d[OFF + 22]), "+f"(d[OFF + 23]),
        "+f"(d[OFF + 24]), "+f"(d[OFF + 25]), "+f"(d[OFF + 26]), "+f"(d[OFF + 27]), "+f"(d[OFF + 28]), "+f"(d[OFF + 29]),
        "+f"(d[OFF + 30]), "+f"(d[OFF + 31])
      : "r"(a0), "r"(a1), "r"(a2), "r"(a3), "l"(desc_b), "r"(scale_d), "r"(meta));
}

template <int OFF, int NN>
__device__ __forceinline__ void wg_s64t1(float (&d)[NN], uint32_t a0, uint32_t a1, uint32_t a2, uint32_t a3,
                                       uint64_t desc_b, int scale_d, uint32_t meta) {
  asm volatile(
      "{\n.reg .pred p;\nsetp.ne.b32 p, %37, 0;\n"
      "wgmma.mma_async.sp.sync.aligned.m64n64k32.f32.bf16.bf16 "
      "{%0,%1,%2,%3,%4,%5,%6,%7,%8,%9,%10,%11,%12,%13,%14,%15,"
      "%16,%17,%18,%19,%20,%21,%22,%23,%24,%25,%26,%27,%28,%29,%30,%31}, "
      "{%32,%33,%34,%35}, %36, %38, 1, p, 1, 1, 1;\n}\n"
      : "+f"(d[OFF + 0]), "+f"(d[OFF + 1]), "+f"(d[OFF + 2]), "+f"(d[OFF + 3]), "+f"(d[OFF + 4]), "+f"(d[OFF + 5]),
        "+f"(d[OFF + 6]), "+f"(d[OFF + 7]), "+f"(d[OFF + 8]), "+f"(d[OFF + 9]), "+f"(d[OFF + 10]), "+f"(d[OFF + 11]),
        "+f"(d[OFF + 12]), "+f"(d[OFF + 13]), "+f"(d[OFF + 14]), "+f"(d[OFF + 15]), "+f"(d[OFF + 16]), "+f"(d[OFF + 17]),
        "+f"(d[OFF + 18]), "+f"(d[OFF + 19]), "+f"(d[OFF + 20]), "+f"(d[OFF + 21]), "+f"(d[OFF + 22]), "+f"(d[OFF + 23]),
        "+f"(d[OFF + 24]), "+f"(d[OFF + 25]), "+f"(d[OFF + 26]), "+f"(d[OFF + 27]), "+f"(d[OFF + 28]), "+f"(d[OFF + 29]),
        "+f"(d[OFF + 30]), "+f"(d[OFF + 31])
      : "r"(a0), "r"(a1), "r"(a2), "r"(a3), "l"(desc_b), "r"(scale_d), "r"(meta));
}

template <int OFF, int NN>
__device__ __forceinline__ void wg_s64tz(float (&d)[NN], uint32_t a0, uint32_t a1, uint32_t a2, uint32_t a3,
                                       uint64_t desc_b, int scale_d, uint32_t meta) {
  asm volatile(
      "{\n.reg .pred p;\nsetp.ne.b32 p, %37, 0;\n"
      "wgmma.mma_async.sp.sync.aligned.m64n64k32.f32.bf16.bf16 "
      "{%0,%1,%2,%3,%4,%5,%6,%7,%8,%9,%10,%11,%12,%13,%14,%15,"
      "%16,%17,%18,%19,%20,%21,%22,%23,%24,%25,%26,%27,%28,%29,%30,%31}, "
      "{%32,%33,%34,%35}, %36, %38, 0, p, 1, 1, 1;\n}\n"
      : "=f"(d[OFF + 0]), "=f"(d[OFF + 1]), "=f"(d[OFF + 2]), "=f"(d[OFF + 3]), "=f"(d[OFF + 4]), "=f"(d[OFF + 5]),
        "=f"(d[OFF + 6]), "=f"(d[OFF + 7]), "=f"(d[OFF + 8]), "=f"(d[OFF + 9]), "=f"(d[OFF + 10]), "=f"(d[OFF + 11]),
        "=f"(d[OFF + 12]), "=f"(d[OFF + 13]), "=f"(d[OFF + 14]), "=f"(d[OFF + 15]), "=f"(d[OFF + 16]), "=f"(d[OFF + 17]),
        "=f"(d[OFF + 18]), "=f"(d[OFF + 19]), "=f"(d[OFF + 20]), "=f"(d[OFF + 21]), "=f"(d[OFF + 22]), "=f"(d[OFF + 23]),
        "=f"(d[OFF + 24]), "=f"(d[OFF + 25]), "=f"(d[OFF + 26]), "=f"(d[OFF + 27]), "=f"(d[OFF + 28]), "=f"(d[OFF + 29]),
        "=f"(d[OFF + 30]), "=f"(d[OFF + 31])
      : "r"(a0), "r"(a1), "r"(a2), "r"(a3), "l"(desc_b), "r"(scale_d), "r"(meta));
}

__device__ __forceinline__ int g2_inv(int ch) { return 32 * (ch >> 5) + 8 * ((ch >> 1) & 3) + 2 * ((ch >> 3) & 3) + (ch & 1); }
__host__ __device__ __forceinline__ uint32_t wimg_off(int n, int k) {
  return (uint32_t)(k >> 6) * kWChunk + (uint32_t)n * 128 + (uint32_t)((((k & 63) >> 3) ^ (n & 7)) << 4) + (k & 7) * 2;
}
__host__ __device__ constexpr int w2piece(int h, int c) { return c == 2 ? 2 + h : 4 * h + c; }
__device__ __forceinline__ uint32_t w2img_off(int n, int k) { return wimg_off(n % 96, k & 63) + w2piece(n >= 96, k >> 6) * (kWChunk / 2); }
__device__ __forceinline__ int qpix(int par, int t) {
  const int a = 2 * t + 13 * par - 6, b = t + 112 * par;
  return par ? min(a, b) : max(a, b);
}
__device__ __forceinline__ int woff(int par, int i, int r) {
  const int a = 99 * par + 6 - 8 * i;
  return par ? min(r, a) : max(r, a);
}

__device__ __forceinline__ void mma16816(float (&c)[4], uint32_t a0, uint32_t a1, uint32_t a2, uint32_t a3, uint32_t b0,
                                         uint32_t b1) {
  asm volatile(
      "mma.sync.aligned.m16n8k16.row.col.f32.bf16.bf16.f32 {%0,%1,%2,%3}, {%4,%5,%6,%7}, {%8,%9}, {%0,%1,%2,%3};"
      : "+f"(c[0]), "+f"(c[1]), "+f"(c[2]), "+f"(c[3])
      : "r"(a0), "r"(a1), "r"(a2), "r"(a3), "r"(b0), "r"(b1));
}

__device__ __forceinline__ void fold_w1(const int u, const __nv_bfloat16* __restrict__ wqkv, uint8_t* wimg) {
  const int g = (threadIdx.x >> 2) & 7, l = threadIdx.x & 3;
  const int m0 = (u / 12) * 16, s = u % 12;
  uint4 A[12], B[12];
  const __nv_bfloat16* arow = wqkv + (m0 + 4 * (g >> 1) + (g & 1)) * 576 + 192 + 8 * l;
  const __nv_bfloat16* brow = wqkv + (16 * s + 4 * (g >> 1) + (g & 1)) * 576 + 8 * l;
#pragma unroll
  for (int i = 0; i < 12; i++) {
    A[i] = ldg128_nc(arow + (i & 1) * 2 * 576 + 32 * (i >> 1));
    B[i] = ldg128_nc(brow + (i & 1) * 2 * 576 + 32 * (i >> 1));
  }
  sched_fence();
  uint8_t* dst = wimg + wimg_off(m0 + g, 16 * s + 4 * l);
  float acc[4][4];
#pragma unroll
  for (int j = 0; j < 16; j++) acc[j >> 2][j & 3] = 0.f;
#pragma unroll
  for (int i = 0; i < 6; i++) {
    const uint4 &a0 = A[2 * i], &a1 = A[2 * i + 1];
#pragma unroll
    for (int nb = 0; nb < 2; nb++) {
      mma16816(acc[2 * nb], a0.x, a1.x, a0.y, a1.y, B[2 * i + nb].x, B[2 * i + nb].y);
      mma16816(acc[2 * nb + 1], a0.z, a1.z, a0.w, a1.w, B[2 * i + nb].z, B[2 * i + nb].w);
    }
  }
#pragma unroll
  for (int j = 0; j < 2; j++) {
    const uint2 v = make_uint2(pack_bf16((acc[0][2 * j] + acc[1][2 * j]) * kAlpha, (acc[0][2 * j + 1] + acc[1][2 * j + 1]) * kAlpha),
                               pack_bf16((acc[2][2 * j] + acc[3][2 * j]) * kAlpha, (acc[2][2 * j + 1] + acc[3][2 * j + 1]) * kAlpha));
    asm volatile("st.relaxed.gpu.global.v2.u32 [%0], {%1,%2};" ::"l"(dst + j * 1024), "r"(v.x), "r"(v.y) : "memory");
  }
}
__device__ __forceinline__ void fold_w2(const int u, const __nv_bfloat16* __restrict__ wqkv, const __nv_bfloat16* __restrict__ wo,
                                        uint8_t* wimg) {
  const int g = (threadIdx.x >> 2) & 7, l = threadIdx.x & 3;
  const int m0 = (u / 12) * 32, n0 = (u % 12) * 16;
  uint4 S[12];
  uint32_t L[96];
  const __nv_bfloat16* brow = wqkv + (n0 + 4 * (g >> 1) + (g & 1)) * 576 + 384 + 8 * l;
#pragma unroll
  for (int i = 0; i < 12; i++) S[i] = ldg128_nc(brow + (i & 1) * 2 * 576 + 32 * (i >> 1));
  const __nv_bfloat16* acol = wo + (8 * l) * 192 + m0 + 4 * g;
#pragma unroll
  for (int c = 0; c < 48; c++)
    asm volatile("ld.global.nc.v2.u32 {%0,%1}, [%2];" : "=r"(L[2 * c]), "=r"(L[2 * c + 1]) : "l"(acol + (32 * (c >> 3) + (c & 7)) * 192));
  const uint32_t off = w2_offset();
  sched_fence();
  uint8_t* img = wimg + off;
  float acc[4][4];
#pragma unroll
  for (int j = 0; j < 16; j++) acc[j >> 2][j & 3] = 0.f;
#pragma unroll
  for (int i = 0; i < 6; i++) {
#pragma unroll
    for (int h = 0; h < 2; h++) {
      const uint4 &s0 = S[2 * i], &s1 = S[2 * i + 1];
#pragma unroll
      for (int mt = 0; mt < 2; mt++) {
        const uint32_t* a = L + 16 * i + 8 * h + mt;
        const uint32_t a0 = __byte_perm(a[0], a[2], 0x5410), a1 = __byte_perm(a[0], a[2], 0x7632);
        const uint32_t a2 = __byte_perm(a[4], a[6], 0x5410), a3 = __byte_perm(a[4], a[6], 0x7632);
        mma16816(acc[2 * mt], a0, a1, a2, a3, h ? s0.z : s0.x, h ? s0.w : s0.y);
        mma16816(acc[2 * mt + 1], a0, a1, a2, a3, h ? s1.z : s1.x, h ? s1.w : s1.y);
      }
    }
  }
#pragma unroll
  for (int j = 0; j < 4; j++) {
    const float(&c0)[4] = acc[j & 2];
    const float(&c1)[4] = acc[(j & 2) + 1];
    asm volatile("st.relaxed.gpu.global.v2.u32 [%0], {%1,%2};" ::"l"(img + w2img_off(g2_inv(m0 + 4 * g + j), n0 + 4 * l)),
                 "r"(pack_bf16(c0[2 * (j & 1)], c0[2 * (j & 1) + 1])), "r"(pack_bf16(c1[2 * (j & 1)], c1[2 * (j & 1) + 1])) : "memory");
  }
}

__global__ void __launch_bounds__(256) fold_kernel(const __nv_bfloat16* __restrict__ wqkv,
                                                   const __nv_bfloat16* __restrict__ wo, uint8_t* wimg) {
  const int u = blockIdx.x * 8 + (threadIdx.x >> 5);
  if (u < 144) fold_w1(u, wqkv, wimg);
  else fold_w2(u - 144, wqkv, wo, wimg);
}

struct TileCoord { int pr, pc, I, J, up, kind; };
struct TileTable { uint16_t e[kCtas * 6], g[6][8][2]; };
inline void make_tiles(TileTable& tt) {
  for (int tile = 0; tile < kCtas * 6; tile++) {
    const int b = tile / 6, k = tile - 6 * b;
    const int p = b < 128 ? (tile - 672) >> 1 : b - 80;
    const int strip = b < 112 ? b >> 1 : b >= 128 && k >= 2 ? (b & 1) * 27 + (b & 2) * 14 : p + (p < 26 ? 1 : 3);
    const int pr = strip >= 28, J = (strip - pr * 28) >> 1, pc = strip & 1, up = b < 112 ? b & 1 : pr;
    const int first = b < 112 ? 8 - 2 * pr - up : 13 * pr, step = b < 112 ? k : k & 1;
    const int I = up ? first - step : first + step;
    const int kind = b < 112 ? (J == 13 * pc ? 1 + pc : 0) : I == 13 * pr ? 4 + pr : b >= 128 && k >= 2 ? 3 : 0;
    tt.e[tile] = (uint16_t)(I | J << 4 | pr << 8 | pc << 9 | up << 10 | kind << 11);
  }
  for (int kind = 0; kind < 6; kind++)
    for (int j = 0; j < 8; j++) {
      const int w = j >> 1, h = j & 1, e = kind % 3;
      auto off = [e](int t) { return e == 0 ? 2 * t : e == 1 ? t + (t == 7) : t + (t > 0); };
      tt.g[kind][j][0] = (uint16_t)(kind < 3 ? 3 * off(w + 4 * h) : 3 * (kW * off(2 * w) + 8 * h));
      tt.g[kind][j][1] = (uint16_t)(128 * (kind < 3 ? kind > 0 : 1 + off(2 * w + 1) - off(2 * w)));
    }
}
__device__ __forceinline__ int num_tiles() { return blockIdx.x < 128 ? 6 : 4; }
__device__ __forceinline__ TileCoord decode_tile(const TileTable& tt, int tile) {
  const uint32_t e = tt.e[tile];
  return TileCoord{(int)(e >> 8) & 1, (int)(e >> 9) & 1, (int)e & 15, (int)(e >> 4) & 15, (int)(e >> 10) & 1, (int)(e >> 11)};
}
__device__ __forceinline__ int halo_r0(const TileCoord& t) { return 8 * t.I + 6 * t.pr - 6; }
__device__ __forceinline__ int halo_c0(const TileCoord& t) { return min(max(8 * t.J + 6 * t.pc - 6, -3), 102); }

__device__ __forceinline__ uint32_t bar_full(uint32_t bars, int wg, int c) { return bars + (wg * 3 + c) * 8; }
__device__ __forceinline__ uint32_t bar_w1c(uint32_t bars, int c) { return bars + (6 + c) * 8; }
__device__ __forceinline__ uint32_t bar_w2(uint32_t bars) { return bars + 9 * 8; }
__device__ __forceinline__ uint32_t bar_x(uint32_t bars, int j) { return bars + (10 + j) * 8; }
__device__ __forceinline__ uint32_t bar_w1q(uint32_t bars) { return bars + 12 * 8; }
__device__ __forceinline__ uint32_t bar_xf(uint32_t bars) { return bars + 13 * 8; }
__device__ __forceinline__ uint32_t bar_w2m(uint32_t bars) { return bars + 14 * 8; }
__device__ __forceinline__ uint32_t bar_redo(uint32_t bars) { return bars + 15 * 8; }
__device__ __forceinline__ uint32_t bar_wok(uint32_t bars) { return bars + 16 * 8; }
__device__ __forceinline__ uint32_t bar_go(uint32_t bars) { return bars + 17 * 8; }
__device__ __forceinline__ uint32_t bar_raw(uint32_t bars, int j = 0) { return bars + (21 + j) * 8; }
__device__ __forceinline__ uint32_t bar_w2a(uint32_t bars) { return bars + 20 * 8; }
constexpr int kNumBars = 22;

__device__ __forceinline__ uint64_t wdesc(uint64_t d0, int s) { return d0 + (((s >> 2) * kWChunk + (s & 3) * 32) >> 4); }

__device__ __forceinline__ uint32_t out_slot(int k, int nt) { return k + 1 < nt ? kW2Off + (~k & 1) * 2 * kWChunk : kW1Off + kWChunk; }
__device__ __forceinline__ bool edge_strip() {
  const int s = blockIdx.x >> 1;
  return s == 0 || s == 27 || s == 28 || s == 55;
}
template <int I0, int I1>
__device__ __forceinline__ void store_rows(bool on, __nv_bfloat16* pA, __nv_bfloat16* pB, const uint32_t (&a)[24], const uint32_t (&b)[24]) {
#pragma unroll
  for (int i = 2 * I0; i < 2 * I1; i++) {
    const uint32_t* v = (i & 1 ? b : a) + 4 * (i >> 1);
    asm volatile("{\n.reg .pred p;\nsetp.ne.u32 p, %5, 0;\n@p st.global.v4.u32 [%0], {%1,%2,%3,%4};\n}\n" ::"l"((i & 1 ? pB : pA) + 32 * (i >> 1)),
                 "r"(v[0]), "r"(v[1]), "r"(v[2]), "r"(v[3]), "r"((uint32_t)on) : "memory");
  }
}
template <int I0, int I1>
__device__ __forceinline__ void stage_out(uint32_t sts, int wg, const uint32_t (&a)[24], const uint32_t (&b)[24]) {
  const uint32_t e = sts, o = sts ^ 64;
  const uint32_t ad[4] = {wg ? o + 1024 : e, wg ? e + 2048 : o, wg ? e : o + 1024, wg ? o : e + 2048};
#pragma unroll
  for (int i = I0; i < I1; i++) {
    const uint32_t* v = (i < 6 ? a : b) + 4 * (i % 6);
    asm volatile("st.shared.v4.u32 [%0], {%1,%2,%3,%4};" ::"r"(ad[i % 6 / 3 * 2 + (i % 3 == 1)] + (i % 3 == 2) * 1024 + (i / 6) * 12288),
                 "r"(v[0]), "r"(v[1]), "r"(v[2]), "r"(v[3]) : "memory");
  }
}
__device__ __forceinline__ uint32_t now_ns() {
  uint32_t t;
  asm volatile("mov.u32 %0, %globaltimer_lo;" : "=r"(t)::"memory");
  return t;
}
__device__ __forceinline__ void wait_clock(uint32_t t_start, uint32_t t) {
  while (now_ns() - t_start < t) { }
}
#define NAT_PRED(f, m) ".reg .pred p;\n.reg .b32 t;\nand.b32 t, " f ", " m ";\nsetp.ne.u32 p, t, 0;\n"
constexpr uint32_t kHiV = 1, kHiU = 8, kColB = 0x20, kInV = 0x100, kInU = 0x1000, kColA = 0x10000;
template <uint32_t M>
__device__ __forceinline__ float pick(const float* a, const float* b, uint32_t f) {
  float d;
  asm("{\n" NAT_PRED("%5", "%6") "add.f32 %0, %1, %2;\n@p add.f32 %0, %3, %4;\n}\n"
      : "=&f"(d) : "f"(a[0]), "f"(a[2]), "f"(b[0]), "f"(b[2]), "r"(f), "n"(M));
  return d;
}
template <uint32_t M>
__device__ __forceinline__ float sel(float a, float b, uint32_t f) {
  float d;
  asm("{\n" NAT_PRED("%3", "%4") "selp.f32 %0, %1, %2, p;\n}\n" : "=f"(d) : "f"(a), "f"(b), "r"(f), "n"(M));
  return d;
}
template <uint32_t M>
__device__ __forceinline__ void max_if(float& m, float v, uint32_t f) {
  asm("{\n" NAT_PRED("%2", "%3") "@p max.f32 %0, %0, %1;\n}\n" : "+f"(m) : "f"(v), "r"(f), "n"(M));
}
template <uint32_t M>
__device__ __forceinline__ void add_if(float& m, float v, uint32_t f) {
  asm("{\n" NAT_PRED("%2", "%3") "@p add.f32 %0, %0, %1;\n}\n" : "+f"(m) : "f"(v), "r"(f), "n"(M));
}
__device__ __forceinline__ void pick_v(const float* a, float* v, uint32_t f) {
  v[0] = pick<kHiV>(a, a + 16, f), v[1] = pick<kHiV>(a + 1, a + 17, f);
  v[2] = pick<kHiV * 2>(a + 4, a + 20, f), v[3] = pick<kHiV * 2>(a + 5, a + 21, f);
  v[4] = pick<kHiV * 4>(a + 8, a + 24, f), v[5] = pick<kHiV * 4>(a + 9, a + 25, f);
  v[6] = a[12] + a[14], v[7] = a[13] + a[15];
}
__device__ __forceinline__ void pick_u(const float* a, float* v, uint32_t f) {
#pragma unroll
  for (int c = 0; c < 3; c++) v[2 * c] = pick<kHiU>(a + 4 * c, a + 4 * c + 12, f), v[2 * c + 1] = pick<kHiU * 2>(a + 4 * c + 1, a + 4 * c + 13, f);
}
__device__ __forceinline__ uint32_t sign_bytes(uint32_t v, uint32_t sel) {
  uint32_t d;
  asm("prmt.b32 %0, %1, %1, %2;" : "=r"(d) : "r"(v), "r"(sel));
  return d;
}
__device__ __forceinline__ float own_max(const float (&v)[14], uint32_t f) {
  float m = sel<kInV>(fmaxf(v[0], v[1]), -INFINITY, f), m2 = sel<kInV * 2>(fmaxf(v[2], v[3]), -INFINITY, f);
  max_if<kInV * 4>(m, fmaxf(v[4], v[5]), f);
  max_if<kInV * 8>(m2, fmaxf(v[6], v[7]), f);
  max_if<kInU>(m, fmaxf(fmaxf(v[8], v[10]), v[12]), f);
  max_if<kInU * 2>(m2, fmaxf(fmaxf(v[9], v[11]), v[13]), f);
  return fmaxf(m, m2);
}
__device__ __forceinline__ float quad_max(float m) {
  const float a = __shfl_xor_sync(0xffffffffu, m, 1), b = __shfl_xor_sync(0xffffffffu, m, 2), c = __shfl_xor_sync(0xffffffffu, m, 3);
  return fmaxf(fmaxf(m, a), fmaxf(b, c));
}
__device__ __forceinline__ float row_rcp(const float (&v)[14], uint32_t f) {
  float s = sel<kInV>(v[0] + v[1], 0.f, f), s2 = sel<kInV * 2>(v[2] + v[3], 0.f, f);
  add_if<kInV * 4>(s, v[4] + v[5], f);
  add_if<kInV * 8>(s2, v[6] + v[7], f);
  add_if<kInU>(s, v[8] + v[10] + v[12], f);
  add_if<kInU * 2>(s2, v[9] + v[11] + v[13], f);
  s += s2;
  const float a = __shfl_xor_sync(0xffffffffu, s, 1), b = __shfl_xor_sync(0xffffffffu, s, 2), c = __shfl_xor_sync(0xffffffffu, s, 3);
  return rcp_approx((s + a) + (b + c));
}
__device__ __forceinline__ void route(const float (&v)[14], float s, const uint32_t (&rt)[9], uint32_t (&p)[14]) {
#pragma unroll
  for (int i = 0; i < 7; i++) {
    const uint32_t u = pack_bf16(v[2 * i] * s, v[2 * i + 1] * s);
    if (i < 4) p[i] = u & rt[i];
    if (i < 3) p[i + 4] = u & rt[i + 4];
    if (i >= 4) {
      p[i + 3] = u & rt[7];
      p[i + 6] = u & rt[8];
    }
  }
}

template <int C, int T0 = 0, int T1 = 7>
__device__ __forceinline__ void pv_chunk(float (&z)[32], const uint32_t (&pa)[14], const uint32_t (&pb)[14],
                                         const uint32_t (&meta)[4], uint64_t dV) {
#pragma unroll
  for (int t = T0; t < T1; t++) {
    if (t & 1)
      wg_s64t1<0, 32>(z, pa[2 * t], pb[2 * t], pa[2 * t + 1], pb[2 * t + 1], dV + ((2 * C * kChunkBytes + t * 2048) >> 4), 1,
                      meta[t >> 1]);
    else if (t > 0)
      wg_s64t<0, 32>(z, pa[2 * t], pb[2 * t], pa[2 * t + 1], pb[2 * t + 1], dV + ((2 * C * kChunkBytes + t * 2048) >> 4), 1,
                     meta[t >> 1]);
    else
      wg_s64tz<0, 32>(z, pa[0], pb[0], pa[1], pb[1], dV + ((2 * C * kChunkBytes) >> 4), 0, meta[0]);
  }
}
template <int C>
__device__ __forceinline__ void pack_z(const float (&z)[32], uint32_t (&za)[24], uint32_t (&zb)[24]) {
#pragma unroll
  for (int j = 0; j < 8; j++) {
    za[8 * C + j] = pack_bf16(z[4 * j], z[4 * j + 1]);
    zb[8 * C + j] = pack_bf16(z[4 * j + 2], z[4 * j + 3]);
  }
}

template <int H>
__device__ __forceinline__ void pack_out(const float (&ac)[48], uint32_t (&oa)[24], uint32_t (&ob)[24]) {
#pragma unroll
  for (int j = 0; j < 12; j++) {
    oa[12 * H + j] = pack_bf16(ac[4 * j], ac[4 * j + 1]);
    ob[12 * H + j] = pack_bf16(ac[4 * j + 2], ac[4 * j + 3]);
  }
}
struct Maps { CUtensorMap v6, v2, v14, u8, px[8], wv, wo; };
__device__ __forceinline__ void tma_prefetch_5d(const CUtensorMap* map, int c0, int c1, int c2, int c3, int c4) {
  asm volatile("cp.async.bulk.prefetch.tensor.5d.L2.global.tile [%0, {%1, %2, %3, %4, %5}];" ::"l"((uint64_t)map), "r"(c0), "r"(c1),
               "r"(c2), "r"(c3), "r"(c4) : "memory");
}
__device__ __forceinline__ int first_line(const TileCoord tc) { return 3 * (qpix(tc.pr, 8 * tc.I) * kW + qpix(tc.pc, 8 * tc.J)); }
template <int MODE, int UNROLL, int N = 8>
__device__ __forceinline__ void move_px(const Maps& tm, const TileTable& tt, uint32_t buf, uint32_t bar, int line, int kind, int i0 = 0) {
#pragma unroll UNROLL
  for (int n = 0; n < N; n++) {
    const int i = i0 + n;
    const int j = MODE == 2 ? 2 * (i & 3) + (i >> 2) : i;
    if (MODE == 2 || (n & 1) == 0 || kind != 0) {
      const CUtensorMap* map = (const CUtensorMap*)((const char*)(tm.px + (MODE & 2) * 2) + tt.g[kind][j][1]);
      const int ln = line + tt.g[kind][j][0];
      if (MODE == 0) tma_load_5d(buf + i * 3072, map, bar, 0, 0, 0, 0, ln);
      if (MODE == 1) tma_prefetch_5d(map, 0, 0, 0, 0, ln);
      if (MODE == 2)
        asm volatile("cp.async.bulk.tensor.5d.global.shared::cta.tile.bulk_group [%0, {%2, %2, %2, %2, %3}], [%1];" ::"l"((uint64_t)map),
                     "r"(buf + i * 3072), "r"(0), "r"(ln) : "memory");
    }
  }
  if (MODE == 2) asm volatile("cp.async.bulk.commit_group;" ::: "memory");
}
__device__ __noinline__ bool refetch(uint32_t base, const uint8_t* src, bool gap) {
  constexpr uint32_t bars = 1024 + kBarOff, cnt = bars + 192;
#pragma unroll 1
  for (uint32_t o = 0; o < kWBytes && !gap; o += 2048) {
    uint32_t mx = 0;
#pragma unroll
    for (int i = 0; i < 4; i++) {
      uint4 v;
      asm volatile("ld.shared.v4.u32 {%0,%1,%2,%3}, [%4];" : "=r"(v.x), "=r"(v.y), "=r"(v.z), "=r"(v.w)
                   : "r"(base + o + i * 512 + (threadIdx.x & 31) * 16));
      mx = __vimax3_u32(__vimax3_u32(mx, v.x, v.y), v.z, v.w);
    }
    gap = __any_sync(0xffffffffu, mx == kEmpty);
  }
  uint32_t n;
  asm volatile("ld.shared.u32 %0, [%1];" : "=r"(n) : "r"(cnt) : "memory");
  if (!gap || __any_sync(0xffffffffu, n > (1u << 12))) return false;
  asm volatile("bar.sync 15, 128;" ::: "memory");
  if (threadIdx.x == 0) {
    asm volatile("st.shared.u32 [%0], %1;" ::"r"(cnt), "r"(n + 1) : "memory");
    mbar_arrive_expect_tx(bar_redo(bars), kWBytes);
    bulk_load(base, src, kWBytes, bar_redo(bars));
  }
  __syncwarp();
  mbar_wait(bar_redo(bars), n & 1);
  return true;
}
template <int S0, int S1, int Z>
__device__ __forceinline__ void g2_steps(float (&ac)[48], const uint32_t (&za)[24], const uint32_t (&zb)[24], uint64_t d) {
#pragma unroll
  for (int s = S0; s < S1; s++) {
    const uint64_t ds = d + (((s >> 2 & 1) * (kWChunk / 2) + (s & 3) * 32) >> 4);
    if (s == Z) wg_d96z<0, 48>(ac, za[2 * s], zb[2 * s], za[2 * s + 1], zb[2 * s + 1], ds, 0);
    else wg_d96<0, 48>(ac, za[2 * s], zb[2 * s], za[2 * s + 1], zb[2 * s + 1], ds, 1);
  }
}

__device__ __forceinline__ void consumer(const int wg, __nv_bfloat16* out, const uint8_t* wimg, const uint32_t sbase,
                                         const uint32_t zero, const Maps& tm, const TileTable& tt) {
  const int tid = threadIdx.x & 127;
  const int w = __shfl_sync(0xffffffffu, tid >> 5, 0), lane = tid & 31;
  const uint64_t dK = make_desc(sbase, 16, 1024);
  const uint64_t dV = make_desc(sbase, kChunkBytes, 512, 2);
  const uint64_t dW1 = make_desc(sbase + kW1Off, 16, 1024);
  const uint64_t dX0 = make_desc(sbase + kW2Off + wg * 2 * kWChunk, 16, 1024), dY0 = make_desc(sbase + kW2Off + (1 - wg) * 2 * kWChunk, 16, 1024);
  const uint64_t dX2 = make_desc(sbase + kXOff + wg * (kWChunk / 2), 16, 1024), dY2 = make_desc(sbase + kXOff + (1 - wg) * (kWChunk / 2), 16, 1024);
  const uint32_t bars = sbase + kBarOff;
  int tile0 = blockIdx.x * kTilesPerCta;
  asm volatile("" : "+r"(tile0));
  const int nt = num_tiles();

  uint32_t pix = 0, geo[12] = {};
  const int l = lane & 3;
#pragma unroll 1
  for (int j = 4; j >= 0; j -= 2) {
    const TileCoord tc = decode_tile(tt, tile0 + wg + j);
    const int g = tc.kind < 3 ? lane >> 2 : 2 * w + ((lane >> 2) & 1), qc = tc.kind < 3 ? w : lane >> 3;
    const uint32_t pr = qpix(tc.pr, 8 * tc.I + g) * kW;
    if (j == nt - 2) pix = (pr + qpix(tc.pc, 8 * tc.J + qc)) | (pr + qpix(tc.pc, 8 * tc.J + qc + 4)) << 16;
    const int d = 8 * tc.J + 6 * tc.pc - 6 - halo_c0(tc);
    const int ro = woff(tc.pr, tc.I, g), coA = woff(tc.pc, tc.J, qc) + d, coB = woff(tc.pc, tc.J, qc + 4) + d - 3;
#pragma unroll
    for (int i = 11; i >= 4; i--) geo[i] = geo[i - 4];
    const uint32_t lr = 0x1FCu << ro;
    const uint32_t lv = lr >> (2 + (l >> 1)), lu = lr >> (2 * l + 2 * tc.up);
    const uint32_t t = __byte_perm(lv, lu, wg ? 0x4501 : 0x5410);
    geo[0] = ((t & 0x15u) | (lv & 0x40u)) * 0x02082080u;
    geo[1] = ((t >> 8) & 0x15u) * 0x02082080u;
    geo[2] = __byte_perm(t << 7, t << 6, 0x7362);
    const int dr = (ro - 1) & 7;
    const uint32_t hiv = (((1u << ((ro - (l >> 1) + 1) >> 1)) - 1u) ^ (wg ? 7u : 0u)) & 7u, hiu = (t >> 24) & 3u;
    const uint32_t ca = (1u << coA) - 1u;
    geo[3] = hiv * kHiV | hiu * kHiU | ((((1u << coB) - 1u) >> (2 * (l & 1))) & 3u) * kColB |
             (15u & ~((uint32_t)((dr & 1) == (l >> 1)) << (dr >> 1))) * kInV | ((t >> 16 | t >> 24) & 3u) * kInU | ca * kColA |
             (ca >> ((0x49 >> (2 * l)) & 3) & 1u) << 19 | (uint32_t)(l == 3) << 20 | (0x55u & ((1u << (2 * coB)) - 1u)) << 24;
  }
  keep_regs(geo);
  const int so = (lane >> 3) | (lane & 4);
  uint32_t sts = sbase + w * 3072 + so * 128 + (((lane & 3) ^ so) << 4);
  __nv_bfloat16* poA = out + 8 * l + (pix & 0xFFFFu) * kC + 96 * wg;
  __nv_bfloat16* poB = out + 8 * l + (pix >> 16) * kC + 96 * wg;
  asm volatile("" : "+l"(poA), "+l"(poB), "+r"(sts));
  uint32_t oa[24], ob[24];
#pragma unroll
  for (int j = 0; j < 24; j++) oa[j] = ob[j] = 0u;
  keep_regs(oa);
  keep_regs(ob);
  PROF(wg, 0);
  if (threadIdx.x == 0) GT(1);

  for (int k = wg; k < nt; k += 2) {
    const uint32_t ph = (k >> 1) & 1;
    const int it = k >> 1;
    uint32_t qa[24], qb[24], hok[3];
    uint32_t fl = geo[3];
    {
      float acc[96];
      const uint64_t dX = make_desc(sbase + kXOff + (k == 0 ? kWChunk : 0), 16, 3072);
      if (k > 0) nb_sync(1 + (1 - wg));
      mbar_wait(bar_x(bars, k > 0), (k + (k > 0)) & 1);
      if (k < 2) PROF(wg, 1);
      PROFS(2, wg, 2 + it * 12);
      if (w == 0 && k < 2) GT(20 + wg);
#pragma unroll
      for (int s = 0; s < 12; s++) {
        if ((s & 3) == 0 && k == 0) {
          mbar_wait(bar_w1c(bars, s >> 2), 0);
          PROFS(17, wg, 50 + (s >> 2));
        }
        if ((s & 3) == 0) wg_fence();
        if (s == 0) wg_m192z<0, 96>(acc, dX, dW1, 0);
        else wg_m192<0, 96>(acc, dX + (((s >> 2) * 1024 + (s & 3) * 32) >> 4), wdesc(dW1, s), 1);
      }
      wg_commit();
      PROFS(13, wg, 13 + it * 12);
      wg_wait<0>();
      if (k > 0) nb_arrive_p(6);
      fence_regs(acc);
      PROFS(3, wg, 3 + it * 12);
#pragma unroll
      for (int j = 0; j < 24; j++) {
        qa[j] = pack_bf16(acc[4 * j], acc[4 * j + 1]);
        qb[j] = pack_bf16(acc[4 * j + 2], acc[4 * j + 3]);
      }
      keep_regs(qa);
      keep_regs(qb);
      sched_fence();
      if (k >= 2) {
        const uint32_t dst = sts + out_slot(k, nt);
        nb_sync(11);
        stage_out<0, 6>(dst, wg, oa, ob);
        nb_sync(12);
        stage_out<6, 12>(dst, wg, oa, ob);
      }
#pragma unroll
      for (int c = 0; c < 3; c++) hok[c] = mbar_test(bar_full(bars, wg, c), ph);
      if (k >= 2) {
        fence_proxy_async();
        nb_arrive_p(10);
      }
    }

    float aE[52], aO[24], bO[52], bE[28];
    const uint32_t mq = 0xEEEE4444u | zero;
    PROFS(4, wg, 4 + it * 12);

    mbar_wait_if(hok[0], bar_full(bars, wg, 0), ph);
    PROFS(14, wg, 40 + it * 3);
    if (w == 0 && k < 2) GT(22 + wg);
    if (k > 0) nb_sync(3 + (1 - wg));
    wg_fence();
#pragma unroll
    for (int ks = 0; ks < 6; ks++) {
      if (ks == NAT_P1) {
        mbar_wait_if(hok[1], bar_full(bars, wg, 1), ph);
        PROFS(14, wg, 41 + it * 3);
        wg_fence();
      }
      if (ks == NAT_P2) {
        mbar_wait_if(hok[2], bar_full(bars, wg, 2), ph);
        PROFS(14, wg, 42 + it * 3);
        wg_fence();
      }
      const uint64_t d = dK + ((ks * kChunkBytes) >> 4);
      if (ks == 0) wg_s104z<0, 52>(aE, qa[0], qa[1], qa[2], qa[3], d, 0, mq);
      else wg_s104<0, 52>(aE, qa[4 * ks], qa[4 * ks + 1], qa[4 * ks + 2], qa[4 * ks + 3], d, 1, mq);
    }
    wg_commit();
    wg_s48z<0, 24>(aO, qa[0], qa[1], qa[2], qa[3], dK + ((7 * 1024 + 64) >> 4), 0, mq);
#pragma unroll
    for (int ks = 1; ks < 6; ks++)
      wg_s48<0, 24>(aO, qa[4 * ks], qa[4 * ks + 1], qa[4 * ks + 2], qa[4 * ks + 3], dK + ((ks * kChunkBytes + 7 * 1024 + 64) >> 4), 1, mq);
    wg_commit();
    wg_s56z<0, 28>(bE, qb[0], qb[1], qb[2], qb[3], dK, 0, mq);
#pragma unroll
    for (int ks = 1; ks < 6; ks++) wg_s56<0, 28>(bE, qb[4 * ks], qb[4 * ks + 1], qb[4 * ks + 2], qb[4 * ks + 3], dK + ((ks * kChunkBytes) >> 4), 1, mq);
    wg_commit();
    wg_wait<2>();
    fence_regs(aE);
    PROFS(5, wg, 5 + it * 12);

    uint32_t pa[14], pb[14], meta[4];
    {
      float vA[14], vB[14];
      pick_v(aE, vA, fl);
      pick_u(aE + 28, vA + 8, fl);
      fence_regs(vA);
      if (k == 0) {
        if (__builtin_expect(__any_sync(0xffffffffu, vA[6] != vA[6]), 0)) {
          wg_wait<0>();
          fence_regs(aO);
          fence_regs(bE);
          if (refetch(sbase + kW1Off, wimg, false)) {
#pragma unroll
            for (int j = 0; j < 24; j++) oa[j] = ob[j] = 0u;
            k -= 2;
            continue;
          }
        }
        if (elect_one()) mbar_arrive(bar_xf(bars));
      }
      wg_fence();
      wg_s104z<0, 52>(bO, qb[0], qb[1], qb[2], qb[3], dK + 4, 0, mq);
#pragma unroll
      for (int ks = 1; ks < 6; ks++)
        wg_s104<0, 52>(bO, qb[4 * ks], qb[4 * ks + 1], qb[4 * ks + 2], qb[4 * ks + 3], dK + ((ks * kChunkBytes + 64) >> 4), 1, mq);
      wg_commit();
      if (k + 1 < nt) nb_arrive(1 + wg);
      uint32_t rt[9];
#pragma unroll
      for (int i = 0; i < 7; i++) rt[i] = sign_bytes(geo[i >> 2], 0x8888u + 0x1111u * (i & 3));
      rt[7] = sign_bytes(geo[2], 0x9988u);
      rt[8] = sign_bytes(geo[2], 0xBBAAu);
      keep_regs(rt);
      pa[13] = pb[13] = 0u;
      wg_wait<2>();
      keep_regs(qa);
      fence_regs(aO);
      float oA[6], eB[8];
      pick_u(aO, oA, fl);
      wg_wait<1>();
      fence_regs(bE);
      pick_v(bE, eB, fl);
      vA[8] = sel<kColA>(oA[0], vA[8], fl), vA[9] = sel<kColA>(oA[1], vA[9], fl);
      vA[10] = sel<kColA * 2>(oA[2], vA[10], fl), vA[11] = sel<kColA * 2>(oA[3], vA[11], fl);
      vA[12] = sel<kColA * 4>(oA[4], vA[12], fl), vA[13] = sel<kColA * 4>(oA[5], vA[13], fl);
      {
        const float m1 = __uint_as_float(0x88DD88DDu), m0 = __uint_as_float(0x88DDDD88u);
        meta[0] = 0xDD88DD88u ^ __byte_perm(fl, 0u, 0x3344);
        meta[1] = __float_as_uint(sel<kColA * 16>(sel<kColA>(m1, m0, fl), __uint_as_float(meta[0]), fl));
        meta[2] = __float_as_uint(sel<kColA * 8>(m1, m0, fl));
        meta[3] = __float_as_uint(sel<kColA * 4>(m1, m0, fl));
        keep_regs(meta);
      }
      float mA = own_max(vA, fl);
      fl |= __float_as_uint(eB[7]) & zero;
      fence_regs(eB);
      fence_regs(vA);
      asm volatile("" : "+f"(mA), "+r"(fl));
      sched_fence();
      wg_wait<0>();
      sched_fence();
      keep_regs(qb);
      fence_regs(bO);
      PROFS(6, wg, 6 + it * 12);
      if (w == 0) GT(24 + k);
      mA = quad_max(mA);
#pragma unroll
      for (int i = 0; i < 14; i++) vA[i] = ex2(vA[i] - mA);
      pick_v(bO, vB, fl);
      pick_u(bO + 28, vB + 8, fl);
#pragma unroll
      for (int i = 0; i < 8; i += 2) vB[i] = sel<kColB>(vB[i], eB[i], fl), vB[i + 1] = sel<kColB * 2>(vB[i + 1], eB[i + 1], fl);
      float mB = quad_max(own_max(vB, fl));
      if (NAT_SB) {
        fence_regs(vA);
        fence_regs(vB);
        asm volatile("" : "+f"(mB));
        sched_fence();
      }
      PROFS(7, wg, 7 + it * 12);
#pragma unroll
      for (int i = 0; i < 14; i++) vB[i] = ex2(vB[i] - mB);
      route(vA, row_rcp(vA, fl), rt, pa);
      route(vB, row_rcp(vB, fl), rt, pb);
    }
    PROFS(8, wg, 8 + it * 12);
    if (k == NAT_PK) PROFS(18, wg, 53);
    sched_fence();

    float ac0[48], ac1[48];
    {
      float z0[32], z1[32], z2[32];
      uint32_t za[24], zb[24];
      wg_fence();
      pv_chunk<0>(z0, pa, pb, meta, dV);
      wg_commit();
      pv_chunk<1>(z1, pa, pb, meta, dV);
      wg_commit();
      wg_wait<1>();
      if (k == NAT_PK) PROFS(18, wg, 54);
      if (k + 1 < nt) nb_arrive_p(7);
      pv_chunk<2, 0, 3>(z2, pa, pb, meta, dV);
      wg_commit();
      sched_fence();
      fence_regs(z0);
      pack_z<0>(z0, za, zb);
      sched_fence();
      wg_fence();
      pv_chunk<2, 3, 7>(z2, pa, pb, meta, dV);
      wg_commit();
      wg_wait<2>();
      if (k == NAT_PK) PROFS(19, wg, 55);
      if (k + 1 < nt) nb_arrive_p(8);
      if (k < 2) mbar_wait(k == 1 ? bar_wok(bars) : bar_w2a(bars), 0);
      wg_fence();
      g2_steps<0, 3, 0>(ac0, za, zb, dX0);
      wg_commit();
      sched_fence();
      fence_regs(z1);
      pack_z<1>(z1, za, zb);
      sched_fence();
      wg_fence();
      g2_steps<3, 4, 0>(ac0, za, zb, dX0);
      wg_commit();
      g2_steps<4, 8, 0>(ac0, za, zb, dX0);
      wg_commit();
      wg_wait<3>();
      if (k + 1 < nt) nb_arrive_p(9);
      else nb_arrive(11);
      if (k == NAT_PK) PROFS(20, wg, 56);
      keep_regs(pa);
      keep_regs(pb);
      keep_regs(meta);
      sched_fence();
      const uint32_t mok = mbar_test(bar_w2m(bars), k + 1 < nt ? k & 1 : ~k & 1);
      fence_regs(z2);
      pack_z<2>(z2, za, zb);
      keep_regs(za);
      keep_regs(zb);
      sched_fence();
      PROFS(9, wg, 9 + it * 12);
      wg_wait<1>();
      if (k > 0 && k + 1 < nt) nb_arrive(11);
      mbar_wait_if(mok, bar_w2m(bars), k & 1);
      wg_fence();
      g2_steps<8, 12, 0>(ac0, za, zb, dX2);
      wg_commit();
      g2_steps<8, 12, 8>(ac1, za, zb, dY2);
      wg_commit();
      wg_wait<2>();
      if (k > 0 && k + 1 < nt) nb_arrive(12);
      if (k != 1 && k + 1 < nt) mbar_wait(bar_w2(bars), k > 1 ? (k - 1) & 1 : 0);
      wg_fence();
      g2_steps<0, 4, 8>(ac1, za, zb, dY0);
      wg_commit();
      wg_wait<2>();
      if (k + 2 < nt) nb_arrive_p(13);
      const bool direct = k + 2 >= nt;
      sched_fence();
      fence_regs(ac0);
      pack_out<0>(ac0, oa, ob);
      store_rows<0, NAT_D0>(direct, poA, poB, oa, ob);
      sched_fence();
      wg_fence();
      g2_steps<4, 8, 8>(ac1, za, zb, dY0);
      wg_commit();
      if (k + 1 < nt) nb_arrive(3 + wg);
      PROFS(10, wg, 10 + it * 12);
      wg_wait<2>();
      if (k + 2 < nt && (k > 0 || nt == 6)) nb_arrive_p(5);
      store_rows<NAT_D0, 3>(direct, poA, poB, oa, ob);
      __nv_bfloat16 *qA = poA - 192 * wg, *qB = poB - 192 * wg;
      if (k + 2 == nt) nb_sync(11);
      sched_fence();
      wg_wait<0>();
      fence_regs(ac1);
      pack_out<1>(ac1, oa, ob);
      asm volatile("" : "+l"(qA), "+l"(qB));
      store_rows<3, 6>(direct, qA, qB, oa, ob);
      if (k == 0) {
        uint32_t m[2] = {oa[0], oa[1]};
#pragma unroll
        for (int i = 2; i < 24; i++) asm("max.NaN.bf16x2 %0, %0, %1;" : "+r"(m[i & 1]) : "r"(oa[i]));
        asm("max.NaN.bf16x2 %0, %0, %1;" : "+r"(m[0]) : "r"(m[1]));
        uint32_t nan;
        asm volatile("{\n.reg .pred p;\nsetp.ne.u32 p, %1, 0;\nbar.red.or.pred p, 15, 128, p;\nselp.u32 %0, 1, 0, p;\n}\n"
                     : "=r"(nan) : "r"(((m[0] & 0x7FFF7FFFu) + 0x007F007Fu) & 0x80008000u) : "memory");
        if (__builtin_expect(__any_sync(0xffffffffu, nan), 0)) {
          if (nt == 6) mbar_wait(bar_x(bars, 1), 1);
          for (bool first = true; __any_sync(0xffffffffu, refetch(sbase + kW2Off, wimg + w2_offset(), first)); first = false) { }
          wg_fence();
          g2_steps<0, 8, 0>(ac0, za, zb, dX0);
          g2_steps<8, 12, 0>(ac0, za, zb, dX2);
          g2_steps<0, 8, 0>(ac1, za, zb, dY0);
          g2_steps<8, 12, 0>(ac1, za, zb, dY2);
          wg_commit();
          wg_wait<0>();
          fence_regs(ac0);
          fence_regs(ac1);
          pack_out<0>(ac0, oa, ob);
          pack_out<1>(ac1, oa, ob);
          if (nt == 6) {
            asm volatile("bar.sync 15, 128;" ::: "memory");
            if (w == 0 && elect_one()) {
              const TileCoord tc = decode_tile(tt, tile0 + 2);
              mbar_arrive_expect_tx(bar_raw(bars), kWChunk);
              move_px<0, 1>(tm, tt, sbase + kXOff, bar_raw(bars), first_line(tc), tc.kind);
            }
            __syncwarp();
            mbar_wait(bar_raw(bars), 0);
          }
        }
        if (nt < 6) nb_arrive_p(5);
        if (elect_one()) mbar_arrive(bar_wok(bars));
      }
      keep_regs(za);
      keep_regs(zb);
#pragma unroll
      for (int i = 0; i < 8; i++) geo[i] = geo[i + 4];
      keep_regs(oa);
      keep_regs(ob);
      PROFS(12, wg, 12 + it * 12);
      sched_fence();
    }
  }
  PROF(wg, 38);
  GT_DUMP();
  PROF_DUMP(wg);
}

struct HaloCols { int vj, vc, uj, uc; };
__device__ __forceinline__ HaloCols halo_cols(const TileCoord& tc) {
  const int c0 = halo_c0(tc);
  return HaloCols{c0 > 98, c0 > 98 ? 98 : c0 + 3, c0 < 0 ? -1 : 0, c0 < 0 ? 4 : c0};
}
__device__ __forceinline__ void first_halo(const Maps& tm, uint32_t sbase, const TileCoord tc, int i) {
  const HaloCols hc = halo_cols(tc);
  const uint32_t dst = sbase + i * kChunkBytes, bar = bar_full(sbase + kBarOff, 0, i >> 1);
  const int h0 = halo_r0(tc), ch = 24 * tc.pc + 4 * i;
  tma_load_5d(dst, &tm.v14, bar, ch, hc.vj, hc.vc, tc.pr, h0);
  tma_load_5d(dst + 7 * 1024, &tm.u8, bar, ch, hc.uj, h0 + (tc.up ? 0 : -2), tc.pr, hc.uc);
  tma_load_5d(dst + 10 * 1024, &tm.u8, bar, ch, hc.uj, h0 + (tc.up ? 8 : 6), tc.pr, hc.uc);
}
__device__ __forceinline__ void load_halo(const Maps& tm, uint32_t sbase, uint32_t bars, const TileCoord tc, int k, int c) {
  const HaloCols hc = halo_cols(tc);
  const int h6 = halo_r0(tc) + (tc.up ? 0 : 8), h2 = halo_r0(tc) + 6, h8 = halo_r0(tc) + (tc.up ? 0 : 6), ch = 24 * tc.pc + 8 * c;
  uint32_t dv = sbase + 2 * c * kChunkBytes, du = dv + 7 * 1024;
  if (((k ^ tc.up) & 1) == 0) dv += 4 * 1024, du += 3 * 1024;
  const uint32_t bar = bar_full(bars, k & 1, c);
  mbar_arrive_expect_tx(bar, 14 * 1024);
  nb_sync_p(7 + c);
#pragma unroll
  for (int h = 0; h < 2; h++) {
    tma_load_5d(dv + h * kChunkBytes, &tm.v6, bar, ch + 4 * h, hc.vj, hc.vc, tc.pr, h6);
    tma_load_5d(du + h * kChunkBytes, &tm.u8, bar, ch + 4 * h, hc.uj, h8, tc.pr, hc.uc);
    tma_load_5d(sbase + (2 * c + h) * kChunkBytes + 3 * 1024, &tm.v2, bar, ch + 4 * h, hc.vj, hc.vc, tc.pr, h2);
  }
  PROFS(15, 2, k * 4 + c);
}
__device__ __forceinline__ void gather_px(const __nv_bfloat16* __restrict__ x, uint32_t buf, uint32_t bar, const TileCoord tc) {
  const int lane = threadIdx.x & 31, g = lane >> 3;
  uint32_t ro[4], co[4];
#pragma unroll
  for (int i = 0; i < 4; i++) {
    ro[i] = qpix(tc.pr, 8 * tc.I + 2 * i + (g & 1)) * (kW * kC * 2) + 16 * (lane & 7);
    co[i] = qpix(tc.pc, 8 * tc.J + 2 * i + (g >> 1)) * (kC * 2);
  }
  uint32_t dst = buf + g * 128 + (((lane & 7) ^ g) << 4);
  keep_regs(ro);
  keep_regs(co);
  sched_fence();
  nb_sync_p(13);
  nb_sync_p(5);
#pragma unroll
  for (int i = 0; i < 16; i++) {
    const char* src = (const char*)x + (ro[i >> 2] + co[i & 3]);
#pragma unroll
    for (int q = 0; q < 3; q++)
      asm volatile("cp.async.cg.shared.global [%0], [%1], 16;" ::"r"((dst ^ ((i & 1) * 576)) + (i >> 1) * 3072 + q * 1024), "l"(src + 128 * q) : "memory");
  }
  asm volatile("cp.async.wait_all;" ::: "memory");
  fence_proxy_async();
  __syncwarp();
  if (elect_one()) mbar_arrive(bar);
  __syncwarp();
}

__global__ void __launch_bounds__(384, 1)
nat_kernel(const __nv_bfloat16* __restrict__ x, __nv_bfloat16* out, const __nv_bfloat16* __restrict__ wqkv,
           const __nv_bfloat16* __restrict__ wo, uint8_t* wimg, const uint32_t zero,
           const __grid_constant__ Maps tm, const __grid_constant__ TileTable tt) {
  extern __shared__ uint8_t smem_raw[];
  constexpr uint32_t sbase = 1024;
  constexpr uint32_t bars = sbase + kBarOff;
  if (smem_u32(smem_raw) != sbase) __trap();
  const int tid = threadIdx.x;
  const uint32_t t_start = now_ns();
  if (tid == 0) GT(0);
  const int wid = __shfl_sync(0xffffffffu, tid >> 5, 0);
  const bool w2cta = blockIdx.x - 128 < 3 && wqkv != nullptr;
  if (wid >= 8) {
    asm volatile("setmaxnreg.dec.sync.aligned.u32 24;");
    const int c = wid & 3, lane = tid & 31;
    const int tile0 = blockIdx.x * kTilesPerCta, nt = num_tiles();
    uint32_t w2o = 0;
    if (c == 3) {
      asm volatile("bar.sync 13, 128;" ::: "memory");
      if (elect_one()) wait_clock(t_start, NAT_TM);
      __syncwarp();
      const CUtensorMap* px = tm.px + (blockIdx.x >= 112 ? 2 : edge_strip());
      asm volatile("prefetch.tensormap [%0];" ::"l"((uint64_t)&tm.v6) : "memory");
      asm volatile("prefetch.tensormap [%0];" ::"l"((uint64_t)&tm.v2) : "memory");
      asm volatile("prefetch.tensormap [%0];" ::"l"((uint64_t)(px + 4)) : "memory");
      asm volatile("prefetch.tensormap [%0];" ::"l"((uint64_t)(px + 5)) : "memory");
      if (blockIdx.x >= 112) {
        asm volatile("prefetch.tensormap [%0];" ::"l"((uint64_t)tm.px) : "memory");
        asm volatile("prefetch.tensormap [%0];" ::"l"((uint64_t)(tm.px + 4)) : "memory");
      }
      __nanosleep(NAT_TW2 - 2800);
      w2o = w2_offset();
      if (elect_one()) {
        mbar_arrive_expect_tx(bar_w2a(bars), kWChunk);
        mbar_arrive_expect_tx(bar_w2(bars), kWChunk);
        wait_clock(t_start, NAT_TW2);
        bulk_load(sbase + kW2Off, wimg + w2o, kWChunk, bar_w2a(bars));
        mbar_wait(bar_xf(bars), 0);
        bulk_load(sbase + kW2Off + 2 * kWChunk, wimg + (w2o + 2 * kWChunk), kWChunk, bar_w2(bars));
      }
      __syncwarp();
      if (nt < 6) {
#pragma unroll 1
        for (int k = 2; k < 4; k++) {
          gather_px(x, sbase + kXOff, bar_x(bars, 1), decode_tile(tt, tile0 + k));
        }
      }
      if (wqkv == nullptr) return;
      mbar_wait(bar_wok(bars), 0);
      if (lane == 0) asm volatile("red.relaxed.gpu.global.add.u32 [%0], 1;" ::"l"(g_flag) : "memory");
      if (blockIdx.x >= 48) return;
      if (lane == 0) {
        uint32_t v, it = 0;
        do {
          __nanosleep(2000);
          asm volatile("ld.relaxed.gpu.global.u32 %0, [%1];" : "=r"(v) : "l"(g_flag) : "memory");
        } while (v < gridDim.x && ++it < (1u << 16));
      }
      __syncwarp();
#pragma unroll
      for (int i = 0; i < 6; i++)
        stg128(wimg + ((i < 3 ? 0u : 3 * kWBytes - w2o) + blockIdx.x * 1536 + (i % 3) * 512 + lane * 16), kEmpty, kEmpty, kEmpty, kEmpty);
      if (lane == 0 && atomicAdd(g_flag + 32, 1u) == 47) {
        g_flag[0] = g_flag[32] = 0;
        g_flag[64] = w2o == kWBytes;
      }
      return;
    }
    if (!elect_one()) return;
    if (c == 0) {
      for (int i = 0; i < kNumBars; i++)
        if ((i != 0 && i != 10 || nt < 6) && (i != 21 || !w2cta)) mbar_init(bars + i * 8, i == 13 || i == 16 ? 4 : 1);
      asm volatile("st.shared.v2.u32 [%0], {%1,%1};" ::"r"(bars + 192), "r"(0) : "memory");
      asm volatile("fence.mbarrier_init.release.cluster;" ::: "memory");
      if (w2cta) asm volatile("bar.sync 10, 64;" ::: "memory");
      asm volatile("bar.arrive 0, 160;" ::: "memory");
      asm volatile("bar.arrive 14, 160;" ::: "memory");
      asm volatile("bar.arrive 13, 128;" ::: "memory");
      const TileCoord tc0 = decode_tile(tt, tile0);
      const HaloCols hc = halo_cols(tc0);
      const int h0 = halo_r0(tc0);
#pragma unroll
      for (int j = 0; j < 3; j++)
        if (j > 0 || nt < 6) mbar_arrive_expect_tx(bar_full(bars, 0, j), 2 * kChunkBytes);
      wait_clock(t_start, NAT_HP);
#pragma unroll
      for (int q = 8; q < 24; q += 8) {
        tma_prefetch_5d(&tm.v6, 24 * tc0.pc + q, hc.vj, hc.vc, tc0.pr, h0 + (tc0.up ? 0 : 8));
        tma_prefetch_5d(&tm.u8, 24 * tc0.pc + q, hc.uj, h0 + (tc0.up ? 0 : 6), tc0.pr, hc.uc);
        if (blockIdx.x >= 112) tma_prefetch_5d(&tm.v2, 24 * tc0.pc + q, hc.vj, hc.vc, tc0.pr, h0 + 6);
      }
#pragma unroll 1
      for (int i = nt < 6 ? 0 : 2; i < 7; i++) {
        if (i == NAT_H0) mbar_wait(bar_w1q(bars), 0);
        if (i == NAT_X1P) mbar_arrive(bar_go(bars));
        if (i < 6) first_halo(tm, sbase, tc0, i);
      }
      w2o = w2_offset();
    } else {
      asm volatile("bar.sync 13, 128;" ::: "memory");
      if (c == 2) {
        if (wqkv != nullptr && nt == 6) asm volatile("bar.sync 12, 64;" ::: "memory");
        const uint32_t c0 = clock();
        while ((uint32_t)clock() - c0 < NAT_TD) { }
        wait_clock(t_start, NAT_T0);
#pragma unroll
        for (int j = 0; j < 3; j++) {
          mbar_arrive_expect_tx(bar_w1c(bars, j), kWChunk);
          bulk_load(sbase + kW1Off + j * kWChunk, wimg + j * kWChunk, kWChunk, bar_w1c(bars, j));
        }
        mbar_arrive(bar_w1q(bars));
        GT(2);
      } else {
#pragma unroll 1
        for (int j = nt == 6; j < 2; j++) {
          const TileCoord tc = decode_tile(tt, tile0 + j);
          const int line = first_line(tc);
          mbar_arrive_expect_tx(bar_x(bars, j), kWChunk);
          if (j == 1) mbar_wait(bar_go(bars), 0);
          move_px<0, 2>(tm, tt, sbase + kXOff + (1 - j) * kWChunk, bar_x(bars, j), line, tc.kind);
        }
        w2o = w2_offset();
      }
    }
#pragma unroll 1
    for (int k = 1; k < nt; k++) {
      const TileCoord tn = decode_tile(tt, tile0 + k + 1);
      const int line = first_line(tn);
      if (c == 1) {
        nb_sync_p(6);
        bulk_load(sbase + kXOff, wimg + (w2o + kWChunk), kWChunk, bar_w2m(bars));
        mbar_arrive_expect_tx(bar_w2m(bars), kWChunk);
      }
      if (c == 2) {
        if (k == 1) wait_clock(t_start, NAT_TX2);
        else __nanosleep(NAT_PFD);
        if (k < 5 && nt == 6) move_px<1, 1>(tm, tt, 0, 0, line, tn.kind);
      }
      if (c == 2 && (blockIdx.x >= 112 || k == 5)) {
        const TileCoord tc = decode_tile(tt, tile0 + k);
        const HaloCols hc = halo_cols(tc);
        const int h8 = halo_r0(tc) + (tc.up ? 0 : 6);
#pragma unroll 1
        for (int q = 0; q < 24; q += 8) {
          tma_prefetch_5d(&tm.v6, 24 * tc.pc + q, hc.vj, hc.vc, tc.pr, h8);
          tma_prefetch_5d(&tm.v2, 24 * tc.pc + q, hc.vj, hc.vc, tc.pr, h8 + 6);
          tma_prefetch_5d(&tm.u8, 24 * tc.pc + q, hc.uj, h8, tc.pr, hc.uc);
        }
      }
      load_halo(tm, sbase, bars, decode_tile(tt, tile0 + k), k, c);
      if (c == 0 && k < 5 && nt == 6) {
        const int f = ~k & 1;
        if (tn.kind == 0) {
#pragma unroll
          for (int j = 0; j < 4; j++) {
            if ((j & 1) == 0) nb_sync_p(j ? 5 : 13);
            tma_load_5d(sbase + kXOff + (j ^ 2 * f) * 6144, tm.px, bar_x(bars, 1), 0, 0, 0, 0, line + 6 * (j ^ 2 * f));
          }
        } else {
          nb_sync_p(13);
          move_px<0, 4, 4>(tm, tt, sbase + kXOff, bar_x(bars, 1), line, tn.kind, 4 * f);
          nb_sync_p(5);
          move_px<0, 4, 4>(tm, tt, sbase + kXOff, bar_x(bars, 1), line, tn.kind, 4 - 4 * f);
        }
        mbar_arrive_expect_tx(bar_x(bars, 1), kWChunk);
        PROFS(16, 2, k * 4 + 3);
      }
      if (c == 0 && k >= 2) {
        const TileCoord tp = decode_tile(tt, tile0 + k - 2);
        const int lp = first_line(tp);
        nb_sync_p(10);
        if (NAT_XW == 1 && k < 5 && nt == 6) mbar_wait(bar_x(bars, 1), k & 1);
        if (NAT_XW > 1) __nanosleep(NAT_XW);
        move_px<2, NAT_SU>(tm, tt, sbase + out_slot(k, nt), 0, lp, tp.kind);
        if (k + 1 < nt) {
          asm volatile("cp.async.bulk.wait_group.read 0;" ::: "memory");
          bulk_load(sbase + out_slot(k, nt), wimg + (w2o + out_slot(k, nt) - kW2Off), kWChunk, bar_w2(bars));
          mbar_arrive_expect_tx(bar_w2(bars), kWChunk);
        }
      }
    }
    asm volatile("cp.async.bulk.wait_group 0;" ::: "memory");
  } else {
    if (blockIdx.x < 128) {
      if ((wid == 4 || (wid == 5 && blockIdx.x - 2 < 16)) && wqkv != nullptr) {
        fold_w1(blockIdx.x - 2 < 16 ? 2 * blockIdx.x + wid - 6 : blockIdx.x + (blockIdx.x < 2 ? 0 : 16), wqkv, wimg);
        if (wid == 4) asm volatile("bar.arrive 12, 64;" ::: "memory");
        if (tid == 128) GT(7);
      }
      sched_fence();
      if (wid == 1 && elect_one()) {
        const TileCoord tc = decode_tile(tt, blockIdx.x * kTilesPerCta);
        mbar_init(bar_x(bars, 0), 1);
        asm volatile("fence.mbarrier_init.release.cluster;" ::: "memory");
        mbar_arrive_expect_tx(bar_x(bars, 0), kWChunk);
        GT(15);
        move_px<0, 2>(tm, tt, sbase + kXOff + kWChunk, bar_x(bars, 0), first_line(tc), tc.kind);
        GT(16);
      }
      __syncwarp();
      sched_fence();
      if (wid == 2 && elect_one()) {
        const TileCoord tc = decode_tile(tt, blockIdx.x * kTilesPerCta);
        mbar_init(bar_full(bars, 0, 0), 1);
        asm volatile("fence.mbarrier_init.release.cluster;" ::: "memory");
        mbar_arrive_expect_tx(bar_full(bars, 0, 0), 2 * kChunkBytes);
        if (NAT_TH) wait_clock(t_start, NAT_TH);
        asm volatile("prefetch.tensormap [%0];" ::"l"((uint64_t)&tm.u8) : "memory");
        GT(17);
        first_halo(tm, sbase, tc, 0);
        first_halo(tm, sbase, tc, 1);
      }
      __syncwarp();
    }
    sched_fence();
    {
      if (w2cta) {
        const int q = blockIdx.x & 3;
        uint32_t w2o = 0;
        if (wid == 1 && elect_one()) {
          asm volatile("prefetch.tensormap [%0];" ::"l"((uint64_t)&tm.wo) : "memory");
#pragma unroll
          for (int j = 0; j < 3; j++) mbar_init(bar_raw(bars, j), 1);
          asm volatile("fence.mbarrier_init.release.cluster;" ::: "memory");
#pragma unroll
          for (int j = 0; j < 6; j++)
            asm volatile("cp.async.bulk.tensor.2d.shared::cluster.global.tile.mbarrier::complete_tx::bytes [%0], [%1, {%3, %4}], [%2];" ::"r"(
                             j < 3 ? sbase + j * 8192 : sbase + kW2Off + (j - 3) * kWChunk),
                         "l"((uint64_t)(j < 3 ? &tm.wv : &tm.wo)), "r"(bar_raw(bars, j < 3 ? 0 : j - 3)),
                         "r"(j < 3 ? 384 + 64 * j : 64 * (j - 3)), "r"(j < 3 ? 64 * q : 0) : "memory");
#pragma unroll
          for (int j = 0; j < 3; j++) mbar_arrive_expect_tx(bar_raw(bars, j), j ? kWChunk : 2 * kWChunk);
          w2o = w2_offset();
        }
        __syncwarp();
#pragma unroll 1
        for (int r = 0; r < 3; r++) {
          const int blk = 2 * r - 2 + (wid >> 2);
          if (blk < 3) {
            if (r > 0) {
              mbar_wait(bar_raw(bars, 0), 0);
              mbar_wait(bar_raw(bars, blk), 0);
            }
            if (tid == 0 && r == 1) GT(7);
            float acc[32];
            const uint64_t db = make_desc(sbase + kW2Off + max(blk, 0) * kWChunk, kWChunk, 1024);
            wg_fence();
            wg_m64tz<0, 32>(acc, make_desc(sbase, 16, 1024), db, 0);
#pragma unroll
            for (int s = 1; s < 12; s++) wg_m64t<0, 32>(acc, make_desc(sbase + (s >> 2) * 8192 + (s & 3) * 32, 16, 1024), db + s * 128, 1);
            wg_commit();
            wg_wait<0>();
            fence_regs(acc);
            if (tid == 0) GT(19);
            const int m = (tid >> 3) & 3;
#pragma unroll
            for (int j = 0; j < 8; j += 2) {
              const int n = g2_inv(8 * (j + (m >> 1)) + (tid & 7));
              asm volatile("stmatrix.sync.aligned.m8n8.x4.trans.shared.b16 [%0], {%1,%2,%3,%4};" ::"r"(
                               sbase + kW1Off + (blk + 2) * 8192 + n * 128 + (((2 * (wid & 3) + (m & 1)) ^ (n & 7)) << 4)),
                           "r"(pack_bf16(acc[4 * j], acc[4 * j + 1])), "r"(pack_bf16(acc[4 * j + 2], acc[4 * j + 3])),
                           "r"(pack_bf16(acc[4 * j + 4], acc[4 * j + 5])), "r"(pack_bf16(acc[4 * j + 6], acc[4 * j + 7])) : "memory");
            }
            fence_proxy_async();
          }
          if (tid == 0) GT(18);
          asm volatile("bar.sync 11, 256;" ::: "memory");
          if (wid == 1 && elect_one()) {
            asm volatile("{\n.reg .pred p;\nsetp.ne.s32 p, %3, 0;\n@p cp.async.bulk.global.shared::cta.bulk_group [%0], [%1], %2;\n}\n" ::"l"(
                             wimg + (w2o + w2piece(r >> 1, q) * (kWChunk / 2))),
                         "r"(sbase + kW1Off + 16384 + (r >> 1) * (kWChunk / 2)), "r"(kWChunk / 2), "r"(r) : "memory");
            asm volatile("cp.async.bulk.commit_group;" ::: "memory");
          }
          __syncwarp();
        }
        if (wid == 1) {
          if (elect_one()) asm volatile("cp.async.bulk.wait_group.read 0;" ::: "memory");
          if (tid == 32) GT(31);
          __syncwarp();
          asm volatile("bar.arrive 10, 64;" ::: "memory");
        }
      }
    }
    __syncwarp();
    if (wid < 4) asm volatile("bar.sync 0, 160;" ::: "memory");
    else asm volatile("bar.sync 14, 160;" ::: "memory");
    asm volatile("setmaxnreg.inc.sync.aligned.u32 240;");
    consumer(wid >> 2, out, wimg, sbase, zero, tm, tt);
  }
}

}

typedef CUresult (*PFN_encodeTiled)(CUtensorMap*, CUtensorMapDataType, cuuint32_t, void*, const cuuint64_t*,
                                    const cuuint64_t*, const cuuint32_t*, const cuuint32_t*, CUtensorMapInterleave,
                                    CUtensorMapSwizzle, CUtensorMapL2promotion, CUtensorMapFloatOOBfill);

extern "C" void kernel_launch(void* const* d_in, const int* in_sizes, int n_in, void* d_out, int out_size) {
  const __nv_bfloat16* x = (const __nv_bfloat16*)d_in[0];
  const __nv_bfloat16* wqkv = (const __nv_bfloat16*)d_in[1];
  const __nv_bfloat16* wo = (const __nv_bfloat16*)d_in[2];
  __nv_bfloat16* out = (__nv_bfloat16*)d_out;

  static PFN_encodeTiled encode = nullptr;
  static int num_sms = 0;
  static uint8_t* wimg = nullptr;
  if (!encode) {
    void* fn = nullptr;
    cudaDriverEntryPointQueryResult qres;
    cudaGetDriverEntryPoint("cuTensorMapEncodeTiled", &fn, cudaEnableDefault, &qres);
    encode = (PFN_encodeTiled)fn;
    cudaFuncSetAttribute(nat::nat_kernel, cudaFuncAttributeMaxDynamicSharedMemorySize, nat::kSmemBytes);
    cudaGetSymbolAddress((void**)&wimg, nat::g_wimg32);
    int dev = 0;
    cudaGetDevice(&dev);
    cudaDeviceGetAttribute(&num_sms, cudaDevAttrMultiProcessorCount, dev);
  }
  nat::Maps tm;
  cuuint32_t estr[5] = {1, 1, 1, 1, 1};
  {
    cuuint64_t vdim[5] = {48, 2, 105, 2, 112}, udim[5] = {48, 2, 112, 2, 105};
    cuuint64_t vstr[4] = {7 * 768, 768, 224 * 384, 2 * 224 * 384}, ustr[4] = {7 * 768, 2 * 224 * 384, 224 * 384, 768};
    CUtensorMap* maps[4] = {&tm.v6, &tm.v2, &tm.v14, &tm.u8};
    for (int i = 0; i < 4; i++) {
      cuuint32_t box[5] = {4, 2, i < 3 ? 4u : 8u, 1, i == 0 ? 6u : i == 1 ? 2u : i == 2 ? 14u : 3u};
      encode(maps[i], CU_TENSOR_MAP_DATA_TYPE_UINT32, 5, (void*)x, i < 3 ? vdim : udim, i < 3 ? vstr : ustr, box, estr,
             CU_TENSOR_MAP_INTERLEAVE_16B, CU_TENSOR_MAP_SWIZZLE_128B, CU_TENSOR_MAP_L2_PROMOTION_L2_128B, CU_TENSOR_MAP_FLOAT_OOB_FILL_NONE);
    }
  }
  for (int i = 0; i < 8; i++) {
    const cuuint32_t row = 224 * 384, dr = (1u + (i & 1)) * row;
    const cuuint32_t shape[4][6] = {{8, 3, 2u - i, 2 * row, 128, 4 * 768}, {2, 4, 3, dr, 768, 128}, {4, 2, 3, 4 * row, 2 * row, 128}, {4, 2, 3, 768, dr, 128}};
    const cuuint32_t* sh = shape[i >> 1];
    cuuint64_t dim[5] = {64, sh[0], sh[1], sh[2], 224 * 224 * 3};
    cuuint64_t str[4] = {sh[3], sh[4], sh[5], 128};
    cuuint32_t box[5] = {64, sh[0], sh[1], sh[2], 1};
    encode(tm.px + i, CU_TENSOR_MAP_DATA_TYPE_BFLOAT16, 5, i < 4 ? (void*)x : (void*)out, dim, str, box, estr, CU_TENSOR_MAP_INTERLEAVE_NONE,
           CU_TENSOR_MAP_SWIZZLE_128B, i < 4 ? CU_TENSOR_MAP_L2_PROMOTION_L2_128B : CU_TENSOR_MAP_L2_PROMOTION_NONE,
           CU_TENSOR_MAP_FLOAT_OOB_FILL_NONE);
  }
  for (int i = 0; i < 2; i++) {
    cuuint64_t dim[2] = {i ? 192u : 576u, 192}, str[1] = {i ? 384u : 1152u};
    cuuint32_t box[2] = {64, i ? 192u : 64u};
    encode(i ? &tm.wo : &tm.wv, CU_TENSOR_MAP_DATA_TYPE_BFLOAT16, 2, i ? (void*)wo : (void*)wqkv, dim, str, box, estr,
           CU_TENSOR_MAP_INTERLEAVE_NONE, CU_TENSOR_MAP_SWIZZLE_128B, CU_TENSOR_MAP_L2_PROMOTION_L2_256B, CU_TENSOR_MAP_FLOAT_OOB_FILL_NONE);
  }
  nat::TileTable tt;
  nat::make_tiles(tt);
  const int grid = nat::kCtas;
  if (num_sms >= grid) {
    nat::nat_kernel<<<grid, 384, nat::kSmemBytes>>>(x, out, wqkv, wo, wimg, 0u, tm, tt);
  } else {
    nat::fold_kernel<<<27, 256>>>(wqkv, wo, wimg);
    nat::nat_kernel<<<grid, 384, nat::kSmemBytes>>>(x, out, nullptr, nullptr, wimg, 0u, tm, tt);
  }
}
```

```cpp
#include <cuda_runtime.h>
#include <cuda_bf16.h>
#include <cuda.h>
#include <stdint.h>

#define NAT_P1 2
#define NAT_P2 4
#define NAT_H0 2
#define NAT_T0 2100
#define NAT_TD 1200
#define NAT_TW2 4650
#define NAT_TX2 3800
#define NAT_X1P 5
#define NAT_PK 3
#define NAT_HP 1800
#define NAT_PFD 400
#define NAT_XW 200
#define NAT_MP 3
#define NAT_D0 1
#define NAT_TH 600
#define NAT_TM 1300
#define NAT_SB 0
namespace nat {

constexpr int kW = 224, kC = 192;
constexpr int kCtas = 132;
constexpr int kTilesPerCta = 6;
constexpr float kAlpha = 0.07216878364870322f * 1.4426950408889634f;
constexpr uint32_t kChunkBytes = 13 * 1024;
constexpr uint32_t kWChunk = 192 * 128;
constexpr uint32_t kWBytes = 3 * kWChunk;
constexpr uint32_t kW1Off = 6 * kChunkBytes;
constexpr uint32_t kW2Off = kW1Off + kWBytes;
constexpr uint32_t kXOff = kW2Off + kWChunk;
constexpr uint32_t kBarOff = kW2Off + kWBytes;
constexpr uint32_t kProfOff = kBarOff + 208;
constexpr uint32_t kSmemBytes = kBarOff + 1024;

static_assert(kW1Off % 1024 == 0 && kW2Off % 1024 == 0 && kChunkBytes % 1024 == 0, "swizzle alignment");
static_assert(kSmemBytes <= 232448, "smem");

constexpr uint32_t kEmpty = 0xFFFFFFFFu;
#define NAT_R8(v) v, v, v, v, v, v, v, v
#define NAT_R2K(v) NAT_R8(NAT_R8(NAT_R8(v))), NAT_R8(NAT_R8(NAT_R8(v))), NAT_R8(NAT_R8(NAT_R8(v))), NAT_R8(NAT_R8(NAT_R8(v)))
#define NAT_IMG NAT_R8(NAT_R2K(kEmpty)), NAT_R2K(kEmpty)
__device__ __align__(1024) uint32_t g_wimg32[3 * kWBytes / 4] = {NAT_IMG, NAT_IMG, NAT_IMG};
static_assert(kWBytes / 4 == 9 * 2048, "initialiser");
__device__ __align__(128) uint32_t g_flag[96];
__device__ __forceinline__ uint32_t w2_offset() {
  uint32_t v;
  asm volatile("ld.relaxed.gpu.global.u32 %0, [%1];" : "=r"(v) : "l"(g_flag + 64) : "memory");
  return (1 + v) * kWBytes;
}

#define PROFS(id, wgid, slotid) do { } while (0)
#define PROF(wgid, slotid) do { } while (0)
#define PROF_DUMP(wgid) do { } while (0)

#define GT(slotid) do { } while (0)
#define GT_DUMP() do { } while (0)

__device__ __forceinline__ uint32_t smem_u32(const void* p) { return (uint32_t)__cvta_generic_to_shared(p); }

__device__ __forceinline__ void mbar_init(uint32_t bar, uint32_t count) {
  asm volatile("mbarrier.init.shared::cta.b64 [%0], %1;" ::"r"(bar), "r"(count) : "memory");
}
__device__ __forceinline__ void mbar_arrive(uint32_t bar) {
  asm volatile("mbarrier.arrive.shared::cta.b64 _, [%0];" ::"r"(bar) : "memory");
}
__device__ __forceinline__ void mbar_arrive_expect_tx(uint32_t bar, uint32_t bytes) {
  asm volatile("mbarrier.arrive.expect_tx.shared::cta.b64 _, [%0], %1;" ::"r"(bar), "r"(bytes) : "memory");
}
__device__ __forceinline__ void mbar_wait(uint32_t bar, uint32_t parity) {
  uint32_t ok;
  uint32_t it = 0;
  do {
    asm volatile(
        "{\n.reg .pred p;\n"
        "mbarrier.try_wait.parity.shared::cta.b64 p, [%1], %2;\n"
        "selp.u32 %0, 1, 0, p;\n}\n"
        : "=r"(ok)
        : "r"(bar), "r"(parity)
        : "memory");
    if (++it > (1u << 24)) break;
  } while (!ok);
}
__device__ __forceinline__ uint32_t mbar_test(uint32_t bar, uint32_t parity) {
  uint32_t ok;
  asm volatile("{\n.reg .pred p;\nmbarrier.test_wait.parity.shared::cta.b64 p, [%1], %2;\nselp.u32 %0, 1, 0, p;\n}\n"
               : "=r"(ok) : "r"(bar), "r"(parity) : "memory");
  return ok;
}
__device__ __forceinline__ void mbar_wait_if(uint32_t ok, uint32_t bar, uint32_t parity) {
  if (!__all_sync(0xffffffffu, ok)) mbar_wait(bar, parity);
}
__device__ __forceinline__ bool elect_one() {
  uint32_t r;
  asm volatile("{\n.reg .pred p;\nelect.sync _|p, 0xffffffff;\nselp.u32 %0, 1, 0, p;\n}\n" : "=r"(r));
  return r != 0;
}
__device__ __forceinline__ void nb_arrive(int id) { asm volatile("bar.arrive %0, 256;" ::"r"(id) : "memory"); }
__device__ __forceinline__ void nb_sync(int id) { asm volatile("bar.sync %0, 256;" ::"r"(id) : "memory"); }
__device__ __forceinline__ void nb_arrive_p(int id) { asm volatile("bar.arrive %0, 160;" ::"r"(id) : "memory"); }
__device__ __forceinline__ void nb_sync_p(int id) { asm volatile("bar.sync %0, 160;" ::"r"(id) : "memory"); }
__device__ __forceinline__ void fence_proxy_async() { asm volatile("fence.proxy.async.shared::cta;" ::: "memory"); }

__device__ __forceinline__ void tma_load_5d(uint32_t dst, const CUtensorMap* map, uint32_t bar, int c0, int c1, int c2,
                                            int c3, int c4) {
  asm volatile(
      "cp.async.bulk.tensor.5d.shared::cluster.global.tile.mbarrier::complete_tx::bytes "
      "[%0], [%1, {%3, %4, %5, %6, %7}], [%2];"
      ::"r"(dst), "l"((uint64_t)map), "r"(bar), "r"(c0), "r"(c1), "r"(c2), "r"(c3), "r"(c4)
      : "memory");
}
__device__ __forceinline__ void bulk_load(uint32_t dst, const void* src, uint32_t bytes, uint32_t bar) {
  asm volatile("cp.async.bulk.shared::cluster.global.mbarrier::complete_tx::bytes [%0], [%1], %2, [%3];"
               ::"r"(dst), "l"((uint64_t)src), "r"(bytes), "r"(bar)
               : "memory");
}

__device__ __forceinline__ void wg_fence() { asm volatile("wgmma.fence.sync.aligned;" ::: "memory"); }
__device__ __forceinline__ void wg_commit() { asm volatile("wgmma.commit_group.sync.aligned;" ::: "memory"); }
template <int N>
__device__ __forceinline__ void wg_wait() { asm volatile("wgmma.wait_group.sync.aligned %0;" ::"n"(N) : "memory"); }

template <int N>
__device__ __forceinline__ void fence_regs(float (&d)[N]) {
#pragma unroll
  for (int i = 0; i < N; i++) asm volatile("" : "+f"(d[i])::"memory");
}
template <int N>
__device__ __forceinline__ void keep_regs(uint32_t (&d)[N]) {
#pragma unroll
  for (int i = 0; i < N; i++) asm volatile("" : "+r"(d[i])::"memory");
}

__device__ __forceinline__ uint32_t pack_bf16(float lo, float hi) {
  uint32_t d;
  asm("cvt.rn.bf16x2.f32 %0, %1, %2;" : "=r"(d) : "f"(hi), "f"(lo));
  return d;
}
__device__ __forceinline__ float ex2(float x) {
  float y;
  asm("ex2.approx.ftz.f32 %0, %1;" : "=f"(y) : "f"(x));
  return y;
}
__device__ __forceinline__ float rcp_approx(float x) {
  float y;
  asm("rcp.approx.ftz.f32 %0, %1;" : "=f"(y) : "f"(x));
  return y;
}
__device__ __forceinline__ uint4 ldg128_nc(const void* p) {
  uint4 v;
  asm volatile("ld.global.nc.v4.u32 {%0,%1,%2,%3}, [%4];" : "=r"(v.x), "=r"(v.y), "=r"(v.z), "=r"(v.w) : "l"(p));
  return v;
}
__device__ __forceinline__ void stg128(void* p, uint32_t a, uint32_t b, uint32_t c, uint32_t d) {
  asm volatile("st.global.v4.u32 [%0], {%1,%2,%3,%4};" ::"l"(p), "r"(a), "r"(b), "r"(c), "r"(d) : "memory");
}

__device__ __forceinline__ long long clk64() {
  long long c;
  asm volatile("mov.u64 %0, %clock64;" : "=l"(c)::"memory");
  return c;
}
__device__ __forceinline__ void sched_fence() { while (clk64() < 0) { } }

__device__ __forceinline__ uint64_t make_desc(uint32_t addr, uint32_t lbo, uint32_t sbo, uint32_t mode = 1) {
  return (uint64_t)((addr & 0x3FFFF) >> 4) | ((uint64_t)(lbo >> 4) << 16) | ((uint64_t)(sbo >> 4) << 32) |
         ((uint64_t)mode << 62);
}

template <int OFF, int NN>
__device__ __forceinline__ void wg_m192(float (&d)[NN], uint64_t desc_a, uint64_t desc_b, int scale_d) {
  asm volatile(
      "{\n.reg .pred p;\nsetp.ne.b32 p, %98, 0;\n"
      "wgmma.mma_async.sync.aligned.m64n192k16.f32.bf16.bf16 "
      "{%0,%1,%2,%3,%4,%5,%6,%7,%8,%9,%10,%11,%12,%13,%14,%15,"
      "%16,%17,%18,%19,%20,%21,%22,%23,%24,%25,%26,%27,%28,%29,%30,%31,"
      "%32,%33,%34,%35,%36,%37,%38,%39,%40,%41,%42,%43,%44,%45,%46,%47,"
      "%48,%49,%50,%51,%52,%53,%54,%55,%56,%57,%58,%59,%60,%61,%62,%63,"
      "%64,%65,%66,%67,%68,%69,%70,%71,%72,%73,%74,%75,%76,%77,%78,%79,"
      "%80,%81,%82,%83,%84,%85,%86,%87,%88,%89,%90,%91,%92,%93,%94,%95}, "
      "%96, %97, p, 1, 1, 0, 0;\n}\n"
      : "+f"(d[OFF + 0]), "+f"(d[OFF + 1]), "+f"(d[OFF + 2]), "+f"(d[OFF + 3]), "+f"(d[OFF + 4]), "+f"(d[OFF + 5]),
        "+f"(d[OFF + 6]), "+f"(d[OFF + 7]), "+f"(d[OFF + 8]), "+f"(d[OFF + 9]), "+f"(d[OFF + 10]), "+f"(d[OFF + 11]),
        "+f"(d[OFF + 12]), "+f"(d[OFF + 13]), "+f"(d[OFF + 14]), "+f"(d[OFF + 15]), "+f"(d[OFF + 16]), "+f"(d[OFF + 17]),
        "+f"(d[OFF + 18]), "+f"(d[OFF + 19]), "+f"(d[OFF + 20]), "+f"(d[OFF + 21]), "+f"(d[OFF + 22]), "+f"(d[OFF + 23]),
        "+f"(d[OFF + 24]), "+f"(d[OFF + 25]), "+f"(d[OFF + 26]), "+f"(d[OFF + 27]), "+f"(d[OFF + 28]), "+f"(d[OFF + 29]),
        "+f"(d[OFF + 30]), "+f"(d[OFF + 31]), "+f"(d[OFF + 32]), "+f"(d[OFF + 33]), "+f"(d[OFF + 34]), "+f"(d[OFF + 35]),
        "+f"(d[OFF + 36]), "+f"(d[OFF + 37]), "+f"(d[OFF + 38]), "+f"(d[OFF + 39]), "+f"(d[OFF + 40]), "+f"(d[OFF + 41]),
        "+f"(d[OFF + 42]), "+f"(d[OFF + 43]), "+f"(d[OFF + 44]), "+f"(d[OFF + 45]), "+f"(d[OFF + 46]), "+f"(d[OFF + 47]),
        "+f"(d[OFF + 48]), "+f"(d[OFF + 49]), "+f"(d[OFF + 50]), "+f"(d[OFF + 51]), "+f"(d[OFF + 52]), "+f"(d[OFF + 53]),
        "+f"(d[OFF + 54]), "+f"(d[OFF + 55]), "+f"(d[OFF + 56]), "+f"(d[OFF + 57]), "+f"(d[OFF + 58]), "+f"(d[OFF + 59]),
        "+f"(d[OFF + 60]), "+f"(d[OFF + 61]), "+f"(d[OFF + 62]), "+f"(d[OFF + 63]), "+f"(d[OFF + 64]), "+f"(d[OFF + 65]),
        "+f"(d[OFF + 66]), "+f"(d[OFF + 67]), "+f"(d[OFF + 68]), "+f"(d[OFF + 69]), "+f"(d[OFF + 70]), "+f"(d[OFF + 71]),
        "+f"(d[OFF + 72]), "+f"(d[OFF + 73]), "+f"(d[OFF + 74]), "+f"(d[OFF + 75]), "+f"(d[OFF + 76]), "+f"(d[OFF + 77]),
        "+f"(d[OFF + 78]), "+f"(d[OFF + 79]), "+f"(d[OFF + 80]), "+f"(d[OFF + 81]), "+f"(d[OFF + 82]), "+f"(d[OFF + 83]),
        "+f"(d[OFF + 84]), "+f"(d[OFF + 85]), "+f"(d[OFF + 86]), "+f"(d[OFF + 87]), "+f"(d[OFF + 88]), "+f"(d[OFF + 89]),
        "+f"(d[OFF + 90]), "+f"(d[OFF + 91]), "+f"(d[OFF + 92]), "+f"(d[OFF + 93]), "+f"(d[OFF + 94]), "+f"(d[OFF + 95])
      : "l"(desc_a), "l"(desc_b), "r"(scale_d));
}

template <int OFF, int NN>
__device__ __forceinline__ void wg_m192z(float (&d)[NN], uint64_t desc_a, uint64_t desc_b, int scale_d) {
  asm volatile(
      "{\n.reg .pred p;\nsetp.ne.b32 p, %98, 0;\n"
      "wgmma.mma_async.sync.aligned.m64n192k16.f32.bf16.bf16 "
      "{%0,%1,%2,%3,%4,%5,%6,%7,%8,%9,%10,%11,%12,%13,%14,%15,"
      "%16,%17,%18,%19,%20,%21,%22,%23,%24,%25,%26,%27,%28,%29,%30,%31,"
      "%32,%33,%34,%35,%36,%37,%38,%39,%40,%41,%42,%43,%44,%45,%46,%47,"
      "%48,%49,%50,%51,%52,%53,%54,%55,%56,%57,%58,%59,%60,%61,%62,%63,"
      "%64,%65,%66,%67,%68,%69,%70,%71,%72,%73,%74,%75,%76,%77,%78,%79,"
      "%80,%81,%82,%83,%84,%85,%86,%87,%88,%89,%90,%91,%92,%93,%94,%95}, "
      "%96, %97, p, 1, 1, 0, 0;\n}\n"
      : "=f"(d[OFF + 0]), "=f"(d[OFF + 1]), "=f"(d[OFF + 2]), "=f"(d[OFF + 3]), "=f"(d[OFF + 4]), "=f"(d[OFF + 5]),
        "=f"(d[OFF + 6]), "=f"(d[OFF + 7]), "=f"(d[OFF + 8]), "=f"(d[OFF + 9]), "=f"(d[OFF + 10]), "=f"(d[OFF + 11]),
        "=f"(d[OFF + 12]), "=f"(d[OFF + 13]), "=f"(d[OFF + 14]), "=f"(d[OFF + 15]), "=f"(d[OFF + 16]), "=f"(d[OFF + 17]),
        "=f"(d[OFF + 18]), "=f"(d[OFF + 19]), "=f"(d[OFF + 20]), "=f"(d[OFF + 21]), "=f"(d[OFF + 22]), "=f"(d[OFF + 23]),
        "=f"(d[OFF + 24]), "=f"(d[OFF + 25]), "=f"(d[OFF + 26]), "=f"(d[OFF + 27]), "=f"(d[OFF + 28]), "=f"(d[OFF + 29]),
        "=f"(d[OFF + 30]), "=f"(d[OFF + 31]), "=f"(d[OFF + 32]), "=f"(d[OFF + 33]), "=f"(d[OFF + 34]), "=f"(d[OFF + 35]),
        "=f"(d[OFF + 36]), "=f"(d[OFF + 37]), "=f"(d[OFF + 38]), "=f"(d[OFF + 39]), "=f"(d[OFF + 40]), "=f"(d[OFF + 41]),
        "=f"(d[OFF + 42]), "=f"(d[OFF + 43]), "=f"(d[OFF + 44]), "=f"(d[OFF + 45]), "=f"(d[OFF + 46]), "=f"(d[OFF + 47]),
        "=f"(d[OFF + 48]), "=f"(d[OFF + 49]), "=f"(d[OFF + 50]), "=f"(d[OFF + 51]), "=f"(d[OFF + 52]), "=f"(d[OFF + 53]),
        "=f"(d[OFF + 54]), "=f"(d[OFF + 55]), "=f"(d[OFF + 56]), "=f"(d[OFF + 57]), "=f"(d[OFF + 58]), "=f"(d[OFF + 59]),
        "=f"(d[OFF + 60]), "=f"(d[OFF + 61]), "=f"(d[OFF + 62]), "=f"(d[OFF + 63]), "=f"(d[OFF + 64]), "=f"(d[OFF + 65]),
        "=f"(d[OFF + 66]), "=f"(d[OFF + 67]), "=f"(d[OFF + 68]), "=f"(d[OFF + 69]), "=f"(d[OFF + 70]), "=f"(d[OFF + 71]),
        "=f"(d[OFF + 72]), "=f"(d[OFF + 73]), "=f"(d[OFF + 74]), "=f"(d[OFF + 75]), "=f"(d[OFF + 76]), "=f"(d[OFF + 77]),
        "=f"(d[OFF + 78]), "=f"(d[OFF + 79]), "=f"(d[OFF + 80]), "=f"(d[OFF + 81]), "=f"(d[OFF + 82]), "=f"(d[OFF + 83]),
        "=f"(d[OFF + 84]), "=f"(d[OFF + 85]), "=f"(d[OFF + 86]), "=f"(d[OFF + 87]), "=f"(d[OFF + 88]), "=f"(d[OFF + 89]),
        "=f"(d[OFF + 90]), "=f"(d[OFF + 91]), "=f"(d[OFF + 92]), "=f"(d[OFF + 93]), "=f"(d[OFF + 94]), "=f"(d[OFF + 95])
      : "l"(desc_a), "l"(desc_b), "r"(scale_d));
}

template <int OFF, int NN>
__device__ __forceinline__ void wg_m64t(float (&d)[NN], uint64_t desc_a, uint64_t desc_b, int scale_d) {
  asm volatile(
      "{\n.reg .pred p;\nsetp.ne.b32 p, %34, 0;\n"
      "wgmma.mma_async.sync.aligned.m64n64k16.f32.bf16.bf16 "
      "{%0,%1,%2,%3,%4,%5,%6,%7,%8,%9,%10,%11,%12,%13,%14,%15,"
      "%16,%17,%18,%19,%20,%21,%22,%23,%24,%25,%26,%27,%28,%29,%30,%31}, "
      "%32, %33, p, 1, 1, 0, 1;\n}\n"
      : "+f"(d[OFF + 0]), "+f"(d[OFF + 1]), "+f"(d[OFF + 2]), "+f"(d[OFF + 3]), "+f"(d[OFF + 4]), "+f"(d[OFF + 5]),
        "+f"(d[OFF + 6]), "+f"(d[OFF + 7]), "+f"(d[OFF + 8]), "+f"(d[OFF + 9]), "+f"(d[OFF + 10]), "+f"(d[OFF + 11]),
        "+f"(d[OFF + 12]), "+f"(d[OFF + 13]), "+f"(d[OFF + 14]), "+f"(d[OFF + 15]), "+f"(d[OFF + 16]), "+f"(d[OFF + 17]),
        "+f"(d[OFF + 18]), "+f"(d[OFF + 19]), "+f"(d[OFF + 20]), "+f"(d[OFF + 21]), "+f"(d[OFF + 22]), "+f"(d[OFF + 23]),
        "+f"(d[OFF + 24]), "+f"(d[OFF + 25]), "+f"(d[OFF + 26]), "+f"(d[OFF + 27]), "+f"(d[OFF + 28]), "+f"(d[OFF + 29]),
        "+f"(d[OFF + 30]), "+f"(d[OFF + 31])
      : "l"(desc_a), "l"(desc_b), "r"(scale_d));
}

template <int OFF, int NN>
__device__ __forceinline__ void wg_m64tz(float (&d)[NN], uint64_t desc_a, uint64_t desc_b, int scale_d) {
  asm volatile(
      "{\n.reg .pred p;\nsetp.ne.b32 p, %34, 0;\n"
      "wgmma.mma_async.sync.aligned.m64n64k16.f32.bf16.bf16 "
      "{%0,%1,%2,%3,%4,%5,%6,%7,%8,%9,%10,%11,%12,%13,%14,%15,"
      "%16,%17,%18,%19,%20,%21,%22,%23,%24,%25,%26,%27,%28,%29,%30,%31}, "
      "%32, %33, p, 1, 1, 0, 1;\n}\n"
      : "=f"(d[OFF + 0]), "=f"(d[OFF + 1]), "=f"(d[OFF + 2]), "=f"(d[OFF + 3]), "=f"(d[OFF + 4]), "=f"(d[OFF + 5]),
        "=f"(d[OFF + 6]), "=f"(d[OFF + 7]), "=f"(d[OFF + 8]), "=f"(d[OFF + 9]), "=f"(d[OFF + 10]), "=f"(d[OFF + 11]),
        "=f"(d[OFF + 12]), "=f"(d[OFF + 13]), "=f"(d[OFF + 14]), "=f"(d[OFF + 15]), "=f"(d[OFF + 16]), "=f"(d[OFF + 17]),
        "=f"(d[OFF + 18]), "=f"(d[OFF + 19]), "=f"(d[OFF + 20]), "=f"(d[OFF + 21]), "=f"(d[OFF + 22]), "=f"(d[OFF + 23]),
        "=f"(d[OFF + 24]), "=f"(d[OFF + 25]), "=f"(d[OFF + 26]), "=f"(d[OFF + 27]), "=f"(d[OFF + 28]), "=f"(d[OFF + 29]),
        "=f"(d[OFF + 30]), "=f"(d[OFF + 31])
      : "l"(desc_a), "l"(desc_b), "r"(scale_d));
}

template <int OFF, int NN>
__device__ __forceinline__ void wg_d96(float (&d)[NN], uint32_t a0, uint32_t a1, uint32_t a2, uint32_t a3,
                                       uint64_t desc_b, int scale_d) {
  asm volatile(
      "{\n.reg .pred p;\nsetp.ne.b32 p, %53, 0;\n"
      "wgmma.mma_async.sync.aligned.m64n96k16.f32.bf16.bf16 "
      "{%0,%1,%2,%3,%4,%5,%6,%7,%8,%9,%10,%11,%12,%13,%14,%15,"
      "%16,%17,%18,%19,%20,%21,%22,%23,%24,%25,%26,%27,%28,%29,%30,%31,"
      "%32,%33,%34,%35,%36,%37,%38,%39,%40,%41,%42,%43,%44,%45,%46,%47}, "
      "{%48,%49,%50,%51}, %52, p, 1, 1, 0;\n}\n"
      : "+f"(d[OFF + 0]), "+f"(d[OFF + 1]), "+f"(d[OFF + 2]), "+f"(d[OFF + 3]), "+f"(d[OFF + 4]), "+f"(d[OFF + 5]),
        "+f"(d[OFF + 6]), "+f"(d[OFF + 7]), "+f"(d[OFF + 8]), "+f"(d[OFF + 9]), "+f"(d[OFF + 10]), "+f"(d[OFF + 11]),
        "+f"(d[OFF + 12]), "+f"(d[OFF + 13]), "+f"(d[OFF + 14]), "+f"(d[OFF + 15]), "+f"(d[OFF + 16]), "+f"(d[OFF + 17]),
        "+f"(d[OFF + 18]), "+f"(d[OFF + 19]), "+f"(d[OFF + 20]), "+f"(d[OFF + 21]), "+f"(d[OFF + 22]), "+f"(d[OFF + 23]),
        "+f"(d[OFF + 24]), "+f"(d[OFF + 25]), "+f"(d[OFF + 26]), "+f"(d[OFF + 27]), "+f"(d[OFF + 28]), "+f"(d[OFF + 29]),
        "+f"(d[OFF + 30]), "+f"(d[OFF + 31]), "+f"(d[OFF + 32]), "+f"(d[OFF + 33]), "+f"(d[OFF + 34]), "+f"(d[OFF + 35]),
        "+f"(d[OFF + 36]), "+f"(d[OFF + 37]), "+f"(d[OFF + 38]), "+f"(d[OFF + 39]), "+f"(d[OFF + 40]), "+f"(d[OFF + 41]),
        "+f"(d[OFF + 42]), "+f"(d[OFF + 43]), "+f"(d[OFF + 44]), "+f"(d[OFF + 45]), "+f"(d[OFF + 46]), "+f"(d[OFF + 47])
      : "r"(a0), "r"(a1), "r"(a2), "r"(a3), "l"(desc_b), "r"(scale_d));
}

template <int OFF, int NN>
__device__ __forceinline__ void wg_d96z(float (&d)[NN], uint32_t a0, uint32_t a1, uint32_t a2, uint32_t a3,
                                       uint64_t desc_b, int scale_d) {
  asm volatile(
      "{\n.reg .pred p;\nsetp.ne.b32 p, %53, 0;\n"
      "wgmma.mma_async.sync.aligned.m64n96k16.f32.bf16.bf16 "
      "{%0,%1,%2,%3,%4,%5,%6,%7,%8,%9,%10,%11,%12,%13,%14,%15,"
      "%16,%17,%18,%19,%20,%21,%22,%23,%24,%25,%26,%27,%28,%29,%30,%31,"
      "%32,%33,%34,%35,%36,%37,%38,%39,%40,%41,%42,%43,%44,%45,%46,%47}, "
      "{%48,%49,%50,%51}, %52, p, 1, 1, 0;\n}\n"
      : "=f"(d[OFF + 0]), "=f"(d[OFF + 1]), "=f"(d[OFF + 2]), "=f"(d[OFF + 3]), "=f"(d[OFF + 4]), "=f"(d[OFF + 5]),
        "=f"(d[OFF + 6]), "=f"(d[OFF + 7]), "=f"(d[OFF + 8]), "=f"(d[OFF + 9]), "=f"(d[OFF + 10]), "=f"(d[OFF + 11]),
        "=f"(d[OFF + 12]), "=f"(d[OFF + 13]), "=f"(d[OFF + 14]), "=f"(d[OFF + 15]), "=f"(d[OFF + 16]), "=f"(d[OFF + 17]),
        "=f"(d[OFF + 18]), "=f"(d[OFF + 19]), "=f"(d[OFF + 20]), "=f"(d[OFF + 21]), "=f"(d[OFF + 22]), "=f"(d[OFF + 23]),
        "=f"(d[OFF + 24]), "=f"(d[OFF + 25]), "=f"(d[OFF + 26]), "=f"(d[OFF + 27]), "=f"(d[OFF + 28]), "=f"(d[OFF + 29]),
        "=f"(d[OFF + 30]), "=f"(d[OFF + 31]), "=f"(d[OFF + 32]), "=f"(d[OFF + 33]), "=f"(d[OFF + 34]), "=f"(d[OFF + 35]),
        "=f"(d[OFF + 36]), "=f"(d[OFF + 37]), "=f"(d[OFF + 38]), "=f"(d[OFF + 39]), "=f"(d[OFF + 40]), "=f"(d[OFF + 41]),
        "=f"(d[OFF + 42]), "=f"(d[OFF + 43]), "=f"(d[OFF + 44]), "=f"(d[OFF + 45]), "=f"(d[OFF + 46]), "=f"(d[OFF + 47])
      : "r"(a0), "r"(a1), "r"(a2), "r"(a3), "l"(desc_b), "r"(scale_d));
}

template <int OFF, int NN>
__device__ __forceinline__ void wg_s104(float (&d)[NN], uint32_t a0, uint32_t a1, uint32_t a2, uint32_t a3,
                                       uint64_t desc_b, int scale_d, uint32_t meta) {
  asm volatile(
      "{\n.reg .pred p;\nsetp.ne.b32 p, %57, 0;\n"
      "wgmma.mma_async.sp.sync.aligned.m64n104k32.f32.bf16.bf16 "
      "{%0,%1,%2,%3,%4,%5,%6,%7,%8,%9,%10,%11,%12,%13,%14,%15,"
      "%16,%17,%18,%19,%20,%21,%22,%23,%24,%25,%26,%27,%28,%29,%30,%31,"
      "%32,%33,%34,%35,%36,%37,%38,%39,%40,%41,%42,%43,%44,%45,%46,%47,"
      "%48,%49,%50,%51}, "
      "{%52,%53,%54,%55}, %56, %58, 0, p, 1, 1, 0;\n}\n"
      : "+f"(d[OFF + 0]), "+f"(d[OFF + 1]), "+f"(d[OFF + 2]), "+f"(d[OFF + 3]), "+f"(d[OFF + 4]), "+f"(d[OFF + 5]),
        "+f"(d[OFF + 6]), "+f"(d[OFF + 7]), "+f"(d[OFF + 8]), "+f"(d[OFF + 9]), "+f"(d[OFF + 10]), "+f"(d[OFF + 11]),
        "+f"(d[OFF + 12]), "+f"(d[OFF + 13]), "+f"(d[OFF + 14]), "+f"(d[OFF + 15]), "+f"(d[OFF + 16]), "+f"(d[OFF + 17]),
        "+f"(d[OFF + 18]), "+f"(d[OFF + 19]), "+f"(d[OFF + 20]), "+f"(d[OFF + 21]), "+f"(d[OFF + 22]), "+f"(d[OFF + 23]),
        "+f"(d[OFF + 24]), "+f"(d[OFF + 25]), "+f"(d[OFF + 26]), "+f"(d[OFF + 27]), "+f"(d[OFF + 28]), "+f"(d[OFF + 29]),
        "+f"(d[OFF + 30]), "+f"(d[OFF + 31]), "+f"(d[OFF + 32]), "+f"(d[OFF + 33]), "+f"(d[OFF + 34]), "+f"(d[OFF + 35]),
        "+f"(d[OFF + 36]), "+f"(d[OFF + 37]), "+f"(d[OFF + 38]), "+f"(d[OFF + 39]), "+f"(d[OFF + 40]), "+f"(d[OFF + 41]),
        "+f"(d[OFF + 42]), "+f"(d[OFF + 43]), "+f"(d[OFF + 44]), "+f"(d[OFF + 45]), "+f"(d[OFF + 46]), "+f"(d[OFF + 47]),
        "+f"(d[OFF + 48]), "+f"(d[OFF + 49]), "+f"(d[OFF + 50]), "+f"(d[OFF + 51])
      : "r"(a0), "r"(a1), "r"(a2), "r"(a3), "l"(desc_b), "r"(scale_d), "r"(meta));
}

template <int OFF, int NN>
__device__ __forceinline__ void wg_s104z(float (&d)[NN], uint32_t a0, uint32_t a1, uint32_t a2, uint32_t a3,
                                       uint64_t desc_b, int scale_d, uint32_t meta) {
  asm volatile(
      "{\n.reg .pred p;\nsetp.ne.b32 p, %57, 0;\n"
      "wgmma.mma_async.sp.sync.aligned.m64n104k32.f32.bf16.bf16 "
      "{%0,%1,%2,%3,%4,%5,%6,%7,%8,%9,%10,%11,%12,%13,%14,%15,"
      "%16,%17,%18,%19,%20,%21,%22,%23,%24,%25,%26,%27,%28,%29,%30,%31,"
      "%32,%33,%34,%35,%36,%37,%38,%39,%40,%41,%42,%43,%44,%45,%46,%47,"
      "%48,%49,%50,%51}, "
      "{%52,%53,%54,%55}, %56, %58, 0, p, 1, 1, 0;\n}\n"
      : "=f"(d[OFF + 0]), "=f"(d[OFF + 1]), "=f"(d[OFF + 2]), "=f"(d[OFF + 3]), "=f"(d[OFF + 4]), "=f"(d[OFF + 5]),
        "=f"(d[OFF + 6]), "=f"(d[OFF + 7]), "=f"(d[OFF + 8]), "=f"(d[OFF + 9]), "=f"(d[OFF + 10]), "=f"(d[OFF + 11]),
        "=f"(d[OFF + 12]), "=f"(d[OFF + 13]), "=f"(d[OFF + 14]), "=f"(d[OFF + 15]), "=f"(d[OFF + 16]), "=f"(d[OFF + 17]),
        "=f"(d[OFF + 18]), "=f"(d[OFF + 19]), "=f"(d[OFF + 20]), "=f"(d[OFF + 21]), "=f"(d[OFF + 22]), "=f"(d[OFF + 23]),
        "=f"(d[OFF + 24]), "=f"(d[OFF + 25]), "=f"(d[OFF + 26]), "=f"(d[OFF + 27]), "=f"(d[OFF + 28]), "=f"(d[OFF + 29]),
        "=f"(d[OFF + 30]), "=f"(d[OFF + 31]), "=f"(d[OFF + 32]), "=f"(d[OFF + 33]), "=f"(d[OFF + 34]), "=f"(d[OFF + 35]),
        "=f"(d[OFF + 36]), "=f"(d[OFF + 37]), "=f"(d[OFF + 38]), "=f"(d[OFF + 39]), "=f"(d[OFF + 40]), "=f"(d[OFF + 41]),
        "=f"(d[OFF + 42]), "=f"(d[OFF + 43]), "=f"(d[OFF + 44]), "=f"(d[OFF + 45]), "=f"(d[OFF + 46]), "=f"(d[OFF + 47]),
        "=f"(d[OFF + 48]), "=f"(d[OFF + 49]), "=f"(d[OFF + 50]), "=f"(d[OFF + 51])
      : "r"(a0), "r"(a1), "r"(a2), "r"(a3), "l"(desc_b), "r"(scale_d), "r"(meta));
}

template <int OFF, int NN>
__device__ __forceinline__ void wg_s48(float (&d)[NN], uint32_t a0, uint32_t a1, uint32_t a2, uint32_t a3,
                                       uint64_t desc_b, int scale_d, uint32_t meta) {
  asm volatile(
      "{\n.reg .pred p;\nsetp.ne.b32 p, %29, 0;\n"
      "wgmma.mma_async.sp.sync.aligned.m64n48k32.f32.bf16.bf16 "
      "{%0,%1,%2,%3,%4,%5,%6,%7,%8,%9,%10,%11,%12,%13,%14,%15,"
      "%16,%17,%18,%19,%20,%21,%22,%23}, "
      "{%24,%25,%26,%27}, %28, %30, 0, p, 1, 1, 0;\n}\n"
      : "+f"(d[OFF + 0]), "+f"(d[OFF + 1]), "+f"(d[OFF + 2]), "+f"(d[OFF + 3]), "+f"(d[OFF + 4]), "+f"(d[OFF + 5]),
        "+f"(d[OFF + 6]), "+f"(d[OFF + 7]), "+f"(d[OFF + 8]), "+f"(d[OFF + 9]), "+f"(d[OFF + 10]), "+f"(d[OFF + 11]),
        "+f"(d[OFF + 12]), "+f"(d[OFF + 13]), "+f"(d[OFF + 14]), "+f"(d[OFF + 15]), "+f"(d[OFF + 16]), "+f"(d[OFF + 17]),
        "+f"(d[OFF + 18]), "+f"(d[OFF + 19]), "+f"(d[OFF + 20]), "+f"(d[OFF + 21]), "+f"(d[OFF + 22]), "+f"(d[OFF + 23])
      : "r"(a0), "r"(a1), "r"(a2), "r"(a3), "l"(desc_b), "r"(scale_d), "r"(meta));
}

template <int OFF, int NN>
__device__ __forceinline__ void wg_s48z(float (&d)[NN], uint32_t a0, uint32_t a1, uint32_t a2, uint32_t a3,
                                       uint64_t desc_b, int scale_d, uint32_t meta) {
  asm volatile(
      "{\n.reg .pred p;\nsetp.ne.b32 p, %29, 0;\n"
      "wgmma.mma_async.sp.sync.aligned.m64n48k32.f32.bf16.bf16 "
      "{%0,%1,%2,%3,%4,%5,%6,%7,%8,%9,%10,%11,%12,%13,%14,%15,"
      "%16,%17,%18,%19,%20,%21,%22,%23}, "
      "{%24,%25,%26,%27}, %28, %30, 0, p, 1, 1, 0;\n}\n"
      : "=f"(d[OFF + 0]), "=f"(d[OFF + 1]), "=f"(d[OFF + 2]), "=f"(d[OFF + 3]), "=f"(d[OFF + 4]), "=f"(d[OFF + 5]),
        "=f"(d[OFF + 6]), "=f"(d[OFF + 7]), "=f"(d[OFF + 8]), "=f"(d[OFF + 9]), "=f"(d[OFF + 10]), "=f"(d[OFF + 11]),
        "=f"(d[OFF + 12]), "=f"(d[OFF + 13]), "=f"(d[OFF + 14]), "=f"(d[OFF + 15]), "=f"(d[OFF + 16]), "=f"(d[OFF + 17]),
        "=f"(d[OFF + 18]), "=f"(d[OFF + 19]), "=f"(d[OFF + 20]), "=f"(d[OFF + 21]), "=f"(d[OFF + 22]), "=f"(d[OFF + 23])
      : "r"(a0), "r"(a1), "r"(a2), "r"(a3), "l"(desc_b), "r"(scale_d), "r"(meta));
}

template <int OFF, int NN>
__device__ __forceinline__ void wg_s56(float (&d)[NN], uint32_t a0, uint32_t a1, uint32_t a2, uint32_t a3,
                                       uint64_t desc_b, int scale_d, uint32_t meta) {
  asm volatile(
      "{\n.reg .pred p;\nsetp.ne.b32 p, %33, 0;\n"
      "wgmma.mma_async.sp.sync.aligned.m64n56k32.f32.bf16.bf16 "
      "{%0,%1,%2,%3,%4,%5,%6,%7,%8,%9,%10,%11,%12,%13,%14,%15,"
      "%16,%17,%18,%19,%20,%21,%22,%23,%24,%25,%26,%27}, "
      "{%28,%29,%30,%31}, %32, %34, 0, p, 1, 1, 0;\n}\n"
      : "+f"(d[OFF + 0]), "+f"(d[OFF + 1]), "+f"(d[OFF + 2]), "+f"(d[OFF + 3]), "+f"(d[OFF + 4]), "+f"(d[OFF + 5]),
        "+f"(d[OFF + 6]), "+f"(d[OFF + 7]), "+f"(d[OFF + 8]), "+f"(d[OFF + 9]), "+f"(d[OFF + 10]), "+f"(d[OFF + 11]),
        "+f"(d[OFF + 12]), "+f"(d[OFF + 13]), "+f"(d[OFF + 14]), "+f"(d[OFF + 15]), "+f"(d[OFF + 16]), "+f"(d[OFF + 17]),
        "+f"(d[OFF + 18]), "+f"(d[OFF + 19]), "+f"(d[OFF + 20]), "+f"(d[OFF + 21]), "+f"(d[OFF + 22]), "+f"(d[OFF + 23]),
        "+f"(d[OFF + 24]), "+f"(d[OFF + 25]), "+f"(d[OFF + 26]), "+f"(d[OFF + 27])
      : "r"(a0), "r"(a1), "r"(a2), "r"(a3), "l"(desc_b), "r"(scale_d), "r"(meta));
}

template <int OFF, int NN>
__device__ __forceinline__ void wg_s56z(float (&d)[NN], uint32_t a0, uint32_t a1, uint32_t a2, uint32_t a3,
                                       uint64_t desc_b, int scale_d, uint32_t meta) {
  asm volatile(
      "{\n.reg .pred p;\nsetp.ne.b32 p, %33, 0;\n"
      "wgmma.mma_async.sp.sync.aligned.m64n56k32.f32.bf16.bf16 "
      "{%0,%1,%2,%3,%4,%5,%6,%7,%8,%9,%10,%11,%12,%13,%14,%15,"
      "%16,%17,%18,%19,%20,%21,%22,%23,%24,%25,%26,%27}, "
      "{%28,%29,%30,%31}, %32, %34, 0, p, 1, 1, 0;\n}\n"
      : "=f"(d[OFF + 0]), "=f"(d[OFF + 1]), "=f"(d[OFF + 2]), "=f"(d[OFF + 3]), "=f"(d[OFF + 4]), "=f"(d[OFF + 5]),
        "=f"(d[OFF + 6]), "=f"(d[OFF + 7]), "=f"(d[OFF + 8]), "=f"(d[OFF + 9]), "=f"(d[OFF + 10]), "=f"(d[OFF + 11]),
        "=f"(d[OFF + 12]), "=f"(d[OFF + 13]), "=f"(d[OFF + 14]), "=f"(d[OFF + 15]), "=f"(d[OFF + 16]), "=f"(d[OFF + 17]),
        "=f"(d[OFF + 18]), "=f"(d[OFF + 19]), "=f"(d[OFF + 20]), "=f"(d[OFF + 21]), "=f"(d[OFF + 22]), "=f"(d[OFF + 23]),
        "=f"(d[OFF + 24]), "=f"(d[OFF + 25]), "=f"(d[OFF + 26]), "=f"(d[OFF + 27])
      : "r"(a0), "r"(a1), "r"(a2), "r"(a3), "l"(desc_b), "r"(scale_d), "r"(meta));
}

template <int OFF, int NN>
__device__ __forceinline__ void wg_s64t(float (&d)[NN], uint32_t a0, uint32_t a1, uint32_t a2, uint32_t a3,
                                       uint64_t desc_b, int scale_d, uint32_t meta) {
  asm volatile(
      "{\n.reg .pred p;\nsetp.ne.b32 p, %37, 0;\n"
      "wgmma.mma_async.sp.sync.aligned.m64n64k32.f32.bf16.bf16 "
      "{%0,%1,%2,%3,%4,%5,%6,%7,%8,%9,%10,%11,%12,%13,%14,%15,"
      "%16,%17,%18,%19,%20,%21,%22,%23,%24,%25,%26,%27,%28,%29,%30,%31}, "
      "{%32,%33,%34,%35}, %36, %38, 0, p, 1, 1, 1;\n}\n"
      : "+f"(d[OFF + 0]), "+f"(d[OFF + 1]), "+f"(d[OFF + 2]), "+f"(d[OFF + 3]), "+f"(d[OFF + 4]), "+f"(d[OFF + 5]),
        "+f"(d[OFF + 6]), "+f"(d[OFF + 7]), "+f"(d[OFF + 8]), "+f"(d[OFF + 9]), "+f"(d[OFF + 10]), "+f"(d[OFF + 11]),
        "+f"(d[OFF + 12]), "+f"(d[OFF + 13]), "+f"(d[OFF + 14]), "+f"(d[OFF + 15]), "+f"(d[OFF + 16]), "+f"(d[OFF + 17]),
        "+f"(d[OFF + 18]), "+f"(d[OFF + 19]), "+f"(d[OFF + 20]), "+f"(d[OFF + 21]), "+f"(d[OFF + 22]), "+f"(d[OFF + 23]),
        "+f"(d[OFF + 24]), "+f"(d[OFF + 25]), "+f"(d[OFF + 26]), "+f"(d[OFF + 27]), "+f"(d[OFF + 28]), "+f"(d[OFF + 29]),
        "+f"(d[OFF + 30]), "+f"(d[OFF + 31])
      : "r"(a0), "r"(a1), "r"(a2), "r"(a3), "l"(desc_b), "r"(scale_d), "r"(meta));
}

template <int OFF, int NN>
__device__ __forceinline__ void wg_s64t1(float (&d)[NN], uint32_t a0, uint32_t a1, uint32_t a2, uint32_t a3,
                                       uint64_t desc_b, int scale_d, uint32_t meta) {
  asm volatile(
      "{\n.reg .pred p;\nsetp.ne.b32 p, %37, 0;\n"
      "wgmma.mma_async.sp.sync.aligned.m64n64k32.f32.bf16.bf16 "
      "{%0,%1,%2,%3,%4,%5,%6,%7,%8,%9,%10,%11,%12,%13,%14,%15,"
      "%16,%17,%18,%19,%20,%21,%22,%23,%24,%25,%26,%27,%28,%29,%30,%31}, "
      "{%32,%33,%34,%35}, %36, %38, 1, p, 1, 1, 1;\n}\n"
      : "+f"(d[OFF + 0]), "+f"(d[OFF + 1]), "+f"(d[OFF + 2]), "+f"(d[OFF + 3]), "+f"(d[OFF + 4]), "+f"(d[OFF + 5]),
        "+f"(d[OFF + 6]), "+f"(d[OFF + 7]), "+f"(d[OFF + 8]), "+f"(d[OFF + 9]), "+f"(d[OFF + 10]), "+f"(d[OFF + 11]),
        "+f"(d[OFF + 12]), "+f"(d[OFF + 13]), "+f"(d[OFF + 14]), "+f"(d[OFF + 15]), "+f"(d[OFF + 16]), "+f"(d[OFF + 17]),
        "+f"(d[OFF + 18]), "+f"(d[OFF + 19]), "+f"(d[OFF + 20]), "+f"(d[OFF + 21]), "+f"(d[OFF + 22]), "+f"(d[OFF + 23]),
        "+f"(d[OFF + 24]), "+f"(d[OFF + 25]), "+f"(d[OFF + 26]), "+f"(d[OFF + 27]), "+f"(d[OFF + 28]), "+f"(d[OFF + 29]),
        "+f"(d[OFF + 30]), "+f"(d[OFF + 31])
      : "r"(a0), "r"(a1), "r"(a2), "r"(a3), "l"(desc_b), "r"(scale_d), "r"(meta));
}

template <int OFF, int NN>
__device__ __forceinline__ void wg_s64tz(float (&d)[NN], uint32_t a0, uint32_t a1, uint32_t a2, uint32_t a3,
                                       uint64_t desc_b, int scale_d, uint32_t meta) {
  asm volatile(
      "{\n.reg .pred p;\nsetp.ne.b32 p, %37, 0;\n"
      "wgmma.mma_async.sp.sync.aligned.m64n64k32.f32.bf16.bf16 "
      "{%0,%1,%2,%3,%4,%5,%6,%7,%8,%9,%10,%11,%12,%13,%14,%15,"
      "%16,%17,%18,%19,%20,%21,%22,%23,%24,%25,%26,%27,%28,%29,%30,%31}, "
      "{%32,%33,%34,%35}, %36, %38, 0, p, 1, 1, 1;\n}\n"
      : "=f"(d[OFF + 0]), "=f"(d[OFF + 1]), "=f"(d[OFF + 2]), "=f"(d[OFF + 3]), "=f"(d[OFF + 4]), "=f"(d[OFF + 5]),
        "=f"(d[OFF + 6]), "=f"(d[OFF + 7]), "=f"(d[OFF + 8]), "=f"(d[OFF + 9]), "=f"(d[OFF + 10]), "=f"(d[OFF + 11]),
        "=f"(d[OFF + 12]), "=f"(d[OFF + 13]), "=f"(d[OFF + 14]), "=f"(d[OFF + 15]), "=f"(d[OFF + 16]), "=f"(d[OFF + 17]),
        "=f"(d[OFF + 18]), "=f"(d[OFF + 19]), "=f"(d[OFF + 20]), "=f"(d[OFF + 21]), "=f"(d[OFF + 22]), "=f"(d[OFF + 23]),
        "=f"(d[OFF + 24]), "=f"(d[OFF + 25]), "=f"(d[OFF + 26]), "=f"(d[OFF + 27]), "=f"(d[OFF + 28]), "=f"(d[OFF + 29]),
        "=f"(d[OFF + 30]), "=f"(d[OFF + 31])
      : "r"(a0), "r"(a1), "r"(a2), "r"(a3), "l"(desc_b), "r"(scale_d), "r"(meta));
}

__device__ __forceinline__ int g2_inv(int ch) { return 32 * (ch >> 5) + 8 * ((ch >> 1) & 3) + 2 * ((ch >> 3) & 3) + (ch & 1); }
__host__ __device__ __forceinline__ uint32_t wimg_off(int n, int k) {
  return (uint32_t)(k >> 6) * kWChunk + (uint32_t)n * 128 + (uint32_t)((((k & 63) >> 3) ^ (n & 7)) << 4) + (k & 7) * 2;
}
__host__ __device__ constexpr int w2piece(int h, int c) { return c == 2 ? 2 + h : 4 * h + c; }
__device__ __forceinline__ uint32_t w2img_off(int n, int k) { return wimg_off(n % 96, k & 63) + w2piece(n >= 96, k >> 6) * (kWChunk / 2); }
__device__ __forceinline__ int qpix(int par, int t) {
  const int a = 2 * t + 13 * par - 6, b = t + 112 * par;
  return par ? min(a, b) : max(a, b);
}
__device__ __forceinline__ int woff(int par, int i, int r) {
  const int a = 99 * par + 6 - 8 * i;
  return par ? min(r, a) : max(r, a);
}

__device__ __forceinline__ void mma16816(float (&c)[4], uint32_t a0, uint32_t a1, uint32_t a2, uint32_t a3, uint32_t b0,
                                         uint32_t b1) {
  asm volatile(
      "mma.sync.aligned.m16n8k16.row.col.f32.bf16.bf16.f32 {%0,%1,%2,%3}, {%4,%5,%6,%7}, {%8,%9}, {%0,%1,%2,%3};"
      : "+f"(c[0]), "+f"(c[1]), "+f"(c[2]), "+f"(c[3])
      : "r"(a0), "r"(a1), "r"(a2), "r"(a3), "r"(b0), "r"(b1));
}

__device__ __forceinline__ void fold_w1(const int u, const __nv_bfloat16* __restrict__ wqkv, uint8_t* wimg) {
  const int g = (threadIdx.x >> 2) & 7, l = threadIdx.x & 3;
  const int m0 = (u / 12) * 16, s = u % 12;
  uint4 A[12], B[12];
  const __nv_bfloat16* arow = wqkv + (m0 + 4 * (g >> 1) + (g & 1)) * 576 + 192 + 8 * l;
  const __nv_bfloat16* brow = wqkv + (16 * s + 4 * (g >> 1) + (g & 1)) * 576 + 8 * l;
#pragma unroll
  for (int i = 0; i < 12; i++) {
    A[i] = ldg128_nc(arow + (i & 1) * 2 * 576 + 32 * (i >> 1));
    B[i] = ldg128_nc(brow + (i & 1) * 2 * 576 + 32 * (i >> 1));
  }
  sched_fence();
  uint8_t* dst = wimg + wimg_off(m0 + g, 16 * s + 4 * l);
  float acc[4][4];
#pragma unroll
  for (int j = 0; j < 16; j++) acc[j >> 2][j & 3] = 0.f;
#pragma unroll
  for (int i = 0; i < 6; i++) {
    const uint4 &a0 = A[2 * i], &a1 = A[2 * i + 1];
#pragma unroll
    for (int nb = 0; nb < 2; nb++) {
      mma16816(acc[2 * nb], a0.x, a1.x, a0.y, a1.y, B[2 * i + nb].x, B[2 * i + nb].y);
      mma16816(acc[2 * nb + 1], a0.z, a1.z, a0.w, a1.w, B[2 * i + nb].z, B[2 * i + nb].w);
    }
  }
#pragma unroll
  for (int j = 0; j < 2; j++) {
    const uint2 v = make_uint2(pack_bf16((acc[0][2 * j] + acc[1][2 * j]) * kAlpha, (acc[0][2 * j + 1] + acc[1][2 * j + 1]) * kAlpha),
                               pack_bf16((acc[2][2 * j] + acc[3][2 * j]) * kAlpha, (acc[2][2 * j + 1] + acc[3][2 * j + 1]) * kAlpha));
    asm volatile("st.relaxed.gpu.global.v2.u32 [%0], {%1,%2};" ::"l"(dst + j * 1024), "r"(v.x), "r"(v.y) : "memory");
  }
}
__device__ __forceinline__ void fold_w2(const int u, const __nv_bfloat16* __restrict__ wqkv, const __nv_bfloat16* __restrict__ wo,
                                        uint8_t* wimg) {
  const int g = (threadIdx.x >> 2) & 7, l = threadIdx.x & 3;
  const int m0 = (u / 12) * 32, n0 = (u % 12) * 16;
  uint4 S[12];
  uint32_t L[96];
  const __nv_bfloat16* brow = wqkv + (n0 + 4 * (g >> 1) + (g & 1)) * 576 + 384 + 8 * l;
#pragma unroll
  for (int i = 0; i < 12; i++) S[i] = ldg128_nc(brow + (i & 1) * 2 * 576 + 32 * (i >> 1));
  const __nv_bfloat16* acol = wo + (8 * l) * 192 + m0 + 4 * g;
#pragma unroll
  for (int c = 0; c < 48; c++)
    asm volatile("ld.global.nc.v2.u32 {%0,%1}, [%2];" : "=r"(L[2 * c]), "=r"(L[2 * c + 1]) : "l"(acol + (32 * (c >> 3) + (c & 7)) * 192));
  const uint32_t off = w2_offset();
  sched_fence();
  uint8_t* img = wimg + off;
  float acc[4][4];
#pragma unroll
  for (int j = 0; j < 16; j++) acc[j >> 2][j & 3] = 0.f;
#pragma unroll
  for (int i = 0; i < 6; i++) {
#pragma unroll
    for (int h = 0; h < 2; h++) {
      const uint4 &s0 = S[2 * i], &s1 = S[2 * i + 1];
#pragma unroll
      for (int mt = 0; mt < 2; mt++) {
        const uint32_t* a = L + 16 * i + 8 * h + mt;
        const uint32_t a0 = __byte_perm(a[0], a[2], 0x5410), a1 = __byte_perm(a[0], a[2], 0x7632);
        const uint32_t a2 = __byte_perm(a[4], a[6], 0x5410), a3 = __byte_perm(a[4], a[6], 0x7632);
        mma16816(acc[2 * mt], a0, a1, a2, a3, h ? s0.z : s0.x, h ? s0.w : s0.y);
        mma16816(acc[2 * mt + 1], a0, a1, a2, a3, h ? s1.z : s1.x, h ? s1.w : s1.y);
      }
    }
  }
#pragma unroll
  for (int j = 0; j < 4; j++) {
    const float(&c0)[4] = acc[j & 2];
    const float(&c1)[4] = acc[(j & 2) + 1];
    asm volatile("st.relaxed.gpu.global.v2.u32 [%0], {%1,%2};" ::"l"(img + w2img_off(g2_inv(m0 + 4 * g + j), n0 + 4 * l)),
                 "r"(pack_bf16(c0[2 * (j & 1)], c0[2 * (j & 1) + 1])), "r"(pack_bf16(c1[2 * (j & 1)], c1[2 * (j & 1) + 1])) : "memory");
  }
}

__global__ void __launch_bounds__(256) fold_kernel(const __nv_bfloat16* __restrict__ wqkv,
                                                   const __nv_bfloat16* __restrict__ wo, uint8_t* wimg) {
  const int u = blockIdx.x * 8 + (threadIdx.x >> 5);
  if (u < 144) fold_w1(u, wqkv, wimg);
  else fold_w2(u - 144, wqkv, wo, wimg);
}

struct TileCoord { int pr, pc, I, J, up, kind; };
struct TileTable { uint16_t e[kCtas * 6], g[5][8][2], b[5][2][4]; };
inline void make_tiles(TileTable& tt) {
  for (int tile = 0; tile < kCtas * 6; tile++) {
    const int b = tile / 6, k = tile - 6 * b;
    const int p = b < 128 ? (tile - 672) >> 1 : b - 80;
    const int strip = b < 112 ? b >> 1 : b >= 128 && k >= 2 ? (b & 1) * 27 + (b & 2) * 14 : p + (p < 26 ? 1 : 3);
    const int pr = strip >= 28, J = (strip - pr * 28) >> 1, pc = strip & 1, up = b < 112 ? b & 1 : pr;
    const int first = b < 112 ? 8 - 2 * pr - up : 13 * pr, step = b < 112 ? k : k & 1;
    const int I = up ? first - step : first + step;
    const int kind = b < 112 ? (J == 13 * pc ? 1 + pc : 0) : I == 13 * pr ? 3 + pr : 0;
    tt.e[tile] = (uint16_t)(I | J << 4 | pr << 8 | pc << 9 | up << 10 | kind << 11);
  }
  for (int kind = 0; kind < 5; kind++) {
    const bool col = kind == 1 || kind == 2;
    auto off = [kind](int t) { return kind == 0 ? 2 * t : kind & 1 ? t + (t == 7) : t + (t > 0); };
    for (int j = 0; j < 8; j++) {
      const int w = j >> 1, h = j & 1;
      tt.g[kind][j][0] = (uint16_t)(col ? 3 * off(w + 4 * h) : 3 * (kW * off(2 * w) + 8 * h));
      tt.g[kind][j][1] = (uint16_t)(128 * (col ? 5 : 5 + off(2 * w + 1) - off(2 * w)));
    }
    for (int i = 0; i < 2; i++) {
      const int w = kind == 0 ? 0 : kind & 1 ? 3 * i : 1 - i;
      tt.b[kind][i][0] = tt.g[kind][2 * w][0];
      tt.b[kind][i][1] = (uint16_t)(128 * (kind == 0 ? 0 : (col ? 3 : 1) + i));
      tt.b[kind][i][2] = (uint16_t)(2048 * w);
      tt.b[kind][i][3] = 0;
    }
  }
}
__device__ __forceinline__ int num_tiles() { return blockIdx.x < 128 ? 6 : 4; }
__device__ __forceinline__ TileCoord decode_tile(const TileTable& tt, int tile) {
  const uint32_t e = tt.e[tile];
  return TileCoord{(int)(e >> 8) & 1, (int)(e >> 9) & 1, (int)e & 15, (int)(e >> 4) & 15, (int)(e >> 10) & 1, (int)(e >> 11)};
}
__device__ __forceinline__ int halo_r0(const TileCoord& t) { return 8 * t.I + 6 * t.pr - 6; }
__device__ __forceinline__ int halo_c0(const TileCoord& t) { return min(max(8 * t.J + 6 * t.pc - 6, -3), 102); }

__device__ __forceinline__ uint32_t bar_full(uint32_t bars, int wg, int c) { return bars + (wg * 3 + c) * 8; }
__device__ __forceinline__ uint32_t bar_w1c(uint32_t bars, int c) { return bars + (6 + c) * 8; }
__device__ __forceinline__ uint32_t bar_w2(uint32_t bars) { return bars + 9 * 8; }
__device__ __forceinline__ uint32_t bar_x(uint32_t bars, int j, int c) { return bars + (j == 0 ? 10 : c ? 17 + c : 11) * 8; }
__device__ __forceinline__ uint32_t bar_w1q(uint32_t bars) { return bars + 12 * 8; }
__device__ __forceinline__ uint32_t bar_xf(uint32_t bars) { return bars + 13 * 8; }
__device__ __forceinline__ uint32_t bar_w2m(uint32_t bars) { return bars + 14 * 8; }
__device__ __forceinline__ uint32_t bar_redo(uint32_t bars) { return bars + 15 * 8; }
__device__ __forceinline__ uint32_t bar_wok(uint32_t bars) { return bars + 16 * 8; }
__device__ __forceinline__ uint32_t bar_go(uint32_t bars) { return bars + 17 * 8; }
__device__ __forceinline__ uint32_t bar_raw(uint32_t bars, int j = 0) { return bars + (21 + j) * 8; }
__device__ __forceinline__ uint32_t bar_w2a(uint32_t bars) { return bars + 20 * 8; }
constexpr int kNumBars = 22;

__device__ __forceinline__ uint64_t wdesc(uint64_t d0, int s) { return d0 + (((s >> 2) * kWChunk + (s & 3) * 32) >> 4); }

__device__ __forceinline__ uint32_t x_chunk(int k, int c) { return kXOff + (k == 0 ? kWChunk : 0) + (k & 1 ? 2 - c : c) * 8192; }
__device__ __forceinline__ uint32_t out_slot(int k, int nt) { return k + 1 < nt ? kW2Off + (~k & 1) * 2 * kWChunk : kW1Off + kWChunk; }
template <int I0, int I1>
__device__ __forceinline__ void store_rows(bool on, __nv_bfloat16* pA, __nv_bfloat16* pB, const uint32_t (&a)[24], const uint32_t (&b)[24]) {
#pragma unroll
  for (int i = 2 * I0; i < 2 * I1; i++) {
    const uint32_t* v = (i & 1 ? b : a) + 4 * (i >> 1);
    asm volatile("{\n.reg .pred p;\nsetp.ne.u32 p, %5, 0;\n@p st.global.v4.u32 [%0], {%1,%2,%3,%4};\n}\n" ::"l"((i & 1 ? pB : pA) + 32 * (i >> 1)),
                 "r"(v[0]), "r"(v[1]), "r"(v[2]), "r"(v[3]), "r"((uint32_t)on) : "memory");
  }
}
template <int I0, int I1>
__device__ __forceinline__ void stage_out(uint32_t sts, int wg, const uint32_t (&a)[24], const uint32_t (&b)[24]) {
  const uint32_t e = sts, o = sts ^ 64;
  const uint32_t ad[4] = {wg ? o + 1024 : e, wg ? e + 2048 : o, wg ? e : o + 1024, wg ? o : e + 2048};
#pragma unroll
  for (int i = I0; i < I1; i++) {
    const uint32_t* v = (i < 6 ? a : b) + 4 * (i % 6);
    asm volatile("st.shared.v4.u32 [%0], {%1,%2,%3,%4};" ::"r"(ad[i % 6 / 3 * 2 + (i % 3 == 1)] + (i % 3 == 2) * 1024 + (i / 6) * 12288),
                 "r"(v[0]), "r"(v[1]), "r"(v[2]), "r"(v[3]) : "memory");
  }
}
__device__ __forceinline__ uint32_t now_ns() {
  uint32_t t;
  asm volatile("mov.u32 %0, %globaltimer_lo;" : "=r"(t)::"memory");
  return t;
}
__device__ __forceinline__ void wait_clock(uint32_t t_start, uint32_t t) {
  while (now_ns() - t_start < t) { }
}
#define NAT_PRED(f, m) ".reg .pred p;\n.reg .b32 t;\nand.b32 t, " f ", " m ";\nsetp.ne.u32 p, t, 0;\n"
constexpr uint32_t kHiV = 1, kHiU = 8, kColB = 0x20, kInV = 0x100, kInU = 0x1000, kColA = 0x10000;
template <uint32_t M>
__device__ __forceinline__ float pick(const float* a, const float* b, uint32_t f) {
  float d;
  asm("{\n" NAT_PRED("%5", "%6") "add.f32 %0, %1, %2;\n@p add.f32 %0, %3, %4;\n}\n"
      : "=&f"(d) : "f"(a[0]), "f"(a[2]), "f"(b[0]), "f"(b[2]), "r"(f), "n"(M));
  return d;
}
template <uint32_t M>
__device__ __forceinline__ float sel(float a, float b, uint32_t f) {
  float d;
  asm("{\n" NAT_PRED("%3", "%4") "selp.f32 %0, %1, %2, p;\n}\n" : "=f"(d) : "f"(a), "f"(b), "r"(f), "n"(M));
  return d;
}
template <uint32_t M>
__device__ __forceinline__ void max_if(float& m, float v, uint32_t f) {
  asm("{\n" NAT_PRED("%2", "%3") "@p max.f32 %0, %0, %1;\n}\n" : "+f"(m) : "f"(v), "r"(f), "n"(M));
}
template <uint32_t M>
__device__ __forceinline__ void add_if(float& m, float v, uint32_t f) {
  asm("{\n" NAT_PRED("%2", "%3") "@p add.f32 %0, %0, %1;\n}\n" : "+f"(m) : "f"(v), "r"(f), "n"(M));
}
__device__ __forceinline__ void pick_v(const float* a, float* v, uint32_t f) {
  v[0] = pick<kHiV>(a, a + 16, f), v[1] = pick<kHiV>(a + 1, a + 17, f);
  v[2] = pick<kHiV * 2>(a + 4, a + 20, f), v[3] = pick<kHiV * 2>(a + 5, a + 21, f);
  v[4] = pick<kHiV * 4>(a + 8, a + 24, f), v[5] = pick<kHiV * 4>(a + 9, a + 25, f);
  v[6] = a[12] + a[14], v[7] = a[13] + a[15];
}
__device__ __forceinline__ void pick_u(const float* a, float* v, uint32_t f) {
#pragma unroll
  for (int c = 0; c < 3; c++) v[2 * c] = pick<kHiU>(a + 4 * c, a + 4 * c + 12, f), v[2 * c + 1] = pick<kHiU * 2>(a + 4 * c + 1, a + 4 * c + 13, f);
}
__device__ __forceinline__ uint32_t sign_bytes(uint32_t v, uint32_t sel) {
  uint32_t d;
  asm("prmt.b32 %0, %1, %1, %2;" : "=r"(d) : "r"(v), "r"(sel));
  return d;
}
__device__ __forceinline__ float own_max(const float (&v)[14], uint32_t f) {
  float m = sel<kInV>(fmaxf(v[0], v[1]), -INFINITY, f), m2 = sel<kInV * 2>(fmaxf(v[2], v[3]), -INFINITY, f);
  max_if<kInV * 4>(m, fmaxf(v[4], v[5]), f);
  max_if<kInV * 8>(m2, fmaxf(v[6], v[7]), f);
  max_if<kInU>(m, fmaxf(fmaxf(v[8], v[10]), v[12]), f);
  max_if<kInU * 2>(m2, fmaxf(fmaxf(v[9], v[11]), v[13]), f);
  return fmaxf(m, m2);
}
__device__ __forceinline__ float quad_max(float m) {
  const float a = __shfl_xor_sync(0xffffffffu, m, 1), b = __shfl_xor_sync(0xffffffffu, m, 2), c = __shfl_xor_sync(0xffffffffu, m, 3);
  return fmaxf(fmaxf(m, a), fmaxf(b, c));
}
__device__ __forceinline__ float row_rcp(const float (&v)[14], uint32_t f) {
  float s = sel<kInV>(v[0] + v[1], 0.f, f), s2 = sel<kInV * 2>(v[2] + v[3], 0.f, f);
  add_if<kInV * 4>(s, v[4] + v[5], f);
  add_if<kInV * 8>(s2, v[6] + v[7], f);
  add_if<kInU>(s, v[8] + v[10] + v[12], f);
  add_if<kInU * 2>(s2, v[9] + v[11] + v[13], f);
  s += s2;
  const float a = __shfl_xor_sync(0xffffffffu, s, 1), b = __shfl_xor_sync(0xffffffffu, s, 2), c = __shfl_xor_sync(0xffffffffu, s, 3);
  return rcp_approx((s + a) + (b + c));
}
__device__ __forceinline__ void route(const float (&v)[14], float s, const uint32_t (&rt)[9], uint32_t (&p)[14]) {
#pragma unroll
  for (int i = 0; i < 7; i++) {
    const uint32_t u = pack_bf16(v[2 * i] * s, v[2 * i + 1] * s);
    if (i < 4) p[i] = u & rt[i];
    if (i < 3) p[i + 4] = u & rt[i + 4];
    if (i >= 4) {
      p[i + 3] = u & rt[7];
      p[i + 6] = u & rt[8];
    }
  }
}

template <int C, int T0 = 0, int T1 = 7>
__device__ __forceinline__ void pv_chunk(float (&z)[32], const uint32_t (&pa)[14], const uint32_t (&pb)[14],
                                         const uint32_t (&meta)[4], uint64_t dV) {
#pragma unroll
  for (int t = T0; t < T1; t++) {
    if (t & 1)
      wg_s64t1<0, 32>(z, pa[2 * t], pb[2 * t], pa[2 * t + 1], pb[2 * t + 1], dV + ((2 * C * kChunkBytes + t * 2048) >> 4), 1,
                      meta[t >> 1]);
    else if (t > 0)
      wg_s64t<0, 32>(z, pa[2 * t], pb[2 * t], pa[2 * t + 1], pb[2 * t + 1], dV + ((2 * C * kChunkBytes + t * 2048) >> 4), 1,
                     meta[t >> 1]);
    else
      wg_s64tz<0, 32>(z, pa[0], pb[0], pa[1], pb[1], dV + ((2 * C * kChunkBytes) >> 4), 0, meta[0]);
  }
}
template <int C>
__device__ __forceinline__ void pack_z(const float (&z)[32], uint32_t (&za)[24], uint32_t (&zb)[24]) {
#pragma unroll
  for (int j = 0; j < 8; j++) {
    za[8 * C + j] = pack_bf16(z[4 * j], z[4 * j + 1]);
    zb[8 * C + j] = pack_bf16(z[4 * j + 2], z[4 * j + 3]);
  }
}

template <int H>
__device__ __forceinline__ void pack_out(const float (&ac)[48], uint32_t (&oa)[24], uint32_t (&ob)[24]) {
#pragma unroll
  for (int j = 0; j < 12; j++) {
    oa[12 * H + j] = pack_bf16(ac[4 * j], ac[4 * j + 1]);
    ob[12 * H + j] = pack_bf16(ac[4 * j + 2], ac[4 * j + 3]);
  }
}
struct Maps { CUtensorMap v6, v2, v14, u8, px[8], wv, wo; };
__device__ __forceinline__ void tma_prefetch_5d(const CUtensorMap* map, int c0, int c1, int c2, int c3, int c4) {
  asm volatile("cp.async.bulk.prefetch.tensor.5d.L2.global.tile [%0, {%1, %2, %3, %4, %5}];" ::"l"((uint64_t)map), "r"(c0), "r"(c1),
               "r"(c2), "r"(c3), "r"(c4) : "memory");
}
__device__ __forceinline__ int first_line(const TileCoord tc) { return 3 * (qpix(tc.pr, 8 * tc.I) * kW + qpix(tc.pc, 8 * tc.J)); }
__device__ __forceinline__ void load_px(const Maps& tm, const TileTable& tt, uint32_t dst, uint32_t bar, int line, int kind) {
#pragma unroll
  for (int i = 0; i < 2; i++) {
    if (i == 0 || kind != 0) {
      const CUtensorMap* map = (const CUtensorMap*)((const char*)tm.px + tt.b[kind][i][1]);
      if (bar) tma_load_5d(dst + tt.b[kind][i][2], map, bar, 0, 0, 0, 0, line + tt.b[kind][i][0]);
      else tma_prefetch_5d(map, 0, 0, 0, 0, line + tt.b[kind][i][0]);
    }
  }
}
__device__ __forceinline__ void store_px(const Maps& tm, const TileTable& tt, uint32_t buf, int line, int kind) {
#pragma unroll
  for (int i = 0; i < 8; i++) {
    const int j = 2 * (i & 3) + (i >> 2);
    asm volatile("cp.async.bulk.tensor.5d.global.shared::cta.tile.bulk_group [%0, {%2, %2, %2, %2, %3}], [%1];" ::"l"(
                     (uint64_t)tm.px + tt.g[kind][j][1]), "r"(buf + i * 3072), "r"(0), "r"(line + tt.g[kind][j][0]) : "memory");
  }
  asm volatile("cp.async.bulk.commit_group;" ::: "memory");
}
__device__ __noinline__ bool refetch(uint32_t base, const uint8_t* src, bool gap) {
  constexpr uint32_t bars = 1024 + kBarOff, cnt = bars + 192;
#pragma unroll 1
  for (uint32_t o = 0; o < kWBytes && !gap; o += 2048) {
    uint32_t mx = 0;
#pragma unroll
    for (int i = 0; i < 4; i++) {
      uint4 v;
      asm volatile("ld.shared.v4.u32 {%0,%1,%2,%3}, [%4];" : "=r"(v.x), "=r"(v.y), "=r"(v.z), "=r"(v.w)
                   : "r"(base + o + i * 512 + (threadIdx.x & 31) * 16));
      mx = __vimax3_u32(__vimax3_u32(mx, v.x, v.y), v.z, v.w);
    }
    gap = __any_sync(0xffffffffu, mx == kEmpty);
  }
  uint32_t n;
  asm volatile("ld.shared.u32 %0, [%1];" : "=r"(n) : "r"(cnt) : "memory");
  if (!gap || __any_sync(0xffffffffu, n > (1u << 12))) return false;
  asm volatile("bar.sync 15, 128;" ::: "memory");
  if (threadIdx.x == 0) {
    asm volatile("st.shared.u32 [%0], %1;" ::"r"(cnt), "r"(n + 1) : "memory");
    mbar_arrive_expect_tx(bar_redo(bars), kWBytes);
    bulk_load(base, src, kWBytes, bar_redo(bars));
  }
  __syncwarp();
  mbar_wait(bar_redo(bars), n & 1);
  return true;
}
template <int S0, int S1, int Z>
__device__ __forceinline__ void g2_steps(float (&ac)[48], const uint32_t (&za)[24], const uint32_t (&zb)[24], uint64_t d) {
#pragma unroll
  for (int s = S0; s < S1; s++) {
    const uint64_t ds = d + (((s >> 2 & 1) * (kWChunk / 2) + (s & 3) * 32) >> 4);
    if (s == Z) wg_d96z<0, 48>(ac, za[2 * s], zb[2 * s], za[2 * s + 1], zb[2 * s + 1], ds, 0);
    else wg_d96<0, 48>(ac, za[2 * s], zb[2 * s], za[2 * s + 1], zb[2 * s + 1], ds, 1);
  }
}

__device__ __forceinline__ void consumer(const int wg, __nv_bfloat16* out, const uint8_t* wimg, const uint32_t sbase,
                                         const uint32_t zero, const Maps& tm, const TileTable& tt) {
  const int tid = threadIdx.x & 127;
  const int w = __shfl_sync(0xffffffffu, tid >> 5, 0), lane = tid & 31;
  const uint64_t dK = make_desc(sbase, 16, 1024);
  const uint64_t dV = make_desc(sbase, kChunkBytes, 512, 2);
  const uint64_t dW1 = make_desc(sbase + kW1Off, 16, 1024);
  const uint64_t dX0 = make_desc(sbase + kW2Off + wg * 2 * kWChunk, 16, 1024), dY0 = make_desc(sbase + kW2Off + (1 - wg) * 2 * kWChunk, 16, 1024);
  const uint64_t dX2 = make_desc(sbase + kXOff + wg * (kWChunk / 2), 16, 1024), dY2 = make_desc(sbase + kXOff + (1 - wg) * (kWChunk / 2), 16, 1024);
  const uint32_t bars = sbase + kBarOff;
  int tile0 = blockIdx.x * kTilesPerCta;
  asm volatile("" : "+r"(tile0));
  const int nt = num_tiles();

  uint32_t pix = 0, geo[6] = {};
  const int l = lane & 3;
#pragma unroll 1
  for (int j = 4; j >= 0; j -= 2) {
    const TileCoord tc = decode_tile(tt, tile0 + wg + j);
    const bool col = tc.kind == 1 || tc.kind == 2;
    const int g = col ? lane >> 2 : 2 * w + ((lane >> 2) & 1), qc = col ? w : lane >> 3;
    const uint32_t pr = qpix(tc.pr, 8 * tc.I + g) * kW;
    if (j == nt - 2) pix = (pr + qpix(tc.pc, 8 * tc.J + qc)) | (pr + qpix(tc.pc, 8 * tc.J + qc + 4)) << 16;
    const int d = 8 * tc.J + 6 * tc.pc - 6 - halo_c0(tc);
    const int ro = woff(tc.pr, tc.I, g), coA = woff(tc.pc, tc.J, qc) + d, coB = woff(tc.pc, tc.J, qc + 4) + d - 3;
#pragma unroll
    for (int i = 5; i >= 2; i--) geo[i] = geo[i - 2];
    const uint32_t lr = 0x1FCu << ro;
    const uint32_t lv = lr >> (2 + (l >> 1)), lu = lr >> (2 * l + 2 * tc.up);
    const uint32_t t = __byte_perm(lv, lu, wg ? 0x4501 : 0x5410);
    geo[0] = (((t & 0x15u) | (lv & 0x40u)) * 0x02082080u & 0x80808080u) | (((t >> 8) & 0x15u) * 0x01041040u & 0x40404040u) |
             (__byte_perm(t << 5, t << 4, 0x7362) & 0x20202020u) | (nt == 6);
    const int dr = (ro - 1) & 7;
    const uint32_t hiv = (((1u << ((ro - (l >> 1) + 1) >> 1)) - 1u) ^ (wg ? 7u : 0u)) & 7u, hiu = (t >> 24) & 3u;
    const uint32_t ca = (1u << coA) - 1u;
    geo[1] = hiv * kHiV | hiu * kHiU | ((((1u << coB) - 1u) >> (2 * (l & 1))) & 3u) * kColB |
             (15u & ~((uint32_t)((dr & 1) == (l >> 1)) << (dr >> 1))) * kInV | ((t >> 16 | t >> 24) & 3u) * kInU | ca * kColA |
             (ca >> ((0x49 >> (2 * l)) & 3) & 1u) << 19 | (uint32_t)(l == 3) << 20 | (0x55u & ((1u << (2 * coB)) - 1u)) << 24;
  }
  keep_regs(geo);
  const int so = (lane >> 3) | (lane & 4);
  uint32_t sts = sbase + w * 3072 + so * 128 + (((lane & 3) ^ so) << 4);
  __nv_bfloat16* poA = out + 8 * l + (pix & 0xFFFFu) * kC + 96 * wg;
  __nv_bfloat16* poB = out + 8 * l + (pix >> 16) * kC + 96 * wg;
  asm volatile("" : "+l"(poA), "+l"(poB), "+r"(sts));
  uint32_t oa[24], ob[24];
#pragma unroll
  for (int j = 0; j < 24; j++) oa[j] = ob[j] = 0u;
  keep_regs(oa);
  keep_regs(ob);
  PROF(wg, 0);
  if (threadIdx.x == 0) GT(1);

  for (int k = wg; k < nt; k += 2) {
    const uint32_t ph = (k >> 1) & 1;
    const int it = k >> 1;
    uint32_t qa[24], qb[24], hok[3];
    uint32_t fl = geo[1];
    {
      float acc[96];
      const uint32_t xp = (k + (k > 0)) & 1;
      uint32_t xok[3];
      if (k > 0) nb_sync(1 + (1 - wg));
#pragma unroll
      for (int c = 0; c < 3; c++) xok[c] = mbar_test(bar_x(bars, k > 0, c), xp);
#pragma unroll
      for (int s = 0; s < 12; s++) {
        if ((s & 3) == 0) mbar_wait_if(xok[s >> 2], bar_x(bars, k > 0, s >> 2), xp);
        if (s == 0 && k < 2) PROF(wg, 1);
        if (s == 0) PROFS(2, wg, 2 + it * 12);
        if (s == 0 && w == 0 && k < 2) GT(20 + wg);
        if ((s & 3) == 0 && k == 0) {
          mbar_wait(bar_w1c(bars, s >> 2), 0);
          PROFS(17, wg, 50 + (s >> 2));
        }
        if ((s & 3) == 0) wg_fence();
        const uint64_t dX = make_desc(sbase + x_chunk(k, s >> 2), 16, 1024) + 2 * (s & 3);
        if (s == 0) wg_m192z<0, 96>(acc, dX, dW1, 0);
        else wg_m192<0, 96>(acc, dX, wdesc(dW1, s), 1);
        if ((s & 3) == 3) wg_commit();
      }
      PROFS(13, wg, 13 + it * 12);
      if (NAT_MP > 2) {
        wg_wait<2>();
        if (k > 0) nb_arrive_p(0);
      }
      if (NAT_MP > 1) {
        wg_wait<1>();
        if (k > 0) nb_arrive_p(14);
      }
      wg_wait<0>();
      if (k > 0) nb_arrive_p(6);
      fence_regs(acc);
      PROFS(3, wg, 3 + it * 12);
#pragma unroll
      for (int j = 0; j < 24; j++) {
        qa[j] = pack_bf16(acc[4 * j], acc[4 * j + 1]);
        qb[j] = pack_bf16(acc[4 * j + 2], acc[4 * j + 3]);
      }
      keep_regs(qa);
      keep_regs(qb);
      sched_fence();
      if (k >= 2) {
        const uint32_t dst = sts + out_slot(k, nt);
        nb_sync(11);
        stage_out<0, 6>(dst, wg, oa, ob);
        nb_sync(12);
        stage_out<6, 12>(dst, wg, oa, ob);
      }
#pragma unroll
      for (int c = 0; c < 3; c++) hok[c] = mbar_test(bar_full(bars, wg, c), ph);
      if (k >= 2) {
        fence_proxy_async();
        nb_arrive_p(10);
      }
    }

    float aE[52], aO[24], bO[52], bE[28];
    const uint32_t mq = 0xEEEE4444u | zero;
    PROFS(4, wg, 4 + it * 12);

    mbar_wait_if(hok[0], bar_full(bars, wg, 0), ph);
    PROFS(14, wg, 40 + it * 3);
    if (w == 0 && k < 2) GT(22 + wg);
    if (k > 0) nb_sync(3 + (1 - wg));
    wg_fence();
#pragma unroll
    for (int ks = 0; ks < 6; ks++) {
      if (ks == NAT_P1) {
        mbar_wait_if(hok[1], bar_full(bars, wg, 1), ph);
        PROFS(14, wg, 41 + it * 3);
        wg_fence();
      }
      if (ks == NAT_P2) {
        mbar_wait_if(hok[2], bar_full(bars, wg, 2), ph);
        PROFS(14, wg, 42 + it * 3);
        wg_fence();
      }
      const uint64_t d = dK + ((ks * kChunkBytes) >> 4);
      if (ks == 0) wg_s104z<0, 52>(aE, qa[0], qa[1], qa[2], qa[3], d, 0, mq);
      else wg_s104<0, 52>(aE, qa[4 * ks], qa[4 * ks + 1], qa[4 * ks + 2], qa[4 * ks + 3], d, 1, mq);
    }
    wg_commit();
    wg_s48z<0, 24>(aO, qa[0], qa[1], qa[2], qa[3], dK + ((7 * 1024 + 64) >> 4), 0, mq);
#pragma unroll
    for (int ks = 1; ks < 6; ks++)
      wg_s48<0, 24>(aO, qa[4 * ks], qa[4 * ks + 1], qa[4 * ks + 2], qa[4 * ks + 3], dK + ((ks * kChunkBytes + 7 * 1024 + 64) >> 4), 1, mq);
    wg_commit();
    wg_s56z<0, 28>(bE, qb[0], qb[1], qb[2], qb[3], dK, 0, mq);
#pragma unroll
    for (int ks = 1; ks < 6; ks++) wg_s56<0, 28>(bE, qb[4 * ks], qb[4 * ks + 1], qb[4 * ks + 2], qb[4 * ks + 3], dK + ((ks * kChunkBytes) >> 4), 1, mq);
    wg_commit();
    wg_wait<2>();
    fence_regs(aE);
    PROFS(5, wg, 5 + it * 12);

    uint32_t pa[14], pb[14], meta[4];
    {
      float vA[14], vB[14];
      pick_v(aE, vA, fl);
      pick_u(aE + 28, vA + 8, fl);
      fence_regs(vA);
      if (k == 0) {
        if (__builtin_expect(__any_sync(0xffffffffu, vA[6] != vA[6]), 0)) {
          wg_wait<0>();
          fence_regs(aO);
          fence_regs(bE);
          if (refetch(sbase + kW1Off, wimg, false)) {
#pragma unroll
            for (int j = 0; j < 24; j++) oa[j] = ob[j] = 0u;
            k -= 2;
            continue;
          }
        }
        if (elect_one()) mbar_arrive(bar_xf(bars));
      }
      wg_fence();
      wg_s104z<0, 52>(bO, qb[0], qb[1], qb[2], qb[3], dK + 4, 0, mq);
#pragma unroll
      for (int ks = 1; ks < 6; ks++)
        wg_s104<0, 52>(bO, qb[4 * ks], qb[4 * ks + 1], qb[4 * ks + 2], qb[4 * ks + 3], dK + ((ks * kChunkBytes + 64) >> 4), 1, mq);
      wg_commit();
      if (k + 1 < nt) nb_arrive(1 + wg);
      uint32_t rt[9];
#pragma unroll
      for (int i = 0; i < 7; i++) rt[i] = sign_bytes(geo[0] << (i >> 2), 0x8888u + 0x1111u * (i & 3));
      rt[7] = sign_bytes(geo[0] << 2, 0x9988u);
      rt[8] = sign_bytes(geo[0] << 2, 0xBBAAu);
      keep_regs(rt);
      pa[13] = pb[13] = 0u;
      wg_wait<2>();
      keep_regs(qa);
      fence_regs(aO);
      float oA[6], eB[8];
      pick_u(aO, oA, fl);
      wg_wait<1>();
      fence_regs(bE);
      pick_v(bE, eB, fl);
      vA[8] = sel<kColA>(oA[0], vA[8], fl), vA[9] = sel<kColA>(oA[1], vA[9], fl);
      vA[10] = sel<kColA * 2>(oA[2], vA[10], fl), vA[11] = sel<kColA * 2>(oA[3], vA[11], fl);
      vA[12] = sel<kColA * 4>(oA[4], vA[12], fl), vA[13] = sel<kColA * 4>(oA[5], vA[13], fl);
      {
        const float m1 = __uint_as_float(0x88DD88DDu), m0 = __uint_as_float(0x88DDDD88u);
        meta[0] = 0xDD88DD88u ^ __byte_perm(fl, 0u, 0x3344);
        meta[1] = __float_as_uint(sel<kColA * 16>(sel<kColA>(m1, m0, fl), __uint_as_float(meta[0]), fl));
        meta[2] = __float_as_uint(sel<kColA * 8>(m1, m0, fl));
        meta[3] = __float_as_uint(sel<kColA * 4>(m1, m0, fl));
        keep_regs(meta);
      }
      float mA = own_max(vA, fl);
      fl |= __float_as_uint(eB[7]) & zero;
      fence_regs(eB);
      fence_regs(vA);
      asm volatile("" : "+f"(mA), "+r"(fl));
      sched_fence();
      wg_wait<0>();
      sched_fence();
      keep_regs(qb);
      fence_regs(bO);
      PROFS(6, wg, 6 + it * 12);
      if (w == 0) GT(24 + k);
      mA = quad_max(mA);
#pragma unroll
      for (int i = 0; i < 14; i++) vA[i] = ex2(vA[i] - mA);
      pick_v(bO, vB, fl);
      pick_u(bO + 28, vB + 8, fl);
#pragma unroll
      for (int i = 0; i < 8; i += 2) vB[i] = sel<kColB>(vB[i], eB[i], fl), vB[i + 1] = sel<kColB * 2>(vB[i + 1], eB[i + 1], fl);
      float mB = quad_max(own_max(vB, fl));
      if (NAT_SB) {
        fence_regs(vA);
        fence_regs(vB);
        asm volatile("" : "+f"(mB));
        sched_fence();
      }
      PROFS(7, wg, 7 + it * 12);
#pragma unroll
      for (int i = 0; i < 14; i++) vB[i] = ex2(vB[i] - mB);
      route(vA, row_rcp(vA, fl), rt, pa);
      route(vB, row_rcp(vB, fl), rt, pb);
    }
    PROFS(8, wg, 8 + it * 12);
    if (k == NAT_PK) PROFS(18, wg, 53);
    sched_fence();

    float ac0[48], ac1[48];
    {
      float z0[32], z1[32], z2[32];
      uint32_t za[24], zb[24];
      wg_fence();
      pv_chunk<0>(z0, pa, pb, meta, dV);
      wg_commit();
      pv_chunk<1>(z1, pa, pb, meta, dV);
      wg_commit();
      wg_wait<1>();
      if (k == NAT_PK) PROFS(18, wg, 54);
      if (k + 1 < nt) nb_arrive_p(7);
      pv_chunk<2, 0, 3>(z2, pa, pb, meta, dV);
      wg_commit();
      sched_fence();
      fence_regs(z0);
      pack_z<0>(z0, za, zb);
      sched_fence();
      wg_fence();
      pv_chunk<2, 3, 7>(z2, pa, pb, meta, dV);
      wg_commit();
      wg_wait<2>();
      if (k == NAT_PK) PROFS(19, wg, 55);
      if (k + 1 < nt) nb_arrive_p(8);
      if (k < 2) mbar_wait(k == 1 ? bar_wok(bars) : bar_w2a(bars), 0);
      wg_fence();
      g2_steps<0, 3, 0>(ac0, za, zb, dX0);
      wg_commit();
      sched_fence();
      fence_regs(z1);
      pack_z<1>(z1, za, zb);
      sched_fence();
      wg_fence();
      g2_steps<3, 4, 0>(ac0, za, zb, dX0);
      wg_commit();
      g2_steps<4, 8, 0>(ac0, za, zb, dX0);
      wg_commit();
      wg_wait<3>();
      if (k + 1 < nt) nb_arrive_p(9);
      else nb_arrive(11);
      if (k == NAT_PK) PROFS(20, wg, 56);
      keep_regs(pa);
      keep_regs(pb);
      keep_regs(meta);
      sched_fence();
      const uint32_t mok = mbar_test(bar_w2m(bars), k + 1 < nt ? k & 1 : ~k & 1);
      fence_regs(z2);
      pack_z<2>(z2, za, zb);
      keep_regs(za);
      keep_regs(zb);
      sched_fence();
      PROFS(9, wg, 9 + it * 12);
      wg_wait<1>();
      if (k > 0 && k + 1 < nt) nb_arrive(11);
      mbar_wait_if(mok, bar_w2m(bars), k & 1);
      wg_fence();
      g2_steps<8, 12, 0>(ac0, za, zb, dX2);
      wg_commit();
      g2_steps<8, 12, 8>(ac1, za, zb, dY2);
      wg_commit();
      wg_wait<2>();
      if (k > 0 && k + 1 < nt) nb_arrive(12);
      if (k != 1 && k + 1 < nt) mbar_wait(bar_w2(bars), k > 1 ? (k - 1) & 1 : 0);
      wg_fence();
      g2_steps<0, 4, 8>(ac1, za, zb, dY0);
      wg_commit();
      wg_wait<2>();
      if (k + 2 < nt) nb_arrive_p(13);
      const bool direct = k + 2 >= nt;
      sched_fence();
      fence_regs(ac0);
      pack_out<0>(ac0, oa, ob);
      store_rows<0, NAT_D0>(direct, poA, poB, oa, ob);
      sched_fence();
      wg_fence();
      g2_steps<4, 8, 8>(ac1, za, zb, dY0);
      wg_commit();
      if (k + 1 < nt) nb_arrive(3 + wg);
      PROFS(10, wg, 10 + it * 12);
      wg_wait<2>();
      if (k + 2 < nt && (k > 0 || nt == 6)) nb_arrive_p(5);
      store_rows<NAT_D0, 3>(direct, poA, poB, oa, ob);
      __nv_bfloat16 *qA = poA - 192 * wg, *qB = poB - 192 * wg;
      if (k + 2 == nt) nb_sync(11);
      sched_fence();
      wg_wait<0>();
      fence_regs(ac1);
      pack_out<1>(ac1, oa, ob);
      asm volatile("" : "+l"(qA), "+l"(qB));
      store_rows<3, 6>(direct, qA, qB, oa, ob);
      if (k == 0) {
        uint32_t m[2] = {oa[0], oa[1]};
#pragma unroll
        for (int i = 2; i < 24; i++) asm("max.NaN.bf16x2 %0, %0, %1;" : "+r"(m[i & 1]) : "r"(oa[i]));
        asm("max.NaN.bf16x2 %0, %0, %1;" : "+r"(m[0]) : "r"(m[1]));
        uint32_t nan;
        asm volatile("{\n.reg .pred p;\nsetp.ne.u32 p, %1, 0;\nbar.red.or.pred p, 15, 128, p;\nselp.u32 %0, 1, 0, p;\n}\n"
                     : "=r"(nan) : "r"(((m[0] & 0x7FFF7FFFu) + 0x007F007Fu) & 0x80008000u) : "memory");
        if (__builtin_expect(__any_sync(0xffffffffu, nan), 0)) {
          for (int c = 0; c < 3 && __any_sync(0xffffffffu, geo[2] & 1u); c++) mbar_wait(bar_x(bars, 1, c), 1);
          for (bool first = true; __any_sync(0xffffffffu, refetch(sbase + kW2Off, wimg + w2_offset(), first)); first = false) { }
          wg_fence();
          g2_steps<0, 8, 0>(ac0, za, zb, dX0);
          g2_steps<8, 12, 0>(ac0, za, zb, dX2);
          g2_steps<0, 8, 0>(ac1, za, zb, dY0);
          g2_steps<8, 12, 0>(ac1, za, zb, dY2);
          wg_commit();
          wg_wait<0>();
          fence_regs(ac0);
          fence_regs(ac1);
          pack_out<0>(ac0, oa, ob);
          pack_out<1>(ac1, oa, ob);
          if (__any_sync(0xffffffffu, geo[2] & 1u)) {
            asm volatile("bar.sync 15, 128;" ::: "memory");
            if (w == 0 && elect_one()) {
              const TileCoord tc = decode_tile(tt, tile0 + 2);
              mbar_arrive_expect_tx(bar_raw(bars), kWChunk);
#pragma unroll 1
              for (int c = 0; c < 3; c++) load_px(tm, tt, sbase + x_chunk(2, c), bar_raw(bars), first_line(tc) + c, tc.kind);
            }
            __syncwarp();
            mbar_wait(bar_raw(bars), 0);
          }
        }
        if (nt < 6) nb_arrive_p(5);
        if (elect_one()) mbar_arrive(bar_wok(bars));
      }
      keep_regs(za);
      keep_regs(zb);
#pragma unroll
      for (int i = 0; i < 4; i++) geo[i] = geo[i + 2];
      keep_regs(oa);
      keep_regs(ob);
      PROFS(12, wg, 12 + it * 12);
      sched_fence();
    }
  }
  PROF(wg, 38);
  GT_DUMP();
  PROF_DUMP(wg);
}

struct HaloCols { int vj, vc, uj, uc; };
__device__ __forceinline__ HaloCols halo_cols(const TileCoord& tc) {
  const int c0 = halo_c0(tc);
  return HaloCols{c0 > 98, c0 > 98 ? 98 : c0 + 3, c0 < 0 ? -1 : 0, c0 < 0 ? 4 : c0};
}
__device__ __forceinline__ void first_halo(const Maps& tm, uint32_t sbase, const TileCoord tc, int i) {
  const HaloCols hc = halo_cols(tc);
  const uint32_t dst = sbase + i * kChunkBytes, bar = bar_full(sbase + kBarOff, 0, i >> 1);
  const int h0 = halo_r0(tc), ch = 24 * tc.pc + 4 * i;
  tma_load_5d(dst, &tm.v14, bar, ch, hc.vj, hc.vc, tc.pr, h0);
  tma_load_5d(dst + 7 * 1024, &tm.u8, bar, ch, hc.uj, h0 + (tc.up ? 0 : -2), tc.pr, hc.uc);
  tma_load_5d(dst + 10 * 1024, &tm.u8, bar, ch, hc.uj, h0 + (tc.up ? 8 : 6), tc.pr, hc.uc);
}
__device__ __forceinline__ void load_halo(const Maps& tm, uint32_t sbase, uint32_t bars, const TileCoord tc, int k, int c) {
  const HaloCols hc = halo_cols(tc);
  const int h6 = halo_r0(tc) + (tc.up ? 0 : 8), h2 = halo_r0(tc) + 6, h8 = halo_r0(tc) + (tc.up ? 0 : 6), ch = 24 * tc.pc + 8 * c;
  uint32_t dv = sbase + 2 * c * kChunkBytes, du = dv + 7 * 1024;
  if (((k ^ tc.up) & 1) == 0) dv += 4 * 1024, du += 3 * 1024;
  const uint32_t bar = bar_full(bars, k & 1, c);
  mbar_arrive_expect_tx(bar, 14 * 1024);
  nb_sync_p(7 + c);
#pragma unroll
  for (int h = 0; h < 2; h++) {
    tma_load_5d(dv + h * kChunkBytes, &tm.v6, bar, ch + 4 * h, hc.vj, hc.vc, tc.pr, h6);
    tma_load_5d(du + h * kChunkBytes, &tm.u8, bar, ch + 4 * h, hc.uj, h8, tc.pr, hc.uc);
    tma_load_5d(sbase + (2 * c + h) * kChunkBytes + 3 * 1024, &tm.v2, bar, ch + 4 * h, hc.vj, hc.vc, tc.pr, h2);
  }
  PROFS(15, 2, k * 4 + c);
}
__device__ __forceinline__ void gather_px(const __nv_bfloat16* __restrict__ x, uint32_t sbase, int k, const TileCoord tc) {
  const int lane = threadIdx.x & 31, g = lane >> 3;
  uint32_t ro[4], co[4];
#pragma unroll
  for (int i = 0; i < 4; i++) {
    ro[i] = qpix(tc.pr, 8 * tc.I + 2 * i + (g & 1)) * (kW * kC * 2) + 16 * (lane & 7);
    co[i] = qpix(tc.pc, 8 * tc.J + 2 * i + (g >> 1)) * (kC * 2);
  }
  const uint32_t dst = sbase + kXOff + g * 128 + (((lane & 7) ^ g) << 4);
  const int dq = k & 1 ? -128 : 128;
  keep_regs(ro);
  keep_regs(co);
  sched_fence();
  nb_sync_p(13);
  nb_sync_p(5);
#pragma unroll
  for (int i = 0; i < 16; i++) {
    const char* src = (const char*)x + (ro[i >> 2] + co[i & 3] + 128);
#pragma unroll
    for (int q = 0; q < 3; q++)
      asm volatile("cp.async.cg.shared.global [%0], [%1], 16;" ::"r"((dst ^ ((i & 1) * 576)) + (i >> 1) * 1024 + q * 8192), "l"(src + (q - 1) * dq) : "memory");
  }
  asm volatile("cp.async.wait_all;" ::: "memory");
  fence_proxy_async();
  __syncwarp();
  if (lane < 3) mbar_arrive(bar_x(sbase + kBarOff, 1, lane));
  __syncwarp();
}

__global__ void __launch_bounds__(384, 1)
nat_kernel(const __nv_bfloat16* __restrict__ x, __nv_bfloat16* out, const __nv_bfloat16* __restrict__ wqkv,
           const __nv_bfloat16* __restrict__ wo, uint8_t* wimg, const uint32_t zero,
           const __grid_constant__ Maps tm, const __grid_constant__ TileTable tt) {
  extern __shared__ uint8_t smem_raw[];
  constexpr uint32_t sbase = 1024;
  constexpr uint32_t bars = sbase + kBarOff;
  if (smem_u32(smem_raw) != sbase) __trap();
  const int tid = threadIdx.x;
  const uint32_t t_start = now_ns();
  if (tid == 0) GT(0);
  const int wid = __shfl_sync(0xffffffffu, tid >> 5, 0);
  const bool w2cta = blockIdx.x - 128 < 3 && wqkv != nullptr;
  if (wid >= 8) {
    asm volatile("setmaxnreg.dec.sync.aligned.u32 24;");
    const int c = wid & 3, lane = tid & 31;
    const int tile0 = blockIdx.x * kTilesPerCta, nt = num_tiles();
    uint32_t w2o = 0;
    if (c == 3) {
      asm volatile("bar.sync 13, 128;" ::: "memory");
      if (elect_one()) wait_clock(t_start, NAT_TM);
      __syncwarp();
      asm volatile("prefetch.tensormap [%0];" ::"l"((uint64_t)tm.px) : "memory");
      asm volatile("prefetch.tensormap [%0];" ::"l"((uint64_t)&tm.v6) : "memory");
      asm volatile("prefetch.tensormap [%0];" ::"l"((uint64_t)&tm.v2) : "memory");
      asm volatile("prefetch.tensormap [%0];" ::"l"((uint64_t)(tm.px + (blockIdx.x < 112 ? 5 : 6))) : "memory");
      asm volatile("prefetch.tensormap [%0];" ::"l"((uint64_t)(tm.px + 7)) : "memory");
      __nanosleep(NAT_TW2 - 2800);
      w2o = w2_offset();
      if (elect_one()) {
        mbar_arrive_expect_tx(bar_w2a(bars), kWChunk);
        mbar_arrive_expect_tx(bar_w2(bars), kWChunk);
        wait_clock(t_start, NAT_TW2);
        bulk_load(sbase + kW2Off, wimg + w2o, kWChunk, bar_w2a(bars));
        mbar_wait(bar_xf(bars), 0);
        bulk_load(sbase + kW2Off + 2 * kWChunk, wimg + (w2o + 2 * kWChunk), kWChunk, bar_w2(bars));
      }
      __syncwarp();
      if (nt < 6) {
#pragma unroll 1
        for (int k = 2; k < 4; k++) {
          gather_px(x, sbase, k, decode_tile(tt, tile0 + k));
        }
      }
      if (wqkv == nullptr) return;
      mbar_wait(bar_wok(bars), 0);
      if (lane == 0) asm volatile("red.relaxed.gpu.global.add.u32 [%0], 1;" ::"l"(g_flag) : "memory");
      if (blockIdx.x >= 48) return;
      if (lane == 0) {
        uint32_t v, it = 0;
        do {
          __nanosleep(2000);
          asm volatile("ld.relaxed.gpu.global.u32 %0, [%1];" : "=r"(v) : "l"(g_flag) : "memory");
        } while (v < gridDim.x && ++it < (1u << 16));
      }
      __syncwarp();
#pragma unroll
      for (int i = 0; i < 6; i++)
        stg128(wimg + ((i < 3 ? 0u : 3 * kWBytes - w2o) + blockIdx.x * 1536 + (i % 3) * 512 + lane * 16), kEmpty, kEmpty, kEmpty, kEmpty);
      if (lane == 0 && atomicAdd(g_flag + 32, 1u) == 47) {
        g_flag[0] = g_flag[32] = 0;
        g_flag[64] = w2o == kWBytes;
      }
      return;
    }
    if (!elect_one()) return;
    if (c == 0) {
      for (int i = 0; i < kNumBars; i++)
        if ((i != 0 && i != 10 || nt < 6) && (i != 21 || !w2cta)) mbar_init(bars + i * 8, i == 13 || i == 16 ? 4 : 1);
      asm volatile("st.shared.v2.u32 [%0], {%1,%1};" ::"r"(bars + 192), "r"(0) : "memory");
      asm volatile("fence.mbarrier_init.release.cluster;" ::: "memory");
      if (w2cta) asm volatile("bar.sync 10, 64;" ::: "memory");
      asm volatile("bar.arrive 0, 160;" ::: "memory");
      asm volatile("bar.arrive 14, 160;" ::: "memory");
      asm volatile("bar.arrive 13, 128;" ::: "memory");
      const TileCoord tc0 = decode_tile(tt, tile0);
      const HaloCols hc = halo_cols(tc0);
      const int h0 = halo_r0(tc0);
#pragma unroll
      for (int j = 0; j < 3; j++)
        if (j > 0 || nt < 6) mbar_arrive_expect_tx(bar_full(bars, 0, j), 2 * kChunkBytes);
      wait_clock(t_start, NAT_HP);
#pragma unroll
      for (int q = 8; q < 24; q += 8) {
        tma_prefetch_5d(&tm.v6, 24 * tc0.pc + q, hc.vj, hc.vc, tc0.pr, h0 + (tc0.up ? 0 : 8));
        tma_prefetch_5d(&tm.u8, 24 * tc0.pc + q, hc.uj, h0 + (tc0.up ? 0 : 6), tc0.pr, hc.uc);
        if (blockIdx.x >= 112) tma_prefetch_5d(&tm.v2, 24 * tc0.pc + q, hc.vj, hc.vc, tc0.pr, h0 + 6);
      }
#pragma unroll 1
      for (int i = nt < 6 ? 0 : 2; i < 7; i++) {
        if (i == NAT_H0) mbar_wait(bar_w1q(bars), 0);
        if (i == NAT_X1P) mbar_arrive(bar_go(bars));
        if (i < 6) first_halo(tm, sbase, tc0, i);
      }
      w2o = w2_offset();
    } else {
      asm volatile("bar.sync 13, 128;" ::: "memory");
      if (c == 2) {
        if (wqkv != nullptr && nt == 6) asm volatile("bar.sync 12, 64;" ::: "memory");
        const uint32_t c0 = clock();
        while ((uint32_t)clock() - c0 < NAT_TD) { }
        wait_clock(t_start, NAT_T0);
#pragma unroll
        for (int j = 0; j < 3; j++) {
          mbar_arrive_expect_tx(bar_w1c(bars, j), kWChunk);
          bulk_load(sbase + kW1Off + j * kWChunk, wimg + j * kWChunk, kWChunk, bar_w1c(bars, j));
        }
        mbar_arrive(bar_w1q(bars));
        GT(2);
      } else {
#pragma unroll 1
        for (int j = nt == 6; j < 2; j++) {
          const TileCoord tc = decode_tile(tt, tile0 + j);
          const int line = first_line(tc);
          if (j == 1) mbar_wait(bar_go(bars), 0);
#pragma unroll 1
          for (int q = 0; q < 3; q++) {
            load_px(tm, tt, sbase + x_chunk(j, q), bar_x(bars, j, q), line + q, tc.kind);
            if (j == 1 || q == 0) mbar_arrive_expect_tx(bar_x(bars, j, q), j ? 8192 : kWChunk);
          }
        }
        w2o = w2_offset();
        wait_clock(t_start, NAT_TW2);
      }
    }
#pragma unroll 1
    for (int k = 1; k < nt; k++) {
      const TileCoord tn = decode_tile(tt, tile0 + k + 1);
      const int line = first_line(tn);
      if (c == 1) {
#pragma unroll
        for (int q = 3 - NAT_MP; q < 3; q++) {
          const uint32_t n = q == 3 - NAT_MP ? q + 1 : 1, o = x_chunk(k, k & 1 ? q : q + 1 - n);
          nb_sync_p(q == 0 ? 0 : q == 1 ? 14 : 6);
          bulk_load(sbase + o, wimg + (w2o + o - kW2Off), n * 8192, bar_w2m(bars));
        }
        mbar_arrive_expect_tx(bar_w2m(bars), kWChunk);
      }
      if (c == 2) {
        if (k == 1) wait_clock(t_start, NAT_TX2);
        else __nanosleep(NAT_PFD);
#pragma unroll 1
        for (int q = 0; q < 3 && k < 5 && nt == 6; q++) load_px(tm, tt, 0, 0, line + q, tn.kind);
      }
      if (c == 2 && (blockIdx.x >= 112 || k == 5)) {
        const TileCoord tc = decode_tile(tt, tile0 + k);
        const HaloCols hc = halo_cols(tc);
        const int h8 = halo_r0(tc) + (tc.up ? 0 : 6);
#pragma unroll 1
        for (int q = 0; q < 24; q += 8) {
          tma_prefetch_5d(&tm.v6, 24 * tc.pc + q, hc.vj, hc.vc, tc.pr, h8);
          tma_prefetch_5d(&tm.v2, 24 * tc.pc + q, hc.vj, hc.vc, tc.pr, h8 + 6);
          tma_prefetch_5d(&tm.u8, 24 * tc.pc + q, hc.uj, h8, tc.pr, hc.uc);
        }
      }
      load_halo(tm, sbase, bars, decode_tile(tt, tile0 + k), k, c);
      if (c == 0 && k < 5 && nt == 6) {
#pragma unroll
        for (int q = 0; q < 3; q++) {
          if (q < 2) nb_sync_p(q ? 5 : 13);
          load_px(tm, tt, sbase + x_chunk(k + 1, q), bar_x(bars, 1, q), line + q, tn.kind);
          if (q != 1) mbar_arrive_expect_tx(bar_x(bars, 1, q), 8192);
        }
        mbar_arrive_expect_tx(bar_x(bars, 1, 1), 8192);
        PROFS(16, 2, k * 4 + 3);
      }
      if (c == 0 && k >= 2) {
        const TileCoord tp = decode_tile(tt, tile0 + k - 2);
        const int lp = first_line(tp);
        nb_sync_p(10);
        if (NAT_XW == 1 && k < 5 && nt == 6) mbar_wait(bar_x(bars, 1, 2), k & 1);
        if (NAT_XW > 1) __nanosleep(NAT_XW);
        store_px(tm, tt, sbase + out_slot(k, nt), lp, tp.kind);
        if (k + 1 < nt) {
          asm volatile("cp.async.bulk.wait_group.read 0;" ::: "memory");
          bulk_load(sbase + out_slot(k, nt), wimg + (w2o + out_slot(k, nt) - kW2Off), kWChunk, bar_w2(bars));
          mbar_arrive_expect_tx(bar_w2(bars), kWChunk);
        }
      }
    }
    asm volatile("cp.async.bulk.wait_group 0;" ::: "memory");
  } else {
    if (blockIdx.x < 128) {
      if ((wid == 4 || (wid == 5 && blockIdx.x - 2 < 16)) && wqkv != nullptr) {
        fold_w1(blockIdx.x - 2 < 16 ? 2 * blockIdx.x + wid - 6 : blockIdx.x + (blockIdx.x < 2 ? 0 : 16), wqkv, wimg);
        if (wid == 4) asm volatile("bar.arrive 12, 64;" ::: "memory");
        if (tid == 128) GT(7);
      }
      sched_fence();
      if (wid == 1 && elect_one()) {
        const TileCoord tc = decode_tile(tt, blockIdx.x * kTilesPerCta);
        mbar_init(bar_x(bars, 0, 0), 1);
        asm volatile("fence.mbarrier_init.release.cluster;" ::: "memory");
        mbar_arrive_expect_tx(bar_x(bars, 0, 0), kWChunk);
        GT(15);
#pragma unroll 1
        for (int q = 0; q < 3; q++) load_px(tm, tt, sbase + x_chunk(0, q), bar_x(bars, 0, 0), first_line(tc) + q, tc.kind);
        GT(16);
      }
      __syncwarp();
      sched_fence();
      if (wid == 2 && elect_one()) {
        const TileCoord tc = decode_tile(tt, blockIdx.x * kTilesPerCta);
        mbar_init(bar_full(bars, 0, 0), 1);
        asm volatile("fence.mbarrier_init.release.cluster;" ::: "memory");
        mbar_arrive_expect_tx(bar_full(bars, 0, 0), 2 * kChunkBytes);
        if (NAT_TH) wait_clock(t_start, NAT_TH);
        asm volatile("prefetch.tensormap [%0];" ::"l"((uint64_t)&tm.u8) : "memory");
        GT(17);
        first_halo(tm, sbase, tc, 0);
        first_halo(tm, sbase, tc, 1);
      }
      __syncwarp();
    }
    sched_fence();
    {
      if (w2cta) {
        const int q = blockIdx.x & 3;
        uint32_t w2o = 0;
        if (wid == 1 && elect_one()) {
          asm volatile("prefetch.tensormap [%0];" ::"l"((uint64_t)&tm.wo) : "memory");
#pragma unroll
          for (int j = 0; j < 3; j++) mbar_init(bar_raw(bars, j), 1);
          asm volatile("fence.mbarrier_init.release.cluster;" ::: "memory");
#pragma unroll
          for (int j = 0; j < 6; j++)
            asm volatile("cp.async.bulk.tensor.2d.shared::cluster.global.tile.mbarrier::complete_tx::bytes [%0], [%1, {%3, %4}], [%2];" ::"r"(
                             j < 3 ? sbase + j * 8192 : sbase + kW2Off + (j - 3) * kWChunk),
                         "l"((uint64_t)(j < 3 ? &tm.wv : &tm.wo)), "r"(bar_raw(bars, j < 3 ? 0 : j - 3)),
                         "r"(j < 3 ? 384 + 64 * j : 64 * (j - 3)), "r"(j < 3 ? 64 * q : 0) : "memory");
#pragma unroll
          for (int j = 0; j < 3; j++) mbar_arrive_expect_tx(bar_raw(bars, j), j ? kWChunk : 2 * kWChunk);
          w2o = w2_offset();
        }
        __syncwarp();
#pragma unroll 1
        for (int r = 0; r < 3; r++) {
          const int blk = 2 * r - 2 + (wid >> 2);
          if (blk < 3) {
            if (r > 0) {
              mbar_wait(bar_raw(bars, 0), 0);
              mbar_wait(bar_raw(bars, blk), 0);
            }
            if (tid == 0 && r == 1) GT(7);
            float acc[32];
            const uint64_t db = make_desc(sbase + kW2Off + max(blk, 0) * kWChunk, kWChunk, 1024);
            wg_fence();
            wg_m64tz<0, 32>(acc, make_desc(sbase, 16, 1024), db, 0);
#pragma unroll
            for (int s = 1; s < 12; s++) wg_m64t<0, 32>(acc, make_desc(sbase + (s >> 2) * 8192 + (s & 3) * 32, 16, 1024), db + s * 128, 1);
            wg_commit();
            wg_wait<0>();
            fence_regs(acc);
            if (tid == 0) GT(19);
            const int m = (tid >> 3) & 3;
#pragma unroll
            for (int j = 0; j < 8; j += 2) {
              const int n = g2_inv(8 * (j + (m >> 1)) + (tid & 7));
              asm volatile("stmatrix.sync.aligned.m8n8.x4.trans.shared.b16 [%0], {%1,%2,%3,%4};" ::"r"(
                               sbase + kW1Off + (blk + 2) * 8192 + n * 128 + (((2 * (wid & 3) + (m & 1)) ^ (n & 7)) << 4)),
                           "r"(pack_bf16(acc[4 * j], acc[4 * j + 1])), "r"(pack_bf16(acc[4 * j + 2], acc[4 * j + 3])),
                           "r"(pack_bf16(acc[4 * j + 4], acc[4 * j + 5])), "r"(pack_bf16(acc[4 * j + 6], acc[4 * j + 7])) : "memory");
            }
            fence_proxy_async();
          }
          if (tid == 0) GT(18);
          asm volatile("bar.sync 11, 256;" ::: "memory");
          if (wid == 1 && elect_one()) {
            asm volatile("{\n.reg .pred p;\nsetp.ne.s32 p, %3, 0;\n@p cp.async.bulk.global.shared::cta.bulk_group [%0], [%1], %2;\n}\n" ::"l"(
                             wimg + (w2o + w2piece(r >> 1, q) * (kWChunk / 2))),
                         "r"(sbase + kW1Off + 16384 + (r >> 1) * (kWChunk / 2)), "r"(kWChunk / 2), "r"(r) : "memory");
            asm volatile("cp.async.bulk.commit_group;" ::: "memory");
          }
          __syncwarp();
        }
        if (wid == 1) {
          if (elect_one()) asm volatile("cp.async.bulk.wait_group.read 0;" ::: "memory");
          if (tid == 32) GT(31);
          __syncwarp();
          asm volatile("bar.arrive 10, 64;" ::: "memory");
        }
      }
    }
    __syncwarp();
    if (wid < 4) asm volatile("bar.sync 0, 160;" ::: "memory");
    else asm volatile("bar.sync 14, 160;" ::: "memory");
    asm volatile("setmaxnreg.inc.sync.aligned.u32 240;");
    consumer(wid >> 2, out, wimg, sbase, zero, tm, tt);
  }
}

}

typedef CUresult (*PFN_encodeTiled)(CUtensorMap*, CUtensorMapDataType, cuuint32_t, void*, const cuuint64_t*,
                                    const cuuint64_t*, const cuuint32_t*, const cuuint32_t*, CUtensorMapInterleave,
                                    CUtensorMapSwizzle, CUtensorMapL2promotion, CUtensorMapFloatOOBfill);

extern "C" void kernel_launch(void* const* d_in, const int* in_sizes, int n_in, void* d_out, int out_size) {
  const __nv_bfloat16* x = (const __nv_bfloat16*)d_in[0];
  const __nv_bfloat16* wqkv = (const __nv_bfloat16*)d_in[1];
  const __nv_bfloat16* wo = (const __nv_bfloat16*)d_in[2];
  __nv_bfloat16* out = (__nv_bfloat16*)d_out;

  static PFN_encodeTiled encode = nullptr;
  static int num_sms = 0;
  static uint8_t* wimg = nullptr;
  if (!encode) {
    void* fn = nullptr;
    cudaDriverEntryPointQueryResult qres;
    cudaGetDriverEntryPoint("cuTensorMapEncodeTiled", &fn, cudaEnableDefault, &qres);
    encode = (PFN_encodeTiled)fn;
    cudaFuncSetAttribute(nat::nat_kernel, cudaFuncAttributeMaxDynamicSharedMemorySize, nat::kSmemBytes);
    cudaGetSymbolAddress((void**)&wimg, nat::g_wimg32);
    int dev = 0;
    cudaGetDevice(&dev);
    cudaDeviceGetAttribute(&num_sms, cudaDevAttrMultiProcessorCount, dev);
  }
  nat::Maps tm;
  cuuint32_t estr[5] = {1, 1, 1, 1, 1};
  {
    cuuint64_t vdim[5] = {48, 2, 105, 2, 112}, udim[5] = {48, 2, 112, 2, 105};
    cuuint64_t vstr[4] = {7 * 768, 768, 224 * 384, 2 * 224 * 384}, ustr[4] = {7 * 768, 2 * 224 * 384, 224 * 384, 768};
    CUtensorMap* maps[4] = {&tm.v6, &tm.v2, &tm.v14, &tm.u8};
    for (int i = 0; i < 4; i++) {
      cuuint32_t box[5] = {4, 2, i < 3 ? 4u : 8u, 1, i == 0 ? 6u : i == 1 ? 2u : i == 2 ? 14u : 3u};
      encode(maps[i], CU_TENSOR_MAP_DATA_TYPE_UINT32, 5, (void*)x, i < 3 ? vdim : udim, i < 3 ? vstr : ustr, box, estr,
             CU_TENSOR_MAP_INTERLEAVE_16B, CU_TENSOR_MAP_SWIZZLE_128B, CU_TENSOR_MAP_L2_PROMOTION_L2_128B, CU_TENSOR_MAP_FLOAT_OOB_FILL_NONE);
    }
  }
  for (int i = 0; i < 8; i++) {
    const cuuint32_t row = 224 * 384;
    const cuuint32_t shape[8][6] = {{2, 8, 4, 2 * row, 768, 4 * row}, {2, 8, 3, row, 768, 2 * row},     {2, 8, 1, 2 * row, 768, 4 * row},
                                    {8, 2, 3, 2 * row, 4 * 384, 384}, {8, 2, 1, 2 * row, 5 * 384, 384}, {4, 2, 3, 4 * row, 2 * row, 128},
                                    {4, 2, 3, 768, row, 128},         {4, 2, 3, 768, 2 * row, 128}};
    const cuuint32_t* sh = shape[i];
    cuuint64_t dim[5] = {64, sh[0], sh[1], sh[2], 224 * 224 * 3};
    cuuint64_t str[4] = {sh[3], sh[4], sh[5], 128};
    cuuint32_t box[5] = {64, sh[0], sh[1], sh[2], 1};
    encode(tm.px + i, CU_TENSOR_MAP_DATA_TYPE_BFLOAT16, 5, i < 5 ? (void*)x : (void*)out, dim, str, box, estr, CU_TENSOR_MAP_INTERLEAVE_NONE,
           CU_TENSOR_MAP_SWIZZLE_128B, i < 5 ? CU_TENSOR_MAP_L2_PROMOTION_L2_128B : CU_TENSOR_MAP_L2_PROMOTION_NONE,
           CU_TENSOR_MAP_FLOAT_OOB_FILL_NONE);
  }
  for (int i = 0; i < 2; i++) {
    cuuint64_t dim[2] = {i ? 192u : 576u, 192}, str[1] = {i ? 384u : 1152u};
    cuuint32_t box[2] = {64, i ? 192u : 64u};
    encode(i ? &tm.wo : &tm.wv, CU_TENSOR_MAP_DATA_TYPE_BFLOAT16, 2, i ? (void*)wo : (void*)wqkv, dim, str, box, estr,
           CU_TENSOR_MAP_INTERLEAVE_NONE, CU_TENSOR_MAP_SWIZZLE_128B, CU_TENSOR_MAP_L2_PROMOTION_L2_256B, CU_TENSOR_MAP_FLOAT_OOB_FILL_NONE);
  }
  nat::TileTable tt;
  nat::make_tiles(tt);
  const int grid = nat::kCtas;
  if (num_sms >= grid) {
    nat::nat_kernel<<<grid, 384, nat::kSmemBytes>>>(x, out, wqkv, wo, wimg, 0u, tm, tt);
  } else {
    nat::fold_kernel<<<27, 256>>>(wqkv, wo, wimg);
    nat::nat_kernel<<<grid, 384, nat::kSmemBytes>>>(x, out, nullptr, nullptr, wimg, 0u, tm, tt);
  }
}
```

```cpp
#include <cuda_runtime.h>
#include <cuda_bf16.h>
#include <cuda.h>
#include <stdint.h>

#define NAT_P1 2
#define NAT_P2 4
#define NAT_H0 2
#define NAT_T0 2100
#define NAT_TD 1200
#define NAT_TW2 4650
#define NAT_TX2 3800
#define NAT_X1P 5
#define NAT_PK 3
#define NAT_HP 1800
#define NAT_PFD 400
#define NAT_XW 200
#define NAT_MP 3
#define NAT_D0 1
#define NAT_TH 600
#define NAT_TM 1300
#define NAT_SB 0
namespace nat {

constexpr int kW = 224, kC = 192;
constexpr int kCtas = 132;
constexpr int kTilesPerCta = 6;
constexpr float kAlpha = 0.07216878364870322f * 1.4426950408889634f;
constexpr uint32_t kChunkBytes = 13 * 1024;
constexpr uint32_t kWChunk = 192 * 128;
constexpr uint32_t kWBytes = 3 * kWChunk;
constexpr uint32_t kW1Off = 6 * kChunkBytes;
constexpr uint32_t kW2Off = kW1Off + kWBytes;
constexpr uint32_t kXOff = kW2Off + kWChunk;
constexpr uint32_t kBarOff = kW2Off + kWBytes;
constexpr uint32_t kProfOff = kBarOff + 208;
constexpr uint32_t kSmemBytes = kBarOff + 1024;

static_assert(kW1Off % 1024 == 0 && kW2Off % 1024 == 0 && kChunkBytes % 1024 == 0, "swizzle alignment");
static_assert(kSmemBytes <= 232448, "smem");

constexpr uint32_t kEmpty = 0xFFFFFFFFu;
#define NAT_R8(v) v, v, v, v, v, v, v, v
#define NAT_R2K(v) NAT_R8(NAT_R8(NAT_R8(v))), NAT_R8(NAT_R8(NAT_R8(v))), NAT_R8(NAT_R8(NAT_R8(v))), NAT_R8(NAT_R8(NAT_R8(v)))
#define NAT_IMG NAT_R8(NAT_R2K(kEmpty)), NAT_R2K(kEmpty)
__device__ __align__(1024) uint32_t g_wimg32[3 * kWBytes / 4] = {NAT_IMG, NAT_IMG, NAT_IMG};
static_assert(kWBytes / 4 == 9 * 2048, "initialiser");
__device__ __align__(128) uint32_t g_flag[96];
__device__ __forceinline__ uint32_t w2_offset() {
  uint32_t v;
  asm volatile("ld.relaxed.gpu.global.u32 %0, [%1];" : "=r"(v) : "l"(g_flag + 64) : "memory");
  return (1 + v) * kWBytes;
}

#define PROFS(id, wgid, slotid) do { } while (0)
#define PROF(wgid, slotid) do { } while (0)
#define PROF_DUMP(wgid) do { } while (0)

#define GT(slotid) do { } while (0)
#define GT_DUMP() do { } while (0)

__device__ __forceinline__ uint32_t smem_u32(const void* p) { return (uint32_t)__cvta_generic_to_shared(p); }

__device__ __forceinline__ void mbar_init(uint32_t bar, uint32_t count) {
  asm volatile("mbarrier.init.shared::cta.b64 [%0], %1;" ::"r"(bar), "r"(count) : "memory");
}
__device__ __forceinline__ void mbar_arrive(uint32_t bar) {
  asm volatile("mbarrier.arrive.shared::cta.b64 _, [%0];" ::"r"(bar) : "memory");
}
__device__ __forceinline__ void mbar_arrive_expect_tx(uint32_t bar, uint32_t bytes) {
  asm volatile("mbarrier.arrive.expect_tx.shared::cta.b64 _, [%0], %1;" ::"r"(bar), "r"(bytes) : "memory");
}
__device__ __forceinline__ void mbar_wait(uint32_t bar, uint32_t parity) {
  uint32_t ok;
  uint32_t it = 0;
  do {
    asm volatile(
        "{\n.reg .pred p;\n"
        "mbarrier.try_wait.parity.shared::cta.b64 p, [%1], %2;\n"
        "selp.u32 %0, 1, 0, p;\n}\n"
        : "=r"(ok)
        : "r"(bar), "r"(parity)
        : "memory");
    if (++it > (1u << 24)) break;
  } while (!ok);
}
__device__ __forceinline__ uint32_t mbar_test(uint32_t bar, uint32_t parity) {
  uint32_t ok;
  asm volatile("{\n.reg .pred p;\nmbarrier.test_wait.parity.shared::cta.b64 p, [%1], %2;\nselp.u32 %0, 1, 0, p;\n}\n"
               : "=r"(ok) : "r"(bar), "r"(parity) : "memory");
  return ok;
}
__device__ __forceinline__ void mbar_wait_if(uint32_t ok, uint32_t bar, uint32_t parity) {
  if (!__all_sync(0xffffffffu, ok)) mbar_wait(bar, parity);
}
__device__ __forceinline__ bool elect_one() {
  uint32_t r;
  asm volatile("{\n.reg .pred p;\nelect.sync _|p, 0xffffffff;\nselp.u32 %0, 1, 0, p;\n}\n" : "=r"(r));
  return r != 0;
}
__device__ __forceinline__ void nb_arrive(int id) { asm volatile("bar.arrive %0, 256;" ::"r"(id) : "memory"); }
__device__ __forceinline__ void nb_sync(int id) { asm volatile("bar.sync %0, 256;" ::"r"(id) : "memory"); }
__device__ __forceinline__ void nb_arrive_p(int id) { asm volatile("bar.arrive %0, 160;" ::"r"(id) : "memory"); }
__device__ __forceinline__ void nb_sync_p(int id) { asm volatile("bar.sync %0, 160;" ::"r"(id) : "memory"); }
__device__ __forceinline__ void fence_proxy_async() { asm volatile("fence.proxy.async.shared::cta;" ::: "memory"); }

__device__ __forceinline__ void tma_load_5d(uint32_t dst, const CUtensorMap* map, uint32_t bar, int c0, int c1, int c2,
                                            int c3, int c4) {
  asm volatile(
      "cp.async.bulk.tensor.5d.shared::cluster.global.tile.mbarrier::complete_tx::bytes "
      "[%0], [%1, {%3, %4, %5, %6, %7}], [%2];"
      ::"r"(dst), "l"((uint64_t)map), "r"(bar), "r"(c0), "r"(c1), "r"(c2), "r"(c3), "r"(c4)
      : "memory");
}
__device__ __forceinline__ void bulk_load(uint32_t dst, const void* src, uint32_t bytes, uint32_t bar) {
  asm volatile("cp.async.bulk.shared::cluster.global.mbarrier::complete_tx::bytes [%0], [%1], %2, [%3];"
               ::"r"(dst), "l"((uint64_t)src), "r"(bytes), "r"(bar)
               : "memory");
}

__device__ __forceinline__ void wg_fence() { asm volatile("wgmma.fence.sync.aligned;" ::: "memory"); }
__device__ __forceinline__ void wg_commit() { asm volatile("wgmma.commit_group.sync.aligned;" ::: "memory"); }
template <int N>
__device__ __forceinline__ void wg_wait() { asm volatile("wgmma.wait_group.sync.aligned %0;" ::"n"(N) : "memory"); }

template <int N>
__device__ __forceinline__ void fence_regs(float (&d)[N]) {
#pragma unroll
  for (int i = 0; i < N; i++) asm volatile("" : "+f"(d[i])::"memory");
}
template <int N>
__device__ __forceinline__ void keep_regs(uint32_t (&d)[N]) {
#pragma unroll
  for (int i = 0; i < N; i++) asm volatile("" : "+r"(d[i])::"memory");
}

__device__ __forceinline__ uint32_t pack_bf16(float lo, float hi) {
  uint32_t d;
  asm("cvt.rn.bf16x2.f32 %0, %1, %2;" : "=r"(d) : "f"(hi), "f"(lo));
  return d;
}
__device__ __forceinline__ float ex2(float x) {
  float y;
  asm("ex2.approx.ftz.f32 %0, %1;" : "=f"(y) : "f"(x));
  return y;
}
__device__ __forceinline__ float rcp_approx(float x) {
  float y;
  asm("rcp.approx.ftz.f32 %0, %1;" : "=f"(y) : "f"(x));
  return y;
}
__device__ __forceinline__ uint4 ldg128_nc(const void* p) {
  uint4 v;
  asm volatile("ld.global.nc.v4.u32 {%0,%1,%2,%3}, [%4];" : "=r"(v.x), "=r"(v.y), "=r"(v.z), "=r"(v.w) : "l"(p));
  return v;
}
__device__ __forceinline__ void stg128(void* p, uint32_t a, uint32_t b, uint32_t c, uint32_t d) {
  asm volatile("st.global.v4.u32 [%0], {%1,%2,%3,%4};" ::"l"(p), "r"(a), "r"(b), "r"(c), "r"(d) : "memory");
}

__device__ __forceinline__ long long clk64() {
  long long c;
  asm volatile("mov.u64 %0, %clock64;" : "=l"(c)::"memory");
  return c;
}
__device__ __forceinline__ void sched_fence() { while (clk64() < 0) { } }

__device__ __forceinline__ uint64_t make_desc(uint32_t addr, uint32_t lbo, uint32_t sbo, uint32_t mode = 1) {
  return (uint64_t)((addr & 0x3FFFF) >> 4) | ((uint64_t)(lbo >> 4) << 16) | ((uint64_t)(sbo >> 4) << 32) |
         ((uint64_t)mode << 62);
}

template <int OFF, int NN>
__device__ __forceinline__ void wg_m192(float (&d)[NN], uint64_t desc_a, uint64_t desc_b, int scale_d) {
  asm volatile(
      "{\n.reg .pred p;\nsetp.ne.b32 p, %98, 0;\n"
      "wgmma.mma_async.sync.aligned.m64n192k16.f32.bf16.bf16 "
      "{%0,%1,%2,%3,%4,%5,%6,%7,%8,%9,%10,%11,%12,%13,%14,%15,"
      "%16,%17,%18,%19,%20,%21,%22,%23,%24,%25,%26,%27,%28,%29,%30,%31,"
      "%32,%33,%34,%35,%36,%37,%38,%39,%40,%41,%42,%43,%44,%45,%46,%47,"
      "%48,%49,%50,%51,%52,%53,%54,%55,%56,%57,%58,%59,%60,%61,%62,%63,"
      "%64,%65,%66,%67,%68,%69,%70,%71,%72,%73,%74,%75,%76,%77,%78,%79,"
      "%80,%81,%82,%83,%84,%85,%86,%87,%88,%89,%90,%91,%92,%93,%94,%95}, "
      "%96, %97, p, 1, 1, 0, 0;\n}\n"
      : "+f"(d[OFF + 0]), "+f"(d[OFF + 1]), "+f"(d[OFF + 2]), "+f"(d[OFF + 3]), "+f"(d[OFF + 4]), "+f"(d[OFF + 5]),
        "+f"(d[OFF + 6]), "+f"(d[OFF + 7]), "+f"(d[OFF + 8]), "+f"(d[OFF + 9]), "+f"(d[OFF + 10]), "+f"(d[OFF + 11]),
        "+f"(d[OFF + 12]), "+f"(d[OFF + 13]), "+f"(d[OFF + 14]), "+f"(d[OFF + 15]), "+f"(d[OFF + 16]), "+f"(d[OFF + 17]),
        "+f"(d[OFF + 18]), "+f"(d[OFF + 19]), "+f"(d[OFF + 20]), "+f"(d[OFF + 21]), "+f"(d[OFF + 22]), "+f"(d[OFF + 23]),
        "+f"(d[OFF + 24]), "+f"(d[OFF + 25]), "+f"(d[OFF + 26]), "+f"(d[OFF + 27]), "+f"(d[OFF + 28]), "+f"(d[OFF + 29]),
        "+f"(d[OFF + 30]), "+f"(d[OFF + 31]), "+f"(d[OFF + 32]), "+f"(d[OFF + 33]), "+f"(d[OFF + 34]), "+f"(d[OFF + 35]),
        "+f"(d[OFF + 36]), "+f"(d[OFF + 37]), "+f"(d[OFF + 38]), "+f"(d[OFF + 39]), "+f"(d[OFF + 40]), "+f"(d[OFF + 41]),
        "+f"(d[OFF + 42]), "+f"(d[OFF + 43]), "+f"(d[OFF + 44]), "+f"(d[OFF + 45]), "+f"(d[OFF + 46]), "+f"(d[OFF + 47]),
        "+f"(d[OFF + 48]), "+f"(d[OFF + 49]), "+f"(d[OFF + 50]), "+f"(d[OFF + 51]), "+f"(d[OFF + 52]), "+f"(d[OFF + 53]),
        "+f"(d[OFF + 54]), "+f"(d[OFF + 55]), "+f"(d[OFF + 56]), "+f"(d[OFF + 57]), "+f"(d[OFF + 58]), "+f"(d[OFF + 59]),
        "+f"(d[OFF + 60]), "+f"(d[OFF + 61]), "+f"(d[OFF + 62]), "+f"(d[OFF + 63]), "+f"(d[OFF + 64]), "+f"(d[OFF + 65]),
        "+f"(d[OFF + 66]), "+f"(d[OFF + 67]), "+f"(d[OFF + 68]), "+f"(d[OFF + 69]), "+f"(d[OFF + 70]), "+f"(d[OFF + 71]),
        "+f"(d[OFF + 72]), "+f"(d[OFF + 73]), "+f"(d[OFF + 74]), "+f"(d[OFF + 75]), "+f"(d[OFF + 76]), "+f"(d[OFF + 77]),
        "+f"(d[OFF + 78]), "+f"(d[OFF + 79]), "+f"(d[OFF + 80]), "+f"(d[OFF + 81]), "+f"(d[OFF + 82]), "+f"(d[OFF + 83]),
        "+f"(d[OFF + 84]), "+f"(d[OFF + 85]), "+f"(d[OFF + 86]), "+f"(d[OFF + 87]), "+f"(d[OFF + 88]), "+f"(d[OFF + 89]),
        "+f"(d[OFF + 90]), "+f"(d[OFF + 91]), "+f"(d[OFF + 92]), "+f"(d[OFF + 93]), "+f"(d[OFF + 94]), "+f"(d[OFF + 95])
      : "l"(desc_a), "l"(desc_b), "r"(scale_d));
}

template <int OFF, int NN>
__device__ __forceinline__ void wg_m192z(float (&d)[NN], uint64_t desc_a, uint64_t desc_b, int scale_d) {
  asm volatile(
      "{\n.reg .pred p;\nsetp.ne.b32 p, %98, 0;\n"
      "wgmma.mma_async.sync.aligned.m64n192k16.f32.bf16.bf16 "
      "{%0,%1,%2,%3,%4,%5,%6,%7,%8,%9,%10,%11,%12,%13,%14,%15,"
      "%16,%17,%18,%19,%20,%21,%22,%23,%24,%25,%26,%27,%28,%29,%30,%31,"
      "%32,%33,%34,%35,%36,%37,%38,%39,%40,%41,%42,%43,%44,%45,%46,%47,"
      "%48,%49,%50,%51,%52,%53,%54,%55,%56,%57,%58,%59,%60,%61,%62,%63,"
      "%64,%65,%66,%67,%68,%69,%70,%71,%72,%73,%74,%75,%76,%77,%78,%79,"
      "%80,%81,%82,%83,%84,%85,%86,%87,%88,%89,%90,%91,%92,%93,%94,%95}, "
      "%96, %97, p, 1, 1, 0, 0;\n}\n"
      : "=f"(d[OFF + 0]), "=f"(d[OFF + 1]), "=f"(d[OFF + 2]), "=f"(d[OFF + 3]), "=f"(d[OFF + 4]), "=f"(d[OFF + 5]),
        "=f"(d[OFF + 6]), "=f"(d[OFF + 7]), "=f"(d[OFF + 8]), "=f"(d[OFF + 9]), "=f"(d[OFF + 10]), "=f"(d[OFF + 11]),
        "=f"(d[OFF + 12]), "=f"(d[OFF + 13]), "=f"(d[OFF + 14]), "=f"(d[OFF + 15]), "=f"(d[OFF + 16]), "=f"(d[OFF + 17]),
        "=f"(d[OFF + 18]), "=f"(d[OFF + 19]), "=f"(d[OFF + 20]), "=f"(d[OFF + 21]), "=f"(d[OFF + 22]), "=f"(d[OFF + 23]),
        "=f"(d[OFF + 24]), "=f"(d[OFF + 25]), "=f"(d[OFF + 26]), "=f"(d[OFF + 27]), "=f"(d[OFF + 28]), "=f"(d[OFF + 29]),
        "=f"(d[OFF + 30]), "=f"(d[OFF + 31]), "=f"(d[OFF + 32]), "=f"(d[OFF + 33]), "=f"(d[OFF + 34]), "=f"(d[OFF + 35]),
        "=f"(d[OFF + 36]), "=f"(d[OFF + 37]), "=f"(d[OFF + 38]), "=f"(d[OFF + 39]), "=f"(d[OFF + 40]), "=f"(d[OFF + 41]),
        "=f"(d[OFF + 42]), "=f"(d[OFF + 43]), "=f"(d[OFF + 44]), "=f"(d[OFF + 45]), "=f"(d[OFF + 46]), "=f"(d[OFF + 47]),
        "=f"(d[OFF + 48]), "=f"(d[OFF + 49]), "=f"(d[OFF + 50]), "=f"(d[OFF + 51]), "=f"(d[OFF + 52]), "=f"(d[OFF + 53]),
        "=f"(d[OFF + 54]), "=f"(d[OFF + 55]), "=f"(d[OFF + 56]), "=f"(d[OFF + 57]), "=f"(d[OFF + 58]), "=f"(d[OFF + 59]),
        "=f"(d[OFF + 60]), "=f"(d[OFF + 61]), "=f"(d[OFF + 62]), "=f"(d[OFF + 63]), "=f"(d[OFF + 64]), "=f"(d[OFF + 65]),
        "=f"(d[OFF + 66]), "=f"(d[OFF + 67]), "=f"(d[OFF + 68]), "=f"(d[OFF + 69]), "=f"(d[OFF + 70]), "=f"(d[OFF + 71]),
        "=f"(d[OFF + 72]), "=f"(d[OFF + 73]), "=f"(d[OFF + 74]), "=f"(d[OFF + 75]), "=f"(d[OFF + 76]), "=f"(d[OFF + 77]),
        "=f"(d[OFF + 78]), "=f"(d[OFF + 79]), "=f"(d[OFF + 80]), "=f"(d[OFF + 81]), "=f"(d[OFF + 82]), "=f"(d[OFF + 83]),
        "=f"(d[OFF + 84]), "=f"(d[OFF + 85]), "=f"(d[OFF + 86]), "=f"(d[OFF + 87]), "=f"(d[OFF + 88]), "=f"(d[OFF + 89]),
        "=f"(d[OFF + 90]), "=f"(d[OFF + 91]), "=f"(d[OFF + 92]), "=f"(d[OFF + 93]), "=f"(d[OFF + 94]), "=f"(d[OFF + 95])
      : "l"(desc_a), "l"(desc_b), "r"(scale_d));
}

template <int OFF, int NN>
__device__ __forceinline__ void wg_m64t(float (&d)[NN], uint64_t desc_a, uint64_t desc_b, int scale_d) {
  asm volatile(
      "{\n.reg .pred p;\nsetp.ne.b32 p, %34, 0;\n"
      "wgmma.mma_async.sync.aligned.m64n64k16.f32.bf16.bf16 "
      "{%0,%1,%2,%3,%4,%5,%6,%7,%8,%9,%10,%11,%12,%13,%14,%15,"
      "%16,%17,%18,%19,%20,%21,%22,%23,%24,%25,%26,%27,%28,%29,%30,%31}, "
      "%32, %33, p, 1, 1, 0, 1;\n}\n"
      : "+f"(d[OFF + 0]), "+f"(d[OFF + 1]), "+f"(d[OFF + 2]), "+f"(d[OFF + 3]), "+f"(d[OFF + 4]), "+f"(d[OFF + 5]),
        "+f"(d[OFF + 6]), "+f"(d[OFF + 7]), "+f"(d[OFF + 8]), "+f"(d[OFF + 9]), "+f"(d[OFF + 10]), "+f"(d[OFF + 11]),
        "+f"(d[OFF + 12]), "+f"(d[OFF + 13]), "+f"(d[OFF + 14]), "+f"(d[OFF + 15]), "+f"(d[OFF + 16]), "+f"(d[OFF + 17]),
        "+f"(d[OFF + 18]), "+f"(d[OFF + 19]), "+f"(d[OFF + 20]), "+f"(d[OFF + 21]), "+f"(d[OFF + 22]), "+f"(d[OFF + 23]),
        "+f"(d[OFF + 24]), "+f"(d[OFF + 25]), "+f"(d[OFF + 26]), "+f"(d[OFF + 27]), "+f"(d[OFF + 28]), "+f"(d[OFF + 29]),
        "+f"(d[OFF + 30]), "+f"(d[OFF + 31])
      : "l"(desc_a), "l"(desc_b), "r"(scale_d));
}

template <int OFF, int NN>
__device__ __forceinline__ void wg_m64tz(float (&d)[NN], uint64_t desc_a, uint64_t desc_b, int scale_d) {
  asm volatile(
      "{\n.reg .pred p;\nsetp.ne.b32 p, %34, 0;\n"
      "wgmma.mma_async.sync.aligned.m64n64k16.f32.bf16.bf16 "
      "{%0,%1,%2,%3,%4,%5,%6,%7,%8,%9,%10,%11,%12,%13,%14,%15,"
      "%16,%17,%18,%19,%20,%21,%22,%23,%24,%25,%26,%27,%28,%29,%30,%31}, "
      "%32, %33, p, 1, 1, 0, 1;\n}\n"
      : "=f"(d[OFF + 0]), "=f"(d[OFF + 1]), "=f"(d[OFF + 2]), "=f"(d[OFF + 3]), "=f"(d[OFF + 4]), "=f"(d[OFF + 5]),
        "=f"(d[OFF + 6]), "=f"(d[OFF + 7]), "=f"(d[OFF + 8]), "=f"(d[OFF + 9]), "=f"(d[OFF + 10]), "=f"(d[OFF + 11]),
        "=f"(d[OFF + 12]), "=f"(d[OFF + 13]), "=f"(d[OFF + 14]), "=f"(d[OFF + 15]), "=f"(d[OFF + 16]), "=f"(d[OFF + 17]),
        "=f"(d[OFF + 18]), "=f"(d[OFF + 19]), "=f"(d[OFF + 20]), "=f"(d[OFF + 21]), "=f"(d[OFF + 22]), "=f"(d[OFF + 23]),
        "=f"(d[OFF + 24]), "=f"(d[OFF + 25]), "=f"(d[OFF + 26]), "=f"(d[OFF + 27]), "=f"(d[OFF + 28]), "=f"(d[OFF + 29]),
        "=f"(d[OFF + 30]), "=f"(d[OFF + 31])
      : "l"(desc_a), "l"(desc_b), "r"(scale_d));
}

template <int OFF, int NN>
__device__ __forceinline__ void wg_d96(float (&d)[NN], uint32_t a0, uint32_t a1, uint32_t a2, uint32_t a3,
                                       uint64_t desc_b, int scale_d) {
  asm volatile(
      "{\n.reg .pred p;\nsetp.ne.b32 p, %53, 0;\n"
      "wgmma.mma_async.sync.aligned.m64n96k16.f32.bf16.bf16 "
      "{%0,%1,%2,%3,%4,%5,%6,%7,%8,%9,%10,%11,%12,%13,%14,%15,"
      "%16,%17,%18,%19,%20,%21,%22,%23,%24,%25,%26,%27,%28,%29,%30,%31,"
      "%32,%33,%34,%35,%36,%37,%38,%39,%40,%41,%42,%43,%44,%45,%46,%47}, "
      "{%48,%49,%50,%51}, %52, p, 1, 1, 0;\n}\n"
      : "+f"(d[OFF + 0]), "+f"(d[OFF + 1]), "+f"(d[OFF + 2]), "+f"(d[OFF + 3]), "+f"(d[OFF + 4]), "+f"(d[OFF + 5]),
        "+f"(d[OFF + 6]), "+f"(d[OFF + 7]), "+f"(d[OFF + 8]), "+f"(d[OFF + 9]), "+f"(d[OFF + 10]), "+f"(d[OFF + 11]),
        "+f"(d[OFF + 12]), "+f"(d[OFF + 13]), "+f"(d[OFF + 14]), "+f"(d[OFF + 15]), "+f"(d[OFF + 16]), "+f"(d[OFF + 17]),
        "+f"(d[OFF + 18]), "+f"(d[OFF + 19]), "+f"(d[OFF + 20]), "+f"(d[OFF + 21]), "+f"(d[OFF + 22]), "+f"(d[OFF + 23]),
        "+f"(d[OFF + 24]), "+f"(d[OFF + 25]), "+f"(d[OFF + 26]), "+f"(d[OFF + 27]), "+f"(d[OFF + 28]), "+f"(d[OFF + 29]),
        "+f"(d[OFF + 30]), "+f"(d[OFF + 31]), "+f"(d[OFF + 32]), "+f"(d[OFF + 33]), "+f"(d[OFF + 34]), "+f"(d[OFF + 35]),
        "+f"(d[OFF + 36]), "+f"(d[OFF + 37]), "+f"(d[OFF + 38]), "+f"(d[OFF + 39]), "+f"(d[OFF + 40]), "+f"(d[OFF + 41]),
        "+f"(d[OFF + 42]), "+f"(d[OFF + 43]), "+f"(d[OFF + 44]), "+f"(d[OFF + 45]), "+f"(d[OFF + 46]), "+f"(d[OFF + 47])
      : "r"(a0), "r"(a1), "r"(a2), "r"(a3), "l"(desc_b), "r"(scale_d));
}

template <int OFF, int NN>
__device__ __forceinline__ void wg_d96z(float (&d)[NN], uint32_t a0, uint32_t a1, uint32_t a2, uint32_t a3,
                                       uint64_t desc_b, int scale_d) {
  asm volatile(
      "{\n.reg .pred p;\nsetp.ne.b32 p, %53, 0;\n"
      "wgmma.mma_async.sync.aligned.m64n96k16.f32.bf16.bf16 "
      "{%0,%1,%2,%3,%4,%5,%6,%7,%8,%9,%10,%11,%12,%13,%14,%15,"
      "%16,%17,%18,%19,%20,%21,%22,%23,%24,%25,%26,%27,%28,%29,%30,%31,"
      "%32,%33,%34,%35,%36,%37,%38,%39,%40,%41,%42,%43,%44,%45,%46,%47}, "
      "{%48,%49,%50,%51}, %52, p, 1, 1, 0;\n}\n"
      : "=f"(d[OFF + 0]), "=f"(d[OFF + 1]), "=f"(d[OFF + 2]), "=f"(d[OFF + 3]), "=f"(d[OFF + 4]), "=f"(d[OFF + 5]),
        "=f"(d[OFF + 6]), "=f"(d[OFF + 7]), "=f"(d[OFF + 8]), "=f"(d[OFF + 9]), "=f"(d[OFF + 10]), "=f"(d[OFF + 11]),
        "=f"(d[OFF + 12]), "=f"(d[OFF + 13]), "=f"(d[OFF + 14]), "=f"(d[OFF + 15]), "=f"(d[OFF + 16]), "=f"(d[OFF + 17]),
        "=f"(d[OFF + 18]), "=f"(d[OFF + 19]), "=f"(d[OFF + 20]), "=f"(d[OFF + 21]), "=f"(d[OFF + 22]), "=f"(d[OFF + 23]),
        "=f"(d[OFF + 24]), "=f"(d[OFF + 25]), "=f"(d[OFF + 26]), "=f"(d[OFF + 27]), "=f"(d[OFF + 28]), "=f"(d[OFF + 29]),
        "=f"(d[OFF + 30]), "=f"(d[OFF + 31]), "=f"(d[OFF + 32]), "=f"(d[OFF + 33]), "=f"(d[OFF + 34]), "=f"(d[OFF + 35]),
        "=f"(d[OFF + 36]), "=f"(d[OFF + 37]), "=f"(d[OFF + 38]), "=f"(d[OFF + 39]), "=f"(d[OFF + 40]), "=f"(d[OFF + 41]),
        "=f"(d[OFF + 42]), "=f"(d[OFF + 43]), "=f"(d[OFF + 44]), "=f"(d[OFF + 45]), "=f"(d[OFF + 46]), "=f"(d[OFF + 47])
      : "r"(a0), "r"(a1), "r"(a2), "r"(a3), "l"(desc_b), "r"(scale_d));
}

template <int OFF, int NN>
__device__ __forceinline__ void wg_s104(float (&d)[NN], uint32_t a0, uint32_t a1, uint32_t a2, uint32_t a3,
                                       uint64_t desc_b, int scale_d, uint32_t meta) {
  asm volatile(
      "{\n.reg .pred p;\nsetp.ne.b32 p, %57, 0;\n"
      "wgmma.mma_async.sp.sync.aligned.m64n104k32.f32.bf16.bf16 "
      "{%0,%1,%2,%3,%4,%5,%6,%7,%8,%9,%10,%11,%12,%13,%14,%15,"
      "%16,%17,%18,%19,%20,%21,%22,%23,%24,%25,%26,%27,%28,%29,%30,%31,"
      "%32,%33,%34,%35,%36,%37,%38,%39,%40,%41,%42,%43,%44,%45,%46,%47,"
      "%48,%49,%50,%51}, "
      "{%52,%53,%54,%55}, %56, %58, 0, p, 1, 1, 0;\n}\n"
      : "+f"(d[OFF + 0]), "+f"(d[OFF + 1]), "+f"(d[OFF + 2]), "+f"(d[OFF + 3]), "+f"(d[OFF + 4]), "+f"(d[OFF + 5]),
        "+f"(d[OFF + 6]), "+f"(d[OFF + 7]), "+f"(d[OFF + 8]), "+f"(d[OFF + 9]), "+f"(d[OFF + 10]), "+f"(d[OFF + 11]),
        "+f"(d[OFF + 12]), "+f"(d[OFF + 13]), "+f"(d[OFF + 14]), "+f"(d[OFF + 15]), "+f"(d[OFF + 16]), "+f"(d[OFF + 17]),
        "+f"(d[OFF + 18]), "+f"(d[OFF + 19]), "+f"(d[OFF + 20]), "+f"(d[OFF + 21]), "+f"(d[OFF + 22]), "+f"(d[OFF + 23]),
        "+f"(d[OFF + 24]), "+f"(d[OFF + 25]), "+f"(d[OFF + 26]), "+f"(d[OFF + 27]), "+f"(d[OFF + 28]), "+f"(d[OFF + 29]),
        "+f"(d[OFF + 30]), "+f"(d[OFF + 31]), "+f"(d[OFF + 32]), "+f"(d[OFF + 33]), "+f"(d[OFF + 34]), "+f"(d[OFF + 35]),
        "+f"(d[OFF + 36]), "+f"(d[OFF + 37]), "+f"(d[OFF + 38]), "+f"(d[OFF + 39]), "+f"(d[OFF + 40]), "+f"(d[OFF + 41]),
        "+f"(d[OFF + 42]), "+f"(d[OFF + 43]), "+f"(d[OFF + 44]), "+f"(d[OFF + 45]), "+f"(d[OFF + 46]), "+f"(d[OFF + 47]),
        "+f"(d[OFF + 48]), "+f"(d[OFF + 49]), "+f"(d[OFF + 50]), "+f"(d[OFF + 51])
      : "r"(a0), "r"(a1), "r"(a2), "r"(a3), "l"(desc_b), "r"(scale_d), "r"(meta));
}

template <int OFF, int NN>
__device__ __forceinline__ void wg_s104z(float (&d)[NN], uint32_t a0, uint32_t a1, uint32_t a2, uint32_t a3,
                                       uint64_t desc_b, int scale_d, uint32_t meta) {
  asm volatile(
      "{\n.reg .pred p;\nsetp.ne.b32 p, %57, 0;\n"
      "wgmma.mma_async.sp.sync.aligned.m64n104k32.f32.bf16.bf16 "
      "{%0,%1,%2,%3,%4,%5,%6,%7,%8,%9,%10,%11,%12,%13,%14,%15,"
      "%16,%17,%18,%19,%20,%21,%22,%23,%24,%25,%26,%27,%28,%29,%30,%31,"
      "%32,%33,%34,%35,%36,%37,%38,%39,%40,%41,%42,%43,%44,%45,%46,%47,"
      "%48,%49,%50,%51}, "
      "{%52,%53,%54,%55}, %56, %58, 0, p, 1, 1, 0;\n}\n"
      : "=f"(d[OFF + 0]), "=f"(d[OFF + 1]), "=f"(d[OFF + 2]), "=f"(d[OFF + 3]), "=f"(d[OFF + 4]), "=f"(d[OFF + 5]),
        "=f"(d[OFF + 6]), "=f"(d[OFF + 7]), "=f"(d[OFF + 8]), "=f"(d[OFF + 9]), "=f"(d[OFF + 10]), "=f"(d[OFF + 11]),
        "=f"(d[OFF + 12]), "=f"(d[OFF + 13]), "=f"(d[OFF + 14]), "=f"(d[OFF + 15]), "=f"(d[OFF + 16]), "=f"(d[OFF + 17]),
        "=f"(d[OFF + 18]), "=f"(d[OFF + 19]), "=f"(d[OFF + 20]), "=f"(d[OFF + 21]), "=f"(d[OFF + 22]), "=f"(d[OFF + 23]),
        "=f"(d[OFF + 24]), "=f"(d[OFF + 25]), "=f"(d[OFF + 26]), "=f"(d[OFF + 27]), "=f"(d[OFF + 28]), "=f"(d[OFF + 29]),
        "=f"(d[OFF + 30]), "=f"(d[OFF + 31]), "=f"(d[OFF + 32]), "=f"(d[OFF + 33]), "=f"(d[OFF + 34]), "=f"(d[OFF + 35]),
        "=f"(d[OFF + 36]), "=f"(d[OFF + 37]), "=f"(d[OFF + 38]), "=f"(d[OFF + 39]), "=f"(d[OFF + 40]), "=f"(d[OFF + 41]),
        "=f"(d[OFF + 42]), "=f"(d[OFF + 43]), "=f"(d[OFF + 44]), "=f"(d[OFF + 45]), "=f"(d[OFF + 46]), "=f"(d[OFF + 47]),
        "=f"(d[OFF + 48]), "=f"(d[OFF + 49]), "=f"(d[OFF + 50]), "=f"(d[OFF + 51])
      : "r"(a0), "r"(a1), "r"(a2), "r"(a3), "l"(desc_b), "r"(scale_d), "r"(meta));
}

template <int OFF, int NN>
__device__ __forceinline__ void wg_s48(float (&d)[NN], uint32_t a0, uint32_t a1, uint32_t a2, uint32_t a3,
                                       uint64_t desc_b, int scale_d, uint32_t meta) {
  asm volatile(
      "{\n.reg .pred p;\nsetp.ne.b32 p, %29, 0;\n"
      "wgmma.mma_async.sp.sync.aligned.m64n48k32.f32.bf16.bf16 "
      "{%0,%1,%2,%3,%4,%5,%6,%7,%8,%9,%10,%11,%12,%13,%14,%15,"
      "%16,%17,%18,%19,%20,%21,%22,%23}, "
      "{%24,%25,%26,%27}, %28, %30, 0, p, 1, 1, 0;\n}\n"
      : "+f"(d[OFF + 0]), "+f"(d[OFF + 1]), "+f"(d[OFF + 2]), "+f"(d[OFF + 3]), "+f"(d[OFF + 4]), "+f"(d[OFF + 5]),
        "+f"(d[OFF + 6]), "+f"(d[OFF + 7]), "+f"(d[OFF + 8]), "+f"(d[OFF + 9]), "+f"(d[OFF + 10]), "+f"(d[OFF + 11]),
        "+f"(d[OFF + 12]), "+f"(d[OFF + 13]), "+f"(d[OFF + 14]), "+f"(d[OFF + 15]), "+f"(d[OFF + 16]), "+f"(d[OFF + 17]),
        "+f"(d[OFF + 18]), "+f"(d[OFF + 19]), "+f"(d[OFF + 20]), "+f"(d[OFF + 21]), "+f"(d[OFF + 22]), "+f"(d[OFF + 23])
      : "r"(a0), "r"(a1), "r"(a2), "r"(a3), "l"(desc_b), "r"(scale_d), "r"(meta));
}

template <int OFF, int NN>
__device__ __forceinline__ void wg_s48z(float (&d)[NN], uint32_t a0, uint32_t a1, uint32_t a2, uint32_t a3,
                                       uint64_t desc_b, int scale_d, uint32_t meta) {
  asm volatile(
      "{\n.reg .pred p;\nsetp.ne.b32 p, %29, 0;\n"
      "wgmma.mma_async.sp.sync.aligned.m64n48k32.f32.bf16.bf16 "
      "{%0,%1,%2,%3,%4,%5,%6,%7,%8,%9,%10,%11,%12,%13,%14,%15,"
      "%16,%17,%18,%19,%20,%21,%22,%23}, "
      "{%24,%25,%26,%27}, %28, %30, 0, p, 1, 1, 0;\n}\n"
      : "=f"(d[OFF + 0]), "=f"(d[OFF + 1]), "=f"(d[OFF + 2]), "=f"(d[OFF + 3]), "=f"(d[OFF + 4]), "=f"(d[OFF + 5]),
        "=f"(d[OFF + 6]), "=f"(d[OFF + 7]), "=f"(d[OFF + 8]), "=f"(d[OFF + 9]), "=f"(d[OFF + 10]), "=f"(d[OFF + 11]),
        "=f"(d[OFF + 12]), "=f"(d[OFF + 13]), "=f"(d[OFF + 14]), "=f"(d[OFF + 15]), "=f"(d[OFF + 16]), "=f"(d[OFF + 17]),
        "=f"(d[OFF + 18]), "=f"(d[OFF + 19]), "=f"(d[OFF + 20]), "=f"(d[OFF + 21]), "=f"(d[OFF + 22]), "=f"(d[OFF + 23])
      : "r"(a0), "r"(a1), "r"(a2), "r"(a3), "l"(desc_b), "r"(scale_d), "r"(meta));
}

template <int OFF, int NN>
__device__ __forceinline__ void wg_s56(float (&d)[NN], uint32_t a0, uint32_t a1, uint32_t a2, uint32_t a3,
                                       uint64_t desc_b, int scale_d, uint32_t meta) {
  asm volatile(
      "{\n.reg .pred p;\nsetp.ne.b32 p, %33, 0;\n"
      "wgmma.mma_async.sp.sync.aligned.m64n56k32.f32.bf16.bf16 "
      "{%0,%1,%2,%3,%4,%5,%6,%7,%8,%9,%10,%11,%12,%13,%14,%15,"
      "%16,%17,%18,%19,%20,%21,%22,%23,%24,%25,%26,%27}, "
      "{%28,%29,%30,%31}, %32, %34, 0, p, 1, 1, 0;\n}\n"
      : "+f"(d[OFF + 0]), "+f"(d[OFF + 1]), "+f"(d[OFF + 2]), "+f"(d[OFF + 3]), "+f"(d[OFF + 4]), "+f"(d[OFF + 5]),
        "+f"(d[OFF + 6]), "+f"(d[OFF + 7]), "+f"(d[OFF + 8]), "+f"(d[OFF + 9]), "+f"(d[OFF + 10]), "+f"(d[OFF + 11]),
        "+f"(d[OFF + 12]), "+f"(d[OFF + 13]), "+f"(d[OFF + 14]), "+f"(d[OFF + 15]), "+f"(d[OFF + 16]), "+f"(d[OFF + 17]),
        "+f"(d[OFF + 18]), "+f"(d[OFF + 19]), "+f"(d[OFF + 20]), "+f"(d[OFF + 21]), "+f"(d[OFF + 22]), "+f"(d[OFF + 23]),
        "+f"(d[OFF + 24]), "+f"(d[OFF + 25]), "+f"(d[OFF + 26]), "+f"(d[OFF + 27])
      : "r"(a0), "r"(a1), "r"(a2), "r"(a3), "l"(desc_b), "r"(scale_d), "r"(meta));
}

template <int OFF, int NN>
__device__ __forceinline__ void wg_s56z(float (&d)[NN], uint32_t a0, uint32_t a1, uint32_t a2, uint32_t a3,
                                       uint64_t desc_b, int scale_d, uint32_t meta) {
  asm volatile(
      "{\n.reg .pred p;\nsetp.ne.b32 p, %33, 0;\n"
      "wgmma.mma_async.sp.sync.aligned.m64n56k32.f32.bf16.bf16 "
      "{%0,%1,%2,%3,%4,%5,%6,%7,%8,%9,%10,%11,%12,%13,%14,%15,"
      "%16,%17,%18,%19,%20,%21,%22,%23,%24,%25,%26,%27}, "
      "{%28,%29,%30,%31}, %32, %34, 0, p, 1, 1, 0;\n}\n"
      : "=f"(d[OFF + 0]), "=f"(d[OFF + 1]), "=f"(d[OFF + 2]), "=f"(d[OFF + 3]), "=f"(d[OFF + 4]), "=f"(d[OFF + 5]),
        "=f"(d[OFF + 6]), "=f"(d[OFF + 7]), "=f"(d[OFF + 8]), "=f"(d[OFF + 9]), "=f"(d[OFF + 10]), "=f"(d[OFF + 11]),
        "=f"(d[OFF + 12]), "=f"(d[OFF + 13]), "=f"(d[OFF + 14]), "=f"(d[OFF + 15]), "=f"(d[OFF + 16]), "=f"(d[OFF + 17]),
        "=f"(d[OFF + 18]), "=f"(d[OFF + 19]), "=f"(d[OFF + 20]), "=f"(d[OFF + 21]), "=f"(d[OFF + 22]), "=f"(d[OFF + 23]),
        "=f"(d[OFF + 24]), "=f"(d[OFF + 25]), "=f"(d[OFF + 26]), "=f"(d[OFF + 27])
      : "r"(a0), "r"(a1), "r"(a2), "r"(a3), "l"(desc_b), "r"(scale_d), "r"(meta));
}

template <int OFF, int NN>
__device__ __forceinline__ void wg_s64t(float (&d)[NN], uint32_t a0, uint32_t a1, uint32_t a2, uint32_t a3,
                                       uint64_t desc_b, int scale_d, uint32_t meta) {
  asm volatile(
      "{\n.reg .pred p;\nsetp.ne.b32 p, %37, 0;\n"
      "wgmma.mma_async.sp.sync.aligned.m64n64k32.f32.bf16.bf16 "
      "{%0,%1,%2,%3,%4,%5,%6,%7,%8,%9,%10,%11,%12,%13,%14,%15,"
      "%16,%17,%18,%19,%20,%21,%22,%23,%24,%25,%26,%27,%28,%29,%30,%31}, "
      "{%32,%33,%34,%35}, %36, %38, 0, p, 1, 1, 1;\n}\n"
      : "+f"(d[OFF + 0]), "+f"(d[OFF + 1]), "+f"(d[OFF + 2]), "+f"(d[OFF + 3]), "+f"(d[OFF + 4]), "+f"(d[OFF + 5]),
        "+f"(d[OFF + 6]), "+f"(d[OFF + 7]), "+f"(d[OFF + 8]), "+f"(d[OFF + 9]), "+f"(d[OFF + 10]), "+f"(d[OFF + 11]),
        "+f"(d[OFF + 12]), "+f"(d[OFF + 13]), "+f"(d[OFF + 14]), "+f"(d[OFF + 15]), "+f"(d[OFF + 16]), "+f"(d[OFF + 17]),
        "+f"(d[OFF + 18]), "+f"(d[OFF + 19]), "+f"(d[OFF + 20]), "+f"(d[OFF + 21]), "+f"(d[OFF + 22]), "+f"(d[OFF + 23]),
        "+f"(d[OFF + 24]), "+f"(d[OFF + 25]), "+f"(d[OFF + 26]), "+f"(d[OFF + 27]), "+f"(d[OFF + 28]), "+f"(d[OFF + 29]),
        "+f"(d[OFF + 30]), "+f"(d[OFF + 31])
      : "r"(a0), "r"(a1), "r"(a2), "r"(a3), "l"(desc_b), "r"(scale_d), "r"(meta));
}

template <int OFF, int NN>
__device__ __forceinline__ void wg_s64t1(float (&d)[NN], uint32_t a0, uint32_t a1, uint32_t a2, uint32_t a3,
                                       uint64_t desc_b, int scale_d, uint32_t meta) {
  asm volatile(
      "{\n.reg .pred p;\nsetp.ne.b32 p, %37, 0;\n"
      "wgmma.mma_async.sp.sync.aligned.m64n64k32.f32.bf16.bf16 "
      "{%0,%1,%2,%3,%4,%5,%6,%7,%8,%9,%10,%11,%12,%13,%14,%15,"
      "%16,%17,%18,%19,%20,%21,%22,%23,%24,%25,%26,%27,%28,%29,%30,%31}, "
      "{%32,%33,%34,%35}, %36, %38, 1, p, 1, 1, 1;\n}\n"
      : "+f"(d[OFF + 0]), "+f"(d[OFF + 1]), "+f"(d[OFF + 2]), "+f"(d[OFF + 3]), "+f"(d[OFF + 4]), "+f"(d[OFF + 5]),
        "+f"(d[OFF + 6]), "+f"(d[OFF + 7]), "+f"(d[OFF + 8]), "+f"(d[OFF + 9]), "+f"(d[OFF + 10]), "+f"(d[OFF + 11]),
        "+f"(d[OFF + 12]), "+f"(d[OFF + 13]), "+f"(d[OFF + 14]), "+f"(d[OFF + 15]), "+f"(d[OFF + 16]), "+f"(d[OFF + 17]),
        "+f"(d[OFF + 18]), "+f"(d[OFF + 19]), "+f"(d[OFF + 20]), "+f"(d[OFF + 21]), "+f"(d[OFF + 22]), "+f"(d[OFF + 23]),
        "+f"(d[OFF + 24]), "+f"(d[OFF + 25]), "+f"(d[OFF + 26]), "+f"(d[OFF + 27]), "+f"(d[OFF + 28]), "+f"(d[OFF + 29]),
        "+f"(d[OFF + 30]), "+f"(d[OFF + 31])
      : "r"(a0), "r"(a1), "r"(a2), "r"(a3), "l"(desc_b), "r"(scale_d), "r"(meta));
}

template <int OFF, int NN>
__device__ __forceinline__ void wg_s64tz(float (&d)[NN], uint32_t a0, uint32_t a1, uint32_t a2, uint32_t a3,
                                       uint64_t desc_b, int scale_d, uint32_t meta) {
  asm volatile(
      "{\n.reg .pred p;\nsetp.ne.b32 p, %37, 0;\n"
      "wgmma.mma_async.sp.sync.aligned.m64n64k32.f32.bf16.bf16 "
      "{%0,%1,%2,%3,%4,%5,%6,%7,%8,%9,%10,%11,%12,%13,%14,%15,"
      "%16,%17,%18,%19,%20,%21,%22,%23,%24,%25,%26,%27,%28,%29,%30,%31}, "
      "{%32,%33,%34,%35}, %36, %38, 0, p, 1, 1, 1;\n}\n"
      : "=f"(d[OFF + 0]), "=f"(d[OFF + 1]), "=f"(d[OFF + 2]), "=f"(d[OFF + 3]), "=f"(d[OFF + 4]), "=f"(d[OFF + 5]),
        "=f"(d[OFF + 6]), "=f"(d[OFF + 7]), "=f"(d[OFF + 8]), "=f"(d[OFF + 9]), "=f"(d[OFF + 10]), "=f"(d[OFF + 11]),
        "=f"(d[OFF + 12]), "=f"(d[OFF + 13]), "=f"(d[OFF + 14]), "=f"(d[OFF + 15]), "=f"(d[OFF + 16]), "=f"(d[OFF + 17]),
        "=f"(d[OFF + 18]), "=f"(d[OFF + 19]), "=f"(d[OFF + 20]), "=f"(d[OFF + 21]), "=f"(d[OFF + 22]), "=f"(d[OFF + 23]),
        "=f"(d[OFF + 24]), "=f"(d[OFF + 25]), "=f"(d[OFF + 26]), "=f"(d[OFF + 27]), "=f"(d[OFF + 28]), "=f"(d[OFF + 29]),
        "=f"(d[OFF + 30]), "=f"(d[OFF + 31])
      : "r"(a0), "r"(a1), "r"(a2), "r"(a3), "l"(desc_b), "r"(scale_d), "r"(meta));
}

__device__ __forceinline__ int g2_inv(int ch) { return 32 * (ch >> 5) + 8 * ((ch >> 1) & 3) + 2 * ((ch >> 3) & 3) + (ch & 1); }
__host__ __device__ __forceinline__ uint32_t wimg_off(int n, int k) {
  return (uint32_t)(k >> 6) * kWChunk + (uint32_t)n * 128 + (uint32_t)((((k & 63) >> 3) ^ (n & 7)) << 4) + (k & 7) * 2;
}
__host__ __device__ constexpr int w2piece(int h, int c) { return c == 2 ? 2 + h : 4 * h + c; }
__device__ __forceinline__ uint32_t w2img_off(int n, int k) { return wimg_off(n % 96, k & 63) + w2piece(n >= 96, k >> 6) * (kWChunk / 2); }
__device__ __forceinline__ int qpix(int par, int t) {
  const int a = 2 * t + 13 * par - 6, b = t + 112 * par;
  return par ? min(a, b) : max(a, b);
}
__device__ __forceinline__ int woff(int par, int i, int r) {
  const int a = 99 * par + 6 - 8 * i;
  return par ? min(r, a) : max(r, a);
}

__device__ __forceinline__ void mma16816(float (&c)[4], uint32_t a0, uint32_t a1, uint32_t a2, uint32_t a3, uint32_t b0,
                                         uint32_t b1) {
  asm volatile(
      "mma.sync.aligned.m16n8k16.row.col.f32.bf16.bf16.f32 {%0,%1,%2,%3}, {%4,%5,%6,%7}, {%8,%9}, {%0,%1,%2,%3};"
      : "+f"(c[0]), "+f"(c[1]), "+f"(c[2]), "+f"(c[3])
      : "r"(a0), "r"(a1), "r"(a2), "r"(a3), "r"(b0), "r"(b1));
}

__device__ __forceinline__ void fold_w1(const int u, const __nv_bfloat16* __restrict__ wqkv, uint8_t* wimg) {
  const int g = (threadIdx.x >> 2) & 7, l = threadIdx.x & 3;
  const int m0 = (u / 12) * 16, s = u % 12;
  uint4 A[12], B[12];
  const __nv_bfloat16* arow = wqkv + (m0 + 4 * (g >> 1) + (g & 1)) * 576 + 192 + 8 * l;
  const __nv_bfloat16* brow = wqkv + (16 * s + 4 * (g >> 1) + (g & 1)) * 576 + 8 * l;
#pragma unroll
  for (int i = 0; i < 12; i++) {
    A[i] = ldg128_nc(arow + (i & 1) * 2 * 576 + 32 * (i >> 1));
    B[i] = ldg128_nc(brow + (i & 1) * 2 * 576 + 32 * (i >> 1));
  }
  sched_fence();
  uint8_t* dst = wimg + wimg_off(m0 + g, 16 * s + 4 * l);
  float acc[4][4];
#pragma unroll
  for (int j = 0; j < 16; j++) acc[j >> 2][j & 3] = 0.f;
#pragma unroll
  for (int i = 0; i < 6; i++) {
    const uint4 &a0 = A[2 * i], &a1 = A[2 * i + 1];
#pragma unroll
    for (int nb = 0; nb < 2; nb++) {
      mma16816(acc[2 * nb], a0.x, a1.x, a0.y, a1.y, B[2 * i + nb].x, B[2 * i + nb].y);
      mma16816(acc[2 * nb + 1], a0.z, a1.z, a0.w, a1.w, B[2 * i + nb].z, B[2 * i + nb].w);
    }
  }
#pragma unroll
  for (int j = 0; j < 2; j++) {
    const uint2 v = make_uint2(pack_bf16((acc[0][2 * j] + acc[1][2 * j]) * kAlpha, (acc[0][2 * j + 1] + acc[1][2 * j + 1]) * kAlpha),
                               pack_bf16((acc[2][2 * j] + acc[3][2 * j]) * kAlpha, (acc[2][2 * j + 1] + acc[3][2 * j + 1]) * kAlpha));
    asm volatile("st.relaxed.gpu.global.v2.u32 [%0], {%1,%2};" ::"l"(dst + j * 1024), "r"(v.x), "r"(v.y) : "memory");
  }
}
__device__ __forceinline__ void fold_w2(const int u, const __nv_bfloat16* __restrict__ wqkv, const __nv_bfloat16* __restrict__ wo,
                                        uint8_t* wimg) {
  const int g = (threadIdx.x >> 2) & 7, l = threadIdx.x & 3;
  const int m0 = (u / 12) * 32, n0 = (u % 12) * 16;
  uint4 S[12];
  uint32_t L[96];
  const __nv_bfloat16* brow = wqkv + (n0 + 4 * (g >> 1) + (g & 1)) * 576 + 384 + 8 * l;
#pragma unroll
  for (int i = 0; i < 12; i++) S[i] = ldg128_nc(brow + (i & 1) * 2 * 576 + 32 * (i >> 1));
  const __nv_bfloat16* acol = wo + (8 * l) * 192 + m0 + 4 * g;
#pragma unroll
  for (int c = 0; c < 48; c++)
    asm volatile("ld.global.nc.v2.u32 {%0,%1}, [%2];" : "=r"(L[2 * c]), "=r"(L[2 * c + 1]) : "l"(acol + (32 * (c >> 3) + (c & 7)) * 192));
  const uint32_t off = w2_offset();
  sched_fence();
  uint8_t* img = wimg + off;
  float acc[4][4];
#pragma unroll
  for (int j = 0; j < 16; j++) acc[j >> 2][j & 3] = 0.f;
#pragma unroll
  for (int i = 0; i < 6; i++) {
#pragma unroll
    for (int h = 0; h < 2; h++) {
      const uint4 &s0 = S[2 * i], &s1 = S[2 * i + 1];
#pragma unroll
      for (int mt = 0; mt < 2; mt++) {
        const uint32_t* a = L + 16 * i + 8 * h + mt;
        const uint32_t a0 = __byte_perm(a[0], a[2], 0x5410), a1 = __byte_perm(a[0], a[2], 0x7632);
        const uint32_t a2 = __byte_perm(a[4], a[6], 0x5410), a3 = __byte_perm(a[4], a[6], 0x7632);
        mma16816(acc[2 * mt], a0, a1, a2, a3, h ? s0.z : s0.x, h ? s0.w : s0.y);
        mma16816(acc[2 * mt + 1], a0, a1, a2, a3, h ? s1.z : s1.x, h ? s1.w : s1.y);
      }
    }
  }
#pragma unroll
  for (int j = 0; j < 4; j++) {
    const float(&c0)[4] = acc[j & 2];
    const float(&c1)[4] = acc[(j & 2) + 1];
    asm volatile("st.relaxed.gpu.global.v2.u32 [%0], {%1,%2};" ::"l"(img + w2img_off(g2_inv(m0 + 4 * g + j), n0 + 4 * l)),
                 "r"(pack_bf16(c0[2 * (j & 1)], c0[2 * (j & 1) + 1])), "r"(pack_bf16(c1[2 * (j & 1)], c1[2 * (j & 1) + 1])) : "memory");
  }
}

__global__ void __launch_bounds__(256) fold_kernel(const __nv_bfloat16* __restrict__ wqkv,
                                                   const __nv_bfloat16* __restrict__ wo, uint8_t* wimg) {
  const int u = blockIdx.x * 8 + (threadIdx.x >> 5);
  if (u < 144) fold_w1(u, wqkv, wimg);
  else fold_w2(u - 144, wqkv, wo, wimg);
}

struct TileCoord { int pr, pc, I, J, up, kind; };
struct TileTable { uint16_t e[kCtas * 6], g[5][8][2], b[5][2][4]; };
inline void make_tiles(TileTable& tt) {
  for (int tile = 0; tile < kCtas * 6; tile++) {
    const int b = tile / 6, k = tile - 6 * b;
    const int p = b < 128 ? (tile - 672) >> 1 : b - 80;
    const int strip = b < 112 ? b >> 1 : b >= 128 && k >= 2 ? (b & 1) * 27 + (b & 2) * 14 : p + (p < 26 ? 1 : 3);
    const int pr = strip >= 28, J = (strip - pr * 28) >> 1, pc = strip & 1, up = b < 112 ? b & 1 : pr;
    const int first = b < 112 ? 8 - 2 * pr - up : 13 * pr, step = b < 112 ? k : k & 1;
    const int I = up ? first - step : first + step;
    const int kind = b < 112 ? (J == 13 * pc ? 1 + pc : 0) : I == 13 * pr ? 3 + pr : 0;
    tt.e[tile] = (uint16_t)(I | J << 4 | pr << 8 | pc << 9 | up << 10 | kind << 11);
  }
  for (int kind = 0; kind < 5; kind++) {
    const bool col = kind == 1 || kind == 2;
    auto off = [kind](int t) { return kind == 0 ? 2 * t : kind & 1 ? t + (t == 7) : t + (t > 0); };
    for (int j = 0; j < 8; j++) {
      const int w = j >> 1, h = j & 1;
      tt.g[kind][j][0] = (uint16_t)(col ? 3 * off(w + 4 * h) : 3 * (kW * off(2 * w) + 8 * h));
      tt.g[kind][j][1] = (uint16_t)(128 * (col ? 5 : 5 + off(2 * w + 1) - off(2 * w)));
    }
    for (int i = 0; i < 2; i++) {
      const int w = kind == 0 ? 0 : kind & 1 ? 3 * i : 1 - i;
      tt.b[kind][i][0] = tt.g[kind][2 * w][0];
      tt.b[kind][i][1] = (uint16_t)(128 * (kind == 0 ? 0 : (col ? 3 : 1) + i));
      tt.b[kind][i][2] = (uint16_t)(2048 * w);
      tt.b[kind][i][3] = 0;
    }
  }
}
__device__ __forceinline__ int num_tiles() { return blockIdx.x < 128 ? 6 : 4; }
__device__ __forceinline__ TileCoord decode_tile(const TileTable& tt, int tile) {
  const uint32_t e = tt.e[tile];
  return TileCoord{(int)(e >> 8) & 1, (int)(e >> 9) & 1, (int)e & 15, (int)(e >> 4) & 15, (int)(e >> 10) & 1, (int)(e >> 11)};
}
__device__ __forceinline__ int halo_r0(const TileCoord& t) { return 8 * t.I + 6 * t.pr - 6; }
__device__ __forceinline__ int halo_c0(const TileCoord& t) { return min(max(8 * t.J + 6 * t.pc - 6, -3), 102); }

__device__ __forceinline__ uint32_t bar_full(uint32_t bars, int wg, int c) { return bars + (wg * 3 + c) * 8; }
__device__ __forceinline__ uint32_t bar_w1c(uint32_t bars, int c) { return bars + (6 + c) * 8; }
__device__ __forceinline__ uint32_t bar_w2(uint32_t bars) { return bars + 9 * 8; }
__device__ __forceinline__ uint32_t bar_x(uint32_t bars, int j, int c) { return bars + (j == 0 ? 10 : c ? 17 + c : 11) * 8; }
__device__ __forceinline__ uint32_t bar_w1q(uint32_t bars) { return bars + 12 * 8; }
__device__ __forceinline__ uint32_t bar_xf(uint32_t bars) { return bars + 13 * 8; }
__device__ __forceinline__ uint32_t bar_w2m(uint32_t bars) { return bars + 14 * 8; }
__device__ __forceinline__ uint32_t bar_redo(uint32_t bars) { return bars + 15 * 8; }
__device__ __forceinline__ uint32_t bar_wok(uint32_t bars) { return bars + 16 * 8; }
__device__ __forceinline__ uint32_t bar_go(uint32_t bars) { return bars + 17 * 8; }
__device__ __forceinline__ uint32_t bar_raw(uint32_t bars, int j = 0) { return bars + (21 + j) * 8; }
__device__ __forceinline__ uint32_t bar_w2a(uint32_t bars) { return bars + 20 * 8; }
constexpr int kNumBars = 22;

__device__ __forceinline__ uint64_t wdesc(uint64_t d0, int s) { return d0 + (((s >> 2) * kWChunk + (s & 3) * 32) >> 4); }

__device__ __forceinline__ uint32_t x_chunk(int k, int c) { return kXOff + (k == 0 ? kWChunk : 0) + (k & 1 ? 2 - c : c) * 8192; }
__device__ __forceinline__ uint32_t out_slot(int k, int nt) { return k + 1 < nt ? kW2Off + (~k & 1) * 2 * kWChunk : kW1Off + kWChunk; }
template <int I0, int I1>
__device__ __forceinline__ void store_rows(bool on, __nv_bfloat16* pA, __nv_bfloat16* pB, const uint32_t (&a)[24], const uint32_t (&b)[24]) {
#pragma unroll
  for (int i = 2 * I0; i < 2 * I1; i++) {
    const uint32_t* v = (i & 1 ? b : a) + 4 * (i >> 1);
    asm volatile("{\n.reg .pred p;\nsetp.ne.u32 p, %5, 0;\n@p st.global.v4.u32 [%0], {%1,%2,%3,%4};\n}\n" ::"l"((i & 1 ? pB : pA) + 32 * (i >> 1)),
                 "r"(v[0]), "r"(v[1]), "r"(v[2]), "r"(v[3]), "r"((uint32_t)on) : "memory");
  }
}
template <int I0, int I1>
__device__ __forceinline__ void stage_out(uint32_t sts, int wg, const uint32_t (&a)[24], const uint32_t (&b)[24]) {
  const uint32_t e = sts, o = sts ^ 64;
  const uint32_t ad[4] = {wg ? o + 1024 : e, wg ? e + 2048 : o, wg ? e : o + 1024, wg ? o : e + 2048};
#pragma unroll
  for (int i = I0; i < I1; i++) {
    const uint32_t* v = (i < 6 ? a : b) + 4 * (i % 6);
    asm volatile("st.shared.v4.u32 [%0], {%1,%2,%3,%4};" ::"r"(ad[i % 6 / 3 * 2 + (i % 3 == 1)] + (i % 3 == 2) * 1024 + (i / 6) * 12288),
                 "r"(v[0]), "r"(v[1]), "r"(v[2]), "r"(v[3]) : "memory");
  }
}
__device__ __forceinline__ uint32_t now_ns() {
  uint32_t t;
  asm volatile("mov.u32 %0, %globaltimer_lo;" : "=r"(t)::"memory");
  return t;
}
__device__ __forceinline__ void wait_clock(uint32_t t_start, uint32_t t) {
  while (now_ns() - t_start < t) { }
}
#define NAT_PRED(f, m) ".reg .pred p;\n.reg .b32 t;\nand.b32 t, " f ", " m ";\nsetp.ne.u32 p, t, 0;\n"
constexpr uint32_t kHiV = 1, kHiU = 8, kColB = 0x20, kInV = 0x100, kInU = 0x1000, kColA = 0x10000;
template <uint32_t M>
__device__ __forceinline__ float pick(const float* a, const float* b, uint32_t f) {
  float d;
  asm("{\n" NAT_PRED("%5", "%6") "add.f32 %0, %1, %2;\n@p add.f32 %0, %3, %4;\n}\n"
      : "=&f"(d) : "f"(a[0]), "f"(a[2]), "f"(b[0]), "f"(b[2]), "r"(f), "n"(M));
  return d;
}
template <uint32_t M>
__device__ __forceinline__ float sel(float a, float b, uint32_t f) {
  float d;
  asm("{\n" NAT_PRED("%3", "%4") "selp.f32 %0, %1, %2, p;\n}\n" : "=f"(d) : "f"(a), "f"(b), "r"(f), "n"(M));
  return d;
}
template <uint32_t M>
__device__ __forceinline__ void max_if(float& m, float v, uint32_t f) {
  asm("{\n" NAT_PRED("%2", "%3") "@p max.f32 %0, %0, %1;\n}\n" : "+f"(m) : "f"(v), "r"(f), "n"(M));
}
template <uint32_t M>
__device__ __forceinline__ void add_if(float& m, float v, uint32_t f) {
  asm("{\n" NAT_PRED("%2", "%3") "@p add.f32 %0, %0, %1;\n}\n" : "+f"(m) : "f"(v), "r"(f), "n"(M));
}
__device__ __forceinline__ void pick_v(const float* a, float* v, uint32_t f) {
  v[0] = pick<kHiV>(a, a + 16, f), v[1] = pick<kHiV>(a + 1, a + 17, f);
  v[2] = pick<kHiV * 2>(a + 4, a + 20, f), v[3] = pick<kHiV * 2>(a + 5, a + 21, f);
  v[4] = pick<kHiV * 4>(a + 8, a + 24, f), v[5] = pick<kHiV * 4>(a + 9, a + 25, f);
  v[6] = a[12] + a[14], v[7] = a[13] + a[15];
}
__device__ __forceinline__ void pick_u(const float* a, float* v, uint32_t f) {
#pragma unroll
  for (int c = 0; c < 3; c++) v[2 * c] = pick<kHiU>(a + 4 * c, a + 4 * c + 12, f), v[2 * c + 1] = pick<kHiU * 2>(a + 4 * c + 1, a + 4 * c + 13, f);
}
__device__ __forceinline__ uint32_t sign_bytes(uint32_t v, uint32_t sel) {
  uint32_t d;
  asm("prmt.b32 %0, %1, %1, %2;" : "=r"(d) : "r"(v), "r"(sel));
  return d;
}
__device__ __forceinline__ float own_max(const float (&v)[14], uint32_t f) {
  float m = sel<kInV>(fmaxf(v[0], v[1]), -INFINITY, f), m2 = sel<kInV * 2>(fmaxf(v[2], v[3]), -INFINITY, f);
  max_if<kInV * 4>(m, fmaxf(v[4], v[5]), f);
  max_if<kInV * 8>(m2, fmaxf(v[6], v[7]), f);
  max_if<kInU>(m, fmaxf(fmaxf(v[8], v[10]), v[12]), f);
  max_if<kInU * 2>(m2, fmaxf(fmaxf(v[9], v[11]), v[13]), f);
  return fmaxf(m, m2);
}
__device__ __forceinline__ float quad_max(float m) {
  const float a = __shfl_xor_sync(0xffffffffu, m, 1), b = __shfl_xor_sync(0xffffffffu, m, 2), c = __shfl_xor_sync(0xffffffffu, m, 3);
  return fmaxf(fmaxf(m, a), fmaxf(b, c));
}
__device__ __forceinline__ float row_rcp(const float (&v)[14], uint32_t f) {
  float s = sel<kInV>(v[0] + v[1], 0.f, f), s2 = sel<kInV * 2>(v[2] + v[3], 0.f, f);
  add_if<kInV * 4>(s, v[4] + v[5], f);
  add_if<kInV * 8>(s2, v[6] + v[7], f);
  add_if<kInU>(s, v[8] + v[10] + v[12], f);
  add_if<kInU * 2>(s2, v[9] + v[11] + v[13], f);
  s += s2;
  const float a = __shfl_xor_sync(0xffffffffu, s, 1), b = __shfl_xor_sync(0xffffffffu, s, 2), c = __shfl_xor_sync(0xffffffffu, s, 3);
  return rcp_approx((s + a) + (b + c));
}
__device__ __forceinline__ void route(const float (&v)[14], float s, const uint32_t (&rt)[9], uint32_t (&p)[14]) {
#pragma unroll
  for (int i = 0; i < 7; i++) {
    const uint32_t u = pack_bf16(v[2 * i] * s, v[2 * i + 1] * s);
    if (i < 4) p[i] = u & rt[i];
    if (i < 3) p[i + 4] = u & rt[i + 4];
    if (i >= 4) {
      p[i + 3] = u & rt[7];
      p[i + 6] = u & rt[8];
    }
  }
}

template <int C, int T0 = 0, int T1 = 7>
__device__ __forceinline__ void pv_chunk(float (&z)[32], const uint32_t (&pa)[14], const uint32_t (&pb)[14],
                                         const uint32_t (&meta)[4], uint64_t dV) {
#pragma unroll
  for (int t = T0; t < T1; t++) {
    if (t & 1)
      wg_s64t1<0, 32>(z, pa[2 * t], pb[2 * t], pa[2 * t + 1], pb[2 * t + 1], dV + ((2 * C * kChunkBytes + t * 2048) >> 4), 1,
                      meta[t >> 1]);
    else if (t > 0)
      wg_s64t<0, 32>(z, pa[2 * t], pb[2 * t], pa[2 * t + 1], pb[2 * t + 1], dV + ((2 * C * kChunkBytes + t * 2048) >> 4), 1,
                     meta[t >> 1]);
    else
      wg_s64tz<0, 32>(z, pa[0], pb[0], pa[1], pb[1], dV + ((2 * C * kChunkBytes) >> 4), 0, meta[0]);
  }
}
template <int C>
__device__ __forceinline__ void pack_z(const float (&z)[32], uint32_t (&za)[24], uint32_t (&zb)[24]) {
#pragma unroll
  for (int j = 0; j < 8; j++) {
    za[8 * C + j] = pack_bf16(z[4 * j], z[4 * j + 1]);
    zb[8 * C + j] = pack_bf16(z[4 * j + 2], z[4 * j + 3]);
  }
}

template <int H>
__device__ __forceinline__ void pack_out(const float (&ac)[48], uint32_t (&oa)[24], uint32_t (&ob)[24]) {
#pragma unroll
  for (int j = 0; j < 12; j++) {
    oa[12 * H + j] = pack_bf16(ac[4 * j], ac[4 * j + 1]);
    ob[12 * H + j] = pack_bf16(ac[4 * j + 2], ac[4 * j + 3]);
  }
}
struct Maps { CUtensorMap v6, v2, v14, u8, px[8], wv, wo; };
__device__ __forceinline__ void tma_prefetch_5d(const CUtensorMap* map, int c0, int c1, int c2, int c3, int c4) {
  asm volatile("cp.async.bulk.prefetch.tensor.5d.L2.global.tile [%0, {%1, %2, %3, %4, %5}];" ::"l"((uint64_t)map), "r"(c0), "r"(c1),
               "r"(c2), "r"(c3), "r"(c4) : "memory");
}
__device__ __forceinline__ int first_line(const TileCoord tc) { return 3 * (qpix(tc.pr, 8 * tc.I) * kW + qpix(tc.pc, 8 * tc.J)); }
__device__ __forceinline__ void load_px(const Maps& tm, const TileTable& tt, uint32_t dst, uint32_t bar, int line, int kind) {
#pragma unroll
  for (int i = 0; i < 2; i++) {
    if (i == 0 || kind != 0) {
      const CUtensorMap* map = (const CUtensorMap*)((const char*)tm.px + tt.b[kind][i][1]);
      if (bar) tma_load_5d(dst + tt.b[kind][i][2], map, bar, 0, 0, 0, 0, line + tt.b[kind][i][0]);
      else tma_prefetch_5d(map, 0, 0, 0, 0, line + tt.b[kind][i][0]);
    }
  }
}
__device__ __forceinline__ void store_px(const Maps& tm, const TileTable& tt, uint32_t buf, int line, int kind) {
#pragma unroll
  for (int i = 0; i < 8; i++) {
    const int j = 2 * (i & 3) + (i >> 2);
    asm volatile("cp.async.bulk.tensor.5d.global.shared::cta.tile.bulk_group [%0, {%2, %2, %2, %2, %3}], [%1];" ::"l"(
                     (uint64_t)tm.px + tt.g[kind][j][1]), "r"(buf + i * 3072), "r"(0), "r"(line + tt.g[kind][j][0]) : "memory");
  }
  asm volatile("cp.async.bulk.commit_group;" ::: "memory");
}
__device__ __noinline__ bool refetch(uint32_t base, const uint8_t* src, bool gap) {
  constexpr uint32_t bars = 1024 + kBarOff, cnt = bars + 192;
#pragma unroll 1
  for (uint32_t o = 0; o < kWBytes && !gap; o += 2048) {
    uint32_t mx = 0;
#pragma unroll
    for (int i = 0; i < 4; i++) {
      uint4 v;
      asm volatile("ld.shared.v4.u32 {%0,%1,%2,%3}, [%4];" : "=r"(v.x), "=r"(v.y), "=r"(v.z), "=r"(v.w)
                   : "r"(base + o + i * 512 + (threadIdx.x & 31) * 16));
      mx = __vimax3_u32(__vimax3_u32(mx, v.x, v.y), v.z, v.w);
    }
    gap = __any_sync(0xffffffffu, mx == kEmpty);
  }
  uint32_t n;
  asm volatile("ld.shared.u32 %0, [%1];" : "=r"(n) : "r"(cnt) : "memory");
  if (!gap || __any_sync(0xffffffffu, n > (1u << 12))) return false;
  asm volatile("bar.sync 15, 128;" ::: "memory");
  if (threadIdx.x == 0) {
    asm volatile("st.shared.u32 [%0], %1;" ::"r"(cnt), "r"(n + 1) : "memory");
    mbar_arrive_expect_tx(bar_redo(bars), kWBytes);
    bulk_load(base, src, kWBytes, bar_redo(bars));
  }
  __syncwarp();
  mbar_wait(bar_redo(bars), n & 1);
  return true;
}
template <int S0, int S1, int Z>
__device__ __forceinline__ void g2_steps(float (&ac)[48], const uint32_t (&za)[24], const uint32_t (&zb)[24], uint64_t d) {
#pragma unroll
  for (int s = S0; s < S1; s++) {
    const uint64_t ds = d + (((s >> 2 & 1) * (kWChunk / 2) + (s & 3) * 32) >> 4);
    if (s == Z) wg_d96z<0, 48>(ac, za[2 * s], zb[2 * s], za[2 * s + 1], zb[2 * s + 1], ds, 0);
    else wg_d96<0, 48>(ac, za[2 * s], zb[2 * s], za[2 * s + 1], zb[2 * s + 1], ds, 1);
  }
}

__device__ __forceinline__ void consumer(const int wg, __nv_bfloat16* out, const uint8_t* wimg, const uint32_t sbase,
                                         const uint32_t zero, const Maps& tm, const TileTable& tt) {
  const int tid = threadIdx.x & 127;
  const int w = __shfl_sync(0xffffffffu, tid >> 5, 0), lane = tid & 31;
  const uint64_t dK = make_desc(sbase, 16, 1024);
  const uint64_t dV = make_desc(sbase, kChunkBytes, 512, 2);
  const uint64_t dW1 = make_desc(sbase + kW1Off, 16, 1024);
  const uint64_t dX0 = make_desc(sbase + kW2Off + wg * 2 * kWChunk, 16, 1024), dY0 = make_desc(sbase + kW2Off + (1 - wg) * 2 * kWChunk, 16, 1024);
  const uint64_t dX2 = make_desc(sbase + kXOff + wg * (kWChunk / 2), 16, 1024), dY2 = make_desc(sbase + kXOff + (1 - wg) * (kWChunk / 2), 16, 1024);
  const uint32_t bars = sbase + kBarOff;
  int tile0 = blockIdx.x * kTilesPerCta;
  asm volatile("" : "+r"(tile0));
  const int nt = num_tiles();

  uint32_t pix = 0, geo[6] = {};
  const int l = lane & 3;
#pragma unroll 1
  for (int j = 4; j >= 0; j -= 2) {
    const TileCoord tc = decode_tile(tt, tile0 + wg + j);
    const bool col = tc.kind == 1 || tc.kind == 2;
    const int g = col ? lane >> 2 : 2 * w + ((lane >> 2) & 1), qc = col ? w : lane >> 3;
    const uint32_t pr = qpix(tc.pr, 8 * tc.I + g) * kW;
    if (j == nt - 2) pix = (pr + qpix(tc.pc, 8 * tc.J + qc)) | (pr + qpix(tc.pc, 8 * tc.J + qc + 4)) << 16;
    const int d = 8 * tc.J + 6 * tc.pc - 6 - halo_c0(tc);
    const int ro = woff(tc.pr, tc.I, g), coA = woff(tc.pc, tc.J, qc) + d, coB = woff(tc.pc, tc.J, qc + 4) + d - 3;
#pragma unroll
    for (int i = 5; i >= 2; i--) geo[i] = geo[i - 2];
    const uint32_t lr = 0x1FCu << ro;
    const uint32_t lv = lr >> (2 + (l >> 1)), lu = lr >> (2 * l + 2 * tc.up);
    const uint32_t t = __byte_perm(lv, lu, wg ? 0x4501 : 0x5410);
    geo[0] = (((t & 0x15u) | (lv & 0x40u)) * 0x02082080u & 0x80808080u) | (((t >> 8) & 0x15u) * 0x01041040u & 0x40404040u) |
             (__byte_perm(t << 5, t << 4, 0x7362) & 0x20202020u) | (nt == 6);
    const int dr = (ro - 1) & 7;
    const uint32_t hiv = (((1u << ((ro - (l >> 1) + 1) >> 1)) - 1u) ^ (wg ? 7u : 0u)) & 7u, hiu = (t >> 24) & 3u;
    const uint32_t ca = (1u << coA) - 1u;
    geo[1] = hiv * kHiV | hiu * kHiU | ((((1u << coB) - 1u) >> (2 * (l & 1))) & 3u) * kColB |
             (15u & ~((uint32_t)((dr & 1) == (l >> 1)) << (dr >> 1))) * kInV | ((t >> 16 | t >> 24) & 3u) * kInU | ca * kColA |
             (ca >> ((0x49 >> (2 * l)) & 3) & 1u) << 19 | (uint32_t)(l == 3) << 20 | (0x55u & ((1u << (2 * coB)) - 1u)) << 24;
  }
  keep_regs(geo);
  const int so = (lane >> 3) | (lane & 4);
  uint32_t sts = sbase + w * 3072 + so * 128 + (((lane & 3) ^ so) << 4);
  __nv_bfloat16* poA = out + 8 * l + (pix & 0xFFFFu) * kC + 96 * wg;
  __nv_bfloat16* poB = out + 8 * l + (pix >> 16) * kC + 96 * wg;
  asm volatile("" : "+l"(poA), "+l"(poB), "+r"(sts));
  uint32_t oa[24], ob[24];
#pragma unroll
  for (int j = 0; j < 24; j++) oa[j] = ob[j] = 0u;
  keep_regs(oa);
  keep_regs(ob);
  PROF(wg, 0);
  if (threadIdx.x == 0) GT(1);

  for (int k = wg; k < nt; k += 2) {
    const uint32_t ph = (k >> 1) & 1;
    const int it = k >> 1;
    uint32_t qa[24], qb[24], hok[3];
    uint32_t fl = geo[1];
    {
      float acc[96];
      const uint32_t xp = (k + (k > 0)) & 1;
      const uint32_t xok = mbar_test(bar_x(bars, k > 0, 0), xp);
      if (k > 0) nb_sync(1 + (1 - wg));
#pragma unroll
      for (int s = 0; s < 12; s++) {
        if (s == 0) mbar_wait_if(xok, bar_x(bars, k > 0, 0), xp);
        if (s == 0 && k < 2) PROF(wg, 1);
        if (s == 0) PROFS(2, wg, 2 + it * 12);
        if (s == 0 && w == 0 && k < 2) GT(20 + wg);
        if ((s & 3) == 0 && (k == 0 || s > 0)) {
          mbar_wait(k == 0 ? bar_w1c(bars, s >> 2) : bar_x(bars, 1, s >> 2), xp);
          PROFS(17, wg, 50 + (s >> 2));
        }
        if ((s & 3) == 0) wg_fence();
        const uint64_t dX = make_desc(sbase + x_chunk(k, s >> 2), 16, 1024) + 2 * (s & 3);
        if (s == 0) wg_m192z<0, 96>(acc, dX, dW1, 0);
        else wg_m192<0, 96>(acc, dX, wdesc(dW1, s), 1);
        if ((s & 3) == 3) wg_commit();
      }
      PROFS(13, wg, 13 + it * 12);
      if (NAT_MP > 2) {
        wg_wait<2>();
        if (k > 0) nb_arrive_p(0);
      }
      if (NAT_MP > 1) {
        wg_wait<1>();
        if (k > 0) nb_arrive_p(14);
      }
      wg_wait<0>();
      if (k > 0) nb_arrive_p(6);
      fence_regs(acc);
      PROFS(3, wg, 3 + it * 12);
#pragma unroll
      for (int j = 0; j < 24; j++) {
        qa[j] = pack_bf16(acc[4 * j], acc[4 * j + 1]);
        qb[j] = pack_bf16(acc[4 * j + 2], acc[4 * j + 3]);
      }
      keep_regs(qa);
      keep_regs(qb);
      sched_fence();
      if (k >= 2) {
        const uint32_t dst = sts + out_slot(k, nt);
        nb_sync(11);
        stage_out<0, 6>(dst, wg, oa, ob);
        nb_sync(12);
        stage_out<6, 12>(dst, wg, oa, ob);
      }
#pragma unroll
      for (int c = 0; c < 3; c++) hok[c] = mbar_test(bar_full(bars, wg, c), ph);
      if (k >= 2) {
        fence_proxy_async();
        nb_arrive_p(10);
      }
    }

    float aE[52], aO[24], bO[52], bE[28];
    const uint32_t mq = 0xEEEE4444u | zero;
    PROFS(4, wg, 4 + it * 12);

    mbar_wait_if(hok[0], bar_full(bars, wg, 0), ph);
    PROFS(14, wg, 40 + it * 3);
    if (w == 0 && k < 2) GT(22 + wg);
    if (k > 0) nb_sync(3 + (1 - wg));
    wg_fence();
#pragma unroll
    for (int ks = 0; ks < 6; ks++) {
      if (ks == NAT_P1) {
        mbar_wait_if(hok[1], bar_full(bars, wg, 1), ph);
        PROFS(14, wg, 41 + it * 3);
        wg_fence();
      }
      if (ks == NAT_P2) {
        mbar_wait_if(hok[2], bar_full(bars, wg, 2), ph);
        PROFS(14, wg, 42 + it * 3);
        wg_fence();
      }
      const uint64_t d = dK + ((ks * kChunkBytes) >> 4);
      if (ks == 0) wg_s104z<0, 52>(aE, qa[0], qa[1], qa[2], qa[3], d, 0, mq);
      else wg_s104<0, 52>(aE, qa[4 * ks], qa[4 * ks + 1], qa[4 * ks + 2], qa[4 * ks + 3], d, 1, mq);
    }
    wg_commit();
    wg_s48z<0, 24>(aO, qa[0], qa[1], qa[2], qa[3], dK + ((7 * 1024 + 64) >> 4), 0, mq);
#pragma unroll
    for (int ks = 1; ks < 6; ks++)
      wg_s48<0, 24>(aO, qa[4 * ks], qa[4 * ks + 1], qa[4 * ks + 2], qa[4 * ks + 3], dK + ((ks * kChunkBytes + 7 * 1024 + 64) >> 4), 1, mq);
    wg_commit();
    wg_s56z<0, 28>(bE, qb[0], qb[1], qb[2], qb[3], dK, 0, mq);
#pragma unroll
    for (int ks = 1; ks < 6; ks++) wg_s56<0, 28>(bE, qb[4 * ks], qb[4 * ks + 1], qb[4 * ks + 2], qb[4 * ks + 3], dK + ((ks * kChunkBytes) >> 4), 1, mq);
    wg_commit();
    wg_wait<2>();
    fence_regs(aE);
    PROFS(5, wg, 5 + it * 12);

    uint32_t pa[14], pb[14], meta[4];
    {
      float vA[14], vB[14];
      pick_v(aE, vA, fl);
      pick_u(aE + 28, vA + 8, fl);
      fence_regs(vA);
      if (k == 0) {
        if (__builtin_expect(__any_sync(0xffffffffu, vA[6] != vA[6]), 0)) {
          wg_wait<0>();
          fence_regs(aO);
          fence_regs(bE);
          if (refetch(sbase + kW1Off, wimg, false)) {
#pragma unroll
            for (int j = 0; j < 24; j++) oa[j] = ob[j] = 0u;
            k -= 2;
            continue;
          }
        }
        if (elect_one()) mbar_arrive(bar_xf(bars));
      }
      wg_fence();
      wg_s104z<0, 52>(bO, qb[0], qb[1], qb[2], qb[3], dK + 4, 0, mq);
#pragma unroll
      for (int ks = 1; ks < 6; ks++)
        wg_s104<0, 52>(bO, qb[4 * ks], qb[4 * ks + 1], qb[4 * ks + 2], qb[4 * ks + 3], dK + ((ks * kChunkBytes + 64) >> 4), 1, mq);
      wg_commit();
      if (k + 1 < nt) nb_arrive(1 + wg);
      uint32_t rt[9];
#pragma unroll
      for (int i = 0; i < 7; i++) rt[i] = sign_bytes(geo[0] << (i >> 2), 0x8888u + 0x1111u * (i & 3));
      rt[7] = sign_bytes(geo[0] << 2, 0x9988u);
      rt[8] = sign_bytes(geo[0] << 2, 0xBBAAu);
      keep_regs(rt);
      pa[13] = pb[13] = 0u;
      wg_wait<2>();
      keep_regs(qa);
      fence_regs(aO);
      float oA[6], eB[8];
      pick_u(aO, oA, fl);
      wg_wait<1>();
      fence_regs(bE);
      pick_v(bE, eB, fl);
      vA[8] = sel<kColA>(oA[0], vA[8], fl), vA[9] = sel<kColA>(oA[1], vA[9], fl);
      vA[10] = sel<kColA * 2>(oA[2], vA[10], fl), vA[11] = sel<kColA * 2>(oA[3], vA[11], fl);
      vA[12] = sel<kColA * 4>(oA[4], vA[12], fl), vA[13] = sel<kColA * 4>(oA[5], vA[13], fl);
      {
        const float m1 = __uint_as_float(0x88DD88DDu), m0 = __uint_as_float(0x88DDDD88u);
        meta[0] = 0xDD88DD88u ^ __byte_perm(fl, 0u, 0x3344);
        meta[1] = __float_as_uint(sel<kColA * 16>(sel<kColA>(m1, m0, fl), __uint_as_float(meta[0]), fl));
        meta[2] = __float_as_uint(sel<kColA * 8>(m1, m0, fl));
        meta[3] = __float_as_uint(sel<kColA * 4>(m1, m0, fl));
        keep_regs(meta);
      }
      float mA = own_max(vA, fl);
      fl |= __float_as_uint(eB[7]) & zero;
      fence_regs(eB);
      fence_regs(vA);
      asm volatile("" : "+f"(mA), "+r"(fl));
      sched_fence();
      wg_wait<0>();
      sched_fence();
      keep_regs(qb);
      fence_regs(bO);
      PROFS(6, wg, 6 + it * 12);
      if (w == 0) GT(24 + k);
      mA = quad_max(mA);
#pragma unroll
      for (int i = 0; i < 14; i++) vA[i] = ex2(vA[i] - mA);
      pick_v(bO, vB, fl);
      pick_u(bO + 28, vB + 8, fl);
#pragma unroll
      for (int i = 0; i < 8; i += 2) vB[i] = sel<kColB>(vB[i], eB[i], fl), vB[i + 1] = sel<kColB * 2>(vB[i + 1], eB[i + 1], fl);
      float mB = quad_max(own_max(vB, fl));
      if (NAT_SB) {
        fence_regs(vA);
        fence_regs(vB);
        asm volatile("" : "+f"(mB));
        sched_fence();
      }
      PROFS(7, wg, 7 + it * 12);
#pragma unroll
      for (int i = 0; i < 14; i++) vB[i] = ex2(vB[i] - mB);
      route(vA, row_rcp(vA, fl), rt, pa);
      route(vB, row_rcp(vB, fl), rt, pb);
    }
    PROFS(8, wg, 8 + it * 12);
    if (k == NAT_PK) PROFS(18, wg, 53);
    sched_fence();

    float ac0[48], ac1[48];
    {
      float z0[32], z1[32], z2[32];
      uint32_t za[24], zb[24];
      wg_fence();
      pv_chunk<0>(z0, pa, pb, meta, dV);
      wg_commit();
      pv_chunk<1>(z1, pa, pb, meta, dV);
      wg_commit();
      wg_wait<1>();
      if (k == NAT_PK) PROFS(18, wg, 54);
      if (k + 1 < nt) nb_arrive_p(7);
      pv_chunk<2, 0, 3>(z2, pa, pb, meta, dV);
      wg_commit();
      sched_fence();
      fence_regs(z0);
      pack_z<0>(z0, za, zb);
      sched_fence();
      wg_fence();
      pv_chunk<2, 3, 7>(z2, pa, pb, meta, dV);
      wg_commit();
      wg_wait<2>();
      if (k == NAT_PK) PROFS(19, wg, 55);
      if (k + 1 < nt) nb_arrive_p(8);
      if (k < 2) mbar_wait(k == 1 ? bar_wok(bars) : bar_w2a(bars), 0);
      wg_fence();
      g2_steps<0, 3, 0>(ac0, za, zb, dX0);
      wg_commit();
      sched_fence();
      fence_regs(z1);
      pack_z<1>(z1, za, zb);
      sched_fence();
      wg_fence();
      g2_steps<3, 4, 0>(ac0, za, zb, dX0);
      wg_commit();
      g2_steps<4, 8, 0>(ac0, za, zb, dX0);
      wg_commit();
      wg_wait<3>();
      if (k + 1 < nt) nb_arrive_p(9);
      else nb_arrive(11);
      if (k == NAT_PK) PROFS(20, wg, 56);
      keep_regs(pa);
      keep_regs(pb);
      keep_regs(meta);
      sched_fence();
      const uint32_t mok = mbar_test(bar_w2m(bars), k + 1 < nt ? k & 1 : ~k & 1);
      const uint32_t wp = k < 2 ? 0 : k + 1 < nt ? ~k & 1 : k & 1, wok = mbar_test(bar_w2(bars), wp);
      fence_regs(z2);
      pack_z<2>(z2, za, zb);
      keep_regs(za);
      keep_regs(zb);
      sched_fence();
      PROFS(9, wg, 9 + it * 12);
      wg_wait<1>();
      if (k > 0 && k + 1 < nt) nb_arrive(11);
      mbar_wait_if(mok, bar_w2m(bars), k & 1);
      wg_fence();
      g2_steps<8, 12, 0>(ac0, za, zb, dX2);
      wg_commit();
      g2_steps<8, 12, 8>(ac1, za, zb, dY2);
      wg_commit();
      wg_wait<2>();
      if (k > 0 && k + 1 < nt) nb_arrive(12);
      mbar_wait_if(wok, bar_w2(bars), wp);
      wg_fence();
      g2_steps<0, 4, 8>(ac1, za, zb, dY0);
      wg_commit();
      wg_wait<2>();
      if (k + 2 < nt) nb_arrive_p(13);
      const bool direct = k + 2 >= nt;
      sched_fence();
      fence_regs(ac0);
      pack_out<0>(ac0, oa, ob);
      store_rows<0, NAT_D0>(direct, poA, poB, oa, ob);
      sched_fence();
      wg_fence();
      g2_steps<4, 8, 8>(ac1, za, zb, dY0);
      wg_commit();
      if (k + 1 < nt) nb_arrive(3 + wg);
      PROFS(10, wg, 10 + it * 12);
      wg_wait<2>();
      if (k + 2 < nt && (k > 0 || nt == 6)) nb_arrive_p(5);
      store_rows<NAT_D0, 3>(direct, poA, poB, oa, ob);
      __nv_bfloat16 *qA = poA - 192 * wg, *qB = poB - 192 * wg;
      if (k + 2 == nt) nb_sync(11);
      sched_fence();
      wg_wait<0>();
      fence_regs(ac1);
      pack_out<1>(ac1, oa, ob);
      asm volatile("" : "+l"(qA), "+l"(qB));
      store_rows<3, 6>(direct, qA, qB, oa, ob);
      if (k == 0) {
        uint32_t m[2] = {oa[0], oa[1]};
#pragma unroll
        for (int i = 2; i < 24; i++) asm("max.NaN.bf16x2 %0, %0, %1;" : "+r"(m[i & 1]) : "r"(oa[i]));
        asm("max.NaN.bf16x2 %0, %0, %1;" : "+r"(m[0]) : "r"(m[1]));
        uint32_t nan;
        asm volatile("{\n.reg .pred p;\nsetp.ne.u32 p, %1, 0;\nbar.red.or.pred p, 15, 128, p;\nselp.u32 %0, 1, 0, p;\n}\n"
                     : "=r"(nan) : "r"(((m[0] & 0x7FFF7FFFu) + 0x007F007Fu) & 0x80008000u) : "memory");
        if (__builtin_expect(__any_sync(0xffffffffu, nan), 0)) {
          for (int c = 0; c < 3 && __any_sync(0xffffffffu, geo[2] & 1u); c++) mbar_wait(bar_x(bars, 1, c), 1);
          for (bool first = true; __any_sync(0xffffffffu, refetch(sbase + kW2Off, wimg + w2_offset(), first)); first = false) { }
          wg_fence();
          g2_steps<0, 8, 0>(ac0, za, zb, dX0);
          g2_steps<8, 12, 0>(ac0, za, zb, dX2);
          g2_steps<0, 8, 0>(ac1, za, zb, dY0);
          g2_steps<8, 12, 0>(ac1, za, zb, dY2);
          wg_commit();
          wg_wait<0>();
          fence_regs(ac0);
          fence_regs(ac1);
          pack_out<0>(ac0, oa, ob);
          pack_out<1>(ac1, oa, ob);
          if (__any_sync(0xffffffffu, geo[2] & 1u)) {
            asm volatile("bar.sync 15, 128;" ::: "memory");
            if (w == 0 && elect_one()) {
              const TileCoord tc = decode_tile(tt, tile0 + 2);
              mbar_arrive_expect_tx(bar_raw(bars), kWChunk);
#pragma unroll 1
              for (int c = 0; c < 3; c++) load_px(tm, tt, sbase + x_chunk(2, c), bar_raw(bars), first_line(tc) + c, tc.kind);
            }
            __syncwarp();
            mbar_wait(bar_raw(bars), 0);
          }
        }
        if (nt < 6) nb_arrive_p(5);
        if (elect_one()) mbar_arrive(bar_wok(bars));
      }
      keep_regs(za);
      keep_regs(zb);
#pragma unroll
      for (int i = 0; i < 4; i++) geo[i] = geo[i + 2];
      keep_regs(oa);
      keep_regs(ob);
      PROFS(12, wg, 12 + it * 12);
      sched_fence();
    }
  }
  PROF(wg, 38);
  GT_DUMP();
  PROF_DUMP(wg);
}

struct HaloCols { int vj, vc, uj, uc; };
__device__ __forceinline__ HaloCols halo_cols(const TileCoord& tc) {
  const int c0 = halo_c0(tc);
  return HaloCols{c0 > 98, c0 > 98 ? 98 : c0 + 3, c0 < 0 ? -1 : 0, c0 < 0 ? 4 : c0};
}
__device__ __forceinline__ void first_halo(const Maps& tm, uint32_t sbase, const TileCoord tc, int i) {
  const HaloCols hc = halo_cols(tc);
  const uint32_t dst = sbase + i * kChunkBytes, bar = bar_full(sbase + kBarOff, 0, i >> 1);
  const int h0 = halo_r0(tc), ch = 24 * tc.pc + 4 * i;
  tma_load_5d(dst, &tm.v14, bar, ch, hc.vj, hc.vc, tc.pr, h0);
  tma_load_5d(dst + 7 * 1024, &tm.u8, bar, ch, hc.uj, h0 + (tc.up ? 0 : -2), tc.pr, hc.uc);
  tma_load_5d(dst + 10 * 1024, &tm.u8, bar, ch, hc.uj, h0 + (tc.up ? 8 : 6), tc.pr, hc.uc);
}
__device__ __forceinline__ void load_halo(const Maps& tm, uint32_t sbase, uint32_t bars, const TileCoord tc, int k, int c) {
  const HaloCols hc = halo_cols(tc);
  const int h6 = halo_r0(tc) + (tc.up ? 0 : 8), h2 = halo_r0(tc) + 6, h8 = halo_r0(tc) + (tc.up ? 0 : 6), ch = 24 * tc.pc + 8 * c;
  uint32_t dv = sbase + 2 * c * kChunkBytes, du = dv + 7 * 1024;
  if (((k ^ tc.up) & 1) == 0) dv += 4 * 1024, du += 3 * 1024;
  const uint32_t bar = bar_full(bars, k & 1, c);
  mbar_arrive_expect_tx(bar, 14 * 1024);
  nb_sync_p(7 + c);
#pragma unroll
  for (int h = 0; h < 2; h++) {
    tma_load_5d(dv + h * kChunkBytes, &tm.v6, bar, ch + 4 * h, hc.vj, hc.vc, tc.pr, h6);
    tma_load_5d(du + h * kChunkBytes, &tm.u8, bar, ch + 4 * h, hc.uj, h8, tc.pr, hc.uc);
    tma_load_5d(sbase + (2 * c + h) * kChunkBytes + 3 * 1024, &tm.v2, bar, ch + 4 * h, hc.vj, hc.vc, tc.pr, h2);
  }
  PROFS(15, 2, k * 4 + c);
}
__device__ __forceinline__ void gather_px(const __nv_bfloat16* __restrict__ x, uint32_t sbase, int k, const TileCoord tc) {
  const int lane = threadIdx.x & 31, g = lane >> 3;
  uint32_t ro[4], co[4];
#pragma unroll
  for (int i = 0; i < 4; i++) {
    ro[i] = qpix(tc.pr, 8 * tc.I + 2 * i + (g & 1)) * (kW * kC * 2) + 16 * (lane & 7);
    co[i] = qpix(tc.pc, 8 * tc.J + 2 * i + (g >> 1)) * (kC * 2);
  }
  const uint32_t dst = sbase + kXOff + g * 128 + (((lane & 7) ^ g) << 4);
  const int dq = k & 1 ? -128 : 128;
  keep_regs(ro);
  keep_regs(co);
  sched_fence();
  nb_sync_p(13);
  nb_sync_p(5);
#pragma unroll
  for (int i = 0; i < 16; i++) {
    const char* src = (const char*)x + (ro[i >> 2] + co[i & 3] + 128);
#pragma unroll
    for (int q = 0; q < 3; q++)
      asm volatile("cp.async.cg.shared.global [%0], [%1], 16;" ::"r"((dst ^ ((i & 1) * 576)) + (i >> 1) * 1024 + q * 8192), "l"(src + (q - 1) * dq) : "memory");
  }
  asm volatile("cp.async.wait_all;" ::: "memory");
  fence_proxy_async();
  __syncwarp();
  if (lane < 3) mbar_arrive(bar_x(sbase + kBarOff, 1, lane));
  __syncwarp();
}

__global__ void __launch_bounds__(384, 1)
nat_kernel(const __nv_bfloat16* __restrict__ x, __nv_bfloat16* out, const __nv_bfloat16* __restrict__ wqkv,
           const __nv_bfloat16* __restrict__ wo, uint8_t* wimg, const uint32_t zero,
           const __grid_constant__ Maps tm, const __grid_constant__ TileTable tt) {
  extern __shared__ uint8_t smem_raw[];
  constexpr uint32_t sbase = 1024;
  constexpr uint32_t bars = sbase + kBarOff;
  if (smem_u32(smem_raw) != sbase) __trap();
  const int tid = threadIdx.x;
  const uint32_t t_start = now_ns();
  if (tid == 0) GT(0);
  const int wid = __shfl_sync(0xffffffffu, tid >> 5, 0);
  const bool w2cta = blockIdx.x - 128 < 3 && wqkv != nullptr;
  if (wid >= 8) {
    asm volatile("setmaxnreg.dec.sync.aligned.u32 24;");
    const int c = wid & 3, lane = tid & 31;
    const int tile0 = blockIdx.x * kTilesPerCta, nt = num_tiles();
    uint32_t w2o = 0;
    if (c == 3) {
      asm volatile("bar.sync 13, 128;" ::: "memory");
      if (elect_one()) wait_clock(t_start, NAT_TM);
      __syncwarp();
      asm volatile("prefetch.tensormap [%0];" ::"l"((uint64_t)tm.px) : "memory");
      asm volatile("prefetch.tensormap [%0];" ::"l"((uint64_t)&tm.v6) : "memory");
      asm volatile("prefetch.tensormap [%0];" ::"l"((uint64_t)&tm.v2) : "memory");
      asm volatile("prefetch.tensormap [%0];" ::"l"((uint64_t)(tm.px + (blockIdx.x < 112 ? 5 : 6))) : "memory");
      asm volatile("prefetch.tensormap [%0];" ::"l"((uint64_t)(tm.px + 7)) : "memory");
      __nanosleep(NAT_TW2 - 2800);
      w2o = w2_offset();
      if (elect_one()) {
        mbar_arrive_expect_tx(bar_w2a(bars), kWChunk);
        mbar_arrive_expect_tx(bar_w2(bars), kWChunk);
        wait_clock(t_start, NAT_TW2);
        bulk_load(sbase + kW2Off, wimg + w2o, kWChunk, bar_w2a(bars));
        mbar_wait(bar_xf(bars), 0);
        bulk_load(sbase + kW2Off + 2 * kWChunk, wimg + (w2o + 2 * kWChunk), kWChunk, bar_w2(bars));
      }
      __syncwarp();
      if (nt < 6) {
#pragma unroll 1
        for (int k = 2; k < 4; k++) {
          gather_px(x, sbase, k, decode_tile(tt, tile0 + k));
        }
      }
      if (wqkv == nullptr) return;
      mbar_wait(bar_wok(bars), 0);
      if (lane == 0) asm volatile("red.relaxed.gpu.global.add.u32 [%0], 1;" ::"l"(g_flag) : "memory");
      if (blockIdx.x >= 48) return;
      if (lane == 0) {
        uint32_t v, it = 0;
        do {
          __nanosleep(2000);
          asm volatile("ld.relaxed.gpu.global.u32 %0, [%1];" : "=r"(v) : "l"(g_flag) : "memory");
        } while (v < gridDim.x && ++it < (1u << 16));
      }
      __syncwarp();
#pragma unroll
      for (int i = 0; i < 6; i++)
        stg128(wimg + ((i < 3 ? 0u : 3 * kWBytes - w2o) + blockIdx.x * 1536 + (i % 3) * 512 + lane * 16), kEmpty, kEmpty, kEmpty, kEmpty);
      if (lane == 0 && atomicAdd(g_flag + 32, 1u) == 47) {
        g_flag[0] = g_flag[32] = 0;
        g_flag[64] = w2o == kWBytes;
      }
      return;
    }
    if (!elect_one()) return;
    if (c == 0) {
      for (int i = 0; i < kNumBars; i++)
        if ((i != 0 && i != 10 || nt < 6) && (i != 21 || !w2cta)) mbar_init(bars + i * 8, i == 13 || i == 16 ? 4 : 1);
      asm volatile("st.shared.v2.u32 [%0], {%1,%1};" ::"r"(bars + 192), "r"(0) : "memory");
      asm volatile("fence.mbarrier_init.release.cluster;" ::: "memory");
      if (w2cta) asm volatile("bar.sync 10, 64;" ::: "memory");
      asm volatile("bar.arrive 0, 160;" ::: "memory");
      asm volatile("bar.arrive 14, 160;" ::: "memory");
      asm volatile("bar.arrive 13, 128;" ::: "memory");
      const TileCoord tc0 = decode_tile(tt, tile0);
      const HaloCols hc = halo_cols(tc0);
      const int h0 = halo_r0(tc0);
#pragma unroll
      for (int j = 0; j < 3; j++)
        if (j > 0 || nt < 6) mbar_arrive_expect_tx(bar_full(bars, 0, j), 2 * kChunkBytes);
      wait_clock(t_start, NAT_HP);
#pragma unroll
      for (int q = 8; q < 24; q += 8) {
        tma_prefetch_5d(&tm.v6, 24 * tc0.pc + q, hc.vj, hc.vc, tc0.pr, h0 + (tc0.up ? 0 : 8));
        tma_prefetch_5d(&tm.u8, 24 * tc0.pc + q, hc.uj, h0 + (tc0.up ? 0 : 6), tc0.pr, hc.uc);
        if (blockIdx.x >= 112) tma_prefetch_5d(&tm.v2, 24 * tc0.pc + q, hc.vj, hc.vc, tc0.pr, h0 + 6);
      }
#pragma unroll 1
      for (int i = nt < 6 ? 0 : 2; i < 7; i++) {
        if (i == NAT_H0) mbar_wait(bar_w1q(bars), 0);
        if (i == NAT_X1P) mbar_arrive(bar_go(bars));
        if (i < 6) first_halo(tm, sbase, tc0, i);
      }
      w2o = w2_offset();
    } else {
      asm volatile("bar.sync 13, 128;" ::: "memory");
      if (c == 2) {
        if (wqkv != nullptr && nt == 6) asm volatile("bar.sync 12, 64;" ::: "memory");
        const uint32_t c0 = clock();
        while ((uint32_t)clock() - c0 < NAT_TD) { }
        wait_clock(t_start, NAT_T0);
#pragma unroll
        for (int j = 0; j < 3; j++) {
          mbar_arrive_expect_tx(bar_w1c(bars, j), kWChunk);
          bulk_load(sbase + kW1Off + j * kWChunk, wimg + j * kWChunk, kWChunk, bar_w1c(bars, j));
        }
        mbar_arrive(bar_w1q(bars));
        GT(2);
      } else {
#pragma unroll 1
        for (int j = nt == 6; j < 2; j++) {
          const TileCoord tc = decode_tile(tt, tile0 + j);
          const int line = first_line(tc);
          if (j == 1) mbar_wait(bar_go(bars), 0);
#pragma unroll 1
          for (int q = 0; q < 3; q++) {
            load_px(tm, tt, sbase + x_chunk(j, q), bar_x(bars, j, q), line + q, tc.kind);
            if (j == 1 || q == 0) mbar_arrive_expect_tx(bar_x(bars, j, q), j ? 8192 : kWChunk);
          }
        }
        w2o = w2_offset();
        wait_clock(t_start, NAT_TW2);
      }
    }
#pragma unroll 1
    for (int k = 1; k < nt; k++) {
      const TileCoord tn = decode_tile(tt, tile0 + k + 1);
      const int line = first_line(tn);
      if (c == 1) {
#pragma unroll
        for (int q = 3 - NAT_MP; q < 3; q++) {
          const uint32_t n = q == 3 - NAT_MP ? q + 1 : 1, o = x_chunk(k, k & 1 ? q : q + 1 - n);
          nb_sync_p(q == 0 ? 0 : q == 1 ? 14 : 6);
          bulk_load(sbase + o, wimg + (w2o + o - kW2Off), n * 8192, bar_w2m(bars));
        }
        mbar_arrive_expect_tx(bar_w2m(bars), kWChunk);
      }
      if (c == 2) {
        if (k == 1) wait_clock(t_start, NAT_TX2);
        else __nanosleep(NAT_PFD);
#pragma unroll 1
        for (int q = 0; q < 3 && k < 5 && nt == 6; q++) load_px(tm, tt, 0, 0, line + q, tn.kind);
      }
      if (c == 2 && (blockIdx.x >= 112 || k == 5)) {
        const TileCoord tc = decode_tile(tt, tile0 + k);
        const HaloCols hc = halo_cols(tc);
        const int h8 = halo_r0(tc) + (tc.up ? 0 : 6);
#pragma unroll 1
        for (int q = 0; q < 24; q += 8) {
          tma_prefetch_5d(&tm.v6, 24 * tc.pc + q, hc.vj, hc.vc, tc.pr, h8);
          tma_prefetch_5d(&tm.v2, 24 * tc.pc + q, hc.vj, hc.vc, tc.pr, h8 + 6);
          tma_prefetch_5d(&tm.u8, 24 * tc.pc + q, hc.uj, h8, tc.pr, hc.uc);
        }
      }
      load_halo(tm, sbase, bars, decode_tile(tt, tile0 + k), k, c);
      if (c == 0 && k < 5 && nt == 6) {
#pragma unroll
        for (int q = 0; q < 3; q++) {
          if (q < 2) nb_sync_p(q ? 5 : 13);
          load_px(tm, tt, sbase + x_chunk(k + 1, q), bar_x(bars, 1, q), line + q, tn.kind);
          if (q != 1) mbar_arrive_expect_tx(bar_x(bars, 1, q), 8192);
        }
        mbar_arrive_expect_tx(bar_x(bars, 1, 1), 8192);
        PROFS(16, 2, k * 4 + 3);
      }
      if (c == 0 && k >= 2) {
        const TileCoord tp = decode_tile(tt, tile0 + k - 2);
        const int lp = first_line(tp);
        nb_sync_p(10);
        if (NAT_XW == 1 && k < 5 && nt == 6) mbar_wait(bar_x(bars, 1, 2), k & 1);
        if (NAT_XW > 1) __nanosleep(NAT_XW);
        store_px(tm, tt, sbase + out_slot(k, nt), lp, tp.kind);
        if (k + 1 < nt) {
          asm volatile("cp.async.bulk.wait_group.read 0;" ::: "memory");
          bulk_load(sbase + out_slot(k, nt), wimg + (w2o + out_slot(k, nt) - kW2Off), kWChunk, bar_w2(bars));
          mbar_arrive_expect_tx(bar_w2(bars), kWChunk);
        }
      }
    }
    asm volatile("cp.async.bulk.wait_group 0;" ::: "memory");
  } else {
    if (blockIdx.x < 128) {
      if ((wid == 4 || (wid == 5 && blockIdx.x - 2 < 16)) && wqkv != nullptr) {
        fold_w1(blockIdx.x - 2 < 16 ? 2 * blockIdx.x + wid - 6 : blockIdx.x + (blockIdx.x < 2 ? 0 : 16), wqkv, wimg);
        if (wid == 4) asm volatile("bar.arrive 12, 64;" ::: "memory");
        if (tid == 128) GT(7);
      }
      sched_fence();
      if (wid == 1 && elect_one()) {
        const TileCoord tc = decode_tile(tt, blockIdx.x * kTilesPerCta);
        mbar_init(bar_x(bars, 0, 0), 1);
        asm volatile("fence.mbarrier_init.release.cluster;" ::: "memory");
        mbar_arrive_expect_tx(bar_x(bars, 0, 0), kWChunk);
        GT(15);
#pragma unroll 1
        for (int q = 0; q < 3; q++) load_px(tm, tt, sbase + x_chunk(0, q), bar_x(bars, 0, 0), first_line(tc) + q, tc.kind);
        GT(16);
      }
      __syncwarp();
      sched_fence();
      if (wid == 2 && elect_one()) {
        const TileCoord tc = decode_tile(tt, blockIdx.x * kTilesPerCta);
        mbar_init(bar_full(bars, 0, 0), 1);
        asm volatile("fence.mbarrier_init.release.cluster;" ::: "memory");
        mbar_arrive_expect_tx(bar_full(bars, 0, 0), 2 * kChunkBytes);
        if (NAT_TH) wait_clock(t_start, NAT_TH);
        asm volatile("prefetch.tensormap [%0];" ::"l"((uint64_t)&tm.u8) : "memory");
        GT(17);
        first_halo(tm, sbase, tc, 0);
        first_halo(tm, sbase, tc, 1);
      }
      __syncwarp();
    }
    sched_fence();
    {
      if (w2cta) {
        const int q = blockIdx.x & 3;
        uint32_t w2o = 0;
        if (wid == 1 && elect_one()) {
          asm volatile("prefetch.tensormap [%0];" ::"l"((uint64_t)&tm.wo) : "memory");
#pragma unroll
          for (int j = 0; j < 3; j++) mbar_init(bar_raw(bars, j), 1);
          asm volatile("fence.mbarrier_init.release.cluster;" ::: "memory");
#pragma unroll
          for (int j = 0; j < 6; j++)
            asm volatile("cp.async.bulk.tensor.2d.shared::cluster.global.tile.mbarrier::complete_tx::bytes [%0], [%1, {%3, %4}], [%2];" ::"r"(
                             j < 3 ? sbase + j * 8192 : sbase + kW2Off + (j - 3) * kWChunk),
                         "l"((uint64_t)(j < 3 ? &tm.wv : &tm.wo)), "r"(bar_raw(bars, j < 3 ? 0 : j - 3)),
                         "r"(j < 3 ? 384 + 64 * j : 64 * (j - 3)), "r"(j < 3 ? 64 * q : 0) : "memory");
#pragma unroll
          for (int j = 0; j < 3; j++) mbar_arrive_expect_tx(bar_raw(bars, j), j ? kWChunk : 2 * kWChunk);
          w2o = w2_offset();
        }
        __syncwarp();
#pragma unroll 1
        for (int r = 0; r < 3; r++) {
          const int blk = 2 * r - 2 + (wid >> 2);
          if (blk < 3) {
            if (r > 0) {
              mbar_wait(bar_raw(bars, 0), 0);
              mbar_wait(bar_raw(bars, blk), 0);
            }
            if (tid == 0 && r == 1) GT(7);
            float acc[32];
            const uint64_t db = make_desc(sbase + kW2Off + max(blk, 0) * kWChunk, kWChunk, 1024);
            wg_fence();
            wg_m64tz<0, 32>(acc, make_desc(sbase, 16, 1024), db, 0);
#pragma unroll
            for (int s = 1; s < 12; s++) wg_m64t<0, 32>(acc, make_desc(sbase + (s >> 2) * 8192 + (s & 3) * 32, 16, 1024), db + s * 128, 1);
            wg_commit();
            wg_wait<0>();
            fence_regs(acc);
            if (tid == 0) GT(19);
            const int m = (tid >> 3) & 3;
#pragma unroll
            for (int j = 0; j < 8; j += 2) {
              const int n = g2_inv(8 * (j + (m >> 1)) + (tid & 7));
              asm volatile("stmatrix.sync.aligned.m8n8.x4.trans.shared.b16 [%0], {%1,%2,%3,%4};" ::"r"(
                               sbase + kW1Off + (blk + 2) * 8192 + n * 128 + (((2 * (wid & 3) + (m & 1)) ^ (n & 7)) << 4)),
                           "r"(pack_bf16(acc[4 * j], acc[4 * j + 1])), "r"(pack_bf16(acc[4 * j + 2], acc[4 * j + 3])),
                           "r"(pack_bf16(acc[4 * j + 4], acc[4 * j + 5])), "r"(pack_bf16(acc[4 * j + 6], acc[4 * j + 7])) : "memory");
            }
            fence_proxy_async();
          }
          if (tid == 0) GT(18);
          asm volatile("bar.sync 11, 256;" ::: "memory");
          if (wid == 1 && elect_one()) {
            asm volatile("{\n.reg .pred p;\nsetp.ne.s32 p, %3, 0;\n@p cp.async.bulk.global.shared::cta.bulk_group [%0], [%1], %2;\n}\n" ::"l"(
                             wimg + (w2o + w2piece(r >> 1, q) * (kWChunk / 2))),
                         "r"(sbase + kW1Off + 16384 + (r >> 1) * (kWChunk / 2)), "r"(kWChunk / 2), "r"(r) : "memory");
            asm volatile("cp.async.bulk.commit_group;" ::: "memory");
          }
          __syncwarp();
        }
        if (wid == 1) {
          if (elect_one()) asm volatile("cp.async.bulk.wait_group.read 0;" ::: "memory");
          if (tid == 32) GT(31);
          __syncwarp();
          asm volatile("bar.arrive 10, 64;" ::: "memory");
        }
      }
    }
    __syncwarp();
    if (wid < 4) asm volatile("bar.sync 0, 160;" ::: "memory");
    else asm volatile("bar.sync 14, 160;" ::: "memory");
    asm volatile("setmaxnreg.inc.sync.aligned.u32 240;");
    consumer(wid >> 2, out, wimg, sbase, zero, tm, tt);
  }
}

}

typedef CUresult (*PFN_encodeTiled)(CUtensorMap*, CUtensorMapDataType, cuuint32_t, void*, const cuuint64_t*,
                                    const cuuint64_t*, const cuuint32_t*, const cuuint32_t*, CUtensorMapInterleave,
                                    CUtensorMapSwizzle, CUtensorMapL2promotion, CUtensorMapFloatOOBfill);

extern "C" void kernel_launch(void* const* d_in, const int* in_sizes, int n_in, void* d_out, int out_size) {
  const __nv_bfloat16* x = (const __nv_bfloat16*)d_in[0];
  const __nv_bfloat16* wqkv = (const __nv_bfloat16*)d_in[1];
  const __nv_bfloat16* wo = (const __nv_bfloat16*)d_in[2];
  __nv_bfloat16* out = (__nv_bfloat16*)d_out;

  static PFN_encodeTiled encode = nullptr;
  static int num_sms = 0;
  static uint8_t* wimg = nullptr;
  if (!encode) {
    void* fn = nullptr;
    cudaDriverEntryPointQueryResult qres;
    cudaGetDriverEntryPoint("cuTensorMapEncodeTiled", &fn, cudaEnableDefault, &qres);
    encode = (PFN_encodeTiled)fn;
    cudaFuncSetAttribute(nat::nat_kernel, cudaFuncAttributeMaxDynamicSharedMemorySize, nat::kSmemBytes);
    cudaGetSymbolAddress((void**)&wimg, nat::g_wimg32);
    int dev = 0;
    cudaGetDevice(&dev);
    cudaDeviceGetAttribute(&num_sms, cudaDevAttrMultiProcessorCount, dev);
  }
  nat::Maps tm;
  cuuint32_t estr[5] = {1, 1, 1, 1, 1};
  {
    cuuint64_t vdim[5] = {48, 2, 105, 2, 112}, udim[5] = {48, 2, 112, 2, 105};
    cuuint64_t vstr[4] = {7 * 768, 768, 224 * 384, 2 * 224 * 384}, ustr[4] = {7 * 768, 2 * 224 * 384, 224 * 384, 768};
    CUtensorMap* maps[4] = {&tm.v6, &tm.v2, &tm.v14, &tm.u8};
    for (int i = 0; i < 4; i++) {
      cuuint32_t box[5] = {4, 2, i < 3 ? 4u : 8u, 1, i == 0 ? 6u : i == 1 ? 2u : i == 2 ? 14u : 3u};
      encode(maps[i], CU_TENSOR_MAP_DATA_TYPE_UINT32, 5, (void*)x, i < 3 ? vdim : udim, i < 3 ? vstr : ustr, box, estr,
             CU_TENSOR_MAP_INTERLEAVE_16B, CU_TENSOR_MAP_SWIZZLE_128B, CU_TENSOR_MAP_L2_PROMOTION_L2_128B, CU_TENSOR_MAP_FLOAT_OOB_FILL_NONE);
    }
  }
  for (int i = 0; i < 8; i++) {
    const cuuint32_t row = 224 * 384;
    const cuuint32_t shape[8][6] = {{2, 8, 4, 2 * row, 768, 4 * row}, {2, 8, 3, row, 768, 2 * row},     {2, 8, 1, 2 * row, 768, 4 * row},
                                    {8, 2, 3, 2 * row, 4 * 384, 384}, {8, 2, 1, 2 * row, 5 * 384, 384}, {4, 2, 3, 4 * row, 2 * row, 128},
                                    {4, 2, 3, 768, row, 128},         {4, 2, 3, 768, 2 * row, 128}};
    const cuuint32_t* sh = shape[i];
    cuuint64_t dim[5] = {64, sh[0], sh[1], sh[2], 224 * 224 * 3};
    cuuint64_t str[4] = {sh[3], sh[4], sh[5], 128};
    cuuint32_t box[5] = {64, sh[0], sh[1], sh[2], 1};
    encode(tm.px + i, CU_TENSOR_MAP_DATA_TYPE_BFLOAT16, 5, i < 5 ? (void*)x : (void*)out, dim, str, box, estr, CU_TENSOR_MAP_INTERLEAVE_NONE,
           CU_TENSOR_MAP_SWIZZLE_128B, i < 5 ? CU_TENSOR_MAP_L2_PROMOTION_L2_128B : CU_TENSOR_MAP_L2_PROMOTION_NONE,
           CU_TENSOR_MAP_FLOAT_OOB_FILL_NONE);
  }
  for (int i = 0; i < 2; i++) {
    cuuint64_t dim[2] = {i ? 192u : 576u, 192}, str[1] = {i ? 384u : 1152u};
    cuuint32_t box[2] = {64, i ? 192u : 64u};
    encode(i ? &tm.wo : &tm.wv, CU_TENSOR_MAP_DATA_TYPE_BFLOAT16, 2, i ? (void*)wo : (void*)wqkv, dim, str, box, estr,
           CU_TENSOR_MAP_INTERLEAVE_NONE, CU_TENSOR_MAP_SWIZZLE_128B, CU_TENSOR_MAP_L2_PROMOTION_L2_256B, CU_TENSOR_MAP_FLOAT_OOB_FILL_NONE);
  }
  nat::TileTable tt;
  nat::make_tiles(tt);
  const int grid = nat::kCtas;
  if (num_sms >= grid) {
    nat::nat_kernel<<<grid, 384, nat::kSmemBytes>>>(x, out, wqkv, wo, wimg, 0u, tm, tt);
  } else {
    nat::fold_kernel<<<27, 256>>>(wqkv, wo, wimg);
    nat::nat_kernel<<<grid, 384, nat::kSmemBytes>>>(x, out, nullptr, nullptr, wimg, 0u, tm, tt);
  }
}
```

```cpp
#include <cuda_runtime.h>
#include <cuda_bf16.h>
#include <cuda.h>
#include <stdint.h>

#define NAT_P1 2
#define NAT_P2 4
#define NAT_H0 2
#define NAT_T0 2100
#define NAT_TD 1200
#define NAT_TW2 4650
#define NAT_TX2 3800
#define NAT_X1P 6
#define NAT_PK 3
#define NAT_HP 1800
#define NAT_PFD 400
#define NAT_XW 200
#define NAT_MP 3
#define NAT_D0 1
#define NAT_TH 0
#define NAT_TM 1300
#define NAT_QA 1
#define NAT_SB 0
namespace nat {

constexpr int kW = 224, kC = 192;
constexpr int kCtas = 132;
constexpr int kTilesPerCta = 6;
constexpr float kAlpha = 0.07216878364870322f * 1.4426950408889634f;
constexpr uint32_t kChunkBytes = 13 * 1024;
constexpr uint32_t kWChunk = 192 * 128;
constexpr uint32_t kWBytes = 3 * kWChunk;
constexpr uint32_t kW1Off = 6 * kChunkBytes;
constexpr uint32_t kW2Off = kW1Off + kWBytes;
constexpr uint32_t kXOff = kW2Off + kWChunk;
constexpr uint32_t kBarOff = kW2Off + kWBytes;
constexpr uint32_t kProfOff = kBarOff + 208;
constexpr uint32_t kSmemBytes = kBarOff + 1024;

static_assert(kW1Off % 1024 == 0 && kW2Off % 1024 == 0 && kChunkBytes % 1024 == 0, "swizzle alignment");
static_assert(kSmemBytes <= 232448, "smem");

constexpr uint32_t kEmpty = 0xFFFFFFFFu;
#define NAT_R8(v) v, v, v, v, v, v, v, v
#define NAT_R2K(v) NAT_R8(NAT_R8(NAT_R8(v))), NAT_R8(NAT_R8(NAT_R8(v))), NAT_R8(NAT_R8(NAT_R8(v))), NAT_R8(NAT_R8(NAT_R8(v)))
#define NAT_IMG NAT_R8(NAT_R2K(kEmpty)), NAT_R2K(kEmpty)
__device__ __align__(1024) uint32_t g_wimg32[3 * kWBytes / 4] = {NAT_IMG, NAT_IMG, NAT_IMG};
static_assert(kWBytes / 4 == 9 * 2048, "initialiser");
__device__ __align__(128) uint32_t g_flag[96];
__device__ __forceinline__ uint32_t w2_offset() {
  uint32_t v;
  asm volatile("ld.relaxed.gpu.global.u32 %0, [%1];" : "=r"(v) : "l"(g_flag + 64) : "memory");
  return (1 + v) * kWBytes;
}

#define PROFS(id, wgid, slotid) do { } while (0)
#define PROF(wgid, slotid) do { } while (0)
#define PROF_DUMP(wgid) do { } while (0)

#define GT(slotid) do { } while (0)
#define GT_DUMP() do { } while (0)

__device__ __forceinline__ uint32_t smem_u32(const void* p) { return (uint32_t)__cvta_generic_to_shared(p); }

__device__ __forceinline__ void mbar_init(uint32_t bar, uint32_t count) {
  asm volatile("mbarrier.init.shared::cta.b64 [%0], %1;" ::"r"(bar), "r"(count) : "memory");
}
__device__ __forceinline__ void mbar_arrive(uint32_t bar) {
  asm volatile("mbarrier.arrive.shared::cta.b64 _, [%0];" ::"r"(bar) : "memory");
}
__device__ __forceinline__ void mbar_arrive_expect_tx(uint32_t bar, uint32_t bytes) {
  asm volatile("mbarrier.arrive.expect_tx.shared::cta.b64 _, [%0], %1;" ::"r"(bar), "r"(bytes) : "memory");
}
__device__ __forceinline__ void mbar_wait(uint32_t bar, uint32_t parity) {
  uint32_t ok;
  uint32_t it = 0;
  do {
    asm volatile(
        "{\n.reg .pred p;\n"
        "mbarrier.try_wait.parity.shared::cta.b64 p, [%1], %2;\n"
        "selp.u32 %0, 1, 0, p;\n}\n"
        : "=r"(ok)
        : "r"(bar), "r"(parity)
        : "memory");
    if (++it > (1u << 24)) break;
  } while (!ok);
}
__device__ __forceinline__ uint32_t mbar_test(uint32_t bar, uint32_t parity) {
  uint32_t ok;
  asm volatile("{\n.reg .pred p;\nmbarrier.test_wait.parity.shared::cta.b64 p, [%1], %2;\nselp.u32 %0, 1, 0, p;\n}\n"
               : "=r"(ok) : "r"(bar), "r"(parity) : "memory");
  return ok;
}
__device__ __forceinline__ void mbar_wait_if(uint32_t ok, uint32_t bar, uint32_t parity) {
  if (!__all_sync(0xffffffffu, ok)) mbar_wait(bar, parity);
}
__device__ __forceinline__ bool elect_one() {
  uint32_t r;
  asm volatile("{\n.reg .pred p;\nelect.sync _|p, 0xffffffff;\nselp.u32 %0, 1, 0, p;\n}\n" : "=r"(r));
  return r != 0;
}
__device__ __forceinline__ void nb_arrive(int id) { asm volatile("bar.arrive %0, 256;" ::"r"(id) : "memory"); }
__device__ __forceinline__ void nb_sync(int id) { asm volatile("bar.sync %0, 256;" ::"r"(id) : "memory"); }
__device__ __forceinline__ void nb_arrive_p(int id) { asm volatile("bar.arrive %0, 160;" ::"r"(id) : "memory"); }
__device__ __forceinline__ void nb_sync_p(int id) { asm volatile("bar.sync %0, 160;" ::"r"(id) : "memory"); }
__device__ __forceinline__ void fence_proxy_async() { asm volatile("fence.proxy.async.shared::cta;" ::: "memory"); }

__device__ __forceinline__ void tma_load_5d(uint32_t dst, const CUtensorMap* map, uint32_t bar, int c0, int c1, int c2,
                                            int c3, int c4) {
  asm volatile(
      "cp.async.bulk.tensor.5d.shared::cluster.global.tile.mbarrier::complete_tx::bytes "
      "[%0], [%1, {%3, %4, %5, %6, %7}], [%2];"
      ::"r"(dst), "l"((uint64_t)map), "r"(bar), "r"(c0), "r"(c1), "r"(c2), "r"(c3), "r"(c4)
      : "memory");
}
__device__ __forceinline__ void bulk_load(uint32_t dst, const void* src, uint32_t bytes, uint32_t bar) {
  asm volatile("cp.async.bulk.shared::cluster.global.mbarrier::complete_tx::bytes [%0], [%1], %2, [%3];"
               ::"r"(dst), "l"((uint64_t)src), "r"(bytes), "r"(bar)
               : "memory");
}

__device__ __forceinline__ void wg_fence() { asm volatile("wgmma.fence.sync.aligned;" ::: "memory"); }
__device__ __forceinline__ void wg_commit() { asm volatile("wgmma.commit_group.sync.aligned;" ::: "memory"); }
template <int N>
__device__ __forceinline__ void wg_wait() { asm volatile("wgmma.wait_group.sync.aligned %0;" ::"n"(N) : "memory"); }

template <int N>
__device__ __forceinline__ void fence_regs(float (&d)[N]) {
#pragma unroll
  for (int i = 0; i < N; i++) asm volatile("" : "+f"(d[i])::"memory");
}
template <int N>
__device__ __forceinline__ void keep_regs(uint32_t (&d)[N]) {
#pragma unroll
  for (int i = 0; i < N; i++) asm volatile("" : "+r"(d[i])::"memory");
}

__device__ __forceinline__ uint32_t pack_bf16(float lo, float hi) {
  uint32_t d;
  asm("cvt.rn.bf16x2.f32 %0, %1, %2;" : "=r"(d) : "f"(hi), "f"(lo));
  return d;
}
__device__ __forceinline__ float ex2(float x) {
  float y;
  asm("ex2.approx.ftz.f32 %0, %1;" : "=f"(y) : "f"(x));
  return y;
}
__device__ __forceinline__ float rcp_approx(float x) {
  float y;
  asm("rcp.approx.ftz.f32 %0, %1;" : "=f"(y) : "f"(x));
  return y;
}
__device__ __forceinline__ uint4 ldg128_nc(const void* p) {
  uint4 v;
  asm volatile("ld.global.nc.v4.u32 {%0,%1,%2,%3}, [%4];" : "=r"(v.x), "=r"(v.y), "=r"(v.z), "=r"(v.w) : "l"(p));
  return v;
}
__device__ __forceinline__ void stg128(void* p, uint32_t a, uint32_t b, uint32_t c, uint32_t d) {
  asm volatile("st.global.v4.u32 [%0], {%1,%2,%3,%4};" ::"l"(p), "r"(a), "r"(b), "r"(c), "r"(d) : "memory");
}

__device__ __forceinline__ long long clk64() {
  long long c;
  asm volatile("mov.u64 %0, %clock64;" : "=l"(c)::"memory");
  return c;
}
__device__ __forceinline__ void sched_fence() { while (clk64() < 0) { } }

__device__ __forceinline__ uint64_t make_desc(uint32_t addr, uint32_t lbo, uint32_t sbo, uint32_t mode = 1) {
  return (uint64_t)((addr & 0x3FFFF) >> 4) | ((uint64_t)(lbo >> 4) << 16) | ((uint64_t)(sbo >> 4) << 32) |
         ((uint64_t)mode << 62);
}

template <int OFF, int NN>
__device__ __forceinline__ void wg_m192(float (&d)[NN], uint64_t desc_a, uint64_t desc_b, int scale_d) {
  asm volatile(
      "{\n.reg .pred p;\nsetp.ne.b32 p, %98, 0;\n"
      "wgmma.mma_async.sync.aligned.m64n192k16.f32.bf16.bf16 "
      "{%0,%1,%2,%3,%4,%5,%6,%7,%8,%9,%10,%11,%12,%13,%14,%15,"
      "%16,%17,%18,%19,%20,%21,%22,%23,%24,%25,%26,%27,%28,%29,%30,%31,"
      "%32,%33,%34,%35,%36,%37,%38,%39,%40,%41,%42,%43,%44,%45,%46,%47,"
      "%48,%49,%50,%51,%52,%53,%54,%55,%56,%57,%58,%59,%60,%61,%62,%63,"
      "%64,%65,%66,%67,%68,%69,%70,%71,%72,%73,%74,%75,%76,%77,%78,%79,"
      "%80,%81,%82,%83,%84,%85,%86,%87,%88,%89,%90,%91,%92,%93,%94,%95}, "
      "%96, %97, p, 1, 1, 0, 0;\n}\n"
      : "+f"(d[OFF + 0]), "+f"(d[OFF + 1]), "+f"(d[OFF + 2]), "+f"(d[OFF + 3]), "+f"(d[OFF + 4]), "+f"(d[OFF + 5]),
        "+f"(d[OFF + 6]), "+f"(d[OFF + 7]), "+f"(d[OFF + 8]), "+f"(d[OFF + 9]), "+f"(d[OFF + 10]), "+f"(d[OFF + 11]),
        "+f"(d[OFF + 12]), "+f"(d[OFF + 13]), "+f"(d[OFF + 14]), "+f"(d[OFF + 15]), "+f"(d[OFF + 16]), "+f"(d[OFF + 17]),
        "+f"(d[OFF + 18]), "+f"(d[OFF + 19]), "+f"(d[OFF + 20]), "+f"(d[OFF + 21]), "+f"(d[OFF + 22]), "+f"(d[OFF + 23]),
        "+f"(d[OFF + 24]), "+f"(d[OFF + 25]), "+f"(d[OFF + 26]), "+f"(d[OFF + 27]), "+f"(d[OFF + 28]), "+f"(d[OFF + 29]),
        "+f"(d[OFF + 30]), "+f"(d[OFF + 31]), "+f"(d[OFF + 32]), "+f"(d[OFF + 33]), "+f"(d[OFF + 34]), "+f"(d[OFF + 35]),
        "+f"(d[OFF + 36]), "+f"(d[OFF + 37]), "+f"(d[OFF + 38]), "+f"(d[OFF + 39]), "+f"(d[OFF + 40]), "+f"(d[OFF + 41]),
        "+f"(d[OFF + 42]), "+f"(d[OFF + 43]), "+f"(d[OFF + 44]), "+f"(d[OFF + 45]), "+f"(d[OFF + 46]), "+f"(d[OFF + 47]),
        "+f"(d[OFF + 48]), "+f"(d[OFF + 49]), "+f"(d[OFF + 50]), "+f"(d[OFF + 51]), "+f"(d[OFF + 52]), "+f"(d[OFF + 53]),
        "+f"(d[OFF + 54]), "+f"(d[OFF + 55]), "+f"(d[OFF + 56]), "+f"(d[OFF + 57]), "+f"(d[OFF + 58]), "+f"(d[OFF + 59]),
        "+f"(d[OFF + 60]), "+f"(d[OFF + 61]), "+f"(d[OFF + 62]), "+f"(d[OFF + 63]), "+f"(d[OFF + 64]), "+f"(d[OFF + 65]),
        "+f"(d[OFF + 66]), "+f"(d[OFF + 67]), "+f"(d[OFF + 68]), "+f"(d[OFF + 69]), "+f"(d[OFF + 70]), "+f"(d[OFF + 71]),
        "+f"(d[OFF + 72]), "+f"(d[OFF + 73]), "+f"(d[OFF + 74]), "+f"(d[OFF + 75]), "+f"(d[OFF + 76]), "+f"(d[OFF + 77]),
        "+f"(d[OFF + 78]), "+f"(d[OFF + 79]), "+f"(d[OFF + 80]), "+f"(d[OFF + 81]), "+f"(d[OFF + 82]), "+f"(d[OFF + 83]),
        "+f"(d[OFF + 84]), "+f"(d[OFF + 85]), "+f"(d[OFF + 86]), "+f"(d[OFF + 87]), "+f"(d[OFF + 88]), "+f"(d[OFF + 89]),
        "+f"(d[OFF + 90]), "+f"(d[OFF + 91]), "+f"(d[OFF + 92]), "+f"(d[OFF + 93]), "+f"(d[OFF + 94]), "+f"(d[OFF + 95])
      : "l"(desc_a), "l"(desc_b), "r"(scale_d));
}

template <int OFF, int NN>
__device__ __forceinline__ void wg_m192z(float (&d)[NN], uint64_t desc_a, uint64_t desc_b, int scale_d) {
  asm volatile(
      "{\n.reg .pred p;\nsetp.ne.b32 p, %98, 0;\n"
      "wgmma.mma_async.sync.aligned.m64n192k16.f32.bf16.bf16 "
      "{%0,%1,%2,%3,%4,%5,%6,%7,%8,%9,%10,%11,%12,%13,%14,%15,"
      "%16,%17,%18,%19,%20,%21,%22,%23,%24,%25,%26,%27,%28,%29,%30,%31,"
      "%32,%33,%34,%35,%36,%37,%38,%39,%40,%41,%42,%43,%44,%45,%46,%47,"
      "%48,%49,%50,%51,%52,%53,%54,%55,%56,%57,%58,%59,%60,%61,%62,%63,"
      "%64,%65,%66,%67,%68,%69,%70,%71,%72,%73,%74,%75,%76,%77,%78,%79,"
      "%80,%81,%82,%83,%84,%85,%86,%87,%88,%89,%90,%91,%92,%93,%94,%95}, "
      "%96, %97, p, 1, 1, 0, 0;\n}\n"
      : "=f"(d[OFF + 0]), "=f"(d[OFF + 1]), "=f"(d[OFF + 2]), "=f"(d[OFF + 3]), "=f"(d[OFF + 4]), "=f"(d[OFF + 5]),
        "=f"(d[OFF + 6]), "=f"(d[OFF + 7]), "=f"(d[OFF + 8]), "=f"(d[OFF + 9]), "=f"(d[OFF + 10]), "=f"(d[OFF + 11]),
        "=f"(d[OFF + 12]), "=f"(d[OFF + 13]), "=f"(d[OFF + 14]), "=f"(d[OFF + 15]), "=f"(d[OFF + 16]), "=f"(d[OFF + 17]),
        "=f"(d[OFF + 18]), "=f"(d[OFF + 19]), "=f"(d[OFF + 20]), "=f"(d[OFF + 21]), "=f"(d[OFF + 22]), "=f"(d[OFF + 23]),
        "=f"(d[OFF + 24]), "=f"(d[OFF + 25]), "=f"(d[OFF + 26]), "=f"(d[OFF + 27]), "=f"(d[OFF + 28]), "=f"(d[OFF + 29]),
        "=f"(d[OFF + 30]), "=f"(d[OFF + 31]), "=f"(d[OFF + 32]), "=f"(d[OFF + 33]), "=f"(d[OFF + 34]), "=f"(d[OFF + 35]),
        "=f"(d[OFF + 36]), "=f"(d[OFF + 37]), "=f"(d[OFF + 38]), "=f"(d[OFF + 39]), "=f"(d[OFF + 40]), "=f"(d[OFF + 41]),
        "=f"(d[OFF + 42]), "=f"(d[OFF + 43]), "=f"(d[OFF + 44]), "=f"(d[OFF + 45]), "=f"(d[OFF + 46]), "=f"(d[OFF + 47]),
        "=f"(d[OFF + 48]), "=f"(d[OFF + 49]), "=f"(d[OFF + 50]), "=f"(d[OFF + 51]), "=f"(d[OFF + 52]), "=f"(d[OFF + 53]),
        "=f"(d[OFF + 54]), "=f"(d[OFF + 55]), "=f"(d[OFF + 56]), "=f"(d[OFF + 57]), "=f"(d[OFF + 58]), "=f"(d[OFF + 59]),
        "=f"(d[OFF + 60]), "=f"(d[OFF + 61]), "=f"(d[OFF + 62]), "=f"(d[OFF + 63]), "=f"(d[OFF + 64]), "=f"(d[OFF + 65]),
        "=f"(d[OFF + 66]), "=f"(d[OFF + 67]), "=f"(d[OFF + 68]), "=f"(d[OFF + 69]), "=f"(d[OFF + 70]), "=f"(d[OFF + 71]),
        "=f"(d[OFF + 72]), "=f"(d[OFF + 73]), "=f"(d[OFF + 74]), "=f"(d[OFF + 75]), "=f"(d[OFF + 76]), "=f"(d[OFF + 77]),
        "=f"(d[OFF + 78]), "=f"(d[OFF + 79]), "=f"(d[OFF + 80]), "=f"(d[OFF + 81]), "=f"(d[OFF + 82]), "=f"(d[OFF + 83]),
        "=f"(d[OFF + 84]), "=f"(d[OFF + 85]), "=f"(d[OFF + 86]), "=f"(d[OFF + 87]), "=f"(d[OFF + 88]), "=f"(d[OFF + 89]),
        "=f"(d[OFF + 90]), "=f"(d[OFF + 91]), "=f"(d[OFF + 92]), "=f"(d[OFF + 93]), "=f"(d[OFF + 94]), "=f"(d[OFF + 95])
      : "l"(desc_a), "l"(desc_b), "r"(scale_d));
}

template <int OFF, int NN>
__device__ __forceinline__ void wg_m64t(float (&d)[NN], uint64_t desc_a, uint64_t desc_b, int scale_d) {
  asm volatile(
      "{\n.reg .pred p;\nsetp.ne.b32 p, %34, 0;\n"
      "wgmma.mma_async.sync.aligned.m64n64k16.f32.bf16.bf16 "
      "{%0,%1,%2,%3,%4,%5,%6,%7,%8,%9,%10,%11,%12,%13,%14,%15,"
      "%16,%17,%18,%19,%20,%21,%22,%23,%24,%25,%26,%27,%28,%29,%30,%31}, "
      "%32, %33, p, 1, 1, 0, 1;\n}\n"
      : "+f"(d[OFF + 0]), "+f"(d[OFF + 1]), "+f"(d[OFF + 2]), "+f"(d[OFF + 3]), "+f"(d[OFF + 4]), "+f"(d[OFF + 5]),
        "+f"(d[OFF + 6]), "+f"(d[OFF + 7]), "+f"(d[OFF + 8]), "+f"(d[OFF + 9]), "+f"(d[OFF + 10]), "+f"(d[OFF + 11]),
        "+f"(d[OFF + 12]), "+f"(d[OFF + 13]), "+f"(d[OFF + 14]), "+f"(d[OFF + 15]), "+f"(d[OFF + 16]), "+f"(d[OFF + 17]),
        "+f"(d[OFF + 18]), "+f"(d[OFF + 19]), "+f"(d[OFF + 20]), "+f"(d[OFF + 21]), "+f"(d[OFF + 22]), "+f"(d[OFF + 23]),
        "+f"(d[OFF + 24]), "+f"(d[OFF + 25]), "+f"(d[OFF + 26]), "+f"(d[OFF + 27]), "+f"(d[OFF + 28]), "+f"(d[OFF + 29]),
        "+f"(d[OFF + 30]), "+f"(d[OFF + 31])
      : "l"(desc_a), "l"(desc_b), "r"(scale_d));
}

template <int OFF, int NN>
__device__ __forceinline__ void wg_m64tz(float (&d)[NN], uint64_t desc_a, uint64_t desc_b, int scale_d) {
  asm volatile(
      "{\n.reg .pred p;\nsetp.ne.b32 p, %34, 0;\n"
      "wgmma.mma_async.sync.aligned.m64n64k16.f32.bf16.bf16 "
      "{%0,%1,%2,%3,%4,%5,%6,%7,%8,%9,%10,%11,%12,%13,%14,%15,"
      "%16,%17,%18,%19,%20,%21,%22,%23,%24,%25,%26,%27,%28,%29,%30,%31}, "
      "%32, %33, p, 1, 1, 0, 1;\n}\n"
      : "=f"(d[OFF + 0]), "=f"(d[OFF + 1]), "=f"(d[OFF + 2]), "=f"(d[OFF + 3]), "=f"(d[OFF + 4]), "=f"(d[OFF + 5]),
        "=f"(d[OFF + 6]), "=f"(d[OFF + 7]), "=f"(d[OFF + 8]), "=f"(d[OFF + 9]), "=f"(d[OFF + 10]), "=f"(d[OFF + 11]),
        "=f"(d[OFF + 12]), "=f"(d[OFF + 13]), "=f"(d[OFF + 14]), "=f"(d[OFF + 15]), "=f"(d[OFF + 16]), "=f"(d[OFF + 17]),
        "=f"(d[OFF + 18]), "=f"(d[OFF + 19]), "=f"(d[OFF + 20]), "=f"(d[OFF + 21]), "=f"(d[OFF + 22]), "=f"(d[OFF + 23]),
        "=f"(d[OFF + 24]), "=f"(d[OFF + 25]), "=f"(d[OFF + 26]), "=f"(d[OFF + 27]), "=f"(d[OFF + 28]), "=f"(d[OFF + 29]),
        "=f"(d[OFF + 30]), "=f"(d[OFF + 31])
      : "l"(desc_a), "l"(desc_b), "r"(scale_d));
}

template <int OFF, int NN>
__device__ __forceinline__ void wg_d96(float (&d)[NN], uint32_t a0, uint32_t a1, uint32_t a2, uint32_t a3,
                                       uint64_t desc_b, int scale_d) {
  asm volatile(
      "{\n.reg .pred p;\nsetp.ne.b32 p, %53, 0;\n"
      "wgmma.mma_async.sync.aligned.m64n96k16.f32.bf16.bf16 "
      "{%0,%1,%2,%3,%4,%5,%6,%7,%8,%9,%10,%11,%12,%13,%14,%15,"
      "%16,%17,%18,%19,%20,%21,%22,%23,%24,%25,%26,%27,%28,%29,%30,%31,"
      "%32,%33,%34,%35,%36,%37,%38,%39,%40,%41,%42,%43,%44,%45,%46,%47}, "
      "{%48,%49,%50,%51}, %52, p, 1, 1, 0;\n}\n"
      : "+f"(d[OFF + 0]), "+f"(d[OFF + 1]), "+f"(d[OFF + 2]), "+f"(d[OFF + 3]), "+f"(d[OFF + 4]), "+f"(d[OFF + 5]),
        "+f"(d[OFF + 6]), "+f"(d[OFF + 7]), "+f"(d[OFF + 8]), "+f"(d[OFF + 9]), "+f"(d[OFF + 10]), "+f"(d[OFF + 11]),
        "+f"(d[OFF + 12]), "+f"(d[OFF + 13]), "+f"(d[OFF + 14]), "+f"(d[OFF + 15]), "+f"(d[OFF + 16]), "+f"(d[OFF + 17]),
        "+f"(d[OFF + 18]), "+f"(d[OFF + 19]), "+f"(d[OFF + 20]), "+f"(d[OFF + 21]), "+f"(d[OFF + 22]), "+f"(d[OFF + 23]),
        "+f"(d[OFF + 24]), "+f"(d[OFF + 25]), "+f"(d[OFF + 26]), "+f"(d[OFF + 27]), "+f"(d[OFF + 28]), "+f"(d[OFF + 29]),
        "+f"(d[OFF + 30]), "+f"(d[OFF + 31]), "+f"(d[OFF + 32]), "+f"(d[OFF + 33]), "+f"(d[OFF + 34]), "+f"(d[OFF + 35]),
        "+f"(d[OFF + 36]), "+f"(d[OFF + 37]), "+f"(d[OFF + 38]), "+f"(d[OFF + 39]), "+f"(d[OFF + 40]), "+f"(d[OFF + 41]),
        "+f"(d[OFF + 42]), "+f"(d[OFF + 43]), "+f"(d[OFF + 44]), "+f"(d[OFF + 45]), "+f"(d[OFF + 46]), "+f"(d[OFF + 47])
      : "r"(a0), "r"(a1), "r"(a2), "r"(a3), "l"(desc_b), "r"(scale_d));
}

template <int OFF, int NN>
__device__ __forceinline__ void wg_d96z(float (&d)[NN], uint32_t a0, uint32_t a1, uint32_t a2, uint32_t a3,
                                       uint64_t desc_b, int scale_d) {
  asm volatile(
      "{\n.reg .pred p;\nsetp.ne.b32 p, %53, 0;\n"
      "wgmma.mma_async.sync.aligned.m64n96k16.f32.bf16.bf16 "
      "{%0,%1,%2,%3,%4,%5,%6,%7,%8,%9,%10,%11,%12,%13,%14,%15,"
      "%16,%17,%18,%19,%20,%21,%22,%23,%24,%25,%26,%27,%28,%29,%30,%31,"
      "%32,%33,%34,%35,%36,%37,%38,%39,%40,%41,%42,%43,%44,%45,%46,%47}, "
      "{%48,%49,%50,%51}, %52, p, 1, 1, 0;\n}\n"
      : "=f"(d[OFF + 0]), "=f"(d[OFF + 1]), "=f"(d[OFF + 2]), "=f"(d[OFF + 3]), "=f"(d[OFF + 4]), "=f"(d[OFF + 5]),
        "=f"(d[OFF + 6]), "=f"(d[OFF + 7]), "=f"(d[OFF + 8]), "=f"(d[OFF + 9]), "=f"(d[OFF + 10]), "=f"(d[OFF + 11]),
        "=f"(d[OFF + 12]), "=f"(d[OFF + 13]), "=f"(d[OFF + 14]), "=f"(d[OFF + 15]), "=f"(d[OFF + 16]), "=f"(d[OFF + 17]),
        "=f"(d[OFF + 18]), "=f"(d[OFF + 19]), "=f"(d[OFF + 20]), "=f"(d[OFF + 21]), "=f"(d[OFF + 22]), "=f"(d[OFF + 23]),
        "=f"(d[OFF + 24]), "=f"(d[OFF + 25]), "=f"(d[OFF + 26]), "=f"(d[OFF + 27]), "=f"(d[OFF + 28]), "=f"(d[OFF + 29]),
        "=f"(d[OFF + 30]), "=f"(d[OFF + 31]), "=f"(d[OFF + 32]), "=f"(d[OFF + 33]), "=f"(d[OFF + 34]), "=f"(d[OFF + 35]),
        "=f"(d[OFF + 36]), "=f"(d[OFF + 37]), "=f"(d[OFF + 38]), "=f"(d[OFF + 39]), "=f"(d[OFF + 40]), "=f"(d[OFF + 41]),
        "=f"(d[OFF + 42]), "=f"(d[OFF + 43]), "=f"(d[OFF + 44]), "=f"(d[OFF + 45]), "=f"(d[OFF + 46]), "=f"(d[OFF + 47])
      : "r"(a0), "r"(a1), "r"(a2), "r"(a3), "l"(desc_b), "r"(scale_d));
}

template <int OFF, int NN>
__device__ __forceinline__ void wg_s104(float (&d)[NN], uint32_t a0, uint32_t a1, uint32_t a2, uint32_t a3,
                                       uint64_t desc_b, int scale_d, uint32_t meta) {
  asm volatile(
      "{\n.reg .pred p;\nsetp.ne.b32 p, %57, 0;\n"
      "wgmma.mma_async.sp.sync.aligned.m64n104k32.f32.bf16.bf16 "
      "{%0,%1,%2,%3,%4,%5,%6,%7,%8,%9,%10,%11,%12,%13,%14,%15,"
      "%16,%17,%18,%19,%20,%21,%22,%23,%24,%25,%26,%27,%28,%29,%30,%31,"
      "%32,%33,%34,%35,%36,%37,%38,%39,%40,%41,%42,%43,%44,%45,%46,%47,"
      "%48,%49,%50,%51}, "
      "{%52,%53,%54,%55}, %56, %58, 0, p, 1, 1, 0;\n}\n"
      : "+f"(d[OFF + 0]), "+f"(d[OFF + 1]), "+f"(d[OFF + 2]), "+f"(d[OFF + 3]), "+f"(d[OFF + 4]), "+f"(d[OFF + 5]),
        "+f"(d[OFF + 6]), "+f"(d[OFF + 7]), "+f"(d[OFF + 8]), "+f"(d[OFF + 9]), "+f"(d[OFF + 10]), "+f"(d[OFF + 11]),
        "+f"(d[OFF + 12]), "+f"(d[OFF + 13]), "+f"(d[OFF + 14]), "+f"(d[OFF + 15]), "+f"(d[OFF + 16]), "+f"(d[OFF + 17]),
        "+f"(d[OFF + 18]), "+f"(d[OFF + 19]), "+f"(d[OFF + 20]), "+f"(d[OFF + 21]), "+f"(d[OFF + 22]), "+f"(d[OFF + 23]),
        "+f"(d[OFF + 24]), "+f"(d[OFF + 25]), "+f"(d[OFF + 26]), "+f"(d[OFF + 27]), "+f"(d[OFF + 28]), "+f"(d[OFF + 29]),
        "+f"(d[OFF + 30]), "+f"(d[OFF + 31]), "+f"(d[OFF + 32]), "+f"(d[OFF + 33]), "+f"(d[OFF + 34]), "+f"(d[OFF + 35]),
        "+f"(d[OFF + 36]), "+f"(d[OFF + 37]), "+f"(d[OFF + 38]), "+f"(d[OFF + 39]), "+f"(d[OFF + 40]), "+f"(d[OFF + 41]),
        "+f"(d[OFF + 42]), "+f"(d[OFF + 43]), "+f"(d[OFF + 44]), "+f"(d[OFF + 45]), "+f"(d[OFF + 46]), "+f"(d[OFF + 47]),
        "+f"(d[OFF + 48]), "+f"(d[OFF + 49]), "+f"(d[OFF + 50]), "+f"(d[OFF + 51])
      : "r"(a0), "r"(a1), "r"(a2), "r"(a3), "l"(desc_b), "r"(scale_d), "r"(meta));
}

template <int OFF, int NN>
__device__ __forceinline__ void wg_s104z(float (&d)[NN], uint32_t a0, uint32_t a1, uint32_t a2, uint32_t a3,
                                       uint64_t desc_b, int scale_d, uint32_t meta) {
  asm volatile(
      "{\n.reg .pred p;\nsetp.ne.b32 p, %57, 0;\n"
      "wgmma.mma_async.sp.sync.aligned.m64n104k32.f32.bf16.bf16 "
      "{%0,%1,%2,%3,%4,%5,%6,%7,%8,%9,%10,%11,%12,%13,%14,%15,"
      "%16,%17,%18,%19,%20,%21,%22,%23,%24,%25,%26,%27,%28,%29,%30,%31,"
      "%32,%33,%34,%35,%36,%37,%38,%39,%40,%41,%42,%43,%44,%45,%46,%47,"
      "%48,%49,%50,%51}, "
      "{%52,%53,%54,%55}, %56, %58, 0, p, 1, 1, 0;\n}\n"
      : "=f"(d[OFF + 0]), "=f"(d[OFF + 1]), "=f"(d[OFF + 2]), "=f"(d[OFF + 3]), "=f"(d[OFF + 4]), "=f"(d[OFF + 5]),
        "=f"(d[OFF + 6]), "=f"(d[OFF + 7]), "=f"(d[OFF + 8]), "=f"(d[OFF + 9]), "=f"(d[OFF + 10]), "=f"(d[OFF + 11]),
        "=f"(d[OFF + 12]), "=f"(d[OFF + 13]), "=f"(d[OFF + 14]), "=f"(d[OFF + 15]), "=f"(d[OFF + 16]), "=f"(d[OFF + 17]),
        "=f"(d[OFF + 18]), "=f"(d[OFF + 19]), "=f"(d[OFF + 20]), "=f"(d[OFF + 21]), "=f"(d[OFF + 22]), "=f"(d[OFF + 23]),
        "=f"(d[OFF + 24]), "=f"(d[OFF + 25]), "=f"(d[OFF + 26]), "=f"(d[OFF + 27]), "=f"(d[OFF + 28]), "=f"(d[OFF + 29]),
        "=f"(d[OFF + 30]), "=f"(d[OFF + 31]), "=f"(d[OFF + 32]), "=f"(d[OFF + 33]), "=f"(d[OFF + 34]), "=f"(d[OFF + 35]),
        "=f"(d[OFF + 36]), "=f"(d[OFF + 37]), "=f"(d[OFF + 38]), "=f"(d[OFF + 39]), "=f"(d[OFF + 40]), "=f"(d[OFF + 41]),
        "=f"(d[OFF + 42]), "=f"(d[OFF + 43]), "=f"(d[OFF + 44]), "=f"(d[OFF + 45]), "=f"(d[OFF + 46]), "=f"(d[OFF + 47]),
        "=f"(d[OFF + 48]), "=f"(d[OFF + 49]), "=f"(d[OFF + 50]), "=f"(d[OFF + 51])
      : "r"(a0), "r"(a1), "r"(a2), "r"(a3), "l"(desc_b), "r"(scale_d), "r"(meta));
}

template <int OFF, int NN>
__device__ __forceinline__ void wg_s48(float (&d)[NN], uint32_t a0, uint32_t a1, uint32_t a2, uint32_t a3,
                                       uint64_t desc_b, int scale_d, uint32_t meta) {
  asm volatile(
      "{\n.reg .pred p;\nsetp.ne.b32 p, %29, 0;\n"
      "wgmma.mma_async.sp.sync.aligned.m64n48k32.f32.bf16.bf16 "
      "{%0,%1,%2,%3,%4,%5,%6,%7,%8,%9,%10,%11,%12,%13,%14,%15,"
      "%16,%17,%18,%19,%20,%21,%22,%23}, "
      "{%24,%25,%26,%27}, %28, %30, 0, p, 1, 1, 0;\n}\n"
      : "+f"(d[OFF + 0]), "+f"(d[OFF + 1]), "+f"(d[OFF + 2]), "+f"(d[OFF + 3]), "+f"(d[OFF + 4]), "+f"(d[OFF + 5]),
        "+f"(d[OFF + 6]), "+f"(d[OFF + 7]), "+f"(d[OFF + 8]), "+f"(d[OFF + 9]), "+f"(d[OFF + 10]), "+f"(d[OFF + 11]),
        "+f"(d[OFF + 12]), "+f"(d[OFF + 13]), "+f"(d[OFF + 14]), "+f"(d[OFF + 15]), "+f"(d[OFF + 16]), "+f"(d[OFF + 17]),
        "+f"(d[OFF + 18]), "+f"(d[OFF + 19]), "+f"(d[OFF + 20]), "+f"(d[OFF + 21]), "+f"(d[OFF + 22]), "+f"(d[OFF + 23])
      : "r"(a0), "r"(a1), "r"(a2), "r"(a3), "l"(desc_b), "r"(scale_d), "r"(meta));
}

template <int OFF, int NN>
__device__ __forceinline__ void wg_s48z(float (&d)[NN], uint32_t a0, uint32_t a1, uint32_t a2, uint32_t a3,
                                       uint64_t desc_b, int scale_d, uint32_t meta) {
  asm volatile(
      "{\n.reg .pred p;\nsetp.ne.b32 p, %29, 0;\n"
      "wgmma.mma_async.sp.sync.aligned.m64n48k32.f32.bf16.bf16 "
      "{%0,%1,%2,%3,%4,%5,%6,%7,%8,%9,%10,%11,%12,%13,%14,%15,"
      "%16,%17,%18,%19,%20,%21,%22,%23}, "
      "{%24,%25,%26,%27}, %28, %30, 0, p, 1, 1, 0;\n}\n"
      : "=f"(d[OFF + 0]), "=f"(d[OFF + 1]), "=f"(d[OFF + 2]), "=f"(d[OFF + 3]), "=f"(d[OFF + 4]), "=f"(d[OFF + 5]),
        "=f"(d[OFF + 6]), "=f"(d[OFF + 7]), "=f"(d[OFF + 8]), "=f"(d[OFF + 9]), "=f"(d[OFF + 10]), "=f"(d[OFF + 11]),
        "=f"(d[OFF + 12]), "=f"(d[OFF + 13]), "=f"(d[OFF + 14]), "=f"(d[OFF + 15]), "=f"(d[OFF + 16]), "=f"(d[OFF + 17]),
        "=f"(d[OFF + 18]), "=f"(d[OFF + 19]), "=f"(d[OFF + 20]), "=f"(d[OFF + 21]), "=f"(d[OFF + 22]), "=f"(d[OFF + 23])
      : "r"(a0), "r"(a1), "r"(a2), "r"(a3), "l"(desc_b), "r"(scale_d), "r"(meta));
}

template <int OFF, int NN>
__device__ __forceinline__ void wg_s56(float (&d)[NN], uint32_t a0, uint32_t a1, uint32_t a2, uint32_t a3,
                                       uint64_t desc_b, int scale_d, uint32_t meta) {
  asm volatile(
      "{\n.reg .pred p;\nsetp.ne.b32 p, %33, 0;\n"
      "wgmma.mma_async.sp.sync.aligned.m64n56k32.f32.bf16.bf16 "
      "{%0,%1,%2,%3,%4,%5,%6,%7,%8,%9,%10,%11,%12,%13,%14,%15,"
      "%16,%17,%18,%19,%20,%21,%22,%23,%24,%25,%26,%27}, "
      "{%28,%29,%30,%31}, %32, %34, 0, p, 1, 1, 0;\n}\n"
      : "+f"(d[OFF + 0]), "+f"(d[OFF + 1]), "+f"(d[OFF + 2]), "+f"(d[OFF + 3]), "+f"(d[OFF + 4]), "+f"(d[OFF + 5]),
        "+f"(d[OFF + 6]), "+f"(d[OFF + 7]), "+f"(d[OFF + 8]), "+f"(d[OFF + 9]), "+f"(d[OFF + 10]), "+f"(d[OFF + 11]),
        "+f"(d[OFF + 12]), "+f"(d[OFF + 13]), "+f"(d[OFF + 14]), "+f"(d[OFF + 15]), "+f"(d[OFF + 16]), "+f"(d[OFF + 17]),
        "+f"(d[OFF + 18]), "+f"(d[OFF + 19]), "+f"(d[OFF + 20]), "+f"(d[OFF + 21]), "+f"(d[OFF + 22]), "+f"(d[OFF + 23]),
        "+f"(d[OFF + 24]), "+f"(d[OFF + 25]), "+f"(d[OFF + 26]), "+f"(d[OFF + 27])
      : "r"(a0), "r"(a1), "r"(a2), "r"(a3), "l"(desc_b), "r"(scale_d), "r"(meta));
}

template <int OFF, int NN>
__device__ __forceinline__ void wg_s56z(float (&d)[NN], uint32_t a0, uint32_t a1, uint32_t a2, uint32_t a3,
                                       uint64_t desc_b, int scale_d, uint32_t meta) {
  asm volatile(
      "{\n.reg .pred p;\nsetp.ne.b32 p, %33, 0;\n"
      "wgmma.mma_async.sp.sync.aligned.m64n56k32.f32.bf16.bf16 "
      "{%0,%1,%2,%3,%4,%5,%6,%7,%8,%9,%10,%11,%12,%13,%14,%15,"
      "%16,%17,%18,%19,%20,%21,%22,%23,%24,%25,%26,%27}, "
      "{%28,%29,%30,%31}, %32, %34, 0, p, 1, 1, 0;\n}\n"
      : "=f"(d[OFF + 0]), "=f"(d[OFF + 1]), "=f"(d[OFF + 2]), "=f"(d[OFF + 3]), "=f"(d[OFF + 4]), "=f"(d[OFF + 5]),
        "=f"(d[OFF + 6]), "=f"(d[OFF + 7]), "=f"(d[OFF + 8]), "=f"(d[OFF + 9]), "=f"(d[OFF + 10]), "=f"(d[OFF + 11]),
        "=f"(d[OFF + 12]), "=f"(d[OFF + 13]), "=f"(d[OFF + 14]), "=f"(d[OFF + 15]), "=f"(d[OFF + 16]), "=f"(d[OFF + 17]),
        "=f"(d[OFF + 18]), "=f"(d[OFF + 19]), "=f"(d[OFF + 20]), "=f"(d[OFF + 21]), "=f"(d[OFF + 22]), "=f"(d[OFF + 23]),
        "=f"(d[OFF + 24]), "=f"(d[OFF + 25]), "=f"(d[OFF + 26]), "=f"(d[OFF + 27])
      : "r"(a0), "r"(a1), "r"(a2), "r"(a3), "l"(desc_b), "r"(scale_d), "r"(meta));
}

template <int OFF, int NN>
__device__ __forceinline__ void wg_s64t(float (&d)[NN], uint32_t a0, uint32_t a1, uint32_t a2, uint32_t a3,
                                       uint64_t desc_b, int scale_d, uint32_t meta) {
  asm volatile(
      "{\n.reg .pred p;\nsetp.ne.b32 p, %37, 0;\n"
      "wgmma.mma_async.sp.sync.aligned.m64n64k32.f32.bf16.bf16 "
      "{%0,%1,%2,%3,%4,%5,%6,%7,%8,%9,%10,%11,%12,%13,%14,%15,"
      "%16,%17,%18,%19,%20,%21,%22,%23,%24,%25,%26,%27,%28,%29,%30,%31}, "
      "{%32,%33,%34,%35}, %36, %38, 0, p, 1, 1, 1;\n}\n"
      : "+f"(d[OFF + 0]), "+f"(d[OFF + 1]), "+f"(d[OFF + 2]), "+f"(d[OFF + 3]), "+f"(d[OFF + 4]), "+f"(d[OFF + 5]),
        "+f"(d[OFF + 6]), "+f"(d[OFF + 7]), "+f"(d[OFF + 8]), "+f"(d[OFF + 9]), "+f"(d[OFF + 10]), "+f"(d[OFF + 11]),
        "+f"(d[OFF + 12]), "+f"(d[OFF + 13]), "+f"(d[OFF + 14]), "+f"(d[OFF + 15]), "+f"(d[OFF + 16]), "+f"(d[OFF + 17]),
        "+f"(d[OFF + 18]), "+f"(d[OFF + 19]), "+f"(d[OFF + 20]), "+f"(d[OFF + 21]), "+f"(d[OFF + 22]), "+f"(d[OFF + 23]),
        "+f"(d[OFF + 24]), "+f"(d[OFF + 25]), "+f"(d[OFF + 26]), "+f"(d[OFF + 27]), "+f"(d[OFF + 28]), "+f"(d[OFF + 29]),
        "+f"(d[OFF + 30]), "+f"(d[OFF + 31])
      : "r"(a0), "r"(a1), "r"(a2), "r"(a3), "l"(desc_b), "r"(scale_d), "r"(meta));
}

template <int OFF, int NN>
__device__ __forceinline__ void wg_s64t1(float (&d)[NN], uint32_t a0, uint32_t a1, uint32_t a2, uint32_t a3,
                                       uint64_t desc_b, int scale_d, uint32_t meta) {
  asm volatile(
      "{\n.reg .pred p;\nsetp.ne.b32 p, %37, 0;\n"
      "wgmma.mma_async.sp.sync.aligned.m64n64k32.f32.bf16.bf16 "
      "{%0,%1,%2,%3,%4,%5,%6,%7,%8,%9,%10,%11,%12,%13,%14,%15,"
      "%16,%17,%18,%19,%20,%21,%22,%23,%24,%25,%26,%27,%28,%29,%30,%31}, "
      "{%32,%33,%34,%35}, %36, %38, 1, p, 1, 1, 1;\n}\n"
      : "+f"(d[OFF + 0]), "+f"(d[OFF + 1]), "+f"(d[OFF + 2]), "+f"(d[OFF + 3]), "+f"(d[OFF + 4]), "+f"(d[OFF + 5]),
        "+f"(d[OFF + 6]), "+f"(d[OFF + 7]), "+f"(d[OFF + 8]), "+f"(d[OFF + 9]), "+f"(d[OFF + 10]), "+f"(d[OFF + 11]),
        "+f"(d[OFF + 12]), "+f"(d[OFF + 13]), "+f"(d[OFF + 14]), "+f"(d[OFF + 15]), "+f"(d[OFF + 16]), "+f"(d[OFF + 17]),
        "+f"(d[OFF + 18]), "+f"(d[OFF + 19]), "+f"(d[OFF + 20]), "+f"(d[OFF + 21]), "+f"(d[OFF + 22]), "+f"(d[OFF + 23]),
        "+f"(d[OFF + 24]), "+f"(d[OFF + 25]), "+f"(d[OFF + 26]), "+f"(d[OFF + 27]), "+f"(d[OFF + 28]), "+f"(d[OFF + 29]),
        "+f"(d[OFF + 30]), "+f"(d[OFF + 31])
      : "r"(a0), "r"(a1), "r"(a2), "r"(a3), "l"(desc_b), "r"(scale_d), "r"(meta));
}

template <int OFF, int NN>
__device__ __forceinline__ void wg_s64tz(float (&d)[NN], uint32_t a0, uint32_t a1, uint32_t a2, uint32_t a3,
                                       uint64_t desc_b, int scale_d, uint32_t meta) {
  asm volatile(
      "{\n.reg .pred p;\nsetp.ne.b32 p, %37, 0;\n"
      "wgmma.mma_async.sp.sync.aligned.m64n64k32.f32.bf16.bf16 "
      "{%0,%1,%2,%3,%4,%5,%6,%7,%8,%9,%10,%11,%12,%13,%14,%15,"
      "%16,%17,%18,%19,%20,%21,%22,%23,%24,%25,%26,%27,%28,%29,%30,%31}, "
      "{%32,%33,%34,%35}, %36, %38, 0, p, 1, 1, 1;\n}\n"
      : "=f"(d[OFF + 0]), "=f"(d[OFF + 1]), "=f"(d[OFF + 2]), "=f"(d[OFF + 3]), "=f"(d[OFF + 4]), "=f"(d[OFF + 5]),
        "=f"(d[OFF + 6]), "=f"(d[OFF + 7]), "=f"(d[OFF + 8]), "=f"(d[OFF + 9]), "=f"(d[OFF + 10]), "=f"(d[OFF + 11]),
        "=f"(d[OFF + 12]), "=f"(d[OFF + 13]), "=f"(d[OFF + 14]), "=f"(d[OFF + 15]), "=f"(d[OFF + 16]), "=f"(d[OFF + 17]),
        "=f"(d[OFF + 18]), "=f"(d[OFF + 19]), "=f"(d[OFF + 20]), "=f"(d[OFF + 21]), "=f"(d[OFF + 22]), "=f"(d[OFF + 23]),
        "=f"(d[OFF + 24]), "=f"(d[OFF + 25]), "=f"(d[OFF + 26]), "=f"(d[OFF + 27]), "=f"(d[OFF + 28]), "=f"(d[OFF + 29]),
        "=f"(d[OFF + 30]), "=f"(d[OFF + 31])
      : "r"(a0), "r"(a1), "r"(a2), "r"(a3), "l"(desc_b), "r"(scale_d), "r"(meta));
}

__device__ __forceinline__ int g2_inv(int ch) { return 32 * (ch >> 5) + 8 * ((ch >> 1) & 3) + 2 * ((ch >> 3) & 3) + (ch & 1); }
__host__ __device__ __forceinline__ uint32_t wimg_off(int n, int k) {
  return (uint32_t)(k >> 6) * kWChunk + (uint32_t)n * 128 + (uint32_t)((((k & 63) >> 3) ^ (n & 7)) << 4) + (k & 7) * 2;
}
__host__ __device__ constexpr int w2piece(int h, int c) { return c == 2 ? 2 + h : 4 * h + c; }
__device__ __forceinline__ uint32_t w2img_off(int n, int k) { return wimg_off(n % 96, k & 63) + w2piece(n >= 96, k >> 6) * (kWChunk / 2); }
__device__ __forceinline__ int qpix(int par, int t) {
  const int a = 2 * t + 13 * par - 6, b = t + 112 * par;
  return par ? min(a, b) : max(a, b);
}
__device__ __forceinline__ int woff(int par, int i, int r) {
  const int a = 99 * par + 6 - 8 * i;
  return par ? min(r, a) : max(r, a);
}

__device__ __forceinline__ void mma16816(float (&c)[4], uint32_t a0, uint32_t a1, uint32_t a2, uint32_t a3, uint32_t b0,
                                         uint32_t b1) {
  asm volatile(
      "mma.sync.aligned.m16n8k16.row.col.f32.bf16.bf16.f32 {%0,%1,%2,%3}, {%4,%5,%6,%7}, {%8,%9}, {%0,%1,%2,%3};"
      : "+f"(c[0]), "+f"(c[1]), "+f"(c[2]), "+f"(c[3])
      : "r"(a0), "r"(a1), "r"(a2), "r"(a3), "r"(b0), "r"(b1));
}

__device__ __forceinline__ void fold_w1(const int u, const __nv_bfloat16* __restrict__ wqkv, uint8_t* wimg) {
  const int g = (threadIdx.x >> 2) & 7, l = threadIdx.x & 3;
  const int m0 = (u / 12) * 16, s = u % 12;
  uint4 A[12], B[12];
  const __nv_bfloat16* arow = wqkv + (m0 + 4 * (g >> 1) + (g & 1)) * 576 + 192 + 8 * l;
  const __nv_bfloat16* brow = wqkv + (16 * s + 4 * (g >> 1) + (g & 1)) * 576 + 8 * l;
#pragma unroll
  for (int i = 0; i < 12; i++) {
    A[i] = ldg128_nc(arow + (i & 1) * 2 * 576 + 32 * (i >> 1));
    B[i] = ldg128_nc(brow + (i & 1) * 2 * 576 + 32 * (i >> 1));
  }
  sched_fence();
  uint8_t* dst = wimg + wimg_off(m0 + g, 16 * s + 4 * l);
  float acc[4][4];
#pragma unroll
  for (int j = 0; j < 16; j++) acc[j >> 2][j & 3] = 0.f;
#pragma unroll
  for (int i = 0; i < 6; i++) {
    const uint4 &a0 = A[2 * i], &a1 = A[2 * i + 1];
#pragma unroll
    for (int nb = 0; nb < 2; nb++) {
      mma16816(acc[2 * nb], a0.x, a1.x, a0.y, a1.y, B[2 * i + nb].x, B[2 * i + nb].y);
      mma16816(acc[2 * nb + 1], a0.z, a1.z, a0.w, a1.w, B[2 * i + nb].z, B[2 * i + nb].w);
    }
  }
#pragma unroll
  for (int j = 0; j < 2; j++) {
    const uint2 v = make_uint2(pack_bf16((acc[0][2 * j] + acc[1][2 * j]) * kAlpha, (acc[0][2 * j + 1] + acc[1][2 * j + 1]) * kAlpha),
                               pack_bf16((acc[2][2 * j] + acc[3][2 * j]) * kAlpha, (acc[2][2 * j + 1] + acc[3][2 * j + 1]) * kAlpha));
    asm volatile("st.relaxed.gpu.global.v2.u32 [%0], {%1,%2};" ::"l"(dst + j * 1024), "r"(v.x), "r"(v.y) : "memory");
  }
}
__device__ __forceinline__ void fold_w2(const int u, const __nv_bfloat16* __restrict__ wqkv, const __nv_bfloat16* __restrict__ wo,
                                        uint8_t* wimg) {
  const int g = (threadIdx.x >> 2) & 7, l = threadIdx.x & 3;
  const int m0 = (u / 12) * 32, n0 = (u % 12) * 16;
  uint4 S[12];
  uint32_t L[96];
  const __nv_bfloat16* brow = wqkv + (n0 + 4 * (g >> 1) + (g & 1)) * 576 + 384 + 8 * l;
#pragma unroll
  for (int i = 0; i < 12; i++) S[i] = ldg128_nc(brow + (i & 1) * 2 * 576 + 32 * (i >> 1));
  const __nv_bfloat16* acol = wo + (8 * l) * 192 + m0 + 4 * g;
#pragma unroll
  for (int c = 0; c < 48; c++)
    asm volatile("ld.global.nc.v2.u32 {%0,%1}, [%2];" : "=r"(L[2 * c]), "=r"(L[2 * c + 1]) : "l"(acol + (32 * (c >> 3) + (c & 7)) * 192));
  const uint32_t off = w2_offset();
  sched_fence();
  uint8_t* img = wimg + off;
  float acc[4][4];
#pragma unroll
  for (int j = 0; j < 16; j++) acc[j >> 2][j & 3] = 0.f;
#pragma unroll
  for (int i = 0; i < 6; i++) {
#pragma unroll
    for (int h = 0; h < 2; h++) {
      const uint4 &s0 = S[2 * i], &s1 = S[2 * i + 1];
#pragma unroll
      for (int mt = 0; mt < 2; mt++) {
        const uint32_t* a = L + 16 * i + 8 * h + mt;
        const uint32_t a0 = __byte_perm(a[0], a[2], 0x5410), a1 = __byte_perm(a[0], a[2], 0x7632);
        const uint32_t a2 = __byte_perm(a[4], a[6], 0x5410), a3 = __byte_perm(a[4], a[6], 0x7632);
        mma16816(acc[2 * mt], a0, a1, a2, a3, h ? s0.z : s0.x, h ? s0.w : s0.y);
        mma16816(acc[2 * mt + 1], a0, a1, a2, a3, h ? s1.z : s1.x, h ? s1.w : s1.y);
      }
    }
  }
#pragma unroll
  for (int j = 0; j < 4; j++) {
    const float(&c0)[4] = acc[j & 2];
    const float(&c1)[4] = acc[(j & 2) + 1];
    asm volatile("st.relaxed.gpu.global.v2.u32 [%0], {%1,%2};" ::"l"(img + w2img_off(g2_inv(m0 + 4 * g + j), n0 + 4 * l)),
                 "r"(pack_bf16(c0[2 * (j & 1)], c0[2 * (j & 1) + 1])), "r"(pack_bf16(c1[2 * (j & 1)], c1[2 * (j & 1) + 1])) : "memory");
  }
}

__global__ void __launch_bounds__(256) fold_kernel(const __nv_bfloat16* __restrict__ wqkv,
                                                   const __nv_bfloat16* __restrict__ wo, uint8_t* wimg) {
  const int u = blockIdx.x * 8 + (threadIdx.x >> 5);
  if (u < 144) fold_w1(u, wqkv, wimg);
  else fold_w2(u - 144, wqkv, wo, wimg);
}

struct TileCoord { int pr, pc, I, J, up, kind; };
struct TileTable { uint16_t e[kCtas * 6], g[5][8][2], b[5][2][4]; };
inline void make_tiles(TileTable& tt) {
  for (int tile = 0; tile < kCtas * 6; tile++) {
    const int b = tile / 6, k = tile - 6 * b;
    const int p = b < 128 ? (tile - 672) >> 1 : b - 80;
    const int strip = b < 112 ? b >> 1 : b >= 128 && k >= 2 ? (b & 1) * 27 + (b & 2) * 14 : p + (p < 26 ? 1 : 3);
    const int pr = strip >= 28, J = (strip - pr * 28) >> 1, pc = strip & 1, up = b < 112 ? b & 1 : pr;
    const int first = b < 112 ? 8 - 2 * pr - up : 13 * pr, step = b < 112 ? k : k & 1;
    const int I = up ? first - step : first + step;
    const int kind = b < 112 ? (J == 13 * pc ? 1 + pc : 0) : I == 13 * pr ? 3 + pr : 0;
    tt.e[tile] = (uint16_t)(I | J << 4 | pr << 8 | pc << 9 | up << 10 | kind << 11);
  }
  for (int kind = 0; kind < 5; kind++) {
    const bool col = kind == 1 || kind == 2;
    auto off = [kind](int t) { return kind == 0 ? 2 * t : kind & 1 ? t + (t == 7) : t + (t > 0); };
    for (int j = 0; j < 8; j++) {
      const int w = j >> 1, h = j & 1;
      tt.g[kind][j][0] = (uint16_t)(col ? 3 * off(w + 4 * h) : 3 * (kW * off(2 * w) + 8 * h));
      tt.g[kind][j][1] = (uint16_t)(128 * (col ? 5 : 5 + off(2 * w + 1) - off(2 * w)));
    }
    for (int i = 0; i < 2; i++) {
      const int w = kind == 0 ? 0 : kind & 1 ? 3 * i : 1 - i;
      tt.b[kind][i][0] = tt.g[kind][2 * w][0];
      tt.b[kind][i][1] = (uint16_t)(128 * (kind == 0 ? 0 : (col ? 3 : 1) + i));
      tt.b[kind][i][2] = (uint16_t)(2048 * w);
      tt.b[kind][i][3] = 0;
    }
  }
}
__device__ __forceinline__ int num_tiles() { return blockIdx.x < 128 ? 6 : 4; }
__device__ __forceinline__ TileCoord decode_tile(const TileTable& tt, int tile) {
  const uint32_t e = tt.e[tile];
  return TileCoord{(int)(e >> 8) & 1, (int)(e >> 9) & 1, (int)e & 15, (int)(e >> 4) & 15, (int)(e >> 10) & 1, (int)(e >> 11)};
}
__device__ __forceinline__ int halo_r0(const TileCoord& t) { return 8 * t.I + 6 * t.pr - 6; }
__device__ __forceinline__ int halo_c0(const TileCoord& t) { return min(max(8 * t.J + 6 * t.pc - 6, -3), 102); }

__device__ __forceinline__ uint32_t bar_full(uint32_t bars, int wg, int c) { return bars + (wg * 3 + c) * 8; }
__device__ __forceinline__ uint32_t bar_w1c(uint32_t bars, int c) { return bars + (6 + c) * 8; }
__device__ __forceinline__ uint32_t bar_w2(uint32_t bars) { return bars + 9 * 8; }
__device__ __forceinline__ uint32_t bar_x(uint32_t bars, int j, int c) { return bars + (j == 0 ? 10 : c ? 17 + c : 11) * 8; }
__device__ __forceinline__ uint32_t bar_w1q(uint32_t bars) { return bars + 12 * 8; }
__device__ __forceinline__ uint32_t bar_xf(uint32_t bars) { return bars + 13 * 8; }
__device__ __forceinline__ uint32_t bar_w2m(uint32_t bars) { return bars + 14 * 8; }
__device__ __forceinline__ uint32_t bar_redo(uint32_t bars) { return bars + 15 * 8; }
__device__ __forceinline__ uint32_t bar_wok(uint32_t bars) { return bars + 16 * 8; }
__device__ __forceinline__ uint32_t bar_go(uint32_t bars) { return bars + 17 * 8; }
__device__ __forceinline__ uint32_t bar_raw(uint32_t bars, int j = 0) { return bars + (21 + j) * 8; }
__device__ __forceinline__ uint32_t bar_w2a(uint32_t bars) { return bars + 20 * 8; }
constexpr int kNumBars = 22;

__device__ __forceinline__ uint64_t wdesc(uint64_t d0, int s) { return d0 + (((s >> 2) * kWChunk + (s & 3) * 32) >> 4); }

__device__ __forceinline__ uint32_t x_chunk(int k, int c) { return kXOff + (k == 0 ? kWChunk : 0) + (k & 1 ? 2 - c : c) * 8192; }
__device__ __forceinline__ uint32_t out_slot(int k, int nt) { return k + 1 < nt ? kW2Off + (~k & 1) * 2 * kWChunk : kW1Off + kWChunk; }
template <int I0, int I1>
__device__ __forceinline__ void store_rows(bool on, __nv_bfloat16* pA, __nv_bfloat16* pB, const uint32_t (&a)[24], const uint32_t (&b)[24]) {
#pragma unroll
  for (int i = 2 * I0; i < 2 * I1; i++) {
    const uint32_t* v = (i & 1 ? b : a) + 4 * (i >> 1);
    asm volatile("{\n.reg .pred p;\nsetp.ne.u32 p, %5, 0;\n@p st.global.v4.u32 [%0], {%1,%2,%3,%4};\n}\n" ::"l"((i & 1 ? pB : pA) + 32 * (i >> 1)),
                 "r"(v[0]), "r"(v[1]), "r"(v[2]), "r"(v[3]), "r"((uint32_t)on) : "memory");
  }
}
template <int I0, int I1>
__device__ __forceinline__ void stage_out(uint32_t sts, int wg, const uint32_t (&a)[24], const uint32_t (&b)[24]) {
  const uint32_t e = sts, o = sts ^ 64;
  const uint32_t ad[4] = {wg ? o + 1024 : e, wg ? e + 2048 : o, wg ? e : o + 1024, wg ? o : e + 2048};
#pragma unroll
  for (int i = I0; i < I1; i++) {
    const uint32_t* v = (i < 6 ? a : b) + 4 * (i % 6);
    asm volatile("st.shared.v4.u32 [%0], {%1,%2,%3,%4};" ::"r"(ad[i % 6 / 3 * 2 + (i % 3 == 1)] + (i % 3 == 2) * 1024 + (i / 6) * 12288),
                 "r"(v[0]), "r"(v[1]), "r"(v[2]), "r"(v[3]) : "memory");
  }
}
__device__ __forceinline__ uint32_t now_ns() {
  uint32_t t;
  asm volatile("mov.u32 %0, %globaltimer_lo;" : "=r"(t)::"memory");
  return t;
}
__device__ __forceinline__ void wait_clock(uint32_t t_start, uint32_t t) {
  while (now_ns() - t_start < t) { }
}
#define NAT_PRED(f, m) ".reg .pred p;\n.reg .b32 t;\nand.b32 t, " f ", " m ";\nsetp.ne.u32 p, t, 0;\n"
constexpr uint32_t kHiV = 1, kHiU = 8, kColB = 0x20, kInV = 0x100, kInU = 0x1000, kColA = 0x10000;
template <uint32_t M>
__device__ __forceinline__ float pick(const float* a, const float* b, uint32_t f) {
  float d;
  asm("{\n" NAT_PRED("%5", "%6") "add.f32 %0, %1, %2;\n@p add.f32 %0, %3, %4;\n}\n"
      : "=&f"(d) : "f"(a[0]), "f"(a[2]), "f"(b[0]), "f"(b[2]), "r"(f), "n"(M));
  return d;
}
template <uint32_t M>
__device__ __forceinline__ float sel(float a, float b, uint32_t f) {
  float d;
  asm("{\n" NAT_PRED("%3", "%4") "selp.f32 %0, %1, %2, p;\n}\n" : "=f"(d) : "f"(a), "f"(b), "r"(f), "n"(M));
  return d;
}
template <uint32_t M>
__device__ __forceinline__ void max_if(float& m, float v, uint32_t f) {
  asm("{\n" NAT_PRED("%2", "%3") "@p max.f32 %0, %0, %1;\n}\n" : "+f"(m) : "f"(v), "r"(f), "n"(M));
}
template <uint32_t M>
__device__ __forceinline__ void add_if(float& m, float v, uint32_t f) {
  asm("{\n" NAT_PRED("%2", "%3") "@p add.f32 %0, %0, %1;\n}\n" : "+f"(m) : "f"(v), "r"(f), "n"(M));
}
__device__ __forceinline__ void pick_v(const float* a, float* v, uint32_t f) {
  v[0] = pick<kHiV>(a, a + 16, f), v[1] = pick<kHiV>(a + 1, a + 17, f);
  v[2] = pick<kHiV * 2>(a + 4, a + 20, f), v[3] = pick<kHiV * 2>(a + 5, a + 21, f);
  v[4] = pick<kHiV * 4>(a + 8, a + 24, f), v[5] = pick<kHiV * 4>(a + 9, a + 25, f);
  v[6] = a[12] + a[14], v[7] = a[13] + a[15];
}
__device__ __forceinline__ void pick_u(const float* a, float* v, uint32_t f) {
#pragma unroll
  for (int c = 0; c < 3; c++) v[2 * c] = pick<kHiU>(a + 4 * c, a + 4 * c + 12, f), v[2 * c + 1] = pick<kHiU * 2>(a + 4 * c + 1, a + 4 * c + 13, f);
}
__device__ __forceinline__ uint32_t sign_bytes(uint32_t v, uint32_t sel) {
  uint32_t d;
  asm("prmt.b32 %0, %1, %1, %2;" : "=r"(d) : "r"(v), "r"(sel));
  return d;
}
__device__ __forceinline__ float own_max(const float (&v)[14], uint32_t f) {
  float m = sel<kInV>(fmaxf(v[0], v[1]), -INFINITY, f), m2 = sel<kInV * 2>(fmaxf(v[2], v[3]), -INFINITY, f);
  max_if<kInV * 4>(m, fmaxf(v[4], v[5]), f);
  max_if<kInV * 8>(m2, fmaxf(v[6], v[7]), f);
  max_if<kInU>(m, fmaxf(fmaxf(v[8], v[10]), v[12]), f);
  max_if<kInU * 2>(m2, fmaxf(fmaxf(v[9], v[11]), v[13]), f);
  return fmaxf(m, m2);
}
__device__ __forceinline__ float quad_max(float m) {
  const float a = __shfl_xor_sync(0xffffffffu, m, 1), b = __shfl_xor_sync(0xffffffffu, m, 2), c = __shfl_xor_sync(0xffffffffu, m, 3);
  return fmaxf(fmaxf(m, a), fmaxf(b, c));
}
__device__ __forceinline__ float row_rcp(const float (&v)[14], uint32_t f) {
  float s = sel<kInV>(v[0] + v[1], 0.f, f), s2 = sel<kInV * 2>(v[2] + v[3], 0.f, f);
  add_if<kInV * 4>(s, v[4] + v[5], f);
  add_if<kInV * 8>(s2, v[6] + v[7], f);
  add_if<kInU>(s, v[8] + v[10] + v[12], f);
  add_if<kInU * 2>(s2, v[9] + v[11] + v[13], f);
  s += s2;
  const float a = __shfl_xor_sync(0xffffffffu, s, 1), b = __shfl_xor_sync(0xffffffffu, s, 2), c = __shfl_xor_sync(0xffffffffu, s, 3);
  return rcp_approx((s + a) + (b + c));
}
__device__ __forceinline__ void route(const float (&v)[14], float s, const uint32_t (&rt)[9], uint32_t (&p)[14]) {
#pragma unroll
  for (int i = 0; i < 7; i++) {
    const uint32_t u = pack_bf16(v[2 * i] * s, v[2 * i + 1] * s);
    if (i < 4) p[i] = u & rt[i];
    if (i < 3) p[i + 4] = u & rt[i + 4];
    if (i >= 4) {
      p[i + 3] = u & rt[7];
      p[i + 6] = u & rt[8];
    }
  }
}

template <int C, int T0 = 0, int T1 = 7>
__device__ __forceinline__ void pv_chunk(float (&z)[32], const uint32_t (&pa)[14], const uint32_t (&pb)[14],
                                         const uint32_t (&meta)[4], uint64_t dV) {
#pragma unroll
  for (int t = T0; t < T1; t++) {
    if (t & 1)
      wg_s64t1<0, 32>(z, pa[2 * t], pb[2 * t], pa[2 * t + 1], pb[2 * t + 1], dV + ((2 * C * kChunkBytes + t * 2048) >> 4), 1,
                      meta[t >> 1]);
    else if (t > 0)
      wg_s64t<0, 32>(z, pa[2 * t], pb[2 * t], pa[2 * t + 1], pb[2 * t + 1], dV + ((2 * C * kChunkBytes + t * 2048) >> 4), 1,
                     meta[t >> 1]);
    else
      wg_s64tz<0, 32>(z, pa[0], pb[0], pa[1], pb[1], dV + ((2 * C * kChunkBytes) >> 4), 0, meta[0]);
  }
}
template <int C>
__device__ __forceinline__ void pack_z(const float (&z)[32], uint32_t (&za)[24], uint32_t (&zb)[24]) {
#pragma unroll
  for (int j = 0; j < 8; j++) {
    za[8 * C + j] = pack_bf16(z[4 * j], z[4 * j + 1]);
    zb[8 * C + j] = pack_bf16(z[4 * j + 2], z[4 * j + 3]);
  }
}

template <int H>
__device__ __forceinline__ void pack_out(const float (&ac)[48], uint32_t (&oa)[24], uint32_t (&ob)[24]) {
#pragma unroll
  for (int j = 0; j < 12; j++) {
    oa[12 * H + j] = pack_bf16(ac[4 * j], ac[4 * j + 1]);
    ob[12 * H + j] = pack_bf16(ac[4 * j + 2], ac[4 * j + 3]);
  }
}
struct Maps { CUtensorMap v6, v2, v14, u8, px[8], wv, wo; };
__device__ __forceinline__ void tma_prefetch_5d(const CUtensorMap* map, int c0, int c1, int c2, int c3, int c4) {
  asm volatile("cp.async.bulk.prefetch.tensor.5d.L2.global.tile [%0, {%1, %2, %3, %4, %5}];" ::"l"((uint64_t)map), "r"(c0), "r"(c1),
               "r"(c2), "r"(c3), "r"(c4) : "memory");
}
__device__ __forceinline__ int first_line(const TileCoord tc) { return 3 * (qpix(tc.pr, 8 * tc.I) * kW + qpix(tc.pc, 8 * tc.J)); }
__device__ __forceinline__ void load_px(const Maps& tm, const TileTable& tt, uint32_t dst, uint32_t bar, int line, int kind) {
#pragma unroll
  for (int i = 0; i < 2; i++) {
    if (i == 0 || kind != 0) {
      const CUtensorMap* map = (const CUtensorMap*)((const char*)tm.px + tt.b[kind][i][1]);
      if (bar) tma_load_5d(dst + tt.b[kind][i][2], map, bar, 0, 0, 0, 0, line + tt.b[kind][i][0]);
      else tma_prefetch_5d(map, 0, 0, 0, 0, line + tt.b[kind][i][0]);
    }
  }
}
__device__ __forceinline__ void store_px(const Maps& tm, const TileTable& tt, uint32_t buf, int line, int kind) {
#pragma unroll
  for (int i = 0; i < 8; i++) {
    const int j = 2 * (i & 3) + (i >> 2);
    asm volatile("cp.async.bulk.tensor.5d.global.shared::cta.tile.bulk_group [%0, {%2, %2, %2, %2, %3}], [%1];" ::"l"(
                     (uint64_t)tm.px + tt.g[kind][j][1]), "r"(buf + i * 3072), "r"(0), "r"(line + tt.g[kind][j][0]) : "memory");
  }
  asm volatile("cp.async.bulk.commit_group;" ::: "memory");
}
__device__ __noinline__ bool refetch(uint32_t base, const uint8_t* src, bool gap) {
  constexpr uint32_t bars = 1024 + kBarOff, cnt = bars + 192;
#pragma unroll 1
  for (uint32_t o = 0; o < kWBytes && !gap; o += 2048) {
    uint32_t mx = 0;
#pragma unroll
    for (int i = 0; i < 4; i++) {
      uint4 v;
      asm volatile("ld.shared.v4.u32 {%0,%1,%2,%3}, [%4];" : "=r"(v.x), "=r"(v.y), "=r"(v.z), "=r"(v.w)
                   : "r"(base + o + i * 512 + (threadIdx.x & 31) * 16));
      mx = __vimax3_u32(__vimax3_u32(mx, v.x, v.y), v.z, v.w);
    }
    gap = __any_sync(0xffffffffu, mx == kEmpty);
  }
  uint32_t n;
  asm volatile("ld.shared.u32 %0, [%1];" : "=r"(n) : "r"(cnt) : "memory");
  if (!gap || __any_sync(0xffffffffu, n > (1u << 12))) return false;
  asm volatile("bar.sync 15, 128;" ::: "memory");
  if (threadIdx.x == 0) {
    asm volatile("st.shared.u32 [%0], %1;" ::"r"(cnt), "r"(n + 1) : "memory");
    mbar_arrive_expect_tx(bar_redo(bars), kWBytes);
    bulk_load(base, src, kWBytes, bar_redo(bars));
  }
  __syncwarp();
  mbar_wait(bar_redo(bars), n & 1);
  return true;
}
template <int S0, int S1, int Z>
__device__ __forceinline__ void g2_steps(float (&ac)[48], const uint32_t (&za)[24], const uint32_t (&zb)[24], uint64_t d) {
#pragma unroll
  for (int s = S0; s < S1; s++) {
    const uint64_t ds = d + (((s >> 2 & 1) * (kWChunk / 2) + (s & 3) * 32) >> 4);
    if (s == Z) wg_d96z<0, 48>(ac, za[2 * s], zb[2 * s], za[2 * s + 1], zb[2 * s + 1], ds, 0);
    else wg_d96<0, 48>(ac, za[2 * s], zb[2 * s], za[2 * s + 1], zb[2 * s + 1], ds, 1);
  }
}

__device__ __forceinline__ void consumer(const int wg, __nv_bfloat16* out, const uint8_t* wimg, const uint32_t sbase,
                                         const uint32_t zero, const Maps& tm, const TileTable& tt) {
  const int tid = threadIdx.x & 127;
  const int w = __shfl_sync(0xffffffffu, tid >> 5, 0), lane = tid & 31;
  const uint64_t dK = make_desc(sbase, 16, 1024);
  const uint64_t dV = make_desc(sbase, kChunkBytes, 512, 2);
  const uint64_t dW1 = make_desc(sbase + kW1Off, 16, 1024);
  const uint64_t dX0 = make_desc(sbase + kW2Off + wg * 2 * kWChunk, 16, 1024), dY0 = make_desc(sbase + kW2Off + (1 - wg) * 2 * kWChunk, 16, 1024);
  const uint64_t dX2 = make_desc(sbase + kXOff + wg * (kWChunk / 2), 16, 1024), dY2 = make_desc(sbase + kXOff + (1 - wg) * (kWChunk / 2), 16, 1024);
  const uint32_t bars = sbase + kBarOff;
  int tile0 = blockIdx.x * kTilesPerCta;
  asm volatile("" : "+r"(tile0));
  const int nt = num_tiles();

  uint32_t pix = 0, geo[6] = {};
  const int l = lane & 3;
#pragma unroll 1
  for (int j = 4; j >= 0; j -= 2) {
    const TileCoord tc = decode_tile(tt, tile0 + wg + j);
    const bool col = tc.kind == 1 || tc.kind == 2;
    const int g = col ? lane >> 2 : 2 * w + ((lane >> 2) & 1), qc = col ? w : lane >> 3;
    const uint32_t pr = qpix(tc.pr, 8 * tc.I + g) * kW;
    if (j == nt - 2) pix = (pr + qpix(tc.pc, 8 * tc.J + qc)) | (pr + qpix(tc.pc, 8 * tc.J + qc + 4)) << 16;
    const int d = 8 * tc.J + 6 * tc.pc - 6 - halo_c0(tc);
    const int ro = woff(tc.pr, tc.I, g), coA = woff(tc.pc, tc.J, qc) + d, coB = woff(tc.pc, tc.J, qc + 4) + d - 3;
#pragma unroll
    for (int i = 5; i >= 2; i--) geo[i] = geo[i - 2];
    const uint32_t lr = 0x1FCu << ro;
    const uint32_t lv = lr >> (2 + (l >> 1)), lu = lr >> (2 * l + 2 * tc.up);
    const uint32_t t = __byte_perm(lv, lu, wg ? 0x4501 : 0x5410);
    geo[0] = (((t & 0x15u) | (lv & 0x40u)) * 0x02082080u & 0x80808080u) | (((t >> 8) & 0x15u) * 0x01041040u & 0x40404040u) |
             (__byte_perm(t << 5, t << 4, 0x7362) & 0x20202020u) | (nt == 6);
    const int dr = (ro - 1) & 7;
    const uint32_t hiv = (((1u << ((ro - (l >> 1) + 1) >> 1)) - 1u) ^ (wg ? 7u : 0u)) & 7u, hiu = (t >> 24) & 3u;
    const uint32_t ca = (1u << coA) - 1u;
    geo[1] = hiv * kHiV | hiu * kHiU | ((((1u << coB) - 1u) >> (2 * (l & 1))) & 3u) * kColB |
             (15u & ~((uint32_t)((dr & 1) == (l >> 1)) << (dr >> 1))) * kInV | ((t >> 16 | t >> 24) & 3u) * kInU | ca * kColA |
             (ca >> ((0x49 >> (2 * l)) & 3) & 1u) << 19 | (uint32_t)(l == 3) << 20 | (0x55u & ((1u << (2 * coB)) - 1u)) << 24;
  }
  keep_regs(geo);
  const int so = (lane >> 3) | (lane & 4);
  uint32_t sts = sbase + w * 3072 + so * 128 + (((lane & 3) ^ so) << 4);
  __nv_bfloat16* poA = out + 8 * l + (pix & 0xFFFFu) * kC + 96 * wg;
  __nv_bfloat16* poB = out + 8 * l + (pix >> 16) * kC + 96 * wg;
  asm volatile("" : "+l"(poA), "+l"(poB), "+r"(sts));
  uint32_t oa[24], ob[24];
#pragma unroll
  for (int j = 0; j < 24; j++) oa[j] = ob[j] = 0u;
  keep_regs(oa);
  keep_regs(ob);
  PROF(wg, 0);
  if (threadIdx.x == 0) GT(1);

  for (int k = wg; k < nt; k += 2) {
    const uint32_t ph = (k >> 1) & 1;
    const int it = k >> 1;
    uint32_t qa[24], qb[24], hok[3];
    uint32_t fl = geo[1];
    {
      float acc[96];
      const uint32_t xp = (k + (k > 0)) & 1;
      const uint32_t xok = mbar_test(bar_x(bars, k > 0, 0), xp);
      if (k > 0) nb_sync(1 + (1 - wg));
#pragma unroll
      for (int s = 0; s < 12; s++) {
        if (s == 0) mbar_wait_if(xok, bar_x(bars, k > 0, 0), xp);
        if (s == 0 && k < 2) PROF(wg, 1);
        if (s == 0) PROFS(2, wg, 2 + it * 12);
        if (s == 0 && w == 0 && k < 2) GT(20 + wg);
        if ((s & 3) == 0 && (k == 0 || s > 0)) {
          mbar_wait(k == 0 ? bar_w1c(bars, s >> 2) : bar_x(bars, 1, s >> 2), xp);
          PROFS(17, wg, 50 + (s >> 2));
        }
        if ((s & 3) == 0) wg_fence();
        const uint64_t dX = make_desc(sbase + x_chunk(k, s >> 2), 16, 1024) + 2 * (s & 3);
        if (s == 0) wg_m192z<0, 96>(acc, dX, dW1, 0);
        else wg_m192<0, 96>(acc, dX, wdesc(dW1, s), 1);
        if ((s & 3) == 3) wg_commit();
      }
      PROFS(13, wg, 13 + it * 12);
      if (NAT_MP > 2) {
        wg_wait<2>();
        if (k > 0) nb_arrive_p(0);
      }
      if (NAT_MP > 1) {
        wg_wait<1>();
        if (k > 0) nb_arrive_p(14);
      }
      wg_wait<0>();
      if (k > 0) nb_arrive_p(6);
      fence_regs(acc);
      PROFS(3, wg, 3 + it * 12);
#pragma unroll
      for (int j = 0; j < 24; j++) {
        qa[j] = pack_bf16(acc[4 * j], acc[4 * j + 1]);
        qb[j] = pack_bf16(acc[4 * j + 2], acc[4 * j + 3]);
      }
      keep_regs(qa);
      keep_regs(qb);
      sched_fence();
      if (k >= 2) {
        const uint32_t dst = sts + out_slot(k, nt);
        nb_sync(11);
        stage_out<0, 6>(dst, wg, oa, ob);
        nb_sync(12);
        stage_out<6, 12>(dst, wg, oa, ob);
      }
#pragma unroll
      for (int c = 0; c < 3; c++) hok[c] = mbar_test(bar_full(bars, wg, c), ph);
      if (k >= 2) {
        fence_proxy_async();
        nb_arrive_p(10);
      }
    }

    float aE[52], aO[24], bO[52], bE[28];
    const uint32_t mq = 0xEEEE4444u | zero;
    PROFS(4, wg, 4 + it * 12);

    mbar_wait_if(hok[0], bar_full(bars, wg, 0), ph);
    PROFS(14, wg, 40 + it * 3);
    if (w == 0 && k < 2) GT(22 + wg);
    if (k > 0) nb_sync(3 + (1 - wg));
    wg_fence();
#pragma unroll
    for (int ks = 0; ks < 6; ks++) {
      if (ks == NAT_P1) {
        mbar_wait_if(hok[1], bar_full(bars, wg, 1), ph);
        PROFS(14, wg, 41 + it * 3);
        wg_fence();
      }
      if (ks == NAT_P2) {
        mbar_wait_if(hok[2], bar_full(bars, wg, 2), ph);
        PROFS(14, wg, 42 + it * 3);
        wg_fence();
      }
      const uint64_t d = dK + ((ks * kChunkBytes) >> 4);
      if (ks == 0) wg_s104z<0, 52>(aE, qa[0], qa[1], qa[2], qa[3], d, 0, mq);
      else wg_s104<0, 52>(aE, qa[4 * ks], qa[4 * ks + 1], qa[4 * ks + 2], qa[4 * ks + 3], d, 1, mq);
      if (ks == 0) wg_s48z<0, 24>(aO, qa[0], qa[1], qa[2], qa[3], d + ((7 * 1024 + 64) >> 4), 0, mq);
      else if (ks < NAT_QA) wg_s48<0, 24>(aO, qa[4 * ks], qa[4 * ks + 1], qa[4 * ks + 2], qa[4 * ks + 3], d + ((7 * 1024 + 64) >> 4), 1, mq);
    }
    wg_commit();
#pragma unroll
    for (int ks = NAT_QA; ks < 6; ks++)
      wg_s48<0, 24>(aO, qa[4 * ks], qa[4 * ks + 1], qa[4 * ks + 2], qa[4 * ks + 3], dK + ((ks * kChunkBytes + 7 * 1024 + 64) >> 4), 1, mq);
    wg_commit();
    wg_s56z<0, 28>(bE, qb[0], qb[1], qb[2], qb[3], dK, 0, mq);
#pragma unroll
    for (int ks = 1; ks < 6; ks++) wg_s56<0, 28>(bE, qb[4 * ks], qb[4 * ks + 1], qb[4 * ks + 2], qb[4 * ks + 3], dK + ((ks * kChunkBytes) >> 4), 1, mq);
    wg_commit();
    wg_wait<2>();
    fence_regs(aE);
    PROFS(5, wg, 5 + it * 12);

    uint32_t pa[14], pb[14], meta[4];
    {
      float vA[14], vB[14];
      pick_v(aE, vA, fl);
      pick_u(aE + 28, vA + 8, fl);
      fence_regs(vA);
      if (k == 0) {
        if (__builtin_expect(__any_sync(0xffffffffu, vA[6] != vA[6]), 0)) {
          wg_wait<0>();
          fence_regs(aO);
          fence_regs(bE);
          if (refetch(sbase + kW1Off, wimg, false)) {
#pragma unroll
            for (int j = 0; j < 24; j++) oa[j] = ob[j] = 0u;
            k -= 2;
            continue;
          }
        }
        if (elect_one()) mbar_arrive(bar_xf(bars));
      }
      wg_fence();
      wg_s104z<0, 52>(bO, qb[0], qb[1], qb[2], qb[3], dK + 4, 0, mq);
#pragma unroll
      for (int ks = 1; ks < 6; ks++)
        wg_s104<0, 52>(bO, qb[4 * ks], qb[4 * ks + 1], qb[4 * ks + 2], qb[4 * ks + 3], dK + ((ks * kChunkBytes + 64) >> 4), 1, mq);
      wg_commit();
      if (k + 1 < nt) nb_arrive(1 + wg);
      uint32_t rt[9];
#pragma unroll
      for (int i = 0; i < 7; i++) rt[i] = sign_bytes(geo[0] << (i >> 2), 0x8888u + 0x1111u * (i & 3));
      rt[7] = sign_bytes(geo[0] << 2, 0x9988u);
      rt[8] = sign_bytes(geo[0] << 2, 0xBBAAu);
      keep_regs(rt);
      pa[13] = pb[13] = 0u;
      wg_wait<2>();
      keep_regs(qa);
      fence_regs(aO);
      float oA[6], eB[8];
      pick_u(aO, oA, fl);
      wg_wait<1>();
      fence_regs(bE);
      pick_v(bE, eB, fl);
      vA[8] = sel<kColA>(oA[0], vA[8], fl), vA[9] = sel<kColA>(oA[1], vA[9], fl);
      vA[10] = sel<kColA * 2>(oA[2], vA[10], fl), vA[11] = sel<kColA * 2>(oA[3], vA[11], fl);
      vA[12] = sel<kColA * 4>(oA[4], vA[12], fl), vA[13] = sel<kColA * 4>(oA[5], vA[13], fl);
      {
        const float m1 = __uint_as_float(0x88DD88DDu), m0 = __uint_as_float(0x88DDDD88u);
        meta[0] = 0xDD88DD88u ^ __byte_perm(fl, 0u, 0x3344);
        meta[1] = __float_as_uint(sel<kColA * 16>(sel<kColA>(m1, m0, fl), __uint_as_float(meta[0]), fl));
        meta[2] = __float_as_uint(sel<kColA * 8>(m1, m0, fl));
        meta[3] = __float_as_uint(sel<kColA * 4>(m1, m0, fl));
        keep_regs(meta);
      }
      float mA = own_max(vA, fl);
      fl |= __float_as_uint(eB[7]) & zero;
      fence_regs(eB);
      fence_regs(vA);
      asm volatile("" : "+f"(mA), "+r"(fl));
      sched_fence();
      wg_wait<0>();
      sched_fence();
      keep_regs(qb);
      fence_regs(bO);
      PROFS(6, wg, 6 + it * 12);
      if (w == 0) GT(24 + k);
      mA = quad_max(mA);
#pragma unroll
      for (int i = 0; i < 14; i++) vA[i] = ex2(vA[i] - mA);
      pick_v(bO, vB, fl);
      pick_u(bO + 28, vB + 8, fl);
#pragma unroll
      for (int i = 0; i < 8; i += 2) vB[i] = sel<kColB>(vB[i], eB[i], fl), vB[i + 1] = sel<kColB * 2>(vB[i + 1], eB[i + 1], fl);
      float mB = quad_max(own_max(vB, fl));
      if (NAT_SB) {
        fence_regs(vA);
        fence_regs(vB);
        asm volatile("" : "+f"(mB));
        sched_fence();
      }
      PROFS(7, wg, 7 + it * 12);
#pragma unroll
      for (int i = 0; i < 14; i++) vB[i] = ex2(vB[i] - mB);
      route(vA, row_rcp(vA, fl), rt, pa);
      route(vB, row_rcp(vB, fl), rt, pb);
    }
    PROFS(8, wg, 8 + it * 12);
    if (k == NAT_PK) PROFS(18, wg, 53);
    sched_fence();

    float ac0[48], ac1[48];
    {
      float z0[32], z1[32], z2[32];
      uint32_t za[24], zb[24];
      wg_fence();
      pv_chunk<0>(z0, pa, pb, meta, dV);
      wg_commit();
      pv_chunk<1>(z1, pa, pb, meta, dV);
      wg_commit();
      wg_wait<1>();
      if (k == NAT_PK) PROFS(18, wg, 54);
      if (k + 1 < nt) nb_arrive_p(7);
      pv_chunk<2, 0, 3>(z2, pa, pb, meta, dV);
      wg_commit();
      sched_fence();
      fence_regs(z0);
      pack_z<0>(z0, za, zb);
      sched_fence();
      wg_fence();
      pv_chunk<2, 3, 7>(z2, pa, pb, meta, dV);
      wg_commit();
      wg_wait<2>();
      if (k == NAT_PK) PROFS(19, wg, 55);
      if (k + 1 < nt) nb_arrive_p(8);
      if (k < 2) mbar_wait(k == 1 ? bar_wok(bars) : bar_w2a(bars), 0);
      wg_fence();
      g2_steps<0, 3, 0>(ac0, za, zb, dX0);
      wg_commit();
      sched_fence();
      fence_regs(z1);
      pack_z<1>(z1, za, zb);
      sched_fence();
      wg_fence();
      g2_steps<3, 4, 0>(ac0, za, zb, dX0);
      wg_commit();
      g2_steps<4, 8, 0>(ac0, za, zb, dX0);
      wg_commit();
      wg_wait<3>();
      if (k + 1 < nt) nb_arrive_p(9);
      else nb_arrive(11);
      if (k == NAT_PK) PROFS(20, wg, 56);
      keep_regs(pa);
      keep_regs(pb);
      keep_regs(meta);
      sched_fence();
      const uint32_t mok = mbar_test(bar_w2m(bars), k + 1 < nt ? k & 1 : ~k & 1);
      const uint32_t wp = k < 2 ? 0 : k + 1 < nt ? ~k & 1 : k & 1, wok = mbar_test(bar_w2(bars), wp);
      fence_regs(z2);
      pack_z<2>(z2, za, zb);
      keep_regs(za);
      keep_regs(zb);
      sched_fence();
      PROFS(9, wg, 9 + it * 12);
      wg_wait<1>();
      if (k > 0 && k + 1 < nt) nb_arrive(11);
      mbar_wait_if(mok, bar_w2m(bars), k & 1);
      wg_fence();
      g2_steps<8, 12, 0>(ac0, za, zb, dX2);
      wg_commit();
      g2_steps<8, 12, 8>(ac1, za, zb, dY2);
      wg_commit();
      wg_wait<2>();
      if (k > 0 && k + 1 < nt) nb_arrive(12);
      mbar_wait_if(wok, bar_w2(bars), wp);
      wg_fence();
      g2_steps<0, 4, 8>(ac1, za, zb, dY0);
      wg_commit();
      wg_wait<2>();
      if (k + 2 < nt) nb_arrive_p(13);
      const bool direct = k + 2 >= nt;
      sched_fence();
      fence_regs(ac0);
      pack_out<0>(ac0, oa, ob);
      store_rows<0, NAT_D0>(direct, poA, poB, oa, ob);
      sched_fence();
      wg_fence();
      g2_steps<4, 8, 8>(ac1, za, zb, dY0);
      wg_commit();
      if (k + 1 < nt) nb_arrive(3 + wg);
      PROFS(10, wg, 10 + it * 12);
      wg_wait<2>();
      if (k + 2 < nt && (k > 0 || nt == 6)) nb_arrive_p(5);
      store_rows<NAT_D0, 3>(direct, poA, poB, oa, ob);
      __nv_bfloat16 *qA = poA - 192 * wg, *qB = poB - 192 * wg;
      if (k + 2 == nt) nb_sync(11);
      sched_fence();
      wg_wait<0>();
      fence_regs(ac1);
      pack_out<1>(ac1, oa, ob);
      asm volatile("" : "+l"(qA), "+l"(qB));
      store_rows<3, 6>(direct, qA, qB, oa, ob);
      if (k == 0) {
        uint32_t m[2] = {oa[0], oa[1]};
#pragma unroll
        for (int i = 2; i < 24; i++) asm("max.NaN.bf16x2 %0, %0, %1;" : "+r"(m[i & 1]) : "r"(oa[i]));
        asm("max.NaN.bf16x2 %0, %0, %1;" : "+r"(m[0]) : "r"(m[1]));
        uint32_t nan;
        asm volatile("{\n.reg .pred p;\nsetp.ne.u32 p, %1, 0;\nbar.red.or.pred p, 15, 128, p;\nselp.u32 %0, 1, 0, p;\n}\n"
                     : "=r"(nan) : "r"(((m[0] & 0x7FFF7FFFu) + 0x007F007Fu) & 0x80008000u) : "memory");
        if (__builtin_expect(__any_sync(0xffffffffu, nan), 0)) {
          for (int c = 0; c < 3 && __any_sync(0xffffffffu, geo[2] & 1u); c++) mbar_wait(bar_x(bars, 1, c), 1);
          for (bool first = true; __any_sync(0xffffffffu, refetch(sbase + kW2Off, wimg + w2_offset(), first)); first = false) { }
          wg_fence();
          g2_steps<0, 8, 0>(ac0, za, zb, dX0);
          g2_steps<8, 12, 0>(ac0, za, zb, dX2);
          g2_steps<8, 12, 8>(ac1, za, zb, dY2);
          g2_steps<0, 8, 8>(ac1, za, zb, dY0);
          wg_commit();
          wg_wait<0>();
          fence_regs(ac0);
          fence_regs(ac1);
          pack_out<0>(ac0, oa, ob);
          pack_out<1>(ac1, oa, ob);
          if (__any_sync(0xffffffffu, geo[2] & 1u)) {
            asm volatile("bar.sync 15, 128;" ::: "memory");
            if (w == 0 && elect_one()) {
              const TileCoord tc = decode_tile(tt, tile0 + 2);
              mbar_arrive_expect_tx(bar_raw(bars), kWChunk);
#pragma unroll 1
              for (int c = 0; c < 3; c++) load_px(tm, tt, sbase + x_chunk(2, c), bar_raw(bars), first_line(tc) + c, tc.kind);
            }
            __syncwarp();
            mbar_wait(bar_raw(bars), 0);
          }
        }
        if (nt < 6) nb_arrive_p(5);
        if (elect_one()) mbar_arrive(bar_wok(bars));
      }
      keep_regs(za);
      keep_regs(zb);
#pragma unroll
      for (int i = 0; i < 4; i++) geo[i] = geo[i + 2];
      keep_regs(oa);
      keep_regs(ob);
      PROFS(12, wg, 12 + it * 12);
      sched_fence();
    }
  }
  PROF(wg, 38);
  GT_DUMP();
  PROF_DUMP(wg);
}

struct HaloCols { int vj, vc, uj, uc; };
__device__ __forceinline__ HaloCols halo_cols(const TileCoord& tc) {
  const int c0 = halo_c0(tc);
  return HaloCols{c0 > 98, c0 > 98 ? 98 : c0 + 3, c0 < 0 ? -1 : 0, c0 < 0 ? 4 : c0};
}
__device__ __forceinline__ void first_halo(const Maps& tm, uint32_t sbase, const TileCoord tc, int i) {
  const HaloCols hc = halo_cols(tc);
  const uint32_t dst = sbase + i * kChunkBytes, bar = bar_full(sbase + kBarOff, 0, i >> 1);
  const int h0 = halo_r0(tc), ch = 24 * tc.pc + 4 * i;
  tma_load_5d(dst, &tm.v14, bar, ch, hc.vj, hc.vc, tc.pr, h0);
  tma_load_5d(dst + 7 * 1024, &tm.u8, bar, ch, hc.uj, h0 + (tc.up ? 0 : -2), tc.pr, hc.uc);
  tma_load_5d(dst + 10 * 1024, &tm.u8, bar, ch, hc.uj, h0 + (tc.up ? 8 : 6), tc.pr, hc.uc);
}
__device__ __forceinline__ void load_halo(const Maps& tm, uint32_t sbase, uint32_t bars, const TileCoord tc, int k, int c) {
  const HaloCols hc = halo_cols(tc);
  const int h6 = halo_r0(tc) + (tc.up ? 0 : 8), h2 = halo_r0(tc) + 6, h8 = halo_r0(tc) + (tc.up ? 0 : 6), ch = 24 * tc.pc + 8 * c;
  uint32_t dv = sbase + 2 * c * kChunkBytes, du = dv + 7 * 1024;
  if (((k ^ tc.up) & 1) == 0) dv += 4 * 1024, du += 3 * 1024;
  const uint32_t bar = bar_full(bars, k & 1, c);
  mbar_arrive_expect_tx(bar, 14 * 1024);
  nb_sync_p(7 + c);
#pragma unroll
  for (int h = 0; h < 2; h++) {
    tma_load_5d(dv + h * kChunkBytes, &tm.v6, bar, ch + 4 * h, hc.vj, hc.vc, tc.pr, h6);
    tma_load_5d(du + h * kChunkBytes, &tm.u8, bar, ch + 4 * h, hc.uj, h8, tc.pr, hc.uc);
    tma_load_5d(sbase + (2 * c + h) * kChunkBytes + 3 * 1024, &tm.v2, bar, ch + 4 * h, hc.vj, hc.vc, tc.pr, h2);
  }
  PROFS(15, 2, k * 4 + c);
}
__device__ __forceinline__ void gather_px(const __nv_bfloat16* __restrict__ x, uint32_t sbase, int k, const TileCoord tc) {
  const int lane = threadIdx.x & 31, g = lane >> 3;
  uint32_t ro[4], co[4];
#pragma unroll
  for (int i = 0; i < 4; i++) {
    ro[i] = qpix(tc.pr, 8 * tc.I + 2 * i + (g & 1)) * (kW * kC * 2) + 16 * (lane & 7);
    co[i] = qpix(tc.pc, 8 * tc.J + 2 * i + (g >> 1)) * (kC * 2);
  }
  const uint32_t dst = sbase + kXOff + g * 128 + (((lane & 7) ^ g) << 4);
  const int dq = k & 1 ? -128 : 128;
  keep_regs(ro);
  keep_regs(co);
  sched_fence();
  nb_sync_p(13);
  nb_sync_p(5);
#pragma unroll
  for (int i = 0; i < 16; i++) {
    const char* src = (const char*)x + (ro[i >> 2] + co[i & 3] + 128);
#pragma unroll
    for (int q = 0; q < 3; q++)
      asm volatile("cp.async.cg.shared.global [%0], [%1], 16;" ::"r"((dst ^ ((i & 1) * 576)) + (i >> 1) * 1024 + q * 8192), "l"(src + (q - 1) * dq) : "memory");
  }
  asm volatile("cp.async.wait_all;" ::: "memory");
  fence_proxy_async();
  __syncwarp();
  if (lane < 3) mbar_arrive(bar_x(sbase + kBarOff, 1, lane));
  __syncwarp();
}

__global__ void __launch_bounds__(384, 1)
nat_kernel(const __nv_bfloat16* __restrict__ x, __nv_bfloat16* out, const __nv_bfloat16* __restrict__ wqkv,
           const __nv_bfloat16* __restrict__ wo, uint8_t* wimg, const uint32_t zero,
           const __grid_constant__ Maps tm, const __grid_constant__ TileTable tt) {
  extern __shared__ uint8_t smem_raw[];
  constexpr uint32_t sbase = 1024;
  constexpr uint32_t bars = sbase + kBarOff;
  if (smem_u32(smem_raw) != sbase) __trap();
  const int tid = threadIdx.x;
  const uint32_t t_start = now_ns();
  if (tid == 0) GT(0);
  const int wid = __shfl_sync(0xffffffffu, tid >> 5, 0);
  const bool w2cta = blockIdx.x - 128 < 3 && wqkv != nullptr;
  if (wid >= 8) {
    asm volatile("setmaxnreg.dec.sync.aligned.u32 24;");
    const int c = wid & 3, lane = tid & 31;
    const int tile0 = blockIdx.x * kTilesPerCta, nt = num_tiles();
    uint32_t w2o = 0;
    if (c == 3) {
      asm volatile("bar.sync 13, 128;" ::: "memory");
      if (elect_one()) wait_clock(t_start, NAT_TM);
      __syncwarp();
      asm volatile("prefetch.tensormap [%0];" ::"l"((uint64_t)tm.px) : "memory");
      asm volatile("prefetch.tensormap [%0];" ::"l"((uint64_t)&tm.v6) : "memory");
      asm volatile("prefetch.tensormap [%0];" ::"l"((uint64_t)&tm.v2) : "memory");
      asm volatile("prefetch.tensormap [%0];" ::"l"((uint64_t)(tm.px + (blockIdx.x < 112 ? 5 : 6))) : "memory");
      asm volatile("prefetch.tensormap [%0];" ::"l"((uint64_t)(tm.px + 7)) : "memory");
      __nanosleep(NAT_TW2 - 2800);
      w2o = w2_offset();
      if (elect_one()) {
        mbar_arrive_expect_tx(bar_w2a(bars), kWChunk);
        mbar_arrive_expect_tx(bar_w2(bars), kWChunk);
        wait_clock(t_start, NAT_TW2);
        bulk_load(sbase + kW2Off, wimg + w2o, kWChunk, bar_w2a(bars));
        mbar_wait(bar_xf(bars), 0);
        bulk_load(sbase + kW2Off + 2 * kWChunk, wimg + (w2o + 2 * kWChunk), kWChunk, bar_w2(bars));
      }
      __syncwarp();
      if (nt < 6) {
#pragma unroll 1
        for (int k = 2; k < 4; k++) {
          gather_px(x, sbase, k, decode_tile(tt, tile0 + k));
        }
      }
      if (wqkv == nullptr) return;
      mbar_wait(bar_wok(bars), 0);
      if (lane == 0) asm volatile("red.relaxed.gpu.global.add.u32 [%0], 1;" ::"l"(g_flag) : "memory");
      if (blockIdx.x >= 48) return;
      if (lane == 0) {
        uint32_t v, it = 0;
        do {
          __nanosleep(2000);
          asm volatile("ld.relaxed.gpu.global.u32 %0, [%1];" : "=r"(v) : "l"(g_flag) : "memory");
        } while (v < gridDim.x && ++it < (1u << 16));
      }
      __syncwarp();
#pragma unroll
      for (int i = 0; i < 6; i++)
        stg128(wimg + ((i < 3 ? 0u : 3 * kWBytes - w2o) + blockIdx.x * 1536 + (i % 3) * 512 + lane * 16), kEmpty, kEmpty, kEmpty, kEmpty);
      if (lane == 0 && atomicAdd(g_flag + 32, 1u) == 47) {
        g_flag[0] = g_flag[32] = 0;
        g_flag[64] = w2o == kWBytes;
      }
      return;
    }
    if (!elect_one()) return;
    if (c == 0) {
      for (int i = 0; i < kNumBars; i++)
        if ((i != 0 && i != 10 || nt < 6) && (i != 21 || !w2cta)) mbar_init(bars + i * 8, i == 13 || i == 16 ? 4 : 1);
      asm volatile("st.shared.v2.u32 [%0], {%1,%1};" ::"r"(bars + 192), "r"(0) : "memory");
      asm volatile("fence.mbarrier_init.release.cluster;" ::: "memory");
      if (w2cta) asm volatile("bar.sync 10, 64;" ::: "memory");
      asm volatile("bar.arrive 0, 160;" ::: "memory");
      asm volatile("bar.arrive 14, 160;" ::: "memory");
      asm volatile("bar.arrive 13, 128;" ::: "memory");
      const TileCoord tc0 = decode_tile(tt, tile0);
      const HaloCols hc = halo_cols(tc0);
      const int h0 = halo_r0(tc0);
#pragma unroll
      for (int j = 0; j < 3; j++)
        if (j > 0 || nt < 6) mbar_arrive_expect_tx(bar_full(bars, 0, j), 2 * kChunkBytes);
      wait_clock(t_start, NAT_HP);
#pragma unroll
      for (int q = 8; q < 24; q += 8) {
        tma_prefetch_5d(&tm.v6, 24 * tc0.pc + q, hc.vj, hc.vc, tc0.pr, h0 + (tc0.up ? 0 : 8));
        tma_prefetch_5d(&tm.u8, 24 * tc0.pc + q, hc.uj, h0 + (tc0.up ? 0 : 6), tc0.pr, hc.uc);
        if (blockIdx.x >= 112) tma_prefetch_5d(&tm.v2, 24 * tc0.pc + q, hc.vj, hc.vc, tc0.pr, h0 + 6);
      }
#pragma unroll 1
      for (int i = nt < 6 ? 0 : 2; i < 7; i++) {
        if (i == NAT_H0) mbar_wait(bar_w1q(bars), 0);
        if (i == NAT_X1P) mbar_arrive(bar_go(bars));
        if (i < 6) first_halo(tm, sbase, tc0, i);
      }
      w2o = w2_offset();
    } else {
      asm volatile("bar.sync 13, 128;" ::: "memory");
      if (c == 2) {
        if (wqkv != nullptr && nt == 6) asm volatile("bar.sync 12, 64;" ::: "memory");
        const uint32_t c0 = clock();
        while ((uint32_t)clock() - c0 < NAT_TD) { }
        wait_clock(t_start, NAT_T0);
#pragma unroll
        for (int j = 0; j < 3; j++) {
          mbar_arrive_expect_tx(bar_w1c(bars, j), kWChunk);
          bulk_load(sbase + kW1Off + j * kWChunk, wimg + j * kWChunk, kWChunk, bar_w1c(bars, j));
        }
        mbar_arrive(bar_w1q(bars));
        GT(2);
      } else {
#pragma unroll 1
        for (int j = nt == 6; j < 2; j++) {
          const TileCoord tc = decode_tile(tt, tile0 + j);
          const int line = first_line(tc);
          if (j == 1) mbar_wait(bar_go(bars), 0);
#pragma unroll 1
          for (int q = 0; q < 3; q++) {
            load_px(tm, tt, sbase + x_chunk(j, q), bar_x(bars, j, q), line + q, tc.kind);
            if (j == 1 || q == 0) mbar_arrive_expect_tx(bar_x(bars, j, q), j ? 8192 : kWChunk);
          }
        }
        w2o = w2_offset();
        wait_clock(t_start, NAT_TW2);
      }
    }
#pragma unroll 1
    for (int k = 1; k < nt; k++) {
      const TileCoord tn = decode_tile(tt, tile0 + k + 1);
      const int line = first_line(tn);
      if (c == 1) {
#pragma unroll
        for (int q = 3 - NAT_MP; q < 3; q++) {
          const uint32_t n = q == 3 - NAT_MP ? q + 1 : 1, o = x_chunk(k, k & 1 ? q : q + 1 - n);
          nb_sync_p(q == 0 ? 0 : q == 1 ? 14 : 6);
          bulk_load(sbase + o, wimg + (w2o + o - kW2Off), n * 8192, bar_w2m(bars));
        }
        mbar_arrive_expect_tx(bar_w2m(bars), kWChunk);
      }
      if (c == 2) {
        if (k == 1) wait_clock(t_start, NAT_TX2);
        else __nanosleep(NAT_PFD);
#pragma unroll 1
        for (int q = 0; q < 3 && k < 5 && nt == 6; q++) load_px(tm, tt, 0, 0, line + q, tn.kind);
      }
      if (c == 2 && (blockIdx.x >= 112 || k == 5)) {
        const TileCoord tc = decode_tile(tt, tile0 + k);
        const HaloCols hc = halo_cols(tc);
        const int h8 = halo_r0(tc) + (tc.up ? 0 : 6);
#pragma unroll 1
        for (int q = 0; q < 24; q += 8) {
          tma_prefetch_5d(&tm.v6, 24 * tc.pc + q, hc.vj, hc.vc, tc.pr, h8);
          tma_prefetch_5d(&tm.v2, 24 * tc.pc + q, hc.vj, hc.vc, tc.pr, h8 + 6);
          tma_prefetch_5d(&tm.u8, 24 * tc.pc + q, hc.uj, h8, tc.pr, hc.uc);
        }
      }
      load_halo(tm, sbase, bars, decode_tile(tt, tile0 + k), k, c);
      if (c == 0 && k < 5 && nt == 6) {
#pragma unroll
        for (int q = 0; q < 3; q++) {
          if (q < 2) nb_sync_p(q ? 5 : 13);
          load_px(tm, tt, sbase + x_chunk(k + 1, q), bar_x(bars, 1, q), line + q, tn.kind);
          if (q != 1) mbar_arrive_expect_tx(bar_x(bars, 1, q), 8192);
        }
        mbar_arrive_expect_tx(bar_x(bars, 1, 1), 8192);
        PROFS(16, 2, k * 4 + 3);
      }
      if (c == 0 && k >= 2) {
        const TileCoord tp = decode_tile(tt, tile0 + k - 2);
        const int lp = first_line(tp);
        nb_sync_p(10);
        if (NAT_XW == 1 && k < 5 && nt == 6) mbar_wait(bar_x(bars, 1, 2), k & 1);
        if (NAT_XW > 1) __nanosleep(NAT_XW);
        store_px(tm, tt, sbase + out_slot(k, nt), lp, tp.kind);
        if (k + 1 < nt) {
          asm volatile("cp.async.bulk.wait_group.read 0;" ::: "memory");
          bulk_load(sbase + out_slot(k, nt), wimg + (w2o + out_slot(k, nt) - kW2Off), kWChunk, bar_w2(bars));
          mbar_arrive_expect_tx(bar_w2(bars), kWChunk);
        }
      }
    }
    asm volatile("cp.async.bulk.wait_group 0;" ::: "memory");
  } else {
    if (blockIdx.x < 128) {
      if ((wid == 4 || (wid == 5 && blockIdx.x - 2 < 16)) && wqkv != nullptr) {
        fold_w1(blockIdx.x - 2 < 16 ? 2 * blockIdx.x + wid - 6 : blockIdx.x + (blockIdx.x < 2 ? 0 : 16), wqkv, wimg);
        if (wid == 4) asm volatile("bar.arrive 12, 64;" ::: "memory");
        if (tid == 128) GT(7);
      }
      sched_fence();
      if (wid == 1 && elect_one()) {
        const TileCoord tc = decode_tile(tt, blockIdx.x * kTilesPerCta);
        mbar_init(bar_x(bars, 0, 0), 1);
        asm volatile("fence.mbarrier_init.release.cluster;" ::: "memory");
        mbar_arrive_expect_tx(bar_x(bars, 0, 0), kWChunk);
        GT(15);
#pragma unroll 1
        for (int q = 0; q < 3; q++) load_px(tm, tt, sbase + x_chunk(0, q), bar_x(bars, 0, 0), first_line(tc) + q, tc.kind);
        GT(16);
      }
      __syncwarp();
      sched_fence();
      if (wid == 2 && elect_one()) {
        const TileCoord tc = decode_tile(tt, blockIdx.x * kTilesPerCta);
        mbar_init(bar_full(bars, 0, 0), 1);
        asm volatile("fence.mbarrier_init.release.cluster;" ::: "memory");
        mbar_arrive_expect_tx(bar_full(bars, 0, 0), 2 * kChunkBytes);
        if (NAT_TH) wait_clock(t_start, NAT_TH);
        asm volatile("prefetch.tensormap [%0];" ::"l"((uint64_t)&tm.u8) : "memory");
        GT(17);
        first_halo(tm, sbase, tc, 0);
        first_halo(tm, sbase, tc, 1);
      }
      __syncwarp();
    }
    sched_fence();
    {
      if (w2cta) {
        const int q = blockIdx.x & 3;
        uint32_t w2o = 0;
        if (wid == 1 && elect_one()) {
          asm volatile("prefetch.tensormap [%0];" ::"l"((uint64_t)&tm.wo) : "memory");
#pragma unroll
          for (int j = 0; j < 3; j++) mbar_init(bar_raw(bars, j), 1);
          asm volatile("fence.mbarrier_init.release.cluster;" ::: "memory");
#pragma unroll
          for (int j = 0; j < 6; j++)
            asm volatile("cp.async.bulk.tensor.2d.shared::cluster.global.tile.mbarrier::complete_tx::bytes [%0], [%1, {%3, %4}], [%2];" ::"r"(
                             j < 3 ? sbase + j * 8192 : sbase + kW2Off + (j - 3) * kWChunk),
                         "l"((uint64_t)(j < 3 ? &tm.wv : &tm.wo)), "r"(bar_raw(bars, j < 3 ? 0 : j - 3)),
                         "r"(j < 3 ? 384 + 64 * j : 64 * (j - 3)), "r"(j < 3 ? 64 * q : 0) : "memory");
#pragma unroll
          for (int j = 0; j < 3; j++) mbar_arrive_expect_tx(bar_raw(bars, j), j ? kWChunk : 2 * kWChunk);
          w2o = w2_offset();
        }
        __syncwarp();
#pragma unroll 1
        for (int r = 0; r < 3; r++) {
          const int blk = 2 * r - 2 + (wid >> 2);
          if (blk < 3) {
            if (r > 0) {
              mbar_wait(bar_raw(bars, 0), 0);
              mbar_wait(bar_raw(bars, blk), 0);
            }
            if (tid == 0 && r == 1) GT(7);
            float acc[32];
            const uint64_t db = make_desc(sbase + kW2Off + max(blk, 0) * kWChunk, kWChunk, 1024);
            wg_fence();
            wg_m64tz<0, 32>(acc, make_desc(sbase, 16, 1024), db, 0);
#pragma unroll
            for (int s = 1; s < 12; s++) wg_m64t<0, 32>(acc, make_desc(sbase + (s >> 2) * 8192 + (s & 3) * 32, 16, 1024), db + s * 128, 1);
            wg_commit();
            wg_wait<0>();
            fence_regs(acc);
            if (tid == 0) GT(19);
            const int m = (tid >> 3) & 3;
#pragma unroll
            for (int j = 0; j < 8; j += 2) {
              const int n = g2_inv(8 * (j + (m >> 1)) + (tid & 7));
              asm volatile("stmatrix.sync.aligned.m8n8.x4.trans.shared.b16 [%0], {%1,%2,%3,%4};" ::"r"(
                               sbase + kW1Off + (blk + 2) * 8192 + n * 128 + (((2 * (wid & 3) + (m & 1)) ^ (n & 7)) << 4)),
                           "r"(pack_bf16(acc[4 * j], acc[4 * j + 1])), "r"(pack_bf16(acc[4 * j + 2], acc[4 * j + 3])),
                           "r"(pack_bf16(acc[4 * j + 4], acc[4 * j + 5])), "r"(pack_bf16(acc[4 * j + 6], acc[4 * j + 7])) : "memory");
            }
            fence_proxy_async();
          }
          if (tid == 0) GT(18);
          asm volatile("bar.sync 11, 256;" ::: "memory");
          if (wid == 1 && elect_one()) {
            asm volatile("{\n.reg .pred p;\nsetp.ne.s32 p, %3, 0;\n@p cp.async.bulk.global.shared::cta.bulk_group [%0], [%1], %2;\n}\n" ::"l"(
                             wimg + (w2o + w2piece(r >> 1, q) * (kWChunk / 2))),
                         "r"(sbase + kW1Off + 16384 + (r >> 1) * (kWChunk / 2)), "r"(kWChunk / 2), "r"(r) : "memory");
            asm volatile("cp.async.bulk.commit_group;" ::: "memory");
          }
          __syncwarp();
        }
        if (wid == 1) {
          if (elect_one()) asm volatile("cp.async.bulk.wait_group.read 0;" ::: "memory");
          if (tid == 32) GT(31);
          __syncwarp();
          asm volatile("bar.arrive 10, 64;" ::: "memory");
        }
      }
    }
    __syncwarp();
    if (wid < 4) asm volatile("bar.sync 0, 160;" ::: "memory");
    else asm volatile("bar.sync 14, 160;" ::: "memory");
    asm volatile("setmaxnreg.inc.sync.aligned.u32 240;");
    consumer(wid >> 2, out, wimg, sbase, zero, tm, tt);
  }
}

}

typedef CUresult (*PFN_encodeTiled)(CUtensorMap*, CUtensorMapDataType, cuuint32_t, void*, const cuuint64_t*,
                                    const cuuint64_t*, const cuuint32_t*, const cuuint32_t*, CUtensorMapInterleave,
                                    CUtensorMapSwizzle, CUtensorMapL2promotion, CUtensorMapFloatOOBfill);

extern "C" void kernel_launch(void* const* d_in, const int* in_sizes, int n_in, void* d_out, int out_size) {
  const __nv_bfloat16* x = (const __nv_bfloat16*)d_in[0];
  const __nv_bfloat16* wqkv = (const __nv_bfloat16*)d_in[1];
  const __nv_bfloat16* wo = (const __nv_bfloat16*)d_in[2];
  __nv_bfloat16* out = (__nv_bfloat16*)d_out;

  static PFN_encodeTiled encode = nullptr;
  static int num_sms = 0;
  static uint8_t* wimg = nullptr;
  if (!encode) {
    void* fn = nullptr;
    cudaDriverEntryPointQueryResult qres;
    cudaGetDriverEntryPoint("cuTensorMapEncodeTiled", &fn, cudaEnableDefault, &qres);
    encode = (PFN_encodeTiled)fn;
    cudaFuncSetAttribute(nat::nat_kernel, cudaFuncAttributeMaxDynamicSharedMemorySize, nat::kSmemBytes);
    cudaGetSymbolAddress((void**)&wimg, nat::g_wimg32);
    int dev = 0;
    cudaGetDevice(&dev);
    cudaDeviceGetAttribute(&num_sms, cudaDevAttrMultiProcessorCount, dev);
  }
  nat::Maps tm;
  cuuint32_t estr[5] = {1, 1, 1, 1, 1};
  {
    cuuint64_t vdim[5] = {48, 2, 105, 2, 112}, udim[5] = {48, 2, 112, 2, 105};
    cuuint64_t vstr[4] = {7 * 768, 768, 224 * 384, 2 * 224 * 384}, ustr[4] = {7 * 768, 2 * 224 * 384, 224 * 384, 768};
    CUtensorMap* maps[4] = {&tm.v6, &tm.v2, &tm.v14, &tm.u8};
    for (int i = 0; i < 4; i++) {
      cuuint32_t box[5] = {4, 2, i < 3 ? 4u : 8u, 1, i == 0 ? 6u : i == 1 ? 2u : i == 2 ? 14u : 3u};
      encode(maps[i], CU_TENSOR_MAP_DATA_TYPE_UINT32, 5, (void*)x, i < 3 ? vdim : udim, i < 3 ? vstr : ustr, box, estr,
             CU_TENSOR_MAP_INTERLEAVE_16B, CU_TENSOR_MAP_SWIZZLE_128B, CU_TENSOR_MAP_L2_PROMOTION_L2_128B, CU_TENSOR_MAP_FLOAT_OOB_FILL_NONE);
    }
  }
  for (int i = 0; i < 8; i++) {
    const cuuint32_t row = 224 * 384;
    const cuuint32_t shape[8][6] = {{2, 8, 4, 2 * row, 768, 4 * row}, {2, 8, 3, row, 768, 2 * row},     {2, 8, 1, 2 * row, 768, 4 * row},
                                    {8, 2, 3, 2 * row, 4 * 384, 384}, {8, 2, 1, 2 * row, 5 * 384, 384}, {4, 2, 3, 4 * row, 2 * row, 128},
                                    {4, 2, 3, 768, row, 128},         {4, 2, 3, 768, 2 * row, 128}};
    const cuuint32_t* sh = shape[i];
    cuuint64_t dim[5] = {64, sh[0], sh[1], sh[2], 224 * 224 * 3};
    cuuint64_t str[4] = {sh[3], sh[4], sh[5], 128};
    cuuint32_t box[5] = {64, sh[0], sh[1], sh[2], 1};
    encode(tm.px + i, CU_TENSOR_MAP_DATA_TYPE_BFLOAT16, 5, i < 5 ? (void*)x : (void*)out, dim, str, box, estr, CU_TENSOR_MAP_INTERLEAVE_NONE,
           CU_TENSOR_MAP_SWIZZLE_128B, i < 5 ? CU_TENSOR_MAP_L2_PROMOTION_L2_128B : CU_TENSOR_MAP_L2_PROMOTION_NONE,
           CU_TENSOR_MAP_FLOAT_OOB_FILL_NONE);
  }
  for (int i = 0; i < 2; i++) {
    cuuint64_t dim[2] = {i ? 192u : 576u, 192}, str[1] = {i ? 384u : 1152u};
    cuuint32_t box[2] = {64, i ? 192u : 64u};
    encode(i ? &tm.wo : &tm.wv, CU_TENSOR_MAP_DATA_TYPE_BFLOAT16, 2, i ? (void*)wo : (void*)wqkv, dim, str, box, estr,
           CU_TENSOR_MAP_INTERLEAVE_NONE, CU_TENSOR_MAP_SWIZZLE_128B, CU_TENSOR_MAP_L2_PROMOTION_L2_256B, CU_TENSOR_MAP_FLOAT_OOB_FILL_NONE);
  }
  nat::TileTable tt;
  nat::make_tiles(tt);
  const int grid = nat::kCtas;
  if (num_sms >= grid) {
    nat::nat_kernel<<<grid, 384, nat::kSmemBytes>>>(x, out, wqkv, wo, wimg, 0u, tm, tt);
  } else {
    nat::fold_kernel<<<27, 256>>>(wqkv, wo, wimg);
    nat::nat_kernel<<<grid, 384, nat::kSmemBytes>>>(x, out, nullptr, nullptr, wimg, 0u, tm, tt);
  }
}
```

```cpp
#include <cuda_runtime.h>
#include <cuda_bf16.h>
#include <cuda.h>
#include <stdint.h>

#define NAT_P1 2
#define NAT_P2 4
#define NAT_H0 2
#define NAT_T0 2100
#define NAT_TD 1200
#define NAT_TW2 4650
#define NAT_TX2 3800
#define NAT_X1P 6
#define NAT_PK 3
#define NAT_HP 1800
#define NAT_PFD 400
#define NAT_XW 200
#define NAT_MP 3
#define NAT_D0 1
#define NAT_TH 0
#define NAT_TM 1300
#define NAT_QA 1
#define NAT_SB 0
namespace nat {

constexpr int kW = 224, kC = 192;
constexpr int kCtas = 132;
constexpr int kTilesPerCta = 6;
constexpr float kAlpha = 0.07216878364870322f * 1.4426950408889634f;
constexpr uint32_t kChunkBytes = 13 * 1024;
constexpr uint32_t kWChunk = 192 * 128;
constexpr uint32_t kWBytes = 3 * kWChunk;
constexpr uint32_t kW1Off = 6 * kChunkBytes;
constexpr uint32_t kW2Off = kW1Off + kWBytes;
constexpr uint32_t kXOff = kW2Off + kWChunk;
constexpr uint32_t kBarOff = kW2Off + kWBytes;
constexpr uint32_t kProfOff = kBarOff + 208;
constexpr uint32_t kSmemBytes = kBarOff + 1024;

static_assert(kW1Off % 1024 == 0 && kW2Off % 1024 == 0 && kChunkBytes % 1024 == 0, "swizzle alignment");
static_assert(kSmemBytes <= 232448, "smem");

constexpr uint32_t kEmpty = 0xFFFFFFFFu;
#define NAT_R8(v) v, v, v, v, v, v, v, v
#define NAT_R2K(v) NAT_R8(NAT_R8(NAT_R8(v))), NAT_R8(NAT_R8(NAT_R8(v))), NAT_R8(NAT_R8(NAT_R8(v))), NAT_R8(NAT_R8(NAT_R8(v)))
#define NAT_IMG NAT_R8(NAT_R2K(kEmpty)), NAT_R2K(kEmpty)
__device__ __align__(1024) uint32_t g_wimg32[3 * kWBytes / 4] = {NAT_IMG, NAT_IMG, NAT_IMG};
static_assert(kWBytes / 4 == 9 * 2048, "initialiser");
__device__ __align__(128) uint32_t g_flag[96];
__device__ __forceinline__ uint32_t w2_offset() {
  uint32_t v;
  asm volatile("ld.relaxed.gpu.global.u32 %0, [%1];" : "=r"(v) : "l"(g_flag + 64) : "memory");
  return (1 + v) * kWBytes;
}

#define PROFS(id, wgid, slotid) do { } while (0)
#define PROF(wgid, slotid) do { } while (0)
#define PROF_DUMP(wgid) do { } while (0)

#define GT(slotid) do { } while (0)
#define GT_DUMP() do { } while (0)

__device__ __forceinline__ uint32_t smem_u32(const void* p) { return (uint32_t)__cvta_generic_to_shared(p); }

__device__ __forceinline__ void mbar_init(uint32_t bar, uint32_t count) {
  asm volatile("mbarrier.init.shared::cta.b64 [%0], %1;" ::"r"(bar), "r"(count) : "memory");
}
__device__ __forceinline__ void mbar_arrive(uint32_t bar) {
  asm volatile("mbarrier.arrive.shared::cta.b64 _, [%0];" ::"r"(bar) : "memory");
}
__device__ __forceinline__ void mbar_arrive_expect_tx(uint32_t bar, uint32_t bytes) {
  asm volatile("mbarrier.arrive.expect_tx.shared::cta.b64 _, [%0], %1;" ::"r"(bar), "r"(bytes) : "memory");
}
__device__ __forceinline__ void mbar_wait(uint32_t bar, uint32_t parity) {
  uint32_t ok;
  uint32_t it = 0;
  do {
    asm volatile(
        "{\n.reg .pred p;\n"
        "mbarrier.try_wait.parity.shared::cta.b64 p, [%1], %2;\n"
        "selp.u32 %0, 1, 0, p;\n}\n"
        : "=r"(ok)
        : "r"(bar), "r"(parity)
        : "memory");
    if (++it > (1u << 24)) break;
  } while (!ok);
}
__device__ __forceinline__ uint32_t mbar_test(uint32_t bar, uint32_t parity) {
  uint32_t ok;
  asm volatile("{\n.reg .pred p;\nmbarrier.test_wait.parity.shared::cta.b64 p, [%1], %2;\nselp.u32 %0, 1, 0, p;\n}\n"
               : "=r"(ok) : "r"(bar), "r"(parity) : "memory");
  return ok;
}
__device__ __forceinline__ void mbar_wait_if(uint32_t ok, uint32_t bar, uint32_t parity) {
  if (!__all_sync(0xffffffffu, ok)) mbar_wait(bar, parity);
}
__device__ __forceinline__ bool elect_one() {
  uint32_t r;
  asm volatile("{\n.reg .pred p;\nelect.sync _|p, 0xffffffff;\nselp.u32 %0, 1, 0, p;\n}\n" : "=r"(r));
  return r != 0;
}
__device__ __forceinline__ void nb_arrive(int id) { asm volatile("bar.arrive %0, 256;" ::"r"(id) : "memory"); }
__device__ __forceinline__ void nb_sync(int id) { asm volatile("bar.sync %0, 256;" ::"r"(id) : "memory"); }
__device__ __forceinline__ void nb_arrive_p(int id) { asm volatile("bar.arrive %0, 160;" ::"r"(id) : "memory"); }
__device__ __forceinline__ void nb_sync_p(int id) { asm volatile("bar.sync %0, 160;" ::"r"(id) : "memory"); }
__device__ __forceinline__ void fence_proxy_async() { asm volatile("fence.proxy.async.shared::cta;" ::: "memory"); }

__device__ __forceinline__ void tma_load_5d(uint32_t dst, const CUtensorMap* map, uint32_t bar, int c0, int c1, int c2,
                                            int c3, int c4) {
  asm volatile(
      "cp.async.bulk.tensor.5d.shared::cluster.global.tile.mbarrier::complete_tx::bytes "
      "[%0], [%1, {%3, %4, %5, %6, %7}], [%2];"
      ::"r"(dst), "l"((uint64_t)map), "r"(bar), "r"(c0), "r"(c1), "r"(c2), "r"(c3), "r"(c4)
      : "memory");
}
__device__ __forceinline__ void bulk_load(uint32_t dst, const void* src, uint32_t bytes, uint32_t bar) {
  asm volatile("cp.async.bulk.shared::cluster.global.mbarrier::complete_tx::bytes [%0], [%1], %2, [%3];"
               ::"r"(dst), "l"((uint64_t)src), "r"(bytes), "r"(bar)
               : "memory");
}

__device__ __forceinline__ void wg_fence() { asm volatile("wgmma.fence.sync.aligned;" ::: "memory"); }
__device__ __forceinline__ void wg_commit() { asm volatile("wgmma.commit_group.sync.aligned;" ::: "memory"); }
template <int N>
__device__ __forceinline__ void wg_wait() { asm volatile("wgmma.wait_group.sync.aligned %0;" ::"n"(N) : "memory"); }

template <int N>
__device__ __forceinline__ void fence_regs(float (&d)[N]) {
#pragma unroll
  for (int i = 0; i < N; i++) asm volatile("" : "+f"(d[i])::"memory");
}
template <int N>
__device__ __forceinline__ void keep_regs(uint32_t (&d)[N]) {
#pragma unroll
  for (int i = 0; i < N; i++) asm volatile("" : "+r"(d[i])::"memory");
}

__device__ __forceinline__ uint32_t pack_bf16(float lo, float hi) {
  uint32_t d;
  asm("cvt.rn.bf16x2.f32 %0, %1, %2;" : "=r"(d) : "f"(hi), "f"(lo));
  return d;
}
__device__ __forceinline__ float ex2(float x) {
  float y;
  asm("ex2.approx.ftz.f32 %0, %1;" : "=f"(y) : "f"(x));
  return y;
}
__device__ __forceinline__ float rcp_approx(float x) {
  float y;
  asm("rcp.approx.ftz.f32 %0, %1;" : "=f"(y) : "f"(x));
  return y;
}
__device__ __forceinline__ uint4 ldg128_nc(const void* p) {
  uint4 v;
  asm volatile("ld.global.nc.v4.u32 {%0,%1,%2,%3}, [%4];" : "=r"(v.x), "=r"(v.y), "=r"(v.z), "=r"(v.w) : "l"(p));
  return v;
}
__device__ __forceinline__ void stg128(void* p, uint32_t a, uint32_t b, uint32_t c, uint32_t d) {
  asm volatile("st.global.v4.u32 [%0], {%1,%2,%3,%4};" ::"l"(p), "r"(a), "r"(b), "r"(c), "r"(d) : "memory");
}

__device__ __forceinline__ long long clk64() {
  long long c;
  asm volatile("mov.u64 %0, %clock64;" : "=l"(c)::"memory");
  return c;
}
__device__ __forceinline__ void sched_fence() { while (clk64() < 0) { } }

__device__ __forceinline__ uint64_t make_desc(uint32_t addr, uint32_t lbo, uint32_t sbo, uint32_t mode = 1) {
  return (uint64_t)((addr & 0x3FFFF) >> 4) | ((uint64_t)(lbo >> 4) << 16) | ((uint64_t)(sbo >> 4) << 32) |
         ((uint64_t)mode << 62);
}

template <int OFF, int NN>
__device__ __forceinline__ void wg_m192(float (&d)[NN], uint64_t desc_a, uint64_t desc_b, int scale_d) {
  asm volatile(
      "{\n.reg .pred p;\nsetp.ne.b32 p, %98, 0;\n"
      "wgmma.mma_async.sync.aligned.m64n192k16.f32.bf16.bf16 "
      "{%0,%1,%2,%3,%4,%5,%6,%7,%8,%9,%10,%11,%12,%13,%14,%15,"
      "%16,%17,%18,%19,%20,%21,%22,%23,%24,%25,%26,%27,%28,%29,%30,%31,"
      "%32,%33,%34,%35,%36,%37,%38,%39,%40,%41,%42,%43,%44,%45,%46,%47,"
      "%48,%49,%50,%51,%52,%53,%54,%55,%56,%57,%58,%59,%60,%61,%62,%63,"
      "%64,%65,%66,%67,%68,%69,%70,%71,%72,%73,%74,%75,%76,%77,%78,%79,"
      "%80,%81,%82,%83,%84,%85,%86,%87,%88,%89,%90,%91,%92,%93,%94,%95}, "
      "%96, %97, p, 1, 1, 0, 0;\n}\n"
      : "+f"(d[OFF + 0]), "+f"(d[OFF + 1]), "+f"(d[OFF + 2]), "+f"(d[OFF + 3]), "+f"(d[OFF + 4]), "+f"(d[OFF + 5]),
        "+f"(d[OFF + 6]), "+f"(d[OFF + 7]), "+f"(d[OFF + 8]), "+f"(d[OFF + 9]), "+f"(d[OFF + 10]), "+f"(d[OFF + 11]),
        "+f"(d[OFF + 12]), "+f"(d[OFF + 13]), "+f"(d[OFF + 14]), "+f"(d[OFF + 15]), "+f"(d[OFF + 16]), "+f"(d[OFF + 17]),
        "+f"(d[OFF + 18]), "+f"(d[OFF + 19]), "+f"(d[OFF + 20]), "+f"(d[OFF + 21]), "+f"(d[OFF + 22]), "+f"(d[OFF + 23]),
        "+f"(d[OFF + 24]), "+f"(d[OFF + 25]), "+f"(d[OFF + 26]), "+f"(d[OFF + 27]), "+f"(d[OFF + 28]), "+f"(d[OFF + 29]),
        "+f"(d[OFF + 30]), "+f"(d[OFF + 31]), "+f"(d[OFF + 32]), "+f"(d[OFF + 33]), "+f"(d[OFF + 34]), "+f"(d[OFF + 35]),
        "+f"(d[OFF + 36]), "+f"(d[OFF + 37]), "+f"(d[OFF + 38]), "+f"(d[OFF + 39]), "+f"(d[OFF + 40]), "+f"(d[OFF + 41]),
        "+f"(d[OFF + 42]), "+f"(d[OFF + 43]), "+f"(d[OFF + 44]), "+f"(d[OFF + 45]), "+f"(d[OFF + 46]), "+f"(d[OFF + 47]),
        "+f"(d[OFF + 48]), "+f"(d[OFF + 49]), "+f"(d[OFF + 50]), "+f"(d[OFF + 51]), "+f"(d[OFF + 52]), "+f"(d[OFF + 53]),
        "+f"(d[OFF + 54]), "+f"(d[OFF + 55]), "+f"(d[OFF + 56]), "+f"(d[OFF + 57]), "+f"(d[OFF + 58]), "+f"(d[OFF + 59]),
        "+f"(d[OFF + 60]), "+f"(d[OFF + 61]), "+f"(d[OFF + 62]), "+f"(d[OFF + 63]), "+f"(d[OFF + 64]), "+f"(d[OFF + 65]),
        "+f"(d[OFF + 66]), "+f"(d[OFF + 67]), "+f"(d[OFF + 68]), "+f"(d[OFF + 69]), "+f"(d[OFF + 70]), "+f"(d[OFF + 71]),
        "+f"(d[OFF + 72]), "+f"(d[OFF + 73]), "+f"(d[OFF + 74]), "+f"(d[OFF + 75]), "+f"(d[OFF + 76]), "+f"(d[OFF + 77]),
        "+f"(d[OFF + 78]), "+f"(d[OFF + 79]), "+f"(d[OFF + 80]), "+f"(d[OFF + 81]), "+f"(d[OFF + 82]), "+f"(d[OFF + 83]),
        "+f"(d[OFF + 84]), "+f"(d[OFF + 85]), "+f"(d[OFF + 86]), "+f"(d[OFF + 87]), "+f"(d[OFF + 88]), "+f"(d[OFF + 89]),
        "+f"(d[OFF + 90]), "+f"(d[OFF + 91]), "+f"(d[OFF + 92]), "+f"(d[OFF + 93]), "+f"(d[OFF + 94]), "+f"(d[OFF + 95])
      : "l"(desc_a), "l"(desc_b), "r"(scale_d));
}

template <int OFF, int NN>
__device__ __forceinline__ void wg_m192z(float (&d)[NN], uint64_t desc_a, uint64_t desc_b, int scale_d) {
  asm volatile(
      "{\n.reg .pred p;\nsetp.ne.b32 p, %98, 0;\n"
      "wgmma.mma_async.sync.aligned.m64n192k16.f32.bf16.bf16 "
      "{%0,%1,%2,%3,%4,%5,%6,%7,%8,%9,%10,%11,%12,%13,%14,%15,"
      "%16,%17,%18,%19,%20,%21,%22,%23,%24,%25,%26,%27,%28,%29,%30,%31,"
      "%32,%33,%34,%35,%36,%37,%38,%39,%40,%41,%42,%43,%44,%45,%46,%47,"
      "%48,%49,%50,%51,%52,%53,%54,%55,%56,%57,%58,%59,%60,%61,%62,%63,"
      "%64,%65,%66,%67,%68,%69,%70,%71,%72,%73,%74,%75,%76,%77,%78,%79,"
      "%80,%81,%82,%83,%84,%85,%86,%87,%88,%89,%90,%91,%92,%93,%94,%95}, "
      "%96, %97, p, 1, 1, 0, 0;\n}\n"
      : "=f"(d[OFF + 0]), "=f"(d[OFF + 1]), "=f"(d[OFF + 2]), "=f"(d[OFF + 3]), "=f"(d[OFF + 4]), "=f"(d[OFF + 5]),
        "=f"(d[OFF + 6]), "=f"(d[OFF + 7]), "=f"(d[OFF + 8]), "=f"(d[OFF + 9]), "=f"(d[OFF + 10]), "=f"(d[OFF + 11]),
        "=f"(d[OFF + 12]), "=f"(d[OFF + 13]), "=f"(d[OFF + 14]), "=f"(d[OFF + 15]), "=f"(d[OFF + 16]), "=f"(d[OFF + 17]),
        "=f"(d[OFF + 18]), "=f"(d[OFF + 19]), "=f"(d[OFF + 20]), "=f"(d[OFF + 21]), "=f"(d[OFF + 22]), "=f"(d[OFF + 23]),
        "=f"(d[OFF + 24]), "=f"(d[OFF + 25]), "=f"(d[OFF + 26]), "=f"(d[OFF + 27]), "=f"(d[OFF + 28]), "=f"(d[OFF + 29]),
        "=f"(d[OFF + 30]), "=f"(d[OFF + 31]), "=f"(d[OFF + 32]), "=f"(d[OFF + 33]), "=f"(d[OFF + 34]), "=f"(d[OFF + 35]),
        "=f"(d[OFF + 36]), "=f"(d[OFF + 37]), "=f"(d[OFF + 38]), "=f"(d[OFF + 39]), "=f"(d[OFF + 40]), "=f"(d[OFF + 41]),
        "=f"(d[OFF + 42]), "=f"(d[OFF + 43]), "=f"(d[OFF + 44]), "=f"(d[OFF + 45]), "=f"(d[OFF + 46]), "=f"(d[OFF + 47]),
        "=f"(d[OFF + 48]), "=f"(d[OFF + 49]), "=f"(d[OFF + 50]), "=f"(d[OFF + 51]), "=f"(d[OFF + 52]), "=f"(d[OFF + 53]),
        "=f"(d[OFF + 54]), "=f"(d[OFF + 55]), "=f"(d[OFF + 56]), "=f"(d[OFF + 57]), "=f"(d[OFF + 58]), "=f"(d[OFF + 59]),
        "=f"(d[OFF + 60]), "=f"(d[OFF + 61]), "=f"(d[OFF + 62]), "=f"(d[OFF + 63]), "=f"(d[OFF + 64]), "=f"(d[OFF + 65]),
        "=f"(d[OFF + 66]), "=f"(d[OFF + 67]), "=f"(d[OFF + 68]), "=f"(d[OFF + 69]), "=f"(d[OFF + 70]), "=f"(d[OFF + 71]),
        "=f"(d[OFF + 72]), "=f"(d[OFF + 73]), "=f"(d[OFF + 74]), "=f"(d[OFF + 75]), "=f"(d[OFF + 76]), "=f"(d[OFF + 77]),
        "=f"(d[OFF + 78]), "=f"(d[OFF + 79]), "=f"(d[OFF + 80]), "=f"(d[OFF + 81]), "=f"(d[OFF + 82]), "=f"(d[OFF + 83]),
        "=f"(d[OFF + 84]), "=f"(d[OFF + 85]), "=f"(d[OFF + 86]), "=f"(d[OFF + 87]), "=f"(d[OFF + 88]), "=f"(d[OFF + 89]),
        "=f"(d[OFF + 90]), "=f"(d[OFF + 91]), "=f"(d[OFF + 92]), "=f"(d[OFF + 93]), "=f"(d[OFF + 94]), "=f"(d[OFF + 95])
      : "l"(desc_a), "l"(desc_b), "r"(scale_d));
}

template <int OFF, int NN>
__device__ __forceinline__ void wg_m64t(float (&d)[NN], uint64_t desc_a, uint64_t desc_b, int scale_d) {
  asm volatile(
      "{\n.reg .pred p;\nsetp.ne.b32 p, %34, 0;\n"
      "wgmma.mma_async.sync.aligned.m64n64k16.f32.bf16.bf16 "
      "{%0,%1,%2,%3,%4,%5,%6,%7,%8,%9,%10,%11,%12,%13,%14,%15,"
      "%16,%17,%18,%19,%20,%21,%22,%23,%24,%25,%26,%27,%28,%29,%30,%31}, "
      "%32, %33, p, 1, 1, 0, 1;\n}\n"
      : "+f"(d[OFF + 0]), "+f"(d[OFF + 1]), "+f"(d[OFF + 2]), "+f"(d[OFF + 3]), "+f"(d[OFF + 4]), "+f"(d[OFF + 5]),
        "+f"(d[OFF + 6]), "+f"(d[OFF + 7]), "+f"(d[OFF + 8]), "+f"(d[OFF + 9]), "+f"(d[OFF + 10]), "+f"(d[OFF + 11]),
        "+f"(d[OFF + 12]), "+f"(d[OFF + 13]), "+f"(d[OFF + 14]), "+f"(d[OFF + 15]), "+f"(d[OFF + 16]), "+f"(d[OFF + 17]),
        "+f"(d[OFF + 18]), "+f"(d[OFF + 19]), "+f"(d[OFF + 20]), "+f"(d[OFF + 21]), "+f"(d[OFF + 22]), "+f"(d[OFF + 23]),
        "+f"(d[OFF + 24]), "+f"(d[OFF + 25]), "+f"(d[OFF + 26]), "+f"(d[OFF + 27]), "+f"(d[OFF + 28]), "+f"(d[OFF + 29]),
        "+f"(d[OFF + 30]), "+f"(d[OFF + 31])
      : "l"(desc_a), "l"(desc_b), "r"(scale_d));
}

template <int OFF, int NN>
__device__ __forceinline__ void wg_m64tz(float (&d)[NN], uint64_t desc_a, uint64_t desc_b, int scale_d) {
  asm volatile(
      "{\n.reg .pred p;\nsetp.ne.b32 p, %34, 0;\n"
      "wgmma.mma_async.sync.aligned.m64n64k16.f32.bf16.bf16 "
      "{%0,%1,%2,%3,%4,%5,%6,%7,%8,%9,%10,%11,%12,%13,%14,%15,"
      "%16,%17,%18,%19,%20,%21,%22,%23,%24,%25,%26,%27,%28,%29,%30,%31}, "
      "%32, %33, p, 1, 1, 0, 1;\n}\n"
      : "=f"(d[OFF + 0]), "=f"(d[OFF + 1]), "=f"(d[OFF + 2]), "=f"(d[OFF + 3]), "=f"(d[OFF + 4]), "=f"(d[OFF + 5]),
        "=f"(d[OFF + 6]), "=f"(d[OFF + 7]), "=f"(d[OFF + 8]), "=f"(d[OFF + 9]), "=f"(d[OFF + 10]), "=f"(d[OFF + 11]),
        "=f"(d[OFF + 12]), "=f"(d[OFF + 13]), "=f"(d[OFF + 14]), "=f"(d[OFF + 15]), "=f"(d[OFF + 16]), "=f"(d[OFF + 17]),
        "=f"(d[OFF + 18]), "=f"(d[OFF + 19]), "=f"(d[OFF + 20]), "=f"(d[OFF + 21]), "=f"(d[OFF + 22]), "=f"(d[OFF + 23]),
        "=f"(d[OFF + 24]), "=f"(d[OFF + 25]), "=f"(d[OFF + 26]), "=f"(d[OFF + 27]), "=f"(d[OFF + 28]), "=f"(d[OFF + 29]),
        "=f"(d[OFF + 30]), "=f"(d[OFF + 31])
      : "l"(desc_a), "l"(desc_b), "r"(scale_d));
}

template <int OFF, int NN>
__device__ __forceinline__ void wg_d96(float (&d)[NN], uint32_t a0, uint32_t a1, uint32_t a2, uint32_t a3,
                                       uint64_t desc_b, int scale_d) {
  asm volatile(
      "{\n.reg .pred p;\nsetp.ne.b32 p, %53, 0;\n"
      "wgmma.mma_async.sync.aligned.m64n96k16.f32.bf16.bf16 "
      "{%0,%1,%2,%3,%4,%5,%6,%7,%8,%9,%10,%11,%12,%13,%14,%15,"
      "%16,%17,%18,%19,%20,%21,%22,%23,%24,%25,%26,%27,%28,%29,%30,%31,"
      "%32,%33,%34,%35,%36,%37,%38,%39,%40,%41,%42,%43,%44,%45,%46,%47}, "
      "{%48,%49,%50,%51}, %52, p, 1, 1, 0;\n}\n"
      : "+f"(d[OFF + 0]), "+f"(d[OFF + 1]), "+f"(d[OFF + 2]), "+f"(d[OFF + 3]), "+f"(d[OFF + 4]), "+f"(d[OFF + 5]),
        "+f"(d[OFF + 6]), "+f"(d[OFF + 7]), "+f"(d[OFF + 8]), "+f"(d[OFF + 9]), "+f"(d[OFF + 10]), "+f"(d[OFF + 11]),
        "+f"(d[OFF + 12]), "+f"(d[OFF + 13]), "+f"(d[OFF + 14]), "+f"(d[OFF + 15]), "+f"(d[OFF + 16]), "+f"(d[OFF + 17]),
        "+f"(d[OFF + 18]), "+f"(d[OFF + 19]), "+f"(d[OFF + 20]), "+f"(d[OFF + 21]), "+f"(d[OFF + 22]), "+f"(d[OFF + 23]),
        "+f"(d[OFF + 24]), "+f"(d[OFF + 25]), "+f"(d[OFF + 26]), "+f"(d[OFF + 27]), "+f"(d[OFF + 28]), "+f"(d[OFF + 29]),
        "+f"(d[OFF + 30]), "+f"(d[OFF + 31]), "+f"(d[OFF + 32]), "+f"(d[OFF + 33]), "+f"(d[OFF + 34]), "+f"(d[OFF + 35]),
        "+f"(d[OFF + 36]), "+f"(d[OFF + 37]), "+f"(d[OFF + 38]), "+f"(d[OFF + 39]), "+f"(d[OFF + 40]), "+f"(d[OFF + 41]),
        "+f"(d[OFF + 42]), "+f"(d[OFF + 43]), "+f"(d[OFF + 44]), "+f"(d[OFF + 45]), "+f"(d[OFF + 46]), "+f"(d[OFF + 47])
      : "r"(a0), "r"(a1), "r"(a2), "r"(a3), "l"(desc_b), "r"(scale_d));
}

template <int OFF, int NN>
__device__ __forceinline__ void wg_d96z(float (&d)[NN], uint32_t a0, uint32_t a1, uint32_t a2, uint32_t a3,
                                       uint64_t desc_b, int scale_d) {
  asm volatile(
      "{\n.reg .pred p;\nsetp.ne.b32 p, %53, 0;\n"
      "wgmma.mma_async.sync.aligned.m64n96k16.f32.bf16.bf16 "
      "{%0,%1,%2,%3,%4,%5,%6,%7,%8,%9,%10,%11,%12,%13,%14,%15,"
      "%16,%17,%18,%19,%20,%21,%22,%23,%24,%25,%26,%27,%28,%29,%30,%31,"
      "%32,%33,%34,%35,%36,%37,%38,%39,%40,%41,%42,%43,%44,%45,%46,%47}, "
      "{%48,%49,%50,%51}, %52, p, 1, 1, 0;\n}\n"
      : "=f"(d[OFF + 0]), "=f"(d[OFF + 1]), "=f"(d[OFF + 2]), "=f"(d[OFF + 3]), "=f"(d[OFF + 4]), "=f"(d[OFF + 5]),
        "=f"(d[OFF + 6]), "=f"(d[OFF + 7]), "=f"(d[OFF + 8]), "=f"(d[OFF + 9]), "=f"(d[OFF + 10]), "=f"(d[OFF + 11]),
        "=f"(d[OFF + 12]), "=f"(d[OFF + 13]), "=f"(d[OFF + 14]), "=f"(d[OFF + 15]), "=f"(d[OFF + 16]), "=f"(d[OFF + 17]),
        "=f"(d[OFF + 18]), "=f"(d[OFF + 19]), "=f"(d[OFF + 20]), "=f"(d[OFF + 21]), "=f"(d[OFF + 22]), "=f"(d[OFF + 23]),
        "=f"(d[OFF + 24]), "=f"(d[OFF + 25]), "=f"(d[OFF + 26]), "=f"(d[OFF + 27]), "=f"(d[OFF + 28]), "=f"(d[OFF + 29]),
        "=f"(d[OFF + 30]), "=f"(d[OFF + 31]), "=f"(d[OFF + 32]), "=f"(d[OFF + 33]), "=f"(d[OFF + 34]), "=f"(d[OFF + 35]),
        "=f"(d[OFF + 36]), "=f"(d[OFF + 37]), "=f"(d[OFF + 38]), "=f"(d[OFF + 39]), "=f"(d[OFF + 40]), "=f"(d[OFF + 41]),
        "=f"(d[OFF + 42]), "=f"(d[OFF + 43]), "=f"(d[OFF + 44]), "=f"(d[OFF + 45]), "=f"(d[OFF + 46]), "=f"(d[OFF + 47])
      : "r"(a0), "r"(a1), "r"(a2), "r"(a3), "l"(desc_b), "r"(scale_d));
}

template <int OFF, int NN>
__device__ __forceinline__ void wg_s104(float (&d)[NN], uint32_t a0, uint32_t a1, uint32_t a2, uint32_t a3,
                                       uint64_t desc_b, int scale_d, uint32_t meta) {
  asm volatile(
      "{\n.reg .pred p;\nsetp.ne.b32 p, %57, 0;\n"
      "wgmma.mma_async.sp.sync.aligned.m64n104k32.f32.bf16.bf16 "
      "{%0,%1,%2,%3,%4,%5,%6,%7,%8,%9,%10,%11,%12,%13,%14,%15,"
      "%16,%17,%18,%19,%20,%21,%22,%23,%24,%25,%26,%27,%28,%29,%30,%31,"
      "%32,%33,%34,%35,%36,%37,%38,%39,%40,%41,%42,%43,%44,%45,%46,%47,"
      "%48,%49,%50,%51}, "
      "{%52,%53,%54,%55}, %56, %58, 0, p, 1, 1, 0;\n}\n"
      : "+f"(d[OFF + 0]), "+f"(d[OFF + 1]), "+f"(d[OFF + 2]), "+f"(d[OFF + 3]), "+f"(d[OFF + 4]), "+f"(d[OFF + 5]),
        "+f"(d[OFF + 6]), "+f"(d[OFF + 7]), "+f"(d[OFF + 8]), "+f"(d[OFF + 9]), "+f"(d[OFF + 10]), "+f"(d[OFF + 11]),
        "+f"(d[OFF + 12]), "+f"(d[OFF + 13]), "+f"(d[OFF + 14]), "+f"(d[OFF + 15]), "+f"(d[OFF + 16]), "+f"(d[OFF + 17]),
        "+f"(d[OFF + 18]), "+f"(d[OFF + 19]), "+f"(d[OFF + 20]), "+f"(d[OFF + 21]), "+f"(d[OFF + 22]), "+f"(d[OFF + 23]),
        "+f"(d[OFF + 24]), "+f"(d[OFF + 25]), "+f"(d[OFF + 26]), "+f"(d[OFF + 27]), "+f"(d[OFF + 28]), "+f"(d[OFF + 29]),
        "+f"(d[OFF + 30]), "+f"(d[OFF + 31]), "+f"(d[OFF + 32]), "+f"(d[OFF + 33]), "+f"(d[OFF + 34]), "+f"(d[OFF + 35]),
        "+f"(d[OFF + 36]), "+f"(d[OFF + 37]), "+f"(d[OFF + 38]), "+f"(d[OFF + 39]), "+f"(d[OFF + 40]), "+f"(d[OFF + 41]),
        "+f"(d[OFF + 42]), "+f"(d[OFF + 43]), "+f"(d[OFF + 44]), "+f"(d[OFF + 45]), "+f"(d[OFF + 46]), "+f"(d[OFF + 47]),
        "+f"(d[OFF + 48]), "+f"(d[OFF + 49]), "+f"(d[OFF + 50]), "+f"(d[OFF + 51])
      : "r"(a0), "r"(a1), "r"(a2), "r"(a3), "l"(desc_b), "r"(scale_d), "r"(meta));
}

template <int OFF, int NN>
__device__ __forceinline__ void wg_s104z(float (&d)[NN], uint32_t a0, uint32_t a1, uint32_t a2, uint32_t a3,
                                       uint64_t desc_b, int scale_d, uint32_t meta) {
  asm volatile(
      "{\n.reg .pred p;\nsetp.ne.b32 p, %57, 0;\n"
      "wgmma.mma_async.sp.sync.aligned.m64n104k32.f32.bf16.bf16 "
      "{%0,%1,%2,%3,%4,%5,%6,%7,%8,%9,%10,%11,%12,%13,%14,%15,"
      "%16,%17,%18,%19,%20,%21,%22,%23,%24,%25,%26,%27,%28,%29,%30,%31,"
      "%32,%33,%34,%35,%36,%37,%38,%39,%40,%41,%42,%43,%44,%45,%46,%47,"
      "%48,%49,%50,%51}, "
      "{%52,%53,%54,%55}, %56, %58, 0, p, 1, 1, 0;\n}\n"
      : "=f"(d[OFF + 0]), "=f"(d[OFF + 1]), "=f"(d[OFF + 2]), "=f"(d[OFF + 3]), "=f"(d[OFF + 4]), "=f"(d[OFF + 5]),
        "=f"(d[OFF + 6]), "=f"(d[OFF + 7]), "=f"(d[OFF + 8]), "=f"(d[OFF + 9]), "=f"(d[OFF + 10]), "=f"(d[OFF + 11]),
        "=f"(d[OFF + 12]), "=f"(d[OFF + 13]), "=f"(d[OFF + 14]), "=f"(d[OFF + 15]), "=f"(d[OFF + 16]), "=f"(d[OFF + 17]),
        "=f"(d[OFF + 18]), "=f"(d[OFF + 19]), "=f"(d[OFF + 20]), "=f"(d[OFF + 21]), "=f"(d[OFF + 22]), "=f"(d[OFF + 23]),
        "=f"(d[OFF + 24]), "=f"(d[OFF + 25]), "=f"(d[OFF + 26]), "=f"(d[OFF + 27]), "=f"(d[OFF + 28]), "=f"(d[OFF + 29]),
        "=f"(d[OFF + 30]), "=f"(d[OFF + 31]), "=f"(d[OFF + 32]), "=f"(d[OFF + 33]), "=f"(d[OFF + 34]), "=f"(d[OFF + 35]),
        "=f"(d[OFF + 36]), "=f"(d[OFF + 37]), "=f"(d[OFF + 38]), "=f"(d[OFF + 39]), "=f"(d[OFF + 40]), "=f"(d[OFF + 41]),
        "=f"(d[OFF + 42]), "=f"(d[OFF + 43]), "=f"(d[OFF + 44]), "=f"(d[OFF + 45]), "=f"(d[OFF + 46]), "=f"(d[OFF + 47]),
        "=f"(d[OFF + 48]), "=f"(d[OFF + 49]), "=f"(d[OFF + 50]), "=f"(d[OFF + 51])
      : "r"(a0), "r"(a1), "r"(a2), "r"(a3), "l"(desc_b), "r"(scale_d), "r"(meta));
}

template <int OFF, int NN>
__device__ __forceinline__ void wg_s48(float (&d)[NN], uint32_t a0, uint32_t a1, uint32_t a2, uint32_t a3,
                                       uint64_t desc_b, int scale_d, uint32_t meta) {
  asm volatile(
      "{\n.reg .pred p;\nsetp.ne.b32 p, %29, 0;\n"
      "wgmma.mma_async.sp.sync.aligned.m64n48k32.f32.bf16.bf16 "
      "{%0,%1,%2,%3,%4,%5,%6,%7,%8,%9,%10,%11,%12,%13,%14,%15,"
      "%16,%17,%18,%19,%20,%21,%22,%23}, "
      "{%24,%25,%26,%27}, %28, %30, 0, p, 1, 1, 0;\n}\n"
      : "+f"(d[OFF + 0]), "+f"(d[OFF + 1]), "+f"(d[OFF + 2]), "+f"(d[OFF + 3]), "+f"(d[OFF + 4]), "+f"(d[OFF + 5]),
        "+f"(d[OFF + 6]), "+f"(d[OFF + 7]), "+f"(d[OFF + 8]), "+f"(d[OFF + 9]), "+f"(d[OFF + 10]), "+f"(d[OFF + 11]),
        "+f"(d[OFF + 12]), "+f"(d[OFF + 13]), "+f"(d[OFF + 14]), "+f"(d[OFF + 15]), "+f"(d[OFF + 16]), "+f"(d[OFF + 17]),
        "+f"(d[OFF + 18]), "+f"(d[OFF + 19]), "+f"(d[OFF + 20]), "+f"(d[OFF + 21]), "+f"(d[OFF + 22]), "+f"(d[OFF + 23])
      : "r"(a0), "r"(a1), "r"(a2), "r"(a3), "l"(desc_b), "r"(scale_d), "r"(meta));
}

template <int OFF, int NN>
__device__ __forceinline__ void wg_s48z(float (&d)[NN], uint32_t a0, uint32_t a1, uint32_t a2, uint32_t a3,
                                       uint64_t desc_b, int scale_d, uint32_t meta) {
  asm volatile(
      "{\n.reg .pred p;\nsetp.ne.b32 p, %29, 0;\n"
      "wgmma.mma_async.sp.sync.aligned.m64n48k32.f32.bf16.bf16 "
      "{%0,%1,%2,%3,%4,%5,%6,%7,%8,%9,%10,%11,%12,%13,%14,%15,"
      "%16,%17,%18,%19,%20,%21,%22,%23}, "
      "{%24,%25,%26,%27}, %28, %30, 0, p, 1, 1, 0;\n}\n"
      : "=f"(d[OFF + 0]), "=f"(d[OFF + 1]), "=f"(d[OFF + 2]), "=f"(d[OFF + 3]), "=f"(d[OFF + 4]), "=f"(d[OFF + 5]),
        "=f"(d[OFF + 6]), "=f"(d[OFF + 7]), "=f"(d[OFF + 8]), "=f"(d[OFF + 9]), "=f"(d[OFF + 10]), "=f"(d[OFF + 11]),
        "=f"(d[OFF + 12]), "=f"(d[OFF + 13]), "=f"(d[OFF + 14]), "=f"(d[OFF + 15]), "=f"(d[OFF + 16]), "=f"(d[OFF + 17]),
        "=f"(d[OFF + 18]), "=f"(d[OFF + 19]), "=f"(d[OFF + 20]), "=f"(d[OFF + 21]), "=f"(d[OFF + 22]), "=f"(d[OFF + 23])
      : "r"(a0), "r"(a1), "r"(a2), "r"(a3), "l"(desc_b), "r"(scale_d), "r"(meta));
}

template <int OFF, int NN>
__device__ __forceinline__ void wg_s56(float (&d)[NN], uint32_t a0, uint32_t a1, uint32_t a2, uint32_t a3,
                                       uint64_t desc_b, int scale_d, uint32_t meta) {
  asm volatile(
      "{\n.reg .pred p;\nsetp.ne.b32 p, %33, 0;\n"
      "wgmma.mma_async.sp.sync.aligned.m64n56k32.f32.bf16.bf16 "
      "{%0,%1,%2,%3,%4,%5,%6,%7,%8,%9,%10,%11,%12,%13,%14,%15,"
      "%16,%17,%18,%19,%20,%21,%22,%23,%24,%25,%26,%27}, "
      "{%28,%29,%30,%31}, %32, %34, 0, p, 1, 1, 0;\n}\n"
      : "+f"(d[OFF + 0]), "+f"(d[OFF + 1]), "+f"(d[OFF + 2]), "+f"(d[OFF + 3]), "+f"(d[OFF + 4]), "+f"(d[OFF + 5]),
        "+f"(d[OFF + 6]), "+f"(d[OFF + 7]), "+f"(d[OFF + 8]), "+f"(d[OFF + 9]), "+f"(d[OFF + 10]), "+f"(d[OFF + 11]),
        "+f"(d[OFF + 12]), "+f"(d[OFF + 13]), "+f"(d[OFF + 14]), "+f"(d[OFF + 15]), "+f"(d[OFF + 16]), "+f"(d[OFF + 17]),
        "+f"(d[OFF + 18]), "+f"(d[OFF + 19]), "+f"(d[OFF + 20]), "+f"(d[OFF + 21]), "+f"(d[OFF + 22]), "+f"(d[OFF + 23]),
        "+f"(d[OFF + 24]), "+f"(d[OFF + 25]), "+f"(d[OFF + 26]), "+f"(d[OFF + 27])
      : "r"(a0), "r"(a1), "r"(a2), "r"(a3), "l"(desc_b), "r"(scale_d), "r"(meta));
}

template <int OFF, int NN>
__device__ __forceinline__ void wg_s56z(float (&d)[NN], uint32_t a0, uint32_t a1, uint32_t a2, uint32_t a3,
                                       uint64_t desc_b, int scale_d, uint32_t meta) {
  asm volatile(
      "{\n.reg .pred p;\nsetp.ne.b32 p, %33, 0;\n"
      "wgmma.mma_async.sp.sync.aligned.m64n56k32.f32.bf16.bf16 "
      "{%0,%1,%2,%3,%4,%5,%6,%7,%8,%9,%10,%11,%12,%13,%14,%15,"
      "%16,%17,%18,%19,%20,%21,%22,%23,%24,%25,%26,%27}, "
      "{%28,%29,%30,%31}, %32, %34, 0, p, 1, 1, 0;\n}\n"
      : "=f"(d[OFF + 0]), "=f"(d[OFF + 1]), "=f"(d[OFF + 2]), "=f"(d[OFF + 3]), "=f"(d[OFF + 4]), "=f"(d[OFF + 5]),
        "=f"(d[OFF + 6]), "=f"(d[OFF + 7]), "=f"(d[OFF + 8]), "=f"(d[OFF + 9]), "=f"(d[OFF + 10]), "=f"(d[OFF + 11]),
        "=f"(d[OFF + 12]), "=f"(d[OFF + 13]), "=f"(d[OFF + 14]), "=f"(d[OFF + 15]), "=f"(d[OFF + 16]), "=f"(d[OFF + 17]),
        "=f"(d[OFF + 18]), "=f"(d[OFF + 19]), "=f"(d[OFF + 20]), "=f"(d[OFF + 21]), "=f"(d[OFF + 22]), "=f"(d[OFF + 23]),
        "=f"(d[OFF + 24]), "=f"(d[OFF + 25]), "=f"(d[OFF + 26]), "=f"(d[OFF + 27])
      : "r"(a0), "r"(a1), "r"(a2), "r"(a3), "l"(desc_b), "r"(scale_d), "r"(meta));
}

template <int OFF, int NN>
__device__ __forceinline__ void wg_s64t(float (&d)[NN], uint32_t a0, uint32_t a1, uint32_t a2, uint32_t a3,
                                       uint64_t desc_b, int scale_d, uint32_t meta) {
  asm volatile(
      "{\n.reg .pred p;\nsetp.ne.b32 p, %37, 0;\n"
      "wgmma.mma_async.sp.sync.aligned.m64n64k32.f32.bf16.bf16 "
      "{%0,%1,%2,%3,%4,%5,%6,%7,%8,%9,%10,%11,%12,%13,%14,%15,"
      "%16,%17,%18,%19,%20,%21,%22,%23,%24,%25,%26,%27,%28,%29,%30,%31}, "
      "{%32,%33,%34,%35}, %36, %38, 0, p, 1, 1, 1;\n}\n"
      : "+f"(d[OFF + 0]), "+f"(d[OFF + 1]), "+f"(d[OFF + 2]), "+f"(d[OFF + 3]), "+f"(d[OFF + 4]), "+f"(d[OFF + 5]),
        "+f"(d[OFF + 6]), "+f"(d[OFF + 7]), "+f"(d[OFF + 8]), "+f"(d[OFF + 9]), "+f"(d[OFF + 10]), "+f"(d[OFF + 11]),
        "+f"(d[OFF + 12]), "+f"(d[OFF + 13]), "+f"(d[OFF + 14]), "+f"(d[OFF + 15]), "+f"(d[OFF + 16]), "+f"(d[OFF + 17]),
        "+f"(d[OFF + 18]), "+f"(d[OFF + 19]), "+f"(d[OFF + 20]), "+f"(d[OFF + 21]), "+f"(d[OFF + 22]), "+f"(d[OFF + 23]),
        "+f"(d[OFF + 24]), "+f"(d[OFF + 25]), "+f"(d[OFF + 26]), "+f"(d[OFF + 27]), "+f"(d[OFF + 28]), "+f"(d[OFF + 29]),
        "+f"(d[OFF + 30]), "+f"(d[OFF + 31])
      : "r"(a0), "r"(a1), "r"(a2), "r"(a3), "l"(desc_b), "r"(scale_d), "r"(meta));
}

template <int OFF, int NN>
__device__ __forceinline__ void wg_s64t1(float (&d)[NN], uint32_t a0, uint32_t a1, uint32_t a2, uint32_t a3,
                                       uint64_t desc_b, int scale_d, uint32_t meta) {
  asm volatile(
      "{\n.reg .pred p;\nsetp.ne.b32 p, %37, 0;\n"
      "wgmma.mma_async.sp.sync.aligned.m64n64k32.f32.bf16.bf16 "
      "{%0,%1,%2,%3,%4,%5,%6,%7,%8,%9,%10,%11,%12,%13,%14,%15,"
      "%16,%17,%18,%19,%20,%21,%22,%23,%24,%25,%26,%27,%28,%29,%30,%31}, "
      "{%32,%33,%34,%35}, %36, %38, 1, p, 1, 1, 1;\n}\n"
      : "+f"(d[OFF + 0]), "+f"(d[OFF + 1]), "+f"(d[OFF + 2]), "+f"(d[OFF + 3]), "+f"(d[OFF + 4]), "+f"(d[OFF + 5]),
        "+f"(d[OFF + 6]), "+f"(d[OFF + 7]), "+f"(d[OFF + 8]), "+f"(d[OFF + 9]), "+f"(d[OFF + 10]), "+f"(d[OFF + 11]),
        "+f"(d[OFF + 12]), "+f"(d[OFF + 13]), "+f"(d[OFF + 14]), "+f"(d[OFF + 15]), "+f"(d[OFF + 16]), "+f"(d[OFF + 17]),
        "+f"(d[OFF + 18]), "+f"(d[OFF + 19]), "+f"(d[OFF + 20]), "+f"(d[OFF + 21]), "+f"(d[OFF + 22]), "+f"(d[OFF + 23]),
        "+f"(d[OFF + 24]), "+f"(d[OFF + 25]), "+f"(d[OFF + 26]), "+f"(d[OFF + 27]), "+f"(d[OFF + 28]), "+f"(d[OFF + 29]),
        "+f"(d[OFF + 30]), "+f"(d[OFF + 31])
      : "r"(a0), "r"(a1), "r"(a2), "r"(a3), "l"(desc_b), "r"(scale_d), "r"(meta));
}

template <int OFF, int NN>
__device__ __forceinline__ void wg_s64tz(float (&d)[NN], uint32_t a0, uint32_t a1, uint32_t a2, uint32_t a3,
                                       uint64_t desc_b, int scale_d, uint32_t meta) {
  asm volatile(
      "{\n.reg .pred p;\nsetp.ne.b32 p, %37, 0;\n"
      "wgmma.mma_async.sp.sync.aligned.m64n64k32.f32.bf16.bf16 "
      "{%0,%1,%2,%3,%4,%5,%6,%7,%8,%9,%10,%11,%12,%13,%14,%15,"
      "%16,%17,%18,%19,%20,%21,%22,%23,%24,%25,%26,%27,%28,%29,%30,%31}, "
      "{%32,%33,%34,%35}, %36, %38, 0, p, 1, 1, 1;\n}\n"
      : "=f"(d[OFF + 0]), "=f"(d[OFF + 1]), "=f"(d[OFF + 2]), "=f"(d[OFF + 3]), "=f"(d[OFF + 4]), "=f"(d[OFF + 5]),
        "=f"(d[OFF + 6]), "=f"(d[OFF + 7]), "=f"(d[OFF + 8]), "=f"(d[OFF + 9]), "=f"(d[OFF + 10]), "=f"(d[OFF + 11]),
        "=f"(d[OFF + 12]), "=f"(d[OFF + 13]), "=f"(d[OFF + 14]), "=f"(d[OFF + 15]), "=f"(d[OFF + 16]), "=f"(d[OFF + 17]),
        "=f"(d[OFF + 18]), "=f"(d[OFF + 19]), "=f"(d[OFF + 20]), "=f"(d[OFF + 21]), "=f"(d[OFF + 22]), "=f"(d[OFF + 23]),
        "=f"(d[OFF + 24]), "=f"(d[OFF + 25]), "=f"(d[OFF + 26]), "=f"(d[OFF + 27]), "=f"(d[OFF + 28]), "=f"(d[OFF + 29]),
        "=f"(d[OFF + 30]), "=f"(d[OFF + 31])
      : "r"(a0), "r"(a1), "r"(a2), "r"(a3), "l"(desc_b), "r"(scale_d), "r"(meta));
}

__device__ __forceinline__ int g2_inv(int ch) { return 32 * (ch >> 5) + 8 * ((ch >> 1) & 3) + 2 * ((ch >> 3) & 3) + (ch & 1); }
__host__ __device__ __forceinline__ uint32_t wimg_off(int n, int k) {
  return (uint32_t)(k >> 6) * kWChunk + (uint32_t)n * 128 + (uint32_t)((((k & 63) >> 3) ^ (n & 7)) << 4) + (k & 7) * 2;
}
__host__ __device__ constexpr int w2piece(int h, int c) { return c == 2 ? 2 + h : 4 * h + c; }
__device__ __forceinline__ uint32_t w2img_off(int n, int k) { return wimg_off(n % 96, k & 63) + w2piece(n >= 96, k >> 6) * (kWChunk / 2); }
__device__ __forceinline__ int qpix(int par, int t) {
  const int a = 2 * t + 13 * par - 6, b = t + 112 * par;
  return par ? min(a, b) : max(a, b);
}
__device__ __forceinline__ int woff(int par, int i, int r) {
  const int a = 99 * par + 6 - 8 * i;
  return par ? min(r, a) : max(r, a);
}

__device__ __forceinline__ void mma16816(float (&c)[4], uint32_t a0, uint32_t a1, uint32_t a2, uint32_t a3, uint32_t b0,
                                         uint32_t b1) {
  asm volatile(
      "mma.sync.aligned.m16n8k16.row.col.f32.bf16.bf16.f32 {%0,%1,%2,%3}, {%4,%5,%6,%7}, {%8,%9}, {%0,%1,%2,%3};"
      : "+f"(c[0]), "+f"(c[1]), "+f"(c[2]), "+f"(c[3])
      : "r"(a0), "r"(a1), "r"(a2), "r"(a3), "r"(b0), "r"(b1));
}

__device__ __forceinline__ void fold_w1(const int u, const __nv_bfloat16* __restrict__ wqkv, uint8_t* wimg) {
  const int g = (threadIdx.x >> 2) & 7, l = threadIdx.x & 3;
  const int m0 = (u / 12) * 16, s = u % 12;
  uint4 A[12], B[12];
  const __nv_bfloat16* arow = wqkv + (m0 + 4 * (g >> 1) + (g & 1)) * 576 + 192 + 8 * l;
  const __nv_bfloat16* brow = wqkv + (16 * s + 4 * (g >> 1) + (g & 1)) * 576 + 8 * l;
#pragma unroll
  for (int i = 0; i < 12; i++) {
    A[i] = ldg128_nc(arow + (i & 1) * 2 * 576 + 32 * (i >> 1));
    B[i] = ldg128_nc(brow + (i & 1) * 2 * 576 + 32 * (i >> 1));
  }
  sched_fence();
  uint8_t* dst = wimg + wimg_off(m0 + g, 16 * s + 4 * l);
  float acc[4][4];
#pragma unroll
  for (int j = 0; j < 16; j++) acc[j >> 2][j & 3] = 0.f;
#pragma unroll
  for (int i = 0; i < 6; i++) {
    const uint4 &a0 = A[2 * i], &a1 = A[2 * i + 1];
#pragma unroll
    for (int nb = 0; nb < 2; nb++) {
      mma16816(acc[2 * nb], a0.x, a1.x, a0.y, a1.y, B[2 * i + nb].x, B[2 * i + nb].y);
      mma16816(acc[2 * nb + 1], a0.z, a1.z, a0.w, a1.w, B[2 * i + nb].z, B[2 * i + nb].w);
    }
  }
#pragma unroll
  for (int j = 0; j < 2; j++) {
    const uint2 v = make_uint2(pack_bf16((acc[0][2 * j] + acc[1][2 * j]) * kAlpha, (acc[0][2 * j + 1] + acc[1][2 * j + 1]) * kAlpha),
                               pack_bf16((acc[2][2 * j] + acc[3][2 * j]) * kAlpha, (acc[2][2 * j + 1] + acc[3][2 * j + 1]) * kAlpha));
    asm volatile("st.relaxed.gpu.global.v2.u32 [%0], {%1,%2};" ::"l"(dst + j * 1024), "r"(v.x), "r"(v.y) : "memory");
  }
}
__device__ __forceinline__ void fold_w2(const int u, const __nv_bfloat16* __restrict__ wqkv, const __nv_bfloat16* __restrict__ wo,
                                        uint8_t* wimg) {
  const int g = (threadIdx.x >> 2) & 7, l = threadIdx.x & 3;
  const int m0 = (u / 12) * 32, n0 = (u % 12) * 16;
  uint4 S[12];
  uint32_t L[96];
  const __nv_bfloat16* brow = wqkv + (n0 + 4 * (g >> 1) + (g & 1)) * 576 + 384 + 8 * l;
#pragma unroll
  for (int i = 0; i < 12; i++) S[i] = ldg128_nc(brow + (i & 1) * 2 * 576 + 32 * (i >> 1));
  const __nv_bfloat16* acol = wo + (8 * l) * 192 + m0 + 4 * g;
#pragma unroll
  for (int c = 0; c < 48; c++)
    asm volatile("ld.global.nc.v2.u32 {%0,%1}, [%2];" : "=r"(L[2 * c]), "=r"(L[2 * c + 1]) : "l"(acol + (32 * (c >> 3) + (c & 7)) * 192));
  const uint32_t off = w2_offset();
  sched_fence();
  uint8_t* img = wimg + off;
  float acc[4][4];
#pragma unroll
  for (int j = 0; j < 16; j++) acc[j >> 2][j & 3] = 0.f;
#pragma unroll
  for (int i = 0; i < 6; i++) {
#pragma unroll
    for (int h = 0; h < 2; h++) {
      const uint4 &s0 = S[2 * i], &s1 = S[2 * i + 1];
#pragma unroll
      for (int mt = 0; mt < 2; mt++) {
        const uint32_t* a = L + 16 * i + 8 * h + mt;
        const uint32_t a0 = __byte_perm(a[0], a[2], 0x5410), a1 = __byte_perm(a[0], a[2], 0x7632);
        const uint32_t a2 = __byte_perm(a[4], a[6], 0x5410), a3 = __byte_perm(a[4], a[6], 0x7632);
        mma16816(acc[2 * mt], a0, a1, a2, a3, h ? s0.z : s0.x, h ? s0.w : s0.y);
        mma16816(acc[2 * mt + 1], a0, a1, a2, a3, h ? s1.z : s1.x, h ? s1.w : s1.y);
      }
    }
  }
#pragma unroll
  for (int j = 0; j < 4; j++) {
    const float(&c0)[4] = acc[j & 2];
    const float(&c1)[4] = acc[(j & 2) + 1];
    asm volatile("st.relaxed.gpu.global.v2.u32 [%0], {%1,%2};" ::"l"(img + w2img_off(g2_inv(m0 + 4 * g + j), n0 + 4 * l)),
                 "r"(pack_bf16(c0[2 * (j & 1)], c0[2 * (j & 1) + 1])), "r"(pack_bf16(c1[2 * (j & 1)], c1[2 * (j & 1) + 1])) : "memory");
  }
}

__global__ void __launch_bounds__(256) fold_kernel(const __nv_bfloat16* __restrict__ wqkv,
                                                   const __nv_bfloat16* __restrict__ wo, uint8_t* wimg) {
  const int u = blockIdx.x * 8 + (threadIdx.x >> 5);
  if (u < 144) fold_w1(u, wqkv, wimg);
  else fold_w2(u - 144, wqkv, wo, wimg);
}

struct TileCoord { int pr, pc, I, J, up, kind; };
struct TileTable { uint16_t e[kCtas * 6], g[5][8][2], b[5][2][4]; };
inline void make_tiles(TileTable& tt) {
  for (int tile = 0; tile < kCtas * 6; tile++) {
    const int b = tile / 6, k = tile - 6 * b;
    const int p = b < 128 ? (tile - 672) >> 1 : b - 80;
    const int strip = b < 112 ? b >> 1 : b >= 128 && k >= 2 ? (b & 1) * 27 + (b & 2) * 14 : p + (p < 26 ? 1 : 3);
    const int pr = strip >= 28, J = (strip - pr * 28) >> 1, pc = strip & 1, up = b < 112 ? b & 1 : pr;
    const int first = b < 112 ? 8 - 2 * pr - up : 13 * pr, step = b < 112 ? k : k & 1;
    const int I = up ? first - step : first + step;
    const int kind = b < 112 ? (J == 13 * pc ? 1 + pc : 0) : I == 13 * pr ? 3 + pr : 0;
    tt.e[tile] = (uint16_t)(I | J << 4 | pr << 8 | pc << 9 | up << 10 | kind << 11);
  }
  for (int kind = 0; kind < 5; kind++) {
    const bool col = kind == 1 || kind == 2;
    auto off = [kind](int t) { return kind == 0 ? 2 * t : kind & 1 ? t + (t == 7) : t + (t > 0); };
    for (int j = 0; j < 8; j++) {
      const int w = j >> 1, h = j & 1;
      tt.g[kind][j][0] = (uint16_t)(col ? 3 * off(w + 4 * h) : 3 * (kW * off(2 * w) + 8 * h));
      tt.g[kind][j][1] = (uint16_t)(128 * (col ? 5 : 5 + off(2 * w + 1) - off(2 * w)));
    }
    for (int i = 0; i < 2; i++) {
      const int w = kind == 0 ? 0 : kind & 1 ? 3 * i : 1 - i;
      tt.b[kind][i][0] = tt.g[kind][2 * w][0];
      tt.b[kind][i][1] = (uint16_t)(128 * (kind == 0 ? 0 : (col ? 3 : 1) + i));
      tt.b[kind][i][2] = (uint16_t)(2048 * w);
      tt.b[kind][i][3] = 0;
    }
  }
}
__device__ __forceinline__ int num_tiles() { return blockIdx.x < 128 ? 6 : 4; }
__device__ __forceinline__ TileCoord decode_tile(const TileTable& tt, int tile) {
  const uint32_t e = tt.e[tile];
  return TileCoord{(int)(e >> 8) & 1, (int)(e >> 9) & 1, (int)e & 15, (int)(e >> 4) & 15, (int)(e >> 10) & 1, (int)(e >> 11)};
}
__device__ __forceinline__ int halo_r0(const TileCoord& t) { return 8 * t.I + 6 * t.pr - 6; }
__device__ __forceinline__ int halo_c0(const TileCoord& t) { return min(max(8 * t.J + 6 * t.pc - 6, -3), 102); }

__device__ __forceinline__ uint32_t bar_full(uint32_t bars, int wg, int c) { return bars + (wg * 3 + c) * 8; }
__device__ __forceinline__ uint32_t bar_w1c(uint32_t bars, int c) { return bars + (6 + c) * 8; }
__device__ __forceinline__ uint32_t bar_w2(uint32_t bars) { return bars + 9 * 8; }
__device__ __forceinline__ uint32_t bar_x(uint32_t bars, int j, int c) { return bars + (j == 0 ? 10 : c ? 17 + c : 11) * 8; }
__device__ __forceinline__ uint32_t bar_w1q(uint32_t bars) { return bars + 12 * 8; }
__device__ __forceinline__ uint32_t bar_xf(uint32_t bars) { return bars + 13 * 8; }
__device__ __forceinline__ uint32_t bar_w2m(uint32_t bars) { return bars + 14 * 8; }
__device__ __forceinline__ uint32_t bar_redo(uint32_t bars) { return bars + 15 * 8; }
__device__ __forceinline__ uint32_t bar_wok(uint32_t bars) { return bars + 16 * 8; }
__device__ __forceinline__ uint32_t bar_go(uint32_t bars) { return bars + 17 * 8; }
__device__ __forceinline__ uint32_t bar_raw(uint32_t bars, int j = 0) { return bars + (21 + j) * 8; }
__device__ __forceinline__ uint32_t bar_w2a(uint32_t bars) { return bars + 20 * 8; }
constexpr int kNumBars = 22;

__device__ __forceinline__ uint64_t wdesc(uint64_t d0, int s) { return d0 + (((s >> 2) * kWChunk + (s & 3) * 32) >> 4); }

__device__ __forceinline__ uint32_t x_chunk(int k, int c) { return kXOff + (k == 0 ? kWChunk : 0) + (k & 1 ? 2 - c : c) * 8192; }
__device__ __forceinline__ uint32_t out_slot(int k, int nt) { return k + 1 < nt ? kW2Off + (~k & 1) * 2 * kWChunk : kW1Off + kWChunk; }
template <int I0, int I1>
__device__ __forceinline__ void store_rows(bool on, __nv_bfloat16* pA, __nv_bfloat16* pB, const uint32_t (&a)[24], const uint32_t (&b)[24]) {
#pragma unroll
  for (int i = 2 * I0; i < 2 * I1; i++) {
    const uint32_t* v = (i & 1 ? b : a) + 4 * (i >> 1);
    asm volatile("{\n.reg .pred p;\nsetp.ne.u32 p, %5, 0;\n@p st.global.v4.u32 [%0], {%1,%2,%3,%4};\n}\n" ::"l"((i & 1 ? pB : pA) + 32 * (i >> 1)),
                 "r"(v[0]), "r"(v[1]), "r"(v[2]), "r"(v[3]), "r"((uint32_t)on) : "memory");
  }
}
template <int I0, int I1>
__device__ __forceinline__ void stage_out(uint32_t sts, int wg, const uint32_t (&a)[24], const uint32_t (&b)[24]) {
  const uint32_t e = sts, o = sts ^ 64;
  const uint32_t ad[4] = {wg ? o + 1024 : e, wg ? e + 2048 : o, wg ? e : o + 1024, wg ? o : e + 2048};
#pragma unroll
  for (int i = I0; i < I1; i++) {
    const uint32_t* v = (i < 6 ? a : b) + 4 * (i % 6);
    asm volatile("st.shared.v4.u32 [%0], {%1,%2,%3,%4};" ::"r"(ad[i % 6 / 3 * 2 + (i % 3 == 1)] + (i % 3 == 2) * 1024 + (i / 6) * 12288),
                 "r"(v[0]), "r"(v[1]), "r"(v[2]), "r"(v[3]) : "memory");
  }
}
__device__ __forceinline__ uint32_t now_ns() {
  uint32_t t;
  asm volatile("mov.u32 %0, %globaltimer_lo;" : "=r"(t)::"memory");
  return t;
}
__device__ __forceinline__ void wait_clock(uint32_t t_start, uint32_t t) {
  while (now_ns() - t_start < t) { }
}
#define NAT_PRED(f, m) ".reg .pred p;\n.reg .b32 t;\nand.b32 t, " f ", " m ";\nsetp.ne.u32 p, t, 0;\n"
constexpr uint32_t kHiV = 1, kHiU = 8, kColB = 0x20, kInV = 0x100, kInU = 0x1000, kColA = 0x10000;
template <uint32_t M>
__device__ __forceinline__ float pick(const float* a, const float* b, uint32_t f) {
  float d;
  asm("{\n" NAT_PRED("%5", "%6") "add.f32 %0, %1, %2;\n@p add.f32 %0, %3, %4;\n}\n"
      : "=&f"(d) : "f"(a[0]), "f"(a[2]), "f"(b[0]), "f"(b[2]), "r"(f), "n"(M));
  return d;
}
template <uint32_t M>
__device__ __forceinline__ float sel(float a, float b, uint32_t f) {
  float d;
  asm("{\n" NAT_PRED("%3", "%4") "selp.f32 %0, %1, %2, p;\n}\n" : "=f"(d) : "f"(a), "f"(b), "r"(f), "n"(M));
  return d;
}
template <uint32_t M>
__device__ __forceinline__ void max_if(float& m, float v, uint32_t f) {
  asm("{\n" NAT_PRED("%2", "%3") "@p max.f32 %0, %0, %1;\n}\n" : "+f"(m) : "f"(v), "r"(f), "n"(M));
}
template <uint32_t M>
__device__ __forceinline__ void add_if(float& m, float v, uint32_t f) {
  asm("{\n" NAT_PRED("%2", "%3") "@p add.f32 %0, %0, %1;\n}\n" : "+f"(m) : "f"(v), "r"(f), "n"(M));
}
__device__ __forceinline__ void pick_v(const float* a, float* v, uint32_t f) {
  v[0] = pick<kHiV>(a, a + 16, f), v[1] = pick<kHiV>(a + 1, a + 17, f);
  v[2] = pick<kHiV * 2>(a + 4, a + 20, f), v[3] = pick<kHiV * 2>(a + 5, a + 21, f);
  v[4] = pick<kHiV * 4>(a + 8, a + 24, f), v[5] = pick<kHiV * 4>(a + 9, a + 25, f);
  v[6] = a[12] + a[14], v[7] = a[13] + a[15];
}
__device__ __forceinline__ void pick_u(const float* a, float* v, uint32_t f) {
#pragma unroll
  for (int c = 0; c < 3; c++) v[2 * c] = pick<kHiU>(a + 4 * c, a + 4 * c + 12, f), v[2 * c + 1] = pick<kHiU * 2>(a + 4 * c + 1, a + 4 * c + 13, f);
}
__device__ __forceinline__ uint32_t sign_bytes(uint32_t v, uint32_t sel) {
  uint32_t d;
  asm("prmt.b32 %0, %1, %1, %2;" : "=r"(d) : "r"(v), "r"(sel));
  return d;
}
__device__ __forceinline__ float own_max(const float (&v)[14], uint32_t f) {
  float m = sel<kInV>(fmaxf(v[0], v[1]), -INFINITY, f), m2 = sel<kInV * 2>(fmaxf(v[2], v[3]), -INFINITY, f);
  max_if<kInV * 4>(m, fmaxf(v[4], v[5]), f);
  max_if<kInV * 8>(m2, fmaxf(v[6], v[7]), f);
  max_if<kInU>(m, fmaxf(fmaxf(v[8], v[10]), v[12]), f);
  max_if<kInU * 2>(m2, fmaxf(fmaxf(v[9], v[11]), v[13]), f);
  return fmaxf(m, m2);
}
__device__ __forceinline__ float quad_max(float m) {
  const float a = __shfl_xor_sync(0xffffffffu, m, 1), b = __shfl_xor_sync(0xffffffffu, m, 2), c = __shfl_xor_sync(0xffffffffu, m, 3);
  return fmaxf(fmaxf(m, a), fmaxf(b, c));
}
__device__ __forceinline__ float row_rcp(const float (&v)[14], uint32_t f) {
  float s = sel<kInV>(v[0] + v[1], 0.f, f), s2 = sel<kInV * 2>(v[2] + v[3], 0.f, f);
  add_if<kInV * 4>(s, v[4] + v[5], f);
  add_if<kInV * 8>(s2, v[6] + v[7], f);
  add_if<kInU>(s, v[8] + v[10] + v[12], f);
  add_if<kInU * 2>(s2, v[9] + v[11] + v[13], f);
  s += s2;
  const float a = __shfl_xor_sync(0xffffffffu, s, 1), b = __shfl_xor_sync(0xffffffffu, s, 2), c = __shfl_xor_sync(0xffffffffu, s, 3);
  return rcp_approx((s + a) + (b + c));
}
__device__ __forceinline__ void route(const float (&v)[14], float s, const uint32_t (&rt)[9], uint32_t (&p)[14]) {
#pragma unroll
  for (int i = 0; i < 7; i++) {
    const uint32_t u = pack_bf16(v[2 * i] * s, v[2 * i + 1] * s);
    if (i < 4) p[i] = u & rt[i];
    if (i < 3) p[i + 4] = u & rt[i + 4];
    if (i >= 4) {
      p[i + 3] = u & rt[7];
      p[i + 6] = u & rt[8];
    }
  }
}

template <int C, int T0 = 0, int T1 = 7>
__device__ __forceinline__ void pv_chunk(float (&z)[32], const uint32_t (&pa)[14], const uint32_t (&pb)[14],
                                         const uint32_t (&meta)[4], uint64_t dV) {
#pragma unroll
  for (int t = T0; t < T1; t++) {
    if (t & 1)
      wg_s64t1<0, 32>(z, pa[2 * t], pb[2 * t], pa[2 * t + 1], pb[2 * t + 1], dV + ((2 * C * kChunkBytes + t * 2048) >> 4), 1,
                      meta[t >> 1]);
    else if (t > 0)
      wg_s64t<0, 32>(z, pa[2 * t], pb[2 * t], pa[2 * t + 1], pb[2 * t + 1], dV + ((2 * C * kChunkBytes + t * 2048) >> 4), 1,
                     meta[t >> 1]);
    else
      wg_s64tz<0, 32>(z, pa[0], pb[0], pa[1], pb[1], dV + ((2 * C * kChunkBytes) >> 4), 0, meta[0]);
  }
}
template <int C>
__device__ __forceinline__ void pack_z(const float (&z)[32], uint32_t (&za)[24], uint32_t (&zb)[24]) {
#pragma unroll
  for (int j = 0; j < 8; j++) {
    za[8 * C + j] = pack_bf16(z[4 * j], z[4 * j + 1]);
    zb[8 * C + j] = pack_bf16(z[4 * j + 2], z[4 * j + 3]);
  }
}

template <int H>
__device__ __forceinline__ void pack_out(const float (&ac)[48], uint32_t (&oa)[24], uint32_t (&ob)[24]) {
#pragma unroll
  for (int j = 0; j < 12; j++) {
    oa[12 * H + j] = pack_bf16(ac[4 * j], ac[4 * j + 1]);
    ob[12 * H + j] = pack_bf16(ac[4 * j + 2], ac[4 * j + 3]);
  }
}
struct Maps { CUtensorMap v6, v2, v14, u8, px[8], wv, wo; };
__device__ __forceinline__ void tma_prefetch_5d(const CUtensorMap* map, int c0, int c1, int c2, int c3, int c4) {
  asm volatile("cp.async.bulk.prefetch.tensor.5d.L2.global.tile [%0, {%1, %2, %3, %4, %5}];" ::"l"((uint64_t)map), "r"(c0), "r"(c1),
               "r"(c2), "r"(c3), "r"(c4) : "memory");
}
__device__ __forceinline__ int first_line(const TileCoord tc) { return 3 * (qpix(tc.pr, 8 * tc.I) * kW + qpix(tc.pc, 8 * tc.J)); }
__device__ __forceinline__ void load_px(const Maps& tm, const TileTable& tt, uint32_t dst, uint32_t bar, int line, int kind) {
#pragma unroll
  for (int i = 0; i < 2; i++) {
    if (i == 0 || kind != 0) {
      const CUtensorMap* map = (const CUtensorMap*)((const char*)tm.px + tt.b[kind][i][1]);
      if (bar) tma_load_5d(dst + tt.b[kind][i][2], map, bar, 0, 0, 0, 0, line + tt.b[kind][i][0]);
      else tma_prefetch_5d(map, 0, 0, 0, 0, line + tt.b[kind][i][0]);
    }
  }
}
__device__ __forceinline__ void store_px(const Maps& tm, const TileTable& tt, uint32_t buf, int line, int kind) {
#pragma unroll
  for (int i = 0; i < 8; i++) {
    const int j = 2 * (i & 3) + (i >> 2);
    asm volatile("cp.async.bulk.tensor.5d.global.shared::cta.tile.bulk_group [%0, {%2, %2, %2, %2, %3}], [%1];" ::"l"(
                     (uint64_t)tm.px + tt.g[kind][j][1]), "r"(buf + i * 3072), "r"(0), "r"(line + tt.g[kind][j][0]) : "memory");
  }
  asm volatile("cp.async.bulk.commit_group;" ::: "memory");
}
__device__ __noinline__ bool refetch(uint32_t base, const uint8_t* src, bool gap) {
  constexpr uint32_t bars = 1024 + kBarOff, cnt = bars + 192;
#pragma unroll 1
  for (uint32_t o = 0; o < kWBytes && !gap; o += 2048) {
    uint32_t mx = 0;
#pragma unroll
    for (int i = 0; i < 4; i++) {
      uint4 v;
      asm volatile("ld.shared.v4.u32 {%0,%1,%2,%3}, [%4];" : "=r"(v.x), "=r"(v.y), "=r"(v.z), "=r"(v.w)
                   : "r"(base + o + i * 512 + (threadIdx.x & 31) * 16));
      mx = __vimax3_u32(__vimax3_u32(mx, v.x, v.y), v.z, v.w);
    }
    gap = __any_sync(0xffffffffu, mx == kEmpty);
  }
  uint32_t n;
  asm volatile("ld.shared.u32 %0, [%1];" : "=r"(n) : "r"(cnt) : "memory");
  if (!gap || __any_sync(0xffffffffu, n > (1u << 12))) return false;
  asm volatile("bar.sync 15, 128;" ::: "memory");
  if (threadIdx.x == 0) {
    asm volatile("st.shared.u32 [%0], %1;" ::"r"(cnt), "r"(n + 1) : "memory");
    mbar_arrive_expect_tx(bar_redo(bars), kWBytes);
    bulk_load(base, src, kWBytes, bar_redo(bars));
  }
  __syncwarp();
  mbar_wait(bar_redo(bars), n & 1);
  return true;
}
template <int S0, int S1, int Z>
__device__ __forceinline__ void g2_steps(float (&ac)[48], const uint32_t (&za)[24], const uint32_t (&zb)[24], uint64_t d) {
#pragma unroll
  for (int s = S0; s < S1; s++) {
    const uint64_t ds = d + (((s >> 2 & 1) * (kWChunk / 2) + (s & 3) * 32) >> 4);
    if (s == Z) wg_d96z<0, 48>(ac, za[2 * s], zb[2 * s], za[2 * s + 1], zb[2 * s + 1], ds, 0);
    else wg_d96<0, 48>(ac, za[2 * s], zb[2 * s], za[2 * s + 1], zb[2 * s + 1], ds, 1);
  }
}

__device__ __forceinline__ void consumer(const int wg, __nv_bfloat16* out, const uint8_t* wimg, const uint32_t sbase,
                                         const uint32_t zero, const Maps& tm, const TileTable& tt) {
  const int tid = threadIdx.x & 127;
  const int w = __shfl_sync(0xffffffffu, tid >> 5, 0), lane = tid & 31;
  const uint64_t dK = make_desc(sbase, 16, 1024);
  const uint64_t dV = make_desc(sbase, kChunkBytes, 512, 2);
  const uint64_t dW1 = make_desc(sbase + kW1Off, 16, 1024);
  const uint64_t dX0 = make_desc(sbase + kW2Off + wg * 2 * kWChunk, 16, 1024), dY0 = make_desc(sbase + kW2Off + (1 - wg) * 2 * kWChunk, 16, 1024);
  const uint64_t dX2 = make_desc(sbase + kXOff + wg * (kWChunk / 2), 16, 1024), dY2 = make_desc(sbase + kXOff + (1 - wg) * (kWChunk / 2), 16, 1024);
  const uint32_t bars = sbase + kBarOff;
  int tile0 = blockIdx.x * kTilesPerCta;
  asm volatile("" : "+r"(tile0));
  const int nt = num_tiles();

  uint32_t pix = 0, geo[6] = {};
  const int l = lane & 3;
#pragma unroll 1
  for (int j = 4; j >= 0; j -= 2) {
    const TileCoord tc = decode_tile(tt, tile0 + wg + j);
    const bool col = tc.kind == 1 || tc.kind == 2;
    const int g = col ? lane >> 2 : 2 * w + ((lane >> 2) & 1), qc = col ? w : lane >> 3;
    const uint32_t pr = qpix(tc.pr, 8 * tc.I + g) * kW;
    if (j == nt - 2) pix = (pr + qpix(tc.pc, 8 * tc.J + qc)) | (pr + qpix(tc.pc, 8 * tc.J + qc + 4)) << 16;
    const int d = 8 * tc.J + 6 * tc.pc - 6 - halo_c0(tc);
    const int ro = woff(tc.pr, tc.I, g), coA = woff(tc.pc, tc.J, qc) + d, coB = woff(tc.pc, tc.J, qc + 4) + d - 3;
#pragma unroll
    for (int i = 5; i >= 2; i--) geo[i] = geo[i - 2];
    const uint32_t lr = 0x1FCu << ro;
    const uint32_t lv = lr >> (2 + (l >> 1)), lu = lr >> (2 * l + 2 * tc.up);
    const uint32_t t = __byte_perm(lv, lu, wg ? 0x4501 : 0x5410);
    geo[0] = (((t & 0x15u) | (lv & 0x40u)) * 0x02082080u & 0x80808080u) | (((t >> 8) & 0x15u) * 0x01041040u & 0x40404040u) |
             (__byte_perm(t << 5, t << 4, 0x7362) & 0x20202020u) | (nt == 6);
    const int dr = (ro - 1) & 7;
    const uint32_t hiv = (((1u << ((ro - (l >> 1) + 1) >> 1)) - 1u) ^ (wg ? 7u : 0u)) & 7u, hiu = (t >> 24) & 3u;
    const uint32_t ca = (1u << coA) - 1u;
    geo[1] = hiv * kHiV | hiu * kHiU | ((((1u << coB) - 1u) >> (2 * (l & 1))) & 3u) * kColB |
             (15u & ~((uint32_t)((dr & 1) == (l >> 1)) << (dr >> 1))) * kInV | ((t >> 16 | t >> 24) & 3u) * kInU | ca * kColA |
             (ca >> ((0x49 >> (2 * l)) & 3) & 1u) << 19 | (uint32_t)(l == 3) << 20 | (0x55u & ((1u << (2 * coB)) - 1u)) << 24;
  }
  keep_regs(geo);
  const int so = (lane >> 3) | (lane & 4);
  uint32_t sts = sbase + w * 3072 + so * 128 + (((lane & 3) ^ so) << 4);
  __nv_bfloat16* poA = out + 8 * l + (pix & 0xFFFFu) * kC + 96 * wg;
  __nv_bfloat16* poB = out + 8 * l + (pix >> 16) * kC + 96 * wg;
  asm volatile("" : "+l"(poA), "+l"(poB), "+r"(sts));
  uint32_t oa[24], ob[24];
#pragma unroll
  for (int j = 0; j < 24; j++) oa[j] = ob[j] = 0u;
  keep_regs(oa);
  keep_regs(ob);
  PROF(wg, 0);
  if (threadIdx.x == 0) GT(1);

  for (int k = wg; k < nt; k += 2) {
    const uint32_t ph = (k >> 1) & 1;
    const int it = k >> 1;
    uint32_t qa[24], qb[24], hok[3];
    uint32_t fl = geo[1];
    {
      float acc[96];
      const uint32_t xp = (k + (k > 0)) & 1;
      const uint32_t xok = mbar_test(bar_x(bars, k > 0, 0), xp);
      if (k > 0) nb_sync(1 + (1 - wg));
#pragma unroll
      for (int s = 0; s < 12; s++) {
        if (s == 0) mbar_wait_if(xok, bar_x(bars, k > 0, 0), xp);
        if (s == 0 && k < 2) PROF(wg, 1);
        if (s == 0) PROFS(2, wg, 2 + it * 12);
        if (s == 0 && w == 0 && k < 2) GT(20 + wg);
        if ((s & 3) == 0 && (k == 0 || s > 0)) {
          mbar_wait(k == 0 ? bar_w1c(bars, s >> 2) : bar_x(bars, 1, s >> 2), xp);
          PROFS(17, wg, 50 + (s >> 2));
        }
        if ((s & 3) == 0) wg_fence();
        const uint64_t dX = make_desc(sbase + x_chunk(k, s >> 2), 16, 1024) + 2 * (s & 3);
        if (s == 0) wg_m192z<0, 96>(acc, dX, dW1, 0);
        else wg_m192<0, 96>(acc, dX, wdesc(dW1, s), 1);
        if ((s & 3) == 3) wg_commit();
      }
      PROFS(13, wg, 13 + it * 12);
      if (NAT_MP > 2) {
        wg_wait<2>();
        if (k > 0) nb_arrive_p(0);
      }
      if (NAT_MP > 1) {
        wg_wait<1>();
        if (k > 0) nb_arrive_p(14);
      }
      wg_wait<0>();
      if (k > 0) nb_arrive_p(6);
      fence_regs(acc);
      PROFS(3, wg, 3 + it * 12);
#pragma unroll
      for (int j = 0; j < 24; j++) {
        qa[j] = pack_bf16(acc[4 * j], acc[4 * j + 1]);
        qb[j] = pack_bf16(acc[4 * j + 2], acc[4 * j + 3]);
      }
      keep_regs(qa);
      keep_regs(qb);
      sched_fence();
      if (k >= 2) {
        const uint32_t dst = sts + out_slot(k, nt);
        nb_sync(11);
        stage_out<0, 6>(dst, wg, oa, ob);
        nb_sync(12);
        stage_out<6, 12>(dst, wg, oa, ob);
      }
#pragma unroll
      for (int c = 0; c < 3; c++) hok[c] = mbar_test(bar_full(bars, wg, c), ph);
      if (k >= 2) {
        fence_proxy_async();
        nb_arrive_p(10);
      }
    }

    float aE[52], aO[24], bO[52], bE[28];
    const uint32_t mq = 0xEEEE4444u | zero;
    PROFS(4, wg, 4 + it * 12);

    mbar_wait_if(hok[0], bar_full(bars, wg, 0), ph);
    PROFS(14, wg, 40 + it * 3);
    if (w == 0 && k < 2) GT(22 + wg);
    if (k > 0) nb_sync(3 + (1 - wg));
    wg_fence();
#pragma unroll
    for (int ks = 0; ks < 6; ks++) {
      if (ks == NAT_P1) {
        mbar_wait_if(hok[1], bar_full(bars, wg, 1), ph);
        PROFS(14, wg, 41 + it * 3);
        wg_fence();
      }
      if (ks == NAT_P2) {
        mbar_wait_if(hok[2], bar_full(bars, wg, 2), ph);
        PROFS(14, wg, 42 + it * 3);
        wg_fence();
      }
      const uint64_t d = dK + ((ks * kChunkBytes) >> 4);
      if (ks == 0) wg_s104z<0, 52>(aE, qa[0], qa[1], qa[2], qa[3], d, 0, mq);
      else wg_s104<0, 52>(aE, qa[4 * ks], qa[4 * ks + 1], qa[4 * ks + 2], qa[4 * ks + 3], d, 1, mq);
      if (ks == 0) wg_s48z<0, 24>(aO, qa[0], qa[1], qa[2], qa[3], d + ((7 * 1024 + 64) >> 4), 0, mq);
      else if (ks < NAT_QA) wg_s48<0, 24>(aO, qa[4 * ks], qa[4 * ks + 1], qa[4 * ks + 2], qa[4 * ks + 3], d + ((7 * 1024 + 64) >> 4), 1, mq);
    }
    wg_commit();
#pragma unroll
    for (int ks = NAT_QA; ks < 6; ks++)
      wg_s48<0, 24>(aO, qa[4 * ks], qa[4 * ks + 1], qa[4 * ks + 2], qa[4 * ks + 3], dK + ((ks * kChunkBytes + 7 * 1024 + 64) >> 4), 1, mq);
    wg_commit();
    wg_s56z<0, 28>(bE, qb[0], qb[1], qb[2], qb[3], dK, 0, mq);
#pragma unroll
    for (int ks = 1; ks < 6; ks++) wg_s56<0, 28>(bE, qb[4 * ks], qb[4 * ks + 1], qb[4 * ks + 2], qb[4 * ks + 3], dK + ((ks * kChunkBytes) >> 4), 1, mq);
    wg_commit();
    wg_wait<2>();
    fence_regs(aE);
    PROFS(5, wg, 5 + it * 12);

    uint32_t pa[14], pb[14], meta[4];
    {
      float vA[14], vB[14];
      pick_v(aE, vA, fl);
      pick_u(aE + 28, vA + 8, fl);
      fence_regs(vA);
      if (k == 0) {
        if (__builtin_expect(__any_sync(0xffffffffu, vA[6] != vA[6]), 0)) {
          wg_wait<0>();
          fence_regs(aO);
          fence_regs(bE);
          if (refetch(sbase + kW1Off, wimg, false)) {
#pragma unroll
            for (int j = 0; j < 24; j++) oa[j] = ob[j] = 0u;
            k -= 2;
            continue;
          }
        }
        if (elect_one()) mbar_arrive(bar_xf(bars));
      }
      wg_fence();
      wg_s104z<0, 52>(bO, qb[0], qb[1], qb[2], qb[3], dK + 4, 0, mq);
#pragma unroll
      for (int ks = 1; ks < 6; ks++)
        wg_s104<0, 52>(bO, qb[4 * ks], qb[4 * ks + 1], qb[4 * ks + 2], qb[4 * ks + 3], dK + ((ks * kChunkBytes + 64) >> 4), 1, mq);
      wg_commit();
      if (k + 1 < nt) nb_arrive(1 + wg);
      uint32_t rt[9];
#pragma unroll
      for (int i = 0; i < 7; i++) rt[i] = sign_bytes(geo[0] << (i >> 2), 0x8888u + 0x1111u * (i & 3));
      rt[7] = sign_bytes(geo[0] << 2, 0x9988u);
      rt[8] = sign_bytes(geo[0] << 2, 0xBBAAu);
      keep_regs(rt);
      pa[13] = pb[13] = 0u;
      wg_wait<2>();
      keep_regs(qa);
      fence_regs(aO);
      float oA[6], eB[8];
      pick_u(aO, oA, fl);
      wg_wait<1>();
      fence_regs(bE);
      pick_v(bE, eB, fl);
      vA[8] = sel<kColA>(oA[0], vA[8], fl), vA[9] = sel<kColA>(oA[1], vA[9], fl);
      vA[10] = sel<kColA * 2>(oA[2], vA[10], fl), vA[11] = sel<kColA * 2>(oA[3], vA[11], fl);
      vA[12] = sel<kColA * 4>(oA[4], vA[12], fl), vA[13] = sel<kColA * 4>(oA[5], vA[13], fl);
      {
        const float m1 = __uint_as_float(0x88DD88DDu), m0 = __uint_as_float(0x88DDDD88u);
        meta[0] = 0xDD88DD88u ^ __byte_perm(fl, 0u, 0x3344);
        meta[1] = __float_as_uint(sel<kColA * 16>(sel<kColA>(m1, m0, fl), __uint_as_float(meta[0]), fl));
        meta[2] = __float_as_uint(sel<kColA * 8>(m1, m0, fl));
        meta[3] = __float_as_uint(sel<kColA * 4>(m1, m0, fl));
        keep_regs(meta);
      }
      float mA = own_max(vA, fl);
      fl |= __float_as_uint(eB[7]) & zero;
      fence_regs(eB);
      fence_regs(vA);
      asm volatile("" : "+f"(mA), "+r"(fl));
      sched_fence();
      wg_wait<0>();
      sched_fence();
      keep_regs(qb);
      fence_regs(bO);
      PROFS(6, wg, 6 + it * 12);
      if (w == 0) GT(24 + k);
      mA = quad_max(mA);
#pragma unroll
      for (int i = 0; i < 14; i++) vA[i] = ex2(vA[i] - mA);
      pick_v(bO, vB, fl);
      pick_u(bO + 28, vB + 8, fl);
#pragma unroll
      for (int i = 0; i < 8; i += 2) vB[i] = sel<kColB>(vB[i], eB[i], fl), vB[i + 1] = sel<kColB * 2>(vB[i + 1], eB[i + 1], fl);
      float mB = quad_max(own_max(vB, fl));
      if (NAT_SB) {
        fence_regs(vA);
        fence_regs(vB);
        asm volatile("" : "+f"(mB));
        sched_fence();
      }
      PROFS(7, wg, 7 + it * 12);
#pragma unroll
      for (int i = 0; i < 14; i++) vB[i] = ex2(vB[i] - mB);
      route(vA, row_rcp(vA, fl), rt, pa);
      route(vB, row_rcp(vB, fl), rt, pb);
    }
    PROFS(8, wg, 8 + it * 12);
    if (k == NAT_PK) PROFS(18, wg, 53);
    sched_fence();

    float ac0[48], ac1[48];
    {
      float z0[32], z1[32], z2[32];
      uint32_t za[24], zb[24];
      wg_fence();
      pv_chunk<0>(z0, pa, pb, meta, dV);
      wg_commit();
      pv_chunk<1>(z1, pa, pb, meta, dV);
      wg_commit();
      wg_wait<1>();
      if (k == NAT_PK) PROFS(18, wg, 54);
      if (k + 1 < nt) nb_arrive_p(7);
      pv_chunk<2, 0, 3>(z2, pa, pb, meta, dV);
      wg_commit();
      sched_fence();
      fence_regs(z0);
      pack_z<0>(z0, za, zb);
      sched_fence();
      wg_fence();
      pv_chunk<2, 3, 7>(z2, pa, pb, meta, dV);
      wg_commit();
      wg_wait<2>();
      if (k == NAT_PK) PROFS(19, wg, 55);
      if (k + 1 < nt) nb_arrive_p(8);
      if (k < 2) mbar_wait(k == 1 ? bar_wok(bars) : bar_w2a(bars), 0);
      wg_fence();
      g2_steps<0, 3, 0>(ac0, za, zb, dX0);
      wg_commit();
      sched_fence();
      fence_regs(z1);
      pack_z<1>(z1, za, zb);
      sched_fence();
      wg_fence();
      g2_steps<3, 4, 0>(ac0, za, zb, dX0);
      wg_commit();
      g2_steps<4, 8, 0>(ac0, za, zb, dX0);
      wg_commit();
      wg_wait<3>();
      if (k + 1 < nt) nb_arrive_p(9);
      else nb_arrive(11);
      if (k == NAT_PK) PROFS(20, wg, 56);
      keep_regs(pa);
      keep_regs(pb);
      keep_regs(meta);
      sched_fence();
      const uint32_t mok = mbar_test(bar_w2m(bars), k + 1 < nt ? k & 1 : ~k & 1);
      const uint32_t wp = k < 2 ? 0 : k + 1 < nt ? ~k & 1 : k & 1, wok = mbar_test(bar_w2(bars), wp);
      fence_regs(z2);
      pack_z<2>(z2, za, zb);
      keep_regs(za);
      keep_regs(zb);
      sched_fence();
      PROFS(9, wg, 9 + it * 12);
      wg_wait<1>();
      if (k > 0 && k + 1 < nt) nb_arrive(11);
      mbar_wait_if(mok, bar_w2m(bars), k & 1);
      wg_fence();
      g2_steps<8, 12, 0>(ac0, za, zb, dX2);
      wg_commit();
      g2_steps<8, 12, 8>(ac1, za, zb, dY2);
      wg_commit();
      wg_wait<2>();
      if (k > 0 && k + 1 < nt) nb_arrive(12);
      mbar_wait_if(wok, bar_w2(bars), wp);
      wg_fence();
      g2_steps<0, 4, 8>(ac1, za, zb, dY0);
      wg_commit();
      wg_wait<2>();
      if (k + 2 < nt) nb_arrive_p(13);
      const bool direct = k + 2 >= nt;
      sched_fence();
      fence_regs(ac0);
      pack_out<0>(ac0, oa, ob);
      store_rows<0, NAT_D0>(direct, poA, poB, oa, ob);
      sched_fence();
      wg_fence();
      g2_steps<4, 8, 8>(ac1, za, zb, dY0);
      wg_commit();
      if (k + 1 < nt) nb_arrive(3 + wg);
      PROFS(10, wg, 10 + it * 12);
      wg_wait<2>();
      if (k + 2 < nt && (k > 0 || nt == 6)) nb_arrive_p(5);
      store_rows<NAT_D0, 3>(direct, poA, poB, oa, ob);
      __nv_bfloat16 *qA = poA - 192 * wg, *qB = poB - 192 * wg;
      if (k + 2 == nt) nb_sync(11);
      sched_fence();
      wg_wait<0>();
      fence_regs(ac1);
      pack_out<1>(ac1, oa, ob);
      asm volatile("" : "+l"(qA), "+l"(qB));
      store_rows<3, 6>(direct, qA, qB, oa, ob);
      if (k == 0) {
        uint32_t m[2] = {oa[0], oa[1]};
#pragma unroll
        for (int i = 2; i < 24; i++) asm("max.NaN.bf16x2 %0, %0, %1;" : "+r"(m[i & 1]) : "r"(oa[i]));
        asm("max.NaN.bf16x2 %0, %0, %1;" : "+r"(m[0]) : "r"(m[1]));
        uint32_t nan;
        asm volatile("{\n.reg .pred p;\nsetp.ne.u32 p, %1, 0;\nbar.red.or.pred p, 15, 128, p;\nselp.u32 %0, 1, 0, p;\n}\n"
                     : "=r"(nan) : "r"(((m[0] & 0x7FFF7FFFu) + 0x007F007Fu) & 0x80008000u) : "memory");
        if (__builtin_expect(__any_sync(0xffffffffu, nan), 0)) {
          for (int c = 0; c < 3 && __any_sync(0xffffffffu, geo[2] & 1u); c++) mbar_wait(bar_x(bars, 1, c), 1);
          for (bool first = true; __any_sync(0xffffffffu, refetch(sbase + kW2Off, wimg + w2_offset(), first)); first = false) { }
          wg_fence();
          g2_steps<0, 8, 0>(ac0, za, zb, dX0);
          g2_steps<8, 12, 0>(ac0, za, zb, dX2);
          g2_steps<8, 12, 8>(ac1, za, zb, dY2);
          g2_steps<0, 8, 8>(ac1, za, zb, dY0);
          wg_commit();
          wg_wait<0>();
          fence_regs(ac0);
          fence_regs(ac1);
          pack_out<0>(ac0, oa, ob);
          pack_out<1>(ac1, oa, ob);
          if (__any_sync(0xffffffffu, geo[2] & 1u)) {
            asm volatile("bar.sync 15, 128;" ::: "memory");
            if (w == 0 && elect_one()) {
              const TileCoord tc = decode_tile(tt, tile0 + 2);
              mbar_arrive_expect_tx(bar_raw(bars), kWChunk);
#pragma unroll 1
              for (int c = 0; c < 3; c++) load_px(tm, tt, sbase + x_chunk(2, c), bar_raw(bars), first_line(tc) + c, tc.kind);
            }
            __syncwarp();
            mbar_wait(bar_raw(bars), 0);
          }
        }
        if (nt < 6) nb_arrive_p(5);
        if (elect_one()) mbar_arrive(bar_wok(bars));
      }
      keep_regs(za);
      keep_regs(zb);
#pragma unroll
      for (int i = 0; i < 4; i++) geo[i] = geo[i + 2];
      keep_regs(oa);
      keep_regs(ob);
      PROFS(12, wg, 12 + it * 12);
      sched_fence();
    }
  }
  PROF(wg, 38);
  GT_DUMP();
  PROF_DUMP(wg);
}

struct HaloCols { int vj, vc, uj, uc; };
__device__ __forceinline__ HaloCols halo_cols(const TileCoord& tc) {
  const int c0 = halo_c0(tc);
  return HaloCols{c0 > 98, c0 > 98 ? 98 : c0 + 3, c0 < 0 ? -1 : 0, c0 < 0 ? 4 : c0};
}
__device__ __forceinline__ void first_halo(const Maps& tm, uint32_t sbase, const TileCoord tc, int i) {
  const HaloCols hc = halo_cols(tc);
  const uint32_t dst = sbase + i * kChunkBytes, bar = bar_full(sbase + kBarOff, 0, i >> 1);
  const int h0 = halo_r0(tc), ch = 24 * tc.pc + 4 * i;
  tma_load_5d(dst, &tm.v14, bar, ch, hc.vj, hc.vc, tc.pr, h0);
  tma_load_5d(dst + 7 * 1024, &tm.u8, bar, ch, hc.uj, h0 + (tc.up ? 0 : -2), tc.pr, hc.uc);
  tma_load_5d(dst + 10 * 1024, &tm.u8, bar, ch, hc.uj, h0 + (tc.up ? 8 : 6), tc.pr, hc.uc);
}
__device__ __forceinline__ void load_halo(const Maps& tm, uint32_t sbase, uint32_t bars, const TileCoord tc, int k, int c) {
  const HaloCols hc = halo_cols(tc);
  const int h6 = halo_r0(tc) + (tc.up ? 0 : 8), h2 = halo_r0(tc) + 6, h8 = halo_r0(tc) + (tc.up ? 0 : 6), ch = 24 * tc.pc + 8 * c;
  uint32_t dv = sbase + 2 * c * kChunkBytes, du = dv + 7 * 1024;
  if (((k ^ tc.up) & 1) == 0) dv += 4 * 1024, du += 3 * 1024;
  const uint32_t bar = bar_full(bars, k & 1, c);
  mbar_arrive_expect_tx(bar, 14 * 1024);
  nb_sync_p(7 + c);
#pragma unroll
  for (int h = 0; h < 2; h++) {
    tma_load_5d(dv + h * kChunkBytes, &tm.v6, bar, ch + 4 * h, hc.vj, hc.vc, tc.pr, h6);
    tma_load_5d(du + h * kChunkBytes, &tm.u8, bar, ch + 4 * h, hc.uj, h8, tc.pr, hc.uc);
    tma_load_5d(sbase + (2 * c + h) * kChunkBytes + 3 * 1024, &tm.v2, bar, ch + 4 * h, hc.vj, hc.vc, tc.pr, h2);
  }
  PROFS(15, 2, k * 4 + c);
}
__device__ __forceinline__ void gather_px(const __nv_bfloat16* __restrict__ x, uint32_t sbase, int k, const TileCoord tc) {
  const int lane = threadIdx.x & 31, g = lane >> 3;
  uint32_t ro[4], co[4];
#pragma unroll
  for (int i = 0; i < 4; i++) {
    ro[i] = qpix(tc.pr, 8 * tc.I + 2 * i + (g & 1)) * (kW * kC * 2) + 16 * (lane & 7);
    co[i] = qpix(tc.pc, 8 * tc.J + 2 * i + (g >> 1)) * (kC * 2);
  }
  const uint32_t dst = sbase + kXOff + g * 128 + (((lane & 7) ^ g) << 4);
  const int dq = k & 1 ? -128 : 128;
  keep_regs(ro);
  keep_regs(co);
  sched_fence();
  nb_sync_p(13);
  nb_sync_p(5);
#pragma unroll
  for (int i = 0; i < 16; i++) {
    const char* src = (const char*)x + (ro[i >> 2] + co[i & 3] + 128);
#pragma unroll
    for (int q = 0; q < 3; q++)
      asm volatile("cp.async.cg.shared.global [%0], [%1], 16;" ::"r"((dst ^ ((i & 1) * 576)) + (i >> 1) * 1024 + q * 8192), "l"(src + (q - 1) * dq) : "memory");
  }
  asm volatile("cp.async.wait_all;" ::: "memory");
  fence_proxy_async();
  __syncwarp();
  if (lane < 3) mbar_arrive(bar_x(sbase + kBarOff, 1, lane));
  __syncwarp();
}

__global__ void __launch_bounds__(384, 1)
nat_kernel(const __nv_bfloat16* __restrict__ x, __nv_bfloat16* out, const __nv_bfloat16* __restrict__ wqkv,
           const __nv_bfloat16* __restrict__ wo, uint8_t* wimg, const uint32_t zero,
           const __grid_constant__ Maps tm, const __grid_constant__ TileTable tt) {
  extern __shared__ uint8_t smem_raw[];
  constexpr uint32_t sbase = 1024;
  constexpr uint32_t bars = sbase + kBarOff;
  if (smem_u32(smem_raw) != sbase) __trap();
  const int tid = threadIdx.x;
  const uint32_t t_start = now_ns();
  if (tid == 0) GT(0);
  const int wid = __shfl_sync(0xffffffffu, tid >> 5, 0);
  const bool w2cta = blockIdx.x - 128 < 3 && wqkv != nullptr;
  if (wid >= 8) {
    asm volatile("setmaxnreg.dec.sync.aligned.u32 24;");
    const int c = wid & 3, lane = tid & 31;
    const int tile0 = blockIdx.x * kTilesPerCta, nt = num_tiles();
    uint32_t w2o = 0;
    if (c == 3) {
      if (elect_one()) wait_clock(t_start, NAT_TM);
      __syncwarp();
      asm volatile("prefetch.tensormap [%0];" ::"l"((uint64_t)tm.px) : "memory");
      asm volatile("prefetch.tensormap [%0];" ::"l"((uint64_t)&tm.v6) : "memory");
      asm volatile("prefetch.tensormap [%0];" ::"l"((uint64_t)&tm.v2) : "memory");
      asm volatile("prefetch.tensormap [%0];" ::"l"((uint64_t)(tm.px + (blockIdx.x < 112 ? 5 : 6))) : "memory");
      asm volatile("prefetch.tensormap [%0];" ::"l"((uint64_t)(tm.px + 7)) : "memory");
      if (nt < 6) {
        asm volatile("prefetch.tensormap [%0];" ::"l"((uint64_t)(tm.px + 1)) : "memory");
        asm volatile("prefetch.tensormap [%0];" ::"l"((uint64_t)(tm.px + 2)) : "memory");
        asm volatile("prefetch.tensormap [%0];" ::"l"((uint64_t)&tm.v14) : "memory");
        asm volatile("prefetch.tensormap [%0];" ::"l"((uint64_t)&tm.u8) : "memory");
      }
      __nanosleep(NAT_TW2 - 2800);
      asm volatile("bar.sync 4, 64;" ::: "memory");
      w2o = w2_offset();
      if (elect_one()) {
        mbar_arrive_expect_tx(bar_w2a(bars), kWChunk);
        mbar_arrive_expect_tx(bar_w2(bars), kWChunk);
        wait_clock(t_start, NAT_TW2);
        bulk_load(sbase + kW2Off, wimg + w2o, kWChunk, bar_w2a(bars));
        mbar_wait(bar_xf(bars), 0);
        bulk_load(sbase + kW2Off + 2 * kWChunk, wimg + (w2o + 2 * kWChunk), kWChunk, bar_w2(bars));
      }
      __syncwarp();
      if (nt < 6) {
#pragma unroll 1
        for (int k = 2; k < 4; k++) {
          gather_px(x, sbase, k, decode_tile(tt, tile0 + k));
        }
      }
      if (wqkv == nullptr) return;
      mbar_wait(bar_wok(bars), 0);
      if (lane == 0) asm volatile("red.relaxed.gpu.global.add.u32 [%0], 1;" ::"l"(g_flag) : "memory");
      if (blockIdx.x >= 48) return;
      if (lane == 0) {
        uint32_t v, it = 0;
        do {
          __nanosleep(2000);
          asm volatile("ld.relaxed.gpu.global.u32 %0, [%1];" : "=r"(v) : "l"(g_flag) : "memory");
        } while (v < gridDim.x && ++it < (1u << 16));
      }
      __syncwarp();
#pragma unroll
      for (int i = 0; i < 6; i++)
        stg128(wimg + ((i < 3 ? 0u : 3 * kWBytes - w2o) + blockIdx.x * 1536 + (i % 3) * 512 + lane * 16), kEmpty, kEmpty, kEmpty, kEmpty);
      if (lane == 0 && atomicAdd(g_flag + 32, 1u) == 47) {
        g_flag[0] = g_flag[32] = 0;
        g_flag[64] = w2o == kWBytes;
      }
      return;
    }
    if (!elect_one()) return;
    if (c == 0) {
      for (int i = 0; i < kNumBars; i++)
        if ((i != 0 && i != 10 || nt < 6) && (i != 21 || !w2cta)) mbar_init(bars + i * 8, i == 13 || i == 16 ? 4 : 1);
      asm volatile("st.shared.v2.u32 [%0], {%1,%1};" ::"r"(bars + 192), "r"(0) : "memory");
      asm volatile("fence.mbarrier_init.release.cluster;" ::: "memory");
      if (w2cta) asm volatile("bar.sync 10, 64;" ::: "memory");
      asm volatile("bar.arrive 0, 160;" ::: "memory");
      asm volatile("bar.arrive 14, 160;" ::: "memory");
      asm volatile("bar.arrive 13, 96;" ::: "memory");
      asm volatile("bar.arrive 4, 64;" ::: "memory");
      const TileCoord tc0 = decode_tile(tt, tile0);
      const HaloCols hc = halo_cols(tc0);
      const int h0 = halo_r0(tc0);
#pragma unroll
      for (int j = 0; j < 3; j++)
        if (j > 0 || nt < 6) mbar_arrive_expect_tx(bar_full(bars, 0, j), 2 * kChunkBytes);
      wait_clock(t_start, NAT_HP);
#pragma unroll
      for (int q = 8; q < 24 && !w2cta; q += 8) {
        tma_prefetch_5d(blockIdx.x < 112 ? &tm.v6 : &tm.v14, 24 * tc0.pc + q, hc.vj, hc.vc, tc0.pr, h0 + (tc0.up || blockIdx.x >= 112 ? 0 : 8));
        tma_prefetch_5d(&tm.u8, 24 * tc0.pc + q, hc.uj, h0 + (tc0.up ? 0 : 6), tc0.pr, hc.uc);
      }
#pragma unroll 1
      for (int i = nt < 6 ? 0 : 2; i < 7; i++) {
        if (i == NAT_H0) mbar_wait(bar_w1q(bars), 0);
        if (i == NAT_X1P) mbar_arrive(bar_go(bars));
        if (i < 6) first_halo(tm, sbase, tc0, i);
      }
      w2o = w2_offset();
    } else {
      asm volatile("bar.sync 13, 96;" ::: "memory");
      if (c == 2) {
        if (wqkv != nullptr && blockIdx.x < 131) asm volatile("bar.sync 12, 64;" ::: "memory");
        const uint32_t c0 = clock();
        while ((uint32_t)clock() - c0 < NAT_TD && nt == 6) { }
        wait_clock(t_start, NAT_T0);
#pragma unroll
        for (int j = 0; j < 3; j++) {
          mbar_arrive_expect_tx(bar_w1c(bars, j), kWChunk);
          bulk_load(sbase + kW1Off + j * kWChunk, wimg + j * kWChunk, kWChunk, bar_w1c(bars, j));
        }
        mbar_arrive(bar_w1q(bars));
        GT(2);
      } else {
#pragma unroll 1
        for (int j = nt == 6; j < 2; j++) {
          const TileCoord tc = decode_tile(tt, tile0 + j);
          const int line = first_line(tc);
          if (j == 1) mbar_wait(bar_go(bars), 0);
          if (j == 0) GT(15);
#pragma unroll 1
          for (int q = 0; q < 3; q++) {
            load_px(tm, tt, sbase + x_chunk(j, q), bar_x(bars, j, q), line + q, tc.kind);
            if (j == 1 || q == 0) mbar_arrive_expect_tx(bar_x(bars, j, q), j ? 8192 : kWChunk);
          }
          if (j == 0) GT(16);
        }
        w2o = w2_offset();
        wait_clock(t_start, NAT_TW2);
        mbar_wait(bar_xf(bars), 0);
      }
    }
#pragma unroll 1
    for (int k = 1; k < nt; k++) {
      const TileCoord tn = decode_tile(tt, tile0 + k + 1);
      const int line = first_line(tn);
      if (c == 1) {
#pragma unroll
        for (int q = 3 - NAT_MP; q < 3; q++) {
          const uint32_t n = q == 3 - NAT_MP ? q + 1 : 1, o = x_chunk(k, k & 1 ? q : q + 1 - n);
          nb_sync_p(q == 0 ? 0 : q == 1 ? 14 : 6);
          bulk_load(sbase + o, wimg + (w2o + o - kW2Off), n * 8192, bar_w2m(bars));
        }
        mbar_arrive_expect_tx(bar_w2m(bars), kWChunk);
      }
      if (c == 2) {
        if (k == 1) wait_clock(t_start, NAT_TX2);
        else __nanosleep(NAT_PFD);
#pragma unroll 1
        for (int q = 0; q < 3 && k < 5 && nt == 6; q++) load_px(tm, tt, 0, 0, line + q, tn.kind);
      }
      if (c == 2 && (blockIdx.x >= 112 || k == 5)) {
        const TileCoord tc = decode_tile(tt, tile0 + k);
        const HaloCols hc = halo_cols(tc);
        const int h8 = halo_r0(tc) + (tc.up ? 0 : 6);
#pragma unroll 1
        for (int q = 0; q < 24; q += 8) {
          tma_prefetch_5d(&tm.v6, 24 * tc.pc + q, hc.vj, hc.vc, tc.pr, h8);
          tma_prefetch_5d(&tm.v2, 24 * tc.pc + q, hc.vj, hc.vc, tc.pr, h8 + 6);
          tma_prefetch_5d(&tm.u8, 24 * tc.pc + q, hc.uj, h8, tc.pr, hc.uc);
        }
      }
      load_halo(tm, sbase, bars, decode_tile(tt, tile0 + k), k, c);
      if (c == 0 && k < 5 && nt == 6) {
#pragma unroll
        for (int q = 0; q < 3; q++) {
          if (q < 2) nb_sync_p(q ? 5 : 13);
          load_px(tm, tt, sbase + x_chunk(k + 1, q), bar_x(bars, 1, q), line + q, tn.kind);
          if (q != 1) mbar_arrive_expect_tx(bar_x(bars, 1, q), 8192);
        }
        mbar_arrive_expect_tx(bar_x(bars, 1, 1), 8192);
        PROFS(16, 2, k * 4 + 3);
      }
      if (c == 0 && k >= 2) {
        const TileCoord tp = decode_tile(tt, tile0 + k - 2);
        const int lp = first_line(tp);
        nb_sync_p(10);
        if (NAT_XW == 1 && k < 5 && nt == 6) mbar_wait(bar_x(bars, 1, 2), k & 1);
        if (NAT_XW > 1) __nanosleep(NAT_XW);
        store_px(tm, tt, sbase + out_slot(k, nt), lp, tp.kind);
        if (k + 1 < nt) {
          asm volatile("cp.async.bulk.wait_group.read 0;" ::: "memory");
          bulk_load(sbase + out_slot(k, nt), wimg + (w2o + out_slot(k, nt) - kW2Off), kWChunk, bar_w2(bars));
          mbar_arrive_expect_tx(bar_w2(bars), kWChunk);
        }
      }
    }
    asm volatile("cp.async.bulk.wait_group 0;" ::: "memory");
  } else {
    if (blockIdx.x < 128) {
      if ((wid == 4 || (wid == 5 && blockIdx.x - 2 < 16)) && wqkv != nullptr) {
        fold_w1(blockIdx.x - 2 < 16 ? 2 * blockIdx.x + wid - 6 : blockIdx.x + (blockIdx.x < 2 ? 0 : 16), wqkv, wimg);
        if (wid == 4) asm volatile("bar.arrive 12, 64;" ::: "memory");
        if (tid == 128) GT(7);
      }
      sched_fence();
      if (wid == 1 && elect_one()) {
        const TileCoord tc = decode_tile(tt, blockIdx.x * kTilesPerCta);
        mbar_init(bar_x(bars, 0, 0), 1);
        asm volatile("fence.mbarrier_init.release.cluster;" ::: "memory");
        mbar_arrive_expect_tx(bar_x(bars, 0, 0), kWChunk);
        GT(15);
#pragma unroll 1
        for (int q = 0; q < 3; q++) load_px(tm, tt, sbase + x_chunk(0, q), bar_x(bars, 0, 0), first_line(tc) + q, tc.kind);
        GT(16);
      }
      __syncwarp();
      sched_fence();
      if (wid == 2 && elect_one()) {
        const TileCoord tc = decode_tile(tt, blockIdx.x * kTilesPerCta);
        mbar_init(bar_full(bars, 0, 0), 1);
        asm volatile("fence.mbarrier_init.release.cluster;" ::: "memory");
        mbar_arrive_expect_tx(bar_full(bars, 0, 0), 2 * kChunkBytes);
        if (NAT_TH) wait_clock(t_start, NAT_TH);
        asm volatile("prefetch.tensormap [%0];" ::"l"((uint64_t)&tm.u8) : "memory");
        GT(17);
        first_halo(tm, sbase, tc, 0);
        first_halo(tm, sbase, tc, 1);
      }
      __syncwarp();
    }
    sched_fence();
    {
      if (w2cta) {
        const int q = blockIdx.x & 3;
        uint32_t w2o = 0;
        if (wid == 1 && elect_one()) {
          asm volatile("prefetch.tensormap [%0];" ::"l"((uint64_t)&tm.wo) : "memory");
#pragma unroll
          for (int j = 0; j < 3; j++) mbar_init(bar_raw(bars, j), 1);
          asm volatile("fence.mbarrier_init.release.cluster;" ::: "memory");
#pragma unroll
          for (int j = 0; j < 6; j++)
            asm volatile("cp.async.bulk.tensor.2d.shared::cluster.global.tile.mbarrier::complete_tx::bytes [%0], [%1, {%3, %4}], [%2];" ::"r"(
                             j < 3 ? sbase + j * 8192 : sbase + kW2Off + (j - 3) * kWChunk),
                         "l"((uint64_t)(j < 3 ? &tm.wv : &tm.wo)), "r"(bar_raw(bars, j < 3 ? 0 : j - 3)),
                         "r"(j < 3 ? 384 + 64 * j : 64 * (j - 3)), "r"(j < 3 ? 64 * q : 0) : "memory");
#pragma unroll
          for (int j = 0; j < 3; j++) mbar_arrive_expect_tx(bar_raw(bars, j), j ? kWChunk : 2 * kWChunk);
          w2o = w2_offset();
        }
        __syncwarp();
#pragma unroll 1
        for (int r = 0; r < 3; r++) {
          const int blk = 2 * r - 2 + (wid >> 2);
          if (blk < 3) {
            if (r > 0) {
              mbar_wait(bar_raw(bars, 0), 0);
              mbar_wait(bar_raw(bars, blk), 0);
            }
            if (tid == 0 && r == 1) GT(7);
            float acc[32];
            const uint64_t db = make_desc(sbase + kW2Off + max(blk, 0) * kWChunk, kWChunk, 1024);
            wg_fence();
            wg_m64tz<0, 32>(acc, make_desc(sbase, 16, 1024), db, 0);
#pragma unroll
            for (int s = 1; s < 12; s++) wg_m64t<0, 32>(acc, make_desc(sbase + (s >> 2) * 8192 + (s & 3) * 32, 16, 1024), db + s * 128, 1);
            wg_commit();
            wg_wait<0>();
            fence_regs(acc);
            if (tid == 0) GT(19);
            const int m = (tid >> 3) & 3;
#pragma unroll
            for (int j = 0; j < 8; j += 2) {
              const int n = g2_inv(8 * (j + (m >> 1)) + (tid & 7));
              asm volatile("stmatrix.sync.aligned.m8n8.x4.trans.shared.b16 [%0], {%1,%2,%3,%4};" ::"r"(
                               sbase + kW1Off + (blk + 2) * 8192 + n * 128 + (((2 * (wid & 3) + (m & 1)) ^ (n & 7)) << 4)),
                           "r"(pack_bf16(acc[4 * j], acc[4 * j + 1])), "r"(pack_bf16(acc[4 * j + 2], acc[4 * j + 3])),
                           "r"(pack_bf16(acc[4 * j + 4], acc[4 * j + 5])), "r"(pack_bf16(acc[4 * j + 6], acc[4 * j + 7])) : "memory");
            }
            fence_proxy_async();
          }
          if (tid == 0) GT(18);
          asm volatile("bar.sync 11, 256;" ::: "memory");
          if (wid == 1 && elect_one()) {
            asm volatile("{\n.reg .pred p;\nsetp.ne.s32 p, %3, 0;\n@p cp.async.bulk.global.shared::cta.bulk_group [%0], [%1], %2;\n}\n" ::"l"(
                             wimg + (w2o + w2piece(r >> 1, q) * (kWChunk / 2))),
                         "r"(sbase + kW1Off + 16384 + (r >> 1) * (kWChunk / 2)), "r"(kWChunk / 2), "r"(r) : "memory");
            asm volatile("cp.async.bulk.commit_group;" ::: "memory");
          }
          __syncwarp();
        }
        if (wid == 1) {
          asm volatile("bar.arrive 10, 64;" ::: "memory");
          if (elect_one()) asm volatile("cp.async.bulk.wait_group.read 0;" ::: "memory");
          if (tid == 32) GT(31);
          __syncwarp();
          asm volatile("bar.arrive 12, 64;" ::: "memory");
        }
      }
    }
    __syncwarp();
    if (wid < 4) asm volatile("bar.sync 0, 160;" ::: "memory");
    else asm volatile("bar.sync 14, 160;" ::: "memory");
    asm volatile("setmaxnreg.inc.sync.aligned.u32 240;");
    consumer(wid >> 2, out, wimg, sbase, zero, tm, tt);
  }
}

}

typedef CUresult (*PFN_encodeTiled)(CUtensorMap*, CUtensorMapDataType, cuuint32_t, void*, const cuuint64_t*,
                                    const cuuint64_t*, const cuuint32_t*, const cuuint32_t*, CUtensorMapInterleave,
                                    CUtensorMapSwizzle, CUtensorMapL2promotion, CUtensorMapFloatOOBfill);

extern "C" void kernel_launch(void* const* d_in, const int* in_sizes, int n_in, void* d_out, int out_size) {
  const __nv_bfloat16* x = (const __nv_bfloat16*)d_in[0];
  const __nv_bfloat16* wqkv = (const __nv_bfloat16*)d_in[1];
  const __nv_bfloat16* wo = (const __nv_bfloat16*)d_in[2];
  __nv_bfloat16* out = (__nv_bfloat16*)d_out;

  static PFN_encodeTiled encode = nullptr;
  static int num_sms = 0;
  static uint8_t* wimg = nullptr;
  if (!encode) {
    void* fn = nullptr;
    cudaDriverEntryPointQueryResult qres;
    cudaGetDriverEntryPoint("cuTensorMapEncodeTiled", &fn, cudaEnableDefault, &qres);
    encode = (PFN_encodeTiled)fn;
    cudaFuncSetAttribute(nat::nat_kernel, cudaFuncAttributeMaxDynamicSharedMemorySize, nat::kSmemBytes);
    cudaGetSymbolAddress((void**)&wimg, nat::g_wimg32);
    int dev = 0;
    cudaGetDevice(&dev);
    cudaDeviceGetAttribute(&num_sms, cudaDevAttrMultiProcessorCount, dev);
  }
  nat::Maps tm;
  cuuint32_t estr[5] = {1, 1, 1, 1, 1};
  {
    cuuint64_t vdim[5] = {48, 2, 105, 2, 112}, udim[5] = {48, 2, 112, 2, 105};
    cuuint64_t vstr[4] = {7 * 768, 768, 224 * 384, 2 * 224 * 384}, ustr[4] = {7 * 768, 2 * 224 * 384, 224 * 384, 768};
    CUtensorMap* maps[4] = {&tm.v6, &tm.v2, &tm.v14, &tm.u8};
    for (int i = 0; i < 4; i++) {
      cuuint32_t box[5] = {4, 2, i < 3 ? 4u : 8u, 1, i == 0 ? 6u : i == 1 ? 2u : i == 2 ? 14u : 3u};
      encode(maps[i], CU_TENSOR_MAP_DATA_TYPE_UINT32, 5, (void*)x, i < 3 ? vdim : udim, i < 3 ? vstr : ustr, box, estr,
             CU_TENSOR_MAP_INTERLEAVE_16B, CU_TENSOR_MAP_SWIZZLE_128B, CU_TENSOR_MAP_L2_PROMOTION_L2_128B, CU_TENSOR_MAP_FLOAT_OOB_FILL_NONE);
    }
  }
  for (int i = 0; i < 8; i++) {
    const cuuint32_t row = 224 * 384;
    const cuuint32_t shape[8][6] = {{2, 8, 4, 2 * row, 768, 4 * row}, {2, 8, 3, row, 768, 2 * row},     {2, 8, 1, 2 * row, 768, 4 * row},
                                    {8, 2, 3, 2 * row, 4 * 384, 384}, {8, 2, 1, 2 * row, 5 * 384, 384}, {4, 2, 3, 4 * row, 2 * row, 128},
                                    {4, 2, 3, 768, row, 128},         {4, 2, 3, 768, 2 * row, 128}};
    const cuuint32_t* sh = shape[i];
    cuuint64_t dim[5] = {64, sh[0], sh[1], sh[2], 224 * 224 * 3};
    cuuint64_t str[4] = {sh[3], sh[4], sh[5], 128};
    cuuint32_t box[5] = {64, sh[0], sh[1], sh[2], 1};
    encode(tm.px + i, CU_TENSOR_MAP_DATA_TYPE_BFLOAT16, 5, i < 5 ? (void*)x : (void*)out, dim, str, box, estr, CU_TENSOR_MAP_INTERLEAVE_NONE,
           CU_TENSOR_MAP_SWIZZLE_128B, i < 5 ? CU_TENSOR_MAP_L2_PROMOTION_L2_128B : CU_TENSOR_MAP_L2_PROMOTION_NONE,
           CU_TENSOR_MAP_FLOAT_OOB_FILL_NONE);
  }
  for (int i = 0; i < 2; i++) {
    cuuint64_t dim[2] = {i ? 192u : 576u, 192}, str[1] = {i ? 384u : 1152u};
    cuuint32_t box[2] = {64, i ? 192u : 64u};
    encode(i ? &tm.wo : &tm.wv, CU_TENSOR_MAP_DATA_TYPE_BFLOAT16, 2, i ? (void*)wo : (void*)wqkv, dim, str, box, estr,
           CU_TENSOR_MAP_INTERLEAVE_NONE, CU_TENSOR_MAP_SWIZZLE_128B, CU_TENSOR_MAP_L2_PROMOTION_L2_256B, CU_TENSOR_MAP_FLOAT_OOB_FILL_NONE);
  }
  nat::TileTable tt;
  nat::make_tiles(tt);
  const int grid = nat::kCtas;
  if (num_sms >= grid) {
    nat::nat_kernel<<<grid, 384, nat::kSmemBytes>>>(x, out, wqkv, wo, wimg, 0u, tm, tt);
  } else {
    nat::fold_kernel<<<27, 256>>>(wqkv, wo, wimg);
    nat::nat_kernel<<<grid, 384, nat::kSmemBytes>>>(x, out, nullptr, nullptr, wimg, 0u, tm, tt);
  }
}
```

```cpp
#include <cuda_runtime.h>
#include <cuda_bf16.h>
#include <cuda.h>
#include <stdint.h>

#define NAT_P1 2
#define NAT_P2 4
#define NAT_H0 2
#define NAT_T0 2100
#define NAT_TD 1200
#define NAT_TW2 4650
#define NAT_TX2 3800
#define NAT_X1P 6
#define NAT_PK 3
#define NAT_HP 1800
#define NAT_PFD 400
#define NAT_XW 200
#define NAT_MP 3
#define NAT_D0 1
#define NAT_TH 0
#define NAT_TM 1300
#define NAT_QA 1
#define NAT_SB 0
namespace nat {

constexpr int kW = 224, kC = 192;
constexpr int kCtas = 132;
constexpr int kTilesPerCta = 6;
constexpr float kAlpha = 0.07216878364870322f * 1.4426950408889634f;
constexpr uint32_t kChunkBytes = 13 * 1024;
constexpr uint32_t kWChunk = 192 * 128;
constexpr uint32_t kWBytes = 3 * kWChunk;
constexpr uint32_t kW1Off = 6 * kChunkBytes;
constexpr uint32_t kW2Off = kW1Off + kWBytes;
constexpr uint32_t kXOff = kW2Off + kWChunk;
constexpr uint32_t kBarOff = kW2Off + kWBytes;
constexpr uint32_t kProfOff = kBarOff + 208;
constexpr uint32_t kSmemBytes = kBarOff + 1024;

static_assert(kW1Off % 1024 == 0 && kW2Off % 1024 == 0 && kChunkBytes % 1024 == 0, "swizzle alignment");
static_assert(kSmemBytes <= 232448, "smem");

constexpr uint32_t kEmpty = 0xFFFFFFFFu;
#define NAT_R8(v) v, v, v, v, v, v, v, v
#define NAT_R2K(v) NAT_R8(NAT_R8(NAT_R8(v))), NAT_R8(NAT_R8(NAT_R8(v))), NAT_R8(NAT_R8(NAT_R8(v))), NAT_R8(NAT_R8(NAT_R8(v)))
#define NAT_IMG NAT_R8(NAT_R2K(kEmpty)), NAT_R2K(kEmpty)
__device__ __align__(1024) uint32_t g_wimg32[3 * kWBytes / 4] = {NAT_IMG, NAT_IMG, NAT_IMG};
static_assert(kWBytes / 4 == 9 * 2048, "initialiser");
__device__ __align__(128) uint32_t g_flag[96];
__device__ __forceinline__ uint32_t w2_offset() {
  uint32_t v;
  asm volatile("ld.relaxed.gpu.global.u32 %0, [%1];" : "=r"(v) : "l"(g_flag + 64) : "memory");
  return (1 + v) * kWBytes;
}

#define PROFS(id, wgid, slotid) do { } while (0)
#define PROF(wgid, slotid) do { } while (0)
#define PROF_DUMP(wgid) do { } while (0)

#define GT(slotid) do { } while (0)
#define GT_DUMP() do { } while (0)

__device__ __forceinline__ uint32_t smem_u32(const void* p) { return (uint32_t)__cvta_generic_to_shared(p); }

__device__ __forceinline__ void mbar_init(uint32_t bar, uint32_t count) {
  asm volatile("mbarrier.init.shared::cta.b64 [%0], %1;" ::"r"(bar), "r"(count) : "memory");
}
__device__ __forceinline__ void mbar_arrive(uint32_t bar) {
  asm volatile("mbarrier.arrive.shared::cta.b64 _, [%0];" ::"r"(bar) : "memory");
}
__device__ __forceinline__ void mbar_arrive_expect_tx(uint32_t bar, uint32_t bytes) {
  asm volatile("mbarrier.arrive.expect_tx.shared::cta.b64 _, [%0], %1;" ::"r"(bar), "r"(bytes) : "memory");
}
__device__ __forceinline__ void mbar_wait(uint32_t bar, uint32_t parity) {
  uint32_t ok;
  uint32_t it = 0;
  do {
    asm volatile(
        "{\n.reg .pred p;\n"
        "mbarrier.try_wait.parity.shared::cta.b64 p, [%1], %2;\n"
        "selp.u32 %0, 1, 0, p;\n}\n"
        : "=r"(ok)
        : "r"(bar), "r"(parity)
        : "memory");
    if (++it > (1u << 24)) break;
  } while (!ok);
}
__device__ __forceinline__ uint32_t mbar_test(uint32_t bar, uint32_t parity) {
  uint32_t ok;
  asm volatile("{\n.reg .pred p;\nmbarrier.test_wait.parity.shared::cta.b64 p, [%1], %2;\nselp.u32 %0, 1, 0, p;\n}\n"
               : "=r"(ok) : "r"(bar), "r"(parity) : "memory");
  return ok;
}
__device__ __forceinline__ void mbar_wait_if(uint32_t ok, uint32_t bar, uint32_t parity) {
  if (!__all_sync(0xffffffffu, ok)) mbar_wait(bar, parity);
}
__device__ __forceinline__ bool elect_one() {
  uint32_t r;
  asm volatile("{\n.reg .pred p;\nelect.sync _|p, 0xffffffff;\nselp.u32 %0, 1, 0, p;\n}\n" : "=r"(r));
  return r != 0;
}
__device__ __forceinline__ void nb_arrive(int id) { asm volatile("bar.arrive %0, 256;" ::"r"(id) : "memory"); }
__device__ __forceinline__ void nb_sync(int id) { asm volatile("bar.sync %0, 256;" ::"r"(id) : "memory"); }
__device__ __forceinline__ void nb_arrive_p(int id) { asm volatile("bar.arrive %0, 160;" ::"r"(id) : "memory"); }
__device__ __forceinline__ void nb_sync_p(int id) { asm volatile("bar.sync %0, 160;" ::"r"(id) : "memory"); }
__device__ __forceinline__ void fence_proxy_async() { asm volatile("fence.proxy.async.shared::cta;" ::: "memory"); }

__device__ __forceinline__ void tma_load_5d(uint32_t dst, const CUtensorMap* map, uint32_t bar, int c0, int c1, int c2,
                                            int c3, int c4) {
  asm volatile(
      "cp.async.bulk.tensor.5d.shared::cluster.global.tile.mbarrier::complete_tx::bytes "
      "[%0], [%1, {%3, %4, %5, %6, %7}], [%2];"
      ::"r"(dst), "l"((uint64_t)map), "r"(bar), "r"(c0), "r"(c1), "r"(c2), "r"(c3), "r"(c4)
      : "memory");
}
__device__ __forceinline__ void bulk_load(uint32_t dst, const void* src, uint32_t bytes, uint32_t bar) {
  asm volatile("cp.async.bulk.shared::cluster.global.mbarrier::complete_tx::bytes [%0], [%1], %2, [%3];"
               ::"r"(dst), "l"((uint64_t)src), "r"(bytes), "r"(bar)
               : "memory");
}

__device__ __forceinline__ void wg_fence() { asm volatile("wgmma.fence.sync.aligned;" ::: "memory"); }
__device__ __forceinline__ void wg_commit() { asm volatile("wgmma.commit_group.sync.aligned;" ::: "memory"); }
template <int N>
__device__ __forceinline__ void wg_wait() { asm volatile("wgmma.wait_group.sync.aligned %0;" ::"n"(N) : "memory"); }

template <int N>
__device__ __forceinline__ void fence_regs(float (&d)[N]) {
#pragma unroll
  for (int i = 0; i < N; i++) asm volatile("" : "+f"(d[i])::"memory");
}
template <int N>
__device__ __forceinline__ void keep_regs(uint32_t (&d)[N]) {
#pragma unroll
  for (int i = 0; i < N; i++) asm volatile("" : "+r"(d[i])::"memory");
}

__device__ __forceinline__ uint32_t pack_bf16(float lo, float hi) {
  uint32_t d;
  asm("cvt.rn.bf16x2.f32 %0, %1, %2;" : "=r"(d) : "f"(hi), "f"(lo));
  return d;
}
__device__ __forceinline__ float ex2(float x) {
  float y;
  asm("ex2.approx.ftz.f32 %0, %1;" : "=f"(y) : "f"(x));
  return y;
}
__device__ __forceinline__ float rcp_approx(float x) {
  float y;
  asm("rcp.approx.ftz.f32 %0, %1;" : "=f"(y) : "f"(x));
  return y;
}
__device__ __forceinline__ uint4 ldg128_nc(const void* p) {
  uint4 v;
  asm volatile("ld.global.nc.v4.u32 {%0,%1,%2,%3}, [%4];" : "=r"(v.x), "=r"(v.y), "=r"(v.z), "=r"(v.w) : "l"(p));
  return v;
}
__device__ __forceinline__ void stg128(void* p, uint32_t a, uint32_t b, uint32_t c, uint32_t d) {
  asm volatile("st.global.v4.u32 [%0], {%1,%2,%3,%4};" ::"l"(p), "r"(a), "r"(b), "r"(c), "r"(d) : "memory");
}

__device__ __forceinline__ long long clk64() {
  long long c;
  asm volatile("mov.u64 %0, %clock64;" : "=l"(c)::"memory");
  return c;
}
__device__ __forceinline__ void sched_fence() { while (clk64() < 0) { } }

__device__ __forceinline__ uint64_t make_desc(uint32_t addr, uint32_t lbo, uint32_t sbo, uint32_t mode = 1) {
  return (uint64_t)((addr & 0x3FFFF) >> 4) | ((uint64_t)(lbo >> 4) << 16) | ((uint64_t)(sbo >> 4) << 32) |
         ((uint64_t)mode << 62);
}

template <int OFF, int NN>
__device__ __forceinline__ void wg_m192(float (&d)[NN], uint64_t desc_a, uint64_t desc_b, int scale_d) {
  asm volatile(
      "{\n.reg .pred p;\nsetp.ne.b32 p, %98, 0;\n"
      "wgmma.mma_async.sync.aligned.m64n192k16.f32.bf16.bf16 "
      "{%0,%1,%2,%3,%4,%5,%6,%7,%8,%9,%10,%11,%12,%13,%14,%15,"
      "%16,%17,%18,%19,%20,%21,%22,%23,%24,%25,%26,%27,%28,%29,%30,%31,"
      "%32,%33,%34,%35,%36,%37,%38,%39,%40,%41,%42,%43,%44,%45,%46,%47,"
      "%48,%49,%50,%51,%52,%53,%54,%55,%56,%57,%58,%59,%60,%61,%62,%63,"
      "%64,%65,%66,%67,%68,%69,%70,%71,%72,%73,%74,%75,%76,%77,%78,%79,"
      "%80,%81,%82,%83,%84,%85,%86,%87,%88,%89,%90,%91,%92,%93,%94,%95}, "
      "%96, %97, p, 1, 1, 0, 0;\n}\n"
      : "+f"(d[OFF + 0]), "+f"(d[OFF + 1]), "+f"(d[OFF + 2]), "+f"(d[OFF + 3]), "+f"(d[OFF + 4]), "+f"(d[OFF + 5]),
        "+f"(d[OFF + 6]), "+f"(d[OFF + 7]), "+f"(d[OFF + 8]), "+f"(d[OFF + 9]), "+f"(d[OFF + 10]), "+f"(d[OFF + 11]),
        "+f"(d[OFF + 12]), "+f"(d[OFF + 13]), "+f"(d[OFF + 14]), "+f"(d[OFF + 15]), "+f"(d[OFF + 16]), "+f"(d[OFF + 17]),
        "+f"(d[OFF + 18]), "+f"(d[OFF + 19]), "+f"(d[OFF + 20]), "+f"(d[OFF + 21]), "+f"(d[OFF + 22]), "+f"(d[OFF + 23]),
        "+f"(d[OFF + 24]), "+f"(d[OFF + 25]), "+f"(d[OFF + 26]), "+f"(d[OFF + 27]), "+f"(d[OFF + 28]), "+f"(d[OFF + 29]),
        "+f"(d[OFF + 30]), "+f"(d[OFF + 31]), "+f"(d[OFF + 32]), "+f"(d[OFF + 33]), "+f"(d[OFF + 34]), "+f"(d[OFF + 35]),
        "+f"(d[OFF + 36]), "+f"(d[OFF + 37]), "+f"(d[OFF + 38]), "+f"(d[OFF + 39]), "+f"(d[OFF + 40]), "+f"(d[OFF + 41]),
        "+f"(d[OFF + 42]), "+f"(d[OFF + 43]), "+f"(d[OFF + 44]), "+f"(d[OFF + 45]), "+f"(d[OFF + 46]), "+f"(d[OFF + 47]),
        "+f"(d[OFF + 48]), "+f"(d[OFF + 49]), "+f"(d[OFF + 50]), "+f"(d[OFF + 51]), "+f"(d[OFF + 52]), "+f"(d[OFF + 53]),
        "+f"(d[OFF + 54]), "+f"(d[OFF + 55]), "+f"(d[OFF + 56]), "+f"(d[OFF + 57]), "+f"(d[OFF + 58]), "+f"(d[OFF + 59]),
        "+f"(d[OFF + 60]), "+f"(d[OFF + 61]), "+f"(d[OFF + 62]), "+f"(d[OFF + 63]), "+f"(d[OFF + 64]), "+f"(d[OFF + 65]),
        "+f"(d[OFF + 66]), "+f"(d[OFF + 67]), "+f"(d[OFF + 68]), "+f"(d[OFF + 69]), "+f"(d[OFF + 70]), "+f"(d[OFF + 71]),
        "+f"(d[OFF + 72]), "+f"(d[OFF + 73]), "+f"(d[OFF + 74]), "+f"(d[OFF + 75]), "+f"(d[OFF + 76]), "+f"(d[OFF + 77]),
        "+f"(d[OFF + 78]), "+f"(d[OFF + 79]), "+f"(d[OFF + 80]), "+f"(d[OFF + 81]), "+f"(d[OFF + 82]), "+f"(d[OFF + 83]),
        "+f"(d[OFF + 84]), "+f"(d[OFF + 85]), "+f"(d[OFF + 86]), "+f"(d[OFF + 87]), "+f"(d[OFF + 88]), "+f"(d[OFF + 89]),
        "+f"(d[OFF + 90]), "+f"(d[OFF + 91]), "+f"(d[OFF + 92]), "+f"(d[OFF + 93]), "+f"(d[OFF + 94]), "+f"(d[OFF + 95])
      : "l"(desc_a), "l"(desc_b), "r"(scale_d));
}

template <int OFF, int NN>
__device__ __forceinline__ void wg_m192z(float (&d)[NN], uint64_t desc_a, uint64_t desc_b, int scale_d) {
  asm volatile(
      "{\n.reg .pred p;\nsetp.ne.b32 p, %98, 0;\n"
      "wgmma.mma_async.sync.aligned.m64n192k16.f32.bf16.bf16 "
      "{%0,%1,%2,%3,%4,%5,%6,%7,%8,%9,%10,%11,%12,%13,%14,%15,"
      "%16,%17,%18,%19,%20,%21,%22,%23,%24,%25,%26,%27,%28,%29,%30,%31,"
      "%32,%33,%34,%35,%36,%37,%38,%39,%40,%41,%42,%43,%44,%45,%46,%47,"
      "%48,%49,%50,%51,%52,%53,%54,%55,%56,%57,%58,%59,%60,%61,%62,%63,"
      "%64,%65,%66,%67,%68,%69,%70,%71,%72,%73,%74,%75,%76,%77,%78,%79,"
      "%80,%81,%82,%83,%84,%85,%86,%87,%88,%89,%90,%91,%92,%93,%94,%95}, "
      "%96, %97, p, 1, 1, 0, 0;\n}\n"
      : "=f"(d[OFF + 0]), "=f"(d[OFF + 1]), "=f"(d[OFF + 2]), "=f"(d[OFF + 3]), "=f"(d[OFF + 4]), "=f"(d[OFF + 5]),
        "=f"(d[OFF + 6]), "=f"(d[OFF + 7]), "=f"(d[OFF + 8]), "=f"(d[OFF + 9]), "=f"(d[OFF + 10]), "=f"(d[OFF + 11]),
        "=f"(d[OFF + 12]), "=f"(d[OFF + 13]), "=f"(d[OFF + 14]), "=f"(d[OFF + 15]), "=f"(d[OFF + 16]), "=f"(d[OFF + 17]),
        "=f"(d[OFF + 18]), "=f"(d[OFF + 19]), "=f"(d[OFF + 20]), "=f"(d[OFF + 21]), "=f"(d[OFF + 22]), "=f"(d[OFF + 23]),
        "=f"(d[OFF + 24]), "=f"(d[OFF + 25]), "=f"(d[OFF + 26]), "=f"(d[OFF + 27]), "=f"(d[OFF + 28]), "=f"(d[OFF + 29]),
        "=f"(d[OFF + 30]), "=f"(d[OFF + 31]), "=f"(d[OFF + 32]), "=f"(d[OFF + 33]), "=f"(d[OFF + 34]), "=f"(d[OFF + 35]),
        "=f"(d[OFF + 36]), "=f"(d[OFF + 37]), "=f"(d[OFF + 38]), "=f"(d[OFF + 39]), "=f"(d[OFF + 40]), "=f"(d[OFF + 41]),
        "=f"(d[OFF + 42]), "=f"(d[OFF + 43]), "=f"(d[OFF + 44]), "=f"(d[OFF + 45]), "=f"(d[OFF + 46]), "=f"(d[OFF + 47]),
        "=f"(d[OFF + 48]), "=f"(d[OFF + 49]), "=f"(d[OFF + 50]), "=f"(d[OFF + 51]), "=f"(d[OFF + 52]), "=f"(d[OFF + 53]),
        "=f"(d[OFF + 54]), "=f"(d[OFF + 55]), "=f"(d[OFF + 56]), "=f"(d[OFF + 57]), "=f"(d[OFF + 58]), "=f"(d[OFF + 59]),
        "=f"(d[OFF + 60]), "=f"(d[OFF + 61]), "=f"(d[OFF + 62]), "=f"(d[OFF + 63]), "=f"(d[OFF + 64]), "=f"(d[OFF + 65]),
        "=f"(d[OFF + 66]), "=f"(d[OFF + 67]), "=f"(d[OFF + 68]), "=f"(d[OFF + 69]), "=f"(d[OFF + 70]), "=f"(d[OFF + 71]),
        "=f"(d[OFF + 72]), "=f"(d[OFF + 73]), "=f"(d[OFF + 74]), "=f"(d[OFF + 75]), "=f"(d[OFF + 76]), "=f"(d[OFF + 77]),
        "=f"(d[OFF + 78]), "=f"(d[OFF + 79]), "=f"(d[OFF + 80]), "=f"(d[OFF + 81]), "=f"(d[OFF + 82]), "=f"(d[OFF + 83]),
        "=f"(d[OFF + 84]), "=f"(d[OFF + 85]), "=f"(d[OFF + 86]), "=f"(d[OFF + 87]), "=f"(d[OFF + 88]), "=f"(d[OFF + 89]),
        "=f"(d[OFF + 90]), "=f"(d[OFF + 91]), "=f"(d[OFF + 92]), "=f"(d[OFF + 93]), "=f"(d[OFF + 94]), "=f"(d[OFF + 95])
      : "l"(desc_a), "l"(desc_b), "r"(scale_d));
}

template <int OFF, int NN>
__device__ __forceinline__ void wg_m64t(float (&d)[NN], uint64_t desc_a, uint64_t desc_b, int scale_d) {
  asm volatile(
      "{\n.reg .pred p;\nsetp.ne.b32 p, %34, 0;\n"
      "wgmma.mma_async.sync.aligned.m64n64k16.f32.bf16.bf16 "
      "{%0,%1,%2,%3,%4,%5,%6,%7,%8,%9,%10,%11,%12,%13,%14,%15,"
      "%16,%17,%18,%19,%20,%21,%22,%23,%24,%25,%26,%27,%28,%29,%30,%31}, "
      "%32, %33, p, 1, 1, 0, 1;\n}\n"
      : "+f"(d[OFF + 0]), "+f"(d[OFF + 1]), "+f"(d[OFF + 2]), "+f"(d[OFF + 3]), "+f"(d[OFF + 4]), "+f"(d[OFF + 5]),
        "+f"(d[OFF + 6]), "+f"(d[OFF + 7]), "+f"(d[OFF + 8]), "+f"(d[OFF + 9]), "+f"(d[OFF + 10]), "+f"(d[OFF + 11]),
        "+f"(d[OFF + 12]), "+f"(d[OFF + 13]), "+f"(d[OFF + 14]), "+f"(d[OFF + 15]), "+f"(d[OFF + 16]), "+f"(d[OFF + 17]),
        "+f"(d[OFF + 18]), "+f"(d[OFF + 19]), "+f"(d[OFF + 20]), "+f"(d[OFF + 21]), "+f"(d[OFF + 22]), "+f"(d[OFF + 23]),
        "+f"(d[OFF + 24]), "+f"(d[OFF + 25]), "+f"(d[OFF + 26]), "+f"(d[OFF + 27]), "+f"(d[OFF + 28]), "+f"(d[OFF + 29]),
        "+f"(d[OFF + 30]), "+f"(d[OFF + 31])
      : "l"(desc_a), "l"(desc_b), "r"(scale_d));
}

template <int OFF, int NN>
__device__ __forceinline__ void wg_m64tz(float (&d)[NN], uint64_t desc_a, uint64_t desc_b, int scale_d) {
  asm volatile(
      "{\n.reg .pred p;\nsetp.ne.b32 p, %34, 0;\n"
      "wgmma.mma_async.sync.aligned.m64n64k16.f32.bf16.bf16 "
      "{%0,%1,%2,%3,%4,%5,%6,%7,%8,%9,%10,%11,%12,%13,%14,%15,"
      "%16,%17,%18,%19,%20,%21,%22,%23,%24,%25,%26,%27,%28,%29,%30,%31}, "
      "%32, %33, p, 1, 1, 0, 1;\n}\n"
      : "=f"(d[OFF + 0]), "=f"(d[OFF + 1]), "=f"(d[OFF + 2]), "=f"(d[OFF + 3]), "=f"(d[OFF + 4]), "=f"(d[OFF + 5]),
        "=f"(d[OFF + 6]), "=f"(d[OFF + 7]), "=f"(d[OFF + 8]), "=f"(d[OFF + 9]), "=f"(d[OFF + 10]), "=f"(d[OFF + 11]),
        "=f"(d[OFF + 12]), "=f"(d[OFF + 13]), "=f"(d[OFF + 14]), "=f"(d[OFF + 15]), "=f"(d[OFF + 16]), "=f"(d[OFF + 17]),
        "=f"(d[OFF + 18]), "=f"(d[OFF + 19]), "=f"(d[OFF + 20]), "=f"(d[OFF + 21]), "=f"(d[OFF + 22]), "=f"(d[OFF + 23]),
        "=f"(d[OFF + 24]), "=f"(d[OFF + 25]), "=f"(d[OFF + 26]), "=f"(d[OFF + 27]), "=f"(d[OFF + 28]), "=f"(d[OFF + 29]),
        "=f"(d[OFF + 30]), "=f"(d[OFF + 31])
      : "l"(desc_a), "l"(desc_b), "r"(scale_d));
}

template <int OFF, int NN>
__device__ __forceinline__ void wg_d96(float (&d)[NN], uint32_t a0, uint32_t a1, uint32_t a2, uint32_t a3,
                                       uint64_t desc_b, int scale_d) {
  asm volatile(
      "{\n.reg .pred p;\nsetp.ne.b32 p, %53, 0;\n"
      "wgmma.mma_async.sync.aligned.m64n96k16.f32.bf16.bf16 "
      "{%0,%1,%2,%3,%4,%5,%6,%7,%8,%9,%10,%11,%12,%13,%14,%15,"
      "%16,%17,%18,%19,%20,%21,%22,%23,%24,%25,%26,%27,%28,%29,%30,%31,"
      "%32,%33,%34,%35,%36,%37,%38,%39,%40,%41,%42,%43,%44,%45,%46,%47}, "
      "{%48,%49,%50,%51}, %52, p, 1, 1, 0;\n}\n"
      : "+f"(d[OFF + 0]), "+f"(d[OFF + 1]), "+f"(d[OFF + 2]), "+f"(d[OFF + 3]), "+f"(d[OFF + 4]), "+f"(d[OFF + 5]),
        "+f"(d[OFF + 6]), "+f"(d[OFF + 7]), "+f"(d[OFF + 8]), "+f"(d[OFF + 9]), "+f"(d[OFF + 10]), "+f"(d[OFF + 11]),
        "+f"(d[OFF + 12]), "+f"(d[OFF + 13]), "+f"(d[OFF + 14]), "+f"(d[OFF + 15]), "+f"(d[OFF + 16]), "+f"(d[OFF + 17]),
        "+f"(d[OFF + 18]), "+f"(d[OFF + 19]), "+f"(d[OFF + 20]), "+f"(d[OFF + 21]), "+f"(d[OFF + 22]), "+f"(d[OFF + 23]),
        "+f"(d[OFF + 24]), "+f"(d[OFF + 25]), "+f"(d[OFF + 26]), "+f"(d[OFF + 27]), "+f"(d[OFF + 28]), "+f"(d[OFF + 29]),
        "+f"(d[OFF + 30]), "+f"(d[OFF + 31]), "+f"(d[OFF + 32]), "+f"(d[OFF + 33]), "+f"(d[OFF + 34]), "+f"(d[OFF + 35]),
        "+f"(d[OFF + 36]), "+f"(d[OFF + 37]), "+f"(d[OFF + 38]), "+f"(d[OFF + 39]), "+f"(d[OFF + 40]), "+f"(d[OFF + 41]),
        "+f"(d[OFF + 42]), "+f"(d[OFF + 43]), "+f"(d[OFF + 44]), "+f"(d[OFF + 45]), "+f"(d[OFF + 46]), "+f"(d[OFF + 47])
      : "r"(a0), "r"(a1), "r"(a2), "r"(a3), "l"(desc_b), "r"(scale_d));
}

template <int OFF, int NN>
__device__ __forceinline__ void wg_d96z(float (&d)[NN], uint32_t a0, uint32_t a1, uint32_t a2, uint32_t a3,
                                       uint64_t desc_b, int scale_d) {
  asm volatile(
      "{\n.reg .pred p;\nsetp.ne.b32 p, %53, 0;\n"
      "wgmma.mma_async.sync.aligned.m64n96k16.f32.bf16.bf16 "
      "{%0,%1,%2,%3,%4,%5,%6,%7,%8,%9,%10,%11,%12,%13,%14,%15,"
      "%16,%17,%18,%19,%20,%21,%22,%23,%24,%25,%26,%27,%28,%29,%30,%31,"
      "%32,%33,%34,%35,%36,%37,%38,%39,%40,%41,%42,%43,%44,%45,%46,%47}, "
      "{%48,%49,%50,%51}, %52, p, 1, 1, 0;\n}\n"
      : "=f"(d[OFF + 0]), "=f"(d[OFF + 1]), "=f"(d[OFF + 2]), "=f"(d[OFF + 3]), "=f"(d[OFF + 4]), "=f"(d[OFF + 5]),
        "=f"(d[OFF + 6]), "=f"(d[OFF + 7]), "=f"(d[OFF + 8]), "=f"(d[OFF + 9]), "=f"(d[OFF + 10]), "=f"(d[OFF + 11]),
        "=f"(d[OFF + 12]), "=f"(d[OFF + 13]), "=f"(d[OFF + 14]), "=f"(d[OFF + 15]), "=f"(d[OFF + 16]), "=f"(d[OFF + 17]),
        "=f"(d[OFF + 18]), "=f"(d[OFF + 19]), "=f"(d[OFF + 20]), "=f"(d[OFF + 21]), "=f"(d[OFF + 22]), "=f"(d[OFF + 23]),
        "=f"(d[OFF + 24]), "=f"(d[OFF + 25]), "=f"(d[OFF + 26]), "=f"(d[OFF + 27]), "=f"(d[OFF + 28]), "=f"(d[OFF + 29]),
        "=f"(d[OFF + 30]), "=f"(d[OFF + 31]), "=f"(d[OFF + 32]), "=f"(d[OFF + 33]), "=f"(d[OFF + 34]), "=f"(d[OFF + 35]),
        "=f"(d[OFF + 36]), "=f"(d[OFF + 37]), "=f"(d[OFF + 38]), "=f"(d[OFF + 39]), "=f"(d[OFF + 40]), "=f"(d[OFF + 41]),
        "=f"(d[OFF + 42]), "=f"(d[OFF + 43]), "=f"(d[OFF + 44]), "=f"(d[OFF + 45]), "=f"(d[OFF + 46]), "=f"(d[OFF + 47])
      : "r"(a0), "r"(a1), "r"(a2), "r"(a3), "l"(desc_b), "r"(scale_d));
}

template <int OFF, int NN>
__device__ __forceinline__ void wg_s104(float (&d)[NN], uint32_t a0, uint32_t a1, uint32_t a2, uint32_t a3,
                                       uint64_t desc_b, int scale_d, uint32_t meta) {
  asm volatile(
      "{\n.reg .pred p;\nsetp.ne.b32 p, %57, 0;\n"
      "wgmma.mma_async.sp.sync.aligned.m64n104k32.f32.bf16.bf16 "
      "{%0,%1,%2,%3,%4,%5,%6,%7,%8,%9,%10,%11,%12,%13,%14,%15,"
      "%16,%17,%18,%19,%20,%21,%22,%23,%24,%25,%26,%27,%28,%29,%30,%31,"
      "%32,%33,%34,%35,%36,%37,%38,%39,%40,%41,%42,%43,%44,%45,%46,%47,"
      "%48,%49,%50,%51}, "
      "{%52,%53,%54,%55}, %56, %58, 0, p, 1, 1, 0;\n}\n"
      : "+f"(d[OFF + 0]), "+f"(d[OFF + 1]), "+f"(d[OFF + 2]), "+f"(d[OFF + 3]), "+f"(d[OFF + 4]), "+f"(d[OFF + 5]),
        "+f"(d[OFF + 6]), "+f"(d[OFF + 7]), "+f"(d[OFF + 8]), "+f"(d[OFF + 9]), "+f"(d[OFF + 10]), "+f"(d[OFF + 11]),
        "+f"(d[OFF + 12]), "+f"(d[OFF + 13]), "+f"(d[OFF + 14]), "+f"(d[OFF + 15]), "+f"(d[OFF + 16]), "+f"(d[OFF + 17]),
        "+f"(d[OFF + 18]), "+f"(d[OFF + 19]), "+f"(d[OFF + 20]), "+f"(d[OFF + 21]), "+f"(d[OFF + 22]), "+f"(d[OFF + 23]),
        "+f"(d[OFF + 24]), "+f"(d[OFF + 25]), "+f"(d[OFF + 26]), "+f"(d[OFF + 27]), "+f"(d[OFF + 28]), "+f"(d[OFF + 29]),
        "+f"(d[OFF + 30]), "+f"(d[OFF + 31]), "+f"(d[OFF + 32]), "+f"(d[OFF + 33]), "+f"(d[OFF + 34]), "+f"(d[OFF + 35]),
        "+f"(d[OFF + 36]), "+f"(d[OFF + 37]), "+f"(d[OFF + 38]), "+f"(d[OFF + 39]), "+f"(d[OFF + 40]), "+f"(d[OFF + 41]),
        "+f"(d[OFF + 42]), "+f"(d[OFF + 43]), "+f"(d[OFF + 44]), "+f"(d[OFF + 45]), "+f"(d[OFF + 46]), "+f"(d[OFF + 47]),
        "+f"(d[OFF + 48]), "+f"(d[OFF + 49]), "+f"(d[OFF + 50]), "+f"(d[OFF + 51])
      : "r"(a0), "r"(a1), "r"(a2), "r"(a3), "l"(desc_b), "r"(scale_d), "r"(meta));
}

template <int OFF, int NN>
__device__ __forceinline__ void wg_s104z(float (&d)[NN], uint32_t a0, uint32_t a1, uint32_t a2, uint32_t a3,
                                       uint64_t desc_b, int scale_d, uint32_t meta) {
  asm volatile(
      "{\n.reg .pred p;\nsetp.ne.b32 p, %57, 0;\n"
      "wgmma.mma_async.sp.sync.aligned.m64n104k32.f32.bf16.bf16 "
      "{%0,%1,%2,%3,%4,%5,%6,%7,%8,%9,%10,%11,%12,%13,%14,%15,"
      "%16,%17,%18,%19,%20,%21,%22,%23,%24,%25,%26,%27,%28,%29,%30,%31,"
      "%32,%33,%34,%35,%36,%37,%38,%39,%40,%41,%42,%43,%44,%45,%46,%47,"
      "%48,%49,%50,%51}, "
      "{%52,%53,%54,%55}, %56, %58, 0, p, 1, 1, 0;\n}\n"
      : "=f"(d[OFF + 0]), "=f"(d[OFF + 1]), "=f"(d[OFF + 2]), "=f"(d[OFF + 3]), "=f"(d[OFF + 4]), "=f"(d[OFF + 5]),
        "=f"(d[OFF + 6]), "=f"(d[OFF + 7]), "=f"(d[OFF + 8]), "=f"(d[OFF + 9]), "=f"(d[OFF + 10]), "=f"(d[OFF + 11]),
        "=f"(d[OFF + 12]), "=f"(d[OFF + 13]), "=f"(d[OFF + 14]), "=f"(d[OFF + 15]), "=f"(d[OFF + 16]), "=f"(d[OFF + 17]),
        "=f"(d[OFF + 18]), "=f"(d[OFF + 19]), "=f"(d[OFF + 20]), "=f"(d[OFF + 21]), "=f"(d[OFF + 22]), "=f"(d[OFF + 23]),
        "=f"(d[OFF + 24]), "=f"(d[OFF + 25]), "=f"(d[OFF + 26]), "=f"(d[OFF + 27]), "=f"(d[OFF + 28]), "=f"(d[OFF + 29]),
        "=f"(d[OFF + 30]), "=f"(d[OFF + 31]), "=f"(d[OFF + 32]), "=f"(d[OFF + 33]), "=f"(d[OFF + 34]), "=f"(d[OFF + 35]),
        "=f"(d[OFF + 36]), "=f"(d[OFF + 37]), "=f"(d[OFF + 38]), "=f"(d[OFF + 39]), "=f"(d[OFF + 40]), "=f"(d[OFF + 41]),
        "=f"(d[OFF + 42]), "=f"(d[OFF + 43]), "=f"(d[OFF + 44]), "=f"(d[OFF + 45]), "=f"(d[OFF + 46]), "=f"(d[OFF + 47]),
        "=f"(d[OFF + 48]), "=f"(d[OFF + 49]), "=f"(d[OFF + 50]), "=f"(d[OFF + 51])
      : "r"(a0), "r"(a1), "r"(a2), "r"(a3), "l"(desc_b), "r"(scale_d), "r"(meta));
}

template <int OFF, int NN>
__device__ __forceinline__ void wg_s48(float (&d)[NN], uint32_t a0, uint32_t a1, uint32_t a2, uint32_t a3,
                                       uint64_t desc_b, int scale_d, uint32_t meta) {
  asm volatile(
      "{\n.reg .pred p;\nsetp.ne.b32 p, %29, 0;\n"
      "wgmma.mma_async.sp.sync.aligned.m64n48k32.f32.bf16.bf16 "
      "{%0,%1,%2,%3,%4,%5,%6,%7,%8,%9,%10,%11,%12,%13,%14,%15,"
      "%16,%17,%18,%19,%20,%21,%22,%23}, "
      "{%24,%25,%26,%27}, %28, %30, 0, p, 1, 1, 0;\n}\n"
      : "+f"(d[OFF + 0]), "+f"(d[OFF + 1]), "+f"(d[OFF + 2]), "+f"(d[OFF + 3]), "+f"(d[OFF + 4]), "+f"(d[OFF + 5]),
        "+f"(d[OFF + 6]), "+f"(d[OFF + 7]), "+f"(d[OFF + 8]), "+f"(d[OFF + 9]), "+f"(d[OFF + 10]), "+f"(d[OFF + 11]),
        "+f"(d[OFF + 12]), "+f"(d[OFF + 13]), "+f"(d[OFF + 14]), "+f"(d[OFF + 15]), "+f"(d[OFF + 16]), "+f"(d[OFF + 17]),
        "+f"(d[OFF + 18]), "+f"(d[OFF + 19]), "+f"(d[OFF + 20]), "+f"(d[OFF + 21]), "+f"(d[OFF + 22]), "+f"(d[OFF + 23])
      : "r"(a0), "r"(a1), "r"(a2), "r"(a3), "l"(desc_b), "r"(scale_d), "r"(meta));
}

template <int OFF, int NN>
__device__ __forceinline__ void wg_s48z(float (&d)[NN], uint32_t a0, uint32_t a1, uint32_t a2, uint32_t a3,
                                       uint64_t desc_b, int scale_d, uint32_t meta) {
  asm volatile(
      "{\n.reg .pred p;\nsetp.ne.b32 p, %29, 0;\n"
      "wgmma.mma_async.sp.sync.aligned.m64n48k32.f32.bf16.bf16 "
      "{%0,%1,%2,%3,%4,%5,%6,%7,%8,%9,%10,%11,%12,%13,%14,%15,"
      "%16,%17,%18,%19,%20,%21,%22,%23}, "
      "{%24,%25,%26,%27}, %28, %30, 0, p, 1, 1, 0;\n}\n"
      : "=f"(d[OFF + 0]), "=f"(d[OFF + 1]), "=f"(d[OFF + 2]), "=f"(d[OFF + 3]), "=f"(d[OFF + 4]), "=f"(d[OFF + 5]),
        "=f"(d[OFF + 6]), "=f"(d[OFF + 7]), "=f"(d[OFF + 8]), "=f"(d[OFF + 9]), "=f"(d[OFF + 10]), "=f"(d[OFF + 11]),
        "=f"(d[OFF + 12]), "=f"(d[OFF + 13]), "=f"(d[OFF + 14]), "=f"(d[OFF + 15]), "=f"(d[OFF + 16]), "=f"(d[OFF + 17]),
        "=f"(d[OFF + 18]), "=f"(d[OFF + 19]), "=f"(d[OFF + 20]), "=f"(d[OFF + 21]), "=f"(d[OFF + 22]), "=f"(d[OFF + 23])
      : "r"(a0), "r"(a1), "r"(a2), "r"(a3), "l"(desc_b), "r"(scale_d), "r"(meta));
}

template <int OFF, int NN>
__device__ __forceinline__ void wg_s56(float (&d)[NN], uint32_t a0, uint32_t a1, uint32_t a2, uint32_t a3,
                                       uint64_t desc_b, int scale_d, uint32_t meta) {
  asm volatile(
      "{\n.reg .pred p;\nsetp.ne.b32 p, %33, 0;\n"
      "wgmma.mma_async.sp.sync.aligned.m64n56k32.f32.bf16.bf16 "
      "{%0,%1,%2,%3,%4,%5,%6,%7,%8,%9,%10,%11,%12,%13,%14,%15,"
      "%16,%17,%18,%19,%20,%21,%22,%23,%24,%25,%26,%27}, "
      "{%28,%29,%30,%31}, %32, %34, 0, p, 1, 1, 0;\n}\n"
      : "+f"(d[OFF + 0]), "+f"(d[OFF + 1]), "+f"(d[OFF + 2]), "+f"(d[OFF + 3]), "+f"(d[OFF + 4]), "+f"(d[OFF + 5]),
        "+f"(d[OFF + 6]), "+f"(d[OFF + 7]), "+f"(d[OFF + 8]), "+f"(d[OFF + 9]), "+f"(d[OFF + 10]), "+f"(d[OFF + 11]),
        "+f"(d[OFF + 12]), "+f"(d[OFF + 13]), "+f"(d[OFF + 14]), "+f"(d[OFF + 15]), "+f"(d[OFF + 16]), "+f"(d[OFF + 17]),
        "+f"(d[OFF + 18]), "+f"(d[OFF + 19]), "+f"(d[OFF + 20]), "+f"(d[OFF + 21]), "+f"(d[OFF + 22]), "+f"(d[OFF + 23]),
        "+f"(d[OFF + 24]), "+f"(d[OFF + 25]), "+f"(d[OFF + 26]), "+f"(d[OFF + 27])
      : "r"(a0), "r"(a1), "r"(a2), "r"(a3), "l"(desc_b), "r"(scale_d), "r"(meta));
}

template <int OFF, int NN>
__device__ __forceinline__ void wg_s56z(float (&d)[NN], uint32_t a0, uint32_t a1, uint32_t a2, uint32_t a3,
                                       uint64_t desc_b, int scale_d, uint32_t meta) {
  asm volatile(
      "{\n.reg .pred p;\nsetp.ne.b32 p, %33, 0;\n"
      "wgmma.mma_async.sp.sync.aligned.m64n56k32.f32.bf16.bf16 "
      "{%0,%1,%2,%3,%4,%5,%6,%7,%8,%9,%10,%11,%12,%13,%14,%15,"
      "%16,%17,%18,%19,%20,%21,%22,%23,%24,%25,%26,%27}, "
      "{%28,%29,%30,%31}, %32, %34, 0, p, 1, 1, 0;\n}\n"
      : "=f"(d[OFF + 0]), "=f"(d[OFF + 1]), "=f"(d[OFF + 2]), "=f"(d[OFF + 3]), "=f"(d[OFF + 4]), "=f"(d[OFF + 5]),
        "=f"(d[OFF + 6]), "=f"(d[OFF + 7]), "=f"(d[OFF + 8]), "=f"(d[OFF + 9]), "=f"(d[OFF + 10]), "=f"(d[OFF + 11]),
        "=f"(d[OFF + 12]), "=f"(d[OFF + 13]), "=f"(d[OFF + 14]), "=f"(d[OFF + 15]), "=f"(d[OFF + 16]), "=f"(d[OFF + 17]),
        "=f"(d[OFF + 18]), "=f"(d[OFF + 19]), "=f"(d[OFF + 20]), "=f"(d[OFF + 21]), "=f"(d[OFF + 22]), "=f"(d[OFF + 23]),
        "=f"(d[OFF + 24]), "=f"(d[OFF + 25]), "=f"(d[OFF + 26]), "=f"(d[OFF + 27])
      : "r"(a0), "r"(a1), "r"(a2), "r"(a3), "l"(desc_b), "r"(scale_d), "r"(meta));
}

template <int OFF, int NN>
__device__ __forceinline__ void wg_s64t(float (&d)[NN], uint32_t a0, uint32_t a1, uint32_t a2, uint32_t a3,
                                       uint64_t desc_b, int scale_d, uint32_t meta) {
  asm volatile(
      "{\n.reg .pred p;\nsetp.ne.b32 p, %37, 0;\n"
      "wgmma.mma_async.sp.sync.aligned.m64n64k32.f32.bf16.bf16 "
      "{%0,%1,%2,%3,%4,%5,%6,%7,%8,%9,%10,%11,%12,%13,%14,%15,"
      "%16,%17,%18,%19,%20,%21,%22,%23,%24,%25,%26,%27,%28,%29,%30,%31}, "
      "{%32,%33,%34,%35}, %36, %38, 0, p, 1, 1, 1;\n}\n"
      : "+f"(d[OFF + 0]), "+f"(d[OFF + 1]), "+f"(d[OFF + 2]), "+f"(d[OFF + 3]), "+f"(d[OFF + 4]), "+f"(d[OFF + 5]),
        "+f"(d[OFF + 6]), "+f"(d[OFF + 7]), "+f"(d[OFF + 8]), "+f"(d[OFF + 9]), "+f"(d[OFF + 10]), "+f"(d[OFF + 11]),
        "+f"(d[OFF + 12]), "+f"(d[OFF + 13]), "+f"(d[OFF + 14]), "+f"(d[OFF + 15]), "+f"(d[OFF + 16]), "+f"(d[OFF + 17]),
        "+f"(d[OFF + 18]), "+f"(d[OFF + 19]), "+f"(d[OFF + 20]), "+f"(d[OFF + 21]), "+f"(d[OFF + 22]), "+f"(d[OFF + 23]),
        "+f"(d[OFF + 24]), "+f"(d[OFF + 25]), "+f"(d[OFF + 26]), "+f"(d[OFF + 27]), "+f"(d[OFF + 28]), "+f"(d[OFF + 29]),
        "+f"(d[OFF + 30]), "+f"(d[OFF + 31])
      : "r"(a0), "r"(a1), "r"(a2), "r"(a3), "l"(desc_b), "r"(scale_d), "r"(meta));
}

template <int OFF, int NN>
__device__ __forceinline__ void wg_s64t1(float (&d)[NN], uint32_t a0, uint32_t a1, uint32_t a2, uint32_t a3,
                                       uint64_t desc_b, int scale_d, uint32_t meta) {
  asm volatile(
      "{\n.reg .pred p;\nsetp.ne.b32 p, %37, 0;\n"
      "wgmma.mma_async.sp.sync.aligned.m64n64k32.f32.bf16.bf16 "
      "{%0,%1,%2,%3,%4,%5,%6,%7,%8,%9,%10,%11,%12,%13,%14,%15,"
      "%16,%17,%18,%19,%20,%21,%22,%23,%24,%25,%26,%27,%28,%29,%30,%31}, "
      "{%32,%33,%34,%35}, %36, %38, 1, p, 1, 1, 1;\n}\n"
      : "+f"(d[OFF + 0]), "+f"(d[OFF + 1]), "+f"(d[OFF + 2]), "+f"(d[OFF + 3]), "+f"(d[OFF + 4]), "+f"(d[OFF + 5]),
        "+f"(d[OFF + 6]), "+f"(d[OFF + 7]), "+f"(d[OFF + 8]), "+f"(d[OFF + 9]), "+f"(d[OFF + 10]), "+f"(d[OFF + 11]),
        "+f"(d[OFF + 12]), "+f"(d[OFF + 13]), "+f"(d[OFF + 14]), "+f"(d[OFF + 15]), "+f"(d[OFF + 16]), "+f"(d[OFF + 17]),
        "+f"(d[OFF + 18]), "+f"(d[OFF + 19]), "+f"(d[OFF + 20]), "+f"(d[OFF + 21]), "+f"(d[OFF + 22]), "+f"(d[OFF + 23]),
        "+f"(d[OFF + 24]), "+f"(d[OFF + 25]), "+f"(d[OFF + 26]), "+f"(d[OFF + 27]), "+f"(d[OFF + 28]), "+f"(d[OFF + 29]),
        "+f"(d[OFF + 30]), "+f"(d[OFF + 31])
      : "r"(a0), "r"(a1), "r"(a2), "r"(a3), "l"(desc_b), "r"(scale_d), "r"(meta));
}

template <int OFF, int NN>
__device__ __forceinline__ void wg_s64tz(float (&d)[NN], uint32_t a0, uint32_t a1, uint32_t a2, uint32_t a3,
                                       uint64_t desc_b, int scale_d, uint32_t meta) {
  asm volatile(
      "{\n.reg .pred p;\nsetp.ne.b32 p, %37, 0;\n"
      "wgmma.mma_async.sp.sync.aligned.m64n64k32.f32.bf16.bf16 "
      "{%0,%1,%2,%3,%4,%5,%6,%7,%8,%9,%10,%11,%12,%13,%14,%15,"
      "%16,%17,%18,%19,%20,%21,%22,%23,%24,%25,%26,%27,%28,%29,%30,%31}, "
      "{%32,%33,%34,%35}, %36, %38, 0, p, 1, 1, 1;\n}\n"
      : "=f"(d[OFF + 0]), "=f"(d[OFF + 1]), "=f"(d[OFF + 2]), "=f"(d[OFF + 3]), "=f"(d[OFF + 4]), "=f"(d[OFF + 5]),
        "=f"(d[OFF + 6]), "=f"(d[OFF + 7]), "=f"(d[OFF + 8]), "=f"(d[OFF + 9]), "=f"(d[OFF + 10]), "=f"(d[OFF + 11]),
        "=f"(d[OFF + 12]), "=f"(d[OFF + 13]), "=f"(d[OFF + 14]), "=f"(d[OFF + 15]), "=f"(d[OFF + 16]), "=f"(d[OFF + 17]),
        "=f"(d[OFF + 18]), "=f"(d[OFF + 19]), "=f"(d[OFF + 20]), "=f"(d[OFF + 21]), "=f"(d[OFF + 22]), "=f"(d[OFF + 23]),
        "=f"(d[OFF + 24]), "=f"(d[OFF + 25]), "=f"(d[OFF + 26]), "=f"(d[OFF + 27]), "=f"(d[OFF + 28]), "=f"(d[OFF + 29]),
        "=f"(d[OFF + 30]), "=f"(d[OFF + 31])
      : "r"(a0), "r"(a1), "r"(a2), "r"(a3), "l"(desc_b), "r"(scale_d), "r"(meta));
}

__device__ __forceinline__ int g2_inv(int ch) { return 32 * (ch >> 5) + 8 * ((ch >> 1) & 3) + 2 * ((ch >> 3) & 3) + (ch & 1); }
__host__ __device__ __forceinline__ uint32_t wimg_off(int n, int k) {
  return (uint32_t)(k >> 6) * kWChunk + (uint32_t)n * 128 + (uint32_t)((((k & 63) >> 3) ^ (n & 7)) << 4) + (k & 7) * 2;
}
__host__ __device__ constexpr int w2piece(int h, int c) { return c == 2 ? 2 + h : 4 * h + c; }
__device__ __forceinline__ uint32_t w2img_off(int n, int k) { return wimg_off(n % 96, k & 63) + w2piece(n >= 96, k >> 6) * (kWChunk / 2); }
__device__ __forceinline__ int qpix(int par, int t) {
  const int a = 2 * t + 13 * par - 6, b = t + 112 * par;
  return par ? min(a, b) : max(a, b);
}
__device__ __forceinline__ int woff(int par, int i, int r) {
  const int a = 99 * par + 6 - 8 * i;
  return par ? min(r, a) : max(r, a);
}

__device__ __forceinline__ void mma16816(float (&c)[4], uint32_t a0, uint32_t a1, uint32_t a2, uint32_t a3, uint32_t b0,
                                         uint32_t b1) {
  asm volatile(
      "mma.sync.aligned.m16n8k16.row.col.f32.bf16.bf16.f32 {%0,%1,%2,%3}, {%4,%5,%6,%7}, {%8,%9}, {%0,%1,%2,%3};"
      : "+f"(c[0]), "+f"(c[1]), "+f"(c[2]), "+f"(c[3])
      : "r"(a0), "r"(a1), "r"(a2), "r"(a3), "r"(b0), "r"(b1));
}

__device__ __forceinline__ void fold_w1(const int u, const __nv_bfloat16* __restrict__ wqkv, uint8_t* wimg) {
  const int g = (threadIdx.x >> 2) & 7, l = threadIdx.x & 3;
  const int m0 = (u / 12) * 16, s = u % 12;
  uint4 A[12], B[12];
  const __nv_bfloat16* arow = wqkv + (m0 + 4 * (g >> 1) + (g & 1)) * 576 + 192 + 8 * l;
  const __nv_bfloat16* brow = wqkv + (16 * s + 4 * (g >> 1) + (g & 1)) * 576 + 8 * l;
#pragma unroll
  for (int i = 0; i < 12; i++) {
    A[i] = ldg128_nc(arow + (i & 1) * 2 * 576 + 32 * (i >> 1));
    B[i] = ldg128_nc(brow + (i & 1) * 2 * 576 + 32 * (i >> 1));
  }
  sched_fence();
  uint8_t* dst = wimg + wimg_off(m0 + g, 16 * s + 4 * l);
  float acc[4][4];
#pragma unroll
  for (int j = 0; j < 16; j++) acc[j >> 2][j & 3] = 0.f;
#pragma unroll
  for (int i = 0; i < 6; i++) {
    const uint4 &a0 = A[2 * i], &a1 = A[2 * i + 1];
#pragma unroll
    for (int nb = 0; nb < 2; nb++) {
      mma16816(acc[2 * nb], a0.x, a1.x, a0.y, a1.y, B[2 * i + nb].x, B[2 * i + nb].y);
      mma16816(acc[2 * nb + 1], a0.z, a1.z, a0.w, a1.w, B[2 * i + nb].z, B[2 * i + nb].w);
    }
  }
#pragma unroll
  for (int j = 0; j < 2; j++) {
    const uint2 v = make_uint2(pack_bf16((acc[0][2 * j] + acc[1][2 * j]) * kAlpha, (acc[0][2 * j + 1] + acc[1][2 * j + 1]) * kAlpha),
                               pack_bf16((acc[2][2 * j] + acc[3][2 * j]) * kAlpha, (acc[2][2 * j + 1] + acc[3][2 * j + 1]) * kAlpha));
    asm volatile("st.relaxed.gpu.global.v2.u32 [%0], {%1,%2};" ::"l"(dst + j * 1024), "r"(v.x), "r"(v.y) : "memory");
  }
}
__device__ __forceinline__ void fold_w2(const int u, const __nv_bfloat16* __restrict__ wqkv, const __nv_bfloat16* __restrict__ wo,
                                        uint8_t* wimg) {
  const int g = (threadIdx.x >> 2) & 7, l = threadIdx.x & 3;
  const int m0 = (u / 12) * 32, n0 = (u % 12) * 16;
  uint4 S[12];
  uint32_t L[96];
  const __nv_bfloat16* brow = wqkv + (n0 + 4 * (g >> 1) + (g & 1)) * 576 + 384 + 8 * l;
#pragma unroll
  for (int i = 0; i < 12; i++) S[i] = ldg128_nc(brow + (i & 1) * 2 * 576 + 32 * (i >> 1));
  const __nv_bfloat16* acol = wo + (8 * l) * 192 + m0 + 4 * g;
#pragma unroll
  for (int c = 0; c < 48; c++)
    asm volatile("ld.global.nc.v2.u32 {%0,%1}, [%2];" : "=r"(L[2 * c]), "=r"(L[2 * c + 1]) : "l"(acol + (32 * (c >> 3) + (c & 7)) * 192));
  const uint32_t off = w2_offset();
  sched_fence();
  uint8_t* img = wimg + off;
  float acc[4][4];
#pragma unroll
  for (int j = 0; j < 16; j++) acc[j >> 2][j & 3] = 0.f;
#pragma unroll
  for (int i = 0; i < 6; i++) {
#pragma unroll
    for (int h = 0; h < 2; h++) {
      const uint4 &s0 = S[2 * i], &s1 = S[2 * i + 1];
#pragma unroll
      for (int mt = 0; mt < 2; mt++) {
        const uint32_t* a = L + 16 * i + 8 * h + mt;
        const uint32_t a0 = __byte_perm(a[0], a[2], 0x5410), a1 = __byte_perm(a[0], a[2], 0x7632);
        const uint32_t a2 = __byte_perm(a[4], a[6], 0x5410), a3 = __byte_perm(a[4], a[6], 0x7632);
        mma16816(acc[2 * mt], a0, a1, a2, a3, h ? s0.z : s0.x, h ? s0.w : s0.y);
        mma16816(acc[2 * mt + 1], a0, a1, a2, a3, h ? s1.z : s1.x, h ? s1.w : s1.y);
      }
    }
  }
#pragma unroll
  for (int j = 0; j < 4; j++) {
    const float(&c0)[4] = acc[j & 2];
    const float(&c1)[4] = acc[(j & 2) + 1];
    asm volatile("st.relaxed.gpu.global.v2.u32 [%0], {%1,%2};" ::"l"(img + w2img_off(g2_inv(m0 + 4 * g + j), n0 + 4 * l)),
                 "r"(pack_bf16(c0[2 * (j & 1)], c0[2 * (j & 1) + 1])), "r"(pack_bf16(c1[2 * (j & 1)], c1[2 * (j & 1) + 1])) : "memory");
  }
}

__global__ void __launch_bounds__(256) fold_kernel(const __nv_bfloat16* __restrict__ wqkv,
                                                   const __nv_bfloat16* __restrict__ wo, uint8_t* wimg) {
  const int u = blockIdx.x * 8 + (threadIdx.x >> 5);
  if (u < 144) fold_w1(u, wqkv, wimg);
  else fold_w2(u - 144, wqkv, wo, wimg);
}

struct TileCoord { int pr, pc, I, J, up, kind; };
struct TileTable { uint16_t e[kCtas * 6], g[5][8][2], b[5][2][4]; };
inline void make_tiles(TileTable& tt) {
  for (int tile = 0; tile < kCtas * 6; tile++) {
    const int b = tile / 6, k = tile - 6 * b;
    const int p = b < 128 ? (tile - 672) >> 1 : b - 80;
    const int strip = b < 112 ? b >> 1 : b >= 128 && k >= 2 ? (b & 1) * 27 + (b & 2) * 14 : p + (p < 26 ? 1 : 3);
    const int pr = strip >= 28, J = (strip - pr * 28) >> 1, pc = strip & 1, up = b < 112 ? b & 1 : pr;
    const int first = b < 112 ? 8 - 2 * pr - up : 13 * pr, step = b < 112 ? k : k & 1;
    const int I = up ? first - step : first + step;
    const int kind = I == 13 * pr ? 3 + pr : J == 13 * pc ? 1 + pc : 0;
    tt.e[tile] = (uint16_t)(I | J << 4 | pr << 8 | pc << 9 | up << 10 | kind << 11);
  }
  for (int kind = 0; kind < 5; kind++) {
    const bool col = kind == 1 || kind == 2;
    auto off = [kind](int t) { return kind == 0 ? 2 * t : kind & 1 ? t + (t == 7) : t + (t > 0); };
    for (int j = 0; j < 8; j++) {
      const int w = j >> 1, h = j & 1;
      tt.g[kind][j][0] = (uint16_t)(col ? 3 * off(w + 4 * h) : 3 * (kW * off(2 * w) + 8 * h));
      tt.g[kind][j][1] = (uint16_t)(128 * (col ? 5 : 5 + off(2 * w + 1) - off(2 * w)));
    }
    for (int i = 0; i < 2; i++) {
      const int w = kind == 0 ? 0 : kind & 1 ? 3 * i : 1 - i;
      tt.b[kind][i][0] = tt.g[kind][2 * w][0];
      tt.b[kind][i][1] = (uint16_t)(128 * (kind == 0 ? 0 : (col ? 3 : 1) + i));
      tt.b[kind][i][2] = (uint16_t)(2048 * w);
      tt.b[kind][i][3] = 0;
    }
  }
}
__device__ __forceinline__ int num_tiles() { return blockIdx.x < 128 ? 6 : 4; }
__device__ __forceinline__ TileCoord decode_tile(const TileTable& tt, int tile) {
  const uint32_t e = tt.e[tile];
  return TileCoord{(int)(e >> 8) & 1, (int)(e >> 9) & 1, (int)e & 15, (int)(e >> 4) & 15, (int)(e >> 10) & 1, (int)(e >> 11)};
}
__device__ __forceinline__ int halo_r0(const TileCoord& t) { return 8 * t.I + 6 * t.pr - 6; }
__device__ __forceinline__ int halo_c0(const TileCoord& t) { return min(max(8 * t.J + 6 * t.pc - 6, -3), 102); }

__device__ __forceinline__ uint32_t bar_full(uint32_t bars, int wg, int c) { return bars + (wg * 3 + c) * 8; }
__device__ __forceinline__ uint32_t bar_w1c(uint32_t bars, int c) { return bars + (6 + c) * 8; }
__device__ __forceinline__ uint32_t bar_w2(uint32_t bars) { return bars + 9 * 8; }
__device__ __forceinline__ uint32_t bar_x(uint32_t bars, int j, int c) { return bars + (j == 0 ? 10 : c ? 17 + c : 11) * 8; }
__device__ __forceinline__ uint32_t bar_w1q(uint32_t bars) { return bars + 12 * 8; }
__device__ __forceinline__ uint32_t bar_xf(uint32_t bars) { return bars + 13 * 8; }
__device__ __forceinline__ uint32_t bar_w2m(uint32_t bars) { return bars + 14 * 8; }
__device__ __forceinline__ uint32_t bar_redo(uint32_t bars) { return bars + 15 * 8; }
__device__ __forceinline__ uint32_t bar_wok(uint32_t bars) { return bars + 16 * 8; }
__device__ __forceinline__ uint32_t bar_go(uint32_t bars) { return bars + 17 * 8; }
__device__ __forceinline__ uint32_t bar_raw(uint32_t bars, int j = 0) { return bars + (21 + j) * 8; }
__device__ __forceinline__ uint32_t bar_w2a(uint32_t bars) { return bars + 20 * 8; }
constexpr int kNumBars = 22;

__device__ __forceinline__ uint64_t wdesc(uint64_t d0, int s) { return d0 + (((s >> 2) * kWChunk + (s & 3) * 32) >> 4); }

__device__ __forceinline__ uint32_t x_chunk(int k, int c) { return kXOff + (k == 0 ? kWChunk : 0) + (k & 1 ? 2 - c : c) * 8192; }
__device__ __forceinline__ uint32_t out_slot(int k, int nt) { return k + 1 < nt ? kW2Off + (~k & 1) * 2 * kWChunk : kW1Off + kWChunk; }
template <int I0, int I1>
__device__ __forceinline__ void store_rows(bool on, __nv_bfloat16* pA, __nv_bfloat16* pB, const uint32_t (&a)[24], const uint32_t (&b)[24]) {
#pragma unroll
  for (int i = 2 * I0; i < 2 * I1; i++) {
    const uint32_t* v = (i & 1 ? b : a) + 4 * (i >> 1);
    asm volatile("{\n.reg .pred p;\nsetp.ne.u32 p, %5, 0;\n@p st.global.v4.u32 [%0], {%1,%2,%3,%4};\n}\n" ::"l"((i & 1 ? pB : pA) + 32 * (i >> 1)),
                 "r"(v[0]), "r"(v[1]), "r"(v[2]), "r"(v[3]), "r"((uint32_t)on) : "memory");
  }
}
template <int I0, int I1>
__device__ __forceinline__ void stage_out(uint32_t sts, int wg, const uint32_t (&a)[24], const uint32_t (&b)[24]) {
  const uint32_t e = sts, o = sts ^ 64;
  const uint32_t ad[4] = {wg ? o + 1024 : e, wg ? e + 2048 : o, wg ? e : o + 1024, wg ? o : e + 2048};
#pragma unroll
  for (int i = I0; i < I1; i++) {
    const uint32_t* v = (i < 6 ? a : b) + 4 * (i % 6);
    asm volatile("st.shared.v4.u32 [%0], {%1,%2,%3,%4};" ::"r"(ad[i % 6 / 3 * 2 + (i % 3 == 1)] + (i % 3 == 2) * 1024 + (i / 6) * 12288),
                 "r"(v[0]), "r"(v[1]), "r"(v[2]), "r"(v[3]) : "memory");
  }
}
__device__ __forceinline__ uint32_t now_ns() {
  uint32_t t;
  asm volatile("mov.u32 %0, %globaltimer_lo;" : "=r"(t)::"memory");
  return t;
}
__device__ __forceinline__ void wait_clock(uint32_t t_start, uint32_t t) {
  while (now_ns() - t_start < t) { }
}
#define NAT_PRED(f, m) ".reg .pred p;\n.reg .b32 t;\nand.b32 t, " f ", " m ";\nsetp.ne.u32 p, t, 0;\n"
constexpr uint32_t kHiV = 1, kHiU = 8, kColB = 0x20, kInV = 0x100, kInU = 0x1000, kColA = 0x10000;
template <uint32_t M>
__device__ __forceinline__ float pick(const float* a, const float* b, uint32_t f) {
  float d;
  asm("{\n" NAT_PRED("%5", "%6") "add.f32 %0, %1, %2;\n@p add.f32 %0, %3, %4;\n}\n"
      : "=&f"(d) : "f"(a[0]), "f"(a[2]), "f"(b[0]), "f"(b[2]), "r"(f), "n"(M));
  return d;
}
template <uint32_t M>
__device__ __forceinline__ float sel(float a, float b, uint32_t f) {
  float d;
  asm("{\n" NAT_PRED("%3", "%4") "selp.f32 %0, %1, %2, p;\n}\n" : "=f"(d) : "f"(a), "f"(b), "r"(f), "n"(M));
  return d;
}
template <uint32_t M>
__device__ __forceinline__ void max_if(float& m, float v, uint32_t f) {
  asm("{\n" NAT_PRED("%2", "%3") "@p max.f32 %0, %0, %1;\n}\n" : "+f"(m) : "f"(v), "r"(f), "n"(M));
}
template <uint32_t M>
__device__ __forceinline__ void add_if(float& m, float v, uint32_t f) {
  asm("{\n" NAT_PRED("%2", "%3") "@p add.f32 %0, %0, %1;\n}\n" : "+f"(m) : "f"(v), "r"(f), "n"(M));
}
__device__ __forceinline__ void pick_v(const float* a, float* v, uint32_t f) {
  v[0] = pick<kHiV>(a, a + 16, f), v[1] = pick<kHiV>(a + 1, a + 17, f);
  v[2] = pick<kHiV * 2>(a + 4, a + 20, f), v[3] = pick<kHiV * 2>(a + 5, a + 21, f);
  v[4] = pick<kHiV * 4>(a + 8, a + 24, f), v[5] = pick<kHiV * 4>(a + 9, a + 25, f);
  v[6] = a[12] + a[14], v[7] = a[13] + a[15];
}
__device__ __forceinline__ void pick_u(const float* a, float* v, uint32_t f) {
#pragma unroll
  for (int c = 0; c < 3; c++) v[2 * c] = pick<kHiU>(a + 4 * c, a + 4 * c + 12, f), v[2 * c + 1] = pick<kHiU * 2>(a + 4 * c + 1, a + 4 * c + 13, f);
}
__device__ __forceinline__ uint32_t sign_bytes(uint32_t v, uint32_t sel) {
  uint32_t d;
  asm("prmt.b32 %0, %1, %1, %2;" : "=r"(d) : "r"(v), "r"(sel));
  return d;
}
__device__ __forceinline__ float own_max(const float (&v)[14], uint32_t f) {
  float m = sel<kInV>(fmaxf(v[0], v[1]), -INFINITY, f), m2 = sel<kInV * 2>(fmaxf(v[2], v[3]), -INFINITY, f);
  max_if<kInV * 4>(m, fmaxf(v[4], v[5]), f);
  max_if<kInV * 8>(m2, fmaxf(v[6], v[7]), f);
  max_if<kInU>(m, fmaxf(fmaxf(v[8], v[10]), v[12]), f);
  max_if<kInU * 2>(m2, fmaxf(fmaxf(v[9], v[11]), v[13]), f);
  return fmaxf(m, m2);
}
__device__ __forceinline__ float quad_max(float m) {
  const float a = __shfl_xor_sync(0xffffffffu, m, 1), b = __shfl_xor_sync(0xffffffffu, m, 2), c = __shfl_xor_sync(0xffffffffu, m, 3);
  return fmaxf(fmaxf(m, a), fmaxf(b, c));
}
__device__ __forceinline__ float row_rcp(const float (&v)[14], uint32_t f) {
  float s = sel<kInV>(v[0] + v[1], 0.f, f), s2 = sel<kInV * 2>(v[2] + v[3], 0.f, f);
  add_if<kInV * 4>(s, v[4] + v[5], f);
  add_if<kInV * 8>(s2, v[6] + v[7], f);
  add_if<kInU>(s, v[8] + v[10] + v[12], f);
  add_if<kInU * 2>(s2, v[9] + v[11] + v[13], f);
  s += s2;
  const float a = __shfl_xor_sync(0xffffffffu, s, 1), b = __shfl_xor_sync(0xffffffffu, s, 2), c = __shfl_xor_sync(0xffffffffu, s, 3);
  return rcp_approx((s + a) + (b + c));
}
__device__ __forceinline__ void route(const float (&v)[14], float s, const uint32_t (&rt)[9], uint32_t (&p)[14]) {
#pragma unroll
  for (int i = 0; i < 7; i++) {
    const uint32_t u = pack_bf16(v[2 * i] * s, v[2 * i + 1] * s);
    if (i < 4) p[i] = u & rt[i];
    if (i < 3) p[i + 4] = u & rt[i + 4];
    if (i >= 4) {
      p[i + 3] = u & rt[7];
      p[i + 6] = u & rt[8];
    }
  }
}

template <int C, int T0 = 0, int T1 = 7>
__device__ __forceinline__ void pv_chunk(float (&z)[32], const uint32_t (&pa)[14], const uint32_t (&pb)[14],
                                         const uint32_t (&meta)[4], uint64_t dV) {
#pragma unroll
  for (int t = T0; t < T1; t++) {
    if (t & 1)
      wg_s64t1<0, 32>(z, pa[2 * t], pb[2 * t], pa[2 * t + 1], pb[2 * t + 1], dV + ((2 * C * kChunkBytes + t * 2048) >> 4), 1,
                      meta[t >> 1]);
    else if (t > 0)
      wg_s64t<0, 32>(z, pa[2 * t], pb[2 * t], pa[2 * t + 1], pb[2 * t + 1], dV + ((2 * C * kChunkBytes + t * 2048) >> 4), 1,
                     meta[t >> 1]);
    else
      wg_s64tz<0, 32>(z, pa[0], pb[0], pa[1], pb[1], dV + ((2 * C * kChunkBytes) >> 4), 0, meta[0]);
  }
}
template <int C>
__device__ __forceinline__ void pack_z(const float (&z)[32], uint32_t (&za)[24], uint32_t (&zb)[24]) {
#pragma unroll
  for (int j = 0; j < 8; j++) {
    za[8 * C + j] = pack_bf16(z[4 * j], z[4 * j + 1]);
    zb[8 * C + j] = pack_bf16(z[4 * j + 2], z[4 * j + 3]);
  }
}

template <int H>
__device__ __forceinline__ void pack_out(const float (&ac)[48], uint32_t (&oa)[24], uint32_t (&ob)[24]) {
#pragma unroll
  for (int j = 0; j < 12; j++) {
    oa[12 * H + j] = pack_bf16(ac[4 * j], ac[4 * j + 1]);
    ob[12 * H + j] = pack_bf16(ac[4 * j + 2], ac[4 * j + 3]);
  }
}
struct Maps { CUtensorMap v6, v2, v14, u8, px[8], wv, wo; };
__device__ __forceinline__ void tma_prefetch_5d(const CUtensorMap* map, int c0, int c1, int c2, int c3, int c4) {
  asm volatile("cp.async.bulk.prefetch.tensor.5d.L2.global.tile [%0, {%1, %2, %3, %4, %5}];" ::"l"((uint64_t)map), "r"(c0), "r"(c1),
               "r"(c2), "r"(c3), "r"(c4) : "memory");
}
__device__ __forceinline__ int first_line(const TileCoord tc) { return 3 * (qpix(tc.pr, 8 * tc.I) * kW + qpix(tc.pc, 8 * tc.J)); }
__device__ __forceinline__ void load_px(const Maps& tm, const TileTable& tt, uint32_t dst, uint32_t bar, int line, int kind) {
#pragma unroll
  for (int i = 0; i < 2; i++) {
    if (i == 0 || kind != 0) {
      const CUtensorMap* map = (const CUtensorMap*)((const char*)tm.px + tt.b[kind][i][1]);
      if (bar) tma_load_5d(dst + tt.b[kind][i][2], map, bar, 0, 0, 0, 0, line + tt.b[kind][i][0]);
      else tma_prefetch_5d(map, 0, 0, 0, 0, line + tt.b[kind][i][0]);
    }
  }
}
__device__ __forceinline__ void store_px(const Maps& tm, const TileTable& tt, uint32_t buf, int line, int kind) {
#pragma unroll
  for (int i = 0; i < 8; i++) {
    const int j = 2 * (i & 3) + (i >> 2);
    asm volatile("cp.async.bulk.tensor.5d.global.shared::cta.tile.bulk_group [%0, {%2, %2, %2, %2, %3}], [%1];" ::"l"(
                     (uint64_t)tm.px + tt.g[kind][j][1]), "r"(buf + i * 3072), "r"(0), "r"(line + tt.g[kind][j][0]) : "memory");
  }
  asm volatile("cp.async.bulk.commit_group;" ::: "memory");
}
__device__ __noinline__ bool refetch(uint32_t base, const uint8_t* src, bool gap) {
  constexpr uint32_t bars = 1024 + kBarOff, cnt = bars + 192;
#pragma unroll 1
  for (uint32_t o = 0; o < kWBytes && !gap; o += 2048) {
    uint32_t mx = 0;
#pragma unroll
    for (int i = 0; i < 4; i++) {
      uint4 v;
      asm volatile("ld.shared.v4.u32 {%0,%1,%2,%3}, [%4];" : "=r"(v.x), "=r"(v.y), "=r"(v.z), "=r"(v.w)
                   : "r"(base + o + i * 512 + (threadIdx.x & 31) * 16));
      mx = __vimax3_u32(__vimax3_u32(mx, v.x, v.y), v.z, v.w);
    }
    gap = __any_sync(0xffffffffu, mx == kEmpty);
  }
  uint32_t n;
  asm volatile("ld.shared.u32 %0, [%1];" : "=r"(n) : "r"(cnt) : "memory");
  if (!gap || __any_sync(0xffffffffu, n > (1u << 12))) return false;
  asm volatile("bar.sync 15, 128;" ::: "memory");
  if (threadIdx.x == 0) {
    asm volatile("st.shared.u32 [%0], %1;" ::"r"(cnt), "r"(n + 1) : "memory");
    mbar_arrive_expect_tx(bar_redo(bars), kWBytes);
    bulk_load(base, src, kWBytes, bar_redo(bars));
  }
  __syncwarp();
  mbar_wait(bar_redo(bars), n & 1);
  return true;
}
template <int S0, int S1, int Z>
__device__ __forceinline__ void g2_steps(float (&ac)[48], const uint32_t (&za)[24], const uint32_t (&zb)[24], uint64_t d) {
#pragma unroll
  for (int s = S0; s < S1; s++) {
    const uint64_t ds = d + (((s >> 2 & 1) * (kWChunk / 2) + (s & 3) * 32) >> 4);
    if (s == Z) wg_d96z<0, 48>(ac, za[2 * s], zb[2 * s], za[2 * s + 1], zb[2 * s + 1], ds, 0);
    else wg_d96<0, 48>(ac, za[2 * s], zb[2 * s], za[2 * s + 1], zb[2 * s + 1], ds, 1);
  }
}

__device__ __forceinline__ void consumer(const int wg, __nv_bfloat16* out, const uint8_t* wimg, const uint32_t sbase,
                                         const uint32_t zero, const Maps& tm, const TileTable& tt) {
  const int tid = threadIdx.x & 127;
  const int w = __shfl_sync(0xffffffffu, tid >> 5, 0), lane = tid & 31;
  const uint64_t dK = make_desc(sbase, 16, 1024);
  const uint64_t dV = make_desc(sbase, kChunkBytes, 512, 2);
  const uint64_t dW1 = make_desc(sbase + kW1Off, 16, 1024);
  const uint64_t dX0 = make_desc(sbase + kW2Off + wg * 2 * kWChunk, 16, 1024), dY0 = make_desc(sbase + kW2Off + (1 - wg) * 2 * kWChunk, 16, 1024);
  const uint64_t dX2 = make_desc(sbase + kXOff + wg * (kWChunk / 2), 16, 1024), dY2 = make_desc(sbase + kXOff + (1 - wg) * (kWChunk / 2), 16, 1024);
  const uint32_t bars = sbase + kBarOff;
  int tile0 = blockIdx.x * kTilesPerCta;
  asm volatile("" : "+r"(tile0));
  const int nt = num_tiles();

  uint32_t pix = 0, geo[6] = {};
  const int l = lane & 3;
#pragma unroll 1
  for (int j = 4; j >= 0; j -= 2) {
    const TileCoord tc = decode_tile(tt, tile0 + wg + j);
    const bool col = tc.kind == 1 || tc.kind == 2;
    const int g = col ? lane >> 2 : 2 * w + ((lane >> 2) & 1), qc = col ? w : lane >> 3;
    const uint32_t pr = qpix(tc.pr, 8 * tc.I + g) * kW;
    if (j == nt - 2) pix = (pr + qpix(tc.pc, 8 * tc.J + qc)) | (pr + qpix(tc.pc, 8 * tc.J + qc + 4)) << 16;
    const int d = 8 * tc.J + 6 * tc.pc - 6 - halo_c0(tc);
    const int ro = woff(tc.pr, tc.I, g), coA = woff(tc.pc, tc.J, qc) + d, coB = woff(tc.pc, tc.J, qc + 4) + d - 3;
#pragma unroll
    for (int i = 5; i >= 2; i--) geo[i] = geo[i - 2];
    const uint32_t lr = 0x1FCu << ro;
    const uint32_t lv = lr >> (2 + (l >> 1)), lu = lr >> (2 * l + 2 * tc.up);
    const uint32_t t = __byte_perm(lv, lu, wg ? 0x4501 : 0x5410);
    geo[0] = (((t & 0x15u) | (lv & 0x40u)) * 0x02082080u & 0x80808080u) | (((t >> 8) & 0x15u) * 0x01041040u & 0x40404040u) |
             (__byte_perm(t << 5, t << 4, 0x7362) & 0x20202020u) | (nt == 6);
    const int dr = (ro - 1) & 7;
    const uint32_t hiv = (((1u << ((ro - (l >> 1) + 1) >> 1)) - 1u) ^ (wg ? 7u : 0u)) & 7u, hiu = (t >> 24) & 3u;
    const uint32_t ca = (1u << coA) - 1u;
    geo[1] = hiv * kHiV | hiu * kHiU | ((((1u << coB) - 1u) >> (2 * (l & 1))) & 3u) * kColB |
             (15u & ~((uint32_t)((dr & 1) == (l >> 1)) << (dr >> 1))) * kInV | ((t >> 16 | t >> 24) & 3u) * kInU | ca * kColA |
             (ca >> ((0x49 >> (2 * l)) & 3) & 1u) << 19 | (uint32_t)(l == 3) << 20 | (0x55u & ((1u << (2 * coB)) - 1u)) << 24;
  }
  keep_regs(geo);
  const int so = (lane >> 3) | (lane & 4);
  uint32_t sts = sbase + w * 3072 + so * 128 + (((lane & 3) ^ so) << 4);
  __nv_bfloat16* poA = out + 8 * l + (pix & 0xFFFFu) * kC + 96 * wg;
  __nv_bfloat16* poB = out + 8 * l + (pix >> 16) * kC + 96 * wg;
  asm volatile("" : "+l"(poA), "+l"(poB), "+r"(sts));
  uint32_t oa[24], ob[24];
#pragma unroll
  for (int j = 0; j < 24; j++) oa[j] = ob[j] = 0u;
  keep_regs(oa);
  keep_regs(ob);
  PROF(wg, 0);
  if (threadIdx.x == 0) GT(1);

  for (int k = wg; k < nt; k += 2) {
    const uint32_t ph = (k >> 1) & 1;
    const int it = k >> 1;
    uint32_t qa[24], qb[24], hok[3];
    uint32_t fl = geo[1];
    {
      float acc[96];
      const uint32_t xp = (k + (k > 0)) & 1;
      const uint32_t xok = mbar_test(bar_x(bars, k > 0, 0), xp);
      if (k > 0) nb_sync(1 + (1 - wg));
#pragma unroll
      for (int s = 0; s < 12; s++) {
        if (s == 0) mbar_wait_if(xok, bar_x(bars, k > 0, 0), xp);
        if (s == 0 && k < 2) PROF(wg, 1);
        if (s == 0) PROFS(2, wg, 2 + it * 12);
        if (s == 0 && w == 0 && k < 2) GT(20 + wg);
        if ((s & 3) == 0 && (k == 0 || s > 0)) {
          mbar_wait(k == 0 ? bar_w1c(bars, s >> 2) : bar_x(bars, 1, s >> 2), xp);
          PROFS(17, wg, 50 + (s >> 2));
        }
        if ((s & 3) == 0) wg_fence();
        const uint64_t dX = make_desc(sbase + x_chunk(k, s >> 2), 16, 1024) + 2 * (s & 3);
        if (s == 0) wg_m192z<0, 96>(acc, dX, dW1, 0);
        else wg_m192<0, 96>(acc, dX, wdesc(dW1, s), 1);
        if ((s & 3) == 3) wg_commit();
      }
      PROFS(13, wg, 13 + it * 12);
      if (NAT_MP > 2) {
        wg_wait<2>();
        if (k > 0) nb_arrive_p(0);
      }
      if (NAT_MP > 1) {
        wg_wait<1>();
        if (k > 0) nb_arrive_p(14);
      }
      wg_wait<0>();
      if (k > 0) nb_arrive_p(6);
      fence_regs(acc);
      PROFS(3, wg, 3 + it * 12);
#pragma unroll
      for (int j = 0; j < 24; j++) {
        qa[j] = pack_bf16(acc[4 * j], acc[4 * j + 1]);
        qb[j] = pack_bf16(acc[4 * j + 2], acc[4 * j + 3]);
      }
      keep_regs(qa);
      keep_regs(qb);
      sched_fence();
      if (k >= 2) {
        const uint32_t dst = sts + out_slot(k, nt);
        nb_sync(11);
        stage_out<0, 6>(dst, wg, oa, ob);
        nb_sync(12);
        stage_out<6, 12>(dst, wg, oa, ob);
      }
#pragma unroll
      for (int c = 0; c < 3; c++) hok[c] = mbar_test(bar_full(bars, wg, c), ph);
      if (k >= 2) {
        fence_proxy_async();
        nb_arrive_p(10);
      }
    }

    float aE[52], aO[24], bO[52], bE[28];
    const uint32_t mq = 0xEEEE4444u | zero;
    PROFS(4, wg, 4 + it * 12);

    mbar_wait_if(hok[0], bar_full(bars, wg, 0), ph);
    PROFS(14, wg, 40 + it * 3);
    if (w == 0 && k < 2) GT(22 + wg);
    if (k > 0) nb_sync(3 + (1 - wg));
    wg_fence();
#pragma unroll
    for (int ks = 0; ks < 6; ks++) {
      if (ks == NAT_P1) {
        mbar_wait_if(hok[1], bar_full(bars, wg, 1), ph);
        PROFS(14, wg, 41 + it * 3);
        wg_fence();
      }
      if (ks == NAT_P2) {
        mbar_wait_if(hok[2], bar_full(bars, wg, 2), ph);
        PROFS(14, wg, 42 + it * 3);
        wg_fence();
      }
      const uint64_t d = dK + ((ks * kChunkBytes) >> 4);
      if (ks == 0) wg_s104z<0, 52>(aE, qa[0], qa[1], qa[2], qa[3], d, 0, mq);
      else wg_s104<0, 52>(aE, qa[4 * ks], qa[4 * ks + 1], qa[4 * ks + 2], qa[4 * ks + 3], d, 1, mq);
      if (ks == 0) wg_s48z<0, 24>(aO, qa[0], qa[1], qa[2], qa[3], d + ((7 * 1024 + 64) >> 4), 0, mq);
      else if (ks < NAT_QA) wg_s48<0, 24>(aO, qa[4 * ks], qa[4 * ks + 1], qa[4 * ks + 2], qa[4 * ks + 3], d + ((7 * 1024 + 64) >> 4), 1, mq);
    }
    wg_commit();
#pragma unroll
    for (int ks = NAT_QA; ks < 6; ks++)
      wg_s48<0, 24>(aO, qa[4 * ks], qa[4 * ks + 1], qa[4 * ks + 2], qa[4 * ks + 3], dK + ((ks * kChunkBytes + 7 * 1024 + 64) >> 4), 1, mq);
    wg_commit();
    wg_s56z<0, 28>(bE, qb[0], qb[1], qb[2], qb[3], dK, 0, mq);
#pragma unroll
    for (int ks = 1; ks < 6; ks++) wg_s56<0, 28>(bE, qb[4 * ks], qb[4 * ks + 1], qb[4 * ks + 2], qb[4 * ks + 3], dK + ((ks * kChunkBytes) >> 4), 1, mq);
    wg_commit();
    wg_wait<2>();
    fence_regs(aE);
    PROFS(5, wg, 5 + it * 12);

    uint32_t pa[14], pb[14], meta[4];
    {
      float vA[14], vB[14];
      pick_v(aE, vA, fl);
      pick_u(aE + 28, vA + 8, fl);
      fence_regs(vA);
      if (k == 0) {
        if (__builtin_expect(__any_sync(0xffffffffu, vA[6] != vA[6]), 0)) {
          wg_wait<0>();
          fence_regs(aO);
          fence_regs(bE);
          if (refetch(sbase + kW1Off, wimg, false)) {
#pragma unroll
            for (int j = 0; j < 24; j++) oa[j] = ob[j] = 0u;
            k -= 2;
            continue;
          }
        }
        if (elect_one()) mbar_arrive(bar_xf(bars));
      }
      wg_fence();
      wg_s104z<0, 52>(bO, qb[0], qb[1], qb[2], qb[3], dK + 4, 0, mq);
#pragma unroll
      for (int ks = 1; ks < 6; ks++)
        wg_s104<0, 52>(bO, qb[4 * ks], qb[4 * ks + 1], qb[4 * ks + 2], qb[4 * ks + 3], dK + ((ks * kChunkBytes + 64) >> 4), 1, mq);
      wg_commit();
      if (k + 1 < nt) nb_arrive(1 + wg);
      uint32_t rt[9];
#pragma unroll
      for (int i = 0; i < 7; i++) rt[i] = sign_bytes(geo[0] << (i >> 2), 0x8888u + 0x1111u * (i & 3));
      rt[7] = sign_bytes(geo[0] << 2, 0x9988u);
      rt[8] = sign_bytes(geo[0] << 2, 0xBBAAu);
      keep_regs(rt);
      pa[13] = pb[13] = 0u;
      wg_wait<2>();
      keep_regs(qa);
      fence_regs(aO);
      float oA[6], eB[8];
      pick_u(aO, oA, fl);
      wg_wait<1>();
      fence_regs(bE);
      pick_v(bE, eB, fl);
      vA[8] = sel<kColA>(oA[0], vA[8], fl), vA[9] = sel<kColA>(oA[1], vA[9], fl);
      vA[10] = sel<kColA * 2>(oA[2], vA[10], fl), vA[11] = sel<kColA * 2>(oA[3], vA[11], fl);
      vA[12] = sel<kColA * 4>(oA[4], vA[12], fl), vA[13] = sel<kColA * 4>(oA[5], vA[13], fl);
      {
        const float m1 = __uint_as_float(0x88DD88DDu), m0 = __uint_as_float(0x88DDDD88u);
        meta[0] = 0xDD88DD88u ^ __byte_perm(fl, 0u, 0x3344);
        meta[1] = __float_as_uint(sel<kColA * 16>(sel<kColA>(m1, m0, fl), __uint_as_float(meta[0]), fl));
        meta[2] = __float_as_uint(sel<kColA * 8>(m1, m0, fl));
        meta[3] = __float_as_uint(sel<kColA * 4>(m1, m0, fl));
        keep_regs(meta);
      }
      float mA = own_max(vA, fl);
      fl |= __float_as_uint(eB[7]) & zero;
      fence_regs(eB);
      fence_regs(vA);
      asm volatile("" : "+f"(mA), "+r"(fl));
      sched_fence();
      wg_wait<0>();
      sched_fence();
      keep_regs(qb);
      fence_regs(bO);
      PROFS(6, wg, 6 + it * 12);
      if (w == 0) GT(24 + k);
      mA = quad_max(mA);
#pragma unroll
      for (int i = 0; i < 14; i++) vA[i] = ex2(vA[i] - mA);
      pick_v(bO, vB, fl);
      pick_u(bO + 28, vB + 8, fl);
#pragma unroll
      for (int i = 0; i < 8; i += 2) vB[i] = sel<kColB>(vB[i], eB[i], fl), vB[i + 1] = sel<kColB * 2>(vB[i + 1], eB[i + 1], fl);
      float mB = quad_max(own_max(vB, fl));
      if (NAT_SB) {
        fence_regs(vA);
        fence_regs(vB);
        asm volatile("" : "+f"(mB));
        sched_fence();
      }
      PROFS(7, wg, 7 + it * 12);
#pragma unroll
      for (int i = 0; i < 14; i++) vB[i] = ex2(vB[i] - mB);
      route(vA, row_rcp(vA, fl), rt, pa);
      route(vB, row_rcp(vB, fl), rt, pb);
    }
    PROFS(8, wg, 8 + it * 12);
    if (k == NAT_PK) PROFS(18, wg, 53);
    sched_fence();

    float ac0[48], ac1[48];
    {
      float z0[32], z1[32], z2[32];
      uint32_t za[24], zb[24];
      wg_fence();
      pv_chunk<0>(z0, pa, pb, meta, dV);
      wg_commit();
      pv_chunk<1>(z1, pa, pb, meta, dV);
      wg_commit();
      wg_wait<1>();
      if (k == NAT_PK) PROFS(18, wg, 54);
      if (k + 1 < nt) nb_arrive_p(7);
      pv_chunk<2, 0, 3>(z2, pa, pb, meta, dV);
      wg_commit();
      sched_fence();
      fence_regs(z0);
      pack_z<0>(z0, za, zb);
      sched_fence();
      wg_fence();
      pv_chunk<2, 3, 7>(z2, pa, pb, meta, dV);
      wg_commit();
      wg_wait<2>();
      if (k == NAT_PK) PROFS(19, wg, 55);
      if (k + 1 < nt) nb_arrive_p(8);
      if (k < 2) mbar_wait(k == 1 ? bar_wok(bars) : bar_w2a(bars), 0);
      wg_fence();
      g2_steps<0, 3, 0>(ac0, za, zb, dX0);
      wg_commit();
      sched_fence();
      fence_regs(z1);
      pack_z<1>(z1, za, zb);
      sched_fence();
      wg_fence();
      g2_steps<3, 4, 0>(ac0, za, zb, dX0);
      wg_commit();
      g2_steps<4, 8, 0>(ac0, za, zb, dX0);
      wg_commit();
      wg_wait<3>();
      if (k + 1 < nt) nb_arrive_p(9);
      else nb_arrive(11);
      if (k == NAT_PK) PROFS(20, wg, 56);
      keep_regs(pa);
      keep_regs(pb);
      keep_regs(meta);
      sched_fence();
      const uint32_t mok = mbar_test(bar_w2m(bars), k + 1 < nt ? k & 1 : ~k & 1);
      const uint32_t wp = k < 2 ? 0 : k + 1 < nt ? ~k & 1 : k & 1, wok = mbar_test(bar_w2(bars), wp);
      fence_regs(z2);
      pack_z<2>(z2, za, zb);
      keep_regs(za);
      keep_regs(zb);
      sched_fence();
      PROFS(9, wg, 9 + it * 12);
      wg_wait<1>();
      if (k > 0 && k + 1 < nt) nb_arrive(11);
      mbar_wait_if(mok, bar_w2m(bars), k & 1);
      wg_fence();
      g2_steps<8, 12, 0>(ac0, za, zb, dX2);
      wg_commit();
      g2_steps<8, 12, 8>(ac1, za, zb, dY2);
      wg_commit();
      wg_wait<2>();
      if (k > 0 && k + 1 < nt) nb_arrive(12);
      mbar_wait_if(wok, bar_w2(bars), wp);
      wg_fence();
      g2_steps<0, 4, 8>(ac1, za, zb, dY0);
      wg_commit();
      wg_wait<2>();
      if (k + 2 < nt) nb_arrive_p(13);
      const bool direct = k + 2 >= nt;
      sched_fence();
      fence_regs(ac0);
      pack_out<0>(ac0, oa, ob);
      store_rows<0, NAT_D0>(direct, poA, poB, oa, ob);
      sched_fence();
      wg_fence();
      g2_steps<4, 8, 8>(ac1, za, zb, dY0);
      wg_commit();
      if (k + 1 < nt) nb_arrive(3 + wg);
      PROFS(10, wg, 10 + it * 12);
      wg_wait<2>();
      if (k + 2 < nt && (k > 0 || nt == 6)) nb_arrive_p(5);
      store_rows<NAT_D0, 3>(direct, poA, poB, oa, ob);
      __nv_bfloat16 *qA = poA - 192 * wg, *qB = poB - 192 * wg;
      if (k + 2 == nt) nb_sync(11);
      sched_fence();
      wg_wait<0>();
      fence_regs(ac1);
      pack_out<1>(ac1, oa, ob);
      asm volatile("" : "+l"(qA), "+l"(qB));
      store_rows<3, 6>(direct, qA, qB, oa, ob);
      if (k == 0) {
        uint32_t m[2] = {oa[0], oa[1]};
#pragma unroll
        for (int i = 2; i < 24; i++) asm("max.NaN.bf16x2 %0, %0, %1;" : "+r"(m[i & 1]) : "r"(oa[i]));
        asm("max.NaN.bf16x2 %0, %0, %1;" : "+r"(m[0]) : "r"(m[1]));
        uint32_t nan;
        asm volatile("{\n.reg .pred p;\nsetp.ne.u32 p, %1, 0;\nbar.red.or.pred p, 15, 128, p;\nselp.u32 %0, 1, 0, p;\n}\n"
                     : "=r"(nan) : "r"(((m[0] & 0x7FFF7FFFu) + 0x007F007Fu) & 0x80008000u) : "memory");
        if (__builtin_expect(__any_sync(0xffffffffu, nan), 0)) {
          for (int c = 0; c < 3 && __any_sync(0xffffffffu, geo[2] & 1u); c++) mbar_wait(bar_x(bars, 1, c), 1);
          for (bool first = true; __any_sync(0xffffffffu, refetch(sbase + kW2Off, wimg + w2_offset(), first)); first = false) { }
          wg_fence();
          g2_steps<0, 8, 0>(ac0, za, zb, dX0);
          g2_steps<8, 12, 0>(ac0, za, zb, dX2);
          g2_steps<8, 12, 8>(ac1, za, zb, dY2);
          g2_steps<0, 8, 8>(ac1, za, zb, dY0);
          wg_commit();
          wg_wait<0>();
          fence_regs(ac0);
          fence_regs(ac1);
          pack_out<0>(ac0, oa, ob);
          pack_out<1>(ac1, oa, ob);
          if (__any_sync(0xffffffffu, geo[2] & 1u)) {
            asm volatile("bar.sync 15, 128;" ::: "memory");
            if (w == 0 && elect_one()) {
              const TileCoord tc = decode_tile(tt, tile0 + 2);
              mbar_arrive_expect_tx(bar_raw(bars), kWChunk);
#pragma unroll 1
              for (int c = 0; c < 3; c++) load_px(tm, tt, sbase + x_chunk(2, c), bar_raw(bars), first_line(tc) + c, tc.kind);
            }
            __syncwarp();
            mbar_wait(bar_raw(bars), 0);
          }
        }
        if (nt < 6) nb_arrive_p(5);
        if (elect_one()) mbar_arrive(bar_wok(bars));
      }
      keep_regs(za);
      keep_regs(zb);
#pragma unroll
      for (int i = 0; i < 4; i++) geo[i] = geo[i + 2];
      keep_regs(oa);
      keep_regs(ob);
      PROFS(12, wg, 12 + it * 12);
      sched_fence();
    }
  }
  PROF(wg, 38);
  GT_DUMP();
  PROF_DUMP(wg);
}

struct HaloCols { int vj, vc, uj, uc; };
__device__ __forceinline__ HaloCols halo_cols(const TileCoord& tc) {
  const int c0 = halo_c0(tc);
  return HaloCols{c0 > 98, c0 > 98 ? 98 : c0 + 3, c0 < 0 ? -1 : 0, c0 < 0 ? 4 : c0};
}
__device__ __forceinline__ void first_halo(const Maps& tm, uint32_t sbase, const TileCoord tc, int i) {
  const HaloCols hc = halo_cols(tc);
  const uint32_t dst = sbase + i * kChunkBytes, bar = bar_full(sbase + kBarOff, 0, i >> 1);
  const int h0 = halo_r0(tc), ch = 24 * tc.pc + 4 * i;
  tma_load_5d(dst, &tm.v14, bar, ch, hc.vj, hc.vc, tc.pr, h0);
  tma_load_5d(dst + 7 * 1024, &tm.u8, bar, ch, hc.uj, h0 + (tc.up ? 0 : -2), tc.pr, hc.uc);
  tma_load_5d(dst + 10 * 1024, &tm.u8, bar, ch, hc.uj, h0 + (tc.up ? 8 : 6), tc.pr, hc.uc);
}
__device__ __forceinline__ void load_halo(const Maps& tm, uint32_t sbase, uint32_t bars, const TileCoord tc, int k, int c) {
  const HaloCols hc = halo_cols(tc);
  const int h6 = halo_r0(tc) + (tc.up ? 0 : 8), h2 = halo_r0(tc) + 6, h8 = halo_r0(tc) + (tc.up ? 0 : 6), ch = 24 * tc.pc + 8 * c;
  uint32_t dv = sbase + 2 * c * kChunkBytes, du = dv + 7 * 1024;
  if (((k ^ tc.up) & 1) == 0) dv += 4 * 1024, du += 3 * 1024;
  const uint32_t bar = bar_full(bars, k & 1, c);
  mbar_arrive_expect_tx(bar, 14 * 1024);
  nb_sync_p(7 + c);
#pragma unroll
  for (int h = 0; h < 2; h++) {
    tma_load_5d(dv + h * kChunkBytes, &tm.v6, bar, ch + 4 * h, hc.vj, hc.vc, tc.pr, h6);
    tma_load_5d(du + h * kChunkBytes, &tm.u8, bar, ch + 4 * h, hc.uj, h8, tc.pr, hc.uc);
    tma_load_5d(sbase + (2 * c + h) * kChunkBytes + 3 * 1024, &tm.v2, bar, ch + 4 * h, hc.vj, hc.vc, tc.pr, h2);
  }
  PROFS(15, 2, k * 4 + c);
}
__device__ __forceinline__ void gather_px(const __nv_bfloat16* __restrict__ x, uint32_t sbase, const TileCoord tc) {
  const int lane = threadIdx.x & 31, g = lane >> 3;
  uint32_t ro[4], co[4];
#pragma unroll
  for (int i = 0; i < 4; i++) {
    ro[i] = qpix(tc.pr, 8 * tc.I + 2 * i + (g & 1)) * (kW * kC * 2) + 16 * (lane & 7);
    co[i] = qpix(tc.pc, 8 * tc.J + 2 * i + (g >> 1)) * (kC * 2);
  }
  const uint32_t dst = sbase + kXOff + g * 128 + (((lane & 7) ^ g) << 4);
  if (lane < 8)
    asm volatile("cp.async.bulk.prefetch.L2.global [%0], 3456;" ::"l"(x + (qpix(tc.pr, 8 * tc.I + lane) * kW + 215 * tc.pc) * kC) : "memory");
  __syncwarp();
  keep_regs(ro);
  keep_regs(co);
  sched_fence();
  nb_sync_p(13);
  nb_sync_p(5);
#pragma unroll
  for (int i = 0; i < 16; i++) {
    const char* src = (const char*)x + (ro[i >> 2] + co[i & 3]);
#pragma unroll
    for (int q = 0; q < 3; q++)
      asm volatile("cp.async.cg.shared.global [%0], [%1], 16;" ::"r"((dst ^ ((i & 1) * 576)) + (i >> 1) * 1024 + q * 8192), "l"(src + 128 * q) : "memory");
  }
  asm volatile("cp.async.wait_all;" ::: "memory");
  fence_proxy_async();
  __syncwarp();
  if (lane < 3) mbar_arrive(bar_x(sbase + kBarOff, 1, lane));
  __syncwarp();
}

__global__ void __launch_bounds__(384, 1)
nat_kernel(const __nv_bfloat16* __restrict__ x, __nv_bfloat16* out, const __nv_bfloat16* __restrict__ wqkv,
           const __nv_bfloat16* __restrict__ wo, uint8_t* wimg, const uint32_t zero,
           const __grid_constant__ Maps tm, const __grid_constant__ TileTable tt) {
  extern __shared__ uint8_t smem_raw[];
  constexpr uint32_t sbase = 1024;
  constexpr uint32_t bars = sbase + kBarOff;
  if (smem_u32(smem_raw) != sbase) __trap();
  const int tid = threadIdx.x;
  const uint32_t t_start = now_ns();
  if (tid == 0) GT(0);
  const int wid = __shfl_sync(0xffffffffu, tid >> 5, 0);
  const bool w2cta = blockIdx.x - 128 < 3 && wqkv != nullptr;
  if (wid >= 8) {
    asm volatile("setmaxnreg.dec.sync.aligned.u32 24;");
    const int c = wid & 3, lane = tid & 31;
    const int tile0 = blockIdx.x * kTilesPerCta, nt = num_tiles();
    uint32_t w2o = 0;
    if (c == 3) {
      if (elect_one()) wait_clock(t_start, NAT_TM);
      __syncwarp();
      asm volatile("prefetch.tensormap [%0];" ::"l"((uint64_t)tm.px) : "memory");
      asm volatile("prefetch.tensormap [%0];" ::"l"((uint64_t)&tm.v6) : "memory");
      asm volatile("prefetch.tensormap [%0];" ::"l"((uint64_t)&tm.v2) : "memory");
      asm volatile("prefetch.tensormap [%0];" ::"l"((uint64_t)(tm.px + (blockIdx.x < 112 ? 5 : 6))) : "memory");
      asm volatile("prefetch.tensormap [%0];" ::"l"((uint64_t)(tm.px + 7)) : "memory");
      if (nt < 6) {
        asm volatile("prefetch.tensormap [%0];" ::"l"((uint64_t)(tm.px + 1)) : "memory");
        asm volatile("prefetch.tensormap [%0];" ::"l"((uint64_t)(tm.px + 2)) : "memory");
        asm volatile("prefetch.tensormap [%0];" ::"l"((uint64_t)&tm.v14) : "memory");
        asm volatile("prefetch.tensormap [%0];" ::"l"((uint64_t)&tm.u8) : "memory");
      }
      __nanosleep(NAT_TW2 - 2800);
      asm volatile("bar.sync 4, 64;" ::: "memory");
      w2o = w2_offset();
      if (elect_one()) {
        mbar_arrive_expect_tx(bar_w2a(bars), kWChunk);
        mbar_arrive_expect_tx(bar_w2(bars), kWChunk);
        wait_clock(t_start, NAT_TW2);
        bulk_load(sbase + kW2Off, wimg + w2o, kWChunk, bar_w2a(bars));
        mbar_wait(bar_xf(bars), 0);
        bulk_load(sbase + kW2Off + 2 * kWChunk, wimg + (w2o + 2 * kWChunk), kWChunk, bar_w2(bars));
      }
      __syncwarp();
      if (nt < 6) gather_px(x, sbase, decode_tile(tt, tile0 + 2));
      if (wqkv == nullptr) return;
      mbar_wait(bar_wok(bars), 0);
      if (lane == 0) asm volatile("red.relaxed.gpu.global.add.u32 [%0], 1;" ::"l"(g_flag) : "memory");
      if (blockIdx.x >= 48) return;
      if (lane == 0) {
        uint32_t v, it = 0;
        do {
          __nanosleep(2000);
          asm volatile("ld.relaxed.gpu.global.u32 %0, [%1];" : "=r"(v) : "l"(g_flag) : "memory");
        } while (v < gridDim.x && ++it < (1u << 16));
      }
      __syncwarp();
#pragma unroll
      for (int i = 0; i < 6; i++)
        stg128(wimg + ((i < 3 ? 0u : 3 * kWBytes - w2o) + blockIdx.x * 1536 + (i % 3) * 512 + lane * 16), kEmpty, kEmpty, kEmpty, kEmpty);
      if (lane == 0 && atomicAdd(g_flag + 32, 1u) == 47) {
        g_flag[0] = g_flag[32] = 0;
        g_flag[64] = w2o == kWBytes;
      }
      return;
    }
    if (!elect_one()) return;
    if (c == 0) {
      for (int i = 0; i < kNumBars; i++)
        if ((i != 0 && i != 10 || nt < 6) && (i != 21 || !w2cta)) mbar_init(bars + i * 8, i == 13 || i == 16 ? 4 : 1);
      asm volatile("st.shared.v2.u32 [%0], {%1,%1};" ::"r"(bars + 192), "r"(0) : "memory");
      asm volatile("fence.mbarrier_init.release.cluster;" ::: "memory");
      if (w2cta) asm volatile("bar.sync 10, 64;" ::: "memory");
      asm volatile("bar.arrive 0, 160;" ::: "memory");
      asm volatile("bar.arrive 14, 160;" ::: "memory");
      asm volatile("bar.arrive 13, 96;" ::: "memory");
      asm volatile("bar.arrive 4, 64;" ::: "memory");
      const TileCoord tc0 = decode_tile(tt, tile0);
      const HaloCols hc = halo_cols(tc0);
      const int h0 = halo_r0(tc0);
#pragma unroll
      for (int j = 0; j < 3; j++)
        if (j > 0 || nt < 6) mbar_arrive_expect_tx(bar_full(bars, 0, j), 2 * kChunkBytes);
      wait_clock(t_start, NAT_HP);
#pragma unroll
      for (int q = 8; q < 24 && !w2cta; q += 8) {
        tma_prefetch_5d(blockIdx.x < 112 ? &tm.v6 : &tm.v14, 24 * tc0.pc + q, hc.vj, hc.vc, tc0.pr, h0 + (tc0.up || blockIdx.x >= 112 ? 0 : 8));
        tma_prefetch_5d(&tm.u8, 24 * tc0.pc + q, hc.uj, h0 + (tc0.up ? 0 : 6), tc0.pr, hc.uc);
      }
#pragma unroll 1
      for (int i = nt < 6 ? 0 : 2; i < 7; i++) {
        if (i == NAT_H0) mbar_wait(bar_w1q(bars), 0);
        if (i == NAT_X1P) mbar_arrive(bar_go(bars));
        if (i < 6) first_halo(tm, sbase, tc0, i);
      }
      w2o = w2_offset();
    } else {
      asm volatile("bar.sync 13, 96;" ::: "memory");
      if (c == 2) {
        if (wqkv != nullptr && blockIdx.x < 131) asm volatile("bar.sync 12, 64;" ::: "memory");
        const uint32_t c0 = clock();
        while ((uint32_t)clock() - c0 < NAT_TD && nt == 6) { }
        wait_clock(t_start, NAT_T0);
#pragma unroll
        for (int j = 0; j < 3; j++) {
          mbar_arrive_expect_tx(bar_w1c(bars, j), kWChunk);
          bulk_load(sbase + kW1Off + j * kWChunk, wimg + j * kWChunk, kWChunk, bar_w1c(bars, j));
        }
        mbar_arrive(bar_w1q(bars));
        GT(2);
      } else {
#pragma unroll 1
        for (int j = nt == 6; j < 2; j++) {
          const TileCoord tc = decode_tile(tt, tile0 + j);
          const int line = first_line(tc);
          if (j == 1) mbar_wait(bar_go(bars), 0);
          if (j == 0) GT(15);
#pragma unroll 1
          for (int q = 0; q < 3; q++) {
            load_px(tm, tt, sbase + x_chunk(j, q), bar_x(bars, j, q), line + q, tc.kind);
            if (j == 1 || q == 0) mbar_arrive_expect_tx(bar_x(bars, j, q), j ? 8192 : kWChunk);
          }
          if (j == 0) GT(16);
        }
        w2o = w2_offset();
        wait_clock(t_start, NAT_TW2);
        mbar_wait(bar_xf(bars), 0);
      }
    }
#pragma unroll 1
    for (int k = 1; k < nt; k++) {
      const TileCoord tn = decode_tile(tt, tile0 + k + 1);
      const int line = first_line(tn);
      const bool more = k + 1 < nt && (k > 1 || nt == 6);
      if (c == 1) {
#pragma unroll
        for (int q = 3 - NAT_MP; q < 3; q++) {
          const uint32_t n = q == 3 - NAT_MP ? q + 1 : 1, o = x_chunk(k, k & 1 ? q : q + 1 - n);
          nb_sync_p(q == 0 ? 0 : q == 1 ? 14 : 6);
          bulk_load(sbase + o, wimg + (w2o + o - kW2Off), n * 8192, bar_w2m(bars));
        }
        mbar_arrive_expect_tx(bar_w2m(bars), kWChunk);
      }
      if (c == 2) {
        if (k == 1) wait_clock(t_start, NAT_TX2);
        else __nanosleep(NAT_PFD);
#pragma unroll 1
        for (int q = 0; q < 3 && more; q++) load_px(tm, tt, 0, 0, line + q, tn.kind);
      }
      if (c == 2 && (blockIdx.x >= 112 || k == 5)) {
        const TileCoord tc = decode_tile(tt, tile0 + k);
        const HaloCols hc = halo_cols(tc);
        const int h8 = halo_r0(tc) + (tc.up ? 0 : 6);
#pragma unroll 1
        for (int q = 0; q < 24; q += 8) {
          tma_prefetch_5d(&tm.v6, 24 * tc.pc + q, hc.vj, hc.vc, tc.pr, h8);
          tma_prefetch_5d(&tm.v2, 24 * tc.pc + q, hc.vj, hc.vc, tc.pr, h8 + 6);
          tma_prefetch_5d(&tm.u8, 24 * tc.pc + q, hc.uj, h8, tc.pr, hc.uc);
        }
      }
      load_halo(tm, sbase, bars, decode_tile(tt, tile0 + k), k, c);
      if (c == 0 && more) {
#pragma unroll
        for (int q = 0; q < 3; q++) {
          if (q < 2) nb_sync_p(q ? 5 : 13);
          load_px(tm, tt, sbase + x_chunk(k + 1, q), bar_x(bars, 1, q), line + q, tn.kind);
          if (q != 1) mbar_arrive_expect_tx(bar_x(bars, 1, q), 8192);
        }
        mbar_arrive_expect_tx(bar_x(bars, 1, 1), 8192);
        PROFS(16, 2, k * 4 + 3);
      }
      if (c == 0 && k >= 2) {
        const TileCoord tp = decode_tile(tt, tile0 + k - 2);
        const int lp = first_line(tp);
        nb_sync_p(10);
        __nanosleep(NAT_XW);
        store_px(tm, tt, sbase + out_slot(k, nt), lp, tp.kind);
        if (k + 1 < nt) {
          asm volatile("cp.async.bulk.wait_group.read 0;" ::: "memory");
          bulk_load(sbase + out_slot(k, nt), wimg + (w2o + out_slot(k, nt) - kW2Off), kWChunk, bar_w2(bars));
          mbar_arrive_expect_tx(bar_w2(bars), kWChunk);
        }
      }
    }
    asm volatile("cp.async.bulk.wait_group 0;" ::: "memory");
  } else {
    if (blockIdx.x < 128) {
      if ((wid == 4 || (wid == 5 && blockIdx.x - 2 < 16)) && wqkv != nullptr) {
        fold_w1(blockIdx.x - 2 < 16 ? 2 * blockIdx.x + wid - 6 : blockIdx.x + (blockIdx.x < 2 ? 0 : 16), wqkv, wimg);
        if (wid == 4) asm volatile("bar.arrive 12, 64;" ::: "memory");
        if (tid == 128) GT(7);
      }
      sched_fence();
      if (wid == 1 && elect_one()) {
        const TileCoord tc = decode_tile(tt, blockIdx.x * kTilesPerCta);
        mbar_init(bar_x(bars, 0, 0), 1);
        asm volatile("fence.mbarrier_init.release.cluster;" ::: "memory");
        mbar_arrive_expect_tx(bar_x(bars, 0, 0), kWChunk);
        GT(15);
#pragma unroll 1
        for (int q = 0; q < 3; q++) load_px(tm, tt, sbase + x_chunk(0, q), bar_x(bars, 0, 0), first_line(tc) + q, tc.kind);
        GT(16);
      }
      __syncwarp();
      sched_fence();
      if (wid == 2 && elect_one()) {
        const TileCoord tc = decode_tile(tt, blockIdx.x * kTilesPerCta);
        mbar_init(bar_full(bars, 0, 0), 1);
        asm volatile("fence.mbarrier_init.release.cluster;" ::: "memory");
        mbar_arrive_expect_tx(bar_full(bars, 0, 0), 2 * kChunkBytes);
        if (NAT_TH) wait_clock(t_start, NAT_TH);
        asm volatile("prefetch.tensormap [%0];" ::"l"((uint64_t)&tm.u8) : "memory");
        GT(17);
        first_halo(tm, sbase, tc, 0);
        first_halo(tm, sbase, tc, 1);
      }
      __syncwarp();
    }
    sched_fence();
    {
      if (w2cta) {
        const int q = blockIdx.x & 3;
        uint32_t w2o = 0;
        if (wid == 1 && elect_one()) {
          asm volatile("prefetch.tensormap [%0];" ::"l"((uint64_t)&tm.wo) : "memory");
#pragma unroll
          for (int j = 0; j < 3; j++) mbar_init(bar_raw(bars, j), 1);
          asm volatile("fence.mbarrier_init.release.cluster;" ::: "memory");
#pragma unroll
          for (int j = 0; j < 6; j++)
            asm volatile("cp.async.bulk.tensor.2d.shared::cluster.global.tile.mbarrier::complete_tx::bytes [%0], [%1, {%3, %4}], [%2];" ::"r"(
                             j < 3 ? sbase + j * 8192 : sbase + kW2Off + (j - 3) * kWChunk),
                         "l"((uint64_t)(j < 3 ? &tm.wv : &tm.wo)), "r"(bar_raw(bars, j < 3 ? 0 : j - 3)),
                         "r"(j < 3 ? 384 + 64 * j : 64 * (j - 3)), "r"(j < 3 ? 64 * q : 0) : "memory");
#pragma unroll
          for (int j = 0; j < 3; j++) mbar_arrive_expect_tx(bar_raw(bars, j), j ? kWChunk : 2 * kWChunk);
          w2o = w2_offset();
        }
        __syncwarp();
#pragma unroll 1
        for (int r = 0; r < 3; r++) {
          const int blk = 2 * r - 2 + (wid >> 2);
          if (blk < 3) {
            if (r > 0) {
              mbar_wait(bar_raw(bars, 0), 0);
              mbar_wait(bar_raw(bars, blk), 0);
            }
            if (tid == 0 && r == 1) GT(7);
            float acc[32];
            const uint64_t db = make_desc(sbase + kW2Off + max(blk, 0) * kWChunk, kWChunk, 1024);
            wg_fence();
            wg_m64tz<0, 32>(acc, make_desc(sbase, 16, 1024), db, 0);
#pragma unroll
            for (int s = 1; s < 12; s++) wg_m64t<0, 32>(acc, make_desc(sbase + (s >> 2) * 8192 + (s & 3) * 32, 16, 1024), db + s * 128, 1);
            wg_commit();
            wg_wait<0>();
            fence_regs(acc);
            if (tid == 0) GT(19);
            const int m = (tid >> 3) & 3;
#pragma unroll
            for (int j = 0; j < 8; j += 2) {
              const int n = g2_inv(8 * (j + (m >> 1)) + (tid & 7));
              asm volatile("stmatrix.sync.aligned.m8n8.x4.trans.shared.b16 [%0], {%1,%2,%3,%4};" ::"r"(
                               sbase + kW1Off + (blk + 2) * 8192 + n * 128 + (((2 * (wid & 3) + (m & 1)) ^ (n & 7)) << 4)),
                           "r"(pack_bf16(acc[4 * j], acc[4 * j + 1])), "r"(pack_bf16(acc[4 * j + 2], acc[4 * j + 3])),
                           "r"(pack_bf16(acc[4 * j + 4], acc[4 * j + 5])), "r"(pack_bf16(acc[4 * j + 6], acc[4 * j + 7])) : "memory");
            }
            fence_proxy_async();
          }
          if (tid == 0) GT(18);
          asm volatile("bar.sync 11, 256;" ::: "memory");
          if (wid == 1 && elect_one()) {
            asm volatile("{\n.reg .pred p;\nsetp.ne.s32 p, %3, 0;\n@p cp.async.bulk.global.shared::cta.bulk_group [%0], [%1], %2;\n}\n" ::"l"(
                             wimg + (w2o + w2piece(r >> 1, q) * (kWChunk / 2))),
                         "r"(sbase + kW1Off + 16384 + (r >> 1) * (kWChunk / 2)), "r"(kWChunk / 2), "r"(r) : "memory");
            asm volatile("cp.async.bulk.commit_group;" ::: "memory");
          }
          __syncwarp();
        }
        if (wid == 1) {
          asm volatile("bar.arrive 10, 64;" ::: "memory");
          if (elect_one()) asm volatile("cp.async.bulk.wait_group.read 0;" ::: "memory");
          if (tid == 32) GT(31);
          __syncwarp();
          asm volatile("bar.arrive 12, 64;" ::: "memory");
        }
      }
    }
    __syncwarp();
    if (wid < 4) asm volatile("bar.sync 0, 160;" ::: "memory");
    else asm volatile("bar.sync 14, 160;" ::: "memory");
    asm volatile("setmaxnreg.inc.sync.aligned.u32 240;");
    consumer(wid >> 2, out, wimg, sbase, zero, tm, tt);
  }
}

}

typedef CUresult (*PFN_encodeTiled)(CUtensorMap*, CUtensorMapDataType, cuuint32_t, void*, const cuuint64_t*,
                                    const cuuint64_t*, const cuuint32_t*, const cuuint32_t*, CUtensorMapInterleave,
                                    CUtensorMapSwizzle, CUtensorMapL2promotion, CUtensorMapFloatOOBfill);

extern "C" void kernel_launch(void* const* d_in, const int* in_sizes, int n_in, void* d_out, int out_size) {
  const __nv_bfloat16* x = (const __nv_bfloat16*)d_in[0];
  const __nv_bfloat16* wqkv = (const __nv_bfloat16*)d_in[1];
  const __nv_bfloat16* wo = (const __nv_bfloat16*)d_in[2];
  __nv_bfloat16* out = (__nv_bfloat16*)d_out;

  static PFN_encodeTiled encode = nullptr;
  static int num_sms = 0;
  static uint8_t* wimg = nullptr;
  if (!encode) {
    void* fn = nullptr;
    cudaDriverEntryPointQueryResult qres;
    cudaGetDriverEntryPoint("cuTensorMapEncodeTiled", &fn, cudaEnableDefault, &qres);
    encode = (PFN_encodeTiled)fn;
    cudaFuncSetAttribute(nat::nat_kernel, cudaFuncAttributeMaxDynamicSharedMemorySize, nat::kSmemBytes);
    cudaGetSymbolAddress((void**)&wimg, nat::g_wimg32);
    int dev = 0;
    cudaGetDevice(&dev);
    cudaDeviceGetAttribute(&num_sms, cudaDevAttrMultiProcessorCount, dev);
  }
  nat::Maps tm;
  cuuint32_t estr[5] = {1, 1, 1, 1, 1};
  {
    cuuint64_t vdim[5] = {48, 2, 105, 2, 112}, udim[5] = {48, 2, 112, 2, 105};
    cuuint64_t vstr[4] = {7 * 768, 768, 224 * 384, 2 * 224 * 384}, ustr[4] = {7 * 768, 2 * 224 * 384, 224 * 384, 768};
    CUtensorMap* maps[4] = {&tm.v6, &tm.v2, &tm.v14, &tm.u8};
    for (int i = 0; i < 4; i++) {
      cuuint32_t box[5] = {4, 2, i < 3 ? 4u : 8u, 1, i == 0 ? 6u : i == 1 ? 2u : i == 2 ? 14u : 3u};
      encode(maps[i], CU_TENSOR_MAP_DATA_TYPE_UINT32, 5, (void*)x, i < 3 ? vdim : udim, i < 3 ? vstr : ustr, box, estr,
             CU_TENSOR_MAP_INTERLEAVE_16B, CU_TENSOR_MAP_SWIZZLE_128B, CU_TENSOR_MAP_L2_PROMOTION_L2_128B, CU_TENSOR_MAP_FLOAT_OOB_FILL_NONE);
    }
  }
  for (int i = 0; i < 8; i++) {
    const cuuint32_t row = 224 * 384;
    const cuuint32_t shape[8][6] = {{2, 8, 4, 2 * row, 768, 4 * row}, {2, 8, 3, row, 768, 2 * row},     {2, 8, 1, 2 * row, 768, 4 * row},
                                    {8, 2, 3, 2 * row, 4 * 384, 384}, {8, 2, 1, 2 * row, 5 * 384, 384}, {4, 2, 3, 4 * row, 2 * row, 128},
                                    {4, 2, 3, 768, row, 128},         {4, 2, 3, 768, 2 * row, 128}};
    const cuuint32_t* sh = shape[i];
    cuuint64_t dim[5] = {64, sh[0], sh[1], sh[2], 224 * 224 * 3};
    cuuint64_t str[4] = {sh[3], sh[4], sh[5], 128};
    cuuint32_t box[5] = {64, sh[0], sh[1], sh[2], 1};
    encode(tm.px + i, CU_TENSOR_MAP_DATA_TYPE_BFLOAT16, 5, i < 5 ? (void*)x : (void*)out, dim, str, box, estr, CU_TENSOR_MAP_INTERLEAVE_NONE,
           CU_TENSOR_MAP_SWIZZLE_128B, i < 5 ? CU_TENSOR_MAP_L2_PROMOTION_L2_128B : CU_TENSOR_MAP_L2_PROMOTION_NONE,
           CU_TENSOR_MAP_FLOAT_OOB_FILL_NONE);
  }
  for (int i = 0; i < 2; i++) {
    cuuint64_t dim[2] = {i ? 192u : 576u, 192}, str[1] = {i ? 384u : 1152u};
    cuuint32_t box[2] = {64, i ? 192u : 64u};
    encode(i ? &tm.wo : &tm.wv, CU_TENSOR_MAP_DATA_TYPE_BFLOAT16, 2, i ? (void*)wo : (void*)wqkv, dim, str, box, estr,
           CU_TENSOR_MAP_INTERLEAVE_NONE, CU_TENSOR_MAP_SWIZZLE_128B, CU_TENSOR_MAP_L2_PROMOTION_L2_256B, CU_TENSOR_MAP_FLOAT_OOB_FILL_NONE);
  }
  nat::TileTable tt;
  nat::make_tiles(tt);
  const int grid = nat::kCtas;
  if (num_sms >= grid) {
    nat::nat_kernel<<<grid, 384, nat::kSmemBytes>>>(x, out, wqkv, wo, wimg, 0u, tm, tt);
  } else {
    nat::fold_kernel<<<27, 256>>>(wqkv, wo, wimg);
    nat::nat_kernel<<<grid, 384, nat::kSmemBytes>>>(x, out, nullptr, nullptr, wimg, 0u, tm, tt);
  }
}
```

```cpp
#include <cuda_runtime.h>
#include <cuda_bf16.h>
#include <cuda.h>
#include <stdint.h>

#define NAT_P1 2
#define NAT_P2 4
#define NAT_H0 2
#define NAT_T0 2100
#define NAT_TD 1200
#define NAT_TW2 4650
#define NAT_TX2 3800
#define NAT_X1P 6
#define NAT_PK 3
#define NAT_HP 1800
#define NAT_PFD 400
#define NAT_XW 200
#define NAT_MP 3
#define NAT_D0 1
#define NAT_TH 0
#define NAT_TM 1300
#define NAT_QA 1
#define NAT_SB 0
namespace nat {

constexpr int kW = 224, kC = 192;
constexpr int kCtas = 132;
constexpr int kTilesPerCta = 6;
constexpr float kAlpha = 0.07216878364870322f * 1.4426950408889634f;
constexpr uint32_t kChunkBytes = 13 * 1024;
constexpr uint32_t kWChunk = 192 * 128;
constexpr uint32_t kWBytes = 3 * kWChunk;
constexpr uint32_t kW1Off = 6 * kChunkBytes;
constexpr uint32_t kW2Off = kW1Off + kWBytes;
constexpr uint32_t kXOff = kW2Off + kWChunk;
constexpr uint32_t kBarOff = kW2Off + kWBytes;
constexpr uint32_t kProfOff = kBarOff + 208;
constexpr uint32_t kSmemBytes = kBarOff + 1024;

static_assert(kW1Off % 1024 == 0 && kW2Off % 1024 == 0 && kChunkBytes % 1024 == 0, "swizzle alignment");
static_assert(kSmemBytes <= 232448, "smem");

constexpr uint32_t kEmpty = 0xFFFFFFFFu;
#define NAT_R8(v) v, v, v, v, v, v, v, v
#define NAT_R2K(v) NAT_R8(NAT_R8(NAT_R8(v))), NAT_R8(NAT_R8(NAT_R8(v))), NAT_R8(NAT_R8(NAT_R8(v))), NAT_R8(NAT_R8(NAT_R8(v)))
#define NAT_IMG NAT_R8(NAT_R2K(kEmpty)), NAT_R2K(kEmpty)
__device__ __align__(1024) uint32_t g_wimg32[3 * kWBytes / 4] = {NAT_IMG, NAT_IMG, NAT_IMG};
static_assert(kWBytes / 4 == 9 * 2048, "initialiser");
__device__ __align__(128) uint32_t g_flag[96];
__device__ __forceinline__ uint32_t w2_offset() {
  uint32_t v;
  asm volatile("ld.relaxed.gpu.global.u32 %0, [%1];" : "=r"(v) : "l"(g_flag + 64) : "memory");
  return (1 + v) * kWBytes;
}

#define PROFS(id, wgid, slotid) do { } while (0)
#define PROF(wgid, slotid) do { } while (0)
#define PROF_DUMP(wgid) do { } while (0)

#define GT(slotid) do { } while (0)
#define GT_DUMP() do { } while (0)

__device__ __forceinline__ uint32_t smem_u32(const void* p) { return (uint32_t)__cvta_generic_to_shared(p); }

__device__ __forceinline__ void mbar_init(uint32_t bar, uint32_t count) {
  asm volatile("mbarrier.init.shared::cta.b64 [%0], %1;" ::"r"(bar), "r"(count) : "memory");
}
__device__ __forceinline__ void mbar_arrive(uint32_t bar) {
  asm volatile("mbarrier.arrive.shared::cta.b64 _, [%0];" ::"r"(bar) : "memory");
}
__device__ __forceinline__ void mbar_arrive_expect_tx(uint32_t bar, uint32_t bytes) {
  asm volatile("mbarrier.arrive.expect_tx.shared::cta.b64 _, [%0], %1;" ::"r"(bar), "r"(bytes) : "memory");
}
__device__ __forceinline__ void mbar_wait(uint32_t bar, uint32_t parity) {
  uint32_t ok;
  uint32_t it = 0;
  do {
    asm volatile(
        "{\n.reg .pred p;\n"
        "mbarrier.try_wait.parity.shared::cta.b64 p, [%1], %2;\n"
        "selp.u32 %0, 1, 0, p;\n}\n"
        : "=r"(ok)
        : "r"(bar), "r"(parity)
        : "memory");
    if (++it > (1u << 24)) break;
  } while (!ok);
}
__device__ __forceinline__ uint32_t mbar_test(uint32_t bar, uint32_t parity) {
  uint32_t ok;
  asm volatile("{\n.reg .pred p;\nmbarrier.test_wait.parity.shared::cta.b64 p, [%1], %2;\nselp.u32 %0, 1, 0, p;\n}\n"
               : "=r"(ok) : "r"(bar), "r"(parity) : "memory");
  return ok;
}
__device__ __forceinline__ void mbar_wait_if(uint32_t ok, uint32_t bar, uint32_t parity) {
  if (!__all_sync(0xffffffffu, ok)) mbar_wait(bar, parity);
}
__device__ __forceinline__ bool elect_one() {
  uint32_t r;
  asm volatile("{\n.reg .pred p;\nelect.sync _|p, 0xffffffff;\nselp.u32 %0, 1, 0, p;\n}\n" : "=r"(r));
  return r != 0;
}
__device__ __forceinline__ void nb_arrive(int id) { asm volatile("bar.arrive %0, 256;" ::"r"(id) : "memory"); }
__device__ __forceinline__ void nb_sync(int id) { asm volatile("bar.sync %0, 256;" ::"r"(id) : "memory"); }
__device__ __forceinline__ void nb_arrive_p(int id) { asm volatile("bar.arrive %0, 160;" ::"r"(id) : "memory"); }
__device__ __forceinline__ void nb_sync_p(int id) { asm volatile("bar.sync %0, 160;" ::"r"(id) : "memory"); }
__device__ __forceinline__ void fence_proxy_async() { asm volatile("fence.proxy.async.shared::cta;" ::: "memory"); }

__device__ __forceinline__ void tma_load_5d(uint32_t dst, const CUtensorMap* map, uint32_t bar, int c0, int c1, int c2,
                                            int c3, int c4) {
  asm volatile(
      "cp.async.bulk.tensor.5d.shared::cluster.global.tile.mbarrier::complete_tx::bytes "
      "[%0], [%1, {%3, %4, %5, %6, %7}], [%2];"
      ::"r"(dst), "l"((uint64_t)map), "r"(bar), "r"(c0), "r"(c1), "r"(c2), "r"(c3), "r"(c4)
      : "memory");
}
__device__ __forceinline__ void bulk_load(uint32_t dst, const void* src, uint32_t bytes, uint32_t bar) {
  asm volatile("cp.async.bulk.shared::cluster.global.mbarrier::complete_tx::bytes [%0], [%1], %2, [%3];"
               ::"r"(dst), "l"((uint64_t)src), "r"(bytes), "r"(bar)
               : "memory");
}

__device__ __forceinline__ void wg_fence() { asm volatile("wgmma.fence.sync.aligned;" ::: "memory"); }
__device__ __forceinline__ void wg_commit() { asm volatile("wgmma.commit_group.sync.aligned;" ::: "memory"); }
template <int N>
__device__ __forceinline__ void wg_wait() { asm volatile("wgmma.wait_group.sync.aligned %0;" ::"n"(N) : "memory"); }

template <int N>
__device__ __forceinline__ void fence_regs(float (&d)[N]) {
#pragma unroll
  for (int i = 0; i < N; i++) asm volatile("" : "+f"(d[i])::"memory");
}
template <int N>
__device__ __forceinline__ void keep_regs(uint32_t (&d)[N]) {
#pragma unroll
  for (int i = 0; i < N; i++) asm volatile("" : "+r"(d[i])::"memory");
}

__device__ __forceinline__ uint32_t pack_bf16(float lo, float hi) {
  uint32_t d;
  asm("cvt.rn.bf16x2.f32 %0, %1, %2;" : "=r"(d) : "f"(hi), "f"(lo));
  return d;
}
__device__ __forceinline__ float ex2(float x) {
  float y;
  asm("ex2.approx.ftz.f32 %0, %1;" : "=f"(y) : "f"(x));
  return y;
}
__device__ __forceinline__ float rcp_approx(float x) {
  float y;
  asm("rcp.approx.ftz.f32 %0, %1;" : "=f"(y) : "f"(x));
  return y;
}
__device__ __forceinline__ uint4 ldg128_nc(const void* p) {
  uint4 v;
  asm volatile("ld.global.nc.v4.u32 {%0,%1,%2,%3}, [%4];" : "=r"(v.x), "=r"(v.y), "=r"(v.z), "=r"(v.w) : "l"(p));
  return v;
}
__device__ __forceinline__ void stg128(void* p, uint32_t a, uint32_t b, uint32_t c, uint32_t d) {
  asm volatile("st.global.v4.u32 [%0], {%1,%2,%3,%4};" ::"l"(p), "r"(a), "r"(b), "r"(c), "r"(d) : "memory");
}

__device__ __forceinline__ long long clk64() {
  long long c;
  asm volatile("mov.u64 %0, %clock64;" : "=l"(c)::"memory");
  return c;
}
__device__ __forceinline__ void sched_fence() { while (clk64() < 0) { } }

__device__ __forceinline__ uint64_t make_desc(uint32_t addr, uint32_t lbo, uint32_t sbo, uint32_t mode = 1) {
  return (uint64_t)((addr & 0x3FFFF) >> 4) | ((uint64_t)(lbo >> 4) << 16) | ((uint64_t)(sbo >> 4) << 32) |
         ((uint64_t)mode << 62);
}

template <int OFF, int NN>
__device__ __forceinline__ void wg_m192(float (&d)[NN], uint64_t desc_a, uint64_t desc_b, int scale_d) {
  asm volatile(
      "{\n.reg .pred p;\nsetp.ne.b32 p, %98, 0;\n"
      "wgmma.mma_async.sync.aligned.m64n192k16.f32.bf16.bf16 "
      "{%0,%1,%2,%3,%4,%5,%6,%7,%8,%9,%10,%11,%12,%13,%14,%15,"
      "%16,%17,%18,%19,%20,%21,%22,%23,%24,%25,%26,%27,%28,%29,%30,%31,"
      "%32,%33,%34,%35,%36,%37,%38,%39,%40,%41,%42,%43,%44,%45,%46,%47,"
      "%48,%49,%50,%51,%52,%53,%54,%55,%56,%57,%58,%59,%60,%61,%62,%63,"
      "%64,%65,%66,%67,%68,%69,%70,%71,%72,%73,%74,%75,%76,%77,%78,%79,"
      "%80,%81,%82,%83,%84,%85,%86,%87,%88,%89,%90,%91,%92,%93,%94,%95}, "
      "%96, %97, p, 1, 1, 0, 0;\n}\n"
      : "+f"(d[OFF + 0]), "+f"(d[OFF + 1]), "+f"(d[OFF + 2]), "+f"(d[OFF + 3]), "+f"(d[OFF + 4]), "+f"(d[OFF + 5]),
        "+f"(d[OFF + 6]), "+f"(d[OFF + 7]), "+f"(d[OFF + 8]), "+f"(d[OFF + 9]), "+f"(d[OFF + 10]), "+f"(d[OFF + 11]),
        "+f"(d[OFF + 12]), "+f"(d[OFF + 13]), "+f"(d[OFF + 14]), "+f"(d[OFF + 15]), "+f"(d[OFF + 16]), "+f"(d[OFF + 17]),
        "+f"(d[OFF + 18]), "+f"(d[OFF + 19]), "+f"(d[OFF + 20]), "+f"(d[OFF + 21]), "+f"(d[OFF + 22]), "+f"(d[OFF + 23]),
        "+f"(d[OFF + 24]), "+f"(d[OFF + 25]), "+f"(d[OFF + 26]), "+f"(d[OFF + 27]), "+f"(d[OFF + 28]), "+f"(d[OFF + 29]),
        "+f"(d[OFF + 30]), "+f"(d[OFF + 31]), "+f"(d[OFF + 32]), "+f"(d[OFF + 33]), "+f"(d[OFF + 34]), "+f"(d[OFF + 35]),
        "+f"(d[OFF + 36]), "+f"(d[OFF + 37]), "+f"(d[OFF + 38]), "+f"(d[OFF + 39]), "+f"(d[OFF + 40]), "+f"(d[OFF + 41]),
        "+f"(d[OFF + 42]), "+f"(d[OFF + 43]), "+f"(d[OFF + 44]), "+f"(d[OFF + 45]), "+f"(d[OFF + 46]), "+f"(d[OFF + 47]),
        "+f"(d[OFF + 48]), "+f"(d[OFF + 49]), "+f"(d[OFF + 50]), "+f"(d[OFF + 51]), "+f"(d[OFF + 52]), "+f"(d[OFF + 53]),
        "+f"(d[OFF + 54]), "+f"(d[OFF + 55]), "+f"(d[OFF + 56]), "+f"(d[OFF + 57]), "+f"(d[OFF + 58]), "+f"(d[OFF + 59]),
        "+f"(d[OFF + 60]), "+f"(d[OFF + 61]), "+f"(d[OFF + 62]), "+f"(d[OFF + 63]), "+f"(d[OFF + 64]), "+f"(d[OFF + 65]),
        "+f"(d[OFF + 66]), "+f"(d[OFF + 67]), "+f"(d[OFF + 68]), "+f"(d[OFF + 69]), "+f"(d[OFF + 70]), "+f"(d[OFF + 71]),
        "+f"(d[OFF + 72]), "+f"(d[OFF + 73]), "+f"(d[OFF + 74]), "+f"(d[OFF + 75]), "+f"(d[OFF + 76]), "+f"(d[OFF + 77]),
        "+f"(d[OFF + 78]), "+f"(d[OFF + 79]), "+f"(d[OFF + 80]), "+f"(d[OFF + 81]), "+f"(d[OFF + 82]), "+f"(d[OFF + 83]),
        "+f"(d[OFF + 84]), "+f"(d[OFF + 85]), "+f"(d[OFF + 86]), "+f"(d[OFF + 87]), "+f"(d[OFF + 88]), "+f"(d[OFF + 89]),
        "+f"(d[OFF + 90]), "+f"(d[OFF + 91]), "+f"(d[OFF + 92]), "+f"(d[OFF + 93]), "+f"(d[OFF + 94]), "+f"(d[OFF + 95])
      : "l"(desc_a), "l"(desc_b), "r"(scale_d));
}

template <int OFF, int NN>
__device__ __forceinline__ void wg_m192z(float (&d)[NN], uint64_t desc_a, uint64_t desc_b, int scale_d) {
  asm volatile(
      "{\n.reg .pred p;\nsetp.ne.b32 p, %98, 0;\n"
      "wgmma.mma_async.sync.aligned.m64n192k16.f32.bf16.bf16 "
      "{%0,%1,%2,%3,%4,%5,%6,%7,%8,%9,%10,%11,%12,%13,%14,%15,"
      "%16,%17,%18,%19,%20,%21,%22,%23,%24,%25,%26,%27,%28,%29,%30,%31,"
      "%32,%33,%34,%35,%36,%37,%38,%39,%40,%41,%42,%43,%44,%45,%46,%47,"
      "%48,%49,%50,%51,%52,%53,%54,%55,%56,%57,%58,%59,%60,%61,%62,%63,"
      "%64,%65,%66,%67,%68,%69,%70,%71,%72,%73,%74,%75,%76,%77,%78,%79,"
      "%80,%81,%82,%83,%84,%85,%86,%87,%88,%89,%90,%91,%92,%93,%94,%95}, "
      "%96, %97, p, 1, 1, 0, 0;\n}\n"
      : "=f"(d[OFF + 0]), "=f"(d[OFF + 1]), "=f"(d[OFF + 2]), "=f"(d[OFF + 3]), "=f"(d[OFF + 4]), "=f"(d[OFF + 5]),
        "=f"(d[OFF + 6]), "=f"(d[OFF + 7]), "=f"(d[OFF + 8]), "=f"(d[OFF + 9]), "=f"(d[OFF + 10]), "=f"(d[OFF + 11]),
        "=f"(d[OFF + 12]), "=f"(d[OFF + 13]), "=f"(d[OFF + 14]), "=f"(d[OFF + 15]), "=f"(d[OFF + 16]), "=f"(d[OFF + 17]),
        "=f"(d[OFF + 18]), "=f"(d[OFF + 19]), "=f"(d[OFF + 20]), "=f"(d[OFF + 21]), "=f"(d[OFF + 22]), "=f"(d[OFF + 23]),
        "=f"(d[OFF + 24]), "=f"(d[OFF + 25]), "=f"(d[OFF + 26]), "=f"(d[OFF + 27]), "=f"(d[OFF + 28]), "=f"(d[OFF + 29]),
        "=f"(d[OFF + 30]), "=f"(d[OFF + 31]), "=f"(d[OFF + 32]), "=f"(d[OFF + 33]), "=f"(d[OFF + 34]), "=f"(d[OFF + 35]),
        "=f"(d[OFF + 36]), "=f"(d[OFF + 37]), "=f"(d[OFF + 38]), "=f"(d[OFF + 39]), "=f"(d[OFF + 40]), "=f"(d[OFF + 41]),
        "=f"(d[OFF + 42]), "=f"(d[OFF + 43]), "=f"(d[OFF + 44]), "=f"(d[OFF + 45]), "=f"(d[OFF + 46]), "=f"(d[OFF + 47]),
        "=f"(d[OFF + 48]), "=f"(d[OFF + 49]), "=f"(d[OFF + 50]), "=f"(d[OFF + 51]), "=f"(d[OFF + 52]), "=f"(d[OFF + 53]),
        "=f"(d[OFF + 54]), "=f"(d[OFF + 55]), "=f"(d[OFF + 56]), "=f"(d[OFF + 57]), "=f"(d[OFF + 58]), "=f"(d[OFF + 59]),
        "=f"(d[OFF + 60]), "=f"(d[OFF + 61]), "=f"(d[OFF + 62]), "=f"(d[OFF + 63]), "=f"(d[OFF + 64]), "=f"(d[OFF + 65]),
        "=f"(d[OFF + 66]), "=f"(d[OFF + 67]), "=f"(d[OFF + 68]), "=f"(d[OFF + 69]), "=f"(d[OFF + 70]), "=f"(d[OFF + 71]),
        "=f"(d[OFF + 72]), "=f"(d[OFF + 73]), "=f"(d[OFF + 74]), "=f"(d[OFF + 75]), "=f"(d[OFF + 76]), "=f"(d[OFF + 77]),
        "=f"(d[OFF + 78]), "=f"(d[OFF + 79]), "=f"(d[OFF + 80]), "=f"(d[OFF + 81]), "=f"(d[OFF + 82]), "=f"(d[OFF + 83]),
        "=f"(d[OFF + 84]), "=f"(d[OFF + 85]), "=f"(d[OFF + 86]), "=f"(d[OFF + 87]), "=f"(d[OFF + 88]), "=f"(d[OFF + 89]),
        "=f"(d[OFF + 90]), "=f"(d[OFF + 91]), "=f"(d[OFF + 92]), "=f"(d[OFF + 93]), "=f"(d[OFF + 94]), "=f"(d[OFF + 95])
      : "l"(desc_a), "l"(desc_b), "r"(scale_d));
}

template <int OFF, int NN>
__device__ __forceinline__ void wg_m64t(float (&d)[NN], uint64_t desc_a, uint64_t desc_b, int scale_d) {
  asm volatile(
      "{\n.reg .pred p;\nsetp.ne.b32 p, %34, 0;\n"
      "wgmma.mma_async.sync.aligned.m64n64k16.f32.bf16.bf16 "
      "{%0,%1,%2,%3,%4,%5,%6,%7,%8,%9,%10,%11,%12,%13,%14,%15,"
      "%16,%17,%18,%19,%20,%21,%22,%23,%24,%25,%26,%27,%28,%29,%30,%31}, "
      "%32, %33, p, 1, 1, 0, 1;\n}\n"
      : "+f"(d[OFF + 0]), "+f"(d[OFF + 1]), "+f"(d[OFF + 2]), "+f"(d[OFF + 3]), "+f"(d[OFF + 4]), "+f"(d[OFF + 5]),
        "+f"(d[OFF + 6]), "+f"(d[OFF + 7]), "+f"(d[OFF + 8]), "+f"(d[OFF + 9]), "+f"(d[OFF + 10]), "+f"(d[OFF + 11]),
        "+f"(d[OFF + 12]), "+f"(d[OFF + 13]), "+f"(d[OFF + 14]), "+f"(d[OFF + 15]), "+f"(d[OFF + 16]), "+f"(d[OFF + 17]),
        "+f"(d[OFF + 18]), "+f"(d[OFF + 19]), "+f"(d[OFF + 20]), "+f"(d[OFF + 21]), "+f"(d[OFF + 22]), "+f"(d[OFF + 23]),
        "+f"(d[OFF + 24]), "+f"(d[OFF + 25]), "+f"(d[OFF + 26]), "+f"(d[OFF + 27]), "+f"(d[OFF + 28]), "+f"(d[OFF + 29]),
        "+f"(d[OFF + 30]), "+f"(d[OFF + 31])
      : "l"(desc_a), "l"(desc_b), "r"(scale_d));
}

template <int OFF, int NN>
__device__ __forceinline__ void wg_m64tz(float (&d)[NN], uint64_t desc_a, uint64_t desc_b, int scale_d) {
  asm volatile(
      "{\n.reg .pred p;\nsetp.ne.b32 p, %34, 0;\n"
      "wgmma.mma_async.sync.aligned.m64n64k16.f32.bf16.bf16 "
      "{%0,%1,%2,%3,%4,%5,%6,%7,%8,%9,%10,%11,%12,%13,%14,%15,"
      "%16,%17,%18,%19,%20,%21,%22,%23,%24,%25,%26,%27,%28,%29,%30,%31}, "
      "%32, %33, p, 1, 1, 0, 1;\n}\n"
      : "=f"(d[OFF + 0]), "=f"(d[OFF + 1]), "=f"(d[OFF + 2]), "=f"(d[OFF + 3]), "=f"(d[OFF + 4]), "=f"(d[OFF + 5]),
        "=f"(d[OFF + 6]), "=f"(d[OFF + 7]), "=f"(d[OFF + 8]), "=f"(d[OFF + 9]), "=f"(d[OFF + 10]), "=f"(d[OFF + 11]),
        "=f"(d[OFF + 12]), "=f"(d[OFF + 13]), "=f"(d[OFF + 14]), "=f"(d[OFF + 15]), "=f"(d[OFF + 16]), "=f"(d[OFF + 17]),
        "=f"(d[OFF + 18]), "=f"(d[OFF + 19]), "=f"(d[OFF + 20]), "=f"(d[OFF + 21]), "=f"(d[OFF + 22]), "=f"(d[OFF + 23]),
        "=f"(d[OFF + 24]), "=f"(d[OFF + 25]), "=f"(d[OFF + 26]), "=f"(d[OFF + 27]), "=f"(d[OFF + 28]), "=f"(d[OFF + 29]),
        "=f"(d[OFF + 30]), "=f"(d[OFF + 31])
      : "l"(desc_a), "l"(desc_b), "r"(scale_d));
}

template <int OFF, int NN>
__device__ __forceinline__ void wg_d96(float (&d)[NN], uint32_t a0, uint32_t a1, uint32_t a2, uint32_t a3,
                                       uint64_t desc_b, int scale_d) {
  asm volatile(
      "{\n.reg .pred p;\nsetp.ne.b32 p, %53, 0;\n"
      "wgmma.mma_async.sync.aligned.m64n96k16.f32.bf16.bf16 "
      "{%0,%1,%2,%3,%4,%5,%6,%7,%8,%9,%10,%11,%12,%13,%14,%15,"
      "%16,%17,%18,%19,%20,%21,%22,%23,%24,%25,%26,%27,%28,%29,%30,%31,"
      "%32,%33,%34,%35,%36,%37,%38,%39,%40,%41,%42,%43,%44,%45,%46,%47}, "
      "{%48,%49,%50,%51}, %52, p, 1, 1, 0;\n}\n"
      : "+f"(d[OFF + 0]), "+f"(d[OFF + 1]), "+f"(d[OFF + 2]), "+f"(d[OFF + 3]), "+f"(d[OFF + 4]), "+f"(d[OFF + 5]),
        "+f"(d[OFF + 6]), "+f"(d[OFF + 7]), "+f"(d[OFF + 8]), "+f"(d[OFF + 9]), "+f"(d[OFF + 10]), "+f"(d[OFF + 11]),
        "+f"(d[OFF + 12]), "+f"(d[OFF + 13]), "+f"(d[OFF + 14]), "+f"(d[OFF + 15]), "+f"(d[OFF + 16]), "+f"(d[OFF + 17]),
        "+f"(d[OFF + 18]), "+f"(d[OFF + 19]), "+f"(d[OFF + 20]), "+f"(d[OFF + 21]), "+f"(d[OFF + 22]), "+f"(d[OFF + 23]),
        "+f"(d[OFF + 24]), "+f"(d[OFF + 25]), "+f"(d[OFF + 26]), "+f"(d[OFF + 27]), "+f"(d[OFF + 28]), "+f"(d[OFF + 29]),
        "+f"(d[OFF + 30]), "+f"(d[OFF + 31]), "+f"(d[OFF + 32]), "+f"(d[OFF + 33]), "+f"(d[OFF + 34]), "+f"(d[OFF + 35]),
        "+f"(d[OFF + 36]), "+f"(d[OFF + 37]), "+f"(d[OFF + 38]), "+f"(d[OFF + 39]), "+f"(d[OFF + 40]), "+f"(d[OFF + 41]),
        "+f"(d[OFF + 42]), "+f"(d[OFF + 43]), "+f"(d[OFF + 44]), "+f"(d[OFF + 45]), "+f"(d[OFF + 46]), "+f"(d[OFF + 47])
      : "r"(a0), "r"(a1), "r"(a2), "r"(a3), "l"(desc_b), "r"(scale_d));
}

template <int OFF, int NN>
__device__ __forceinline__ void wg_d96z(float (&d)[NN], uint32_t a0, uint32_t a1, uint32_t a2, uint32_t a3,
                                       uint64_t desc_b, int scale_d) {
  asm volatile(
      "{\n.reg .pred p;\nsetp.ne.b32 p, %53, 0;\n"
      "wgmma.mma_async.sync.aligned.m64n96k16.f32.bf16.bf16 "
      "{%0,%1,%2,%3,%4,%5,%6,%7,%8,%9,%10,%11,%12,%13,%14,%15,"
      "%16,%17,%18,%19,%20,%21,%22,%23,%24,%25,%26,%27,%28,%29,%30,%31,"
      "%32,%33,%34,%35,%36,%37,%38,%39,%40,%41,%42,%43,%44,%45,%46,%47}, "
      "{%48,%49,%50,%51}, %52, p, 1, 1, 0;\n}\n"
      : "=f"(d[OFF + 0]), "=f"(d[OFF + 1]), "=f"(d[OFF + 2]), "=f"(d[OFF + 3]), "=f"(d[OFF + 4]), "=f"(d[OFF + 5]),
        "=f"(d[OFF + 6]), "=f"(d[OFF + 7]), "=f"(d[OFF + 8]), "=f"(d[OFF + 9]), "=f"(d[OFF + 10]), "=f"(d[OFF + 11]),
        "=f"(d[OFF + 12]), "=f"(d[OFF + 13]), "=f"(d[OFF + 14]), "=f"(d[OFF + 15]), "=f"(d[OFF + 16]), "=f"(d[OFF + 17]),
        "=f"(d[OFF + 18]), "=f"(d[OFF + 19]), "=f"(d[OFF + 20]), "=f"(d[OFF + 21]), "=f"(d[OFF + 22]), "=f"(d[OFF + 23]),
        "=f"(d[OFF + 24]), "=f"(d[OFF + 25]), "=f"(d[OFF + 26]), "=f"(d[OFF + 27]), "=f"(d[OFF + 28]), "=f"(d[OFF + 29]),
        "=f"(d[OFF + 30]), "=f"(d[OFF + 31]), "=f"(d[OFF + 32]), "=f"(d[OFF + 33]), "=f"(d[OFF + 34]), "=f"(d[OFF + 35]),
        "=f"(d[OFF + 36]), "=f"(d[OFF + 37]), "=f"(d[OFF + 38]), "=f"(d[OFF + 39]), "=f"(d[OFF + 40]), "=f"(d[OFF + 41]),
        "=f"(d[OFF + 42]), "=f"(d[OFF + 43]), "=f"(d[OFF + 44]), "=f"(d[OFF + 45]), "=f"(d[OFF + 46]), "=f"(d[OFF + 47])
      : "r"(a0), "r"(a1), "r"(a2), "r"(a3), "l"(desc_b), "r"(scale_d));
}

template <int OFF, int NN>
__device__ __forceinline__ void wg_s104(float (&d)[NN], uint32_t a0, uint32_t a1, uint32_t a2, uint32_t a3,
                                       uint64_t desc_b, int scale_d, uint32_t meta) {
  asm volatile(
      "{\n.reg .pred p;\nsetp.ne.b32 p, %57, 0;\n"
      "wgmma.mma_async.sp.sync.aligned.m64n104k32.f32.bf16.bf16 "
      "{%0,%1,%2,%3,%4,%5,%6,%7,%8,%9,%10,%11,%12,%13,%14,%15,"
      "%16,%17,%18,%19,%20,%21,%22,%23,%24,%25,%26,%27,%28,%29,%30,%31,"
      "%32,%33,%34,%35,%36,%37,%38,%39,%40,%41,%42,%43,%44,%45,%46,%47,"
      "%48,%49,%50,%51}, "
      "{%52,%53,%54,%55}, %56, %58, 0, p, 1, 1, 0;\n}\n"
      : "+f"(d[OFF + 0]), "+f"(d[OFF + 1]), "+f"(d[OFF + 2]), "+f"(d[OFF + 3]), "+f"(d[OFF + 4]), "+f"(d[OFF + 5]),
        "+f"(d[OFF + 6]), "+f"(d[OFF + 7]), "+f"(d[OFF + 8]), "+f"(d[OFF + 9]), "+f"(d[OFF + 10]), "+f"(d[OFF + 11]),
        "+f"(d[OFF + 12]), "+f"(d[OFF + 13]), "+f"(d[OFF + 14]), "+f"(d[OFF + 15]), "+f"(d[OFF + 16]), "+f"(d[OFF + 17]),
        "+f"(d[OFF + 18]), "+f"(d[OFF + 19]), "+f"(d[OFF + 20]), "+f"(d[OFF + 21]), "+f"(d[OFF + 22]), "+f"(d[OFF + 23]),
        "+f"(d[OFF + 24]), "+f"(d[OFF + 25]), "+f"(d[OFF + 26]), "+f"(d[OFF + 27]), "+f"(d[OFF + 28]), "+f"(d[OFF + 29]),
        "+f"(d[OFF + 30]), "+f"(d[OFF + 31]), "+f"(d[OFF + 32]), "+f"(d[OFF + 33]), "+f"(d[OFF + 34]), "+f"(d[OFF + 35]),
        "+f"(d[OFF + 36]), "+f"(d[OFF + 37]), "+f"(d[OFF + 38]), "+f"(d[OFF + 39]), "+f"(d[OFF + 40]), "+f"(d[OFF + 41]),
        "+f"(d[OFF + 42]), "+f"(d[OFF + 43]), "+f"(d[OFF + 44]), "+f"(d[OFF + 45]), "+f"(d[OFF + 46]), "+f"(d[OFF + 47]),
        "+f"(d[OFF + 48]), "+f"(d[OFF + 49]), "+f"(d[OFF + 50]), "+f"(d[OFF + 51])
      : "r"(a0), "r"(a1), "r"(a2), "r"(a3), "l"(desc_b), "r"(scale_d), "r"(meta));
}

template <int OFF, int NN>
__device__ __forceinline__ void wg_s104z(float (&d)[NN], uint32_t a0, uint32_t a1, uint32_t a2, uint32_t a3,
                                       uint64_t desc_b, int scale_d, uint32_t meta) {
  asm volatile(
      "{\n.reg .pred p;\nsetp.ne.b32 p, %57, 0;\n"
      "wgmma.mma_async.sp.sync.aligned.m64n104k32.f32.bf16.bf16 "
      "{%0,%1,%2,%3,%4,%5,%6,%7,%8,%9,%10,%11,%12,%13,%14,%15,"
      "%16,%17,%18,%19,%20,%21,%22,%23,%24,%25,%26,%27,%28,%29,%30,%31,"
      "%32,%33,%34,%35,%36,%37,%38,%39,%40,%41,%42,%43,%44,%45,%46,%47,"
      "%48,%49,%50,%51}, "
      "{%52,%53,%54,%55}, %56, %58, 0, p, 1, 1, 0;\n}\n"
      : "=f"(d[OFF + 0]), "=f"(d[OFF + 1]), "=f"(d[OFF + 2]), "=f"(d[OFF + 3]), "=f"(d[OFF + 4]), "=f"(d[OFF + 5]),
        "=f"(d[OFF + 6]), "=f"(d[OFF + 7]), "=f"(d[OFF + 8]), "=f"(d[OFF + 9]), "=f"(d[OFF + 10]), "=f"(d[OFF + 11]),
        "=f"(d[OFF + 12]), "=f"(d[OFF + 13]), "=f"(d[OFF + 14]), "=f"(d[OFF + 15]), "=f"(d[OFF + 16]), "=f"(d[OFF + 17]),
        "=f"(d[OFF + 18]), "=f"(d[OFF + 19]), "=f"(d[OFF + 20]), "=f"(d[OFF + 21]), "=f"(d[OFF + 22]), "=f"(d[OFF + 23]),
        "=f"(d[OFF + 24]), "=f"(d[OFF + 25]), "=f"(d[OFF + 26]), "=f"(d[OFF + 27]), "=f"(d[OFF + 28]), "=f"(d[OFF + 29]),
        "=f"(d[OFF + 30]), "=f"(d[OFF + 31]), "=f"(d[OFF + 32]), "=f"(d[OFF + 33]), "=f"(d[OFF + 34]), "=f"(d[OFF + 35]),
        "=f"(d[OFF + 36]), "=f"(d[OFF + 37]), "=f"(d[OFF + 38]), "=f"(d[OFF + 39]), "=f"(d[OFF + 40]), "=f"(d[OFF + 41]),
        "=f"(d[OFF + 42]), "=f"(d[OFF + 43]), "=f"(d[OFF + 44]), "=f"(d[OFF + 45]), "=f"(d[OFF + 46]), "=f"(d[OFF + 47]),
        "=f"(d[OFF + 48]), "=f"(d[OFF + 49]), "=f"(d[OFF + 50]), "=f"(d[OFF + 51])
      : "r"(a0), "r"(a1), "r"(a2), "r"(a3), "l"(desc_b), "r"(scale_d), "r"(meta));
}

template <int OFF, int NN>
__device__ __forceinline__ void wg_s48(float (&d)[NN], uint32_t a0, uint32_t a1, uint32_t a2, uint32_t a3,
                                       uint64_t desc_b, int scale_d, uint32_t meta) {
  asm volatile(
      "{\n.reg .pred p;\nsetp.ne.b32 p, %29, 0;\n"
      "wgmma.mma_async.sp.sync.aligned.m64n48k32.f32.bf16.bf16 "
      "{%0,%1,%2,%3,%4,%5,%6,%7,%8,%9,%10,%11,%12,%13,%14,%15,"
      "%16,%17,%18,%19,%20,%21,%22,%23}, "
      "{%24,%25,%26,%27}, %28, %30, 0, p, 1, 1, 0;\n}\n"
      : "+f"(d[OFF + 0]), "+f"(d[OFF + 1]), "+f"(d[OFF + 2]), "+f"(d[OFF + 3]), "+f"(d[OFF + 4]), "+f"(d[OFF + 5]),
        "+f"(d[OFF + 6]), "+f"(d[OFF + 7]), "+f"(d[OFF + 8]), "+f"(d[OFF + 9]), "+f"(d[OFF + 10]), "+f"(d[OFF + 11]),
        "+f"(d[OFF + 12]), "+f"(d[OFF + 13]), "+f"(d[OFF + 14]), "+f"(d[OFF + 15]), "+f"(d[OFF + 16]), "+f"(d[OFF + 17]),
        "+f"(d[OFF + 18]), "+f"(d[OFF + 19]), "+f"(d[OFF + 20]), "+f"(d[OFF + 21]), "+f"(d[OFF + 22]), "+f"(d[OFF + 23])
      : "r"(a0), "r"(a1), "r"(a2), "r"(a3), "l"(desc_b), "r"(scale_d), "r"(meta));
}

template <int OFF, int NN>
__device__ __forceinline__ void wg_s48z(float (&d)[NN], uint32_t a0, uint32_t a1, uint32_t a2, uint32_t a3,
                                       uint64_t desc_b, int scale_d, uint32_t meta) {
  asm volatile(
      "{\n.reg .pred p;\nsetp.ne.b32 p, %29, 0;\n"
      "wgmma.mma_async.sp.sync.aligned.m64n48k32.f32.bf16.bf16 "
      "{%0,%1,%2,%3,%4,%5,%6,%7,%8,%9,%10,%11,%12,%13,%14,%15,"
      "%16,%17,%18,%19,%20,%21,%22,%23}, "
      "{%24,%25,%26,%27}, %28, %30, 0, p, 1, 1, 0;\n}\n"
      : "=f"(d[OFF + 0]), "=f"(d[OFF + 1]), "=f"(d[OFF + 2]), "=f"(d[OFF + 3]), "=f"(d[OFF + 4]), "=f"(d[OFF + 5]),
        "=f"(d[OFF + 6]), "=f"(d[OFF + 7]), "=f"(d[OFF + 8]), "=f"(d[OFF + 9]), "=f"(d[OFF + 10]), "=f"(d[OFF + 11]),
        "=f"(d[OFF + 12]), "=f"(d[OFF + 13]), "=f"(d[OFF + 14]), "=f"(d[OFF + 15]), "=f"(d[OFF + 16]), "=f"(d[OFF + 17]),
        "=f"(d[OFF + 18]), "=f"(d[OFF + 19]), "=f"(d[OFF + 20]), "=f"(d[OFF + 21]), "=f"(d[OFF + 22]), "=f"(d[OFF + 23])
      : "r"(a0), "r"(a1), "r"(a2), "r"(a3), "l"(desc_b), "r"(scale_d), "r"(meta));
}

template <int OFF, int NN>
__device__ __forceinline__ void wg_s56(float (&d)[NN], uint32_t a0, uint32_t a1, uint32_t a2, uint32_t a3,
                                       uint64_t desc_b, int scale_d, uint32_t meta) {
  asm volatile(
      "{\n.reg .pred p;\nsetp.ne.b32 p, %33, 0;\n"
      "wgmma.mma_async.sp.sync.aligned.m64n56k32.f32.bf16.bf16 "
      "{%0,%1,%2,%3,%4,%5,%6,%7,%8,%9,%10,%11,%12,%13,%14,%15,"
      "%16,%17,%18,%19,%20,%21,%22,%23,%24,%25,%26,%27}, "
      "{%28,%29,%30,%31}, %32, %34, 0, p, 1, 1, 0;\n}\n"
      : "+f"(d[OFF + 0]), "+f"(d[OFF + 1]), "+f"(d[OFF + 2]), "+f"(d[OFF + 3]), "+f"(d[OFF + 4]), "+f"(d[OFF + 5]),
        "+f"(d[OFF + 6]), "+f"(d[OFF + 7]), "+f"(d[OFF + 8]), "+f"(d[OFF + 9]), "+f"(d[OFF + 10]), "+f"(d[OFF + 11]),
        "+f"(d[OFF + 12]), "+f"(d[OFF + 13]), "+f"(d[OFF + 14]), "+f"(d[OFF + 15]), "+f"(d[OFF + 16]), "+f"(d[OFF + 17]),
        "+f"(d[OFF + 18]), "+f"(d[OFF + 19]), "+f"(d[OFF + 20]), "+f"(d[OFF + 21]), "+f"(d[OFF + 22]), "+f"(d[OFF + 23]),
        "+f"(d[OFF + 24]), "+f"(d[OFF + 25]), "+f"(d[OFF + 26]), "+f"(d[OFF + 27])
      : "r"(a0), "r"(a1), "r"(a2), "r"(a3), "l"(desc_b), "r"(scale_d), "r"(meta));
}

template <int OFF, int NN>
__device__ __forceinline__ void wg_s56z(float (&d)[NN], uint32_t a0, uint32_t a1, uint32_t a2, uint32_t a3,
                                       uint64_t desc_b, int scale_d, uint32_t meta) {
  asm volatile(
      "{\n.reg .pred p;\nsetp.ne.b32 p, %33, 0;\n"
      "wgmma.mma_async.sp.sync.aligned.m64n56k32.f32.bf16.bf16 "
      "{%0,%1,%2,%3,%4,%5,%6,%7,%8,%9,%10,%11,%12,%13,%14,%15,"
      "%16,%17,%18,%19,%20,%21,%22,%23,%24,%25,%26,%27}, "
      "{%28,%29,%30,%31}, %32, %34, 0, p, 1, 1, 0;\n}\n"
      : "=f"(d[OFF + 0]), "=f"(d[OFF + 1]), "=f"(d[OFF + 2]), "=f"(d[OFF + 3]), "=f"(d[OFF + 4]), "=f"(d[OFF + 5]),
        "=f"(d[OFF + 6]), "=f"(d[OFF + 7]), "=f"(d[OFF + 8]), "=f"(d[OFF + 9]), "=f"(d[OFF + 10]), "=f"(d[OFF + 11]),
        "=f"(d[OFF + 12]), "=f"(d[OFF + 13]), "=f"(d[OFF + 14]), "=f"(d[OFF + 15]), "=f"(d[OFF + 16]), "=f"(d[OFF + 17]),
        "=f"(d[OFF + 18]), "=f"(d[OFF + 19]), "=f"(d[OFF + 20]), "=f"(d[OFF + 21]), "=f"(d[OFF + 22]), "=f"(d[OFF + 23]),
        "=f"(d[OFF + 24]), "=f"(d[OFF + 25]), "=f"(d[OFF + 26]), "=f"(d[OFF + 27])
      : "r"(a0), "r"(a1), "r"(a2), "r"(a3), "l"(desc_b), "r"(scale_d), "r"(meta));
}

template <int OFF, int NN>
__device__ __forceinline__ void wg_s64t(float (&d)[NN], uint32_t a0, uint32_t a1, uint32_t a2, uint32_t a3,
                                       uint64_t desc_b, int scale_d, uint32_t meta) {
  asm volatile(
      "{\n.reg .pred p;\nsetp.ne.b32 p, %37, 0;\n"
      "wgmma.mma_async.sp.sync.aligned.m64n64k32.f32.bf16.bf16 "
      "{%0,%1,%2,%3,%4,%5,%6,%7,%8,%9,%10,%11,%12,%13,%14,%15,"
      "%16,%17,%18,%19,%20,%21,%22,%23,%24,%25,%26,%27,%28,%29,%30,%31}, "
      "{%32,%33,%34,%35}, %36, %38, 0, p, 1, 1, 1;\n}\n"
      : "+f"(d[OFF + 0]), "+f"(d[OFF + 1]), "+f"(d[OFF + 2]), "+f"(d[OFF + 3]), "+f"(d[OFF + 4]), "+f"(d[OFF + 5]),
        "+f"(d[OFF + 6]), "+f"(d[OFF + 7]), "+f"(d[OFF + 8]), "+f"(d[OFF + 9]), "+f"(d[OFF + 10]), "+f"(d[OFF + 11]),
        "+f"(d[OFF + 12]), "+f"(d[OFF + 13]), "+f"(d[OFF + 14]), "+f"(d[OFF + 15]), "+f"(d[OFF + 16]), "+f"(d[OFF + 17]),
        "+f"(d[OFF + 18]), "+f"(d[OFF + 19]), "+f"(d[OFF + 20]), "+f"(d[OFF + 21]), "+f"(d[OFF + 22]), "+f"(d[OFF + 23]),
        "+f"(d[OFF + 24]), "+f"(d[OFF + 25]), "+f"(d[OFF + 26]), "+f"(d[OFF + 27]), "+f"(d[OFF + 28]), "+f"(d[OFF + 29]),
        "+f"(d[OFF + 30]), "+f"(d[OFF + 31])
      : "r"(a0), "r"(a1), "r"(a2), "r"(a3), "l"(desc_b), "r"(scale_d), "r"(meta));
}

template <int OFF, int NN>
__device__ __forceinline__ void wg_s64t1(float (&d)[NN], uint32_t a0, uint32_t a1, uint32_t a2, uint32_t a3,
                                       uint64_t desc_b, int scale_d, uint32_t meta) {
  asm volatile(
      "{\n.reg .pred p;\nsetp.ne.b32 p, %37, 0;\n"
      "wgmma.mma_async.sp.sync.aligned.m64n64k32.f32.bf16.bf16 "
      "{%0,%1,%2,%3,%4,%5,%6,%7,%8,%9,%10,%11,%12,%13,%14,%15,"
      "%16,%17,%18,%19,%20,%21,%22,%23,%24,%25,%26,%27,%28,%29,%30,%31}, "
      "{%32,%33,%34,%35}, %36, %38, 1, p, 1, 1, 1;\n}\n"
      : "+f"(d[OFF + 0]), "+f"(d[OFF + 1]), "+f"(d[OFF + 2]), "+f"(d[OFF + 3]), "+f"(d[OFF + 4]), "+f"(d[OFF + 5]),
        "+f"(d[OFF + 6]), "+f"(d[OFF + 7]), "+f"(d[OFF + 8]), "+f"(d[OFF + 9]), "+f"(d[OFF + 10]), "+f"(d[OFF + 11]),
        "+f"(d[OFF + 12]), "+f"(d[OFF + 13]), "+f"(d[OFF + 14]), "+f"(d[OFF + 15]), "+f"(d[OFF + 16]), "+f"(d[OFF + 17]),
        "+f"(d[OFF + 18]), "+f"(d[OFF + 19]), "+f"(d[OFF + 20]), "+f"(d[OFF + 21]), "+f"(d[OFF + 22]), "+f"(d[OFF + 23]),
        "+f"(d[OFF + 24]), "+f"(d[OFF + 25]), "+f"(d[OFF + 26]), "+f"(d[OFF + 27]), "+f"(d[OFF + 28]), "+f"(d[OFF + 29]),
        "+f"(d[OFF + 30]), "+f"(d[OFF + 31])
      : "r"(a0), "r"(a1), "r"(a2), "r"(a3), "l"(desc_b), "r"(scale_d), "r"(meta));
}

template <int OFF, int NN>
__device__ __forceinline__ void wg_s64tz(float (&d)[NN], uint32_t a0, uint32_t a1, uint32_t a2, uint32_t a3,
                                       uint64_t desc_b, int scale_d, uint32_t meta) {
  asm volatile(
      "{\n.reg .pred p;\nsetp.ne.b32 p, %37, 0;\n"
      "wgmma.mma_async.sp.sync.aligned.m64n64k32.f32.bf16.bf16 "
      "{%0,%1,%2,%3,%4,%5,%6,%7,%8,%9,%10,%11,%12,%13,%14,%15,"
      "%16,%17,%18,%19,%20,%21,%22,%23,%24,%25,%26,%27,%28,%29,%30,%31}, "
      "{%32,%33,%34,%35}, %36, %38, 0, p, 1, 1, 1;\n}\n"
      : "=f"(d[OFF + 0]), "=f"(d[OFF + 1]), "=f"(d[OFF + 2]), "=f"(d[OFF + 3]), "=f"(d[OFF + 4]), "=f"(d[OFF + 5]),
        "=f"(d[OFF + 6]), "=f"(d[OFF + 7]), "=f"(d[OFF + 8]), "=f"(d[OFF + 9]), "=f"(d[OFF + 10]), "=f"(d[OFF + 11]),
        "=f"(d[OFF + 12]), "=f"(d[OFF + 13]), "=f"(d[OFF + 14]), "=f"(d[OFF + 15]), "=f"(d[OFF + 16]), "=f"(d[OFF + 17]),
        "=f"(d[OFF + 18]), "=f"(d[OFF + 19]), "=f"(d[OFF + 20]), "=f"(d[OFF + 21]), "=f"(d[OFF + 22]), "=f"(d[OFF + 23]),
        "=f"(d[OFF + 24]), "=f"(d[OFF + 25]), "=f"(d[OFF + 26]), "=f"(d[OFF + 27]), "=f"(d[OFF + 28]), "=f"(d[OFF + 29]),
        "=f"(d[OFF + 30]), "=f"(d[OFF + 31])
      : "r"(a0), "r"(a1), "r"(a2), "r"(a3), "l"(desc_b), "r"(scale_d), "r"(meta));
}

__device__ __forceinline__ int g2_inv(int ch) { return 32 * (ch >> 5) + 8 * ((ch >> 1) & 3) + 2 * ((ch >> 3) & 3) + (ch & 1); }
__host__ __device__ __forceinline__ uint32_t wimg_off(int n, int k) {
  return (uint32_t)(k >> 6) * kWChunk + (uint32_t)n * 128 + (uint32_t)((((k & 63) >> 3) ^ (n & 7)) << 4) + (k & 7) * 2;
}
__host__ __device__ constexpr int w2piece(int h, int c) { return c == 2 ? 2 + h : 4 * h + c; }
__device__ __forceinline__ uint32_t w2img_off(int n, int k) { return wimg_off(n % 96, k & 63) + w2piece(n >= 96, k >> 6) * (kWChunk / 2); }
__device__ __forceinline__ int qpix(int par, int t) {
  const int a = 2 * t + 13 * par - 6, b = t + 112 * par;
  return par ? min(a, b) : max(a, b);
}
__device__ __forceinline__ int woff(int par, int i, int r) {
  const int a = 99 * par + 6 - 8 * i;
  return par ? min(r, a) : max(r, a);
}

__device__ __forceinline__ void mma16816(float (&c)[4], uint32_t a0, uint32_t a1, uint32_t a2, uint32_t a3, uint32_t b0,
                                         uint32_t b1) {
  asm volatile(
      "mma.sync.aligned.m16n8k16.row.col.f32.bf16.bf16.f32 {%0,%1,%2,%3}, {%4,%5,%6,%7}, {%8,%9}, {%0,%1,%2,%3};"
      : "+f"(c[0]), "+f"(c[1]), "+f"(c[2]), "+f"(c[3])
      : "r"(a0), "r"(a1), "r"(a2), "r"(a3), "r"(b0), "r"(b1));
}

__device__ __forceinline__ void fold_w1(const int u, const __nv_bfloat16* __restrict__ wqkv, uint8_t* wimg) {
  const int g = (threadIdx.x >> 2) & 7, l = threadIdx.x & 3;
  const int m0 = (u / 12) * 16, s = u % 12;
  uint4 A[12], B[12];
  const __nv_bfloat16* arow = wqkv + (m0 + 4 * (g >> 1) + (g & 1)) * 576 + 192 + 8 * l;
  const __nv_bfloat16* brow = wqkv + (16 * s + 4 * (g >> 1) + (g & 1)) * 576 + 8 * l;
#pragma unroll
  for (int i = 0; i < 12; i++) {
    A[i] = ldg128_nc(arow + (i & 1) * 2 * 576 + 32 * (i >> 1));
    B[i] = ldg128_nc(brow + (i & 1) * 2 * 576 + 32 * (i >> 1));
  }
  sched_fence();
  uint8_t* dst = wimg + wimg_off(m0 + g, 16 * s + 4 * l);
  float acc[4][4];
#pragma unroll
  for (int j = 0; j < 16; j++) acc[j >> 2][j & 3] = 0.f;
#pragma unroll
  for (int i = 0; i < 6; i++) {
    const uint4 &a0 = A[2 * i], &a1 = A[2 * i + 1];
#pragma unroll
    for (int nb = 0; nb < 2; nb++) {
      mma16816(acc[2 * nb], a0.x, a1.x, a0.y, a1.y, B[2 * i + nb].x, B[2 * i + nb].y);
      mma16816(acc[2 * nb + 1], a0.z, a1.z, a0.w, a1.w, B[2 * i + nb].z, B[2 * i + nb].w);
    }
  }
#pragma unroll
  for (int j = 0; j < 2; j++) {
    const uint2 v = make_uint2(pack_bf16((acc[0][2 * j] + acc[1][2 * j]) * kAlpha, (acc[0][2 * j + 1] + acc[1][2 * j + 1]) * kAlpha),
                               pack_bf16((acc[2][2 * j] + acc[3][2 * j]) * kAlpha, (acc[2][2 * j + 1] + acc[3][2 * j + 1]) * kAlpha));
    asm volatile("st.relaxed.gpu.global.v2.u32 [%0], {%1,%2};" ::"l"(dst + j * 1024), "r"(v.x), "r"(v.y) : "memory");
  }
}
__device__ __forceinline__ void fold_w2(const int u, const __nv_bfloat16* __restrict__ wqkv, const __nv_bfloat16* __restrict__ wo,
                                        uint8_t* wimg) {
  const int g = (threadIdx.x >> 2) & 7, l = threadIdx.x & 3;
  const int m0 = (u / 12) * 32, n0 = (u % 12) * 16;
  uint4 S[12];
  uint32_t L[96];
  const __nv_bfloat16* brow = wqkv + (n0 + 4 * (g >> 1) + (g & 1)) * 576 + 384 + 8 * l;
#pragma unroll
  for (int i = 0; i < 12; i++) S[i] = ldg128_nc(brow + (i & 1) * 2 * 576 + 32 * (i >> 1));
  const __nv_bfloat16* acol = wo + (8 * l) * 192 + m0 + 4 * g;
#pragma unroll
  for (int c = 0; c < 48; c++)
    asm volatile("ld.global.nc.v2.u32 {%0,%1}, [%2];" : "=r"(L[2 * c]), "=r"(L[2 * c + 1]) : "l"(acol + (32 * (c >> 3) + (c & 7)) * 192));
  const uint32_t off = w2_offset();
  sched_fence();
  uint8_t* img = wimg + off;
  float acc[4][4];
#pragma unroll
  for (int j = 0; j < 16; j++) acc[j >> 2][j & 3] = 0.f;
#pragma unroll
  for (int i = 0; i < 6; i++) {
#pragma unroll
    for (int h = 0; h < 2; h++) {
      const uint4 &s0 = S[2 * i], &s1 = S[2 * i + 1];
#pragma unroll
      for (int mt = 0; mt < 2; mt++) {
        const uint32_t* a = L + 16 * i + 8 * h + mt;
        const uint32_t a0 = __byte_perm(a[0], a[2], 0x5410), a1 = __byte_perm(a[0], a[2], 0x7632);
        const uint32_t a2 = __byte_perm(a[4], a[6], 0x5410), a3 = __byte_perm(a[4], a[6], 0x7632);
        mma16816(acc[2 * mt], a0, a1, a2, a3, h ? s0.z : s0.x, h ? s0.w : s0.y);
        mma16816(acc[2 * mt + 1], a0, a1, a2, a3, h ? s1.z : s1.x, h ? s1.w : s1.y);
      }
    }
  }
#pragma unroll
  for (int j = 0; j < 4; j++) {
    const float(&c0)[4] = acc[j & 2];
    const float(&c1)[4] = acc[(j & 2) + 1];
    asm volatile("st.relaxed.gpu.global.v2.u32 [%0], {%1,%2};" ::"l"(img + w2img_off(g2_inv(m0 + 4 * g + j), n0 + 4 * l)),
                 "r"(pack_bf16(c0[2 * (j & 1)], c0[2 * (j & 1) + 1])), "r"(pack_bf16(c1[2 * (j & 1)], c1[2 * (j & 1) + 1])) : "memory");
  }
}

__global__ void __launch_bounds__(256) fold_kernel(const __nv_bfloat16* __restrict__ wqkv,
                                                   const __nv_bfloat16* __restrict__ wo, uint8_t* wimg) {
  const int u = blockIdx.x * 8 + (threadIdx.x >> 5);
  if (u < 144) fold_w1(u, wqkv, wimg);
  else fold_w2(u - 144, wqkv, wo, wimg);
}

struct TileCoord { int pr, pc, I, J, up, kind; };
struct TileTable { uint16_t e[kCtas * 6], g[5][8][2], b[5][2][4]; };
inline void make_tiles(TileTable& tt) {
  for (int tile = 0; tile < kCtas * 6; tile++) {
    const int b = tile / 6, k = tile - 6 * b;
    const int p = b < 128 ? (tile - 672) >> 1 : b - 80;
    const int strip = b < 112 ? b >> 1 : b >= 128 && k >= 2 ? (b & 1) * 27 + (b & 2) * 14 : p + (p < 26 ? 1 : 3);
    const int pr = strip >= 28, J = (strip - pr * 28) >> 1, pc = strip & 1, up = b < 112 ? b & 1 : pr;
    const int first = b < 112 ? 8 - 2 * pr - up : 13 * pr, step = b < 112 ? k : k & 1;
    const int I = up ? first - step : first + step;
    const int kind = I == 13 * pr ? 3 + pr : J == 13 * pc ? 1 + pc : 0;
    tt.e[tile] = (uint16_t)(I | J << 4 | pr << 8 | pc << 9 | up << 10 | kind << 11);
  }
  for (int kind = 0; kind < 5; kind++) {
    const bool col = kind == 1 || kind == 2;
    auto off = [kind](int t) { return kind == 0 ? 2 * t : kind & 1 ? t + (t == 7) : t + (t > 0); };
    for (int j = 0; j < 8; j++) {
      const int w = j >> 1, h = j & 1;
      tt.g[kind][j][0] = (uint16_t)(col ? 3 * off(w + 4 * h) : 3 * (kW * off(2 * w) + 8 * h));
      tt.g[kind][j][1] = (uint16_t)(128 * (col ? 5 : 5 + off(2 * w + 1) - off(2 * w)));
    }
    for (int i = 0; i < 2; i++) {
      const int w = kind == 0 ? 0 : kind & 1 ? 3 * i : 1 - i;
      tt.b[kind][i][0] = tt.g[kind][2 * w][0];
      tt.b[kind][i][1] = (uint16_t)(128 * (kind == 0 ? 0 : (col ? 3 : 1) + i));
      tt.b[kind][i][2] = (uint16_t)(2048 * w);
      tt.b[kind][i][3] = 0;
    }
  }
}
__device__ __forceinline__ int num_tiles() { return blockIdx.x < 128 ? 6 : 4; }
__device__ __forceinline__ TileCoord decode_tile(const TileTable& tt, int tile) {
  const uint32_t e = tt.e[tile];
  return TileCoord{(int)(e >> 8) & 1, (int)(e >> 9) & 1, (int)e & 15, (int)(e >> 4) & 15, (int)(e >> 10) & 1, (int)(e >> 11)};
}
__device__ __forceinline__ int halo_r0(const TileCoord& t) { return 8 * t.I + 6 * t.pr - 6; }
__device__ __forceinline__ int halo_c0(const TileCoord& t) { return min(max(8 * t.J + 6 * t.pc - 6, -3), 102); }

__device__ __forceinline__ uint32_t bar_full(uint32_t bars, int wg, int c) { return bars + (wg * 3 + c) * 8; }
__device__ __forceinline__ uint32_t bar_w1c(uint32_t bars, int c) { return bars + (6 + c) * 8; }
__device__ __forceinline__ uint32_t bar_w2(uint32_t bars) { return bars + 9 * 8; }
__device__ __forceinline__ uint32_t bar_x(uint32_t bars, int j, int c) { return bars + (j == 0 ? 10 : c ? 17 + c : 11) * 8; }
__device__ __forceinline__ uint32_t bar_w1q(uint32_t bars) { return bars + 12 * 8; }
__device__ __forceinline__ uint32_t bar_xf(uint32_t bars) { return bars + 13 * 8; }
__device__ __forceinline__ uint32_t bar_w2m(uint32_t bars) { return bars + 14 * 8; }
__device__ __forceinline__ uint32_t bar_redo(uint32_t bars) { return bars + 15 * 8; }
__device__ __forceinline__ uint32_t bar_wok(uint32_t bars) { return bars + 16 * 8; }
__device__ __forceinline__ uint32_t bar_go(uint32_t bars) { return bars + 17 * 8; }
__device__ __forceinline__ uint32_t bar_raw(uint32_t bars, int j = 0) { return bars + (21 + j) * 8; }
__device__ __forceinline__ uint32_t bar_w2a(uint32_t bars) { return bars + 20 * 8; }
constexpr int kNumBars = 22;

__device__ __forceinline__ uint64_t wdesc(uint64_t d0, int s) { return d0 + (((s >> 2) * kWChunk + (s & 3) * 32) >> 4); }

__device__ __forceinline__ uint32_t x_chunk(int k, int c) { return kXOff + (k == 0 ? kWChunk : 0) + (k & 1 ? 2 - c : c) * 8192; }
__device__ __forceinline__ uint32_t out_slot(int k, int nt) { return k + 1 < nt ? kW2Off + (~k & 1) * 2 * kWChunk : kW1Off + kWChunk; }
template <int I0, int I1>
__device__ __forceinline__ void store_rows(bool on, __nv_bfloat16* pA, __nv_bfloat16* pB, const uint32_t (&a)[24], const uint32_t (&b)[24]) {
#pragma unroll
  for (int i = 2 * I0; i < 2 * I1; i++) {
    const uint32_t* v = (i & 1 ? b : a) + 4 * (i >> 1);
    asm volatile("{\n.reg .pred p;\nsetp.ne.u32 p, %5, 0;\n@p st.global.v4.u32 [%0], {%1,%2,%3,%4};\n}\n" ::"l"((i & 1 ? pB : pA) + 32 * (i >> 1)),
                 "r"(v[0]), "r"(v[1]), "r"(v[2]), "r"(v[3]), "r"((uint32_t)on) : "memory");
  }
}
template <int I0, int I1>
__device__ __forceinline__ void stage_out(const uint32_t (&ad)[4], const uint32_t (&a)[24], const uint32_t (&b)[24]) {
#pragma unroll
  for (int i = I0; i < I1; i++) {
    const uint32_t* v = (i < 6 ? a : b) + 4 * (i % 6);
    asm volatile("st.shared.v4.u32 [%0], {%1,%2,%3,%4};" ::"r"(ad[i % 6 / 3 * 2 + (i % 3 == 1)] + (i % 3 == 2) * 1024 + (i / 6) * 12288),
                 "r"(v[0]), "r"(v[1]), "r"(v[2]), "r"(v[3]) : "memory");
  }
}
__device__ __forceinline__ uint32_t now_ns() {
  uint32_t t;
  asm volatile("mov.u32 %0, %globaltimer_lo;" : "=r"(t)::"memory");
  return t;
}
__device__ __forceinline__ void wait_clock(uint32_t t_start, uint32_t t) {
  while (now_ns() - t_start < t) { }
}
#define NAT_PRED(f, m) ".reg .pred p;\n.reg .b32 t;\nand.b32 t, " f ", " m ";\nsetp.ne.u32 p, t, 0;\n"
constexpr uint32_t kHiV = 1, kHiU = 8, kColB = 0x20, kInV = 0x100, kInU = 0x1000, kColA = 0x10000;
template <uint32_t M>
__device__ __forceinline__ float pick(const float* a, const float* b, uint32_t f) {
  float d;
  asm("{\n" NAT_PRED("%5", "%6") "add.f32 %0, %1, %2;\n@p add.f32 %0, %3, %4;\n}\n"
      : "=&f"(d) : "f"(a[0]), "f"(a[2]), "f"(b[0]), "f"(b[2]), "r"(f), "n"(M));
  return d;
}
template <uint32_t M>
__device__ __forceinline__ float sel(float a, float b, uint32_t f) {
  float d;
  asm("{\n" NAT_PRED("%3", "%4") "selp.f32 %0, %1, %2, p;\n}\n" : "=f"(d) : "f"(a), "f"(b), "r"(f), "n"(M));
  return d;
}
template <uint32_t M>
__device__ __forceinline__ void max_if(float& m, float v, uint32_t f) {
  asm("{\n" NAT_PRED("%2", "%3") "@p max.f32 %0, %0, %1;\n}\n" : "+f"(m) : "f"(v), "r"(f), "n"(M));
}
template <uint32_t M>
__device__ __forceinline__ void add_if(float& m, float v, uint32_t f) {
  asm("{\n" NAT_PRED("%2", "%3") "@p add.f32 %0, %0, %1;\n}\n" : "+f"(m) : "f"(v), "r"(f), "n"(M));
}
__device__ __forceinline__ void pick_v(const float* a, float* v, uint32_t f) {
  v[0] = pick<kHiV>(a, a + 16, f), v[1] = pick<kHiV>(a + 1, a + 17, f);
  v[2] = pick<kHiV * 2>(a + 4, a + 20, f), v[3] = pick<kHiV * 2>(a + 5, a + 21, f);
  v[4] = pick<kHiV * 4>(a + 8, a + 24, f), v[5] = pick<kHiV * 4>(a + 9, a + 25, f);
  v[6] = a[12] + a[14], v[7] = a[13] + a[15];
}
__device__ __forceinline__ void pick_u(const float* a, float* v, uint32_t f) {
#pragma unroll
  for (int c = 0; c < 3; c++) v[2 * c] = pick<kHiU>(a + 4 * c, a + 4 * c + 12, f), v[2 * c + 1] = pick<kHiU * 2>(a + 4 * c + 1, a + 4 * c + 13, f);
}
__device__ __forceinline__ uint32_t sign_bytes(uint32_t v, uint32_t sel) {
  uint32_t d;
  asm("prmt.b32 %0, %1, %1, %2;" : "=r"(d) : "r"(v), "r"(sel));
  return d;
}
__device__ __forceinline__ float own_max(const float (&v)[14], uint32_t f) {
  float m = sel<kInV>(fmaxf(v[0], v[1]), -INFINITY, f), m2 = sel<kInV * 2>(fmaxf(v[2], v[3]), -INFINITY, f);
  max_if<kInV * 4>(m, fmaxf(v[4], v[5]), f);
  max_if<kInV * 8>(m2, fmaxf(v[6], v[7]), f);
  max_if<kInU>(m, fmaxf(fmaxf(v[8], v[10]), v[12]), f);
  max_if<kInU * 2>(m2, fmaxf(fmaxf(v[9], v[11]), v[13]), f);
  return fmaxf(m, m2);
}
__device__ __forceinline__ float quad_max(float m) {
  const float a = __shfl_xor_sync(0xffffffffu, m, 1), b = __shfl_xor_sync(0xffffffffu, m, 2), c = __shfl_xor_sync(0xffffffffu, m, 3);
  return fmaxf(fmaxf(m, a), fmaxf(b, c));
}
__device__ __forceinline__ float row_rcp(const float (&v)[14], uint32_t f) {
  float s = sel<kInV>(v[0] + v[1], 0.f, f), s2 = sel<kInV * 2>(v[2] + v[3], 0.f, f);
  add_if<kInV * 4>(s, v[4] + v[5], f);
  add_if<kInV * 8>(s2, v[6] + v[7], f);
  add_if<kInU>(s, v[8] + v[10] + v[12], f);
  add_if<kInU * 2>(s2, v[9] + v[11] + v[13], f);
  s += s2;
  const float a = __shfl_xor_sync(0xffffffffu, s, 1), b = __shfl_xor_sync(0xffffffffu, s, 2), c = __shfl_xor_sync(0xffffffffu, s, 3);
  return rcp_approx((s + a) + (b + c));
}
__device__ __forceinline__ void route(const float (&v)[14], float s, const uint32_t (&rt)[9], uint32_t (&p)[14]) {
#pragma unroll
  for (int i = 0; i < 7; i++) {
    const uint32_t u = pack_bf16(v[2 * i] * s, v[2 * i + 1] * s);
    if (i < 4) p[i] = u & rt[i];
    if (i < 3) p[i + 4] = u & rt[i + 4];
    if (i >= 4) {
      p[i + 3] = u & rt[7];
      p[i + 6] = u & rt[8];
    }
  }
}

template <int C, int T0 = 0, int T1 = 7>
__device__ __forceinline__ void pv_chunk(float (&z)[32], const uint32_t (&pa)[14], const uint32_t (&pb)[14],
                                         const uint32_t (&meta)[4], uint64_t dV) {
#pragma unroll
  for (int t = T0; t < T1; t++) {
    if (t & 1)
      wg_s64t1<0, 32>(z, pa[2 * t], pb[2 * t], pa[2 * t + 1], pb[2 * t + 1], dV + ((2 * C * kChunkBytes + t * 2048) >> 4), 1,
                      meta[t >> 1]);
    else if (t > 0)
      wg_s64t<0, 32>(z, pa[2 * t], pb[2 * t], pa[2 * t + 1], pb[2 * t + 1], dV + ((2 * C * kChunkBytes + t * 2048) >> 4), 1,
                     meta[t >> 1]);
    else
      wg_s64tz<0, 32>(z, pa[0], pb[0], pa[1], pb[1], dV + ((2 * C * kChunkBytes) >> 4), 0, meta[0]);
  }
}
template <int C>
__device__ __forceinline__ void pack_z(const float (&z)[32], uint32_t (&za)[24], uint32_t (&zb)[24]) {
#pragma unroll
  for (int j = 0; j < 8; j++) {
    za[8 * C + j] = pack_bf16(z[4 * j], z[4 * j + 1]);
    zb[8 * C + j] = pack_bf16(z[4 * j + 2], z[4 * j + 3]);
  }
}

template <int H>
__device__ __forceinline__ void pack_out(const float (&ac)[48], uint32_t (&oa)[24], uint32_t (&ob)[24]) {
#pragma unroll
  for (int j = 0; j < 12; j++) {
    oa[12 * H + j] = pack_bf16(ac[4 * j], ac[4 * j + 1]);
    ob[12 * H + j] = pack_bf16(ac[4 * j + 2], ac[4 * j + 3]);
  }
}
struct Maps { CUtensorMap v6, v2, v14, u8, px[8], wv, wo; };
__device__ __forceinline__ void tma_prefetch_5d(const CUtensorMap* map, int c0, int c1, int c2, int c3, int c4) {
  asm volatile("cp.async.bulk.prefetch.tensor.5d.L2.global.tile [%0, {%1, %2, %3, %4, %5}];" ::"l"((uint64_t)map), "r"(c0), "r"(c1),
               "r"(c2), "r"(c3), "r"(c4) : "memory");
}
__device__ __forceinline__ int first_line(const TileCoord tc) { return 3 * (qpix(tc.pr, 8 * tc.I) * kW + qpix(tc.pc, 8 * tc.J)); }
__device__ __forceinline__ void load_px(const Maps& tm, const TileTable& tt, uint32_t dst, uint32_t bar, int line, int kind) {
#pragma unroll
  for (int i = 0; i < 2; i++) {
    if (i == 0 || kind != 0) {
      const CUtensorMap* map = (const CUtensorMap*)((const char*)tm.px + tt.b[kind][i][1]);
      if (bar) tma_load_5d(dst + tt.b[kind][i][2], map, bar, 0, 0, 0, 0, line + tt.b[kind][i][0]);
      else tma_prefetch_5d(map, 0, 0, 0, 0, line + tt.b[kind][i][0]);
    }
  }
}
__device__ __forceinline__ void store_px(const Maps& tm, const TileTable& tt, uint32_t buf, int line, int kind) {
#pragma unroll
  for (int i = 0; i < 8; i++) {
    const int j = 2 * (i & 3) + (i >> 2);
    asm volatile("cp.async.bulk.tensor.5d.global.shared::cta.tile.bulk_group [%0, {%2, %2, %2, %2, %3}], [%1];" ::"l"(
                     (uint64_t)tm.px + tt.g[kind][j][1]), "r"(buf + i * 3072), "r"(0), "r"(line + tt.g[kind][j][0]) : "memory");
  }
  asm volatile("cp.async.bulk.commit_group;" ::: "memory");
}
__device__ __noinline__ bool refetch(uint32_t base, const uint8_t* src, bool gap) {
  constexpr uint32_t bars = 1024 + kBarOff, cnt = bars + 192;
#pragma unroll 1
  for (uint32_t o = 0; o < kWBytes && !gap; o += 2048) {
    uint32_t mx = 0;
#pragma unroll
    for (int i = 0; i < 4; i++) {
      uint4 v;
      asm volatile("ld.shared.v4.u32 {%0,%1,%2,%3}, [%4];" : "=r"(v.x), "=r"(v.y), "=r"(v.z), "=r"(v.w)
                   : "r"(base + o + i * 512 + (threadIdx.x & 31) * 16));
      mx = __vimax3_u32(__vimax3_u32(mx, v.x, v.y), v.z, v.w);
    }
    gap = __any_sync(0xffffffffu, mx == kEmpty);
  }
  uint32_t n;
  asm volatile("ld.shared.u32 %0, [%1];" : "=r"(n) : "r"(cnt) : "memory");
  if (!gap || __any_sync(0xffffffffu, n > (1u << 12))) return false;
  asm volatile("bar.sync 15, 128;" ::: "memory");
  if (threadIdx.x == 0) {
    asm volatile("st.shared.u32 [%0], %1;" ::"r"(cnt), "r"(n + 1) : "memory");
    mbar_arrive_expect_tx(bar_redo(bars), kWBytes);
    bulk_load(base, src, kWBytes, bar_redo(bars));
  }
  __syncwarp();
  mbar_wait(bar_redo(bars), n & 1);
  return true;
}
template <int S0, int S1, int Z>
__device__ __forceinline__ void g2_steps(float (&ac)[48], const uint32_t (&za)[24], const uint32_t (&zb)[24], uint64_t d) {
#pragma unroll
  for (int s = S0; s < S1; s++) {
    const uint64_t ds = d + (((s >> 2 & 1) * (kWChunk / 2) + (s & 3) * 32) >> 4);
    if (s == Z) wg_d96z<0, 48>(ac, za[2 * s], zb[2 * s], za[2 * s + 1], zb[2 * s + 1], ds, 0);
    else wg_d96<0, 48>(ac, za[2 * s], zb[2 * s], za[2 * s + 1], zb[2 * s + 1], ds, 1);
  }
}

__device__ __forceinline__ void consumer(const int wg, __nv_bfloat16* out, const uint8_t* wimg, const uint32_t sbase,
                                         const uint32_t zero, const Maps& tm, const TileTable& tt) {
  const int tid = threadIdx.x & 127;
  const int w = __shfl_sync(0xffffffffu, tid >> 5, 0), lane = tid & 31;
  const uint64_t dK = make_desc(sbase, 16, 1024);
  const uint64_t dV = make_desc(sbase, kChunkBytes, 512, 2);
  const uint64_t dW1 = make_desc(sbase + kW1Off, 16, 1024);
  const uint64_t dX0 = make_desc(sbase + kW2Off + wg * 2 * kWChunk, 16, 1024), dY0 = make_desc(sbase + kW2Off + (1 - wg) * 2 * kWChunk, 16, 1024);
  const uint64_t dX2 = make_desc(sbase + kXOff + wg * (kWChunk / 2), 16, 1024), dY2 = make_desc(sbase + kXOff + (1 - wg) * (kWChunk / 2), 16, 1024);
  const uint32_t bars = sbase + kBarOff;
  int tile0 = blockIdx.x * kTilesPerCta;
  asm volatile("" : "+r"(tile0));
  const int nt = num_tiles();

  uint32_t pix = 0, geo[6] = {};
  const int l = lane & 3;
#pragma unroll 1
  for (int j = 4; j >= 0; j -= 2) {
    const TileCoord tc = decode_tile(tt, tile0 + wg + j);
    const bool col = tc.kind == 1 || tc.kind == 2;
    const int g = col ? lane >> 2 : 2 * w + ((lane >> 2) & 1), qc = col ? w : lane >> 3;
    const uint32_t pr = qpix(tc.pr, 8 * tc.I + g) * kW;
    if (j == nt - 2) pix = (pr + qpix(tc.pc, 8 * tc.J + qc)) | (pr + qpix(tc.pc, 8 * tc.J + qc + 4)) << 16;
    const int d = 8 * tc.J + 6 * tc.pc - 6 - halo_c0(tc);
    const int ro = woff(tc.pr, tc.I, g), coA = woff(tc.pc, tc.J, qc) + d, coB = woff(tc.pc, tc.J, qc + 4) + d - 3;
#pragma unroll
    for (int i = 5; i >= 2; i--) geo[i] = geo[i - 2];
    const uint32_t lr = 0x1FCu << ro;
    const uint32_t lv = lr >> (2 + (l >> 1)), lu = lr >> (2 * l + 2 * tc.up);
    const uint32_t t = __byte_perm(lv, lu, wg ? 0x4501 : 0x5410);
    geo[0] = (((t & 0x15u) | (lv & 0x40u)) * 0x02082080u & 0x80808080u) | (((t >> 8) & 0x15u) * 0x01041040u & 0x40404040u) |
             (__byte_perm(t << 5, t << 4, 0x7362) & 0x20202020u) | (nt == 6);
    const int dr = (ro - 1) & 7;
    const uint32_t hiv = (((1u << ((ro - (l >> 1) + 1) >> 1)) - 1u) ^ (wg ? 7u : 0u)) & 7u, hiu = (t >> 24) & 3u;
    const uint32_t ca = (1u << coA) - 1u;
    geo[1] = hiv * kHiV | hiu * kHiU | ((((1u << coB) - 1u) >> (2 * (l & 1))) & 3u) * kColB |
             (15u & ~((uint32_t)((dr & 1) == (l >> 1)) << (dr >> 1))) * kInV | ((t >> 16 | t >> 24) & 3u) * kInU | ca * kColA |
             (ca >> ((0x49 >> (2 * l)) & 3) & 1u) << 19 | (uint32_t)(l == 3) << 20 | (0x55u & ((1u << (2 * coB)) - 1u)) << 24;
  }
  keep_regs(geo);
  const int so = (lane >> 3) | (lane & 4);
  uint32_t sts = sbase + w * 3072 + so * 128 + (((lane & 3) ^ so) << 4);
  __nv_bfloat16* poA = out + 8 * l + (pix & 0xFFFFu) * kC + 96 * wg;
  __nv_bfloat16* poB = out + 8 * l + (pix >> 16) * kC + 96 * wg;
  asm volatile("" : "+l"(poA), "+l"(poB), "+r"(sts));
  uint32_t oa[24], ob[24];
#pragma unroll
  for (int j = 0; j < 24; j++) oa[j] = ob[j] = 0u;
  keep_regs(oa);
  keep_regs(ob);
  PROF(wg, 0);
  if (threadIdx.x == 0) GT(1);

  for (int k = wg; k < nt; k += 2) {
    const uint32_t ph = (k >> 1) & 1;
    const int it = k >> 1;
    uint32_t qa[24], qb[24], hok[3];
    uint32_t fl = geo[1];
    {
      float acc[96];
      const uint32_t xp = (k + (k > 0)) & 1;
      const uint32_t xok = mbar_test(bar_x(bars, k > 0, 0), xp);
      if (k > 0) nb_sync(1 + (1 - wg));
#pragma unroll
      for (int s = 0; s < 12; s++) {
        if (s == 0) mbar_wait_if(xok, bar_x(bars, k > 0, 0), xp);
        if (s == 0 && k < 2) PROF(wg, 1);
        if (s == 0) PROFS(2, wg, 2 + it * 12);
        if (s == 0 && w == 0 && k < 2) GT(20 + wg);
        if ((s & 3) == 0 && (k == 0 || s > 0)) {
          mbar_wait(k == 0 ? bar_w1c(bars, s >> 2) : bar_x(bars, 1, s >> 2), xp);
          PROFS(17, wg, 50 + (s >> 2));
        }
        if ((s & 3) == 0) wg_fence();
        const uint64_t dX = make_desc(sbase + x_chunk(k, s >> 2), 16, 1024) + 2 * (s & 3);
        if (s == 0) wg_m192z<0, 96>(acc, dX, dW1, 0);
        else wg_m192<0, 96>(acc, dX, wdesc(dW1, s), 1);
        if ((s & 3) == 3) wg_commit();
      }
      PROFS(13, wg, 13 + it * 12);
      const uint32_t e = sts + out_slot(k, nt), o = e ^ 64;
      uint32_t ad[4] = {wg ? o + 1024 : e, wg ? e + 2048 : o, wg ? e : o + 1024, wg ? o : e + 2048};
      keep_regs(ad);
      if (NAT_MP > 2) {
        wg_wait<2>();
        if (k > 0) nb_arrive_p(0);
      }
      if (NAT_MP > 1) {
        wg_wait<1>();
        if (k > 0) nb_arrive_p(14);
      }
      wg_wait<0>();
      if (k > 0) {
        nb_arrive_p(6);
        sched_fence();
      }
      fence_regs(acc);
      PROFS(3, wg, 3 + it * 12);
#pragma unroll
      for (int j = 0; j < 24; j++) {
        qa[j] = pack_bf16(acc[4 * j], acc[4 * j + 1]);
        qb[j] = pack_bf16(acc[4 * j + 2], acc[4 * j + 3]);
      }
      keep_regs(qa);
      keep_regs(qb);
      sched_fence();
      if (k >= 2) {
        nb_sync(11);
        stage_out<0, 6>(ad, oa, ob);
        nb_sync(12);
        stage_out<6, 12>(ad, oa, ob);
      }
#pragma unroll
      for (int c = 0; c < 3; c++) hok[c] = mbar_test(bar_full(bars, wg, c), ph);
      if (k >= 2) {
        fence_proxy_async();
        nb_arrive_p(10);
      }
    }

    float aE[52], aO[24], bO[52], bE[28];
    const uint32_t mq = 0xEEEE4444u | zero;
    PROFS(4, wg, 4 + it * 12);

    mbar_wait_if(hok[0], bar_full(bars, wg, 0), ph);
    PROFS(14, wg, 40 + it * 3);
    if (w == 0 && k < 2) GT(22 + wg);
    if (k > 0) nb_sync(3 + (1 - wg));
    wg_fence();
#pragma unroll
    for (int ks = 0; ks < 6; ks++) {
      if (ks == NAT_P1) {
        mbar_wait_if(hok[1], bar_full(bars, wg, 1), ph);
        PROFS(14, wg, 41 + it * 3);
        wg_fence();
      }
      if (ks == NAT_P2) {
        mbar_wait_if(hok[2], bar_full(bars, wg, 2), ph);
        PROFS(14, wg, 42 + it * 3);
        wg_fence();
      }
      const uint64_t d = dK + ((ks * kChunkBytes) >> 4);
      if (ks == 0) wg_s104z<0, 52>(aE, qa[0], qa[1], qa[2], qa[3], d, 0, mq);
      else wg_s104<0, 52>(aE, qa[4 * ks], qa[4 * ks + 1], qa[4 * ks + 2], qa[4 * ks + 3], d, 1, mq);
      if (ks == 0) wg_s48z<0, 24>(aO, qa[0], qa[1], qa[2], qa[3], d + ((7 * 1024 + 64) >> 4), 0, mq);
      else if (ks < NAT_QA) wg_s48<0, 24>(aO, qa[4 * ks], qa[4 * ks + 1], qa[4 * ks + 2], qa[4 * ks + 3], d + ((7 * 1024 + 64) >> 4), 1, mq);
    }
    wg_commit();
#pragma unroll
    for (int ks = NAT_QA; ks < 6; ks++)
      wg_s48<0, 24>(aO, qa[4 * ks], qa[4 * ks + 1], qa[4 * ks + 2], qa[4 * ks + 3], dK + ((ks * kChunkBytes + 7 * 1024 + 64) >> 4), 1, mq);
    wg_commit();
    wg_s56z<0, 28>(bE, qb[0], qb[1], qb[2], qb[3], dK, 0, mq);
#pragma unroll
    for (int ks = 1; ks < 6; ks++) wg_s56<0, 28>(bE, qb[4 * ks], qb[4 * ks + 1], qb[4 * ks + 2], qb[4 * ks + 3], dK + ((ks * kChunkBytes) >> 4), 1, mq);
    wg_commit();
    wg_wait<2>();
    fence_regs(aE);
    PROFS(5, wg, 5 + it * 12);

    uint32_t pa[14], pb[14], meta[4];
    {
      float vA[14], vB[14];
      pick_v(aE, vA, fl);
      pick_u(aE + 28, vA + 8, fl);
      fence_regs(vA);
      if (k == 0) {
        if (__builtin_expect(__any_sync(0xffffffffu, vA[6] != vA[6]), 0)) {
          wg_wait<0>();
          fence_regs(aO);
          fence_regs(bE);
          if (refetch(sbase + kW1Off, wimg, false)) {
#pragma unroll
            for (int j = 0; j < 24; j++) oa[j] = ob[j] = 0u;
            k -= 2;
            continue;
          }
        }
        if (elect_one()) mbar_arrive(bar_xf(bars));
      }
      wg_fence();
      wg_s104z<0, 52>(bO, qb[0], qb[1], qb[2], qb[3], dK + 4, 0, mq);
#pragma unroll
      for (int ks = 1; ks < 6; ks++)
        wg_s104<0, 52>(bO, qb[4 * ks], qb[4 * ks + 1], qb[4 * ks + 2], qb[4 * ks + 3], dK + ((ks * kChunkBytes + 64) >> 4), 1, mq);
      wg_commit();
      if (k + 1 < nt) nb_arrive(1 + wg);
      uint32_t rt[9];
#pragma unroll
      for (int i = 0; i < 7; i++) rt[i] = sign_bytes(geo[0] << (i >> 2), 0x8888u + 0x1111u * (i & 3));
      rt[7] = sign_bytes(geo[0] << 2, 0x9988u);
      rt[8] = sign_bytes(geo[0] << 2, 0xBBAAu);
      keep_regs(rt);
      pa[13] = pb[13] = 0u;
      wg_wait<2>();
      keep_regs(qa);
      fence_regs(aO);
      float oA[6], eB[8];
      pick_u(aO, oA, fl);
      wg_wait<1>();
      fence_regs(bE);
      pick_v(bE, eB, fl);
      vA[8] = sel<kColA>(oA[0], vA[8], fl), vA[9] = sel<kColA>(oA[1], vA[9], fl);
      vA[10] = sel<kColA * 2>(oA[2], vA[10], fl), vA[11] = sel<kColA * 2>(oA[3], vA[11], fl);
      vA[12] = sel<kColA * 4>(oA[4], vA[12], fl), vA[13] = sel<kColA * 4>(oA[5], vA[13], fl);
      {
        const float m1 = __uint_as_float(0x88DD88DDu), m0 = __uint_as_float(0x88DDDD88u);
        meta[0] = 0xDD88DD88u ^ __byte_perm(fl, 0u, 0x3344);
        meta[1] = __float_as_uint(sel<kColA * 16>(sel<kColA>(m1, m0, fl), __uint_as_float(meta[0]), fl));
        meta[2] = __float_as_uint(sel<kColA * 8>(m1, m0, fl));
        meta[3] = __float_as_uint(sel<kColA * 4>(m1, m0, fl));
        keep_regs(meta);
      }
      float mA = own_max(vA, fl);
      fl |= __float_as_uint(eB[7]) & zero;
      fence_regs(eB);
      fence_regs(vA);
      asm volatile("" : "+f"(mA), "+r"(fl));
      sched_fence();
      wg_wait<0>();
      sched_fence();
      keep_regs(qb);
      fence_regs(bO);
      PROFS(6, wg, 6 + it * 12);
      if (w == 0) GT(24 + k);
      mA = quad_max(mA);
#pragma unroll
      for (int i = 0; i < 14; i++) vA[i] = ex2(vA[i] - mA);
      pick_v(bO, vB, fl);
      pick_u(bO + 28, vB + 8, fl);
#pragma unroll
      for (int i = 0; i < 8; i += 2) vB[i] = sel<kColB>(vB[i], eB[i], fl), vB[i + 1] = sel<kColB * 2>(vB[i + 1], eB[i + 1], fl);
      float mB = quad_max(own_max(vB, fl));
      if (NAT_SB) {
        fence_regs(vA);
        fence_regs(vB);
        asm volatile("" : "+f"(mB));
        sched_fence();
      }
      PROFS(7, wg, 7 + it * 12);
#pragma unroll
      for (int i = 0; i < 14; i++) vB[i] = ex2(vB[i] - mB);
      route(vA, row_rcp(vA, fl), rt, pa);
      route(vB, row_rcp(vB, fl), rt, pb);
    }
    PROFS(8, wg, 8 + it * 12);
    if (k == NAT_PK) PROFS(18, wg, 53);
    sched_fence();

    float ac0[48], ac1[48];
    {
      float z0[32], z1[32], z2[32];
      uint32_t za[24], zb[24];
      wg_fence();
      pv_chunk<0>(z0, pa, pb, meta, dV);
      wg_commit();
      pv_chunk<1>(z1, pa, pb, meta, dV);
      wg_commit();
      wg_wait<1>();
      if (k == NAT_PK) PROFS(18, wg, 54);
      if (k + 1 < nt) nb_arrive_p(7);
      pv_chunk<2, 0, 3>(z2, pa, pb, meta, dV);
      wg_commit();
      sched_fence();
      fence_regs(z0);
      pack_z<0>(z0, za, zb);
      sched_fence();
      wg_fence();
      pv_chunk<2, 3, 7>(z2, pa, pb, meta, dV);
      wg_commit();
      wg_wait<2>();
      if (k == NAT_PK) PROFS(19, wg, 55);
      if (k + 1 < nt) nb_arrive_p(8);
      if (k < 2) mbar_wait(k == 1 ? bar_wok(bars) : bar_w2a(bars), 0);
      wg_fence();
      g2_steps<0, 3, 0>(ac0, za, zb, dX0);
      wg_commit();
      sched_fence();
      fence_regs(z1);
      pack_z<1>(z1, za, zb);
      sched_fence();
      wg_fence();
      g2_steps<3, 4, 0>(ac0, za, zb, dX0);
      wg_commit();
      g2_steps<4, 8, 0>(ac0, za, zb, dX0);
      wg_commit();
      wg_wait<3>();
      if (k + 1 < nt) nb_arrive_p(9);
      else nb_arrive(11);
      if (k == NAT_PK) PROFS(20, wg, 56);
      keep_regs(pa);
      keep_regs(pb);
      keep_regs(meta);
      sched_fence();
      const uint32_t mok = mbar_test(bar_w2m(bars), k + 1 < nt ? k & 1 : ~k & 1);
      const uint32_t wp = k < 2 ? 0 : k + 1 < nt ? ~k & 1 : k & 1, wok = mbar_test(bar_w2(bars), wp);
      fence_regs(z2);
      pack_z<2>(z2, za, zb);
      keep_regs(za);
      keep_regs(zb);
      sched_fence();
      PROFS(9, wg, 9 + it * 12);
      wg_wait<1>();
      if (k > 0 && k + 1 < nt) nb_arrive(11);
      mbar_wait_if(mok, bar_w2m(bars), k & 1);
      wg_fence();
      g2_steps<8, 12, 0>(ac0, za, zb, dX2);
      wg_commit();
      g2_steps<8, 12, 8>(ac1, za, zb, dY2);
      wg_commit();
      wg_wait<2>();
      if (k > 0 && k + 1 < nt) nb_arrive(12);
      mbar_wait_if(wok, bar_w2(bars), wp);
      wg_fence();
      g2_steps<0, 4, 8>(ac1, za, zb, dY0);
      wg_commit();
      wg_wait<2>();
      if (k + 2 < nt) nb_arrive_p(13);
      const bool direct = k + 2 >= nt;
      sched_fence();
      fence_regs(ac0);
      pack_out<0>(ac0, oa, ob);
      store_rows<0, NAT_D0>(direct, poA, poB, oa, ob);
      sched_fence();
      wg_fence();
      g2_steps<4, 8, 8>(ac1, za, zb, dY0);
      wg_commit();
      if (k + 1 < nt) nb_arrive(3 + wg);
      PROFS(10, wg, 10 + it * 12);
      wg_wait<2>();
      if (k + 2 < nt && (k > 0 || nt == 6)) nb_arrive_p(5);
      store_rows<NAT_D0, 3>(direct, poA, poB, oa, ob);
      __nv_bfloat16 *qA = poA - 192 * wg, *qB = poB - 192 * wg;
      if (k + 2 == nt) nb_sync(11);
      sched_fence();
      wg_wait<0>();
      fence_regs(ac1);
      pack_out<1>(ac1, oa, ob);
      asm volatile("" : "+l"(qA), "+l"(qB));
      store_rows<3, 6>(direct, qA, qB, oa, ob);
      if (k == 0) {
        uint32_t m[2] = {oa[0], oa[1]};
#pragma unroll
        for (int i = 2; i < 24; i++) asm("max.NaN.bf16x2 %0, %0, %1;" : "+r"(m[i & 1]) : "r"(oa[i]));
        asm("max.NaN.bf16x2 %0, %0, %1;" : "+r"(m[0]) : "r"(m[1]));
        uint32_t nan;
        asm volatile("{\n.reg .pred p;\nsetp.ne.u32 p, %1, 0;\nbar.red.or.pred p, 15, 128, p;\nselp.u32 %0, 1, 0, p;\n}\n"
                     : "=r"(nan) : "r"(((m[0] & 0x7FFF7FFFu) + 0x007F007Fu) & 0x80008000u) : "memory");
        if (__builtin_expect(__any_sync(0xffffffffu, nan), 0)) {
          for (int c = 0; c < 3 && __any_sync(0xffffffffu, geo[2] & 1u); c++) mbar_wait(bar_x(bars, 1, c), 1);
          for (bool first = true; __any_sync(0xffffffffu, refetch(sbase + kW2Off, wimg + w2_offset(), first)); first = false) { }
          wg_fence();
          g2_steps<0, 8, 0>(ac0, za, zb, dX0);
          g2_steps<8, 12, 0>(ac0, za, zb, dX2);
          g2_steps<8, 12, 8>(ac1, za, zb, dY2);
          g2_steps<0, 8, 8>(ac1, za, zb, dY0);
          wg_commit();
          wg_wait<0>();
          fence_regs(ac0);
          fence_regs(ac1);
          pack_out<0>(ac0, oa, ob);
          pack_out<1>(ac1, oa, ob);
          if (__any_sync(0xffffffffu, geo[2] & 1u)) {
            asm volatile("bar.sync 15, 128;" ::: "memory");
            if (w == 0 && elect_one()) {
              const TileCoord tc = decode_tile(tt, tile0 + 2);
              mbar_arrive_expect_tx(bar_raw(bars), kWChunk);
#pragma unroll 1
              for (int c = 0; c < 3; c++) load_px(tm, tt, sbase + x_chunk(2, c), bar_raw(bars), first_line(tc) + c, tc.kind);
            }
            __syncwarp();
            mbar_wait(bar_raw(bars), 0);
          }
        }
        if (nt < 6) nb_arrive_p(5);
        if (elect_one()) mbar_arrive(bar_wok(bars));
      }
      keep_regs(za);
      keep_regs(zb);
#pragma unroll
      for (int i = 0; i < 4; i++) geo[i] = geo[i + 2];
      keep_regs(oa);
      keep_regs(ob);
      PROFS(12, wg, 12 + it * 12);
      sched_fence();
    }
  }
  PROF(wg, 38);
  GT_DUMP();
  PROF_DUMP(wg);
}

struct HaloCols { int vj, vc, uj, uc; };
__device__ __forceinline__ HaloCols halo_cols(const TileCoord& tc) {
  const int c0 = halo_c0(tc);
  return HaloCols{c0 > 98, c0 > 98 ? 98 : c0 + 3, c0 < 0 ? -1 : 0, c0 < 0 ? 4 : c0};
}
__device__ __forceinline__ void first_halo(const Maps& tm, uint32_t sbase, const TileCoord tc, int i) {
  const HaloCols hc = halo_cols(tc);
  const uint32_t dst = sbase + i * kChunkBytes, bar = bar_full(sbase + kBarOff, 0, i >> 1);
  const int h0 = halo_r0(tc), ch = 24 * tc.pc + 4 * i;
  tma_load_5d(dst, &tm.v14, bar, ch, hc.vj, hc.vc, tc.pr, h0);
  tma_load_5d(dst + 7 * 1024, &tm.u8, bar, ch, hc.uj, h0 + (tc.up ? 0 : -2), tc.pr, hc.uc);
  tma_load_5d(dst + 10 * 1024, &tm.u8, bar, ch, hc.uj, h0 + (tc.up ? 8 : 6), tc.pr, hc.uc);
}
__device__ __forceinline__ void load_halo(const Maps& tm, uint32_t sbase, uint32_t bars, const TileCoord tc, int k, int c) {
  const HaloCols hc = halo_cols(tc);
  const int h6 = halo_r0(tc) + (tc.up ? 0 : 8), h2 = halo_r0(tc) + 6, h8 = halo_r0(tc) + (tc.up ? 0 : 6), ch = 24 * tc.pc + 8 * c;
  uint32_t dv = sbase + 2 * c * kChunkBytes, du = dv + 7 * 1024;
  if (((k ^ tc.up) & 1) == 0) dv += 4 * 1024, du += 3 * 1024;
  const uint32_t bar = bar_full(bars, k & 1, c);
  mbar_arrive_expect_tx(bar, 14 * 1024);
  nb_sync_p(7 + c);
#pragma unroll
  for (int h = 0; h < 2; h++) {
    tma_load_5d(dv + h * kChunkBytes, &tm.v6, bar, ch + 4 * h, hc.vj, hc.vc, tc.pr, h6);
    tma_load_5d(du + h * kChunkBytes, &tm.u8, bar, ch + 4 * h, hc.uj, h8, tc.pr, hc.uc);
    tma_load_5d(sbase + (2 * c + h) * kChunkBytes + 3 * 1024, &tm.v2, bar, ch + 4 * h, hc.vj, hc.vc, tc.pr, h2);
  }
  PROFS(15, 2, k * 4 + c);
}
__device__ __forceinline__ void gather_px(const __nv_bfloat16* __restrict__ x, uint32_t sbase, const TileCoord tc) {
  const int lane = threadIdx.x & 31, g = lane >> 3;
  uint32_t ro[4], co[4];
#pragma unroll
  for (int i = 0; i < 4; i++) {
    ro[i] = qpix(tc.pr, 8 * tc.I + 2 * i + (g & 1)) * (kW * kC * 2) + 16 * (lane & 7);
    co[i] = qpix(tc.pc, 8 * tc.J + 2 * i + (g >> 1)) * (kC * 2);
  }
  const uint32_t dst = sbase + kXOff + g * 128 + (((lane & 7) ^ g) << 4);
  if (lane < 8)
    asm volatile("cp.async.bulk.prefetch.L2.global [%0], 3456;" ::"l"(x + (qpix(tc.pr, 8 * tc.I + lane) * kW + 215 * tc.pc) * kC) : "memory");
  __syncwarp();
  keep_regs(ro);
  keep_regs(co);
  sched_fence();
  nb_sync_p(13);
  nb_sync_p(5);
#pragma unroll
  for (int i = 0; i < 16; i++) {
    const char* src = (const char*)x + (ro[i >> 2] + co[i & 3]);
#pragma unroll
    for (int q = 0; q < 3; q++)
      asm volatile("cp.async.cg.shared.global [%0], [%1], 16;" ::"r"((dst ^ ((i & 1) * 576)) + (i >> 1) * 1024 + q * 8192), "l"(src + 128 * q) : "memory");
  }
  asm volatile("cp.async.wait_all;" ::: "memory");
  fence_proxy_async();
  __syncwarp();
  if (lane < 3) mbar_arrive(bar_x(sbase + kBarOff, 1, lane));
  __syncwarp();
}

__global__ void __launch_bounds__(384, 1)
nat_kernel(const __nv_bfloat16* __restrict__ x, __nv_bfloat16* out, const __nv_bfloat16* __restrict__ wqkv,
           const __nv_bfloat16* __restrict__ wo, uint8_t* wimg, const uint32_t zero,
           const __grid_constant__ Maps tm, const __grid_constant__ TileTable tt) {
  extern __shared__ uint8_t smem_raw[];
  constexpr uint32_t sbase = 1024;
  constexpr uint32_t bars = sbase + kBarOff;
  if (smem_u32(smem_raw) != sbase) __trap();
  const int tid = threadIdx.x;
  const uint32_t t_start = now_ns();
  if (tid == 0) GT(0);
  const int wid = __shfl_sync(0xffffffffu, tid >> 5, 0);
  const bool w2cta = blockIdx.x - 128 < 3 && wqkv != nullptr;
  if (wid >= 8) {
    asm volatile("setmaxnreg.dec.sync.aligned.u32 24;");
    const int c = wid & 3, lane = tid & 31;
    const int tile0 = blockIdx.x * kTilesPerCta, nt = num_tiles();
    uint32_t w2o = 0;
    if (c == 3) {
      if (elect_one()) wait_clock(t_start, NAT_TM);
      __syncwarp();
      asm volatile("prefetch.tensormap [%0];" ::"l"((uint64_t)tm.px) : "memory");
      asm volatile("prefetch.tensormap [%0];" ::"l"((uint64_t)&tm.v6) : "memory");
      asm volatile("prefetch.tensormap [%0];" ::"l"((uint64_t)&tm.v2) : "memory");
      asm volatile("prefetch.tensormap [%0];" ::"l"((uint64_t)(tm.px + (blockIdx.x < 112 ? 5 : 6))) : "memory");
      asm volatile("prefetch.tensormap [%0];" ::"l"((uint64_t)(tm.px + 7)) : "memory");
      if (nt < 6) {
        asm volatile("prefetch.tensormap [%0];" ::"l"((uint64_t)(tm.px + 1)) : "memory");
        asm volatile("prefetch.tensormap [%0];" ::"l"((uint64_t)(tm.px + 2)) : "memory");
        asm volatile("prefetch.tensormap [%0];" ::"l"((uint64_t)&tm.v14) : "memory");
        asm volatile("prefetch.tensormap [%0];" ::"l"((uint64_t)&tm.u8) : "memory");
      }
      __nanosleep(NAT_TW2 - 2800);
      asm volatile("bar.sync 4, 64;" ::: "memory");
      w2o = w2_offset();
      if (elect_one()) {
        mbar_arrive_expect_tx(bar_w2a(bars), kWChunk);
        mbar_arrive_expect_tx(bar_w2(bars), kWChunk);
        wait_clock(t_start, NAT_TW2);
        bulk_load(sbase + kW2Off, wimg + w2o, kWChunk, bar_w2a(bars));
        mbar_wait(bar_xf(bars), 0);
        bulk_load(sbase + kW2Off + 2 * kWChunk, wimg + (w2o + 2 * kWChunk), kWChunk, bar_w2(bars));
      }
      __syncwarp();
      if (nt < 6) gather_px(x, sbase, decode_tile(tt, tile0 + 2));
      if (wqkv == nullptr) return;
      mbar_wait(bar_wok(bars), 0);
      if (lane == 0) asm volatile("red.relaxed.gpu.global.add.u32 [%0], 1;" ::"l"(g_flag) : "memory");
      if (blockIdx.x >= 48) return;
      if (lane == 0) {
        uint32_t v, it = 0;
        do {
          __nanosleep(2000);
          asm volatile("ld.relaxed.gpu.global.u32 %0, [%1];" : "=r"(v) : "l"(g_flag) : "memory");
        } while (v < gridDim.x && ++it < (1u << 16));
      }
      __syncwarp();
#pragma unroll
      for (int i = 0; i < 6; i++)
        stg128(wimg + ((i < 3 ? 0u : 3 * kWBytes - w2o) + blockIdx.x * 1536 + (i % 3) * 512 + lane * 16), kEmpty, kEmpty, kEmpty, kEmpty);
      if (lane == 0 && atomicAdd(g_flag + 32, 1u) == 47) {
        g_flag[0] = g_flag[32] = 0;
        g_flag[64] = w2o == kWBytes;
      }
      return;
    }
    if (!elect_one()) return;
    if (c == 0) {
      for (int i = 0; i < kNumBars; i++)
        if ((i != 0 && i != 10 || nt < 6) && (i != 21 || !w2cta)) mbar_init(bars + i * 8, i == 13 || i == 16 ? 4 : 1);
      asm volatile("st.shared.v2.u32 [%0], {%1,%1};" ::"r"(bars + 192), "r"(0) : "memory");
      asm volatile("fence.mbarrier_init.release.cluster;" ::: "memory");
      if (w2cta) asm volatile("bar.sync 10, 64;" ::: "memory");
      asm volatile("bar.arrive 0, 160;" ::: "memory");
      asm volatile("bar.arrive 14, 160;" ::: "memory");
      asm volatile("bar.arrive 13, 96;" ::: "memory");
      asm volatile("bar.arrive 4, 64;" ::: "memory");
      const TileCoord tc0 = decode_tile(tt, tile0);
      const HaloCols hc = halo_cols(tc0);
      const int h0 = halo_r0(tc0);
#pragma unroll
      for (int j = 0; j < 3; j++)
        if (j > 0 || nt < 6) mbar_arrive_expect_tx(bar_full(bars, 0, j), 2 * kChunkBytes);
      wait_clock(t_start, NAT_HP);
#pragma unroll
      for (int q = 8; q < 24 && !w2cta; q += 8) {
        tma_prefetch_5d(blockIdx.x < 112 ? &tm.v6 : &tm.v14, 24 * tc0.pc + q, hc.vj, hc.vc, tc0.pr, h0 + (tc0.up || blockIdx.x >= 112 ? 0 : 8));
        tma_prefetch_5d(&tm.u8, 24 * tc0.pc + q, hc.uj, h0 + (tc0.up ? 0 : 6), tc0.pr, hc.uc);
      }
#pragma unroll 1
      for (int i = nt < 6 ? 0 : 2; i < 7; i++) {
        if (i == NAT_H0) mbar_wait(bar_w1q(bars), 0);
        if (i == NAT_X1P) mbar_arrive(bar_go(bars));
        if (i < 6) first_halo(tm, sbase, tc0, i);
      }
      w2o = w2_offset();
    } else {
      asm volatile("bar.sync 13, 96;" ::: "memory");
      if (c == 2) {
        if (wqkv != nullptr && blockIdx.x < 131) asm volatile("bar.sync 12, 64;" ::: "memory");
        const uint32_t c0 = clock();
        while ((uint32_t)clock() - c0 < NAT_TD && nt == 6) { }
        wait_clock(t_start, NAT_T0);
#pragma unroll
        for (int j = 0; j < 3; j++) {
          mbar_arrive_expect_tx(bar_w1c(bars, j), kWChunk);
          bulk_load(sbase + kW1Off + j * kWChunk, wimg + j * kWChunk, kWChunk, bar_w1c(bars, j));
        }
        mbar_arrive(bar_w1q(bars));
        GT(2);
      } else {
#pragma unroll 1
        for (int j = nt == 6; j < 2; j++) {
          const TileCoord tc = decode_tile(tt, tile0 + j);
          const int line = first_line(tc);
          if (j == 1) mbar_wait(bar_go(bars), 0);
          if (j == 0) GT(15);
#pragma unroll 1
          for (int q = 0; q < 3; q++) {
            load_px(tm, tt, sbase + x_chunk(j, q), bar_x(bars, j, q), line + q, tc.kind);
            if (j == 1 || q == 0) mbar_arrive_expect_tx(bar_x(bars, j, q), j ? 8192 : kWChunk);
          }
          if (j == 0) GT(16);
        }
        w2o = w2_offset();
        wait_clock(t_start, NAT_TW2);
        mbar_wait(bar_xf(bars), 0);
      }
    }
#pragma unroll 1
    for (int k = 1; k < nt; k++) {
      const TileCoord tn = decode_tile(tt, tile0 + k + 1);
      const int line = first_line(tn);
      const bool more = k + 1 < nt && (k > 1 || nt == 6);
      if (c == 1) {
#pragma unroll
        for (int q = 3 - NAT_MP; q < 3; q++) {
          const uint32_t n = q == 3 - NAT_MP ? q + 1 : 1, o = x_chunk(k, k & 1 ? q : q + 1 - n);
          nb_sync_p(q == 0 ? 0 : q == 1 ? 14 : 6);
          bulk_load(sbase + o, wimg + (w2o + o - kW2Off), n * 8192, bar_w2m(bars));
        }
        mbar_arrive_expect_tx(bar_w2m(bars), kWChunk);
      }
      if (c == 2) {
        if (k == 1) wait_clock(t_start, NAT_TX2);
        else __nanosleep(NAT_PFD);
#pragma unroll 1
        for (int q = 0; q < 3 && more; q++) load_px(tm, tt, 0, 0, line + q, tn.kind);
      }
      if (c == 2 && (blockIdx.x >= 112 || k == 5)) {
        const TileCoord tc = decode_tile(tt, tile0 + k);
        const HaloCols hc = halo_cols(tc);
        const int h8 = halo_r0(tc) + (tc.up ? 0 : 6);
#pragma unroll 1
        for (int q = 0; q < 24; q += 8) {
          tma_prefetch_5d(&tm.v6, 24 * tc.pc + q, hc.vj, hc.vc, tc.pr, h8);
          tma_prefetch_5d(&tm.v2, 24 * tc.pc + q, hc.vj, hc.vc, tc.pr, h8 + 6);
          tma_prefetch_5d(&tm.u8, 24 * tc.pc + q, hc.uj, h8, tc.pr, hc.uc);
        }
      }
      load_halo(tm, sbase, bars, decode_tile(tt, tile0 + k), k, c);
      if (c == 0 && more) {
#pragma unroll
        for (int q = 0; q < 3; q++) {
          if (q < 2) nb_sync_p(q ? 5 : 13);
          load_px(tm, tt, sbase + x_chunk(k + 1, q), bar_x(bars, 1, q), line + q, tn.kind);
          if (q != 1) mbar_arrive_expect_tx(bar_x(bars, 1, q), 8192);
        }
        mbar_arrive_expect_tx(bar_x(bars, 1, 1), 8192);
        PROFS(16, 2, k * 4 + 3);
      }
      if (c == 0 && k >= 2) {
        const TileCoord tp = decode_tile(tt, tile0 + k - 2);
        const int lp = first_line(tp);
        nb_sync_p(10);
        __nanosleep(NAT_XW);
        store_px(tm, tt, sbase + out_slot(k, nt), lp, tp.kind);
        if (k + 1 < nt) {
          asm volatile("cp.async.bulk.wait_group.read 0;" ::: "memory");
          bulk_load(sbase + out_slot(k, nt), wimg + (w2o + out_slot(k, nt) - kW2Off), kWChunk, bar_w2(bars));
          mbar_arrive_expect_tx(bar_w2(bars), kWChunk);
        }
      }
    }
    asm volatile("cp.async.bulk.wait_group 0;" ::: "memory");
  } else {
    if (blockIdx.x < 128) {
      if ((wid == 4 || (wid == 5 && blockIdx.x - 2 < 16)) && wqkv != nullptr) {
        fold_w1(blockIdx.x - 2 < 16 ? 2 * blockIdx.x + wid - 6 : blockIdx.x + (blockIdx.x < 2 ? 0 : 16), wqkv, wimg);
        if (wid == 4) asm volatile("bar.arrive 12, 64;" ::: "memory");
        if (tid == 128) GT(7);
      }
      sched_fence();
      if (wid == 1 && elect_one()) {
        const TileCoord tc = decode_tile(tt, blockIdx.x * kTilesPerCta);
        mbar_init(bar_x(bars, 0, 0), 1);
        asm volatile("fence.mbarrier_init.release.cluster;" ::: "memory");
        mbar_arrive_expect_tx(bar_x(bars, 0, 0), kWChunk);
        GT(15);
#pragma unroll 1
        for (int q = 0; q < 3; q++) load_px(tm, tt, sbase + x_chunk(0, q), bar_x(bars, 0, 0), first_line(tc) + q, tc.kind);
        GT(16);
      }
      __syncwarp();
      sched_fence();
      if (wid == 2 && elect_one()) {
        const TileCoord tc = decode_tile(tt, blockIdx.x * kTilesPerCta);
        mbar_init(bar_full(bars, 0, 0), 1);
        asm volatile("fence.mbarrier_init.release.cluster;" ::: "memory");
        mbar_arrive_expect_tx(bar_full(bars, 0, 0), 2 * kChunkBytes);
        if (NAT_TH) wait_clock(t_start, NAT_TH);
        asm volatile("prefetch.tensormap [%0];" ::"l"((uint64_t)&tm.u8) : "memory");
        GT(17);
        first_halo(tm, sbase, tc, 0);
        first_halo(tm, sbase, tc, 1);
      }
      __syncwarp();
    }
    sched_fence();
    {
      if (w2cta) {
        const int q = blockIdx.x & 3;
        uint32_t w2o = 0;
        if (wid == 1 && elect_one()) {
          asm volatile("prefetch.tensormap [%0];" ::"l"((uint64_t)&tm.wo) : "memory");
#pragma unroll
          for (int j = 0; j < 3; j++) mbar_init(bar_raw(bars, j), 1);
          asm volatile("fence.mbarrier_init.release.cluster;" ::: "memory");
#pragma unroll
          for (int j = 0; j < 6; j++)
            asm volatile("cp.async.bulk.tensor.2d.shared::cluster.global.tile.mbarrier::complete_tx::bytes [%0], [%1, {%3, %4}], [%2];" ::"r"(
                             j < 3 ? sbase + j * 8192 : sbase + kW2Off + (j - 3) * kWChunk),
                         "l"((uint64_t)(j < 3 ? &tm.wv : &tm.wo)), "r"(bar_raw(bars, j < 3 ? 0 : j - 3)),
                         "r"(j < 3 ? 384 + 64 * j : 64 * (j - 3)), "r"(j < 3 ? 64 * q : 0) : "memory");
#pragma unroll
          for (int j = 0; j < 3; j++) mbar_arrive_expect_tx(bar_raw(bars, j), j ? kWChunk : 2 * kWChunk);
          w2o = w2_offset();
        }
        __syncwarp();
#pragma unroll 1
        for (int r = 0; r < 3; r++) {
          const int blk = 2 * r - 2 + (wid >> 2);
          if (blk < 3) {
            if (r > 0) {
              mbar_wait(bar_raw(bars, 0), 0);
              mbar_wait(bar_raw(bars, blk), 0);
            }
            if (tid == 0 && r == 1) GT(7);
            float acc[32];
            const uint64_t db = make_desc(sbase + kW2Off + max(blk, 0) * kWChunk, kWChunk, 1024);
            wg_fence();
            wg_m64tz<0, 32>(acc, make_desc(sbase, 16, 1024), db, 0);
#pragma unroll
            for (int s = 1; s < 12; s++) wg_m64t<0, 32>(acc, make_desc(sbase + (s >> 2) * 8192 + (s & 3) * 32, 16, 1024), db + s * 128, 1);
            wg_commit();
            wg_wait<0>();
            fence_regs(acc);
            if (tid == 0) GT(19);
            const int m = (tid >> 3) & 3;
#pragma unroll
            for (int j = 0; j < 8; j += 2) {
              const int n = g2_inv(8 * (j + (m >> 1)) + (tid & 7));
              asm volatile("stmatrix.sync.aligned.m8n8.x4.trans.shared.b16 [%0], {%1,%2,%3,%4};" ::"r"(
                               sbase + kW1Off + (blk + 2) * 8192 + n * 128 + (((2 * (wid & 3) + (m & 1)) ^ (n & 7)) << 4)),
                           "r"(pack_bf16(acc[4 * j], acc[4 * j + 1])), "r"(pack_bf16(acc[4 * j + 2], acc[4 * j + 3])),
                           "r"(pack_bf16(acc[4 * j + 4], acc[4 * j + 5])), "r"(pack_bf16(acc[4 * j + 6], acc[4 * j + 7])) : "memory");
            }
            fence_proxy_async();
          }
          if (tid == 0) GT(18);
          asm volatile("bar.sync 11, 256;" ::: "memory");
          if (wid == 1 && elect_one()) {
            asm volatile("{\n.reg .pred p;\nsetp.ne.s32 p, %3, 0;\n@p cp.async.bulk.global.shared::cta.bulk_group [%0], [%1], %2;\n}\n" ::"l"(
                             wimg + (w2o + w2piece(r >> 1, q) * (kWChunk / 2))),
                         "r"(sbase + kW1Off + 16384 + (r >> 1) * (kWChunk / 2)), "r"(kWChunk / 2), "r"(r) : "memory");
            asm volatile("cp.async.bulk.commit_group;" ::: "memory");
          }
          __syncwarp();
        }
        if (wid == 1) {
          asm volatile("bar.arrive 10, 64;" ::: "memory");
          if (elect_one()) asm volatile("cp.async.bulk.wait_group.read 0;" ::: "memory");
          if (tid == 32) GT(31);
          __syncwarp();
          asm volatile("bar.arrive 12, 64;" ::: "memory");
        }
      }
    }
    __syncwarp();
    if (wid < 4) asm volatile("bar.sync 0, 160;" ::: "memory");
    else asm volatile("bar.sync 14, 160;" ::: "memory");
    asm volatile("setmaxnreg.inc.sync.aligned.u32 240;");
    consumer(wid >> 2, out, wimg, sbase, zero, tm, tt);
  }
}

}

typedef CUresult (*PFN_encodeTiled)(CUtensorMap*, CUtensorMapDataType, cuuint32_t, void*, const cuuint64_t*,
                                    const cuuint64_t*, const cuuint32_t*, const cuuint32_t*, CUtensorMapInterleave,
                                    CUtensorMapSwizzle, CUtensorMapL2promotion, CUtensorMapFloatOOBfill);

extern "C" void kernel_launch(void* const* d_in, const int* in_sizes, int n_in, void* d_out, int out_size) {
  const __nv_bfloat16* x = (const __nv_bfloat16*)d_in[0];
  const __nv_bfloat16* wqkv = (const __nv_bfloat16*)d_in[1];
  const __nv_bfloat16* wo = (const __nv_bfloat16*)d_in[2];
  __nv_bfloat16* out = (__nv_bfloat16*)d_out;

  static PFN_encodeTiled encode = nullptr;
  static int num_sms = 0;
  static uint8_t* wimg = nullptr;
  if (!encode) {
    void* fn = nullptr;
    cudaDriverEntryPointQueryResult qres;
    cudaGetDriverEntryPoint("cuTensorMapEncodeTiled", &fn, cudaEnableDefault, &qres);
    encode = (PFN_encodeTiled)fn;
    cudaFuncSetAttribute(nat::nat_kernel, cudaFuncAttributeMaxDynamicSharedMemorySize, nat::kSmemBytes);
    cudaGetSymbolAddress((void**)&wimg, nat::g_wimg32);
    int dev = 0;
    cudaGetDevice(&dev);
    cudaDeviceGetAttribute(&num_sms, cudaDevAttrMultiProcessorCount, dev);
  }
  nat::Maps tm;
  cuuint32_t estr[5] = {1, 1, 1, 1, 1};
  {
    cuuint64_t vdim[5] = {48, 2, 105, 2, 112}, udim[5] = {48, 2, 112, 2, 105};
    cuuint64_t vstr[4] = {7 * 768, 768, 224 * 384, 2 * 224 * 384}, ustr[4] = {7 * 768, 2 * 224 * 384, 224 * 384, 768};
    CUtensorMap* maps[4] = {&tm.v6, &tm.v2, &tm.v14, &tm.u8};
    for (int i = 0; i < 4; i++) {
      cuuint32_t box[5] = {4, 2, i < 3 ? 4u : 8u, 1, i == 0 ? 6u : i == 1 ? 2u : i == 2 ? 14u : 3u};
      encode(maps[i], CU_TENSOR_MAP_DATA_TYPE_UINT32, 5, (void*)x, i < 3 ? vdim : udim, i < 3 ? vstr : ustr, box, estr,
             CU_TENSOR_MAP_INTERLEAVE_16B, CU_TENSOR_MAP_SWIZZLE_128B, CU_TENSOR_MAP_L2_PROMOTION_L2_128B, CU_TENSOR_MAP_FLOAT_OOB_FILL_NONE);
    }
  }
  for (int i = 0; i < 8; i++) {
    const cuuint32_t row = 224 * 384;
    const cuuint32_t shape[8][6] = {{2, 8, 4, 2 * row, 768, 4 * row}, {2, 8, 3, row, 768, 2 * row},     {2, 8, 1, 2 * row, 768, 4 * row},
                                    {8, 2, 3, 2 * row, 4 * 384, 384}, {8, 2, 1, 2 * row, 5 * 384, 384}, {4, 2, 3, 4 * row, 2 * row, 128},
                                    {4, 2, 3, 768, row, 128},         {4, 2, 3, 768, 2 * row, 128}};
    const cuuint32_t* sh = shape[i];
    cuuint64_t dim[5] = {64, sh[0], sh[1], sh[2], 224 * 224 * 3};
    cuuint64_t str[4] = {sh[3], sh[4], sh[5], 128};
    cuuint32_t box[5] = {64, sh[0], sh[1], sh[2], 1};
    encode(tm.px + i, CU_TENSOR_MAP_DATA_TYPE_BFLOAT16, 5, i < 5 ? (void*)x : (void*)out, dim, str, box, estr, CU_TENSOR_MAP_INTERLEAVE_NONE,
           CU_TENSOR_MAP_SWIZZLE_128B, i < 5 ? CU_TENSOR_MAP_L2_PROMOTION_L2_128B : CU_TENSOR_MAP_L2_PROMOTION_NONE,
           CU_TENSOR_MAP_FLOAT_OOB_FILL_NONE);
  }
  for (int i = 0; i < 2; i++) {
    cuuint64_t dim[2] = {i ? 192u : 576u, 192}, str[1] = {i ? 384u : 1152u};
    cuuint32_t box[2] = {64, i ? 192u : 64u};
    encode(i ? &tm.wo : &tm.wv, CU_TENSOR_MAP_DATA_TYPE_BFLOAT16, 2, i ? (void*)wo : (void*)wqkv, dim, str, box, estr,
           CU_TENSOR_MAP_INTERLEAVE_NONE, CU_TENSOR_MAP_SWIZZLE_128B, CU_TENSOR_MAP_L2_PROMOTION_L2_256B, CU_TENSOR_MAP_FLOAT_OOB_FILL_NONE);
  }
  nat::TileTable tt;
  nat::make_tiles(tt);
  const int grid = nat::kCtas;
  if (num_sms >= grid) {
    nat::nat_kernel<<<grid, 384, nat::kSmemBytes>>>(x, out, wqkv, wo, wimg, 0u, tm, tt);
  } else {
    nat::fold_kernel<<<27, 256>>>(wqkv, wo, wimg);
    nat::nat_kernel<<<grid, 384, nat::kSmemBytes>>>(x, out, nullptr, nullptr, wimg, 0u, tm, tt);
  }
}
```

```cpp
#include <cuda_runtime.h>
#include <cuda_bf16.h>
#include <cuda.h>
#include <stdint.h>

#define NAT_P1 2
#define NAT_P2 4
#define NAT_H0 2
#define NAT_T0 2100
#define NAT_TD 1200
#define NAT_TW2 4650
#define NAT_TX2 3800
#define NAT_X1P 6
#define NAT_PK 3
#define NAT_HP 1800
#define NAT_PFD 400
#define NAT_XW 200
#define NAT_MP 3
#define NAT_D0 1
#define NAT_TH 0
#define NAT_TM 1300
#define NAT_QA 1
#define NAT_SB 0
namespace nat {

constexpr int kW = 224, kC = 192;
constexpr int kCtas = 132;
constexpr int kTilesPerCta = 6;
constexpr float kAlpha = 0.07216878364870322f * 1.4426950408889634f;
constexpr uint32_t kChunkBytes = 13 * 1024;
constexpr uint32_t kWChunk = 192 * 128;
constexpr uint32_t kWBytes = 3 * kWChunk;
constexpr uint32_t kW1Off = 6 * kChunkBytes;
constexpr uint32_t kW2Off = kW1Off + kWBytes;
constexpr uint32_t kXOff = kW2Off + kWChunk;
constexpr uint32_t kBarOff = kW2Off + kWBytes;
constexpr uint32_t kProfOff = kBarOff + 208;
constexpr uint32_t kSmemBytes = kBarOff + 1024;

static_assert(kW1Off % 1024 == 0 && kW2Off % 1024 == 0 && kChunkBytes % 1024 == 0, "swizzle alignment");
static_assert(kSmemBytes <= 232448, "smem");

constexpr uint32_t kEmpty = 0xFFFFFFFFu;
#define NAT_R8(v) v, v, v, v, v, v, v, v
#define NAT_R2K(v) NAT_R8(NAT_R8(NAT_R8(v))), NAT_R8(NAT_R8(NAT_R8(v))), NAT_R8(NAT_R8(NAT_R8(v))), NAT_R8(NAT_R8(NAT_R8(v)))
#define NAT_IMG NAT_R8(NAT_R2K(kEmpty)), NAT_R2K(kEmpty)
__device__ __align__(1024) uint32_t g_wimg32[3 * kWBytes / 4] = {NAT_IMG, NAT_IMG, NAT_IMG};
static_assert(kWBytes / 4 == 9 * 2048, "initialiser");
__device__ __align__(128) uint32_t g_flag[96];
__device__ __forceinline__ uint32_t w2_offset() {
  uint32_t v;
  asm volatile("ld.relaxed.gpu.global.u32 %0, [%1];" : "=r"(v) : "l"(g_flag + 64) : "memory");
  return (1 + v) * kWBytes;
}

#define PROFS(id, wgid, slotid) do { } while (0)
#define PROF(wgid, slotid) do { } while (0)
#define PROF_DUMP(wgid) do { } while (0)

#define GT(slotid) do { } while (0)
#define GT_DUMP() do { } while (0)

__device__ __forceinline__ uint32_t smem_u32(const void* p) { return (uint32_t)__cvta_generic_to_shared(p); }

__device__ __forceinline__ void mbar_init(uint32_t bar, uint32_t count) {
  asm volatile("mbarrier.init.shared::cta.b64 [%0], %1;" ::"r"(bar), "r"(count) : "memory");
}
__device__ __forceinline__ void mbar_arrive(uint32_t bar) {
  asm volatile("mbarrier.arrive.shared::cta.b64 _, [%0];" ::"r"(bar) : "memory");
}
__device__ __forceinline__ void mbar_arrive_expect_tx(uint32_t bar, uint32_t bytes) {
  asm volatile("mbarrier.arrive.expect_tx.shared::cta.b64 _, [%0], %1;" ::"r"(bar), "r"(bytes) : "memory");
}
__device__ __forceinline__ void mbar_wait(uint32_t bar, uint32_t parity) {
  uint32_t ok;
  uint32_t it = 0;
  do {
    asm volatile(
        "{\n.reg .pred p;\n"
        "mbarrier.try_wait.parity.shared::cta.b64 p, [%1], %2;\n"
        "selp.u32 %0, 1, 0, p;\n}\n"
        : "=r"(ok)
        : "r"(bar), "r"(parity)
        : "memory");
    if (++it > (1u << 24)) break;
  } while (!ok);
}
__device__ __forceinline__ uint32_t mbar_test(uint32_t bar, uint32_t parity) {
  uint32_t ok;
  asm volatile("{\n.reg .pred p;\nmbarrier.test_wait.parity.shared::cta.b64 p, [%1], %2;\nselp.u32 %0, 1, 0, p;\n}\n"
               : "=r"(ok) : "r"(bar), "r"(parity) : "memory");
  return ok;
}
__device__ __forceinline__ void mbar_wait_if(uint32_t ok, uint32_t bar, uint32_t parity) {
  if (!__all_sync(0xffffffffu, ok)) mbar_wait(bar, parity);
}
__device__ __forceinline__ bool elect_one() {
  uint32_t r;
  asm volatile("{\n.reg .pred p;\nelect.sync _|p, 0xffffffff;\nselp.u32 %0, 1, 0, p;\n}\n" : "=r"(r));
  return r != 0;
}
__device__ __forceinline__ void nb_arrive(int id) { asm volatile("bar.arrive %0, 256;" ::"r"(id) : "memory"); }
__device__ __forceinline__ void nb_sync(int id) { asm volatile("bar.sync %0, 256;" ::"r"(id) : "memory"); }
__device__ __forceinline__ void nb_arrive_p(int id) { asm volatile("bar.arrive %0, 160;" ::"r"(id) : "memory"); }
__device__ __forceinline__ void nb_sync_p(int id) { asm volatile("bar.sync %0, 160;" ::"r"(id) : "memory"); }
__device__ __forceinline__ void fence_proxy_async() { asm volatile("fence.proxy.async.shared::cta;" ::: "memory"); }

__device__ __forceinline__ void tma_load_5d(uint32_t dst, const CUtensorMap* map, uint32_t bar, int c0, int c1, int c2,
                                            int c3, int c4) {
  asm volatile(
      "cp.async.bulk.tensor.5d.shared::cluster.global.tile.mbarrier::complete_tx::bytes "
      "[%0], [%1, {%3, %4, %5, %6, %7}], [%2];"
      ::"r"(dst), "l"((uint64_t)map), "r"(bar), "r"(c0), "r"(c1), "r"(c2), "r"(c3), "r"(c4)
      : "memory");
}
__device__ __forceinline__ void bulk_load(uint32_t dst, const void* src, uint32_t bytes, uint32_t bar) {
  asm volatile("cp.async.bulk.shared::cluster.global.mbarrier::complete_tx::bytes [%0], [%1], %2, [%3];"
               ::"r"(dst), "l"((uint64_t)src), "r"(bytes), "r"(bar)
               : "memory");
}

__device__ __forceinline__ void wg_fence() { asm volatile("wgmma.fence.sync.aligned;" ::: "memory"); }
__device__ __forceinline__ void wg_commit() { asm volatile("wgmma.commit_group.sync.aligned;" ::: "memory"); }
template <int N>
__device__ __forceinline__ void wg_wait() { asm volatile("wgmma.wait_group.sync.aligned %0;" ::"n"(N) : "memory"); }

template <int N>
__device__ __forceinline__ void fence_regs(float (&d)[N]) {
#pragma unroll
  for (int i = 0; i < N; i++) asm volatile("" : "+f"(d[i])::"memory");
}
template <int N>
__device__ __forceinline__ void keep_regs(uint32_t (&d)[N]) {
#pragma unroll
  for (int i = 0; i < N; i++) asm volatile("" : "+r"(d[i])::"memory");
}

__device__ __forceinline__ uint32_t pack_bf16(float lo, float hi) {
  uint32_t d;
  asm("cvt.rn.bf16x2.f32 %0, %1, %2;" : "=r"(d) : "f"(hi), "f"(lo));
  return d;
}
__device__ __forceinline__ float ex2(float x) {
  float y;
  asm("ex2.approx.ftz.f32 %0, %1;" : "=f"(y) : "f"(x));
  return y;
}
__device__ __forceinline__ float rcp_approx(float x) {
  float y;
  asm("rcp.approx.ftz.f32 %0, %1;" : "=f"(y) : "f"(x));
  return y;
}
__device__ __forceinline__ uint4 ldg128_nc(const void* p) {
  uint4 v;
  asm volatile("ld.global.nc.v4.u32 {%0,%1,%2,%3}, [%4];" : "=r"(v.x), "=r"(v.y), "=r"(v.z), "=r"(v.w) : "l"(p));
  return v;
}
__device__ __forceinline__ void stg128(void* p, uint32_t a, uint32_t b, uint32_t c, uint32_t d) {
  asm volatile("st.global.v4.u32 [%0], {%1,%2,%3,%4};" ::"l"(p), "r"(a), "r"(b), "r"(c), "r"(d) : "memory");
}

__device__ __forceinline__ long long clk64() {
  long long c;
  asm volatile("mov.u64 %0, %clock64;" : "=l"(c)::"memory");
  return c;
}
__device__ __forceinline__ void sched_fence() { while (clk64() < 0) { } }

__device__ __forceinline__ uint64_t make_desc(uint32_t addr, uint32_t lbo, uint32_t sbo, uint32_t mode = 1) {
  return (uint64_t)((addr & 0x3FFFF) >> 4) | ((uint64_t)(lbo >> 4) << 16) | ((uint64_t)(sbo >> 4) << 32) |
         ((uint64_t)mode << 62);
}

template <int OFF, int NN>
__device__ __forceinline__ void wg_m192(float (&d)[NN], uint64_t desc_a, uint64_t desc_b, int scale_d) {
  asm volatile(
      "{\n.reg .pred p;\nsetp.ne.b32 p, %98, 0;\n"
      "wgmma.mma_async.sync.aligned.m64n192k16.f32.bf16.bf16 "
      "{%0,%1,%2,%3,%4,%5,%6,%7,%8,%9,%10,%11,%12,%13,%14,%15,"
      "%16,%17,%18,%19,%20,%21,%22,%23,%24,%25,%26,%27,%28,%29,%30,%31,"
      "%32,%33,%34,%35,%36,%37,%38,%39,%40,%41,%42,%43,%44,%45,%46,%47,"
      "%48,%49,%50,%51,%52,%53,%54,%55,%56,%57,%58,%59,%60,%61,%62,%63,"
      "%64,%65,%66,%67,%68,%69,%70,%71,%72,%73,%74,%75,%76,%77,%78,%79,"
      "%80,%81,%82,%83,%84,%85,%86,%87,%88,%89,%90,%91,%92,%93,%94,%95}, "
      "%96, %97, p, 1, 1, 0, 0;\n}\n"
      : "+f"(d[OFF + 0]), "+f"(d[OFF + 1]), "+f"(d[OFF + 2]), "+f"(d[OFF + 3]), "+f"(d[OFF + 4]), "+f"(d[OFF + 5]),
        "+f"(d[OFF + 6]), "+f"(d[OFF + 7]), "+f"(d[OFF + 8]), "+f"(d[OFF + 9]), "+f"(d[OFF + 10]), "+f"(d[OFF + 11]),
        "+f"(d[OFF + 12]), "+f"(d[OFF + 13]), "+f"(d[OFF + 14]), "+f"(d[OFF + 15]), "+f"(d[OFF + 16]), "+f"(d[OFF + 17]),
        "+f"(d[OFF + 18]), "+f"(d[OFF + 19]), "+f"(d[OFF + 20]), "+f"(d[OFF + 21]), "+f"(d[OFF + 22]), "+f"(d[OFF + 23]),
        "+f"(d[OFF + 24]), "+f"(d[OFF + 25]), "+f"(d[OFF + 26]), "+f"(d[OFF + 27]), "+f"(d[OFF + 28]), "+f"(d[OFF + 29]),
        "+f"(d[OFF + 30]), "+f"(d[OFF + 31]), "+f"(d[OFF + 32]), "+f"(d[OFF + 33]), "+f"(d[OFF + 34]), "+f"(d[OFF + 35]),
        "+f"(d[OFF + 36]), "+f"(d[OFF + 37]), "+f"(d[OFF + 38]), "+f"(d[OFF + 39]), "+f"(d[OFF + 40]), "+f"(d[OFF + 41]),
        "+f"(d[OFF + 42]), "+f"(d[OFF + 43]), "+f"(d[OFF + 44]), "+f"(d[OFF + 45]), "+f"(d[OFF + 46]), "+f"(d[OFF + 47]),
        "+f"(d[OFF + 48]), "+f"(d[OFF + 49]), "+f"(d[OFF + 50]), "+f"(d[OFF + 51]), "+f"(d[OFF + 52]), "+f"(d[OFF + 53]),
        "+f"(d[OFF + 54]), "+f"(d[OFF + 55]), "+f"(d[OFF + 56]), "+f"(d[OFF + 57]), "+f"(d[OFF + 58]), "+f"(d[OFF + 59]),
        "+f"(d[OFF + 60]), "+f"(d[OFF + 61]), "+f"(d[OFF + 62]), "+f"(d[OFF + 63]), "+f"(d[OFF + 64]), "+f"(d[OFF + 65]),
        "+f"(d[OFF + 66]), "+f"(d[OFF + 67]), "+f"(d[OFF + 68]), "+f"(d[OFF + 69]), "+f"(d[OFF + 70]), "+f"(d[OFF + 71]),
        "+f"(d[OFF + 72]), "+f"(d[OFF + 73]), "+f"(d[OFF + 74]), "+f"(d[OFF + 75]), "+f"(d[OFF + 76]), "+f"(d[OFF + 77]),
        "+f"(d[OFF + 78]), "+f"(d[OFF + 79]), "+f"(d[OFF + 80]), "+f"(d[OFF + 81]), "+f"(d[OFF + 82]), "+f"(d[OFF + 83]),
        "+f"(d[OFF + 84]), "+f"(d[OFF + 85]), "+f"(d[OFF + 86]), "+f"(d[OFF + 87]), "+f"(d[OFF + 88]), "+f"(d[OFF + 89]),
        "+f"(d[OFF + 90]), "+f"(d[OFF + 91]), "+f"(d[OFF + 92]), "+f"(d[OFF + 93]), "+f"(d[OFF + 94]), "+f"(d[OFF + 95])
      : "l"(desc_a), "l"(desc_b), "r"(scale_d));
}

template <int OFF, int NN>
__device__ __forceinline__ void wg_m192z(float (&d)[NN], uint64_t desc_a, uint64_t desc_b, int scale_d) {
  asm volatile(
      "{\n.reg .pred p;\nsetp.ne.b32 p, %98, 0;\n"
      "wgmma.mma_async.sync.aligned.m64n192k16.f32.bf16.bf16 "
      "{%0,%1,%2,%3,%4,%5,%6,%7,%8,%9,%10,%11,%12,%13,%14,%15,"
      "%16,%17,%18,%19,%20,%21,%22,%23,%24,%25,%26,%27,%28,%29,%30,%31,"
      "%32,%33,%34,%35,%36,%37,%38,%39,%40,%41,%42,%43,%44,%45,%46,%47,"
      "%48,%49,%50,%51,%52,%53,%54,%55,%56,%57,%58,%59,%60,%61,%62,%63,"
      "%64,%65,%66,%67,%68,%69,%70,%71,%72,%73,%74,%75,%76,%77,%78,%79,"
      "%80,%81,%82,%83,%84,%85,%86,%87,%88,%89,%90,%91,%92,%93,%94,%95}, "
      "%96, %97, p, 1, 1, 0, 0;\n}\n"
      : "=f"(d[OFF + 0]), "=f"(d[OFF + 1]), "=f"(d[OFF + 2]), "=f"(d[OFF + 3]), "=f"(d[OFF + 4]), "=f"(d[OFF + 5]),
        "=f"(d[OFF + 6]), "=f"(d[OFF + 7]), "=f"(d[OFF + 8]), "=f"(d[OFF + 9]), "=f"(d[OFF + 10]), "=f"(d[OFF + 11]),
        "=f"(d[OFF + 12]), "=f"(d[OFF + 13]), "=f"(d[OFF + 14]), "=f"(d[OFF + 15]), "=f"(d[OFF + 16]), "=f"(d[OFF + 17]),
        "=f"(d[OFF + 18]), "=f"(d[OFF + 19]), "=f"(d[OFF + 20]), "=f"(d[OFF + 21]), "=f"(d[OFF + 22]), "=f"(d[OFF + 23]),
        "=f"(d[OFF + 24]), "=f"(d[OFF + 25]), "=f"(d[OFF + 26]), "=f"(d[OFF + 27]), "=f"(d[OFF + 28]), "=f"(d[OFF + 29]),
        "=f"(d[OFF + 30]), "=f"(d[OFF + 31]), "=f"(d[OFF + 32]), "=f"(d[OFF + 33]), "=f"(d[OFF + 34]), "=f"(d[OFF + 35]),
        "=f"(d[OFF + 36]), "=f"(d[OFF + 37]), "=f"(d[OFF + 38]), "=f"(d[OFF + 39]), "=f"(d[OFF + 40]), "=f"(d[OFF + 41]),
        "=f"(d[OFF + 42]), "=f"(d[OFF + 43]), "=f"(d[OFF + 44]), "=f"(d[OFF + 45]), "=f"(d[OFF + 46]), "=f"(d[OFF + 47]),
        "=f"(d[OFF + 48]), "=f"(d[OFF + 49]), "=f"(d[OFF + 50]), "=f"(d[OFF + 51]), "=f"(d[OFF + 52]), "=f"(d[OFF + 53]),
        "=f"(d[OFF + 54]), "=f"(d[OFF + 55]), "=f"(d[OFF + 56]), "=f"(d[OFF + 57]), "=f"(d[OFF + 58]), "=f"(d[OFF + 59]),
        "=f"(d[OFF + 60]), "=f"(d[OFF + 61]), "=f"(d[OFF + 62]), "=f"(d[OFF + 63]), "=f"(d[OFF + 64]), "=f"(d[OFF + 65]),
        "=f"(d[OFF + 66]), "=f"(d[OFF + 67]), "=f"(d[OFF + 68]), "=f"(d[OFF + 69]), "=f"(d[OFF + 70]), "=f"(d[OFF + 71]),
        "=f"(d[OFF + 72]), "=f"(d[OFF + 73]), "=f"(d[OFF + 74]), "=f"(d[OFF + 75]), "=f"(d[OFF + 76]), "=f"(d[OFF + 77]),
        "=f"(d[OFF + 78]), "=f"(d[OFF + 79]), "=f"(d[OFF + 80]), "=f"(d[OFF + 81]), "=f"(d[OFF + 82]), "=f"(d[OFF + 83]),
        "=f"(d[OFF + 84]), "=f"(d[OFF + 85]), "=f"(d[OFF + 86]), "=f"(d[OFF + 87]), "=f"(d[OFF + 88]), "=f"(d[OFF + 89]),
        "=f"(d[OFF + 90]), "=f"(d[OFF + 91]), "=f"(d[OFF + 92]), "=f"(d[OFF + 93]), "=f"(d[OFF + 94]), "=f"(d[OFF + 95])
      : "l"(desc_a), "l"(desc_b), "r"(scale_d));
}

template <int OFF, int NN>
__device__ __forceinline__ void wg_m64t(float (&d)[NN], uint64_t desc_a, uint64_t desc_b, int scale_d) {
  asm volatile(
      "{\n.reg .pred p;\nsetp.ne.b32 p, %34, 0;\n"
      "wgmma.mma_async.sync.aligned.m64n64k16.f32.bf16.bf16 "
      "{%0,%1,%2,%3,%4,%5,%6,%7,%8,%9,%10,%11,%12,%13,%14,%15,"
      "%16,%17,%18,%19,%20,%21,%22,%23,%24,%25,%26,%27,%28,%29,%30,%31}, "
      "%32, %33, p, 1, 1, 0, 1;\n}\n"
      : "+f"(d[OFF + 0]), "+f"(d[OFF + 1]), "+f"(d[OFF + 2]), "+f"(d[OFF + 3]), "+f"(d[OFF + 4]), "+f"(d[OFF + 5]),
        "+f"(d[OFF + 6]), "+f"(d[OFF + 7]), "+f"(d[OFF + 8]), "+f"(d[OFF + 9]), "+f"(d[OFF + 10]), "+f"(d[OFF + 11]),
        "+f"(d[OFF + 12]), "+f"(d[OFF + 13]), "+f"(d[OFF + 14]), "+f"(d[OFF + 15]), "+f"(d[OFF + 16]), "+f"(d[OFF + 17]),
        "+f"(d[OFF + 18]), "+f"(d[OFF + 19]), "+f"(d[OFF + 20]), "+f"(d[OFF + 21]), "+f"(d[OFF + 22]), "+f"(d[OFF + 23]),
        "+f"(d[OFF + 24]), "+f"(d[OFF + 25]), "+f"(d[OFF + 26]), "+f"(d[OFF + 27]), "+f"(d[OFF + 28]), "+f"(d[OFF + 29]),
        "+f"(d[OFF + 30]), "+f"(d[OFF + 31])
      : "l"(desc_a), "l"(desc_b), "r"(scale_d));
}

template <int OFF, int NN>
__device__ __forceinline__ void wg_m64tz(float (&d)[NN], uint64_t desc_a, uint64_t desc_b, int scale_d) {
  asm volatile(
      "{\n.reg .pred p;\nsetp.ne.b32 p, %34, 0;\n"
      "wgmma.mma_async.sync.aligned.m64n64k16.f32.bf16.bf16 "
      "{%0,%1,%2,%3,%4,%5,%6,%7,%8,%9,%10,%11,%12,%13,%14,%15,"
      "%16,%17,%18,%19,%20,%21,%22,%23,%24,%25,%26,%27,%28,%29,%30,%31}, "
      "%32, %33, p, 1, 1, 0, 1;\n}\n"
      : "=f"(d[OFF + 0]), "=f"(d[OFF + 1]), "=f"(d[OFF + 2]), "=f"(d[OFF + 3]), "=f"(d[OFF + 4]), "=f"(d[OFF + 5]),
        "=f"(d[OFF + 6]), "=f"(d[OFF + 7]), "=f"(d[OFF + 8]), "=f"(d[OFF + 9]), "=f"(d[OFF + 10]), "=f"(d[OFF + 11]),
        "=f"(d[OFF + 12]), "=f"(d[OFF + 13]), "=f"(d[OFF + 14]), "=f"(d[OFF + 15]), "=f"(d[OFF + 16]), "=f"(d[OFF + 17]),
        "=f"(d[OFF + 18]), "=f"(d[OFF + 19]), "=f"(d[OFF + 20]), "=f"(d[OFF + 21]), "=f"(d[OFF + 22]), "=f"(d[OFF + 23]),
        "=f"(d[OFF + 24]), "=f"(d[OFF + 25]), "=f"(d[OFF + 26]), "=f"(d[OFF + 27]), "=f"(d[OFF + 28]), "=f"(d[OFF + 29]),
        "=f"(d[OFF + 30]), "=f"(d[OFF + 31])
      : "l"(desc_a), "l"(desc_b), "r"(scale_d));
}

template <int OFF, int NN>
__device__ __forceinline__ void wg_d96(float (&d)[NN], uint32_t a0, uint32_t a1, uint32_t a2, uint32_t a3,
                                       uint64_t desc_b, int scale_d) {
  asm volatile(
      "{\n.reg .pred p;\nsetp.ne.b32 p, %53, 0;\n"
      "wgmma.mma_async.sync.aligned.m64n96k16.f32.bf16.bf16 "
      "{%0,%1,%2,%3,%4,%5,%6,%7,%8,%9,%10,%11,%12,%13,%14,%15,"
      "%16,%17,%18,%19,%20,%21,%22,%23,%24,%25,%26,%27,%28,%29,%30,%31,"
      "%32,%33,%34,%35,%36,%37,%38,%39,%40,%41,%42,%43,%44,%45,%46,%47}, "
      "{%48,%49,%50,%51}, %52, p, 1, 1, 0;\n}\n"
      : "+f"(d[OFF + 0]), "+f"(d[OFF + 1]), "+f"(d[OFF + 2]), "+f"(d[OFF + 3]), "+f"(d[OFF + 4]), "+f"(d[OFF + 5]),
        "+f"(d[OFF + 6]), "+f"(d[OFF + 7]), "+f"(d[OFF + 8]), "+f"(d[OFF + 9]), "+f"(d[OFF + 10]), "+f"(d[OFF + 11]),
        "+f"(d[OFF + 12]), "+f"(d[OFF + 13]), "+f"(d[OFF + 14]), "+f"(d[OFF + 15]), "+f"(d[OFF + 16]), "+f"(d[OFF + 17]),
        "+f"(d[OFF + 18]), "+f"(d[OFF + 19]), "+f"(d[OFF + 20]), "+f"(d[OFF + 21]), "+f"(d[OFF + 22]), "+f"(d[OFF + 23]),
        "+f"(d[OFF + 24]), "+f"(d[OFF + 25]), "+f"(d[OFF + 26]), "+f"(d[OFF + 27]), "+f"(d[OFF + 28]), "+f"(d[OFF + 29]),
        "+f"(d[OFF + 30]), "+f"(d[OFF + 31]), "+f"(d[OFF + 32]), "+f"(d[OFF + 33]), "+f"(d[OFF + 34]), "+f"(d[OFF + 35]),
        "+f"(d[OFF + 36]), "+f"(d[OFF + 37]), "+f"(d[OFF + 38]), "+f"(d[OFF + 39]), "+f"(d[OFF + 40]), "+f"(d[OFF + 41]),
        "+f"(d[OFF + 42]), "+f"(d[OFF + 43]), "+f"(d[OFF + 44]), "+f"(d[OFF + 45]), "+f"(d[OFF + 46]), "+f"(d[OFF + 47])
      : "r"(a0), "r"(a1), "r"(a2), "r"(a3), "l"(desc_b), "r"(scale_d));
}

template <int OFF, int NN>
__device__ __forceinline__ void wg_d96z(float (&d)[NN], uint32_t a0, uint32_t a1, uint32_t a2, uint32_t a3,
                                       uint64_t desc_b, int scale_d) {
  asm volatile(
      "{\n.reg .pred p;\nsetp.ne.b32 p, %53, 0;\n"
      "wgmma.mma_async.sync.aligned.m64n96k16.f32.bf16.bf16 "
      "{%0,%1,%2,%3,%4,%5,%6,%7,%8,%9,%10,%11,%12,%13,%14,%15,"
      "%16,%17,%18,%19,%20,%21,%22,%23,%24,%25,%26,%27,%28,%29,%30,%31,"
      "%32,%33,%34,%35,%36,%37,%38,%39,%40,%41,%42,%43,%44,%45,%46,%47}, "
      "{%48,%49,%50,%51}, %52, p, 1, 1, 0;\n}\n"
      : "=f"(d[OFF + 0]), "=f"(d[OFF + 1]), "=f"(d[OFF + 2]), "=f"(d[OFF + 3]), "=f"(d[OFF + 4]), "=f"(d[OFF + 5]),
        "=f"(d[OFF + 6]), "=f"(d[OFF + 7]), "=f"(d[OFF + 8]), "=f"(d[OFF + 9]), "=f"(d[OFF + 10]), "=f"(d[OFF + 11]),
        "=f"(d[OFF + 12]), "=f"(d[OFF + 13]), "=f"(d[OFF + 14]), "=f"(d[OFF + 15]), "=f"(d[OFF + 16]), "=f"(d[OFF + 17]),
        "=f"(d[OFF + 18]), "=f"(d[OFF + 19]), "=f"(d[OFF + 20]), "=f"(d[OFF + 21]), "=f"(d[OFF + 22]), "=f"(d[OFF + 23]),
        "=f"(d[OFF + 24]), "=f"(d[OFF + 25]), "=f"(d[OFF + 26]), "=f"(d[OFF + 27]), "=f"(d[OFF + 28]), "=f"(d[OFF + 29]),
        "=f"(d[OFF + 30]), "=f"(d[OFF + 31]), "=f"(d[OFF + 32]), "=f"(d[OFF + 33]), "=f"(d[OFF + 34]), "=f"(d[OFF + 35]),
        "=f"(d[OFF + 36]), "=f"(d[OFF + 37]), "=f"(d[OFF + 38]), "=f"(d[OFF + 39]), "=f"(d[OFF + 40]), "=f"(d[OFF + 41]),
        "=f"(d[OFF + 42]), "=f"(d[OFF + 43]), "=f"(d[OFF + 44]), "=f"(d[OFF + 45]), "=f"(d[OFF + 46]), "=f"(d[OFF + 47])
      : "r"(a0), "r"(a1), "r"(a2), "r"(a3), "l"(desc_b), "r"(scale_d));
}

template <int OFF, int NN>
__device__ __forceinline__ void wg_s104(float (&d)[NN], uint32_t a0, uint32_t a1, uint32_t a2, uint32_t a3,
                                       uint64_t desc_b, int scale_d, uint32_t meta) {
  asm volatile(
      "{\n.reg .pred p;\nsetp.ne.b32 p, %57, 0;\n"
      "wgmma.mma_async.sp.sync.aligned.m64n104k32.f32.bf16.bf16 "
      "{%0,%1,%2,%3,%4,%5,%6,%7,%8,%9,%10,%11,%12,%13,%14,%15,"
      "%16,%17,%18,%19,%20,%21,%22,%23,%24,%25,%26,%27,%28,%29,%30,%31,"
      "%32,%33,%34,%35,%36,%37,%38,%39,%40,%41,%42,%43,%44,%45,%46,%47,"
      "%48,%49,%50,%51}, "
      "{%52,%53,%54,%55}, %56, %58, 0, p, 1, 1, 0;\n}\n"
      : "+f"(d[OFF + 0]), "+f"(d[OFF + 1]), "+f"(d[OFF + 2]), "+f"(d[OFF + 3]), "+f"(d[OFF + 4]), "+f"(d[OFF + 5]),
        "+f"(d[OFF + 6]), "+f"(d[OFF + 7]), "+f"(d[OFF + 8]), "+f"(d[OFF + 9]), "+f"(d[OFF + 10]), "+f"(d[OFF + 11]),
        "+f"(d[OFF + 12]), "+f"(d[OFF + 13]), "+f"(d[OFF + 14]), "+f"(d[OFF + 15]), "+f"(d[OFF + 16]), "+f"(d[OFF + 17]),
        "+f"(d[OFF + 18]), "+f"(d[OFF + 19]), "+f"(d[OFF + 20]), "+f"(d[OFF + 21]), "+f"(d[OFF + 22]), "+f"(d[OFF + 23]),
        "+f"(d[OFF + 24]), "+f"(d[OFF + 25]), "+f"(d[OFF + 26]), "+f"(d[OFF + 27]), "+f"(d[OFF + 28]), "+f"(d[OFF + 29]),
        "+f"(d[OFF + 30]), "+f"(d[OFF + 31]), "+f"(d[OFF + 32]), "+f"(d[OFF + 33]), "+f"(d[OFF + 34]), "+f"(d[OFF + 35]),
        "+f"(d[OFF + 36]), "+f"(d[OFF + 37]), "+f"(d[OFF + 38]), "+f"(d[OFF + 39]), "+f"(d[OFF + 40]), "+f"(d[OFF + 41]),
        "+f"(d[OFF + 42]), "+f"(d[OFF + 43]), "+f"(d[OFF + 44]), "+f"(d[OFF + 45]), "+f"(d[OFF + 46]), "+f"(d[OFF + 47]),
        "+f"(d[OFF + 48]), "+f"(d[OFF + 49]), "+f"(d[OFF + 50]), "+f"(d[OFF + 51])
      : "r"(a0), "r"(a1), "r"(a2), "r"(a3), "l"(desc_b), "r"(scale_d), "r"(meta));
}

template <int OFF, int NN>
__device__ __forceinline__ void wg_s104z(float (&d)[NN], uint32_t a0, uint32_t a1, uint32_t a2, uint32_t a3,
                                       uint64_t desc_b, int scale_d, uint32_t meta) {
  asm volatile(
      "{\n.reg .pred p;\nsetp.ne.b32 p, %57, 0;\n"
      "wgmma.mma_async.sp.sync.aligned.m64n104k32.f32.bf16.bf16 "
      "{%0,%1,%2,%3,%4,%5,%6,%7,%8,%9,%10,%11,%12,%13,%14,%15,"
      "%16,%17,%18,%19,%20,%21,%22,%23,%24,%25,%26,%27,%28,%29,%30,%31,"
      "%32,%33,%34,%35,%36,%37,%38,%39,%40,%41,%42,%43,%44,%45,%46,%47,"
      "%48,%49,%50,%51}, "
      "{%52,%53,%54,%55}, %56, %58, 0, p, 1, 1, 0;\n}\n"
      : "=f"(d[OFF + 0]), "=f"(d[OFF + 1]), "=f"(d[OFF + 2]), "=f"(d[OFF + 3]), "=f"(d[OFF + 4]), "=f"(d[OFF + 5]),
        "=f"(d[OFF + 6]), "=f"(d[OFF + 7]), "=f"(d[OFF + 8]), "=f"(d[OFF + 9]), "=f"(d[OFF + 10]), "=f"(d[OFF + 11]),
        "=f"(d[OFF + 12]), "=f"(d[OFF + 13]), "=f"(d[OFF + 14]), "=f"(d[OFF + 15]), "=f"(d[OFF + 16]), "=f"(d[OFF + 17]),
        "=f"(d[OFF + 18]), "=f"(d[OFF + 19]), "=f"(d[OFF + 20]), "=f"(d[OFF + 21]), "=f"(d[OFF + 22]), "=f"(d[OFF + 23]),
        "=f"(d[OFF + 24]), "=f"(d[OFF + 25]), "=f"(d[OFF + 26]), "=f"(d[OFF + 27]), "=f"(d[OFF + 28]), "=f"(d[OFF + 29]),
        "=f"(d[OFF + 30]), "=f"(d[OFF + 31]), "=f"(d[OFF + 32]), "=f"(d[OFF + 33]), "=f"(d[OFF + 34]), "=f"(d[OFF + 35]),
        "=f"(d[OFF + 36]), "=f"(d[OFF + 37]), "=f"(d[OFF + 38]), "=f"(d[OFF + 39]), "=f"(d[OFF + 40]), "=f"(d[OFF + 41]),
        "=f"(d[OFF + 42]), "=f"(d[OFF + 43]), "=f"(d[OFF + 44]), "=f"(d[OFF + 45]), "=f"(d[OFF + 46]), "=f"(d[OFF + 47]),
        "=f"(d[OFF + 48]), "=f"(d[OFF + 49]), "=f"(d[OFF + 50]), "=f"(d[OFF + 51])
      : "r"(a0), "r"(a1), "r"(a2), "r"(a3), "l"(desc_b), "r"(scale_d), "r"(meta));
}

template <int OFF, int NN>
__device__ __forceinline__ void wg_s48(float (&d)[NN], uint32_t a0, uint32_t a1, uint32_t a2, uint32_t a3,
                                       uint64_t desc_b, int scale_d, uint32_t meta) {
  asm volatile(
      "{\n.reg .pred p;\nsetp.ne.b32 p, %29, 0;\n"
      "wgmma.mma_async.sp.sync.aligned.m64n48k32.f32.bf16.bf16 "
      "{%0,%1,%2,%3,%4,%5,%6,%7,%8,%9,%10,%11,%12,%13,%14,%15,"
      "%16,%17,%18,%19,%20,%21,%22,%23}, "
      "{%24,%25,%26,%27}, %28, %30, 0, p, 1, 1, 0;\n}\n"
      : "+f"(d[OFF + 0]), "+f"(d[OFF + 1]), "+f"(d[OFF + 2]), "+f"(d[OFF + 3]), "+f"(d[OFF + 4]), "+f"(d[OFF + 5]),
        "+f"(d[OFF + 6]), "+f"(d[OFF + 7]), "+f"(d[OFF + 8]), "+f"(d[OFF + 9]), "+f"(d[OFF + 10]), "+f"(d[OFF + 11]),
        "+f"(d[OFF + 12]), "+f"(d[OFF + 13]), "+f"(d[OFF + 14]), "+f"(d[OFF + 15]), "+f"(d[OFF + 16]), "+f"(d[OFF + 17]),
        "+f"(d[OFF + 18]), "+f"(d[OFF + 19]), "+f"(d[OFF + 20]), "+f"(d[OFF + 21]), "+f"(d[OFF + 22]), "+f"(d[OFF + 23])
      : "r"(a0), "r"(a1), "r"(a2), "r"(a3), "l"(desc_b), "r"(scale_d), "r"(meta));
}

template <int OFF, int NN>
__device__ __forceinline__ void wg_s48z(float (&d)[NN], uint32_t a0, uint32_t a1, uint32_t a2, uint32_t a3,
                                       uint64_t desc_b, int scale_d, uint32_t meta) {
  asm volatile(
      "{\n.reg .pred p;\nsetp.ne.b32 p, %29, 0;\n"
      "wgmma.mma_async.sp.sync.aligned.m64n48k32.f32.bf16.bf16 "
      "{%0,%1,%2,%3,%4,%5,%6,%7,%8,%9,%10,%11,%12,%13,%14,%15,"
      "%16,%17,%18,%19,%20,%21,%22,%23}, "
      "{%24,%25,%26,%27}, %28, %30, 0, p, 1, 1, 0;\n}\n"
      : "=f"(d[OFF + 0]), "=f"(d[OFF + 1]), "=f"(d[OFF + 2]), "=f"(d[OFF + 3]), "=f"(d[OFF + 4]), "=f"(d[OFF + 5]),
        "=f"(d[OFF + 6]), "=f"(d[OFF + 7]), "=f"(d[OFF + 8]), "=f"(d[OFF + 9]), "=f"(d[OFF + 10]), "=f"(d[OFF + 11]),
        "=f"(d[OFF + 12]), "=f"(d[OFF + 13]), "=f"(d[OFF + 14]), "=f"(d[OFF + 15]), "=f"(d[OFF + 16]), "=f"(d[OFF + 17]),
        "=f"(d[OFF + 18]), "=f"(d[OFF + 19]), "=f"(d[OFF + 20]), "=f"(d[OFF + 21]), "=f"(d[OFF + 22]), "=f"(d[OFF + 23])
      : "r"(a0), "r"(a1), "r"(a2), "r"(a3), "l"(desc_b), "r"(scale_d), "r"(meta));
}

template <int OFF, int NN>
__device__ __forceinline__ void wg_s56(float (&d)[NN], uint32_t a0, uint32_t a1, uint32_t a2, uint32_t a3,
                                       uint64_t desc_b, int scale_d, uint32_t meta) {
  asm volatile(
      "{\n.reg .pred p;\nsetp.ne.b32 p, %33, 0;\n"
      "wgmma.mma_async.sp.sync.aligned.m64n56k32.f32.bf16.bf16 "
      "{%0,%1,%2,%3,%4,%5,%6,%7,%8,%9,%10,%11,%12,%13,%14,%15,"
      "%16,%17,%18,%19,%20,%21,%22,%23,%24,%25,%26,%27}, "
      "{%28,%29,%30,%31}, %32, %34, 0, p, 1, 1, 0;\n}\n"
      : "+f"(d[OFF + 0]), "+f"(d[OFF + 1]), "+f"(d[OFF + 2]), "+f"(d[OFF + 3]), "+f"(d[OFF + 4]), "+f"(d[OFF + 5]),
        "+f"(d[OFF + 6]), "+f"(d[OFF + 7]), "+f"(d[OFF + 8]), "+f"(d[OFF + 9]), "+f"(d[OFF + 10]), "+f"(d[OFF + 11]),
        "+f"(d[OFF + 12]), "+f"(d[OFF + 13]), "+f"(d[OFF + 14]), "+f"(d[OFF + 15]), "+f"(d[OFF + 16]), "+f"(d[OFF + 17]),
        "+f"(d[OFF + 18]), "+f"(d[OFF + 19]), "+f"(d[OFF + 20]), "+f"(d[OFF + 21]), "+f"(d[OFF + 22]), "+f"(d[OFF + 23]),
        "+f"(d[OFF + 24]), "+f"(d[OFF + 25]), "+f"(d[OFF + 26]), "+f"(d[OFF + 27])
      : "r"(a0), "r"(a1), "r"(a2), "r"(a3), "l"(desc_b), "r"(scale_d), "r"(meta));
}

template <int OFF, int NN>
__device__ __forceinline__ void wg_s56z(float (&d)[NN], uint32_t a0, uint32_t a1, uint32_t a2, uint32_t a3,
                                       uint64_t desc_b, int scale_d, uint32_t meta) {
  asm volatile(
      "{\n.reg .pred p;\nsetp.ne.b32 p, %33, 0;\n"
      "wgmma.mma_async.sp.sync.aligned.m64n56k32.f32.bf16.bf16 "
      "{%0,%1,%2,%3,%4,%5,%6,%7,%8,%9,%10,%11,%12,%13,%14,%15,"
      "%16,%17,%18,%19,%20,%21,%22,%23,%24,%25,%26,%27}, "
      "{%28,%29,%30,%31}, %32, %34, 0, p, 1, 1, 0;\n}\n"
      : "=f"(d[OFF + 0]), "=f"(d[OFF + 1]), "=f"(d[OFF + 2]), "=f"(d[OFF + 3]), "=f"(d[OFF + 4]), "=f"(d[OFF + 5]),
        "=f"(d[OFF + 6]), "=f"(d[OFF + 7]), "=f"(d[OFF + 8]), "=f"(d[OFF + 9]), "=f"(d[OFF + 10]), "=f"(d[OFF + 11]),
        "=f"(d[OFF + 12]), "=f"(d[OFF + 13]), "=f"(d[OFF + 14]), "=f"(d[OFF + 15]), "=f"(d[OFF + 16]), "=f"(d[OFF + 17]),
        "=f"(d[OFF + 18]), "=f"(d[OFF + 19]), "=f"(d[OFF + 20]), "=f"(d[OFF + 21]), "=f"(d[OFF + 22]), "=f"(d[OFF + 23]),
        "=f"(d[OFF + 24]), "=f"(d[OFF + 25]), "=f"(d[OFF + 26]), "=f"(d[OFF + 27])
      : "r"(a0), "r"(a1), "r"(a2), "r"(a3), "l"(desc_b), "r"(scale_d), "r"(meta));
}

template <int OFF, int NN>
__device__ __forceinline__ void wg_s64t(float (&d)[NN], uint32_t a0, uint32_t a1, uint32_t a2, uint32_t a3,
                                       uint64_t desc_b, int scale_d, uint32_t meta) {
  asm volatile(
      "{\n.reg .pred p;\nsetp.ne.b32 p, %37, 0;\n"
      "wgmma.mma_async.sp.sync.aligned.m64n64k32.f32.bf16.bf16 "
      "{%0,%1,%2,%3,%4,%5,%6,%7,%8,%9,%10,%11,%12,%13,%14,%15,"
      "%16,%17,%18,%19,%20,%21,%22,%23,%24,%25,%26,%27,%28,%29,%30,%31}, "
      "{%32,%33,%34,%35}, %36, %38, 0, p, 1, 1, 1;\n}\n"
      : "+f"(d[OFF + 0]), "+f"(d[OFF + 1]), "+f"(d[OFF + 2]), "+f"(d[OFF + 3]), "+f"(d[OFF + 4]), "+f"(d[OFF + 5]),
        "+f"(d[OFF + 6]), "+f"(d[OFF + 7]), "+f"(d[OFF + 8]), "+f"(d[OFF + 9]), "+f"(d[OFF + 10]), "+f"(d[OFF + 11]),
        "+f"(d[OFF + 12]), "+f"(d[OFF + 13]), "+f"(d[OFF + 14]), "+f"(d[OFF + 15]), "+f"(d[OFF + 16]), "+f"(d[OFF + 17]),
        "+f"(d[OFF + 18]), "+f"(d[OFF + 19]), "+f"(d[OFF + 20]), "+f"(d[OFF + 21]), "+f"(d[OFF + 22]), "+f"(d[OFF + 23]),
        "+f"(d[OFF + 24]), "+f"(d[OFF + 25]), "+f"(d[OFF + 26]), "+f"(d[OFF + 27]), "+f"(d[OFF + 28]), "+f"(d[OFF + 29]),
        "+f"(d[OFF + 30]), "+f"(d[OFF + 31])
      : "r"(a0), "r"(a1), "r"(a2), "r"(a3), "l"(desc_b), "r"(scale_d), "r"(meta));
}

template <int OFF, int NN>
__device__ __forceinline__ void wg_s64t1(float (&d)[NN], uint32_t a0, uint32_t a1, uint32_t a2, uint32_t a3,
                                       uint64_t desc_b, int scale_d, uint32_t meta) {
  asm volatile(
      "{\n.reg .pred p;\nsetp.ne.b32 p, %37, 0;\n"
      "wgmma.mma_async.sp.sync.aligned.m64n64k32.f32.bf16.bf16 "
      "{%0,%1,%2,%3,%4,%5,%6,%7,%8,%9,%10,%11,%12,%13,%14,%15,"
      "%16,%17,%18,%19,%20,%21,%22,%23,%24,%25,%26,%27,%28,%29,%30,%31}, "
      "{%32,%33,%34,%35}, %36, %38, 1, p, 1, 1, 1;\n}\n"
      : "+f"(d[OFF + 0]), "+f"(d[OFF + 1]), "+f"(d[OFF + 2]), "+f"(d[OFF + 3]), "+f"(d[OFF + 4]), "+f"(d[OFF + 5]),
        "+f"(d[OFF + 6]), "+f"(d[OFF + 7]), "+f"(d[OFF + 8]), "+f"(d[OFF + 9]), "+f"(d[OFF + 10]), "+f"(d[OFF + 11]),
        "+f"(d[OFF + 12]), "+f"(d[OFF + 13]), "+f"(d[OFF + 14]), "+f"(d[OFF + 15]), "+f"(d[OFF + 16]), "+f"(d[OFF + 17]),
        "+f"(d[OFF + 18]), "+f"(d[OFF + 19]), "+f"(d[OFF + 20]), "+f"(d[OFF + 21]), "+f"(d[OFF + 22]), "+f"(d[OFF + 23]),
        "+f"(d[OFF + 24]), "+f"(d[OFF + 25]), "+f"(d[OFF + 26]), "+f"(d[OFF + 27]), "+f"(d[OFF + 28]), "+f"(d[OFF + 29]),
        "+f"(d[OFF + 30]), "+f"(d[OFF + 31])
      : "r"(a0), "r"(a1), "r"(a2), "r"(a3), "l"(desc_b), "r"(scale_d), "r"(meta));
}

template <int OFF, int NN>
__device__ __forceinline__ void wg_s64tz(float (&d)[NN], uint32_t a0, uint32_t a1, uint32_t a2, uint32_t a3,
                                       uint64_t desc_b, int scale_d, uint32_t meta) {
  asm volatile(
      "{\n.reg .pred p;\nsetp.ne.b32 p, %37, 0;\n"
      "wgmma.mma_async.sp.sync.aligned.m64n64k32.f32.bf16.bf16 "
      "{%0,%1,%2,%3,%4,%5,%6,%7,%8,%9,%10,%11,%12,%13,%14,%15,"
      "%16,%17,%18,%19,%20,%21,%22,%23,%24,%25,%26,%27,%28,%29,%30,%31}, "
      "{%32,%33,%34,%35}, %36, %38, 0, p, 1, 1, 1;\n}\n"
      : "=f"(d[OFF + 0]), "=f"(d[OFF + 1]), "=f"(d[OFF + 2]), "=f"(d[OFF + 3]), "=f"(d[OFF + 4]), "=f"(d[OFF + 5]),
        "=f"(d[OFF + 6]), "=f"(d[OFF + 7]), "=f"(d[OFF + 8]), "=f"(d[OFF + 9]), "=f"(d[OFF + 10]), "=f"(d[OFF + 11]),
        "=f"(d[OFF + 12]), "=f"(d[OFF + 13]), "=f"(d[OFF + 14]), "=f"(d[OFF + 15]), "=f"(d[OFF + 16]), "=f"(d[OFF + 17]),
        "=f"(d[OFF + 18]), "=f"(d[OFF + 19]), "=f"(d[OFF + 20]), "=f"(d[OFF + 21]), "=f"(d[OFF + 22]), "=f"(d[OFF + 23]),
        "=f"(d[OFF + 24]), "=f"(d[OFF + 25]), "=f"(d[OFF + 26]), "=f"(d[OFF + 27]), "=f"(d[OFF + 28]), "=f"(d[OFF + 29]),
        "=f"(d[OFF + 30]), "=f"(d[OFF + 31])
      : "r"(a0), "r"(a1), "r"(a2), "r"(a3), "l"(desc_b), "r"(scale_d), "r"(meta));
}

__device__ __forceinline__ int g2_inv(int ch) { return 32 * (ch >> 5) + 8 * ((ch >> 1) & 3) + 2 * ((ch >> 3) & 3) + (ch & 1); }
__host__ __device__ __forceinline__ uint32_t wimg_off(int n, int k) {
  return (uint32_t)(k >> 6) * kWChunk + (uint32_t)n * 128 + (uint32_t)((((k & 63) >> 3) ^ (n & 7)) << 4) + (k & 7) * 2;
}
__host__ __device__ constexpr int w2piece(int h, int c) { return c == 2 ? 2 + h : 4 * h + c; }
__device__ __forceinline__ uint32_t w2img_off(int n, int k) { return wimg_off(n % 96, k & 63) + w2piece(n >= 96, k >> 6) * (kWChunk / 2); }
__device__ __forceinline__ int qpix(int par, int t) {
  const int a = 2 * t + 13 * par - 6, b = t + 112 * par;
  return par ? min(a, b) : max(a, b);
}
__device__ __forceinline__ int woff(int par, int i, int r) {
  const int a = 99 * par + 6 - 8 * i;
  return par ? min(r, a) : max(r, a);
}

__device__ __forceinline__ void mma16816(float (&c)[4], uint32_t a0, uint32_t a1, uint32_t a2, uint32_t a3, uint32_t b0,
                                         uint32_t b1) {
  asm volatile(
      "mma.sync.aligned.m16n8k16.row.col.f32.bf16.bf16.f32 {%0,%1,%2,%3}, {%4,%5,%6,%7}, {%8,%9}, {%0,%1,%2,%3};"
      : "+f"(c[0]), "+f"(c[1]), "+f"(c[2]), "+f"(c[3])
      : "r"(a0), "r"(a1), "r"(a2), "r"(a3), "r"(b0), "r"(b1));
}

__device__ __forceinline__ void fold_w1(const int u, const __nv_bfloat16* __restrict__ wqkv, uint8_t* wimg) {
  const int g = (threadIdx.x >> 2) & 7, l = threadIdx.x & 3;
  const int m0 = (u / 12) * 16, s = u % 12;
  uint4 A[12], B[12];
  const __nv_bfloat16* arow = wqkv + (m0 + 4 * (g >> 1) + (g & 1)) * 576 + 192 + 8 * l;
  const __nv_bfloat16* brow = wqkv + (16 * s + 4 * (g >> 1) + (g & 1)) * 576 + 8 * l;
#pragma unroll
  for (int i = 0; i < 12; i++) {
    A[i] = ldg128_nc(arow + (i & 1) * 2 * 576 + 32 * (i >> 1));
    B[i] = ldg128_nc(brow + (i & 1) * 2 * 576 + 32 * (i >> 1));
  }
  sched_fence();
  uint8_t* dst = wimg + wimg_off(m0 + g, 16 * s + 4 * l);
  float acc[4][4];
#pragma unroll
  for (int j = 0; j < 16; j++) acc[j >> 2][j & 3] = 0.f;
#pragma unroll
  for (int i = 0; i < 6; i++) {
    const uint4 &a0 = A[2 * i], &a1 = A[2 * i + 1];
#pragma unroll
    for (int nb = 0; nb < 2; nb++) {
      mma16816(acc[2 * nb], a0.x, a1.x, a0.y, a1.y, B[2 * i + nb].x, B[2 * i + nb].y);
      mma16816(acc[2 * nb + 1], a0.z, a1.z, a0.w, a1.w, B[2 * i + nb].z, B[2 * i + nb].w);
    }
  }
#pragma unroll
  for (int j = 0; j < 2; j++) {
    const uint2 v = make_uint2(pack_bf16((acc[0][2 * j] + acc[1][2 * j]) * kAlpha, (acc[0][2 * j + 1] + acc[1][2 * j + 1]) * kAlpha),
                               pack_bf16((acc[2][2 * j] + acc[3][2 * j]) * kAlpha, (acc[2][2 * j + 1] + acc[3][2 * j + 1]) * kAlpha));
    asm volatile("st.relaxed.gpu.global.v2.u32 [%0], {%1,%2};" ::"l"(dst + j * 1024), "r"(v.x), "r"(v.y) : "memory");
  }
}
__device__ __forceinline__ void fold_w2(const int u, const __nv_bfloat16* __restrict__ wqkv, const __nv_bfloat16* __restrict__ wo,
                                        uint8_t* wimg) {
  const int g = (threadIdx.x >> 2) & 7, l = threadIdx.x & 3;
  const int m0 = (u / 12) * 32, n0 = (u % 12) * 16;
  uint4 S[12];
  uint32_t L[96];
  const __nv_bfloat16* brow = wqkv + (n0 + 4 * (g >> 1) + (g & 1)) * 576 + 384 + 8 * l;
#pragma unroll
  for (int i = 0; i < 12; i++) S[i] = ldg128_nc(brow + (i & 1) * 2 * 576 + 32 * (i >> 1));
  const __nv_bfloat16* acol = wo + (8 * l) * 192 + m0 + 4 * g;
#pragma unroll
  for (int c = 0; c < 48; c++)
    asm volatile("ld.global.nc.v2.u32 {%0,%1}, [%2];" : "=r"(L[2 * c]), "=r"(L[2 * c + 1]) : "l"(acol + (32 * (c >> 3) + (c & 7)) * 192));
  const uint32_t off = w2_offset();
  sched_fence();
  uint8_t* img = wimg + off;
  float acc[4][4];
#pragma unroll
  for (int j = 0; j < 16; j++) acc[j >> 2][j & 3] = 0.f;
#pragma unroll
  for (int i = 0; i < 6; i++) {
#pragma unroll
    for (int h = 0; h < 2; h++) {
      const uint4 &s0 = S[2 * i], &s1 = S[2 * i + 1];
#pragma unroll
      for (int mt = 0; mt < 2; mt++) {
        const uint32_t* a = L + 16 * i + 8 * h + mt;
        const uint32_t a0 = __byte_perm(a[0], a[2], 0x5410), a1 = __byte_perm(a[0], a[2], 0x7632);
        const uint32_t a2 = __byte_perm(a[4], a[6], 0x5410), a3 = __byte_perm(a[4], a[6], 0x7632);
        mma16816(acc[2 * mt], a0, a1, a2, a3, h ? s0.z : s0.x, h ? s0.w : s0.y);
        mma16816(acc[2 * mt + 1], a0, a1, a2, a3, h ? s1.z : s1.x, h ? s1.w : s1.y);
      }
    }
  }
#pragma unroll
  for (int j = 0; j < 4; j++) {
    const float(&c0)[4] = acc[j & 2];
    const float(&c1)[4] = acc[(j & 2) + 1];
    asm volatile("st.relaxed.gpu.global.v2.u32 [%0], {%1,%2};" ::"l"(img + w2img_off(g2_inv(m0 + 4 * g + j), n0 + 4 * l)),
                 "r"(pack_bf16(c0[2 * (j & 1)], c0[2 * (j & 1) + 1])), "r"(pack_bf16(c1[2 * (j & 1)], c1[2 * (j & 1) + 1])) : "memory");
  }
}

__global__ void __launch_bounds__(256) fold_kernel(const __nv_bfloat16* __restrict__ wqkv,
                                                   const __nv_bfloat16* __restrict__ wo, uint8_t* wimg) {
  const int u = blockIdx.x * 8 + (threadIdx.x >> 5);
  if (u < 144) fold_w1(u, wqkv, wimg);
  else fold_w2(u - 144, wqkv, wo, wimg);
}

struct TileCoord { int pr, pc, I, J, up, kind; };
struct TileTable { uint16_t e[kCtas * 6], g[5][8][2], b[5][2][4]; };
inline void make_tiles(TileTable& tt) {
  for (int tile = 0; tile < kCtas * 6; tile++) {
    const int b = tile / 6, k = tile - 6 * b;
    const int p = b < 128 ? (tile - 672) >> 1 : b - 80;
    const int strip = b < 112 ? b >> 1 : b >= 128 && k >= 2 ? (b & 1) * 27 + (b & 2) * 14 : p + (p < 26 ? 1 : 3);
    const int pr = strip >= 28, J = (strip - pr * 28) >> 1, pc = strip & 1, up = b < 112 ? b & 1 : pr;
    const int first = b < 112 ? 8 - 2 * pr - up : 13 * pr, step = b < 112 ? k : k & 1;
    const int I = up ? first - step : first + step;
    const int kind = I == 13 * pr ? 3 + pr : J == 13 * pc ? 1 + pc : 0;
    tt.e[tile] = (uint16_t)(I | J << 4 | pr << 8 | pc << 9 | up << 10 | kind << 11);
  }
  for (int kind = 0; kind < 5; kind++) {
    const bool col = kind == 1 || kind == 2;
    auto off = [kind](int t) { return kind == 0 ? 2 * t : kind & 1 ? t + (t == 7) : t + (t > 0); };
    for (int j = 0; j < 8; j++) {
      const int w = j >> 1, h = j & 1;
      tt.g[kind][j][0] = (uint16_t)(col ? 3 * off(w + 4 * h) : 3 * (kW * off(2 * w) + 8 * h));
      tt.g[kind][j][1] = (uint16_t)(128 * (col ? 5 : 5 + off(2 * w + 1) - off(2 * w)));
    }
    for (int i = 0; i < 2; i++) {
      const int w = kind == 0 ? 0 : kind & 1 ? 3 * i : 1 - i;
      tt.b[kind][i][0] = tt.g[kind][2 * w][0];
      tt.b[kind][i][1] = (uint16_t)(128 * (kind == 0 ? 0 : (col ? 3 : 1) + i));
      tt.b[kind][i][2] = (uint16_t)(2048 * w);
      tt.b[kind][i][3] = 0;
    }
  }
}
__device__ __forceinline__ int num_tiles() { return blockIdx.x < 128 ? 6 : 4; }
__device__ __forceinline__ TileCoord decode_tile(const TileTable& tt, int tile) {
  const uint32_t e = tt.e[tile];
  return TileCoord{(int)(e >> 8) & 1, (int)(e >> 9) & 1, (int)e & 15, (int)(e >> 4) & 15, (int)(e >> 10) & 1, (int)(e >> 11)};
}
__device__ __forceinline__ int halo_r0(const TileCoord& t) { return 8 * t.I + 6 * t.pr - 6; }
__device__ __forceinline__ int halo_c0(const TileCoord& t) { return min(max(8 * t.J + 6 * t.pc - 6, -3), 102); }

__device__ __forceinline__ uint32_t bar_full(uint32_t bars, int wg, int c) { return bars + (wg * 3 + c) * 8; }
__device__ __forceinline__ uint32_t bar_w1c(uint32_t bars, int c) { return bars + (6 + c) * 8; }
__device__ __forceinline__ uint32_t bar_w2(uint32_t bars) { return bars + 9 * 8; }
__device__ __forceinline__ uint32_t bar_x(uint32_t bars, int j, int c) { return bars + (j == 0 ? 10 : c ? 17 + c : 11) * 8; }
__device__ __forceinline__ uint32_t bar_w1q(uint32_t bars) { return bars + 12 * 8; }
__device__ __forceinline__ uint32_t bar_xf(uint32_t bars) { return bars + 13 * 8; }
__device__ __forceinline__ uint32_t bar_w2m(uint32_t bars) { return bars + 14 * 8; }
__device__ __forceinline__ uint32_t bar_redo(uint32_t bars) { return bars + 15 * 8; }
__device__ __forceinline__ uint32_t bar_wok(uint32_t bars) { return bars + 16 * 8; }
__device__ __forceinline__ uint32_t bar_go(uint32_t bars) { return bars + 17 * 8; }
__device__ __forceinline__ uint32_t bar_raw(uint32_t bars, int j = 0) { return bars + (21 + j) * 8; }
__device__ __forceinline__ uint32_t bar_w2a(uint32_t bars) { return bars + 20 * 8; }
constexpr int kNumBars = 22;

__device__ __forceinline__ uint64_t wdesc(uint64_t d0, int s) { return d0 + (((s >> 2) * kWChunk + (s & 3) * 32) >> 4); }

__device__ __forceinline__ uint32_t x_chunk(int k, int c) { return kXOff + (k == 0 ? kWChunk : 0) + (k & 1 ? 2 - c : c) * 8192; }
__device__ __forceinline__ uint32_t out_slot(int k, int nt) { return k + 1 < nt ? kW2Off + (~k & 1) * 2 * kWChunk : kW1Off + kWChunk; }
template <int I0, int I1>
__device__ __forceinline__ void store_rows(bool on, __nv_bfloat16* pA, __nv_bfloat16* pB, const uint32_t (&a)[24], const uint32_t (&b)[24]) {
#pragma unroll
  for (int i = 2 * I0; i < 2 * I1; i++) {
    const uint32_t* v = (i & 1 ? b : a) + 4 * (i >> 1);
    asm volatile("{\n.reg .pred p;\nsetp.ne.u32 p, %5, 0;\n@p st.global.v4.u32 [%0], {%1,%2,%3,%4};\n}\n" ::"l"((i & 1 ? pB : pA) + 32 * (i >> 1)),
                 "r"(v[0]), "r"(v[1]), "r"(v[2]), "r"(v[3]), "r"((uint32_t)on) : "memory");
  }
}
template <int I0, int I1>
__device__ __forceinline__ void stage_out(const uint32_t (&ad)[4], const uint32_t (&a)[24], const uint32_t (&b)[24]) {
#pragma unroll
  for (int i = I0; i < I1; i++) {
    const uint32_t* v = (i < 6 ? a : b) + 4 * (i % 6);
    asm volatile("st.shared.v4.u32 [%0], {%1,%2,%3,%4};" ::"r"(ad[i % 6 / 3 * 2 + (i % 3 == 1)] + (i % 3 == 2) * 1024 + (i / 6) * 12288),
                 "r"(v[0]), "r"(v[1]), "r"(v[2]), "r"(v[3]) : "memory");
  }
}
__device__ __forceinline__ uint32_t now_ns() {
  uint32_t t;
  asm volatile("mov.u32 %0, %globaltimer_lo;" : "=r"(t)::"memory");
  return t;
}
__device__ __forceinline__ void wait_clock(uint32_t t_start, uint32_t t) {
  while (now_ns() - t_start < t) { }
}
#define NAT_PRED(f, m) ".reg .pred p;\n.reg .b32 t;\nand.b32 t, " f ", " m ";\nsetp.ne.u32 p, t, 0;\n"
constexpr uint32_t kHiV = 1, kHiU = 8, kColB = 0x20, kInV = 0x100, kInU = 0x1000, kColA = 0x10000;
template <uint32_t M>
__device__ __forceinline__ float pick(const float* a, const float* b, uint32_t f) {
  float d;
  asm("{\n" NAT_PRED("%5", "%6") "add.f32 %0, %1, %2;\n@p add.f32 %0, %3, %4;\n}\n"
      : "=&f"(d) : "f"(a[0]), "f"(a[2]), "f"(b[0]), "f"(b[2]), "r"(f), "n"(M));
  return d;
}
template <uint32_t M>
__device__ __forceinline__ float sel(float a, float b, uint32_t f) {
  float d;
  asm("{\n" NAT_PRED("%3", "%4") "selp.f32 %0, %1, %2, p;\n}\n" : "=f"(d) : "f"(a), "f"(b), "r"(f), "n"(M));
  return d;
}
template <uint32_t M>
__device__ __forceinline__ void max_if(float& m, float v, uint32_t f) {
  asm("{\n" NAT_PRED("%2", "%3") "@p max.f32 %0, %0, %1;\n}\n" : "+f"(m) : "f"(v), "r"(f), "n"(M));
}
template <uint32_t M>
__device__ __forceinline__ void add_if(float& m, float v, uint32_t f) {
  asm("{\n" NAT_PRED("%2", "%3") "@p add.f32 %0, %0, %1;\n}\n" : "+f"(m) : "f"(v), "r"(f), "n"(M));
}
__device__ __forceinline__ void pick_v(const float* a, float* v, uint32_t f) {
  v[0] = pick<kHiV>(a, a + 16, f), v[1] = pick<kHiV>(a + 1, a + 17, f);
  v[2] = pick<kHiV * 2>(a + 4, a + 20, f), v[3] = pick<kHiV * 2>(a + 5, a + 21, f);
  v[4] = pick<kHiV * 4>(a + 8, a + 24, f), v[5] = pick<kHiV * 4>(a + 9, a + 25, f);
  v[6] = a[12] + a[14], v[7] = a[13] + a[15];
}
__device__ __forceinline__ void pick_u(const float* a, float* v, uint32_t f) {
#pragma unroll
  for (int c = 0; c < 3; c++) v[2 * c] = pick<kHiU>(a + 4 * c, a + 4 * c + 12, f), v[2 * c + 1] = pick<kHiU * 2>(a + 4 * c + 1, a + 4 * c + 13, f);
}
__device__ __forceinline__ uint32_t sign_bytes(uint32_t v, uint32_t sel) {
  uint32_t d;
  asm("prmt.b32 %0, %1, %1, %2;" : "=r"(d) : "r"(v), "r"(sel));
  return d;
}
__device__ __forceinline__ float own_max(const float (&v)[14], uint32_t f) {
  float m = sel<kInV>(fmaxf(v[0], v[1]), -INFINITY, f), m2 = sel<kInV * 2>(fmaxf(v[2], v[3]), -INFINITY, f);
  max_if<kInV * 4>(m, fmaxf(v[4], v[5]), f);
  max_if<kInV * 8>(m2, fmaxf(v[6], v[7]), f);
  max_if<kInU>(m, fmaxf(fmaxf(v[8], v[10]), v[12]), f);
  max_if<kInU * 2>(m2, fmaxf(fmaxf(v[9], v[11]), v[13]), f);
  return fmaxf(m, m2);
}
__device__ __forceinline__ float quad_max(float m) {
  const float a = __shfl_xor_sync(0xffffffffu, m, 1), b = __shfl_xor_sync(0xffffffffu, m, 2), c = __shfl_xor_sync(0xffffffffu, m, 3);
  return fmaxf(fmaxf(m, a), fmaxf(b, c));
}
__device__ __forceinline__ float row_rcp(const float (&v)[14], uint32_t f) {
  float s = sel<kInV>(v[0] + v[1], 0.f, f), s2 = sel<kInV * 2>(v[2] + v[3], 0.f, f);
  add_if<kInV * 4>(s, v[4] + v[5], f);
  add_if<kInV * 8>(s2, v[6] + v[7], f);
  add_if<kInU>(s, v[8] + v[10] + v[12], f);
  add_if<kInU * 2>(s2, v[9] + v[11] + v[13], f);
  s += s2;
  const float a = __shfl_xor_sync(0xffffffffu, s, 1), b = __shfl_xor_sync(0xffffffffu, s, 2), c = __shfl_xor_sync(0xffffffffu, s, 3);
  return rcp_approx((s + a) + (b + c));
}
__device__ __forceinline__ void route(const float (&v)[14], float s, const uint32_t (&rt)[9], uint32_t (&p)[14]) {
#pragma unroll
  for (int i = 0; i < 7; i++) {
    const uint32_t u = pack_bf16(v[2 * i] * s, v[2 * i + 1] * s);
    if (i < 4) p[i] = u & rt[i];
    if (i < 3) p[i + 4] = u & rt[i + 4];
    if (i >= 4) {
      p[i + 3] = u & rt[7];
      p[i + 6] = u & rt[8];
    }
  }
}

template <int C, int T0 = 0, int T1 = 7>
__device__ __forceinline__ void pv_chunk(float (&z)[32], const uint32_t (&pa)[14], const uint32_t (&pb)[14],
                                         const uint32_t (&meta)[4], uint64_t dV) {
#pragma unroll
  for (int t = T0; t < T1; t++) {
    if (t & 1)
      wg_s64t1<0, 32>(z, pa[2 * t], pb[2 * t], pa[2 * t + 1], pb[2 * t + 1], dV + ((2 * C * kChunkBytes + t * 2048) >> 4), 1,
                      meta[t >> 1]);
    else if (t > 0)
      wg_s64t<0, 32>(z, pa[2 * t], pb[2 * t], pa[2 * t + 1], pb[2 * t + 1], dV + ((2 * C * kChunkBytes + t * 2048) >> 4), 1,
                     meta[t >> 1]);
    else
      wg_s64tz<0, 32>(z, pa[0], pb[0], pa[1], pb[1], dV + ((2 * C * kChunkBytes) >> 4), 0, meta[0]);
  }
}
template <int C>
__device__ __forceinline__ void pack_z(const float (&z)[32], uint32_t (&za)[24], uint32_t (&zb)[24]) {
#pragma unroll
  for (int j = 0; j < 8; j++) {
    za[8 * C + j] = pack_bf16(z[4 * j], z[4 * j + 1]);
    zb[8 * C + j] = pack_bf16(z[4 * j + 2], z[4 * j + 3]);
  }
}

template <int H>
__device__ __forceinline__ void pack_out(const float (&ac)[48], uint32_t (&oa)[24], uint32_t (&ob)[24]) {
#pragma unroll
  for (int j = 0; j < 12; j++) {
    oa[12 * H + j] = pack_bf16(ac[4 * j], ac[4 * j + 1]);
    ob[12 * H + j] = pack_bf16(ac[4 * j + 2], ac[4 * j + 3]);
  }
}
struct Maps { CUtensorMap v6, v2, v14, u8, px[8], wv, wo; };
__device__ __forceinline__ void tma_prefetch_5d(const CUtensorMap* map, int c0, int c1, int c2, int c3, int c4) {
  asm volatile("cp.async.bulk.prefetch.tensor.5d.L2.global.tile [%0, {%1, %2, %3, %4, %5}];" ::"l"((uint64_t)map), "r"(c0), "r"(c1),
               "r"(c2), "r"(c3), "r"(c4) : "memory");
}
__device__ __forceinline__ int first_line(const TileCoord tc) { return 3 * (qpix(tc.pr, 8 * tc.I) * kW + qpix(tc.pc, 8 * tc.J)); }
__device__ __forceinline__ void load_px(const Maps& tm, const TileTable& tt, uint32_t dst, uint32_t bar, int line, int kind) {
#pragma unroll
  for (int i = 0; i < 2; i++) {
    if (i == 0 || kind != 0) {
      const CUtensorMap* map = (const CUtensorMap*)((const char*)tm.px + tt.b[kind][i][1]);
      if (bar) tma_load_5d(dst + tt.b[kind][i][2], map, bar, 0, 0, 0, 0, line + tt.b[kind][i][0]);
      else tma_prefetch_5d(map, 0, 0, 0, 0, line + tt.b[kind][i][0]);
    }
  }
}
__device__ __forceinline__ void store_px(const Maps& tm, const TileTable& tt, uint32_t buf, int line, int kind) {
#pragma unroll
  for (int i = 0; i < 8; i++) {
    const int j = 2 * (i & 3) + (i >> 2);
    asm volatile("cp.async.bulk.tensor.5d.global.shared::cta.tile.bulk_group [%0, {%2, %2, %2, %2, %3}], [%1];" ::"l"(
                     (uint64_t)tm.px + tt.g[kind][j][1]), "r"(buf + i * 3072), "r"(0), "r"(line + tt.g[kind][j][0]) : "memory");
  }
  asm volatile("cp.async.bulk.commit_group;" ::: "memory");
}
__device__ __noinline__ bool refetch(uint32_t base, const uint8_t* src, bool gap) {
  constexpr uint32_t bars = 1024 + kBarOff, cnt = bars + 192;
#pragma unroll 1
  for (uint32_t o = 0; o < kWBytes && !gap; o += 2048) {
    uint32_t mx = 0;
#pragma unroll
    for (int i = 0; i < 4; i++) {
      uint4 v;
      asm volatile("ld.shared.v4.u32 {%0,%1,%2,%3}, [%4];" : "=r"(v.x), "=r"(v.y), "=r"(v.z), "=r"(v.w)
                   : "r"(base + o + i * 512 + (threadIdx.x & 31) * 16));
      mx = __vimax3_u32(__vimax3_u32(mx, v.x, v.y), v.z, v.w);
    }
    gap = __any_sync(0xffffffffu, mx == kEmpty);
  }
  uint32_t n;
  asm volatile("ld.shared.u32 %0, [%1];" : "=r"(n) : "r"(cnt) : "memory");
  if (!gap || __any_sync(0xffffffffu, n > (1u << 12))) return false;
  asm volatile("bar.sync 15, 128;" ::: "memory");
  if (threadIdx.x == 0) {
    asm volatile("st.shared.u32 [%0], %1;" ::"r"(cnt), "r"(n + 1) : "memory");
    mbar_arrive_expect_tx(bar_redo(bars), kWBytes);
    bulk_load(base, src, kWBytes, bar_redo(bars));
  }
  __syncwarp();
  mbar_wait(bar_redo(bars), n & 1);
  return true;
}
template <int S0, int S1, int Z>
__device__ __forceinline__ void g2_steps(float (&ac)[48], const uint32_t (&za)[24], const uint32_t (&zb)[24], uint64_t d) {
#pragma unroll
  for (int s = S0; s < S1; s++) {
    const uint64_t ds = d + (((s >> 2 & 1) * (kWChunk / 2) + (s & 3) * 32) >> 4);
    if (s == Z) wg_d96z<0, 48>(ac, za[2 * s], zb[2 * s], za[2 * s + 1], zb[2 * s + 1], ds, 0);
    else wg_d96<0, 48>(ac, za[2 * s], zb[2 * s], za[2 * s + 1], zb[2 * s + 1], ds, 1);
  }
}

__device__ __forceinline__ void consumer(const int wg, __nv_bfloat16* out, const uint8_t* wimg, const uint32_t sbase,
                                         const uint32_t zero, const Maps& tm, const TileTable& tt) {
  const int tid = threadIdx.x & 127;
  const int w = __shfl_sync(0xffffffffu, tid >> 5, 0), lane = tid & 31;
  const uint64_t dK = make_desc(sbase, 16, 1024);
  const uint64_t dV = make_desc(sbase, kChunkBytes, 512, 2);
  const uint64_t dW1 = make_desc(sbase + kW1Off, 16, 1024);
  const uint64_t dX0 = make_desc(sbase + kW2Off + wg * 2 * kWChunk, 16, 1024), dY0 = make_desc(sbase + kW2Off + (1 - wg) * 2 * kWChunk, 16, 1024);
  const uint64_t dX2 = make_desc(sbase + kXOff + wg * (kWChunk / 2), 16, 1024), dY2 = make_desc(sbase + kXOff + (1 - wg) * (kWChunk / 2), 16, 1024);
  const uint32_t bars = sbase + kBarOff;
  int tile0 = blockIdx.x * kTilesPerCta;
  asm volatile("" : "+r"(tile0));
  const int nt = num_tiles();

  uint32_t pix = 0, geo[6] = {};
  const int l = lane & 3;
#pragma unroll 1
  for (int j = 4; j >= 0; j -= 2) {
    const TileCoord tc = decode_tile(tt, tile0 + wg + j);
    const bool col = tc.kind == 1 || tc.kind == 2;
    const int g = col ? lane >> 2 : 2 * w + ((lane >> 2) & 1), qc = col ? w : lane >> 3;
    const uint32_t pr = qpix(tc.pr, 8 * tc.I + g) * kW;
    if (j == nt - 2) pix = (pr + qpix(tc.pc, 8 * tc.J + qc)) | (pr + qpix(tc.pc, 8 * tc.J + qc + 4)) << 16;
    const int d = 8 * tc.J + 6 * tc.pc - 6 - halo_c0(tc);
    const int ro = woff(tc.pr, tc.I, g), coA = woff(tc.pc, tc.J, qc) + d, coB = woff(tc.pc, tc.J, qc + 4) + d - 3;
#pragma unroll
    for (int i = 5; i >= 2; i--) geo[i] = geo[i - 2];
    const uint32_t lr = 0x1FCu << ro;
    const uint32_t lv = lr >> (2 + (l >> 1)), lu = lr >> (2 * l + 2 * tc.up);
    const uint32_t t = __byte_perm(lv, lu, wg ? 0x4501 : 0x5410);
    geo[0] = (((t & 0x15u) | (lv & 0x40u)) * 0x02082080u & 0x80808080u) | (((t >> 8) & 0x15u) * 0x01041040u & 0x40404040u) |
             (__byte_perm(t << 5, t << 4, 0x7362) & 0x20202020u) | (nt == 6);
    const int dr = (ro - 1) & 7;
    const uint32_t hiv = (((1u << ((ro - (l >> 1) + 1) >> 1)) - 1u) ^ (wg ? 7u : 0u)) & 7u, hiu = (t >> 24) & 3u;
    const uint32_t ca = (1u << coA) - 1u;
    geo[1] = hiv * kHiV | hiu * kHiU | ((((1u << coB) - 1u) >> (2 * (l & 1))) & 3u) * kColB |
             (15u & ~((uint32_t)((dr & 1) == (l >> 1)) << (dr >> 1))) * kInV | ((t >> 16 | t >> 24) & 3u) * kInU | ca * kColA |
             (ca >> ((0x49 >> (2 * l)) & 3) & 1u) << 19 | (uint32_t)(l == 3) << 20 | (0x55u & ((1u << (2 * coB)) - 1u)) << 24;
  }
  keep_regs(geo);
  const int so = (lane >> 3) | (lane & 4);
  uint32_t sts = sbase + w * 3072 + so * 128 + (((lane & 3) ^ so) << 4);
  __nv_bfloat16* poA = out + 8 * l + (pix & 0xFFFFu) * kC + 96 * wg;
  __nv_bfloat16* poB = out + 8 * l + (pix >> 16) * kC + 96 * wg;
  asm volatile("" : "+l"(poA), "+l"(poB), "+r"(sts));
  uint32_t oa[24], ob[24];
#pragma unroll
  for (int j = 0; j < 24; j++) oa[j] = ob[j] = 0u;
  keep_regs(oa);
  keep_regs(ob);
  PROF(wg, 0);
  if (threadIdx.x == 0) GT(1);

  for (int k = wg; k < nt; k += 2) {
    const uint32_t ph = (k >> 1) & 1;
    const int it = k >> 1;
    uint32_t qa[24], qb[24], hok[3];
    uint32_t fl = geo[1];
    {
      float acc[96];
      const uint32_t xp = (k + (k > 0)) & 1;
      const uint32_t xok = mbar_test(bar_x(bars, k > 0, 0), xp);
      if (k > 0) nb_sync(1 + (1 - wg));
#pragma unroll
      for (int s = 0; s < 12; s++) {
        if (s == 0) mbar_wait_if(xok, bar_x(bars, k > 0, 0), xp);
        if (s == 0 && k < 2) PROF(wg, 1);
        if (s == 0) PROFS(2, wg, 2 + it * 12);
        if (s == 0 && w == 0 && k < 2) GT(20 + wg);
        if ((s & 3) == 0 && (k == 0 || s > 0)) {
          mbar_wait(k == 0 ? bar_w1c(bars, s >> 2) : bar_x(bars, 1, s >> 2), xp);
          PROFS(17, wg, 50 + (s >> 2));
        }
        if ((s & 3) == 0) wg_fence();
        const uint64_t dX = make_desc(sbase + x_chunk(k, s >> 2), 16, 1024) + 2 * (s & 3);
        if (s == 0) wg_m192z<0, 96>(acc, dX, dW1, 0);
        else wg_m192<0, 96>(acc, dX, wdesc(dW1, s), 1);
        if ((s & 3) == 3) wg_commit();
      }
      PROFS(13, wg, 13 + it * 12);
      const uint32_t e = sts + out_slot(k, nt), o = e ^ 64;
      uint32_t ad[4] = {wg ? o + 1024 : e, wg ? e + 2048 : o, wg ? e : o + 1024, wg ? o : e + 2048};
      keep_regs(ad);
      if (NAT_MP > 2) {
        wg_wait<2>();
        if (k > 0) nb_arrive_p(0);
      }
      if (NAT_MP > 1) {
        wg_wait<1>();
        if (k > 0) nb_arrive_p(14);
      }
      wg_wait<0>();
      if (k > 0) {
        nb_arrive_p(6);
        sched_fence();
      }
      fence_regs(acc);
      PROFS(3, wg, 3 + it * 12);
#pragma unroll
      for (int j = 0; j < 24; j++) {
        qa[j] = pack_bf16(acc[4 * j], acc[4 * j + 1]);
        qb[j] = pack_bf16(acc[4 * j + 2], acc[4 * j + 3]);
      }
      keep_regs(qa);
      keep_regs(qb);
      sched_fence();
      if (k >= 2) {
        nb_sync(11);
        stage_out<0, 6>(ad, oa, ob);
        nb_sync(12);
        stage_out<6, 12>(ad, oa, ob);
      }
#pragma unroll
      for (int c = 0; c < 3; c++) hok[c] = mbar_test(bar_full(bars, wg, c), ph);
      if (k >= 2) {
        fence_proxy_async();
        nb_arrive_p(10);
      }
    }

    float aE[52], aO[24], bO[52], bE[28];
    const uint32_t mq = 0xEEEE4444u | zero;
    PROFS(4, wg, 4 + it * 12);

    mbar_wait_if(hok[0], bar_full(bars, wg, 0), ph);
    PROFS(14, wg, 40 + it * 3);
    if (w == 0 && k < 2) GT(22 + wg);
    if (k > 0) nb_sync(3 + (1 - wg));
    wg_fence();
#pragma unroll
    for (int ks = 0; ks < 6; ks++) {
      if (ks == NAT_P1) {
        mbar_wait_if(hok[1], bar_full(bars, wg, 1), ph);
        PROFS(14, wg, 41 + it * 3);
        wg_fence();
      }
      if (ks == NAT_P2) {
        mbar_wait_if(hok[2], bar_full(bars, wg, 2), ph);
        PROFS(14, wg, 42 + it * 3);
        wg_fence();
      }
      const uint64_t d = dK + ((ks * kChunkBytes) >> 4);
      if (ks == 0) wg_s104z<0, 52>(aE, qa[0], qa[1], qa[2], qa[3], d, 0, mq);
      else wg_s104<0, 52>(aE, qa[4 * ks], qa[4 * ks + 1], qa[4 * ks + 2], qa[4 * ks + 3], d, 1, mq);
      if (ks == 0) wg_s48z<0, 24>(aO, qa[0], qa[1], qa[2], qa[3], d + ((7 * 1024 + 64) >> 4), 0, mq);
      else if (ks < NAT_QA) wg_s48<0, 24>(aO, qa[4 * ks], qa[4 * ks + 1], qa[4 * ks + 2], qa[4 * ks + 3], d + ((7 * 1024 + 64) >> 4), 1, mq);
    }
    wg_commit();
#pragma unroll
    for (int ks = NAT_QA; ks < 6; ks++)
      wg_s48<0, 24>(aO, qa[4 * ks], qa[4 * ks + 1], qa[4 * ks + 2], qa[4 * ks + 3], dK + ((ks * kChunkBytes + 7 * 1024 + 64) >> 4), 1, mq);
    wg_commit();
    wg_s56z<0, 28>(bE, qb[0], qb[1], qb[2], qb[3], dK, 0, mq);
#pragma unroll
    for (int ks = 1; ks < 6; ks++) wg_s56<0, 28>(bE, qb[4 * ks], qb[4 * ks + 1], qb[4 * ks + 2], qb[4 * ks + 3], dK + ((ks * kChunkBytes) >> 4), 1, mq);
    wg_commit();
    wg_wait<2>();
    fence_regs(aE);
    PROFS(5, wg, 5 + it * 12);

    uint32_t pa[14], pb[14], meta[4];
    {
      float vA[14], vB[14];
      pick_v(aE, vA, fl);
      pick_u(aE + 28, vA + 8, fl);
      fence_regs(vA);
      if (k == 0) {
        if (__builtin_expect(__any_sync(0xffffffffu, vA[6] != vA[6]), 0)) {
          wg_wait<0>();
          fence_regs(aO);
          fence_regs(bE);
          if (refetch(sbase + kW1Off, wimg, false)) {
#pragma unroll
            for (int j = 0; j < 24; j++) oa[j] = ob[j] = 0u;
            k -= 2;
            continue;
          }
        }
        if (elect_one()) mbar_arrive(bar_xf(bars));
      }
      wg_fence();
      wg_s104z<0, 52>(bO, qb[0], qb[1], qb[2], qb[3], dK + 4, 0, mq);
#pragma unroll
      for (int ks = 1; ks < 6; ks++)
        wg_s104<0, 52>(bO, qb[4 * ks], qb[4 * ks + 1], qb[4 * ks + 2], qb[4 * ks + 3], dK + ((ks * kChunkBytes + 64) >> 4), 1, mq);
      wg_commit();
      if (k + 1 < nt) nb_arrive(1 + wg);
      uint32_t rt[9];
#pragma unroll
      for (int i = 0; i < 7; i++) rt[i] = sign_bytes(geo[0] << (i >> 2), 0x8888u + 0x1111u * (i & 3));
      rt[7] = sign_bytes(geo[0] << 2, 0x9988u);
      rt[8] = sign_bytes(geo[0] << 2, 0xBBAAu);
      keep_regs(rt);
      pa[13] = pb[13] = 0u;
      wg_wait<2>();
      keep_regs(qa);
      fence_regs(aO);
      float oA[6], eB[8];
      pick_u(aO, oA, fl);
      wg_wait<1>();
      fence_regs(bE);
      pick_v(bE, eB, fl);
      vA[8] = sel<kColA>(oA[0], vA[8], fl), vA[9] = sel<kColA>(oA[1], vA[9], fl);
      vA[10] = sel<kColA * 2>(oA[2], vA[10], fl), vA[11] = sel<kColA * 2>(oA[3], vA[11], fl);
      vA[12] = sel<kColA * 4>(oA[4], vA[12], fl), vA[13] = sel<kColA * 4>(oA[5], vA[13], fl);
      {
        const float m1 = __uint_as_float(0x88DD88DDu), m0 = __uint_as_float(0x88DDDD88u);
        meta[0] = 0xDD88DD88u ^ __byte_perm(fl, 0u, 0x3344);
        meta[1] = __float_as_uint(sel<kColA * 16>(sel<kColA>(m1, m0, fl), __uint_as_float(meta[0]), fl));
        meta[2] = __float_as_uint(sel<kColA * 8>(m1, m0, fl));
        meta[3] = __float_as_uint(sel<kColA * 4>(m1, m0, fl));
        keep_regs(meta);
      }
      float mA = own_max(vA, fl);
      fl |= __float_as_uint(eB[7]) & zero;
      fence_regs(eB);
      fence_regs(vA);
      asm volatile("" : "+f"(mA), "+r"(fl));
      sched_fence();
      wg_wait<0>();
      sched_fence();
      keep_regs(qb);
      fence_regs(bO);
      PROFS(6, wg, 6 + it * 12);
      if (w == 0) GT(24 + k);
      mA = quad_max(mA);
#pragma unroll
      for (int i = 0; i < 14; i++) vA[i] = ex2(vA[i] - mA);
      pick_v(bO, vB, fl);
      pick_u(bO + 28, vB + 8, fl);
#pragma unroll
      for (int i = 0; i < 8; i += 2) vB[i] = sel<kColB>(vB[i], eB[i], fl), vB[i + 1] = sel<kColB * 2>(vB[i + 1], eB[i + 1], fl);
      float mB = quad_max(own_max(vB, fl));
      if (NAT_SB) {
        fence_regs(vA);
        fence_regs(vB);
        asm volatile("" : "+f"(mB));
        sched_fence();
      }
      PROFS(7, wg, 7 + it * 12);
#pragma unroll
      for (int i = 0; i < 14; i++) vB[i] = ex2(vB[i] - mB);
      route(vA, row_rcp(vA, fl), rt, pa);
      route(vB, row_rcp(vB, fl), rt, pb);
    }
    PROFS(8, wg, 8 + it * 12);
    if (k == NAT_PK) PROFS(18, wg, 53);
    sched_fence();

    float ac0[48], ac1[48];
    {
      float z0[32], z1[32], z2[32];
      uint32_t za[24], zb[24];
      wg_fence();
      pv_chunk<0>(z0, pa, pb, meta, dV);
      wg_commit();
      pv_chunk<1>(z1, pa, pb, meta, dV);
      wg_commit();
      wg_wait<1>();
      if (k == NAT_PK) PROFS(18, wg, 54);
      if (k + 1 < nt) nb_arrive_p(7);
      pv_chunk<2, 0, 3>(z2, pa, pb, meta, dV);
      wg_commit();
      sched_fence();
      fence_regs(z0);
      pack_z<0>(z0, za, zb);
      sched_fence();
      wg_fence();
      pv_chunk<2, 3, 7>(z2, pa, pb, meta, dV);
      wg_commit();
      wg_wait<2>();
      if (k == NAT_PK) PROFS(19, wg, 55);
      if (k + 1 < nt) nb_arrive_p(8);
      if (k < 2) mbar_wait(k == 1 ? bar_wok(bars) : bar_w2a(bars), 0);
      wg_fence();
      g2_steps<0, 3, 0>(ac0, za, zb, dX0);
      wg_commit();
      sched_fence();
      fence_regs(z1);
      pack_z<1>(z1, za, zb);
      sched_fence();
      wg_fence();
      g2_steps<3, 4, 0>(ac0, za, zb, dX0);
      wg_commit();
      g2_steps<4, 8, 0>(ac0, za, zb, dX0);
      wg_commit();
      wg_wait<3>();
      if (k + 1 < nt) nb_arrive_p(9);
      else nb_arrive(11);
      if (k == NAT_PK) PROFS(20, wg, 56);
      keep_regs(pa);
      keep_regs(pb);
      keep_regs(meta);
      sched_fence();
      const uint32_t mok = mbar_test(bar_w2m(bars), k + 1 < nt ? k & 1 : ~k & 1);
      const uint32_t wp = k < 2 ? 0 : k + 1 < nt ? ~k & 1 : k & 1, wok = mbar_test(bar_w2(bars), wp);
      fence_regs(z2);
      pack_z<2>(z2, za, zb);
      keep_regs(za);
      keep_regs(zb);
      sched_fence();
      PROFS(9, wg, 9 + it * 12);
      wg_wait<1>();
      if (k > 0 && k + 1 < nt) nb_arrive(11);
      mbar_wait_if(mok, bar_w2m(bars), k & 1);
      wg_fence();
      g2_steps<8, 12, 0>(ac0, za, zb, dX2);
      wg_commit();
      g2_steps<8, 12, 8>(ac1, za, zb, dY2);
      wg_commit();
      wg_wait<2>();
      if (k > 0 && k + 1 < nt) nb_arrive(12);
      mbar_wait_if(wok, bar_w2(bars), wp);
      wg_fence();
      g2_steps<0, 4, 8>(ac1, za, zb, dY0);
      wg_commit();
      wg_wait<2>();
      if (k + 2 < nt) nb_arrive_p(13);
      const bool direct = k + 2 >= nt;
      sched_fence();
      fence_regs(ac0);
      pack_out<0>(ac0, oa, ob);
      store_rows<0, NAT_D0>(direct, poA, poB, oa, ob);
      sched_fence();
      wg_fence();
      g2_steps<4, 8, 8>(ac1, za, zb, dY0);
      wg_commit();
      if (k + 1 < nt) nb_arrive(3 + wg);
      PROFS(10, wg, 10 + it * 12);
      wg_wait<2>();
      if (k + 2 < nt && (k > 0 || nt == 6)) nb_arrive_p(5);
      store_rows<NAT_D0, 3>(direct, poA, poB, oa, ob);
      __nv_bfloat16 *qA = poA - 192 * wg, *qB = poB - 192 * wg;
      if (k + 2 == nt) nb_sync(11);
      sched_fence();
      wg_wait<0>();
      fence_regs(ac1);
      pack_out<1>(ac1, oa, ob);
      asm volatile("" : "+l"(qA), "+l"(qB));
      store_rows<3, 6>(direct, qA, qB, oa, ob);
      if (k == 0) {
        bool first = true;
        for (;; first = false) {
          uint32_t m[2] = {oa[0], oa[1]};
#pragma unroll
          for (int i = 2; i < 24; i++) asm("max.NaN.bf16x2 %0, %0, %1;" : "+r"(m[i & 1]) : "r"(oa[i]));
          asm("max.NaN.bf16x2 %0, %0, %1;" : "+r"(m[0]) : "r"(m[1]));
          uint32_t nan;
          asm volatile("{\n.reg .pred p;\nsetp.ne.u32 p, %1, 0;\nbar.red.or.pred p, 15, 128, p;\nselp.u32 %0, 1, 0, p;\n}\n"
                       : "=r"(nan) : "r"(((m[0] & 0x7FFF7FFFu) + 0x007F007Fu) & 0x80008000u) : "memory");
          if (__builtin_expect(!__any_sync(0xffffffffu, nan), 1)) break;
          for (int c = 0; c < 3 && __any_sync(0xffffffffu, geo[2] & 1u); c++) mbar_wait(bar_x(bars, 1, c), 1);
          if (!__any_sync(0xffffffffu, refetch(sbase + kW2Off, wimg + w2_offset(), first))) break;
          wg_fence();
          g2_steps<0, 8, 0>(ac0, za, zb, dX0);
          g2_steps<8, 12, 0>(ac0, za, zb, dX2);
          g2_steps<8, 12, 8>(ac1, za, zb, dY2);
          g2_steps<0, 8, 8>(ac1, za, zb, dY0);
          wg_commit();
          wg_wait<0>();
          fence_regs(ac0);
          fence_regs(ac1);
          pack_out<0>(ac0, oa, ob);
          pack_out<1>(ac1, oa, ob);
        }
        if (!first && __any_sync(0xffffffffu, geo[2] & 1u)) {
          asm volatile("bar.sync 15, 128;" ::: "memory");
          if (w == 0 && elect_one()) {
            const TileCoord tc = decode_tile(tt, tile0 + 2);
            mbar_arrive_expect_tx(bar_raw(bars), kWChunk);
#pragma unroll 1
            for (int c = 0; c < 3; c++) load_px(tm, tt, sbase + x_chunk(2, c), bar_raw(bars), first_line(tc) + c, tc.kind);
          }
          __syncwarp();
          mbar_wait(bar_raw(bars), 0);
        }
        if (nt < 6) nb_arrive_p(5);
        if (elect_one()) mbar_arrive(bar_wok(bars));
      }
      keep_regs(za);
      keep_regs(zb);
#pragma unroll
      for (int i = 0; i < 4; i++) geo[i] = geo[i + 2];
      keep_regs(oa);
      keep_regs(ob);
      PROFS(12, wg, 12 + it * 12);
      sched_fence();
    }
  }
  PROF(wg, 38);
  GT_DUMP();
  PROF_DUMP(wg);
}

struct HaloCols { int vj, vc, uj, uc; };
__device__ __forceinline__ HaloCols halo_cols(const TileCoord& tc) {
  const int c0 = halo_c0(tc);
  return HaloCols{c0 > 98, c0 > 98 ? 98 : c0 + 3, c0 < 0 ? -1 : 0, c0 < 0 ? 4 : c0};
}
__device__ __forceinline__ void first_halo(const Maps& tm, uint32_t sbase, const TileCoord tc, int i) {
  const HaloCols hc = halo_cols(tc);
  const uint32_t dst = sbase + i * kChunkBytes, bar = bar_full(sbase + kBarOff, 0, i >> 1);
  const int h0 = halo_r0(tc), ch = 24 * tc.pc + 4 * i;
  tma_load_5d(dst, &tm.v14, bar, ch, hc.vj, hc.vc, tc.pr, h0);
  tma_load_5d(dst + 7 * 1024, &tm.u8, bar, ch, hc.uj, h0 + (tc.up ? 0 : -2), tc.pr, hc.uc);
  tma_load_5d(dst + 10 * 1024, &tm.u8, bar, ch, hc.uj, h0 + (tc.up ? 8 : 6), tc.pr, hc.uc);
}
__device__ __forceinline__ void load_halo(const Maps& tm, uint32_t sbase, uint32_t bars, const TileCoord tc, int k, int c) {
  const HaloCols hc = halo_cols(tc);
  const int h6 = halo_r0(tc) + (tc.up ? 0 : 8), h2 = halo_r0(tc) + 6, h8 = halo_r0(tc) + (tc.up ? 0 : 6), ch = 24 * tc.pc + 8 * c;
  uint32_t dv = sbase + 2 * c * kChunkBytes, du = dv + 7 * 1024;
  if (((k ^ tc.up) & 1) == 0) dv += 4 * 1024, du += 3 * 1024;
  const uint32_t bar = bar_full(bars, k & 1, c);
  mbar_arrive_expect_tx(bar, 14 * 1024);
  nb_sync_p(7 + c);
#pragma unroll
  for (int h = 0; h < 2; h++) {
    tma_load_5d(dv + h * kChunkBytes, &tm.v6, bar, ch + 4 * h, hc.vj, hc.vc, tc.pr, h6);
    tma_load_5d(du + h * kChunkBytes, &tm.u8, bar, ch + 4 * h, hc.uj, h8, tc.pr, hc.uc);
    tma_load_5d(sbase + (2 * c + h) * kChunkBytes + 3 * 1024, &tm.v2, bar, ch + 4 * h, hc.vj, hc.vc, tc.pr, h2);
  }
  PROFS(15, 2, k * 4 + c);
}
__device__ __forceinline__ void gather_px(const __nv_bfloat16* __restrict__ x, uint32_t sbase, const TileCoord tc) {
  const int lane = threadIdx.x & 31, g = lane >> 3;
  uint32_t ro[4], co[4];
#pragma unroll
  for (int i = 0; i < 4; i++) {
    ro[i] = qpix(tc.pr, 8 * tc.I + 2 * i + (g & 1)) * (kW * kC * 2) + 16 * (lane & 7);
    co[i] = qpix(tc.pc, 8 * tc.J + 2 * i + (g >> 1)) * (kC * 2);
  }
  const uint32_t dst = sbase + kXOff + g * 128 + (((lane & 7) ^ g) << 4);
  if (lane < 8)
    asm volatile("cp.async.bulk.prefetch.L2.global [%0], 3456;" ::"l"(x + (qpix(tc.pr, 8 * tc.I + lane) * kW + 215 * tc.pc) * kC) : "memory");
  __syncwarp();
  keep_regs(ro);
  keep_regs(co);
  sched_fence();
  nb_sync_p(13);
  nb_sync_p(5);
#pragma unroll
  for (int i = 0; i < 16; i++) {
    const char* src = (const char*)x + (ro[i >> 2] + co[i & 3]);
#pragma unroll
    for (int q = 0; q < 3; q++)
      asm volatile("cp.async.cg.shared.global [%0], [%1], 16;" ::"r"((dst ^ ((i & 1) * 576)) + (i >> 1) * 1024 + q * 8192), "l"(src + 128 * q) : "memory");
  }
  asm volatile("cp.async.wait_all;" ::: "memory");
  fence_proxy_async();
  __syncwarp();
  if (lane < 3) mbar_arrive(bar_x(sbase + kBarOff, 1, lane));
  __syncwarp();
}

__global__ void __launch_bounds__(384, 1)
nat_kernel(const __nv_bfloat16* __restrict__ x, __nv_bfloat16* out, const __nv_bfloat16* __restrict__ wqkv,
           const __nv_bfloat16* __restrict__ wo, uint8_t* wimg, const uint32_t zero,
           const __grid_constant__ Maps tm, const __grid_constant__ TileTable tt) {
  extern __shared__ uint8_t smem_raw[];
  constexpr uint32_t sbase = 1024;
  constexpr uint32_t bars = sbase + kBarOff;
  if (smem_u32(smem_raw) != sbase) __trap();
  const int tid = threadIdx.x;
  const uint32_t t_start = now_ns();
  if (tid == 0) GT(0);
  const int wid = __shfl_sync(0xffffffffu, tid >> 5, 0);
  const bool w2cta = blockIdx.x - 128 < 3 && wqkv != nullptr;
  if (wid >= 8) {
    asm volatile("setmaxnreg.dec.sync.aligned.u32 24;");
    const int c = wid & 3, lane = tid & 31;
    const int tile0 = blockIdx.x * kTilesPerCta, nt = num_tiles();
    uint32_t w2o = 0;
    if (c == 3) {
      if (elect_one()) wait_clock(t_start, NAT_TM);
      __syncwarp();
      asm volatile("prefetch.tensormap [%0];" ::"l"((uint64_t)tm.px) : "memory");
      asm volatile("prefetch.tensormap [%0];" ::"l"((uint64_t)&tm.v6) : "memory");
      asm volatile("prefetch.tensormap [%0];" ::"l"((uint64_t)&tm.v2) : "memory");
      asm volatile("prefetch.tensormap [%0];" ::"l"((uint64_t)(tm.px + (blockIdx.x < 112 ? 5 : 6))) : "memory");
      asm volatile("prefetch.tensormap [%0];" ::"l"((uint64_t)(tm.px + 7)) : "memory");
      if (nt < 6) {
        asm volatile("prefetch.tensormap [%0];" ::"l"((uint64_t)(tm.px + 1)) : "memory");
        asm volatile("prefetch.tensormap [%0];" ::"l"((uint64_t)(tm.px + 2)) : "memory");
        asm volatile("prefetch.tensormap [%0];" ::"l"((uint64_t)&tm.v14) : "memory");
        asm volatile("prefetch.tensormap [%0];" ::"l"((uint64_t)&tm.u8) : "memory");
      }
      __nanosleep(NAT_TW2 - 2800);
      asm volatile("bar.sync 4, 64;" ::: "memory");
      w2o = w2_offset();
      if (elect_one()) {
        mbar_arrive_expect_tx(bar_w2a(bars), kWChunk);
        mbar_arrive_expect_tx(bar_w2(bars), kWChunk);
        wait_clock(t_start, NAT_TW2);
        bulk_load(sbase + kW2Off, wimg + w2o, kWChunk, bar_w2a(bars));
        mbar_wait(bar_xf(bars), 0);
        bulk_load(sbase + kW2Off + 2 * kWChunk, wimg + (w2o + 2 * kWChunk), kWChunk, bar_w2(bars));
      }
      __syncwarp();
      if (nt < 6) gather_px(x, sbase, decode_tile(tt, tile0 + 2));
      if (wqkv == nullptr) return;
      mbar_wait(bar_wok(bars), 0);
      if (lane == 0) asm volatile("red.relaxed.gpu.global.add.u32 [%0], 1;" ::"l"(g_flag) : "memory");
      if (blockIdx.x >= 48) return;
      if (lane == 0) {
        uint32_t v, it = 0;
        do {
          __nanosleep(2000);
          asm volatile("ld.relaxed.gpu.global.u32 %0, [%1];" : "=r"(v) : "l"(g_flag) : "memory");
        } while (v < gridDim.x && ++it < (1u << 16));
      }
      __syncwarp();
#pragma unroll
      for (int i = 0; i < 6; i++)
        stg128(wimg + ((i < 3 ? 0u : 3 * kWBytes - w2o) + blockIdx.x * 1536 + (i % 3) * 512 + lane * 16), kEmpty, kEmpty, kEmpty, kEmpty);
      if (lane == 0 && atomicAdd(g_flag + 32, 1u) == 47) {
        g_flag[0] = g_flag[32] = 0;
        g_flag[64] = w2o == kWBytes;
      }
      return;
    }
    if (!elect_one()) return;
    if (c == 0) {
      for (int i = 0; i < kNumBars; i++)
        if ((i != 0 && i != 10 || nt < 6) && (i != 21 || !w2cta)) mbar_init(bars + i * 8, i == 13 || i == 16 ? 4 : 1);
      asm volatile("st.shared.v2.u32 [%0], {%1,%1};" ::"r"(bars + 192), "r"(0) : "memory");
      asm volatile("fence.mbarrier_init.release.cluster;" ::: "memory");
      if (w2cta) asm volatile("bar.sync 10, 64;" ::: "memory");
      asm volatile("bar.arrive 0, 160;" ::: "memory");
      asm volatile("bar.arrive 14, 160;" ::: "memory");
      asm volatile("bar.arrive 13, 96;" ::: "memory");
      asm volatile("bar.arrive 4, 64;" ::: "memory");
      const TileCoord tc0 = decode_tile(tt, tile0);
      const HaloCols hc = halo_cols(tc0);
      const int h0 = halo_r0(tc0);
#pragma unroll
      for (int j = 0; j < 3; j++)
        if (j > 0 || nt < 6) mbar_arrive_expect_tx(bar_full(bars, 0, j), 2 * kChunkBytes);
      wait_clock(t_start, NAT_HP);
#pragma unroll
      for (int q = 8; q < 24 && !w2cta; q += 8) {
        tma_prefetch_5d(blockIdx.x < 112 ? &tm.v6 : &tm.v14, 24 * tc0.pc + q, hc.vj, hc.vc, tc0.pr, h0 + (tc0.up || blockIdx.x >= 112 ? 0 : 8));
        tma_prefetch_5d(&tm.u8, 24 * tc0.pc + q, hc.uj, h0 + (tc0.up ? 0 : 6), tc0.pr, hc.uc);
      }
#pragma unroll 1
      for (int i = nt < 6 ? 0 : 2; i < 7; i++) {
        if (i == NAT_H0) mbar_wait(bar_w1q(bars), 0);
        if (i == NAT_X1P) mbar_arrive(bar_go(bars));
        if (i < 6) first_halo(tm, sbase, tc0, i);
      }
      w2o = w2_offset();
    } else {
      asm volatile("bar.sync 13, 96;" ::: "memory");
      if (c == 2) {
        if (wqkv != nullptr && blockIdx.x < 131) asm volatile("bar.sync 12, 64;" ::: "memory");
        const uint32_t c0 = clock();
        while ((uint32_t)clock() - c0 < NAT_TD && nt == 6) { }
        wait_clock(t_start, NAT_T0);
#pragma unroll
        for (int j = 0; j < 3; j++) {
          mbar_arrive_expect_tx(bar_w1c(bars, j), kWChunk);
          bulk_load(sbase + kW1Off + j * kWChunk, wimg + j * kWChunk, kWChunk, bar_w1c(bars, j));
        }
        mbar_arrive(bar_w1q(bars));
        GT(2);
      } else {
#pragma unroll 1
        for (int j = nt == 6; j < 2; j++) {
          const TileCoord tc = decode_tile(tt, tile0 + j);
          const int line = first_line(tc);
          if (j == 1) mbar_wait(bar_go(bars), 0);
          if (j == 0) GT(15);
#pragma unroll 1
          for (int q = 0; q < 3; q++) {
            load_px(tm, tt, sbase + x_chunk(j, q), bar_x(bars, j, q), line + q, tc.kind);
            if (j == 1 || q == 0) mbar_arrive_expect_tx(bar_x(bars, j, q), j ? 8192 : kWChunk);
          }
          if (j == 0) GT(16);
        }
        w2o = w2_offset();
        wait_clock(t_start, NAT_TW2);
        mbar_wait(bar_xf(bars), 0);
      }
    }
#pragma unroll 1
    for (int k = 1; k < nt; k++) {
      const TileCoord tn = decode_tile(tt, tile0 + k + 1);
      const int line = first_line(tn);
      const bool more = k + 1 < nt && (k > 1 || nt == 6);
      if (c == 1) {
#pragma unroll
        for (int q = 3 - NAT_MP; q < 3; q++) {
          const uint32_t n = q == 3 - NAT_MP ? q + 1 : 1, o = x_chunk(k, k & 1 ? q : q + 1 - n);
          nb_sync_p(q == 0 ? 0 : q == 1 ? 14 : 6);
          bulk_load(sbase + o, wimg + (w2o + o - kW2Off), n * 8192, bar_w2m(bars));
        }
        mbar_arrive_expect_tx(bar_w2m(bars), kWChunk);
      }
      if (c == 2) {
        if (k == 1) wait_clock(t_start, NAT_TX2);
        else __nanosleep(NAT_PFD);
#pragma unroll 1
        for (int q = 0; q < 3 && more; q++) load_px(tm, tt, 0, 0, line + q, tn.kind);
      }
      if (c == 2 && (blockIdx.x >= 112 || k == 5)) {
        const TileCoord tc = decode_tile(tt, tile0 + k);
        const HaloCols hc = halo_cols(tc);
        const int h8 = halo_r0(tc) + (tc.up ? 0 : 6);
#pragma unroll 1
        for (int q = 0; q < 24; q += 8) {
          tma_prefetch_5d(&tm.v6, 24 * tc.pc + q, hc.vj, hc.vc, tc.pr, h8);
          tma_prefetch_5d(&tm.v2, 24 * tc.pc + q, hc.vj, hc.vc, tc.pr, h8 + 6);
          tma_prefetch_5d(&tm.u8, 24 * tc.pc + q, hc.uj, h8, tc.pr, hc.uc);
        }
      }
      load_halo(tm, sbase, bars, decode_tile(tt, tile0 + k), k, c);
      if (c == 0 && more) {
#pragma unroll
        for (int q = 0; q < 3; q++) {
          if (q < 2) nb_sync_p(q ? 5 : 13);
          load_px(tm, tt, sbase + x_chunk(k + 1, q), bar_x(bars, 1, q), line + q, tn.kind);
          if (q != 1) mbar_arrive_expect_tx(bar_x(bars, 1, q), 8192);
        }
        mbar_arrive_expect_tx(bar_x(bars, 1, 1), 8192);
        PROFS(16, 2, k * 4 + 3);
      }
      if (c == 0 && k >= 2) {
        const TileCoord tp = decode_tile(tt, tile0 + k - 2);
        const int lp = first_line(tp);
        nb_sync_p(10);
        __nanosleep(NAT_XW);
        store_px(tm, tt, sbase + out_slot(k, nt), lp, tp.kind);
        if (k + 1 < nt) {
          asm volatile("cp.async.bulk.wait_group.read 0;" ::: "memory");
          bulk_load(sbase + out_slot(k, nt), wimg + (w2o + out_slot(k, nt) - kW2Off), kWChunk, bar_w2(bars));
          mbar_arrive_expect_tx(bar_w2(bars), kWChunk);
        }
      }
    }
    asm volatile("cp.async.bulk.wait_group 0;" ::: "memory");
  } else {
    if (blockIdx.x < 128) {
      if ((wid == 4 || (wid == 5 && blockIdx.x - 2 < 16)) && wqkv != nullptr) {
        fold_w1(blockIdx.x - 2 < 16 ? 2 * blockIdx.x + wid - 6 : blockIdx.x + (blockIdx.x < 2 ? 0 : 16), wqkv, wimg);
        if (wid == 4) asm volatile("bar.arrive 12, 64;" ::: "memory");
        if (tid == 128) GT(7);
      }
      sched_fence();
      if (wid == 1 && elect_one()) {
        const TileCoord tc = decode_tile(tt, blockIdx.x * kTilesPerCta);
        mbar_init(bar_x(bars, 0, 0), 1);
        asm volatile("fence.mbarrier_init.release.cluster;" ::: "memory");
        mbar_arrive_expect_tx(bar_x(bars, 0, 0), kWChunk);
        GT(15);
#pragma unroll 1
        for (int q = 0; q < 3; q++) load_px(tm, tt, sbase + x_chunk(0, q), bar_x(bars, 0, 0), first_line(tc) + q, tc.kind);
        GT(16);
      }
      __syncwarp();
      sched_fence();
      if (wid == 2 && elect_one()) {
        const TileCoord tc = decode_tile(tt, blockIdx.x * kTilesPerCta);
        mbar_init(bar_full(bars, 0, 0), 1);
        asm volatile("fence.mbarrier_init.release.cluster;" ::: "memory");
        mbar_arrive_expect_tx(bar_full(bars, 0, 0), 2 * kChunkBytes);
        if (NAT_TH) wait_clock(t_start, NAT_TH);
        asm volatile("prefetch.tensormap [%0];" ::"l"((uint64_t)&tm.u8) : "memory");
        GT(17);
        first_halo(tm, sbase, tc, 0);
        first_halo(tm, sbase, tc, 1);
      }
      __syncwarp();
    }
    sched_fence();
    {
      if (w2cta) {
        const int q = blockIdx.x & 3;
        uint32_t w2o = 0;
        if (wid == 1 && elect_one()) {
          asm volatile("prefetch.tensormap [%0];" ::"l"((uint64_t)&tm.wo) : "memory");
#pragma unroll
          for (int j = 0; j < 3; j++) mbar_init(bar_raw(bars, j), 1);
          asm volatile("fence.mbarrier_init.release.cluster;" ::: "memory");
#pragma unroll
          for (int j = 0; j < 6; j++)
            asm volatile("cp.async.bulk.tensor.2d.shared::cluster.global.tile.mbarrier::complete_tx::bytes [%0], [%1, {%3, %4}], [%2];" ::"r"(
                             j < 3 ? sbase + j * 8192 : sbase + kW2Off + (j - 3) * kWChunk),
                         "l"((uint64_t)(j < 3 ? &tm.wv : &tm.wo)), "r"(bar_raw(bars, j < 3 ? 0 : j - 3)),
                         "r"(j < 3 ? 384 + 64 * j : 64 * (j - 3)), "r"(j < 3 ? 64 * q : 0) : "memory");
#pragma unroll
          for (int j = 0; j < 3; j++) mbar_arrive_expect_tx(bar_raw(bars, j), j ? kWChunk : 2 * kWChunk);
          w2o = w2_offset();
        }
        __syncwarp();
#pragma unroll 1
        for (int r = 0; r < 3; r++) {
          const int blk = 2 * r - 2 + (wid >> 2);
          if (blk < 3) {
            if (r > 0) {
              mbar_wait(bar_raw(bars, 0), 0);
              mbar_wait(bar_raw(bars, blk), 0);
            }
            if (tid == 0 && r == 1) GT(7);
            float acc[32];
            const uint64_t db = make_desc(sbase + kW2Off + max(blk, 0) * kWChunk, kWChunk, 1024);
            wg_fence();
            wg_m64tz<0, 32>(acc, make_desc(sbase, 16, 1024), db, 0);
#pragma unroll
            for (int s = 1; s < 12; s++) wg_m64t<0, 32>(acc, make_desc(sbase + (s >> 2) * 8192 + (s & 3) * 32, 16, 1024), db + s * 128, 1);
            wg_commit();
            wg_wait<0>();
            fence_regs(acc);
            if (tid == 0) GT(19);
            const int m = (tid >> 3) & 3;
#pragma unroll
            for (int j = 0; j < 8; j += 2) {
              const int n = g2_inv(8 * (j + (m >> 1)) + (tid & 7));
              asm volatile("stmatrix.sync.aligned.m8n8.x4.trans.shared.b16 [%0], {%1,%2,%3,%4};" ::"r"(
                               sbase + kW1Off + (blk + 2) * 8192 + n * 128 + (((2 * (wid & 3) + (m & 1)) ^ (n & 7)) << 4)),
                           "r"(pack_bf16(acc[4 * j], acc[4 * j + 1])), "r"(pack_bf16(acc[4 * j + 2], acc[4 * j + 3])),
                           "r"(pack_bf16(acc[4 * j + 4], acc[4 * j + 5])), "r"(pack_bf16(acc[4 * j + 6], acc[4 * j + 7])) : "memory");
            }
            fence_proxy_async();
          }
          if (tid == 0) GT(18);
          asm volatile("bar.sync 11, 256;" ::: "memory");
          if (wid == 1 && elect_one()) {
            asm volatile("{\n.reg .pred p;\nsetp.ne.s32 p, %3, 0;\n@p cp.async.bulk.global.shared::cta.bulk_group [%0], [%1], %2;\n}\n" ::"l"(
                             wimg + (w2o + w2piece(r >> 1, q) * (kWChunk / 2))),
                         "r"(sbase + kW1Off + 16384 + (r >> 1) * (kWChunk / 2)), "r"(kWChunk / 2), "r"(r) : "memory");
            asm volatile("cp.async.bulk.commit_group;" ::: "memory");
          }
          __syncwarp();
        }
        if (wid == 1) {
          asm volatile("bar.arrive 10, 64;" ::: "memory");
          if (elect_one()) asm volatile("cp.async.bulk.wait_group.read 0;" ::: "memory");
          if (tid == 32) GT(31);
          __syncwarp();
          asm volatile("bar.arrive 12, 64;" ::: "memory");
        }
      }
    }
    __syncwarp();
    if (wid < 4) asm volatile("bar.sync 0, 160;" ::: "memory");
    else asm volatile("bar.sync 14, 160;" ::: "memory");
    asm volatile("setmaxnreg.inc.sync.aligned.u32 240;");
    consumer(wid >> 2, out, wimg, sbase, zero, tm, tt);
  }
}

}

typedef CUresult (*PFN_encodeTiled)(CUtensorMap*, CUtensorMapDataType, cuuint32_t, void*, const cuuint64_t*,
                                    const cuuint64_t*, const cuuint32_t*, const cuuint32_t*, CUtensorMapInterleave,
                                    CUtensorMapSwizzle, CUtensorMapL2promotion, CUtensorMapFloatOOBfill);

extern "C" void kernel_launch(void* const* d_in, const int* in_sizes, int n_in, void* d_out, int out_size) {
  const __nv_bfloat16* x = (const __nv_bfloat16*)d_in[0];
  const __nv_bfloat16* wqkv = (const __nv_bfloat16*)d_in[1];
  const __nv_bfloat16* wo = (const __nv_bfloat16*)d_in[2];
  __nv_bfloat16* out = (__nv_bfloat16*)d_out;

  static PFN_encodeTiled encode = nullptr;
  static int num_sms = 0;
  static uint8_t* wimg = nullptr;
  if (!encode) {
    void* fn = nullptr;
    cudaDriverEntryPointQueryResult qres;
    cudaGetDriverEntryPoint("cuTensorMapEncodeTiled", &fn, cudaEnableDefault, &qres);
    encode = (PFN_encodeTiled)fn;
    cudaFuncSetAttribute(nat::nat_kernel, cudaFuncAttributeMaxDynamicSharedMemorySize, nat::kSmemBytes);
    cudaGetSymbolAddress((void**)&wimg, nat::g_wimg32);
    int dev = 0;
    cudaGetDevice(&dev);
    cudaDeviceGetAttribute(&num_sms, cudaDevAttrMultiProcessorCount, dev);
  }
  nat::Maps tm;
  cuuint32_t estr[5] = {1, 1, 1, 1, 1};
  {
    cuuint64_t vdim[5] = {48, 2, 105, 2, 112}, udim[5] = {48, 2, 112, 2, 105};
    cuuint64_t vstr[4] = {7 * 768, 768, 224 * 384, 2 * 224 * 384}, ustr[4] = {7 * 768, 2 * 224 * 384, 224 * 384, 768};
    CUtensorMap* maps[4] = {&tm.v6, &tm.v2, &tm.v14, &tm.u8};
    for (int i = 0; i < 4; i++) {
      cuuint32_t box[5] = {4, 2, i < 3 ? 4u : 8u, 1, i == 0 ? 6u : i == 1 ? 2u : i == 2 ? 14u : 3u};
      encode(maps[i], CU_TENSOR_MAP_DATA_TYPE_UINT32, 5, (void*)x, i < 3 ? vdim : udim, i < 3 ? vstr : ustr, box, estr,
             CU_TENSOR_MAP_INTERLEAVE_16B, CU_TENSOR_MAP_SWIZZLE_128B, CU_TENSOR_MAP_L2_PROMOTION_L2_128B, CU_TENSOR_MAP_FLOAT_OOB_FILL_NONE);
    }
  }
  for (int i = 0; i < 8; i++) {
    const cuuint32_t row = 224 * 384;
    const cuuint32_t shape[8][6] = {{2, 8, 4, 2 * row, 768, 4 * row}, {2, 8, 3, row, 768, 2 * row},     {2, 8, 1, 2 * row, 768, 4 * row},
                                    {8, 2, 3, 2 * row, 4 * 384, 384}, {8, 2, 1, 2 * row, 5 * 384, 384}, {4, 2, 3, 4 * row, 2 * row, 128},
                                    {4, 2, 3, 768, row, 128},         {4, 2, 3, 768, 2 * row, 128}};
    const cuuint32_t* sh = shape[i];
    cuuint64_t dim[5] = {64, sh[0], sh[1], sh[2], 224 * 224 * 3};
    cuuint64_t str[4] = {sh[3], sh[4], sh[5], 128};
    cuuint32_t box[5] = {64, sh[0], sh[1], sh[2], 1};
    encode(tm.px + i, CU_TENSOR_MAP_DATA_TYPE_BFLOAT16, 5, i < 5 ? (void*)x : (void*)out, dim, str, box, estr, CU_TENSOR_MAP_INTERLEAVE_NONE,
           CU_TENSOR_MAP_SWIZZLE_128B, i < 5 ? CU_TENSOR_MAP_L2_PROMOTION_L2_128B : CU_TENSOR_MAP_L2_PROMOTION_NONE,
           CU_TENSOR_MAP_FLOAT_OOB_FILL_NONE);
  }
  for (int i = 0; i < 2; i++) {
    cuuint64_t dim[2] = {i ? 192u : 576u, 192}, str[1] = {i ? 384u : 1152u};
    cuuint32_t box[2] = {64, i ? 192u : 64u};
    encode(i ? &tm.wo : &tm.wv, CU_TENSOR_MAP_DATA_TYPE_BFLOAT16, 2, i ? (void*)wo : (void*)wqkv, dim, str, box, estr,
           CU_TENSOR_MAP_INTERLEAVE_NONE, CU_TENSOR_MAP_SWIZZLE_128B, CU_TENSOR_MAP_L2_PROMOTION_L2_256B, CU_TENSOR_MAP_FLOAT_OOB_FILL_NONE);
  }
  nat::TileTable tt;
  nat::make_tiles(tt);
  const int grid = nat::kCtas;
  if (num_sms >= grid) {
    nat::nat_kernel<<<grid, 384, nat::kSmemBytes>>>(x, out, wqkv, wo, wimg, 0u, tm, tt);
  } else {
    nat::fold_kernel<<<27, 256>>>(wqkv, wo, wimg);
    nat::nat_kernel<<<grid, 384, nat::kSmemBytes>>>(x, out, nullptr, nullptr, wimg, 0u, tm, tt);
  }
}
```

```cpp
#include <cuda_runtime.h>
#include <cuda_bf16.h>
#include <cuda.h>
#include <stdint.h>

#define NAT_TM 1300
#define NAT_HP 1800
#define NAT_T0 2100
#define NAT_TD 1200
#define NAT_TX2 3800
#define NAT_TW2 4650
#define NAT_PFD 400
#define NAT_XW 200
#define NAT_PK 3
namespace nat {

constexpr int kW = 224, kC = 192;
constexpr int kCtas = 132;
constexpr int kTilesPerCta = 6;
constexpr float kAlpha = 0.07216878364870322f * 1.4426950408889634f;
constexpr uint32_t kChunkBytes = 13 * 1024;
constexpr uint32_t kWChunk = 192 * 128;
constexpr uint32_t kWBytes = 3 * kWChunk;
constexpr uint32_t kW1Off = 6 * kChunkBytes;
constexpr uint32_t kW2Off = kW1Off + kWBytes;
constexpr uint32_t kXOff = kW2Off + kWChunk;
constexpr uint32_t kBarOff = kW2Off + kWBytes;
constexpr uint32_t kProfOff = kBarOff + 208;
constexpr uint32_t kSmemBytes = kBarOff + 1024;

static_assert(kW1Off % 1024 == 0 && kW2Off % 1024 == 0 && kChunkBytes % 1024 == 0, "swizzle alignment");
static_assert(kSmemBytes <= 232448, "smem");

constexpr uint32_t kEmpty = 0xFFFFFFFFu;
#define NAT_R8(v) v, v, v, v, v, v, v, v
#define NAT_R2K(v) NAT_R8(NAT_R8(NAT_R8(v))), NAT_R8(NAT_R8(NAT_R8(v))), NAT_R8(NAT_R8(NAT_R8(v))), NAT_R8(NAT_R8(NAT_R8(v)))
#define NAT_IMG NAT_R8(NAT_R2K(kEmpty)), NAT_R2K(kEmpty)
__device__ __align__(1024) uint32_t g_wimg32[3 * kWBytes / 4] = {NAT_IMG, NAT_IMG, NAT_IMG};
static_assert(kWBytes / 4 == 9 * 2048, "initialiser");
__device__ __align__(128) uint32_t g_flag[96];
__device__ __forceinline__ uint32_t w2_offset() {
  uint32_t v;
  asm volatile("ld.relaxed.gpu.global.u32 %0, [%1];" : "=r"(v) : "l"(g_flag + 64) : "memory");
  return (1 + v) * kWBytes;
}

#define PROFS(id, wgid, slotid) do { } while (0)
#define PROF(wgid, slotid) do { } while (0)
#define PROF_DUMP(wgid) do { } while (0)

#define GT(slotid) do { } while (0)
#define GT_DUMP() do { } while (0)

__device__ __forceinline__ uint32_t smem_u32(const void* p) { return (uint32_t)__cvta_generic_to_shared(p); }

__device__ __forceinline__ void mbar_init(uint32_t bar, uint32_t count) {
  asm volatile("mbarrier.init.shared::cta.b64 [%0], %1;" ::"r"(bar), "r"(count) : "memory");
}
__device__ __forceinline__ void mbar_arrive(uint32_t bar) {
  asm volatile("mbarrier.arrive.shared::cta.b64 _, [%0];" ::"r"(bar) : "memory");
}
__device__ __forceinline__ void mbar_arrive_expect_tx(uint32_t bar, uint32_t bytes) {
  asm volatile("mbarrier.arrive.expect_tx.shared::cta.b64 _, [%0], %1;" ::"r"(bar), "r"(bytes) : "memory");
}
__device__ __forceinline__ void mbar_wait(uint32_t bar, uint32_t parity) {
  uint32_t ok;
  uint32_t it = 0;
  do {
    asm volatile(
        "{\n.reg .pred p;\n"
        "mbarrier.try_wait.parity.shared::cta.b64 p, [%1], %2;\n"
        "selp.u32 %0, 1, 0, p;\n}\n"
        : "=r"(ok)
        : "r"(bar), "r"(parity)
        : "memory");
    if (++it > (1u << 24)) break;
  } while (!ok);
}
__device__ __forceinline__ uint32_t mbar_test(uint32_t bar, uint32_t parity) {
  uint32_t ok;
  asm volatile("{\n.reg .pred p;\nmbarrier.test_wait.parity.shared::cta.b64 p, [%1], %2;\nselp.u32 %0, 1, 0, p;\n}\n"
               : "=r"(ok) : "r"(bar), "r"(parity) : "memory");
  return ok;
}
__device__ __forceinline__ void mbar_wait_if(uint32_t ok, uint32_t bar, uint32_t parity) {
  if (!__all_sync(0xffffffffu, ok)) mbar_wait(bar, parity);
}
__device__ __forceinline__ bool elect_one() {
  uint32_t r;
  asm volatile("{\n.reg .pred p;\nelect.sync _|p, 0xffffffff;\nselp.u32 %0, 1, 0, p;\n}\n" : "=r"(r));
  return r != 0;
}
__device__ __forceinline__ void nb_arrive(int id) { asm volatile("bar.arrive %0, 256;" ::"r"(id) : "memory"); }
__device__ __forceinline__ void nb_sync(int id) { asm volatile("bar.sync %0, 256;" ::"r"(id) : "memory"); }
__device__ __forceinline__ void nb_arrive_p(int id) { asm volatile("bar.arrive %0, 160;" ::"r"(id) : "memory"); }
__device__ __forceinline__ void nb_sync_p(int id) { asm volatile("bar.sync %0, 160;" ::"r"(id) : "memory"); }
__device__ __forceinline__ void fence_proxy_async() { asm volatile("fence.proxy.async.shared::cta;" ::: "memory"); }

__device__ __forceinline__ void tma_load_5d(uint32_t dst, const CUtensorMap* map, uint32_t bar, int c0, int c1, int c2,
                                            int c3, int c4) {
  asm volatile(
      "cp.async.bulk.tensor.5d.shared::cluster.global.tile.mbarrier::complete_tx::bytes "
      "[%0], [%1, {%3, %4, %5, %6, %7}], [%2];"
      ::"r"(dst), "l"((uint64_t)map), "r"(bar), "r"(c0), "r"(c1), "r"(c2), "r"(c3), "r"(c4)
      : "memory");
}
__device__ __forceinline__ void bulk_load(uint32_t dst, const void* src, uint32_t bytes, uint32_t bar) {
  asm volatile("cp.async.bulk.shared::cluster.global.mbarrier::complete_tx::bytes [%0], [%1], %2, [%3];"
               ::"r"(dst), "l"((uint64_t)src), "r"(bytes), "r"(bar)
               : "memory");
}

__device__ __forceinline__ void wg_fence() { asm volatile("wgmma.fence.sync.aligned;" ::: "memory"); }
__device__ __forceinline__ void wg_commit() { asm volatile("wgmma.commit_group.sync.aligned;" ::: "memory"); }
template <int N>
__device__ __forceinline__ void wg_wait() { asm volatile("wgmma.wait_group.sync.aligned %0;" ::"n"(N) : "memory"); }

template <int N>
__device__ __forceinline__ void fence_regs(float (&d)[N]) {
#pragma unroll
  for (int i = 0; i < N; i++) asm volatile("" : "+f"(d[i])::"memory");
}
template <int N>
__device__ __forceinline__ void keep_regs(uint32_t (&d)[N]) {
#pragma unroll
  for (int i = 0; i < N; i++) asm volatile("" : "+r"(d[i])::"memory");
}

__device__ __forceinline__ uint32_t pack_bf16(float lo, float hi) {
  uint32_t d;
  asm("cvt.rn.bf16x2.f32 %0, %1, %2;" : "=r"(d) : "f"(hi), "f"(lo));
  return d;
}
__device__ __forceinline__ float ex2(float x) {
  float y;
  asm("ex2.approx.ftz.f32 %0, %1;" : "=f"(y) : "f"(x));
  return y;
}
__device__ __forceinline__ float rcp_approx(float x) {
  float y;
  asm("rcp.approx.ftz.f32 %0, %1;" : "=f"(y) : "f"(x));
  return y;
}
__device__ __forceinline__ uint4 ldg128_nc(const void* p) {
  uint4 v;
  asm volatile("ld.global.nc.v4.u32 {%0,%1,%2,%3}, [%4];" : "=r"(v.x), "=r"(v.y), "=r"(v.z), "=r"(v.w) : "l"(p));
  return v;
}
__device__ __forceinline__ void stg128(void* p, uint32_t a, uint32_t b, uint32_t c, uint32_t d) {
  asm volatile("st.global.v4.u32 [%0], {%1,%2,%3,%4};" ::"l"(p), "r"(a), "r"(b), "r"(c), "r"(d) : "memory");
}

__device__ __forceinline__ long long clk64() {
  long long c;
  asm volatile("mov.u64 %0, %clock64;" : "=l"(c)::"memory");
  return c;
}
__device__ __forceinline__ void sched_fence() { while (clk64() < 0) { } }

__device__ __forceinline__ uint64_t make_desc(uint32_t addr, uint32_t lbo, uint32_t sbo, uint32_t mode = 1) {
  return (uint64_t)((addr & 0x3FFFF) >> 4) | ((uint64_t)(lbo >> 4) << 16) | ((uint64_t)(sbo >> 4) << 32) |
         ((uint64_t)mode << 62);
}

template <int OFF, int NN>
__device__ __forceinline__ void wg_m192(float (&d)[NN], uint64_t desc_a, uint64_t desc_b, int scale_d) {
  asm volatile(
      "{\n.reg .pred p;\nsetp.ne.b32 p, %98, 0;\n"
      "wgmma.mma_async.sync.aligned.m64n192k16.f32.bf16.bf16 "
      "{%0,%1,%2,%3,%4,%5,%6,%7,%8,%9,%10,%11,%12,%13,%14,%15,"
      "%16,%17,%18,%19,%20,%21,%22,%23,%24,%25,%26,%27,%28,%29,%30,%31,"
      "%32,%33,%34,%35,%36,%37,%38,%39,%40,%41,%42,%43,%44,%45,%46,%47,"
      "%48,%49,%50,%51,%52,%53,%54,%55,%56,%57,%58,%59,%60,%61,%62,%63,"
      "%64,%65,%66,%67,%68,%69,%70,%71,%72,%73,%74,%75,%76,%77,%78,%79,"
      "%80,%81,%82,%83,%84,%85,%86,%87,%88,%89,%90,%91,%92,%93,%94,%95}, "
      "%96, %97, p, 1, 1, 0, 0;\n}\n"
      : "+f"(d[OFF + 0]), "+f"(d[OFF + 1]), "+f"(d[OFF + 2]), "+f"(d[OFF + 3]), "+f"(d[OFF + 4]), "+f"(d[OFF + 5]),
        "+f"(d[OFF + 6]), "+f"(d[OFF + 7]), "+f"(d[OFF + 8]), "+f"(d[OFF + 9]), "+f"(d[OFF + 10]), "+f"(d[OFF + 11]),
        "+f"(d[OFF + 12]), "+f"(d[OFF + 13]), "+f"(d[OFF + 14]), "+f"(d[OFF + 15]), "+f"(d[OFF + 16]), "+f"(d[OFF + 17]),
        "+f"(d[OFF + 18]), "+f"(d[OFF + 19]), "+f"(d[OFF + 20]), "+f"(d[OFF + 21]), "+f"(d[OFF + 22]), "+f"(d[OFF + 23]),
        "+f"(d[OFF + 24]), "+f"(d[OFF + 25]), "+f"(d[OFF + 26]), "+f"(d[OFF + 27]), "+f"(d[OFF + 28]), "+f"(d[OFF + 29]),
        "+f"(d[OFF + 30]), "+f"(d[OFF + 31]), "+f"(d[OFF + 32]), "+f"(d[OFF + 33]), "+f"(d[OFF + 34]), "+f"(d[OFF + 35]),
        "+f"(d[OFF + 36]), "+f"(d[OFF + 37]), "+f"(d[OFF + 38]), "+f"(d[OFF + 39]), "+f"(d[OFF + 40]), "+f"(d[OFF + 41]),
        "+f"(d[OFF + 42]), "+f"(d[OFF + 43]), "+f"(d[OFF + 44]), "+f"(d[OFF + 45]), "+f"(d[OFF + 46]), "+f"(d[OFF + 47]),
        "+f"(d[OFF + 48]), "+f"(d[OFF + 49]), "+f"(d[OFF + 50]), "+f"(d[OFF + 51]), "+f"(d[OFF + 52]), "+f"(d[OFF + 53]),
        "+f"(d[OFF + 54]), "+f"(d[OFF + 55]), "+f"(d[OFF + 56]), "+f"(d[OFF + 57]), "+f"(d[OFF + 58]), "+f"(d[OFF + 59]),
        "+f"(d[OFF + 60]), "+f"(d[OFF + 61]), "+f"(d[OFF + 62]), "+f"(d[OFF + 63]), "+f"(d[OFF + 64]), "+f"(d[OFF + 65]),
        "+f"(d[OFF + 66]), "+f"(d[OFF + 67]), "+f"(d[OFF + 68]), "+f"(d[OFF + 69]), "+f"(d[OFF + 70]), "+f"(d[OFF + 71]),
        "+f"(d[OFF + 72]), "+f"(d[OFF + 73]), "+f"(d[OFF + 74]), "+f"(d[OFF + 75]), "+f"(d[OFF + 76]), "+f"(d[OFF + 77]),
        "+f"(d[OFF + 78]), "+f"(d[OFF + 79]), "+f"(d[OFF + 80]), "+f"(d[OFF + 81]), "+f"(d[OFF + 82]), "+f"(d[OFF + 83]),
        "+f"(d[OFF + 84]), "+f"(d[OFF + 85]), "+f"(d[OFF + 86]), "+f"(d[OFF + 87]), "+f"(d[OFF + 88]), "+f"(d[OFF + 89]),
        "+f"(d[OFF + 90]), "+f"(d[OFF + 91]), "+f"(d[OFF + 92]), "+f"(d[OFF + 93]), "+f"(d[OFF + 94]), "+f"(d[OFF + 95])
      : "l"(desc_a), "l"(desc_b), "r"(scale_d));
}

template <int OFF, int NN>
__device__ __forceinline__ void wg_m192z(float (&d)[NN], uint64_t desc_a, uint64_t desc_b, int scale_d) {
  asm volatile(
      "{\n.reg .pred p;\nsetp.ne.b32 p, %98, 0;\n"
      "wgmma.mma_async.sync.aligned.m64n192k16.f32.bf16.bf16 "
      "{%0,%1,%2,%3,%4,%5,%6,%7,%8,%9,%10,%11,%12,%13,%14,%15,"
      "%16,%17,%18,%19,%20,%21,%22,%23,%24,%25,%26,%27,%28,%29,%30,%31,"
      "%32,%33,%34,%35,%36,%37,%38,%39,%40,%41,%42,%43,%44,%45,%46,%47,"
      "%48,%49,%50,%51,%52,%53,%54,%55,%56,%57,%58,%59,%60,%61,%62,%63,"
      "%64,%65,%66,%67,%68,%69,%70,%71,%72,%73,%74,%75,%76,%77,%78,%79,"
      "%80,%81,%82,%83,%84,%85,%86,%87,%88,%89,%90,%91,%92,%93,%94,%95}, "
      "%96, %97, p, 1, 1, 0, 0;\n}\n"
      : "=f"(d[OFF + 0]), "=f"(d[OFF + 1]), "=f"(d[OFF + 2]), "=f"(d[OFF + 3]), "=f"(d[OFF + 4]), "=f"(d[OFF + 5]),
        "=f"(d[OFF + 6]), "=f"(d[OFF + 7]), "=f"(d[OFF + 8]), "=f"(d[OFF + 9]), "=f"(d[OFF + 10]), "=f"(d[OFF + 11]),
        "=f"(d[OFF + 12]), "=f"(d[OFF + 13]), "=f"(d[OFF + 14]), "=f"(d[OFF + 15]), "=f"(d[OFF + 16]), "=f"(d[OFF + 17]),
        "=f"(d[OFF + 18]), "=f"(d[OFF + 19]), "=f"(d[OFF + 20]), "=f"(d[OFF + 21]), "=f"(d[OFF + 22]), "=f"(d[OFF + 23]),
        "=f"(d[OFF + 24]), "=f"(d[OFF + 25]), "=f"(d[OFF + 26]), "=f"(d[OFF + 27]), "=f"(d[OFF + 28]), "=f"(d[OFF + 29]),
        "=f"(d[OFF + 30]), "=f"(d[OFF + 31]), "=f"(d[OFF + 32]), "=f"(d[OFF + 33]), "=f"(d[OFF + 34]), "=f"(d[OFF + 35]),
        "=f"(d[OFF + 36]), "=f"(d[OFF + 37]), "=f"(d[OFF + 38]), "=f"(d[OFF + 39]), "=f"(d[OFF + 40]), "=f"(d[OFF + 41]),
        "=f"(d[OFF + 42]), "=f"(d[OFF + 43]), "=f"(d[OFF + 44]), "=f"(d[OFF + 45]), "=f"(d[OFF + 46]), "=f"(d[OFF + 47]),
        "=f"(d[OFF + 48]), "=f"(d[OFF + 49]), "=f"(d[OFF + 50]), "=f"(d[OFF + 51]), "=f"(d[OFF + 52]), "=f"(d[OFF + 53]),
        "=f"(d[OFF + 54]), "=f"(d[OFF + 55]), "=f"(d[OFF + 56]), "=f"(d[OFF + 57]), "=f"(d[OFF + 58]), "=f"(d[OFF + 59]),
        "=f"(d[OFF + 60]), "=f"(d[OFF + 61]), "=f"(d[OFF + 62]), "=f"(d[OFF + 63]), "=f"(d[OFF + 64]), "=f"(d[OFF + 65]),
        "=f"(d[OFF + 66]), "=f"(d[OFF + 67]), "=f"(d[OFF + 68]), "=f"(d[OFF + 69]), "=f"(d[OFF + 70]), "=f"(d[OFF + 71]),
        "=f"(d[OFF + 72]), "=f"(d[OFF + 73]), "=f"(d[OFF + 74]), "=f"(d[OFF + 75]), "=f"(d[OFF + 76]), "=f"(d[OFF + 77]),
        "=f"(d[OFF + 78]), "=f"(d[OFF + 79]), "=f"(d[OFF + 80]), "=f"(d[OFF + 81]), "=f"(d[OFF + 82]), "=f"(d[OFF + 83]),
        "=f"(d[OFF + 84]), "=f"(d[OFF + 85]), "=f"(d[OFF + 86]), "=f"(d[OFF + 87]), "=f"(d[OFF + 88]), "=f"(d[OFF + 89]),
        "=f"(d[OFF + 90]), "=f"(d[OFF + 91]), "=f"(d[OFF + 92]), "=f"(d[OFF + 93]), "=f"(d[OFF + 94]), "=f"(d[OFF + 95])
      : "l"(desc_a), "l"(desc_b), "r"(scale_d));
}

template <int OFF, int NN>
__device__ __forceinline__ void wg_m64t(float (&d)[NN], uint64_t desc_a, uint64_t desc_b, int scale_d) {
  asm volatile(
      "{\n.reg .pred p;\nsetp.ne.b32 p, %34, 0;\n"
      "wgmma.mma_async.sync.aligned.m64n64k16.f32.bf16.bf16 "
      "{%0,%1,%2,%3,%4,%5,%6,%7,%8,%9,%10,%11,%12,%13,%14,%15,"
      "%16,%17,%18,%19,%20,%21,%22,%23,%24,%25,%26,%27,%28,%29,%30,%31}, "
      "%32, %33, p, 1, 1, 0, 1;\n}\n"
      : "+f"(d[OFF + 0]), "+f"(d[OFF + 1]), "+f"(d[OFF + 2]), "+f"(d[OFF + 3]), "+f"(d[OFF + 4]), "+f"(d[OFF + 5]),
        "+f"(d[OFF + 6]), "+f"(d[OFF + 7]), "+f"(d[OFF + 8]), "+f"(d[OFF + 9]), "+f"(d[OFF + 10]), "+f"(d[OFF + 11]),
        "+f"(d[OFF + 12]), "+f"(d[OFF + 13]), "+f"(d[OFF + 14]), "+f"(d[OFF + 15]), "+f"(d[OFF + 16]), "+f"(d[OFF + 17]),
        "+f"(d[OFF + 18]), "+f"(d[OFF + 19]), "+f"(d[OFF + 20]), "+f"(d[OFF + 21]), "+f"(d[OFF + 22]), "+f"(d[OFF + 23]),
        "+f"(d[OFF + 24]), "+f"(d[OFF + 25]), "+f"(d[OFF + 26]), "+f"(d[OFF + 27]), "+f"(d[OFF + 28]), "+f"(d[OFF + 29]),
        "+f"(d[OFF + 30]), "+f"(d[OFF + 31])
      : "l"(desc_a), "l"(desc_b), "r"(scale_d));
}

template <int OFF, int NN>
__device__ __forceinline__ void wg_m64tz(float (&d)[NN], uint64_t desc_a, uint64_t desc_b, int scale_d) {
  asm volatile(
      "{\n.reg .pred p;\nsetp.ne.b32 p, %34, 0;\n"
      "wgmma.mma_async.sync.aligned.m64n64k16.f32.bf16.bf16 "
      "{%0,%1,%2,%3,%4,%5,%6,%7,%8,%9,%10,%11,%12,%13,%14,%15,"
      "%16,%17,%18,%19,%20,%21,%22,%23,%24,%25,%26,%27,%28,%29,%30,%31}, "
      "%32, %33, p, 1, 1, 0, 1;\n}\n"
      : "=f"(d[OFF + 0]), "=f"(d[OFF + 1]), "=f"(d[OFF + 2]), "=f"(d[OFF + 3]), "=f"(d[OFF + 4]), "=f"(d[OFF + 5]),
        "=f"(d[OFF + 6]), "=f"(d[OFF + 7]), "=f"(d[OFF + 8]), "=f"(d[OFF + 9]), "=f"(d[OFF + 10]), "=f"(d[OFF + 11]),
        "=f"(d[OFF + 12]), "=f"(d[OFF + 13]), "=f"(d[OFF + 14]), "=f"(d[OFF + 15]), "=f"(d[OFF + 16]), "=f"(d[OFF + 17]),
        "=f"(d[OFF + 18]), "=f"(d[OFF + 19]), "=f"(d[OFF + 20]), "=f"(d[OFF + 21]), "=f"(d[OFF + 22]), "=f"(d[OFF + 23]),
        "=f"(d[OFF + 24]), "=f"(d[OFF + 25]), "=f"(d[OFF + 26]), "=f"(d[OFF + 27]), "=f"(d[OFF + 28]), "=f"(d[OFF + 29]),
        "=f"(d[OFF + 30]), "=f"(d[OFF + 31])
      : "l"(desc_a), "l"(desc_b), "r"(scale_d));
}

template <int OFF, int NN>
__device__ __forceinline__ void wg_d96(float (&d)[NN], uint32_t a0, uint32_t a1, uint32_t a2, uint32_t a3,
                                       uint64_t desc_b, int scale_d) {
  asm volatile(
      "{\n.reg .pred p;\nsetp.ne.b32 p, %53, 0;\n"
      "wgmma.mma_async.sync.aligned.m64n96k16.f32.bf16.bf16 "
      "{%0,%1,%2,%3,%4,%5,%6,%7,%8,%9,%10,%11,%12,%13,%14,%15,"
      "%16,%17,%18,%19,%20,%21,%22,%23,%24,%25,%26,%27,%28,%29,%30,%31,"
      "%32,%33,%34,%35,%36,%37,%38,%39,%40,%41,%42,%43,%44,%45,%46,%47}, "
      "{%48,%49,%50,%51}, %52, p, 1, 1, 0;\n}\n"
      : "+f"(d[OFF + 0]), "+f"(d[OFF + 1]), "+f"(d[OFF + 2]), "+f"(d[OFF + 3]), "+f"(d[OFF + 4]), "+f"(d[OFF + 5]),
        "+f"(d[OFF + 6]), "+f"(d[OFF + 7]), "+f"(d[OFF + 8]), "+f"(d[OFF + 9]), "+f"(d[OFF + 10]), "+f"(d[OFF + 11]),
        "+f"(d[OFF + 12]), "+f"(d[OFF + 13]), "+f"(d[OFF + 14]), "+f"(d[OFF + 15]), "+f"(d[OFF + 16]), "+f"(d[OFF + 17]),
        "+f"(d[OFF + 18]), "+f"(d[OFF + 19]), "+f"(d[OFF + 20]), "+f"(d[OFF + 21]), "+f"(d[OFF + 22]), "+f"(d[OFF + 23]),
        "+f"(d[OFF + 24]), "+f"(d[OFF + 25]), "+f"(d[OFF + 26]), "+f"(d[OFF + 27]), "+f"(d[OFF + 28]), "+f"(d[OFF + 29]),
        "+f"(d[OFF + 30]), "+f"(d[OFF + 31]), "+f"(d[OFF + 32]), "+f"(d[OFF + 33]), "+f"(d[OFF + 34]), "+f"(d[OFF + 35]),
        "+f"(d[OFF + 36]), "+f"(d[OFF + 37]), "+f"(d[OFF + 38]), "+f"(d[OFF + 39]), "+f"(d[OFF + 40]), "+f"(d[OFF + 41]),
        "+f"(d[OFF + 42]), "+f"(d[OFF + 43]), "+f"(d[OFF + 44]), "+f"(d[OFF + 45]), "+f"(d[OFF + 46]), "+f"(d[OFF + 47])
      : "r"(a0), "r"(a1), "r"(a2), "r"(a3), "l"(desc_b), "r"(scale_d));
}

template <int OFF, int NN>
__device__ __forceinline__ void wg_d96z(float (&d)[NN], uint32_t a0, uint32_t a1, uint32_t a2, uint32_t a3,
                                       uint64_t desc_b, int scale_d) {
  asm volatile(
      "{\n.reg .pred p;\nsetp.ne.b32 p, %53, 0;\n"
      "wgmma.mma_async.sync.aligned.m64n96k16.f32.bf16.bf16 "
      "{%0,%1,%2,%3,%4,%5,%6,%7,%8,%9,%10,%11,%12,%13,%14,%15,"
      "%16,%17,%18,%19,%20,%21,%22,%23,%24,%25,%26,%27,%28,%29,%30,%31,"
      "%32,%33,%34,%35,%36,%37,%38,%39,%40,%41,%42,%43,%44,%45,%46,%47}, "
      "{%48,%49,%50,%51}, %52, p, 1, 1, 0;\n}\n"
      : "=f"(d[OFF + 0]), "=f"(d[OFF + 1]), "=f"(d[OFF + 2]), "=f"(d[OFF + 3]), "=f"(d[OFF + 4]), "=f"(d[OFF + 5]),
        "=f"(d[OFF + 6]), "=f"(d[OFF + 7]), "=f"(d[OFF + 8]), "=f"(d[OFF + 9]), "=f"(d[OFF + 10]), "=f"(d[OFF + 11]),
        "=f"(d[OFF + 12]), "=f"(d[OFF + 13]), "=f"(d[OFF + 14]), "=f"(d[OFF + 15]), "=f"(d[OFF + 16]), "=f"(d[OFF + 17]),
        "=f"(d[OFF + 18]), "=f"(d[OFF + 19]), "=f"(d[OFF + 20]), "=f"(d[OFF + 21]), "=f"(d[OFF + 22]), "=f"(d[OFF + 23]),
        "=f"(d[OFF + 24]), "=f"(d[OFF + 25]), "=f"(d[OFF + 26]), "=f"(d[OFF + 27]), "=f"(d[OFF + 28]), "=f"(d[OFF + 29]),
        "=f"(d[OFF + 30]), "=f"(d[OFF + 31]), "=f"(d[OFF + 32]), "=f"(d[OFF + 33]), "=f"(d[OFF + 34]), "=f"(d[OFF + 35]),
        "=f"(d[OFF + 36]), "=f"(d[OFF + 37]), "=f"(d[OFF + 38]), "=f"(d[OFF + 39]), "=f"(d[OFF + 40]), "=f"(d[OFF + 41]),
        "=f"(d[OFF + 42]), "=f"(d[OFF + 43]), "=f"(d[OFF + 44]), "=f"(d[OFF + 45]), "=f"(d[OFF + 46]), "=f"(d[OFF + 47])
      : "r"(a0), "r"(a1), "r"(a2), "r"(a3), "l"(desc_b), "r"(scale_d));
}

template <int OFF, int NN>
__device__ __forceinline__ void wg_s104(float (&d)[NN], uint32_t a0, uint32_t a1, uint32_t a2, uint32_t a3,
                                       uint64_t desc_b, int scale_d, uint32_t meta) {
  asm volatile(
      "{\n.reg .pred p;\nsetp.ne.b32 p, %57, 0;\n"
      "wgmma.mma_async.sp.sync.aligned.m64n104k32.f32.bf16.bf16 "
      "{%0,%1,%2,%3,%4,%5,%6,%7,%8,%9,%10,%11,%12,%13,%14,%15,"
      "%16,%17,%18,%19,%20,%21,%22,%23,%24,%25,%26,%27,%28,%29,%30,%31,"
      "%32,%33,%34,%35,%36,%37,%38,%39,%40,%41,%42,%43,%44,%45,%46,%47,"
      "%48,%49,%50,%51}, "
      "{%52,%53,%54,%55}, %56, %58, 0, p, 1, 1, 0;\n}\n"
      : "+f"(d[OFF + 0]), "+f"(d[OFF + 1]), "+f"(d[OFF + 2]), "+f"(d[OFF + 3]), "+f"(d[OFF + 4]), "+f"(d[OFF + 5]),
        "+f"(d[OFF + 6]), "+f"(d[OFF + 7]), "+f"(d[OFF + 8]), "+f"(d[OFF + 9]), "+f"(d[OFF + 10]), "+f"(d[OFF + 11]),
        "+f"(d[OFF + 12]), "+f"(d[OFF + 13]), "+f"(d[OFF + 14]), "+f"(d[OFF + 15]), "+f"(d[OFF + 16]), "+f"(d[OFF + 17]),
        "+f"(d[OFF + 18]), "+f"(d[OFF + 19]), "+f"(d[OFF + 20]), "+f"(d[OFF + 21]), "+f"(d[OFF + 22]), "+f"(d[OFF + 23]),
        "+f"(d[OFF + 24]), "+f"(d[OFF + 25]), "+f"(d[OFF + 26]), "+f"(d[OFF + 27]), "+f"(d[OFF + 28]), "+f"(d[OFF + 29]),
        "+f"(d[OFF + 30]), "+f"(d[OFF + 31]), "+f"(d[OFF + 32]), "+f"(d[OFF + 33]), "+f"(d[OFF + 34]), "+f"(d[OFF + 35]),
        "+f"(d[OFF + 36]), "+f"(d[OFF + 37]), "+f"(d[OFF + 38]), "+f"(d[OFF + 39]), "+f"(d[OFF + 40]), "+f"(d[OFF + 41]),
        "+f"(d[OFF + 42]), "+f"(d[OFF + 43]), "+f"(d[OFF + 44]), "+f"(d[OFF + 45]), "+f"(d[OFF + 46]), "+f"(d[OFF + 47]),
        "+f"(d[OFF + 48]), "+f"(d[OFF + 49]), "+f"(d[OFF + 50]), "+f"(d[OFF + 51])
      : "r"(a0), "r"(a1), "r"(a2), "r"(a3), "l"(desc_b), "r"(scale_d), "r"(meta));
}

template <int OFF, int NN>
__device__ __forceinline__ void wg_s104z(float (&d)[NN], uint32_t a0, uint32_t a1, uint32_t a2, uint32_t a3,
                                       uint64_t desc_b, int scale_d, uint32_t meta) {
  asm volatile(
      "{\n.reg .pred p;\nsetp.ne.b32 p, %57, 0;\n"
      "wgmma.mma_async.sp.sync.aligned.m64n104k32.f32.bf16.bf16 "
      "{%0,%1,%2,%3,%4,%5,%6,%7,%8,%9,%10,%11,%12,%13,%14,%15,"
      "%16,%17,%18,%19,%20,%21,%22,%23,%24,%25,%26,%27,%28,%29,%30,%31,"
      "%32,%33,%34,%35,%36,%37,%38,%39,%40,%41,%42,%43,%44,%45,%46,%47,"
      "%48,%49,%50,%51}, "
      "{%52,%53,%54,%55}, %56, %58, 0, p, 1, 1, 0;\n}\n"
      : "=f"(d[OFF + 0]), "=f"(d[OFF + 1]), "=f"(d[OFF + 2]), "=f"(d[OFF + 3]), "=f"(d[OFF + 4]), "=f"(d[OFF + 5]),
        "=f"(d[OFF + 6]), "=f"(d[OFF + 7]), "=f"(d[OFF + 8]), "=f"(d[OFF + 9]), "=f"(d[OFF + 10]), "=f"(d[OFF + 11]),
        "=f"(d[OFF + 12]), "=f"(d[OFF + 13]), "=f"(d[OFF + 14]), "=f"(d[OFF + 15]), "=f"(d[OFF + 16]), "=f"(d[OFF + 17]),
        "=f"(d[OFF + 18]), "=f"(d[OFF + 19]), "=f"(d[OFF + 20]), "=f"(d[OFF + 21]), "=f"(d[OFF + 22]), "=f"(d[OFF + 23]),
        "=f"(d[OFF + 24]), "=f"(d[OFF + 25]), "=f"(d[OFF + 26]), "=f"(d[OFF + 27]), "=f"(d[OFF + 28]), "=f"(d[OFF + 29]),
        "=f"(d[OFF + 30]), "=f"(d[OFF + 31]), "=f"(d[OFF + 32]), "=f"(d[OFF + 33]), "=f"(d[OFF + 34]), "=f"(d[OFF + 35]),
        "=f"(d[OFF + 36]), "=f"(d[OFF + 37]), "=f"(d[OFF + 38]), "=f"(d[OFF + 39]), "=f"(d[OFF + 40]), "=f"(d[OFF + 41]),
        "=f"(d[OFF + 42]), "=f"(d[OFF + 43]), "=f"(d[OFF + 44]), "=f"(d[OFF + 45]), "=f"(d[OFF + 46]), "=f"(d[OFF + 47]),
        "=f"(d[OFF + 48]), "=f"(d[OFF + 49]), "=f"(d[OFF + 50]), "=f"(d[OFF + 51])
      : "r"(a0), "r"(a1), "r"(a2), "r"(a3), "l"(desc_b), "r"(scale_d), "r"(meta));
}

template <int OFF, int NN>
__device__ __forceinline__ void wg_s48(float (&d)[NN], uint32_t a0, uint32_t a1, uint32_t a2, uint32_t a3,
                                       uint64_t desc_b, int scale_d, uint32_t meta) {
  asm volatile(
      "{\n.reg .pred p;\nsetp.ne.b32 p, %29, 0;\n"
      "wgmma.mma_async.sp.sync.aligned.m64n48k32.f32.bf16.bf16 "
      "{%0,%1,%2,%3,%4,%5,%6,%7,%8,%9,%10,%11,%12,%13,%14,%15,"
      "%16,%17,%18,%19,%20,%21,%22,%23}, "
      "{%24,%25,%26,%27}, %28, %30, 0, p, 1, 1, 0;\n}\n"
      : "+f"(d[OFF + 0]), "+f"(d[OFF + 1]), "+f"(d[OFF + 2]), "+f"(d[OFF + 3]), "+f"(d[OFF + 4]), "+f"(d[OFF + 5]),
        "+f"(d[OFF + 6]), "+f"(d[OFF + 7]), "+f"(d[OFF + 8]), "+f"(d[OFF + 9]), "+f"(d[OFF + 10]), "+f"(d[OFF + 11]),
        "+f"(d[OFF + 12]), "+f"(d[OFF + 13]), "+f"(d[OFF + 14]), "+f"(d[OFF + 15]), "+f"(d[OFF + 16]), "+f"(d[OFF + 17]),
        "+f"(d[OFF + 18]), "+f"(d[OFF + 19]), "+f"(d[OFF + 20]), "+f"(d[OFF + 21]), "+f"(d[OFF + 22]), "+f"(d[OFF + 23])
      : "r"(a0), "r"(a1), "r"(a2), "r"(a3), "l"(desc_b), "r"(scale_d), "r"(meta));
}

template <int OFF, int NN>
__device__ __forceinline__ void wg_s48z(float (&d)[NN], uint32_t a0, uint32_t a1, uint32_t a2, uint32_t a3,
                                       uint64_t desc_b, int scale_d, uint32_t meta) {
  asm volatile(
      "{\n.reg .pred p;\nsetp.ne.b32 p, %29, 0;\n"
      "wgmma.mma_async.sp.sync.aligned.m64n48k32.f32.bf16.bf16 "
      "{%0,%1,%2,%3,%4,%5,%6,%7,%8,%9,%10,%11,%12,%13,%14,%15,"
      "%16,%17,%18,%19,%20,%21,%22,%23}, "
      "{%24,%25,%26,%27}, %28, %30, 0, p, 1, 1, 0;\n}\n"
      : "=f"(d[OFF + 0]), "=f"(d[OFF + 1]), "=f"(d[OFF + 2]), "=f"(d[OFF + 3]), "=f"(d[OFF + 4]), "=f"(d[OFF + 5]),
        "=f"(d[OFF + 6]), "=f"(d[OFF + 7]), "=f"(d[OFF + 8]), "=f"(d[OFF + 9]), "=f"(d[OFF + 10]), "=f"(d[OFF + 11]),
        "=f"(d[OFF + 12]), "=f"(d[OFF + 13]), "=f"(d[OFF + 14]), "=f"(d[OFF + 15]), "=f"(d[OFF + 16]), "=f"(d[OFF + 17]),
        "=f"(d[OFF + 18]), "=f"(d[OFF + 19]), "=f"(d[OFF + 20]), "=f"(d[OFF + 21]), "=f"(d[OFF + 22]), "=f"(d[OFF + 23])
      : "r"(a0), "r"(a1), "r"(a2), "r"(a3), "l"(desc_b), "r"(scale_d), "r"(meta));
}

template <int OFF, int NN>
__device__ __forceinline__ void wg_s56(float (&d)[NN], uint32_t a0, uint32_t a1, uint32_t a2, uint32_t a3,
                                       uint64_t desc_b, int scale_d, uint32_t meta) {
  asm volatile(
      "{\n.reg .pred p;\nsetp.ne.b32 p, %33, 0;\n"
      "wgmma.mma_async.sp.sync.aligned.m64n56k32.f32.bf16.bf16 "
      "{%0,%1,%2,%3,%4,%5,%6,%7,%8,%9,%10,%11,%12,%13,%14,%15,"
      "%16,%17,%18,%19,%20,%21,%22,%23,%24,%25,%26,%27}, "
      "{%28,%29,%30,%31}, %32, %34, 0, p, 1, 1, 0;\n}\n"
      : "+f"(d[OFF + 0]), "+f"(d[OFF + 1]), "+f"(d[OFF + 2]), "+f"(d[OFF + 3]), "+f"(d[OFF + 4]), "+f"(d[OFF + 5]),
        "+f"(d[OFF + 6]), "+f"(d[OFF + 7]), "+f"(d[OFF + 8]), "+f"(d[OFF + 9]), "+f"(d[OFF + 10]), "+f"(d[OFF + 11]),
        "+f"(d[OFF + 12]), "+f"(d[OFF + 13]), "+f"(d[OFF + 14]), "+f"(d[OFF + 15]), "+f"(d[OFF + 16]), "+f"(d[OFF + 17]),
        "+f"(d[OFF + 18]), "+f"(d[OFF + 19]), "+f"(d[OFF + 20]), "+f"(d[OFF + 21]), "+f"(d[OFF + 22]), "+f"(d[OFF + 23]),
        "+f"(d[OFF + 24]), "+f"(d[OFF + 25]), "+f"(d[OFF + 26]), "+f"(d[OFF + 27])
      : "r"(a0), "r"(a1), "r"(a2), "r"(a3), "l"(desc_b), "r"(scale_d), "r"(meta));
}

template <int OFF, int NN>
__device__ __forceinline__ void wg_s56z(float (&d)[NN], uint32_t a0, uint32_t a1, uint32_t a2, uint32_t a3,
                                       uint64_t desc_b, int scale_d, uint32_t meta) {
  asm volatile(
      "{\n.reg .pred p;\nsetp.ne.b32 p, %33, 0;\n"
      "wgmma.mma_async.sp.sync.aligned.m64n56k32.f32.bf16.bf16 "
      "{%0,%1,%2,%3,%4,%5,%6,%7,%8,%9,%10,%11,%12,%13,%14,%15,"
      "%16,%17,%18,%19,%20,%21,%22,%23,%24,%25,%26,%27}, "
      "{%28,%29,%30,%31}, %32, %34, 0, p, 1, 1, 0;\n}\n"
      : "=f"(d[OFF + 0]), "=f"(d[OFF + 1]), "=f"(d[OFF + 2]), "=f"(d[OFF + 3]), "=f"(d[OFF + 4]), "=f"(d[OFF + 5]),
        "=f"(d[OFF + 6]), "=f"(d[OFF + 7]), "=f"(d[OFF + 8]), "=f"(d[OFF + 9]), "=f"(d[OFF + 10]), "=f"(d[OFF + 11]),
        "=f"(d[OFF + 12]), "=f"(d[OFF + 13]), "=f"(d[OFF + 14]), "=f"(d[OFF + 15]), "=f"(d[OFF + 16]), "=f"(d[OFF + 17]),
        "=f"(d[OFF + 18]), "=f"(d[OFF + 19]), "=f"(d[OFF + 20]), "=f"(d[OFF + 21]), "=f"(d[OFF + 22]), "=f"(d[OFF + 23]),
        "=f"(d[OFF + 24]), "=f"(d[OFF + 25]), "=f"(d[OFF + 26]), "=f"(d[OFF + 27])
      : "r"(a0), "r"(a1), "r"(a2), "r"(a3), "l"(desc_b), "r"(scale_d), "r"(meta));
}

template <int OFF, int NN>
__device__ __forceinline__ void wg_s64t(float (&d)[NN], uint32_t a0, uint32_t a1, uint32_t a2, uint32_t a3,
                                       uint64_t desc_b, int scale_d, uint32_t meta) {
  asm volatile(
      "{\n.reg .pred p;\nsetp.ne.b32 p, %37, 0;\n"
      "wgmma.mma_async.sp.sync.aligned.m64n64k32.f32.bf16.bf16 "
      "{%0,%1,%2,%3,%4,%5,%6,%7,%8,%9,%10,%11,%12,%13,%14,%15,"
      "%16,%17,%18,%19,%20,%21,%22,%23,%24,%25,%26,%27,%28,%29,%30,%31}, "
      "{%32,%33,%34,%35}, %36, %38, 0, p, 1, 1, 1;\n}\n"
      : "+f"(d[OFF + 0]), "+f"(d[OFF + 1]), "+f"(d[OFF + 2]), "+f"(d[OFF + 3]), "+f"(d[OFF + 4]), "+f"(d[OFF + 5]),
        "+f"(d[OFF + 6]), "+f"(d[OFF + 7]), "+f"(d[OFF + 8]), "+f"(d[OFF + 9]), "+f"(d[OFF + 10]), "+f"(d[OFF + 11]),
        "+f"(d[OFF + 12]), "+f"(d[OFF + 13]), "+f"(d[OFF + 14]), "+f"(d[OFF + 15]), "+f"(d[OFF + 16]), "+f"(d[OFF + 17]),
        "+f"(d[OFF + 18]), "+f"(d[OFF + 19]), "+f"(d[OFF + 20]), "+f"(d[OFF + 21]), "+f"(d[OFF + 22]), "+f"(d[OFF + 23]),
        "+f"(d[OFF + 24]), "+f"(d[OFF + 25]), "+f"(d[OFF + 26]), "+f"(d[OFF + 27]), "+f"(d[OFF + 28]), "+f"(d[OFF + 29]),
        "+f"(d[OFF + 30]), "+f"(d[OFF + 31])
      : "r"(a0), "r"(a1), "r"(a2), "r"(a3), "l"(desc_b), "r"(scale_d), "r"(meta));
}

template <int OFF, int NN>
__device__ __forceinline__ void wg_s64t1(float (&d)[NN], uint32_t a0, uint32_t a1, uint32_t a2, uint32_t a3,
                                       uint64_t desc_b, int scale_d, uint32_t meta) {
  asm volatile(
      "{\n.reg .pred p;\nsetp.ne.b32 p, %37, 0;\n"
      "wgmma.mma_async.sp.sync.aligned.m64n64k32.f32.bf16.bf16 "
      "{%0,%1,%2,%3,%4,%5,%6,%7,%8,%9,%10,%11,%12,%13,%14,%15,"
      "%16,%17,%18,%19,%20,%21,%22,%23,%24,%25,%26,%27,%28,%29,%30,%31}, "
      "{%32,%33,%34,%35}, %36, %38, 1, p, 1, 1, 1;\n}\n"
      : "+f"(d[OFF + 0]), "+f"(d[OFF + 1]), "+f"(d[OFF + 2]), "+f"(d[OFF + 3]), "+f"(d[OFF + 4]), "+f"(d[OFF + 5]),
        "+f"(d[OFF + 6]), "+f"(d[OFF + 7]), "+f"(d[OFF + 8]), "+f"(d[OFF + 9]), "+f"(d[OFF + 10]), "+f"(d[OFF + 11]),
        "+f"(d[OFF + 12]), "+f"(d[OFF + 13]), "+f"(d[OFF + 14]), "+f"(d[OFF + 15]), "+f"(d[OFF + 16]), "+f"(d[OFF + 17]),
        "+f"(d[OFF + 18]), "+f"(d[OFF + 19]), "+f"(d[OFF + 20]), "+f"(d[OFF + 21]), "+f"(d[OFF + 22]), "+f"(d[OFF + 23]),
        "+f"(d[OFF + 24]), "+f"(d[OFF + 25]), "+f"(d[OFF + 26]), "+f"(d[OFF + 27]), "+f"(d[OFF + 28]), "+f"(d[OFF + 29]),
        "+f"(d[OFF + 30]), "+f"(d[OFF + 31])
      : "r"(a0), "r"(a1), "r"(a2), "r"(a3), "l"(desc_b), "r"(scale_d), "r"(meta));
}

template <int OFF, int NN>
__device__ __forceinline__ void wg_s64tz(float (&d)[NN], uint32_t a0, uint32_t a1, uint32_t a2, uint32_t a3,
                                       uint64_t desc_b, int scale_d, uint32_t meta) {
  asm volatile(
      "{\n.reg .pred p;\nsetp.ne.b32 p, %37, 0;\n"
      "wgmma.mma_async.sp.sync.aligned.m64n64k32.f32.bf16.bf16 "
      "{%0,%1,%2,%3,%4,%5,%6,%7,%8,%9,%10,%11,%12,%13,%14,%15,"
      "%16,%17,%18,%19,%20,%21,%22,%23,%24,%25,%26,%27,%28,%29,%30,%31}, "
      "{%32,%33,%34,%35}, %36, %38, 0, p, 1, 1, 1;\n}\n"
      : "=f"(d[OFF + 0]), "=f"(d[OFF + 1]), "=f"(d[OFF + 2]), "=f"(d[OFF + 3]), "=f"(d[OFF + 4]), "=f"(d[OFF + 5]),
        "=f"(d[OFF + 6]), "=f"(d[OFF + 7]), "=f"(d[OFF + 8]), "=f"(d[OFF + 9]), "=f"(d[OFF + 10]), "=f"(d[OFF + 11]),
        "=f"(d[OFF + 12]), "=f"(d[OFF + 13]), "=f"(d[OFF + 14]), "=f"(d[OFF + 15]), "=f"(d[OFF + 16]), "=f"(d[OFF + 17]),
        "=f"(d[OFF + 18]), "=f"(d[OFF + 19]), "=f"(d[OFF + 20]), "=f"(d[OFF + 21]), "=f"(d[OFF + 22]), "=f"(d[OFF + 23]),
        "=f"(d[OFF + 24]), "=f"(d[OFF + 25]), "=f"(d[OFF + 26]), "=f"(d[OFF + 27]), "=f"(d[OFF + 28]), "=f"(d[OFF + 29]),
        "=f"(d[OFF + 30]), "=f"(d[OFF + 31])
      : "r"(a0), "r"(a1), "r"(a2), "r"(a3), "l"(desc_b), "r"(scale_d), "r"(meta));
}

__device__ __forceinline__ int g2_inv(int ch) { return 32 * (ch >> 5) + 8 * ((ch >> 1) & 3) + 2 * ((ch >> 3) & 3) + (ch & 1); }
__host__ __device__ __forceinline__ uint32_t wimg_off(int n, int k) {
  return (uint32_t)(k >> 6) * kWChunk + (uint32_t)n * 128 + (uint32_t)((((k & 63) >> 3) ^ (n & 7)) << 4) + (k & 7) * 2;
}
__host__ __device__ constexpr int w2piece(int h, int c) { return c == 2 ? 2 + h : 4 * h + c; }
__device__ __forceinline__ uint32_t w2img_off(int n, int k) { return wimg_off(n % 96, k & 63) + w2piece(n >= 96, k >> 6) * (kWChunk / 2); }
__device__ __forceinline__ int qpix(int par, int t) {
  const int a = 2 * t + 13 * par - 6, b = t + 112 * par;
  return par ? min(a, b) : max(a, b);
}
__device__ __forceinline__ int woff(int par, int i, int r) {
  const int a = 99 * par + 6 - 8 * i;
  return par ? min(r, a) : max(r, a);
}

__device__ __forceinline__ void mma16816(float (&c)[4], uint32_t a0, uint32_t a1, uint32_t a2, uint32_t a3, uint32_t b0,
                                         uint32_t b1) {
  asm volatile(
      "mma.sync.aligned.m16n8k16.row.col.f32.bf16.bf16.f32 {%0,%1,%2,%3}, {%4,%5,%6,%7}, {%8,%9}, {%0,%1,%2,%3};"
      : "+f"(c[0]), "+f"(c[1]), "+f"(c[2]), "+f"(c[3])
      : "r"(a0), "r"(a1), "r"(a2), "r"(a3), "r"(b0), "r"(b1));
}

__device__ __forceinline__ void fold_w1(const int u, const __nv_bfloat16* __restrict__ wqkv, uint8_t* wimg) {
  const int g = (threadIdx.x >> 2) & 7, l = threadIdx.x & 3;
  const int m0 = (u / 12) * 16, s = u % 12;
  uint4 A[12], B[12];
  const __nv_bfloat16* arow = wqkv + (m0 + 4 * (g >> 1) + (g & 1)) * 576 + 192 + 8 * l;
  const __nv_bfloat16* brow = wqkv + (16 * s + 4 * (g >> 1) + (g & 1)) * 576 + 8 * l;
#pragma unroll
  for (int i = 0; i < 12; i++) {
    A[i] = ldg128_nc(arow + (i & 1) * 2 * 576 + 32 * (i >> 1));
    B[i] = ldg128_nc(brow + (i & 1) * 2 * 576 + 32 * (i >> 1));
  }
  sched_fence();
  uint8_t* dst = wimg + wimg_off(m0 + g, 16 * s + 4 * l);
  float acc[4][4];
#pragma unroll
  for (int j = 0; j < 16; j++) acc[j >> 2][j & 3] = 0.f;
#pragma unroll
  for (int i = 0; i < 6; i++) {
    const uint4 &a0 = A[2 * i], &a1 = A[2 * i + 1];
#pragma unroll
    for (int nb = 0; nb < 2; nb++) {
      mma16816(acc[2 * nb], a0.x, a1.x, a0.y, a1.y, B[2 * i + nb].x, B[2 * i + nb].y);
      mma16816(acc[2 * nb + 1], a0.z, a1.z, a0.w, a1.w, B[2 * i + nb].z, B[2 * i + nb].w);
    }
  }
#pragma unroll
  for (int j = 0; j < 2; j++) {
    const uint2 v = make_uint2(pack_bf16((acc[0][2 * j] + acc[1][2 * j]) * kAlpha, (acc[0][2 * j + 1] + acc[1][2 * j + 1]) * kAlpha),
                               pack_bf16((acc[2][2 * j] + acc[3][2 * j]) * kAlpha, (acc[2][2 * j + 1] + acc[3][2 * j + 1]) * kAlpha));
    asm volatile("st.relaxed.gpu.global.v2.u32 [%0], {%1,%2};" ::"l"(dst + j * 1024), "r"(v.x), "r"(v.y) : "memory");
  }
}
__device__ __forceinline__ void fold_w2(const int u, const __nv_bfloat16* __restrict__ wqkv, const __nv_bfloat16* __restrict__ wo,
                                        uint8_t* wimg) {
  const int g = (threadIdx.x >> 2) & 7, l = threadIdx.x & 3;
  const int m0 = (u / 12) * 32, n0 = (u % 12) * 16;
  uint4 S[12];
  uint32_t L[96];
  const __nv_bfloat16* brow = wqkv + (n0 + 4 * (g >> 1) + (g & 1)) * 576 + 384 + 8 * l;
#pragma unroll
  for (int i = 0; i < 12; i++) S[i] = ldg128_nc(brow + (i & 1) * 2 * 576 + 32 * (i >> 1));
  const __nv_bfloat16* acol = wo + (8 * l) * 192 + m0 + 4 * g;
#pragma unroll
  for (int c = 0; c < 48; c++)
    asm volatile("ld.global.nc.v2.u32 {%0,%1}, [%2];" : "=r"(L[2 * c]), "=r"(L[2 * c + 1]) : "l"(acol + (32 * (c >> 3) + (c & 7)) * 192));
  const uint32_t off = w2_offset();
  sched_fence();
  uint8_t* img = wimg + off;
  float acc[4][4];
#pragma unroll
  for (int j = 0; j < 16; j++) acc[j >> 2][j & 3] = 0.f;
#pragma unroll
  for (int i = 0; i < 6; i++) {
#pragma unroll
    for (int h = 0; h < 2; h++) {
      const uint4 &s0 = S[2 * i], &s1 = S[2 * i + 1];
#pragma unroll
      for (int mt = 0; mt < 2; mt++) {
        const uint32_t* a = L + 16 * i + 8 * h + mt;
        const uint32_t a0 = __byte_perm(a[0], a[2], 0x5410), a1 = __byte_perm(a[0], a[2], 0x7632);
        const uint32_t a2 = __byte_perm(a[4], a[6], 0x5410), a3 = __byte_perm(a[4], a[6], 0x7632);
        mma16816(acc[2 * mt], a0, a1, a2, a3, h ? s0.z : s0.x, h ? s0.w : s0.y);
        mma16816(acc[2 * mt + 1], a0, a1, a2, a3, h ? s1.z : s1.x, h ? s1.w : s1.y);
      }
    }
  }
#pragma unroll
  for (int j = 0; j < 4; j++) {
    const float(&c0)[4] = acc[j & 2];
    const float(&c1)[4] = acc[(j & 2) + 1];
    asm volatile("st.relaxed.gpu.global.v2.u32 [%0], {%1,%2};" ::"l"(img + w2img_off(g2_inv(m0 + 4 * g + j), n0 + 4 * l)),
                 "r"(pack_bf16(c0[2 * (j & 1)], c0[2 * (j & 1) + 1])), "r"(pack_bf16(c1[2 * (j & 1)], c1[2 * (j & 1) + 1])) : "memory");
  }
}

__global__ void __launch_bounds__(256) fold_kernel(const __nv_bfloat16* __restrict__ wqkv,
                                                   const __nv_bfloat16* __restrict__ wo, uint8_t* wimg) {
  const int u = blockIdx.x * 8 + (threadIdx.x >> 5);
  if (u < 144) fold_w1(u, wqkv, wimg);
  else fold_w2(u - 144, wqkv, wo, wimg);
}

struct TileCoord { int pr, pc, I, J, up, kind; };
struct TileTable { uint16_t e[kCtas * 6], g[5][8][2], b[5][2][4]; };
inline void make_tiles(TileTable& tt) {
  for (int tile = 0; tile < kCtas * 6; tile++) {
    const int b = tile / 6, k = tile - 6 * b;
    const int p = b < 128 ? (tile - 672) >> 1 : b - 80;
    const int strip = b < 112 ? b >> 1 : b >= 128 && k >= 2 ? (b & 1) * 27 + (b & 2) * 14 : p + (p < 26 ? 1 : 3);
    const int pr = strip >= 28, J = (strip - pr * 28) >> 1, pc = strip & 1, up = b < 112 ? b & 1 : pr;
    const int first = b < 112 ? 8 - 2 * pr - up : 13 * pr, step = b < 112 ? k : k & 1;
    const int I = up ? first - step : first + step;
    const int kind = I == 13 * pr ? 3 + pr : J == 13 * pc ? 1 + pc : 0;
    tt.e[tile] = (uint16_t)(I | J << 4 | pr << 8 | pc << 9 | up << 10 | kind << 11);
  }
  for (int kind = 0; kind < 5; kind++) {
    const bool col = kind == 1 || kind == 2;
    auto off = [kind](int t) { return kind == 0 ? 2 * t : kind & 1 ? t + (t == 7) : t + (t > 0); };
    for (int j = 0; j < 8; j++) {
      const int w = j >> 1, h = j & 1;
      tt.g[kind][j][0] = (uint16_t)(col ? 3 * off(w + 4 * h) : 3 * (kW * off(2 * w) + 8 * h));
      tt.g[kind][j][1] = (uint16_t)(128 * (col ? 5 : 5 + off(2 * w + 1) - off(2 * w)));
    }
    for (int i = 0; i < 2; i++) {
      const int w = kind == 0 ? 0 : kind & 1 ? 3 * i : 1 - i;
      tt.b[kind][i][0] = tt.g[kind][2 * w][0];
      tt.b[kind][i][1] = (uint16_t)(128 * (kind == 0 ? 0 : (col ? 3 : 1) + i));
      tt.b[kind][i][2] = (uint16_t)(2048 * w);
      tt.b[kind][i][3] = 0;
    }
  }
}
__device__ __forceinline__ int num_tiles() { return blockIdx.x < 128 ? 6 : 4; }
__device__ __forceinline__ TileCoord decode_tile(const TileTable& tt, int tile) {
  const uint32_t e = tt.e[tile];
  return TileCoord{(int)(e >> 8) & 1, (int)(e >> 9) & 1, (int)e & 15, (int)(e >> 4) & 15, (int)(e >> 10) & 1, (int)(e >> 11)};
}
__device__ __forceinline__ int halo_r0(const TileCoord& t) { return 8 * t.I + 6 * t.pr - 6; }
__device__ __forceinline__ int halo_c0(const TileCoord& t) { return min(max(8 * t.J + 6 * t.pc - 6, -3), 102); }

__device__ __forceinline__ uint32_t bar_full(uint32_t bars, int wg, int c) { return bars + (wg * 3 + c) * 8; }
__device__ __forceinline__ uint32_t bar_w1c(uint32_t bars, int c) { return bars + (6 + c) * 8; }
__device__ __forceinline__ uint32_t bar_w2(uint32_t bars) { return bars + 9 * 8; }
__device__ __forceinline__ uint32_t bar_x(uint32_t bars, int j, int c) { return bars + (j == 0 ? 10 : c ? 17 + c : 11) * 8; }
__device__ __forceinline__ uint32_t bar_w1q(uint32_t bars) { return bars + 12 * 8; }
__device__ __forceinline__ uint32_t bar_xf(uint32_t bars) { return bars + 13 * 8; }
__device__ __forceinline__ uint32_t bar_w2m(uint32_t bars) { return bars + 14 * 8; }
__device__ __forceinline__ uint32_t bar_redo(uint32_t bars) { return bars + 15 * 8; }
__device__ __forceinline__ uint32_t bar_wok(uint32_t bars) { return bars + 16 * 8; }
__device__ __forceinline__ uint32_t bar_go(uint32_t bars) { return bars + 17 * 8; }
__device__ __forceinline__ uint32_t bar_raw(uint32_t bars, int j = 0) { return bars + (21 + j) * 8; }
__device__ __forceinline__ uint32_t bar_w2a(uint32_t bars) { return bars + 20 * 8; }
constexpr int kNumBars = 22;

__device__ __forceinline__ uint64_t wdesc(uint64_t d0, int s) { return d0 + (((s >> 2) * kWChunk + (s & 3) * 32) >> 4); }

__device__ __forceinline__ uint32_t x_chunk(int k, int c) { return kXOff + (k == 0 ? kWChunk : 0) + (k & 1 ? 2 - c : c) * 8192; }
__device__ __forceinline__ uint32_t out_slot(int k, int nt) { return k + 1 < nt ? kW2Off + (~k & 1) * 2 * kWChunk : kW1Off + kWChunk; }
template <int I0, int I1>
__device__ __forceinline__ void store_rows(bool on, __nv_bfloat16* pA, __nv_bfloat16* pB, const uint32_t (&a)[24], const uint32_t (&b)[24]) {
#pragma unroll
  for (int i = 2 * I0; i < 2 * I1; i++) {
    const uint32_t* v = (i & 1 ? b : a) + 4 * (i >> 1);
    asm volatile("{\n.reg .pred p;\nsetp.ne.u32 p, %5, 0;\n@p st.global.v4.u32 [%0], {%1,%2,%3,%4};\n}\n" ::"l"((i & 1 ? pB : pA) + 32 * (i >> 1)),
                 "r"(v[0]), "r"(v[1]), "r"(v[2]), "r"(v[3]), "r"((uint32_t)on) : "memory");
  }
}
template <int I0, int I1>
__device__ __forceinline__ void stage_out(const uint32_t (&ad)[4], const uint32_t (&a)[24], const uint32_t (&b)[24]) {
#pragma unroll
  for (int i = I0; i < I1; i++) {
    const uint32_t* v = (i < 6 ? a : b) + 4 * (i % 6);
    asm volatile("st.shared.v4.u32 [%0], {%1,%2,%3,%4};" ::"r"(ad[i % 6 / 3 * 2 + (i % 3 == 1)] + (i % 3 == 2) * 1024 + (i / 6) * 12288),
                 "r"(v[0]), "r"(v[1]), "r"(v[2]), "r"(v[3]) : "memory");
  }
}
__device__ __forceinline__ uint32_t now_ns() {
  uint32_t t;
  asm volatile("mov.u32 %0, %globaltimer_lo;" : "=r"(t)::"memory");
  return t;
}
__device__ __forceinline__ void wait_clock(uint32_t t_start, uint32_t t) {
  while (now_ns() - t_start < t) { }
}
#define NAT_PRED(f, m) ".reg .pred p;\n.reg .b32 t;\nand.b32 t, " f ", " m ";\nsetp.ne.u32 p, t, 0;\n"
constexpr uint32_t kHiV = 1, kHiU = 8, kColB = 0x20, kInV = 0x100, kInU = 0x1000, kColA = 0x10000;
template <uint32_t M>
__device__ __forceinline__ float pick(const float* a, const float* b, uint32_t f) {
  float d;
  asm("{\n" NAT_PRED("%5", "%6") "add.f32 %0, %1, %2;\n@p add.f32 %0, %3, %4;\n}\n"
      : "=&f"(d) : "f"(a[0]), "f"(a[2]), "f"(b[0]), "f"(b[2]), "r"(f), "n"(M));
  return d;
}
template <uint32_t M>
__device__ __forceinline__ float sel(float a, float b, uint32_t f) {
  float d;
  asm("{\n" NAT_PRED("%3", "%4") "selp.f32 %0, %1, %2, p;\n}\n" : "=f"(d) : "f"(a), "f"(b), "r"(f), "n"(M));
  return d;
}
template <uint32_t M>
__device__ __forceinline__ void max_if(float& m, float v, uint32_t f) {
  asm("{\n" NAT_PRED("%2", "%3") "@p max.f32 %0, %0, %1;\n}\n" : "+f"(m) : "f"(v), "r"(f), "n"(M));
}
template <uint32_t M>
__device__ __forceinline__ void add_if(float& m, float v, uint32_t f) {
  asm("{\n" NAT_PRED("%2", "%3") "@p add.f32 %0, %0, %1;\n}\n" : "+f"(m) : "f"(v), "r"(f), "n"(M));
}
__device__ __forceinline__ void pick_v(const float* a, float* v, uint32_t f) {
  v[0] = pick<kHiV>(a, a + 16, f), v[1] = pick<kHiV>(a + 1, a + 17, f);
  v[2] = pick<kHiV * 2>(a + 4, a + 20, f), v[3] = pick<kHiV * 2>(a + 5, a + 21, f);
  v[4] = pick<kHiV * 4>(a + 8, a + 24, f), v[5] = pick<kHiV * 4>(a + 9, a + 25, f);
  v[6] = a[12] + a[14], v[7] = a[13] + a[15];
}
__device__ __forceinline__ void pick_u(const float* a, float* v, uint32_t f) {
#pragma unroll
  for (int c = 0; c < 3; c++) v[2 * c] = pick<kHiU>(a + 4 * c, a + 4 * c + 12, f), v[2 * c + 1] = pick<kHiU * 2>(a + 4 * c + 1, a + 4 * c + 13, f);
}
__device__ __forceinline__ uint32_t sign_bytes(uint32_t v, uint32_t sel) {
  uint32_t d;
  asm("prmt.b32 %0, %1, %1, %2;" : "=r"(d) : "r"(v), "r"(sel));
  return d;
}
__device__ __forceinline__ float own_max(const float (&v)[14], uint32_t f) {
  float m = sel<kInV>(fmaxf(v[0], v[1]), -INFINITY, f), m2 = sel<kInV * 2>(fmaxf(v[2], v[3]), -INFINITY, f);
  max_if<kInV * 4>(m, fmaxf(v[4], v[5]), f);
  max_if<kInV * 8>(m2, fmaxf(v[6], v[7]), f);
  max_if<kInU>(m, fmaxf(fmaxf(v[8], v[10]), v[12]), f);
  max_if<kInU * 2>(m2, fmaxf(fmaxf(v[9], v[11]), v[13]), f);
  return fmaxf(m, m2);
}
__device__ __forceinline__ float quad_max(float m) {
  const float a = __shfl_xor_sync(0xffffffffu, m, 1), b = __shfl_xor_sync(0xffffffffu, m, 2), c = __shfl_xor_sync(0xffffffffu, m, 3);
  return fmaxf(fmaxf(m, a), fmaxf(b, c));
}
__device__ __forceinline__ float row_rcp(const float (&v)[14], uint32_t f) {
  float s = sel<kInV>(v[0] + v[1], 0.f, f), s2 = sel<kInV * 2>(v[2] + v[3], 0.f, f);
  add_if<kInV * 4>(s, v[4] + v[5], f);
  add_if<kInV * 8>(s2, v[6] + v[7], f);
  add_if<kInU>(s, v[8] + v[10] + v[12], f);
  add_if<kInU * 2>(s2, v[9] + v[11] + v[13], f);
  s += s2;
  const float a = __shfl_xor_sync(0xffffffffu, s, 1), b = __shfl_xor_sync(0xffffffffu, s, 2), c = __shfl_xor_sync(0xffffffffu, s, 3);
  return rcp_approx((s + a) + (b + c));
}
__device__ __forceinline__ void route(const float (&v)[14], float s, const uint32_t (&rt)[9], uint32_t (&p)[14]) {
#pragma unroll
  for (int i = 0; i < 7; i++) {
    const uint32_t u = pack_bf16(v[2 * i] * s, v[2 * i + 1] * s);
    if (i < 4) p[i] = u & rt[i];
    if (i < 3) p[i + 4] = u & rt[i + 4];
    if (i >= 4) {
      p[i + 3] = u & rt[7];
      p[i + 6] = u & rt[8];
    }
  }
}

template <int C, int T0 = 0, int T1 = 7>
__device__ __forceinline__ void pv_chunk(float (&z)[32], const uint32_t (&pa)[14], const uint32_t (&pb)[14],
                                         const uint32_t (&meta)[4], uint64_t dV) {
#pragma unroll
  for (int t = T0; t < T1; t++) {
    if (t & 1)
      wg_s64t1<0, 32>(z, pa[2 * t], pb[2 * t], pa[2 * t + 1], pb[2 * t + 1], dV + ((2 * C * kChunkBytes + t * 2048) >> 4), 1,
                      meta[t >> 1]);
    else if (t > 0)
      wg_s64t<0, 32>(z, pa[2 * t], pb[2 * t], pa[2 * t + 1], pb[2 * t + 1], dV + ((2 * C * kChunkBytes + t * 2048) >> 4), 1,
                     meta[t >> 1]);
    else
      wg_s64tz<0, 32>(z, pa[0], pb[0], pa[1], pb[1], dV + ((2 * C * kChunkBytes) >> 4), 0, meta[0]);
  }
}
template <int C>
__device__ __forceinline__ void pack_z(const float (&z)[32], uint32_t (&za)[24], uint32_t (&zb)[24]) {
#pragma unroll
  for (int j = 0; j < 8; j++) {
    za[8 * C + j] = pack_bf16(z[4 * j], z[4 * j + 1]);
    zb[8 * C + j] = pack_bf16(z[4 * j + 2], z[4 * j + 3]);
  }
}

template <int H>
__device__ __forceinline__ void pack_out(const float (&ac)[48], uint32_t (&oa)[24], uint32_t (&ob)[24]) {
#pragma unroll
  for (int j = 0; j < 12; j++) {
    oa[12 * H + j] = pack_bf16(ac[4 * j], ac[4 * j + 1]);
    ob[12 * H + j] = pack_bf16(ac[4 * j + 2], ac[4 * j + 3]);
  }
}
struct Maps { CUtensorMap v6, v2, v14, u8, px[8], wv, wo; };
__device__ __forceinline__ void tma_prefetch_5d(const CUtensorMap* map, int c0, int c1, int c2, int c3, int c4) {
  asm volatile("cp.async.bulk.prefetch.tensor.5d.L2.global.tile [%0, {%1, %2, %3, %4, %5}];" ::"l"((uint64_t)map), "r"(c0), "r"(c1),
               "r"(c2), "r"(c3), "r"(c4) : "memory");
}
__device__ __forceinline__ int first_line(const TileCoord tc) { return 3 * (qpix(tc.pr, 8 * tc.I) * kW + qpix(tc.pc, 8 * tc.J)); }
__device__ __forceinline__ void load_px(const Maps& tm, const TileTable& tt, uint32_t dst, uint32_t bar, int line, int kind) {
#pragma unroll
  for (int i = 0; i < 2; i++) {
    if (i == 0 || kind != 0) {
      const CUtensorMap* map = (const CUtensorMap*)((const char*)tm.px + tt.b[kind][i][1]);
      if (bar) tma_load_5d(dst + tt.b[kind][i][2], map, bar, 0, 0, 0, 0, line + tt.b[kind][i][0]);
      else tma_prefetch_5d(map, 0, 0, 0, 0, line + tt.b[kind][i][0]);
    }
  }
}
__device__ __forceinline__ void store_px(const Maps& tm, const TileTable& tt, uint32_t buf, int line, int kind) {
#pragma unroll
  for (int i = 0; i < 8; i++) {
    const int j = 2 * (i & 3) + (i >> 2);
    asm volatile("cp.async.bulk.tensor.5d.global.shared::cta.tile.bulk_group [%0, {%2, %2, %2, %2, %3}], [%1];" ::"l"(
                     (uint64_t)tm.px + tt.g[kind][j][1]), "r"(buf + i * 3072), "r"(0), "r"(line + tt.g[kind][j][0]) : "memory");
  }
  asm volatile("cp.async.bulk.commit_group;" ::: "memory");
}
__device__ __noinline__ bool refetch(uint32_t base, const uint8_t* src, bool gap) {
  constexpr uint32_t bars = 1024 + kBarOff, cnt = bars + 192;
#pragma unroll 1
  for (uint32_t o = 0; o < kWBytes && !gap; o += 2048) {
    uint32_t mx = 0;
#pragma unroll
    for (int i = 0; i < 4; i++) {
      uint4 v;
      asm volatile("ld.shared.v4.u32 {%0,%1,%2,%3}, [%4];" : "=r"(v.x), "=r"(v.y), "=r"(v.z), "=r"(v.w)
                   : "r"(base + o + i * 512 + (threadIdx.x & 31) * 16));
      mx = __vimax3_u32(__vimax3_u32(mx, v.x, v.y), v.z, v.w);
    }
    gap = __any_sync(0xffffffffu, mx == kEmpty);
  }
  uint32_t n;
  asm volatile("ld.shared.u32 %0, [%1];" : "=r"(n) : "r"(cnt) : "memory");
  if (!gap || __any_sync(0xffffffffu, n > (1u << 12))) return false;
  asm volatile("bar.sync 15, 128;" ::: "memory");
  if (threadIdx.x == 0) {
    asm volatile("st.shared.u32 [%0], %1;" ::"r"(cnt), "r"(n + 1) : "memory");
    mbar_arrive_expect_tx(bar_redo(bars), kWBytes);
    bulk_load(base, src, kWBytes, bar_redo(bars));
  }
  __syncwarp();
  mbar_wait(bar_redo(bars), n & 1);
  return true;
}
__device__ __forceinline__ bool any_nan(const uint32_t (&a)[24]) {
  uint32_t m[2] = {a[0], a[1]}, nan;
#pragma unroll
  for (int i = 2; i < 24; i++) asm("max.NaN.bf16x2 %0, %0, %1;" : "+r"(m[i & 1]) : "r"(a[i]));
  asm("max.NaN.bf16x2 %0, %0, %1;" : "+r"(m[0]) : "r"(m[1]));
  asm volatile("{\n.reg .pred p;\nsetp.ne.u32 p, %1, 0;\nbar.red.or.pred p, 15, 128, p;\nselp.u32 %0, 1, 0, p;\n}\n"
               : "=r"(nan) : "r"(((m[0] & 0x7FFF7FFFu) + 0x007F007Fu) & 0x80008000u) : "memory");
  return __any_sync(0xffffffffu, nan);
}
template <int S0, int S1, int Z>
__device__ __forceinline__ void g2_steps(float (&ac)[48], const uint32_t (&za)[24], const uint32_t (&zb)[24], uint64_t d) {
#pragma unroll
  for (int s = S0; s < S1; s++) {
    const uint64_t ds = d + (((s >> 2 & 1) * (kWChunk / 2) + (s & 3) * 32) >> 4);
    if (s == Z) wg_d96z<0, 48>(ac, za[2 * s], zb[2 * s], za[2 * s + 1], zb[2 * s + 1], ds, 0);
    else wg_d96<0, 48>(ac, za[2 * s], zb[2 * s], za[2 * s + 1], zb[2 * s + 1], ds, 1);
  }
}

__device__ __forceinline__ void consumer(const int wg, __nv_bfloat16* out, const uint8_t* wimg, const uint32_t sbase,
                                         const uint32_t zero, const Maps& tm, const TileTable& tt) {
  const int tid = threadIdx.x & 127;
  const int w = __shfl_sync(0xffffffffu, tid >> 5, 0), lane = tid & 31;
  const uint64_t dK = make_desc(sbase, 16, 1024);
  const uint64_t dV = make_desc(sbase, kChunkBytes, 512, 2);
  const uint64_t dW1 = make_desc(sbase + kW1Off, 16, 1024);
  const uint64_t dX0 = make_desc(sbase + kW2Off + wg * 2 * kWChunk, 16, 1024), dY0 = make_desc(sbase + kW2Off + (1 - wg) * 2 * kWChunk, 16, 1024);
  const uint64_t dX2 = make_desc(sbase + kXOff + wg * (kWChunk / 2), 16, 1024), dY2 = make_desc(sbase + kXOff + (1 - wg) * (kWChunk / 2), 16, 1024);
  const uint32_t bars = sbase + kBarOff;
  int tile0 = blockIdx.x * kTilesPerCta;
  asm volatile("" : "+r"(tile0));
  const int nt = num_tiles();

  uint32_t pix = 0, geo[6] = {};
  const int l = lane & 3;
#pragma unroll 1
  for (int j = 4; j >= 0; j -= 2) {
    const TileCoord tc = decode_tile(tt, tile0 + wg + j);
    const bool col = tc.kind == 1 || tc.kind == 2;
    const int g = col ? lane >> 2 : 2 * w + ((lane >> 2) & 1), qc = col ? w : lane >> 3;
    const uint32_t pr = qpix(tc.pr, 8 * tc.I + g) * kW;
    if (j == nt - 2) pix = (pr + qpix(tc.pc, 8 * tc.J + qc)) | (pr + qpix(tc.pc, 8 * tc.J + qc + 4)) << 16;
    const int d = 8 * tc.J + 6 * tc.pc - 6 - halo_c0(tc);
    const int ro = woff(tc.pr, tc.I, g), coA = woff(tc.pc, tc.J, qc) + d, coB = woff(tc.pc, tc.J, qc + 4) + d - 3;
#pragma unroll
    for (int i = 5; i >= 2; i--) geo[i] = geo[i - 2];
    const uint32_t lr = 0x1FCu << ro;
    const uint32_t lv = lr >> (2 + (l >> 1)), lu = lr >> (2 * l + 2 * tc.up);
    const uint32_t t = __byte_perm(lv, lu, wg ? 0x4501 : 0x5410);
    geo[0] = (((t & 0x15u) | (lv & 0x40u)) * 0x02082080u & 0x80808080u) | (((t >> 8) & 0x15u) * 0x01041040u & 0x40404040u) |
             (__byte_perm(t << 5, t << 4, 0x7362) & 0x20202020u) | (nt == 6);
    const int dr = (ro - 1) & 7;
    const uint32_t hiv = (((1u << ((ro - (l >> 1) + 1) >> 1)) - 1u) ^ (wg ? 7u : 0u)) & 7u, hiu = (t >> 24) & 3u;
    const uint32_t ca = (1u << coA) - 1u;
    geo[1] = hiv * kHiV | hiu * kHiU | ((((1u << coB) - 1u) >> (2 * (l & 1))) & 3u) * kColB |
             (15u & ~((uint32_t)((dr & 1) == (l >> 1)) << (dr >> 1))) * kInV | ((t >> 16 | t >> 24) & 3u) * kInU | ca * kColA |
             (ca >> ((0x49 >> (2 * l)) & 3) & 1u) << 19 | (uint32_t)(l == 3) << 20 | (0x55u & ((1u << (2 * coB)) - 1u)) << 24;
  }
  keep_regs(geo);
  const int so = (lane >> 3) | (lane & 4);
  uint32_t sts = sbase + w * 3072 + so * 128 + (((lane & 3) ^ so) << 4);
  __nv_bfloat16* poA = out + 8 * l + (pix & 0xFFFFu) * kC + 96 * wg;
  __nv_bfloat16* poB = out + 8 * l + (pix >> 16) * kC + 96 * wg;
  asm volatile("" : "+l"(poA), "+l"(poB), "+r"(sts));
  uint32_t oa[24], ob[24];
#pragma unroll
  for (int j = 0; j < 24; j++) oa[j] = ob[j] = 0u;
  keep_regs(oa);
  keep_regs(ob);
  PROF(wg, 0);
  if (threadIdx.x == 0) GT(1);

  for (int k = wg; k < nt; k += 2) {
    const uint32_t ph = (k >> 1) & 1;
    const int it = k >> 1;
    uint32_t qa[24], qb[24], hok[3];
    uint32_t fl = geo[1];
    {
      float acc[96];
      const uint32_t xp = (k + (k > 0)) & 1;
      const uint32_t xok = mbar_test(bar_x(bars, k > 0, 0), xp);
      if (k > 0) nb_sync(1 + (1 - wg));
#pragma unroll
      for (int s = 0; s < 12; s++) {
        if (s == 0) mbar_wait_if(xok, bar_x(bars, k > 0, 0), xp);
        if (s == 0 && k < 2) PROF(wg, 1);
        if (s == 0) PROFS(2, wg, 2 + it * 12);
        if (s == 0 && w == 0 && k < 2) GT(20 + wg);
        if ((s & 3) == 0 && (k == 0 || s > 0)) {
          mbar_wait(k == 0 ? bar_w1c(bars, s >> 2) : bar_x(bars, 1, s >> 2), xp);
          PROFS(17, wg, 50 + (s >> 2));
        }
        if ((s & 3) == 0) wg_fence();
        const uint64_t dX = make_desc(sbase + x_chunk(k, s >> 2), 16, 1024) + 2 * (s & 3);
        if (s == 0) wg_m192z<0, 96>(acc, dX, dW1, 0);
        else wg_m192<0, 96>(acc, dX, wdesc(dW1, s), 1);
        if ((s & 3) == 3) wg_commit();
      }
      PROFS(13, wg, 13 + it * 12);
      const uint32_t e = sts + out_slot(k, nt), o = e ^ 64;
      uint32_t ad[4] = {wg ? o + 1024 : e, wg ? e + 2048 : o, wg ? e : o + 1024, wg ? o : e + 2048};
      keep_regs(ad);
      wg_wait<2>();
      if (k > 0) nb_arrive_p(0);
      wg_wait<1>();
      if (k > 0) nb_arrive_p(14);
      wg_wait<0>();
      if (k > 0) {
        nb_arrive_p(6);
        sched_fence();
      }
      fence_regs(acc);
      PROFS(3, wg, 3 + it * 12);
#pragma unroll
      for (int j = 0; j < 24; j++) {
        qa[j] = pack_bf16(acc[4 * j], acc[4 * j + 1]);
        qb[j] = pack_bf16(acc[4 * j + 2], acc[4 * j + 3]);
      }
      keep_regs(qa);
      keep_regs(qb);
      sched_fence();
      if (k >= 2) {
        nb_sync(11);
        stage_out<0, 6>(ad, oa, ob);
        nb_sync(12);
        stage_out<6, 12>(ad, oa, ob);
      }
#pragma unroll
      for (int c = 0; c < 3; c++) hok[c] = mbar_test(bar_full(bars, wg, c), ph);
      if (k >= 2) {
        fence_proxy_async();
        nb_arrive_p(10);
      }
    }

    float aE[52], aO[24], bO[52], bE[28];
    const uint32_t mq = 0xEEEE4444u | zero;
    PROFS(4, wg, 4 + it * 12);

    mbar_wait_if(hok[0], bar_full(bars, wg, 0), ph);
    PROFS(14, wg, 40 + it * 3);
    if (w == 0 && k < 2) GT(22 + wg);
    if (k > 0) nb_sync(3 + (1 - wg));
    wg_fence();
#pragma unroll
    for (int ks = 0; ks < 6; ks++) {
      if (ks == 2) {
        mbar_wait_if(hok[1], bar_full(bars, wg, 1), ph);
        PROFS(14, wg, 41 + it * 3);
        wg_fence();
      }
      if (ks == 4) {
        mbar_wait_if(hok[2], bar_full(bars, wg, 2), ph);
        PROFS(14, wg, 42 + it * 3);
        wg_fence();
      }
      const uint64_t d = dK + ((ks * kChunkBytes) >> 4);
      if (ks == 0) wg_s104z<0, 52>(aE, qa[0], qa[1], qa[2], qa[3], d, 0, mq);
      else wg_s104<0, 52>(aE, qa[4 * ks], qa[4 * ks + 1], qa[4 * ks + 2], qa[4 * ks + 3], d, 1, mq);
      if (ks == 0) wg_s48z<0, 24>(aO, qa[0], qa[1], qa[2], qa[3], d + ((7 * 1024 + 64) >> 4), 0, mq);
    }
    wg_commit();
#pragma unroll
    for (int ks = 1; ks < 6; ks++)
      wg_s48<0, 24>(aO, qa[4 * ks], qa[4 * ks + 1], qa[4 * ks + 2], qa[4 * ks + 3], dK + ((ks * kChunkBytes + 7 * 1024 + 64) >> 4), 1, mq);
    wg_commit();
    wg_s56z<0, 28>(bE, qb[0], qb[1], qb[2], qb[3], dK, 0, mq);
#pragma unroll
    for (int ks = 1; ks < 6; ks++) wg_s56<0, 28>(bE, qb[4 * ks], qb[4 * ks + 1], qb[4 * ks + 2], qb[4 * ks + 3], dK + ((ks * kChunkBytes) >> 4), 1, mq);
    wg_commit();
    wg_wait<2>();
    fence_regs(aE);
    PROFS(5, wg, 5 + it * 12);

    uint32_t pa[14], pb[14], meta[4];
    {
      float vA[14], vB[14];
      pick_v(aE, vA, fl);
      pick_u(aE + 28, vA + 8, fl);
      fence_regs(vA);
      if (k == 0) {
        if (__builtin_expect(__any_sync(0xffffffffu, vA[6] != vA[6]), 0)) {
          wg_wait<0>();
          fence_regs(aO);
          fence_regs(bE);
          if (refetch(sbase + kW1Off, wimg, false)) {
#pragma unroll
            for (int j = 0; j < 24; j++) oa[j] = ob[j] = 0u;
            k -= 2;
            continue;
          }
        }
        if (elect_one()) mbar_arrive(bar_xf(bars));
      }
      wg_fence();
      wg_s104z<0, 52>(bO, qb[0], qb[1], qb[2], qb[3], dK + 4, 0, mq);
#pragma unroll
      for (int ks = 1; ks < 6; ks++)
        wg_s104<0, 52>(bO, qb[4 * ks], qb[4 * ks + 1], qb[4 * ks + 2], qb[4 * ks + 3], dK + ((ks * kChunkBytes + 64) >> 4), 1, mq);
      wg_commit();
      if (k + 1 < nt) nb_arrive(1 + wg);
      uint32_t rt[9];
#pragma unroll
      for (int i = 0; i < 7; i++) rt[i] = sign_bytes(geo[0] << (i >> 2), 0x8888u + 0x1111u * (i & 3));
      rt[7] = sign_bytes(geo[0] << 2, 0x9988u);
      rt[8] = sign_bytes(geo[0] << 2, 0xBBAAu);
      keep_regs(rt);
      pa[13] = pb[13] = 0u;
      wg_wait<2>();
      keep_regs(qa);
      fence_regs(aO);
      float oA[6], eB[8];
      pick_u(aO, oA, fl);
      wg_wait<1>();
      fence_regs(bE);
      pick_v(bE, eB, fl);
      vA[8] = sel<kColA>(oA[0], vA[8], fl), vA[9] = sel<kColA>(oA[1], vA[9], fl);
      vA[10] = sel<kColA * 2>(oA[2], vA[10], fl), vA[11] = sel<kColA * 2>(oA[3], vA[11], fl);
      vA[12] = sel<kColA * 4>(oA[4], vA[12], fl), vA[13] = sel<kColA * 4>(oA[5], vA[13], fl);
      {
        const float m1 = __uint_as_float(0x88DD88DDu), m0 = __uint_as_float(0x88DDDD88u);
        meta[0] = 0xDD88DD88u ^ __byte_perm(fl, 0u, 0x3344);
        meta[1] = __float_as_uint(sel<kColA * 16>(sel<kColA>(m1, m0, fl), __uint_as_float(meta[0]), fl));
        meta[2] = __float_as_uint(sel<kColA * 8>(m1, m0, fl));
        meta[3] = __float_as_uint(sel<kColA * 4>(m1, m0, fl));
        keep_regs(meta);
      }
      float mA = own_max(vA, fl);
      fl |= __float_as_uint(eB[7]) & zero;
      fence_regs(eB);
      fence_regs(vA);
      asm volatile("" : "+f"(mA), "+r"(fl));
      sched_fence();
      wg_wait<0>();
      sched_fence();
      keep_regs(qb);
      fence_regs(bO);
      PROFS(6, wg, 6 + it * 12);
      if (w == 0) GT(24 + k);
      mA = quad_max(mA);
#pragma unroll
      for (int i = 0; i < 14; i++) vA[i] = ex2(vA[i] - mA);
      pick_v(bO, vB, fl);
      pick_u(bO + 28, vB + 8, fl);
#pragma unroll
      for (int i = 0; i < 8; i += 2) vB[i] = sel<kColB>(vB[i], eB[i], fl), vB[i + 1] = sel<kColB * 2>(vB[i + 1], eB[i + 1], fl);
      float mB = quad_max(own_max(vB, fl));
      PROFS(7, wg, 7 + it * 12);
#pragma unroll
      for (int i = 0; i < 14; i++) vB[i] = ex2(vB[i] - mB);
      route(vA, row_rcp(vA, fl), rt, pa);
      route(vB, row_rcp(vB, fl), rt, pb);
    }
    PROFS(8, wg, 8 + it * 12);
    if (k == NAT_PK) PROFS(18, wg, 53);
    sched_fence();

    float ac0[48], ac1[48];
    {
      float z0[32], z1[32], z2[32];
      uint32_t za[24], zb[24];
      wg_fence();
      pv_chunk<0>(z0, pa, pb, meta, dV);
      wg_commit();
      pv_chunk<1>(z1, pa, pb, meta, dV);
      wg_commit();
      wg_wait<1>();
      if (k == NAT_PK) PROFS(18, wg, 54);
      if (k + 1 < nt) nb_arrive_p(7);
      pv_chunk<2, 0, 3>(z2, pa, pb, meta, dV);
      wg_commit();
      sched_fence();
      fence_regs(z0);
      pack_z<0>(z0, za, zb);
      sched_fence();
      wg_fence();
      pv_chunk<2, 3, 7>(z2, pa, pb, meta, dV);
      wg_commit();
      wg_wait<2>();
      if (k == NAT_PK) PROFS(19, wg, 55);
      if (k + 1 < nt) nb_arrive_p(8);
      if (k < 2) mbar_wait(k == 1 ? bar_wok(bars) : bar_w2a(bars), 0);
      wg_fence();
      g2_steps<0, 3, 0>(ac0, za, zb, dX0);
      wg_commit();
      sched_fence();
      fence_regs(z1);
      pack_z<1>(z1, za, zb);
      sched_fence();
      wg_fence();
      g2_steps<3, 4, 0>(ac0, za, zb, dX0);
      wg_commit();
      g2_steps<4, 8, 0>(ac0, za, zb, dX0);
      wg_commit();
      wg_wait<3>();
      if (k + 1 < nt) nb_arrive_p(9);
      else nb_arrive(11);
      if (k == NAT_PK) PROFS(20, wg, 56);
      keep_regs(pa);
      keep_regs(pb);
      keep_regs(meta);
      sched_fence();
      const uint32_t mok = mbar_test(bar_w2m(bars), k + 1 < nt ? k & 1 : ~k & 1);
      const uint32_t wp = k < 2 ? 0 : k + 1 < nt ? ~k & 1 : k & 1, wok = mbar_test(bar_w2(bars), wp);
      fence_regs(z2);
      pack_z<2>(z2, za, zb);
      keep_regs(za);
      keep_regs(zb);
      sched_fence();
      PROFS(9, wg, 9 + it * 12);
      wg_wait<1>();
      if (k > 0 && k + 1 < nt) nb_arrive(11);
      mbar_wait_if(mok, bar_w2m(bars), k & 1);
      wg_fence();
      g2_steps<8, 12, 0>(ac0, za, zb, dX2);
      wg_commit();
      g2_steps<8, 12, 8>(ac1, za, zb, dY2);
      wg_commit();
      wg_wait<2>();
      if (k > 0 && k + 1 < nt) nb_arrive(12);
      mbar_wait_if(wok, bar_w2(bars), wp);
      wg_fence();
      g2_steps<0, 4, 8>(ac1, za, zb, dY0);
      wg_commit();
      wg_wait<2>();
      if (k + 2 < nt) nb_arrive_p(13);
      const bool direct = k + 2 >= nt;
      sched_fence();
      fence_regs(ac0);
      pack_out<0>(ac0, oa, ob);
      store_rows<0, 1>(direct, poA, poB, oa, ob);
      sched_fence();
      wg_fence();
      g2_steps<4, 8, 8>(ac1, za, zb, dY0);
      wg_commit();
      if (k + 1 < nt) nb_arrive(3 + wg);
      PROFS(10, wg, 10 + it * 12);
      wg_wait<2>();
      if (k + 2 < nt && (k > 0 || nt == 6)) nb_arrive_p(5);
      store_rows<1, 3>(direct, poA, poB, oa, ob);
      __nv_bfloat16 *qA = poA - 192 * wg, *qB = poB - 192 * wg;
      if (k + 2 == nt) nb_sync(11);
      sched_fence();
      wg_wait<0>();
      fence_regs(ac1);
      pack_out<1>(ac1, oa, ob);
      asm volatile("" : "+l"(qA), "+l"(qB));
      store_rows<3, 6>(direct, qA, qB, oa, ob);
      if (direct) break;
      if (k == 0) {
        if (any_nan(oa)) {
          for (int c = 0; c < 3 && __any_sync(0xffffffffu, geo[2] & 1u); c++) mbar_wait(bar_x(bars, 1, c), 1);
          bool first = true;
          do {
            if (!__any_sync(0xffffffffu, refetch(sbase + kW2Off, wimg + w2_offset(), first))) break;
            first = false;
            wg_fence();
            g2_steps<0, 8, 0>(ac0, za, zb, dX0);
            g2_steps<8, 12, 0>(ac0, za, zb, dX2);
            g2_steps<8, 12, 8>(ac1, za, zb, dY2);
            g2_steps<0, 8, 8>(ac1, za, zb, dY0);
            wg_commit();
            wg_wait<0>();
            fence_regs(ac0);
            fence_regs(ac1);
            pack_out<0>(ac0, oa, ob);
            pack_out<1>(ac1, oa, ob);
          } while (any_nan(oa));
          if (__any_sync(0xffffffffu, geo[2] & 1u)) {
            asm volatile("bar.sync 15, 128;" ::: "memory");
            if (w == 0 && elect_one()) {
              const TileCoord tc = decode_tile(tt, tile0 + 2);
              mbar_arrive_expect_tx(bar_raw(bars), kWChunk);
#pragma unroll 1
              for (int c = 0; c < 3; c++) load_px(tm, tt, sbase + x_chunk(2, c), bar_raw(bars), first_line(tc) + c, tc.kind);
            }
            __syncwarp();
            mbar_wait(bar_raw(bars), 0);
          }
        }
        if (nt < 6) nb_arrive_p(5);
        if (elect_one()) mbar_arrive(bar_wok(bars));
      }
      keep_regs(za);
      keep_regs(zb);
#pragma unroll
      for (int i = 0; i < 4; i++) geo[i] = geo[i + 2];
      keep_regs(oa);
      keep_regs(ob);
      PROFS(12, wg, 12 + it * 12);
      sched_fence();
    }
  }
  PROF(wg, 38);
  GT_DUMP();
  PROF_DUMP(wg);
}

struct HaloCols { int vj, vc, uj, uc; };
__device__ __forceinline__ HaloCols halo_cols(const TileCoord& tc) {
  const int c0 = halo_c0(tc);
  return HaloCols{c0 > 98, c0 > 98 ? 98 : c0 + 3, c0 < 0 ? -1 : 0, c0 < 0 ? 4 : c0};
}
__device__ __forceinline__ void first_halo(const Maps& tm, uint32_t sbase, const TileCoord tc, int i) {
  const HaloCols hc = halo_cols(tc);
  const uint32_t dst = sbase + i * kChunkBytes, bar = bar_full(sbase + kBarOff, 0, i >> 1);
  const int h0 = halo_r0(tc), ch = 24 * tc.pc + 4 * i;
  tma_load_5d(dst, &tm.v14, bar, ch, hc.vj, hc.vc, tc.pr, h0);
  tma_load_5d(dst + 7 * 1024, &tm.u8, bar, ch, hc.uj, h0 + (tc.up ? 0 : -2), tc.pr, hc.uc);
  tma_load_5d(dst + 10 * 1024, &tm.u8, bar, ch, hc.uj, h0 + (tc.up ? 8 : 6), tc.pr, hc.uc);
}
__device__ __forceinline__ void load_halo(const Maps& tm, uint32_t sbase, uint32_t bars, const TileCoord tc, int k, int c) {
  const HaloCols hc = halo_cols(tc);
  const int h6 = halo_r0(tc) + (tc.up ? 0 : 8), h2 = halo_r0(tc) + 6, h8 = halo_r0(tc) + (tc.up ? 0 : 6), ch = 24 * tc.pc + 8 * c;
  uint32_t dv = sbase + 2 * c * kChunkBytes, du = dv + 7 * 1024;
  if (((k ^ tc.up) & 1) == 0) dv += 4 * 1024, du += 3 * 1024;
  const uint32_t bar = bar_full(bars, k & 1, c);
  mbar_arrive_expect_tx(bar, 14 * 1024);
  nb_sync_p(7 + c);
#pragma unroll
  for (int h = 0; h < 2; h++) {
    tma_load_5d(dv + h * kChunkBytes, &tm.v6, bar, ch + 4 * h, hc.vj, hc.vc, tc.pr, h6);
    tma_load_5d(du + h * kChunkBytes, &tm.u8, bar, ch + 4 * h, hc.uj, h8, tc.pr, hc.uc);
    tma_load_5d(sbase + (2 * c + h) * kChunkBytes + 3 * 1024, &tm.v2, bar, ch + 4 * h, hc.vj, hc.vc, tc.pr, h2);
  }
  PROFS(15, 2, k * 4 + c);
}
__device__ __forceinline__ void gather_px(const __nv_bfloat16* __restrict__ x, uint32_t sbase, const TileCoord tc) {
  const int lane = threadIdx.x & 31, g = lane >> 3;
  uint32_t ro[4], co[4];
#pragma unroll
  for (int i = 0; i < 4; i++) {
    ro[i] = qpix(tc.pr, 8 * tc.I + 2 * i + (g & 1)) * (kW * kC * 2) + 16 * (lane & 7);
    co[i] = qpix(tc.pc, 8 * tc.J + 2 * i + (g >> 1)) * (kC * 2);
  }
  const uint32_t dst = sbase + kXOff + g * 128 + (((lane & 7) ^ g) << 4);
  if (lane < 8)
    asm volatile("cp.async.bulk.prefetch.L2.global [%0], 3456;" ::"l"(x + (qpix(tc.pr, 8 * tc.I + lane) * kW + 215 * tc.pc) * kC) : "memory");
  __syncwarp();
  keep_regs(ro);
  keep_regs(co);
  sched_fence();
  nb_sync_p(13);
  nb_sync_p(5);
#pragma unroll
  for (int i = 0; i < 16; i++) {
    const char* src = (const char*)x + (ro[i >> 2] + co[i & 3]);
#pragma unroll
    for (int q = 0; q < 3; q++)
      asm volatile("cp.async.cg.shared.global [%0], [%1], 16;" ::"r"((dst ^ ((i & 1) * 576)) + (i >> 1) * 1024 + q * 8192), "l"(src + 128 * q) : "memory");
  }
  asm volatile("cp.async.wait_all;" ::: "memory");
  fence_proxy_async();
  __syncwarp();
  if (lane < 3) mbar_arrive(bar_x(sbase + kBarOff, 1, lane));
  __syncwarp();
}

__global__ void __launch_bounds__(384, 1)
nat_kernel(const __nv_bfloat16* __restrict__ x, __nv_bfloat16* out, const __nv_bfloat16* __restrict__ wqkv,
           const __nv_bfloat16* __restrict__ wo, uint8_t* wimg, const uint32_t zero,
           const __grid_constant__ Maps tm, const __grid_constant__ TileTable tt) {
  extern __shared__ uint8_t smem_raw[];
  constexpr uint32_t sbase = 1024;
  constexpr uint32_t bars = sbase + kBarOff;
  if (smem_u32(smem_raw) != sbase) __trap();
  const int tid = threadIdx.x;
  const uint32_t t_start = now_ns();
  if (tid == 0) GT(0);
  const int wid = __shfl_sync(0xffffffffu, tid >> 5, 0);
  const bool w2cta = blockIdx.x - 128 < 3 && wqkv != nullptr;
  if (wid >= 8) {
    asm volatile("setmaxnreg.dec.sync.aligned.u32 24;");
    const int c = wid & 3, lane = tid & 31;
    const int tile0 = blockIdx.x * kTilesPerCta, nt = num_tiles();
    uint32_t w2o = 0;
    if (c == 3) {
      if (elect_one()) wait_clock(t_start, NAT_TM);
      __syncwarp();
      asm volatile("prefetch.tensormap [%0];" ::"l"((uint64_t)tm.px) : "memory");
      asm volatile("prefetch.tensormap [%0];" ::"l"((uint64_t)&tm.v6) : "memory");
      asm volatile("prefetch.tensormap [%0];" ::"l"((uint64_t)&tm.v2) : "memory");
      asm volatile("prefetch.tensormap [%0];" ::"l"((uint64_t)(tm.px + (blockIdx.x < 112 ? 5 : 6))) : "memory");
      asm volatile("prefetch.tensormap [%0];" ::"l"((uint64_t)(tm.px + 7)) : "memory");
      if (nt < 6) {
        asm volatile("prefetch.tensormap [%0];" ::"l"((uint64_t)(tm.px + 1)) : "memory");
        asm volatile("prefetch.tensormap [%0];" ::"l"((uint64_t)(tm.px + 2)) : "memory");
        asm volatile("prefetch.tensormap [%0];" ::"l"((uint64_t)&tm.v14) : "memory");
        asm volatile("prefetch.tensormap [%0];" ::"l"((uint64_t)&tm.u8) : "memory");
      }
      __nanosleep(NAT_TW2 - 2800);
      asm volatile("bar.sync 4, 64;" ::: "memory");
      w2o = w2_offset();
      if (elect_one()) {
        mbar_arrive_expect_tx(bar_w2a(bars), kWChunk);
        mbar_arrive_expect_tx(bar_w2(bars), kWChunk);
        wait_clock(t_start, NAT_TW2);
        bulk_load(sbase + kW2Off, wimg + w2o, kWChunk, bar_w2a(bars));
        mbar_wait(bar_xf(bars), 0);
        bulk_load(sbase + kW2Off + 2 * kWChunk, wimg + (w2o + 2 * kWChunk), kWChunk, bar_w2(bars));
      }
      __syncwarp();
      if (nt < 6) gather_px(x, sbase, decode_tile(tt, tile0 + 2));
      if (wqkv == nullptr) return;
      mbar_wait(bar_wok(bars), 0);
      if (lane == 0) asm volatile("red.relaxed.gpu.global.add.u32 [%0], 1;" ::"l"(g_flag) : "memory");
      if (blockIdx.x >= 48) return;
      if (lane == 0) {
        uint32_t v, it = 0;
        do {
          __nanosleep(2000);
          asm volatile("ld.relaxed.gpu.global.u32 %0, [%1];" : "=r"(v) : "l"(g_flag) : "memory");
        } while (v < gridDim.x && ++it < (1u << 16));
      }
      __syncwarp();
#pragma unroll
      for (int i = 0; i < 6; i++)
        stg128(wimg + ((i < 3 ? 0u : 3 * kWBytes - w2o) + blockIdx.x * 1536 + (i % 3) * 512 + lane * 16), kEmpty, kEmpty, kEmpty, kEmpty);
      if (lane == 0 && atomicAdd(g_flag + 32, 1u) == 47) {
        g_flag[0] = g_flag[32] = 0;
        g_flag[64] = w2o == kWBytes;
      }
      return;
    }
    if (!elect_one()) return;
    if (c == 0) {
      for (int i = 0; i < kNumBars; i++)
        if ((i != 0 && i != 10 || nt < 6) && (i != 21 || !w2cta)) mbar_init(bars + i * 8, i == 13 || i == 16 ? 4 : 1);
      asm volatile("st.shared.v2.u32 [%0], {%1,%1};" ::"r"(bars + 192), "r"(0) : "memory");
      asm volatile("fence.mbarrier_init.release.cluster;" ::: "memory");
      if (w2cta) asm volatile("bar.sync 10, 64;" ::: "memory");
      asm volatile("bar.arrive 0, 160;" ::: "memory");
      asm volatile("bar.arrive 14, 160;" ::: "memory");
      asm volatile("bar.arrive 13, 96;" ::: "memory");
      asm volatile("bar.arrive 4, 64;" ::: "memory");
      const TileCoord tc0 = decode_tile(tt, tile0);
      const HaloCols hc = halo_cols(tc0);
      const int h0 = halo_r0(tc0);
#pragma unroll
      for (int j = 0; j < 3; j++)
        if (j > 0 || nt < 6) mbar_arrive_expect_tx(bar_full(bars, 0, j), 2 * kChunkBytes);
      wait_clock(t_start, NAT_HP);
#pragma unroll
      for (int q = 8; q < 24 && !w2cta; q += 8) {
        tma_prefetch_5d(blockIdx.x < 112 ? &tm.v6 : &tm.v14, 24 * tc0.pc + q, hc.vj, hc.vc, tc0.pr, h0 + (tc0.up || blockIdx.x >= 112 ? 0 : 8));
        tma_prefetch_5d(&tm.u8, 24 * tc0.pc + q, hc.uj, h0 + (tc0.up ? 0 : 6), tc0.pr, hc.uc);
      }
#pragma unroll 1
      for (int i = nt < 6 ? 0 : 2; i < 6; i++) {
        if (i == 2) mbar_wait(bar_w1q(bars), 0);
        first_halo(tm, sbase, tc0, i);
      }
      mbar_arrive(bar_go(bars));
      w2o = w2_offset();
    } else {
      asm volatile("bar.sync 13, 96;" ::: "memory");
      if (c == 2) {
        if (wqkv != nullptr && blockIdx.x < 131) asm volatile("bar.sync 12, 64;" ::: "memory");
        const uint32_t c0 = clock();
        while ((uint32_t)clock() - c0 < NAT_TD && nt == 6) { }
        wait_clock(t_start, NAT_T0);
#pragma unroll
        for (int j = 0; j < 3; j++) {
          mbar_arrive_expect_tx(bar_w1c(bars, j), kWChunk);
          bulk_load(sbase + kW1Off + j * kWChunk, wimg + j * kWChunk, kWChunk, bar_w1c(bars, j));
        }
        mbar_arrive(bar_w1q(bars));
        GT(2);
      } else {
#pragma unroll 1
        for (int j = nt == 6; j < 2; j++) {
          const TileCoord tc = decode_tile(tt, tile0 + j);
          const int line = first_line(tc);
          if (j == 1) mbar_wait(bar_go(bars), 0);
          if (j == 0) GT(15);
#pragma unroll 1
          for (int q = 0; q < 3; q++) {
            load_px(tm, tt, sbase + x_chunk(j, q), bar_x(bars, j, q), line + q, tc.kind);
            if (j == 1 || q == 0) mbar_arrive_expect_tx(bar_x(bars, j, q), j ? 8192 : kWChunk);
          }
          if (j == 0) GT(16);
        }
        w2o = w2_offset();
        wait_clock(t_start, NAT_TW2);
        mbar_wait(bar_xf(bars), 0);
      }
    }
#pragma unroll 1
    for (int k = 1; k < nt; k++) {
      const TileCoord tn = decode_tile(tt, tile0 + k + 1);
      const int line = first_line(tn);
      const bool more = k + 1 < nt && (k > 1 || nt == 6);
      if (c == 1) {
#pragma unroll
        for (int q = 0; q < 3; q++) {
          nb_sync_p(q == 0 ? 0 : q == 1 ? 14 : 6);
          bulk_load(sbase + x_chunk(k, q), wimg + (w2o + x_chunk(k, q) - kW2Off), 8192, bar_w2m(bars));
        }
        mbar_arrive_expect_tx(bar_w2m(bars), kWChunk);
      }
      if (c == 2) {
        if (k == 1) wait_clock(t_start, NAT_TX2);
        else __nanosleep(NAT_PFD);
#pragma unroll 1
        for (int q = 0; q < 3 && more; q++) load_px(tm, tt, 0, 0, line + q, tn.kind);
      }
      if (c == 2 && (blockIdx.x >= 112 || k == 5)) {
        const TileCoord tc = decode_tile(tt, tile0 + k);
        const HaloCols hc = halo_cols(tc);
        const int h8 = halo_r0(tc) + (tc.up ? 0 : 6);
#pragma unroll 1
        for (int q = 0; q < 24; q += 8) {
          tma_prefetch_5d(&tm.v6, 24 * tc.pc + q, hc.vj, hc.vc, tc.pr, h8);
          tma_prefetch_5d(&tm.v2, 24 * tc.pc + q, hc.vj, hc.vc, tc.pr, h8 + 6);
          tma_prefetch_5d(&tm.u8, 24 * tc.pc + q, hc.uj, h8, tc.pr, hc.uc);
        }
      }
      load_halo(tm, sbase, bars, decode_tile(tt, tile0 + k), k, c);
      if (c == 0 && more) {
#pragma unroll
        for (int q = 0; q < 3; q++) {
          if (q < 2) nb_sync_p(q ? 5 : 13);
          load_px(tm, tt, sbase + x_chunk(k + 1, q), bar_x(bars, 1, q), line + q, tn.kind);
          if (q != 1) mbar_arrive_expect_tx(bar_x(bars, 1, q), 8192);
        }
        mbar_arrive_expect_tx(bar_x(bars, 1, 1), 8192);
        PROFS(16, 2, k * 4 + 3);
      }
      if (c == 0 && k >= 2) {
        const TileCoord tp = decode_tile(tt, tile0 + k - 2);
        const int lp = first_line(tp);
        nb_sync_p(10);
        __nanosleep(NAT_XW);
        store_px(tm, tt, sbase + out_slot(k, nt), lp, tp.kind);
        if (k + 1 < nt) {
          asm volatile("cp.async.bulk.wait_group.read 0;" ::: "memory");
          bulk_load(sbase + out_slot(k, nt), wimg + (w2o + out_slot(k, nt) - kW2Off), kWChunk, bar_w2(bars));
          mbar_arrive_expect_tx(bar_w2(bars), kWChunk);
        }
      }
    }
    asm volatile("cp.async.bulk.wait_group 0;" ::: "memory");
  } else {
    if (blockIdx.x < 128) {
      if ((wid == 4 || (wid == 5 && blockIdx.x - 2 < 16)) && wqkv != nullptr) {
        fold_w1(blockIdx.x - 2 < 16 ? 2 * blockIdx.x + wid - 6 : blockIdx.x + (blockIdx.x < 2 ? 0 : 16), wqkv, wimg);
        if (wid == 4) asm volatile("bar.arrive 12, 64;" ::: "memory");
        if (tid == 128) GT(7);
      }
      sched_fence();
      if (wid == 1 && elect_one()) {
        const TileCoord tc = decode_tile(tt, blockIdx.x * kTilesPerCta);
        mbar_init(bar_x(bars, 0, 0), 1);
        asm volatile("fence.mbarrier_init.release.cluster;" ::: "memory");
        mbar_arrive_expect_tx(bar_x(bars, 0, 0), kWChunk);
        GT(15);
#pragma unroll 1
        for (int q = 0; q < 3; q++) load_px(tm, tt, sbase + x_chunk(0, q), bar_x(bars, 0, 0), first_line(tc) + q, tc.kind);
        GT(16);
      }
      __syncwarp();
      sched_fence();
      if (wid == 2 && elect_one()) {
        const TileCoord tc = decode_tile(tt, blockIdx.x * kTilesPerCta);
        mbar_init(bar_full(bars, 0, 0), 1);
        asm volatile("fence.mbarrier_init.release.cluster;" ::: "memory");
        mbar_arrive_expect_tx(bar_full(bars, 0, 0), 2 * kChunkBytes);
        asm volatile("prefetch.tensormap [%0];" ::"l"((uint64_t)&tm.u8) : "memory");
        GT(17);
        first_halo(tm, sbase, tc, 0);
        first_halo(tm, sbase, tc, 1);
      }
      __syncwarp();
    }
    sched_fence();
    {
      if (w2cta) {
        const int q = blockIdx.x & 3;
        uint32_t w2o = 0;
        if (wid == 1 && elect_one()) {
          asm volatile("prefetch.tensormap [%0];" ::"l"((uint64_t)&tm.wo) : "memory");
#pragma unroll
          for (int j = 0; j < 3; j++) mbar_init(bar_raw(bars, j), 1);
          asm volatile("fence.mbarrier_init.release.cluster;" ::: "memory");
#pragma unroll
          for (int j = 0; j < 6; j++)
            asm volatile("cp.async.bulk.tensor.2d.shared::cluster.global.tile.mbarrier::complete_tx::bytes [%0], [%1, {%3, %4}], [%2];" ::"r"(
                             j < 3 ? sbase + j * 8192 : sbase + kW2Off + (j - 3) * kWChunk),
                         "l"((uint64_t)(j < 3 ? &tm.wv : &tm.wo)), "r"(bar_raw(bars, j < 3 ? 0 : j - 3)),
                         "r"(j < 3 ? 384 + 64 * j : 64 * (j - 3)), "r"(j < 3 ? 64 * q : 0) : "memory");
#pragma unroll
          for (int j = 0; j < 3; j++) mbar_arrive_expect_tx(bar_raw(bars, j), j ? kWChunk : 2 * kWChunk);
          w2o = w2_offset();
        }
        __syncwarp();
#pragma unroll 1
        for (int r = 0; r < 3; r++) {
          const int blk = 2 * r - 2 + (wid >> 2);
          if (blk < 3) {
            if (r > 0) {
              mbar_wait(bar_raw(bars, 0), 0);
              mbar_wait(bar_raw(bars, blk), 0);
            }
            if (tid == 0 && r == 1) GT(7);
            float acc[32];
            const uint64_t db = make_desc(sbase + kW2Off + max(blk, 0) * kWChunk, kWChunk, 1024);
            wg_fence();
            wg_m64tz<0, 32>(acc, make_desc(sbase, 16, 1024), db, 0);
#pragma unroll
            for (int s = 1; s < 12; s++) wg_m64t<0, 32>(acc, make_desc(sbase + (s >> 2) * 8192 + (s & 3) * 32, 16, 1024), db + s * 128, 1);
            wg_commit();
            wg_wait<0>();
            fence_regs(acc);
            if (tid == 0) GT(19);
            const int m = (tid >> 3) & 3;
#pragma unroll
            for (int j = 0; j < 8; j += 2) {
              const int n = g2_inv(8 * (j + (m >> 1)) + (tid & 7));
              asm volatile("stmatrix.sync.aligned.m8n8.x4.trans.shared.b16 [%0], {%1,%2,%3,%4};" ::"r"(
                               sbase + kW1Off + (blk + 2) * 8192 + n * 128 + (((2 * (wid & 3) + (m & 1)) ^ (n & 7)) << 4)),
                           "r"(pack_bf16(acc[4 * j], acc[4 * j + 1])), "r"(pack_bf16(acc[4 * j + 2], acc[4 * j + 3])),
                           "r"(pack_bf16(acc[4 * j + 4], acc[4 * j + 5])), "r"(pack_bf16(acc[4 * j + 6], acc[4 * j + 7])) : "memory");
            }
            fence_proxy_async();
          }
          if (tid == 0) GT(18);
          asm volatile("bar.sync 11, 256;" ::: "memory");
          if (wid == 1 && elect_one()) {
            asm volatile("{\n.reg .pred p;\nsetp.ne.s32 p, %3, 0;\n@p cp.async.bulk.global.shared::cta.bulk_group [%0], [%1], %2;\n}\n" ::"l"(
                             wimg + (w2o + w2piece(r >> 1, q) * (kWChunk / 2))),
                         "r"(sbase + kW1Off + 16384 + (r >> 1) * (kWChunk / 2)), "r"(kWChunk / 2), "r"(r) : "memory");
            asm volatile("cp.async.bulk.commit_group;" ::: "memory");
          }
          __syncwarp();
        }
        if (wid == 1) {
          asm volatile("bar.arrive 10, 64;" ::: "memory");
          if (elect_one()) asm volatile("cp.async.bulk.wait_group.read 0;" ::: "memory");
          if (tid == 32) GT(31);
          __syncwarp();
          asm volatile("bar.arrive 12, 64;" ::: "memory");
        }
      }
    }
    __syncwarp();
    if (wid < 4) asm volatile("bar.sync 0, 160;" ::: "memory");
    else asm volatile("bar.sync 14, 160;" ::: "memory");
    asm volatile("setmaxnreg.inc.sync.aligned.u32 240;");
    consumer(wid >> 2, out, wimg, sbase, zero, tm, tt);
  }
}

}

typedef CUresult (*PFN_encodeTiled)(CUtensorMap*, CUtensorMapDataType, cuuint32_t, void*, const cuuint64_t*,
                                    const cuuint64_t*, const cuuint32_t*, const cuuint32_t*, CUtensorMapInterleave,
                                    CUtensorMapSwizzle, CUtensorMapL2promotion, CUtensorMapFloatOOBfill);

extern "C" void kernel_launch(void* const* d_in, const int* in_sizes, int n_in, void* d_out, int out_size) {
  const __nv_bfloat16* x = (const __nv_bfloat16*)d_in[0];
  const __nv_bfloat16* wqkv = (const __nv_bfloat16*)d_in[1];
  const __nv_bfloat16* wo = (const __nv_bfloat16*)d_in[2];
  __nv_bfloat16* out = (__nv_bfloat16*)d_out;

  static PFN_encodeTiled encode = nullptr;
  static int num_sms = 0;
  static uint8_t* wimg = nullptr;
  if (!encode) {
    void* fn = nullptr;
    cudaDriverEntryPointQueryResult qres;
    cudaGetDriverEntryPoint("cuTensorMapEncodeTiled", &fn, cudaEnableDefault, &qres);
    encode = (PFN_encodeTiled)fn;
    cudaFuncSetAttribute(nat::nat_kernel, cudaFuncAttributeMaxDynamicSharedMemorySize, nat::kSmemBytes);
    cudaGetSymbolAddress((void**)&wimg, nat::g_wimg32);
    int dev = 0;
    cudaGetDevice(&dev);
    cudaDeviceGetAttribute(&num_sms, cudaDevAttrMultiProcessorCount, dev);
  }
  nat::Maps tm;
  cuuint32_t estr[5] = {1, 1, 1, 1, 1};
  {
    cuuint64_t vdim[5] = {48, 2, 105, 2, 112}, udim[5] = {48, 2, 112, 2, 105};
    cuuint64_t vstr[4] = {7 * 768, 768, 224 * 384, 2 * 224 * 384}, ustr[4] = {7 * 768, 2 * 224 * 384, 224 * 384, 768};
    CUtensorMap* maps[4] = {&tm.v6, &tm.v2, &tm.v14, &tm.u8};
    for (int i = 0; i < 4; i++) {
      cuuint32_t box[5] = {4, 2, i < 3 ? 4u : 8u, 1, i == 0 ? 6u : i == 1 ? 2u : i == 2 ? 14u : 3u};
      encode(maps[i], CU_TENSOR_MAP_DATA_TYPE_UINT32, 5, (void*)x, i < 3 ? vdim : udim, i < 3 ? vstr : ustr, box, estr,
             CU_TENSOR_MAP_INTERLEAVE_16B, CU_TENSOR_MAP_SWIZZLE_128B, CU_TENSOR_MAP_L2_PROMOTION_L2_128B, CU_TENSOR_MAP_FLOAT_OOB_FILL_NONE);
    }
  }
  for (int i = 0; i < 8; i++) {
    const cuuint32_t row = 224 * 384;
    const cuuint32_t shape[8][6] = {{2, 8, 4, 2 * row, 768, 4 * row}, {2, 8, 3, row, 768, 2 * row},     {2, 8, 1, 2 * row, 768, 4 * row},
                                    {8, 2, 3, 2 * row, 4 * 384, 384}, {8, 2, 1, 2 * row, 5 * 384, 384}, {4, 2, 3, 4 * row, 2 * row, 128},
                                    {4, 2, 3, 768, row, 128},         {4, 2, 3, 768, 2 * row, 128}};
    const cuuint32_t* sh = shape[i];
    cuuint64_t dim[5] = {64, sh[0], sh[1], sh[2], 224 * 224 * 3};
    cuuint64_t str[4] = {sh[3], sh[4], sh[5], 128};
    cuuint32_t box[5] = {64, sh[0], sh[1], sh[2], 1};
    encode(tm.px + i, CU_TENSOR_MAP_DATA_TYPE_BFLOAT16, 5, i < 5 ? (void*)x : (void*)out, dim, str, box, estr, CU_TENSOR_MAP_INTERLEAVE_NONE,
           CU_TENSOR_MAP_SWIZZLE_128B, i < 5 ? CU_TENSOR_MAP_L2_PROMOTION_L2_128B : CU_TENSOR_MAP_L2_PROMOTION_NONE,
           CU_TENSOR_MAP_FLOAT_OOB_FILL_NONE);
  }
  for (int i = 0; i < 2; i++) {
    cuuint64_t dim[2] = {i ? 192u : 576u, 192}, str[1] = {i ? 384u : 1152u};
    cuuint32_t box[2] = {64, i ? 192u : 64u};
    encode(i ? &tm.wo : &tm.wv, CU_TENSOR_MAP_DATA_TYPE_BFLOAT16, 2, i ? (void*)wo : (void*)wqkv, dim, str, box, estr,
           CU_TENSOR_MAP_INTERLEAVE_NONE, CU_TENSOR_MAP_SWIZZLE_128B, CU_TENSOR_MAP_L2_PROMOTION_L2_256B, CU_TENSOR_MAP_FLOAT_OOB_FILL_NONE);
  }
  nat::TileTable tt;
  nat::make_tiles(tt);
  const int grid = nat::kCtas;
  if (num_sms >= grid) {
    nat::nat_kernel<<<grid, 384, nat::kSmemBytes>>>(x, out, wqkv, wo, wimg, 0u, tm, tt);
  } else {
    nat::fold_kernel<<<27, 256>>>(wqkv, wo, wimg);
    nat::nat_kernel<<<grid, 384, nat::kSmemBytes>>>(x, out, nullptr, nullptr, wimg, 0u, tm, tt);
  }
}
```

```cpp
#include <cuda_runtime.h>
#include <cuda_bf16.h>
#include <cuda.h>
#include <stdint.h>

#define NAT_TM 1300
#define NAT_HP 1800
#define NAT_T0 2130
#define NAT_TD 1250
#define NAT_TX2 3800
#define NAT_TW2 4680
#define NAT_PFD 300
#define NAT_XW 200
#define NAT_PK 3
namespace nat {

constexpr int kW = 224, kC = 192;
constexpr int kCtas = 132;
constexpr int kTilesPerCta = 6;
constexpr float kAlpha = 0.07216878364870322f * 1.4426950408889634f;
constexpr uint32_t kChunkBytes = 13 * 1024;
constexpr uint32_t kWChunk = 192 * 128;
constexpr uint32_t kWBytes = 3 * kWChunk;
constexpr uint32_t kW1Off = 6 * kChunkBytes;
constexpr uint32_t kW2Off = kW1Off + kWBytes;
constexpr uint32_t kXOff = kW2Off + kWChunk;
constexpr uint32_t kBarOff = kW2Off + kWBytes;
constexpr uint32_t kProfOff = kBarOff + 208;
constexpr uint32_t kSmemBytes = kBarOff + 1024;

static_assert(kW1Off % 1024 == 0 && kW2Off % 1024 == 0 && kChunkBytes % 1024 == 0, "swizzle alignment");
static_assert(kSmemBytes <= 232448, "smem");

constexpr uint32_t kEmpty = 0xFFFFFFFFu;
#define NAT_R8(v) v, v, v, v, v, v, v, v
#define NAT_R2K(v) NAT_R8(NAT_R8(NAT_R8(v))), NAT_R8(NAT_R8(NAT_R8(v))), NAT_R8(NAT_R8(NAT_R8(v))), NAT_R8(NAT_R8(NAT_R8(v)))
#define NAT_IMG NAT_R8(NAT_R2K(kEmpty)), NAT_R2K(kEmpty)
__device__ __align__(1024) uint32_t g_wimg32[3 * kWBytes / 4] = {NAT_IMG, NAT_IMG, NAT_IMG};
static_assert(kWBytes / 4 == 9 * 2048, "initialiser");
__device__ __align__(128) uint32_t g_flag[96];
__device__ __forceinline__ uint32_t w2_offset() {
  uint32_t v;
  asm volatile("ld.relaxed.gpu.global.u32 %0, [%1];" : "=r"(v) : "l"(g_flag + 64) : "memory");
  return (1 + v) * kWBytes;
}

#define PROFS(id, wgid, slotid) do { } while (0)
#define PROF(wgid, slotid) do { } while (0)
#define PROF_DUMP(wgid) do { } while (0)

#define GT(slotid) do { } while (0)
#define GT_DUMP() do { } while (0)

__device__ __forceinline__ uint32_t smem_u32(const void* p) { return (uint32_t)__cvta_generic_to_shared(p); }

__device__ __forceinline__ void mbar_init(uint32_t bar, uint32_t count) {
  asm volatile("mbarrier.init.shared::cta.b64 [%0], %1;" ::"r"(bar), "r"(count) : "memory");
}
__device__ __forceinline__ void mbar_arrive(uint32_t bar) {
  asm volatile("mbarrier.arrive.shared::cta.b64 _, [%0];" ::"r"(bar) : "memory");
}
__device__ __forceinline__ void mbar_arrive_expect_tx(uint32_t bar, uint32_t bytes) {
  asm volatile("mbarrier.arrive.expect_tx.shared::cta.b64 _, [%0], %1;" ::"r"(bar), "r"(bytes) : "memory");
}
__device__ __forceinline__ void mbar_wait(uint32_t bar, uint32_t parity) {
  uint32_t ok;
  uint32_t it = 0;
  do {
    asm volatile(
        "{\n.reg .pred p;\n"
        "mbarrier.try_wait.parity.shared::cta.b64 p, [%1], %2;\n"
        "selp.u32 %0, 1, 0, p;\n}\n"
        : "=r"(ok)
        : "r"(bar), "r"(parity)
        : "memory");
    if (++it > (1u << 24)) break;
  } while (!ok);
}
__device__ __forceinline__ uint32_t mbar_test(uint32_t bar, uint32_t parity) {
  uint32_t ok;
  asm volatile("{\n.reg .pred p;\nmbarrier.test_wait.parity.shared::cta.b64 p, [%1], %2;\nselp.u32 %0, 1, 0, p;\n}\n"
               : "=r"(ok) : "r"(bar), "r"(parity) : "memory");
  return ok;
}
__device__ __forceinline__ void mbar_wait_if(uint32_t ok, uint32_t bar, uint32_t parity) {
  if (!__all_sync(0xffffffffu, ok)) mbar_wait(bar, parity);
}
__device__ __forceinline__ bool elect_one() {
  uint32_t r;
  asm volatile("{\n.reg .pred p;\nelect.sync _|p, 0xffffffff;\nselp.u32 %0, 1, 0, p;\n}\n" : "=r"(r));
  return r != 0;
}
__device__ __forceinline__ void nb_arrive(int id) { asm volatile("bar.arrive %0, 256;" ::"r"(id) : "memory"); }
__device__ __forceinline__ void nb_sync(int id) { asm volatile("bar.sync %0, 256;" ::"r"(id) : "memory"); }
__device__ __forceinline__ void nb_arrive_p(int id) { asm volatile("bar.arrive %0, 160;" ::"r"(id) : "memory"); }
__device__ __forceinline__ void nb_sync_p(int id) { asm volatile("bar.sync %0, 160;" ::"r"(id) : "memory"); }
__device__ __forceinline__ void fence_proxy_async() { asm volatile("fence.proxy.async.shared::cta;" ::: "memory"); }

__device__ __forceinline__ void tma_load_5d(uint32_t dst, const CUtensorMap* map, uint32_t bar, int c0, int c1, int c2,
                                            int c3, int c4) {
  asm volatile(
      "cp.async.bulk.tensor.5d.shared::cluster.global.tile.mbarrier::complete_tx::bytes "
      "[%0], [%1, {%3, %4, %5, %6, %7}], [%2];"
      ::"r"(dst), "l"((uint64_t)map), "r"(bar), "r"(c0), "r"(c1), "r"(c2), "r"(c3), "r"(c4)
      : "memory");
}
__device__ __forceinline__ void bulk_load(uint32_t dst, const void* src, uint32_t bytes, uint32_t bar) {
  asm volatile("cp.async.bulk.shared::cluster.global.mbarrier::complete_tx::bytes [%0], [%1], %2, [%3];"
               ::"r"(dst), "l"((uint64_t)src), "r"(bytes), "r"(bar)
               : "memory");
}

__device__ __forceinline__ void wg_fence() { asm volatile("wgmma.fence.sync.aligned;" ::: "memory"); }
__device__ __forceinline__ void wg_commit() { asm volatile("wgmma.commit_group.sync.aligned;" ::: "memory"); }
template <int N>
__device__ __forceinline__ void wg_wait() { asm volatile("wgmma.wait_group.sync.aligned %0;" ::"n"(N) : "memory"); }

template <int N>
__device__ __forceinline__ void fence_regs(float (&d)[N]) {
#pragma unroll
  for (int i = 0; i < N; i++) asm volatile("" : "+f"(d[i])::"memory");
}
template <int N>
__device__ __forceinline__ void keep_regs(uint32_t (&d)[N]) {
#pragma unroll
  for (int i = 0; i < N; i++) asm volatile("" : "+r"(d[i])::"memory");
}

__device__ __forceinline__ uint32_t pack_bf16(float lo, float hi) {
  uint32_t d;
  asm("cvt.rn.bf16x2.f32 %0, %1, %2;" : "=r"(d) : "f"(hi), "f"(lo));
  return d;
}
__device__ __forceinline__ float ex2(float x) {
  float y;
  asm("ex2.approx.ftz.f32 %0, %1;" : "=f"(y) : "f"(x));
  return y;
}
__device__ __forceinline__ float rcp_approx(float x) {
  float y;
  asm("rcp.approx.ftz.f32 %0, %1;" : "=f"(y) : "f"(x));
  return y;
}
__device__ __forceinline__ uint4 ldg128_nc(const void* p) {
  uint4 v;
  asm volatile("ld.global.nc.v4.u32 {%0,%1,%2,%3}, [%4];" : "=r"(v.x), "=r"(v.y), "=r"(v.z), "=r"(v.w) : "l"(p));
  return v;
}
__device__ __forceinline__ void stg128(void* p, uint32_t a, uint32_t b, uint32_t c, uint32_t d) {
  asm volatile("st.global.v4.u32 [%0], {%1,%2,%3,%4};" ::"l"(p), "r"(a), "r"(b), "r"(c), "r"(d) : "memory");
}

__device__ __forceinline__ long long clk64() {
  long long c;
  asm volatile("mov.u64 %0, %clock64;" : "=l"(c)::"memory");
  return c;
}
__device__ __forceinline__ void sched_fence() { while (clk64() < 0) { } }

__device__ __forceinline__ uint64_t make_desc(uint32_t addr, uint32_t lbo, uint32_t sbo, uint32_t mode = 1) {
  return (uint64_t)((addr & 0x3FFFF) >> 4) | ((uint64_t)(lbo >> 4) << 16) | ((uint64_t)(sbo >> 4) << 32) |
         ((uint64_t)mode << 62);
}

template <int OFF, int NN>
__device__ __forceinline__ void wg_m192(float (&d)[NN], uint64_t desc_a, uint64_t desc_b, int scale_d) {
  asm volatile(
      "{\n.reg .pred p;\nsetp.ne.b32 p, %98, 0;\n"
      "wgmma.mma_async.sync.aligned.m64n192k16.f32.bf16.bf16 "
      "{%0,%1,%2,%3,%4,%5,%6,%7,%8,%9,%10,%11,%12,%13,%14,%15,"
      "%16,%17,%18,%19,%20,%21,%22,%23,%24,%25,%26,%27,%28,%29,%30,%31,"
      "%32,%33,%34,%35,%36,%37,%38,%39,%40,%41,%42,%43,%44,%45,%46,%47,"
      "%48,%49,%50,%51,%52,%53,%54,%55,%56,%57,%58,%59,%60,%61,%62,%63,"
      "%64,%65,%66,%67,%68,%69,%70,%71,%72,%73,%74,%75,%76,%77,%78,%79,"
      "%80,%81,%82,%83,%84,%85,%86,%87,%88,%89,%90,%91,%92,%93,%94,%95}, "
      "%96, %97, p, 1, 1, 0, 0;\n}\n"
      : "+f"(d[OFF + 0]), "+f"(d[OFF + 1]), "+f"(d[OFF + 2]), "+f"(d[OFF + 3]), "+f"(d[OFF + 4]), "+f"(d[OFF + 5]),
        "+f"(d[OFF + 6]), "+f"(d[OFF + 7]), "+f"(d[OFF + 8]), "+f"(d[OFF + 9]), "+f"(d[OFF + 10]), "+f"(d[OFF + 11]),
        "+f"(d[OFF + 12]), "+f"(d[OFF + 13]), "+f"(d[OFF + 14]), "+f"(d[OFF + 15]), "+f"(d[OFF + 16]), "+f"(d[OFF + 17]),
        "+f"(d[OFF + 18]), "+f"(d[OFF + 19]), "+f"(d[OFF + 20]), "+f"(d[OFF + 21]), "+f"(d[OFF + 22]), "+f"(d[OFF + 23]),
        "+f"(d[OFF + 24]), "+f"(d[OFF + 25]), "+f"(d[OFF + 26]), "+f"(d[OFF + 27]), "+f"(d[OFF + 28]), "+f"(d[OFF + 29]),
        "+f"(d[OFF + 30]), "+f"(d[OFF + 31]), "+f"(d[OFF + 32]), "+f"(d[OFF + 33]), "+f"(d[OFF + 34]), "+f"(d[OFF + 35]),
        "+f"(d[OFF + 36]), "+f"(d[OFF + 37]), "+f"(d[OFF + 38]), "+f"(d[OFF + 39]), "+f"(d[OFF + 40]), "+f"(d[OFF + 41]),
        "+f"(d[OFF + 42]), "+f"(d[OFF + 43]), "+f"(d[OFF + 44]), "+f"(d[OFF + 45]), "+f"(d[OFF + 46]), "+f"(d[OFF + 47]),
        "+f"(d[OFF + 48]), "+f"(d[OFF + 49]), "+f"(d[OFF + 50]), "+f"(d[OFF + 51]), "+f"(d[OFF + 52]), "+f"(d[OFF + 53]),
        "+f"(d[OFF + 54]), "+f"(d[OFF + 55]), "+f"(d[OFF + 56]), "+f"(d[OFF + 57]), "+f"(d[OFF + 58]), "+f"(d[OFF + 59]),
        "+f"(d[OFF + 60]), "+f"(d[OFF + 61]), "+f"(d[OFF + 62]), "+f"(d[OFF + 63]), "+f"(d[OFF + 64]), "+f"(d[OFF + 65]),
        "+f"(d[OFF + 66]), "+f"(d[OFF + 67]), "+f"(d[OFF + 68]), "+f"(d[OFF + 69]), "+f"(d[OFF + 70]), "+f"(d[OFF + 71]),
        "+f"(d[OFF + 72]), "+f"(d[OFF + 73]), "+f"(d[OFF + 74]), "+f"(d[OFF + 75]), "+f"(d[OFF + 76]), "+f"(d[OFF + 77]),
        "+f"(d[OFF + 78]), "+f"(d[OFF + 79]), "+f"(d[OFF + 80]), "+f"(d[OFF + 81]), "+f"(d[OFF + 82]), "+f"(d[OFF + 83]),
        "+f"(d[OFF + 84]), "+f"(d[OFF + 85]), "+f"(d[OFF + 86]), "+f"(d[OFF + 87]), "+f"(d[OFF + 88]), "+f"(d[OFF + 89]),
        "+f"(d[OFF + 90]), "+f"(d[OFF + 91]), "+f"(d[OFF + 92]), "+f"(d[OFF + 93]), "+f"(d[OFF + 94]), "+f"(d[OFF + 95])
      : "l"(desc_a), "l"(desc_b), "r"(scale_d));
}

template <int OFF, int NN>
__device__ __forceinline__ void wg_m192z(float (&d)[NN], uint64_t desc_a, uint64_t desc_b, int scale_d) {
  asm volatile(
      "{\n.reg .pred p;\nsetp.ne.b32 p, %98, 0;\n"
      "wgmma.mma_async.sync.aligned.m64n192k16.f32.bf16.bf16 "
      "{%0,%1,%2,%3,%4,%5,%6,%7,%8,%9,%10,%11,%12,%13,%14,%15,"
      "%16,%17,%18,%19,%20,%21,%22,%23,%24,%25,%26,%27,%28,%29,%30,%31,"
      "%32,%33,%34,%35,%36,%37,%38,%39,%40,%41,%42,%43,%44,%45,%46,%47,"
      "%48,%49,%50,%51,%52,%53,%54,%55,%56,%57,%58,%59,%60,%61,%62,%63,"
      "%64,%65,%66,%67,%68,%69,%70,%71,%72,%73,%74,%75,%76,%77,%78,%79,"
      "%80,%81,%82,%83,%84,%85,%86,%87,%88,%89,%90,%91,%92,%93,%94,%95}, "
      "%96, %97, p, 1, 1, 0, 0;\n}\n"
      : "=f"(d[OFF + 0]), "=f"(d[OFF + 1]), "=f"(d[OFF + 2]), "=f"(d[OFF + 3]), "=f"(d[OFF + 4]), "=f"(d[OFF + 5]),
        "=f"(d[OFF + 6]), "=f"(d[OFF + 7]), "=f"(d[OFF + 8]), "=f"(d[OFF + 9]), "=f"(d[OFF + 10]), "=f"(d[OFF + 11]),
        "=f"(d[OFF + 12]), "=f"(d[OFF + 13]), "=f"(d[OFF + 14]), "=f"(d[OFF + 15]), "=f"(d[OFF + 16]), "=f"(d[OFF + 17]),
        "=f"(d[OFF + 18]), "=f"(d[OFF + 19]), "=f"(d[OFF + 20]), "=f"(d[OFF + 21]), "=f"(d[OFF + 22]), "=f"(d[OFF + 23]),
        "=f"(d[OFF + 24]), "=f"(d[OFF + 25]), "=f"(d[OFF + 26]), "=f"(d[OFF + 27]), "=f"(d[OFF + 28]), "=f"(d[OFF + 29]),
        "=f"(d[OFF + 30]), "=f"(d[OFF + 31]), "=f"(d[OFF + 32]), "=f"(d[OFF + 33]), "=f"(d[OFF + 34]), "=f"(d[OFF + 35]),
        "=f"(d[OFF + 36]), "=f"(d[OFF + 37]), "=f"(d[OFF + 38]), "=f"(d[OFF + 39]), "=f"(d[OFF + 40]), "=f"(d[OFF + 41]),
        "=f"(d[OFF + 42]), "=f"(d[OFF + 43]), "=f"(d[OFF + 44]), "=f"(d[OFF + 45]), "=f"(d[OFF + 46]), "=f"(d[OFF + 47]),
        "=f"(d[OFF + 48]), "=f"(d[OFF + 49]), "=f"(d[OFF + 50]), "=f"(d[OFF + 51]), "=f"(d[OFF + 52]), "=f"(d[OFF + 53]),
        "=f"(d[OFF + 54]), "=f"(d[OFF + 55]), "=f"(d[OFF + 56]), "=f"(d[OFF + 57]), "=f"(d[OFF + 58]), "=f"(d[OFF + 59]),
        "=f"(d[OFF + 60]), "=f"(d[OFF + 61]), "=f"(d[OFF + 62]), "=f"(d[OFF + 63]), "=f"(d[OFF + 64]), "=f"(d[OFF + 65]),
        "=f"(d[OFF + 66]), "=f"(d[OFF + 67]), "=f"(d[OFF + 68]), "=f"(d[OFF + 69]), "=f"(d[OFF + 70]), "=f"(d[OFF + 71]),
        "=f"(d[OFF + 72]), "=f"(d[OFF + 73]), "=f"(d[OFF + 74]), "=f"(d[OFF + 75]), "=f"(d[OFF + 76]), "=f"(d[OFF + 77]),
        "=f"(d[OFF + 78]), "=f"(d[OFF + 79]), "=f"(d[OFF + 80]), "=f"(d[OFF + 81]), "=f"(d[OFF + 82]), "=f"(d[OFF + 83]),
        "=f"(d[OFF + 84]), "=f"(d[OFF + 85]), "=f"(d[OFF + 86]), "=f"(d[OFF + 87]), "=f"(d[OFF + 88]), "=f"(d[OFF + 89]),
        "=f"(d[OFF + 90]), "=f"(d[OFF + 91]), "=f"(d[OFF + 92]), "=f"(d[OFF + 93]), "=f"(d[OFF + 94]), "=f"(d[OFF + 95])
      : "l"(desc_a), "l"(desc_b), "r"(scale_d));
}

template <int OFF, int NN>
__device__ __forceinline__ void wg_m64t(float (&d)[NN], uint64_t desc_a, uint64_t desc_b, int scale_d) {
  asm volatile(
      "{\n.reg .pred p;\nsetp.ne.b32 p, %34, 0;\n"
      "wgmma.mma_async.sync.aligned.m64n64k16.f32.bf16.bf16 "
      "{%0,%1,%2,%3,%4,%5,%6,%7,%8,%9,%10,%11,%12,%13,%14,%15,"
      "%16,%17,%18,%19,%20,%21,%22,%23,%24,%25,%26,%27,%28,%29,%30,%31}, "
      "%32, %33, p, 1, 1, 0, 1;\n}\n"
      : "+f"(d[OFF + 0]), "+f"(d[OFF + 1]), "+f"(d[OFF + 2]), "+f"(d[OFF + 3]), "+f"(d[OFF + 4]), "+f"(d[OFF + 5]),
        "+f"(d[OFF + 6]), "+f"(d[OFF + 7]), "+f"(d[OFF + 8]), "+f"(d[OFF + 9]), "+f"(d[OFF + 10]), "+f"(d[OFF + 11]),
        "+f"(d[OFF + 12]), "+f"(d[OFF + 13]), "+f"(d[OFF + 14]), "+f"(d[OFF + 15]), "+f"(d[OFF + 16]), "+f"(d[OFF + 17]),
        "+f"(d[OFF + 18]), "+f"(d[OFF + 19]), "+f"(d[OFF + 20]), "+f"(d[OFF + 21]), "+f"(d[OFF + 22]), "+f"(d[OFF + 23]),
        "+f"(d[OFF + 24]), "+f"(d[OFF + 25]), "+f"(d[OFF + 26]), "+f"(d[OFF + 27]), "+f"(d[OFF + 28]), "+f"(d[OFF + 29]),
        "+f"(d[OFF + 30]), "+f"(d[OFF + 31])
      : "l"(desc_a), "l"(desc_b), "r"(scale_d));
}

template <int OFF, int NN>
__device__ __forceinline__ void wg_m64tz(float (&d)[NN], uint64_t desc_a, uint64_t desc_b, int scale_d) {
  asm volatile(
      "{\n.reg .pred p;\nsetp.ne.b32 p, %34, 0;\n"
      "wgmma.mma_async.sync.aligned.m64n64k16.f32.bf16.bf16 "
      "{%0,%1,%2,%3,%4,%5,%6,%7,%8,%9,%10,%11,%12,%13,%14,%15,"
      "%16,%17,%18,%19,%20,%21,%22,%23,%24,%25,%26,%27,%28,%29,%30,%31}, "
      "%32, %33, p, 1, 1, 0, 1;\n}\n"
      : "=f"(d[OFF + 0]), "=f"(d[OFF + 1]), "=f"(d[OFF + 2]), "=f"(d[OFF + 3]), "=f"(d[OFF + 4]), "=f"(d[OFF + 5]),
        "=f"(d[OFF + 6]), "=f"(d[OFF + 7]), "=f"(d[OFF + 8]), "=f"(d[OFF + 9]), "=f"(d[OFF + 10]), "=f"(d[OFF + 11]),
        "=f"(d[OFF + 12]), "=f"(d[OFF + 13]), "=f"(d[OFF + 14]), "=f"(d[OFF + 15]), "=f"(d[OFF + 16]), "=f"(d[OFF + 17]),
        "=f"(d[OFF + 18]), "=f"(d[OFF + 19]), "=f"(d[OFF + 20]), "=f"(d[OFF + 21]), "=f"(d[OFF + 22]), "=f"(d[OFF + 23]),
        "=f"(d[OFF + 24]), "=f"(d[OFF + 25]), "=f"(d[OFF + 26]), "=f"(d[OFF + 27]), "=f"(d[OFF + 28]), "=f"(d[OFF + 29]),
        "=f"(d[OFF + 30]), "=f"(d[OFF + 31])
      : "l"(desc_a), "l"(desc_b), "r"(scale_d));
}

template <int OFF, int NN>
__device__ __forceinline__ void wg_d96(float (&d)[NN], uint32_t a0, uint32_t a1, uint32_t a2, uint32_t a3,
                                       uint64_t desc_b, int scale_d) {
  asm volatile(
      "{\n.reg .pred p;\nsetp.ne.b32 p, %53, 0;\n"
      "wgmma.mma_async.sync.aligned.m64n96k16.f32.bf16.bf16 "
      "{%0,%1,%2,%3,%4,%5,%6,%7,%8,%9,%10,%11,%12,%13,%14,%15,"
      "%16,%17,%18,%19,%20,%21,%22,%23,%24,%25,%26,%27,%28,%29,%30,%31,"
      "%32,%33,%34,%35,%36,%37,%38,%39,%40,%41,%42,%43,%44,%45,%46,%47}, "
      "{%48,%49,%50,%51}, %52, p, 1, 1, 0;\n}\n"
      : "+f"(d[OFF + 0]), "+f"(d[OFF + 1]), "+f"(d[OFF + 2]), "+f"(d[OFF + 3]), "+f"(d[OFF + 4]), "+f"(d[OFF + 5]),
        "+f"(d[OFF + 6]), "+f"(d[OFF + 7]), "+f"(d[OFF + 8]), "+f"(d[OFF + 9]), "+f"(d[OFF + 10]), "+f"(d[OFF + 11]),
        "+f"(d[OFF + 12]), "+f"(d[OFF + 13]), "+f"(d[OFF + 14]), "+f"(d[OFF + 15]), "+f"(d[OFF + 16]), "+f"(d[OFF + 17]),
        "+f"(d[OFF + 18]), "+f"(d[OFF + 19]), "+f"(d[OFF + 20]), "+f"(d[OFF + 21]), "+f"(d[OFF + 22]), "+f"(d[OFF + 23]),
        "+f"(d[OFF + 24]), "+f"(d[OFF + 25]), "+f"(d[OFF + 26]), "+f"(d[OFF + 27]), "+f"(d[OFF + 28]), "+f"(d[OFF + 29]),
        "+f"(d[OFF + 30]), "+f"(d[OFF + 31]), "+f"(d[OFF + 32]), "+f"(d[OFF + 33]), "+f"(d[OFF + 34]), "+f"(d[OFF + 35]),
        "+f"(d[OFF + 36]), "+f"(d[OFF + 37]), "+f"(d[OFF + 38]), "+f"(d[OFF + 39]), "+f"(d[OFF + 40]), "+f"(d[OFF + 41]),
        "+f"(d[OFF + 42]), "+f"(d[OFF + 43]), "+f"(d[OFF + 44]), "+f"(d[OFF + 45]), "+f"(d[OFF + 46]), "+f"(d[OFF + 47])
      : "r"(a0), "r"(a1), "r"(a2), "r"(a3), "l"(desc_b), "r"(scale_d));
}

template <int OFF, int NN>
__device__ __forceinline__ void wg_d96z(float (&d)[NN], uint32_t a0, uint32_t a1, uint32_t a2, uint32_t a3,
                                       uint64_t desc_b, int scale_d) {
  asm volatile(
      "{\n.reg .pred p;\nsetp.ne.b32 p, %53, 0;\n"
      "wgmma.mma_async.sync.aligned.m64n96k16.f32.bf16.bf16 "
      "{%0,%1,%2,%3,%4,%5,%6,%7,%8,%9,%10,%11,%12,%13,%14,%15,"
      "%16,%17,%18,%19,%20,%21,%22,%23,%24,%25,%26,%27,%28,%29,%30,%31,"
      "%32,%33,%34,%35,%36,%37,%38,%39,%40,%41,%42,%43,%44,%45,%46,%47}, "
      "{%48,%49,%50,%51}, %52, p, 1, 1, 0;\n}\n"
      : "=f"(d[OFF + 0]), "=f"(d[OFF + 1]), "=f"(d[OFF + 2]), "=f"(d[OFF + 3]), "=f"(d[OFF + 4]), "=f"(d[OFF + 5]),
        "=f"(d[OFF + 6]), "=f"(d[OFF + 7]), "=f"(d[OFF + 8]), "=f"(d[OFF + 9]), "=f"(d[OFF + 10]), "=f"(d[OFF + 11]),
        "=f"(d[OFF + 12]), "=f"(d[OFF + 13]), "=f"(d[OFF + 14]), "=f"(d[OFF + 15]), "=f"(d[OFF + 16]), "=f"(d[OFF + 17]),
        "=f"(d[OFF + 18]), "=f"(d[OFF + 19]), "=f"(d[OFF + 20]), "=f"(d[OFF + 21]), "=f"(d[OFF + 22]), "=f"(d[OFF + 23]),
        "=f"(d[OFF + 24]), "=f"(d[OFF + 25]), "=f"(d[OFF + 26]), "=f"(d[OFF + 27]), "=f"(d[OFF + 28]), "=f"(d[OFF + 29]),
        "=f"(d[OFF + 30]), "=f"(d[OFF + 31]), "=f"(d[OFF + 32]), "=f"(d[OFF + 33]), "=f"(d[OFF + 34]), "=f"(d[OFF + 35]),
        "=f"(d[OFF + 36]), "=f"(d[OFF + 37]), "=f"(d[OFF + 38]), "=f"(d[OFF + 39]), "=f"(d[OFF + 40]), "=f"(d[OFF + 41]),
        "=f"(d[OFF + 42]), "=f"(d[OFF + 43]), "=f"(d[OFF + 44]), "=f"(d[OFF + 45]), "=f"(d[OFF + 46]), "=f"(d[OFF + 47])
      : "r"(a0), "r"(a1), "r"(a2), "r"(a3), "l"(desc_b), "r"(scale_d));
}

template <int OFF, int NN>
__device__ __forceinline__ void wg_s104(float (&d)[NN], uint32_t a0, uint32_t a1, uint32_t a2, uint32_t a3,
                                       uint64_t desc_b, int scale_d, uint32_t meta) {
  asm volatile(
      "{\n.reg .pred p;\nsetp.ne.b32 p, %57, 0;\n"
      "wgmma.mma_async.sp.sync.aligned.m64n104k32.f32.bf16.bf16 "
      "{%0,%1,%2,%3,%4,%5,%6,%7,%8,%9,%10,%11,%12,%13,%14,%15,"
      "%16,%17,%18,%19,%20,%21,%22,%23,%24,%25,%26,%27,%28,%29,%30,%31,"
      "%32,%33,%34,%35,%36,%37,%38,%39,%40,%41,%42,%43,%44,%45,%46,%47,"
      "%48,%49,%50,%51}, "
      "{%52,%53,%54,%55}, %56, %58, 0, p, 1, 1, 0;\n}\n"
      : "+f"(d[OFF + 0]), "+f"(d[OFF + 1]), "+f"(d[OFF + 2]), "+f"(d[OFF + 3]), "+f"(d[OFF + 4]), "+f"(d[OFF + 5]),
        "+f"(d[OFF + 6]), "+f"(d[OFF + 7]), "+f"(d[OFF + 8]), "+f"(d[OFF + 9]), "+f"(d[OFF + 10]), "+f"(d[OFF + 11]),
        "+f"(d[OFF + 12]), "+f"(d[OFF + 13]), "+f"(d[OFF + 14]), "+f"(d[OFF + 15]), "+f"(d[OFF + 16]), "+f"(d[OFF + 17]),
        "+f"(d[OFF + 18]), "+f"(d[OFF + 19]), "+f"(d[OFF + 20]), "+f"(d[OFF + 21]), "+f"(d[OFF + 22]), "+f"(d[OFF + 23]),
        "+f"(d[OFF + 24]), "+f"(d[OFF + 25]), "+f"(d[OFF + 26]), "+f"(d[OFF + 27]), "+f"(d[OFF + 28]), "+f"(d[OFF + 29]),
        "+f"(d[OFF + 30]), "+f"(d[OFF + 31]), "+f"(d[OFF + 32]), "+f"(d[OFF + 33]), "+f"(d[OFF + 34]), "+f"(d[OFF + 35]),
        "+f"(d[OFF + 36]), "+f"(d[OFF + 37]), "+f"(d[OFF + 38]), "+f"(d[OFF + 39]), "+f"(d[OFF + 40]), "+f"(d[OFF + 41]),
        "+f"(d[OFF + 42]), "+f"(d[OFF + 43]), "+f"(d[OFF + 44]), "+f"(d[OFF + 45]), "+f"(d[OFF + 46]), "+f"(d[OFF + 47]),
        "+f"(d[OFF + 48]), "+f"(d[OFF + 49]), "+f"(d[OFF + 50]), "+f"(d[OFF + 51])
      : "r"(a0), "r"(a1), "r"(a2), "r"(a3), "l"(desc_b), "r"(scale_d), "r"(meta));
}

template <int OFF, int NN>
__device__ __forceinline__ void wg_s104z(float (&d)[NN], uint32_t a0, uint32_t a1, uint32_t a2, uint32_t a3,
                                       uint64_t desc_b, int scale_d, uint32_t meta) {
  asm volatile(
      "{\n.reg .pred p;\nsetp.ne.b32 p, %57, 0;\n"
      "wgmma.mma_async.sp.sync.aligned.m64n104k32.f32.bf16.bf16 "
      "{%0,%1,%2,%3,%4,%5,%6,%7,%8,%9,%10,%11,%12,%13,%14,%15,"
      "%16,%17,%18,%19,%20,%21,%22,%23,%24,%25,%26,%27,%28,%29,%30,%31,"
      "%32,%33,%34,%35,%36,%37,%38,%39,%40,%41,%42,%43,%44,%45,%46,%47,"
      "%48,%49,%50,%51}, "
      "{%52,%53,%54,%55}, %56, %58, 0, p, 1, 1, 0;\n}\n"
      : "=f"(d[OFF + 0]), "=f"(d[OFF + 1]), "=f"(d[OFF + 2]), "=f"(d[OFF + 3]), "=f"(d[OFF + 4]), "=f"(d[OFF + 5]),
        "=f"(d[OFF + 6]), "=f"(d[OFF + 7]), "=f"(d[OFF + 8]), "=f"(d[OFF + 9]), "=f"(d[OFF + 10]), "=f"(d[OFF + 11]),
        "=f"(d[OFF + 12]), "=f"(d[OFF + 13]), "=f"(d[OFF + 14]), "=f"(d[OFF + 15]), "=f"(d[OFF + 16]), "=f"(d[OFF + 17]),
        "=f"(d[OFF + 18]), "=f"(d[OFF + 19]), "=f"(d[OFF + 20]), "=f"(d[OFF + 21]), "=f"(d[OFF + 22]), "=f"(d[OFF + 23]),
        "=f"(d[OFF + 24]), "=f"(d[OFF + 25]), "=f"(d[OFF + 26]), "=f"(d[OFF + 27]), "=f"(d[OFF + 28]), "=f"(d[OFF + 29]),
        "=f"(d[OFF + 30]), "=f"(d[OFF + 31]), "=f"(d[OFF + 32]), "=f"(d[OFF + 33]), "=f"(d[OFF + 34]), "=f"(d[OFF + 35]),
        "=f"(d[OFF + 36]), "=f"(d[OFF + 37]), "=f"(d[OFF + 38]), "=f"(d[OFF + 39]), "=f"(d[OFF + 40]), "=f"(d[OFF + 41]),
        "=f"(d[OFF + 42]), "=f"(d[OFF + 43]), "=f"(d[OFF + 44]), "=f"(d[OFF + 45]), "=f"(d[OFF + 46]), "=f"(d[OFF + 47]),
        "=f"(d[OFF + 48]), "=f"(d[OFF + 49]), "=f"(d[OFF + 50]), "=f"(d[OFF + 51])
      : "r"(a0), "r"(a1), "r"(a2), "r"(a3), "l"(desc_b), "r"(scale_d), "r"(meta));
}

template <int OFF, int NN>
__device__ __forceinline__ void wg_s48(float (&d)[NN], uint32_t a0, uint32_t a1, uint32_t a2, uint32_t a3,
                                       uint64_t desc_b, int scale_d, uint32_t meta) {
  asm volatile(
      "{\n.reg .pred p;\nsetp.ne.b32 p, %29, 0;\n"
      "wgmma.mma_async.sp.sync.aligned.m64n48k32.f32.bf16.bf16 "
      "{%0,%1,%2,%3,%4,%5,%6,%7,%8,%9,%10,%11,%12,%13,%14,%15,"
      "%16,%17,%18,%19,%20,%21,%22,%23}, "
      "{%24,%25,%26,%27}, %28, %30, 0, p, 1, 1, 0;\n}\n"
      : "+f"(d[OFF + 0]), "+f"(d[OFF + 1]), "+f"(d[OFF + 2]), "+f"(d[OFF + 3]), "+f"(d[OFF + 4]), "+f"(d[OFF + 5]),
        "+f"(d[OFF + 6]), "+f"(d[OFF + 7]), "+f"(d[OFF + 8]), "+f"(d[OFF + 9]), "+f"(d[OFF + 10]), "+f"(d[OFF + 11]),
        "+f"(d[OFF + 12]), "+f"(d[OFF + 13]), "+f"(d[OFF + 14]), "+f"(d[OFF + 15]), "+f"(d[OFF + 16]), "+f"(d[OFF + 17]),
        "+f"(d[OFF + 18]), "+f"(d[OFF + 19]), "+f"(d[OFF + 20]), "+f"(d[OFF + 21]), "+f"(d[OFF + 22]), "+f"(d[OFF + 23])
      : "r"(a0), "r"(a1), "r"(a2), "r"(a3), "l"(desc_b), "r"(scale_d), "r"(meta));
}

template <int OFF, int NN>
__device__ __forceinline__ void wg_s48z(float (&d)[NN], uint32_t a0, uint32_t a1, uint32_t a2, uint32_t a3,
                                       uint64_t desc_b, int scale_d, uint32_t meta) {
  asm volatile(
      "{\n.reg .pred p;\nsetp.ne.b32 p, %29, 0;\n"
      "wgmma.mma_async.sp.sync.aligned.m64n48k32.f32.bf16.bf16 "
      "{%0,%1,%2,%3,%4,%5,%6,%7,%8,%9,%10,%11,%12,%13,%14,%15,"
      "%16,%17,%18,%19,%20,%21,%22,%23}, "
      "{%24,%25,%26,%27}, %28, %30, 0, p, 1, 1, 0;\n}\n"
      : "=f"(d[OFF + 0]), "=f"(d[OFF + 1]), "=f"(d[OFF + 2]), "=f"(d[OFF + 3]), "=f"(d[OFF + 4]), "=f"(d[OFF + 5]),
        "=f"(d[OFF + 6]), "=f"(d[OFF + 7]), "=f"(d[OFF + 8]), "=f"(d[OFF + 9]), "=f"(d[OFF + 10]), "=f"(d[OFF + 11]),
        "=f"(d[OFF + 12]), "=f"(d[OFF + 13]), "=f"(d[OFF + 14]), "=f"(d[OFF + 15]), "=f"(d[OFF + 16]), "=f"(d[OFF + 17]),
        "=f"(d[OFF + 18]), "=f"(d[OFF + 19]), "=f"(d[OFF + 20]), "=f"(d[OFF + 21]), "=f"(d[OFF + 22]), "=f"(d[OFF + 23])
      : "r"(a0), "r"(a1), "r"(a2), "r"(a3), "l"(desc_b), "r"(scale_d), "r"(meta));
}

template <int OFF, int NN>
__device__ __forceinline__ void wg_s56(float (&d)[NN], uint32_t a0, uint32_t a1, uint32_t a2, uint32_t a3,
                                       uint64_t desc_b, int scale_d, uint32_t meta) {
  asm volatile(
      "{\n.reg .pred p;\nsetp.ne.b32 p, %33, 0;\n"
      "wgmma.mma_async.sp.sync.aligned.m64n56k32.f32.bf16.bf16 "
      "{%0,%1,%2,%3,%4,%5,%6,%7,%8,%9,%10,%11,%12,%13,%14,%15,"
      "%16,%17,%18,%19,%20,%21,%22,%23,%24,%25,%26,%27}, "
      "{%28,%29,%30,%31}, %32, %34, 0, p, 1, 1, 0;\n}\n"
      : "+f"(d[OFF + 0]), "+f"(d[OFF + 1]), "+f"(d[OFF + 2]), "+f"(d[OFF + 3]), "+f"(d[OFF + 4]), "+f"(d[OFF + 5]),
        "+f"(d[OFF + 6]), "+f"(d[OFF + 7]), "+f"(d[OFF + 8]), "+f"(d[OFF + 9]), "+f"(d[OFF + 10]), "+f"(d[OFF + 11]),
        "+f"(d[OFF + 12]), "+f"(d[OFF + 13]), "+f"(d[OFF + 14]), "+f"(d[OFF + 15]), "+f"(d[OFF + 16]), "+f"(d[OFF + 17]),
        "+f"(d[OFF + 18]), "+f"(d[OFF + 19]), "+f"(d[OFF + 20]), "+f"(d[OFF + 21]), "+f"(d[OFF + 22]), "+f"(d[OFF + 23]),
        "+f"(d[OFF + 24]), "+f"(d[OFF + 25]), "+f"(d[OFF + 26]), "+f"(d[OFF + 27])
      : "r"(a0), "r"(a1), "r"(a2), "r"(a3), "l"(desc_b), "r"(scale_d), "r"(meta));
}

template <int OFF, int NN>
__device__ __forceinline__ void wg_s56z(float (&d)[NN], uint32_t a0, uint32_t a1, uint32_t a2, uint32_t a3,
                                       uint64_t desc_b, int scale_d, uint32_t meta) {
  asm volatile(
      "{\n.reg .pred p;\nsetp.ne.b32 p, %33, 0;\n"
      "wgmma.mma_async.sp.sync.aligned.m64n56k32.f32.bf16.bf16 "
      "{%0,%1,%2,%3,%4,%5,%6,%7,%8,%9,%10,%11,%12,%13,%14,%15,"
      "%16,%17,%18,%19,%20,%21,%22,%23,%24,%25,%26,%27}, "
      "{%28,%29,%30,%31}, %32, %34, 0, p, 1, 1, 0;\n}\n"
      : "=f"(d[OFF + 0]), "=f"(d[OFF + 1]), "=f"(d[OFF + 2]), "=f"(d[OFF + 3]), "=f"(d[OFF + 4]), "=f"(d[OFF + 5]),
        "=f"(d[OFF + 6]), "=f"(d[OFF + 7]), "=f"(d[OFF + 8]), "=f"(d[OFF + 9]), "=f"(d[OFF + 10]), "=f"(d[OFF + 11]),
        "=f"(d[OFF + 12]), "=f"(d[OFF + 13]), "=f"(d[OFF + 14]), "=f"(d[OFF + 15]), "=f"(d[OFF + 16]), "=f"(d[OFF + 17]),
        "=f"(d[OFF + 18]), "=f"(d[OFF + 19]), "=f"(d[OFF + 20]), "=f"(d[OFF + 21]), "=f"(d[OFF + 22]), "=f"(d[OFF + 23]),
        "=f"(d[OFF + 24]), "=f"(d[OFF + 25]), "=f"(d[OFF + 26]), "=f"(d[OFF + 27])
      : "r"(a0), "r"(a1), "r"(a2), "r"(a3), "l"(desc_b), "r"(scale_d), "r"(meta));
}

template <int OFF, int NN>
__device__ __forceinline__ void wg_s64t(float (&d)[NN], uint32_t a0, uint32_t a1, uint32_t a2, uint32_t a3,
                                       uint64_t desc_b, int scale_d, uint32_t meta) {
  asm volatile(
      "{\n.reg .pred p;\nsetp.ne.b32 p, %37, 0;\n"
      "wgmma.mma_async.sp.sync.aligned.m64n64k32.f32.bf16.bf16 "
      "{%0,%1,%2,%3,%4,%5,%6,%7,%8,%9,%10,%11,%12,%13,%14,%15,"
      "%16,%17,%18,%19,%20,%21,%22,%23,%24,%25,%26,%27,%28,%29,%30,%31}, "
      "{%32,%33,%34,%35}, %36, %38, 0, p, 1, 1, 1;\n}\n"
      : "+f"(d[OFF + 0]), "+f"(d[OFF + 1]), "+f"(d[OFF + 2]), "+f"(d[OFF + 3]), "+f"(d[OFF + 4]), "+f"(d[OFF + 5]),
        "+f"(d[OFF + 6]), "+f"(d[OFF + 7]), "+f"(d[OFF + 8]), "+f"(d[OFF + 9]), "+f"(d[OFF + 10]), "+f"(d[OFF + 11]),
        "+f"(d[OFF + 12]), "+f"(d[OFF + 13]), "+f"(d[OFF + 14]), "+f"(d[OFF + 15]), "+f"(d[OFF + 16]), "+f"(d[OFF + 17]),
        "+f"(d[OFF + 18]), "+f"(d[OFF + 19]), "+f"(d[OFF + 20]), "+f"(d[OFF + 21]), "+f"(d[OFF + 22]), "+f"(d[OFF + 23]),
        "+f"(d[OFF + 24]), "+f"(d[OFF + 25]), "+f"(d[OFF + 26]), "+f"(d[OFF + 27]), "+f"(d[OFF + 28]), "+f"(d[OFF + 29]),
        "+f"(d[OFF + 30]), "+f"(d[OFF + 31])
      : "r"(a0), "r"(a1), "r"(a2), "r"(a3), "l"(desc_b), "r"(scale_d), "r"(meta));
}

template <int OFF, int NN>
__device__ __forceinline__ void wg_s64t1(float (&d)[NN], uint32_t a0, uint32_t a1, uint32_t a2, uint32_t a3,
                                       uint64_t desc_b, int scale_d, uint32_t meta) {
  asm volatile(
      "{\n.reg .pred p;\nsetp.ne.b32 p, %37, 0;\n"
      "wgmma.mma_async.sp.sync.aligned.m64n64k32.f32.bf16.bf16 "
      "{%0,%1,%2,%3,%4,%5,%6,%7,%8,%9,%10,%11,%12,%13,%14,%15,"
      "%16,%17,%18,%19,%20,%21,%22,%23,%24,%25,%26,%27,%28,%29,%30,%31}, "
      "{%32,%33,%34,%35}, %36, %38, 1, p, 1, 1, 1;\n}\n"
      : "+f"(d[OFF + 0]), "+f"(d[OFF + 1]), "+f"(d[OFF + 2]), "+f"(d[OFF + 3]), "+f"(d[OFF + 4]), "+f"(d[OFF + 5]),
        "+f"(d[OFF + 6]), "+f"(d[OFF + 7]), "+f"(d[OFF + 8]), "+f"(d[OFF + 9]), "+f"(d[OFF + 10]), "+f"(d[OFF + 11]),
        "+f"(d[OFF + 12]), "+f"(d[OFF + 13]), "+f"(d[OFF + 14]), "+f"(d[OFF + 15]), "+f"(d[OFF + 16]), "+f"(d[OFF + 17]),
        "+f"(d[OFF + 18]), "+f"(d[OFF + 19]), "+f"(d[OFF + 20]), "+f"(d[OFF + 21]), "+f"(d[OFF + 22]), "+f"(d[OFF + 23]),
        "+f"(d[OFF + 24]), "+f"(d[OFF + 25]), "+f"(d[OFF + 26]), "+f"(d[OFF + 27]), "+f"(d[OFF + 28]), "+f"(d[OFF + 29]),
        "+f"(d[OFF + 30]), "+f"(d[OFF + 31])
      : "r"(a0), "r"(a1), "r"(a2), "r"(a3), "l"(desc_b), "r"(scale_d), "r"(meta));
}

template <int OFF, int NN>
__device__ __forceinline__ void wg_s64tz(float (&d)[NN], uint32_t a0, uint32_t a1, uint32_t a2, uint32_t a3,
                                       uint64_t desc_b, int scale_d, uint32_t meta) {
  asm volatile(
      "{\n.reg .pred p;\nsetp.ne.b32 p, %37, 0;\n"
      "wgmma.mma_async.sp.sync.aligned.m64n64k32.f32.bf16.bf16 "
      "{%0,%1,%2,%3,%4,%5,%6,%7,%8,%9,%10,%11,%12,%13,%14,%15,"
      "%16,%17,%18,%19,%20,%21,%22,%23,%24,%25,%26,%27,%28,%29,%30,%31}, "
      "{%32,%33,%34,%35}, %36, %38, 0, p, 1, 1, 1;\n}\n"
      : "=f"(d[OFF + 0]), "=f"(d[OFF + 1]), "=f"(d[OFF + 2]), "=f"(d[OFF + 3]), "=f"(d[OFF + 4]), "=f"(d[OFF + 5]),
        "=f"(d[OFF + 6]), "=f"(d[OFF + 7]), "=f"(d[OFF + 8]), "=f"(d[OFF + 9]), "=f"(d[OFF + 10]), "=f"(d[OFF + 11]),
        "=f"(d[OFF + 12]), "=f"(d[OFF + 13]), "=f"(d[OFF + 14]), "=f"(d[OFF + 15]), "=f"(d[OFF + 16]), "=f"(d[OFF + 17]),
        "=f"(d[OFF + 18]), "=f"(d[OFF + 19]), "=f"(d[OFF + 20]), "=f"(d[OFF + 21]), "=f"(d[OFF + 22]), "=f"(d[OFF + 23]),
        "=f"(d[OFF + 24]), "=f"(d[OFF + 25]), "=f"(d[OFF + 26]), "=f"(d[OFF + 27]), "=f"(d[OFF + 28]), "=f"(d[OFF + 29]),
        "=f"(d[OFF + 30]), "=f"(d[OFF + 31])
      : "r"(a0), "r"(a1), "r"(a2), "r"(a3), "l"(desc_b), "r"(scale_d), "r"(meta));
}

__device__ __forceinline__ int g2_inv(int ch) { return 32 * (ch >> 5) + 8 * ((ch >> 1) & 3) + 2 * ((ch >> 3) & 3) + (ch & 1); }
__host__ __device__ __forceinline__ uint32_t wimg_off(int n, int k) {
  return (uint32_t)(k >> 6) * kWChunk + (uint32_t)n * 128 + (uint32_t)((((k & 63) >> 3) ^ (n & 7)) << 4) + (k & 7) * 2;
}
__host__ __device__ constexpr int w2piece(int h, int c) { return c == 2 ? 2 + h : 4 * h + c; }
__device__ __forceinline__ uint32_t w2img_off(int n, int k) { return wimg_off(n % 96, k & 63) + w2piece(n >= 96, k >> 6) * (kWChunk / 2); }
__device__ __forceinline__ int qpix(int par, int t) {
  const int a = 2 * t + 13 * par - 6, b = t + 112 * par;
  return par ? min(a, b) : max(a, b);
}
__device__ __forceinline__ int woff(int par, int i, int r) {
  const int a = 99 * par + 6 - 8 * i;
  return par ? min(r, a) : max(r, a);
}

__device__ __forceinline__ void mma16816(float (&c)[4], uint32_t a0, uint32_t a1, uint32_t a2, uint32_t a3, uint32_t b0,
                                         uint32_t b1) {
  asm volatile(
      "mma.sync.aligned.m16n8k16.row.col.f32.bf16.bf16.f32 {%0,%1,%2,%3}, {%4,%5,%6,%7}, {%8,%9}, {%0,%1,%2,%3};"
      : "+f"(c[0]), "+f"(c[1]), "+f"(c[2]), "+f"(c[3])
      : "r"(a0), "r"(a1), "r"(a2), "r"(a3), "r"(b0), "r"(b1));
}

__device__ __forceinline__ void fold_w1(const int u, const __nv_bfloat16* __restrict__ wqkv, uint8_t* wimg) {
  const int g = (threadIdx.x >> 2) & 7, l = threadIdx.x & 3;
  const int m0 = (u / 12) * 16, s = u % 12;
  uint4 A[12], B[12];
  const __nv_bfloat16* arow = wqkv + (m0 + 4 * (g >> 1) + (g & 1)) * 576 + 192 + 8 * l;
  const __nv_bfloat16* brow = wqkv + (16 * s + 4 * (g >> 1) + (g & 1)) * 576 + 8 * l;
#pragma unroll
  for (int i = 0; i < 12; i++) {
    A[i] = ldg128_nc(arow + (i & 1) * 2 * 576 + 32 * (i >> 1));
    B[i] = ldg128_nc(brow + (i & 1) * 2 * 576 + 32 * (i >> 1));
  }
  sched_fence();
  uint8_t* dst = wimg + wimg_off(m0 + g, 16 * s + 4 * l);
  float acc[4][4];
#pragma unroll
  for (int j = 0; j < 16; j++) acc[j >> 2][j & 3] = 0.f;
#pragma unroll
  for (int i = 0; i < 6; i++) {
    const uint4 &a0 = A[2 * i], &a1 = A[2 * i + 1];
#pragma unroll
    for (int nb = 0; nb < 2; nb++) {
      mma16816(acc[2 * nb], a0.x, a1.x, a0.y, a1.y, B[2 * i + nb].x, B[2 * i + nb].y);
      mma16816(acc[2 * nb + 1], a0.z, a1.z, a0.w, a1.w, B[2 * i + nb].z, B[2 * i + nb].w);
    }
  }
#pragma unroll
  for (int j = 0; j < 2; j++) {
    const uint2 v = make_uint2(pack_bf16((acc[0][2 * j] + acc[1][2 * j]) * kAlpha, (acc[0][2 * j + 1] + acc[1][2 * j + 1]) * kAlpha),
                               pack_bf16((acc[2][2 * j] + acc[3][2 * j]) * kAlpha, (acc[2][2 * j + 1] + acc[3][2 * j + 1]) * kAlpha));
    asm volatile("st.relaxed.gpu.global.v2.u32 [%0], {%1,%2};" ::"l"(dst + j * 1024), "r"(v.x), "r"(v.y) : "memory");
  }
}
__device__ __forceinline__ void fold_w2(const int u, const __nv_bfloat16* __restrict__ wqkv, const __nv_bfloat16* __restrict__ wo,
                                        uint8_t* wimg) {
  const int g = (threadIdx.x >> 2) & 7, l = threadIdx.x & 3;
  const int m0 = (u / 12) * 32, n0 = (u % 12) * 16;
  uint4 S[12];
  uint32_t L[96];
  const __nv_bfloat16* brow = wqkv + (n0 + 4 * (g >> 1) + (g & 1)) * 576 + 384 + 8 * l;
#pragma unroll
  for (int i = 0; i < 12; i++) S[i] = ldg128_nc(brow + (i & 1) * 2 * 576 + 32 * (i >> 1));
  const __nv_bfloat16* acol = wo + (8 * l) * 192 + m0 + 4 * g;
#pragma unroll
  for (int c = 0; c < 48; c++)
    asm volatile("ld.global.nc.v2.u32 {%0,%1}, [%2];" : "=r"(L[2 * c]), "=r"(L[2 * c + 1]) : "l"(acol + (32 * (c >> 3) + (c & 7)) * 192));
  const uint32_t off = w2_offset();
  sched_fence();
  uint8_t* img = wimg + off;
  float acc[4][4];
#pragma unroll
  for (int j = 0; j < 16; j++) acc[j >> 2][j & 3] = 0.f;
#pragma unroll
  for (int i = 0; i < 6; i++) {
#pragma unroll
    for (int h = 0; h < 2; h++) {
      const uint4 &s0 = S[2 * i], &s1 = S[2 * i + 1];
#pragma unroll
      for (int mt = 0; mt < 2; mt++) {
        const uint32_t* a = L + 16 * i + 8 * h + mt;
        const uint32_t a0 = __byte_perm(a[0], a[2], 0x5410), a1 = __byte_perm(a[0], a[2], 0x7632);
        const uint32_t a2 = __byte_perm(a[4], a[6], 0x5410), a3 = __byte_perm(a[4], a[6], 0x7632);
        mma16816(acc[2 * mt], a0, a1, a2, a3, h ? s0.z : s0.x, h ? s0.w : s0.y);
        mma16816(acc[2 * mt + 1], a0, a1, a2, a3, h ? s1.z : s1.x, h ? s1.w : s1.y);
      }
    }
  }
#pragma unroll
  for (int j = 0; j < 4; j++) {
    const float(&c0)[4] = acc[j & 2];
    const float(&c1)[4] = acc[(j & 2) + 1];
    asm volatile("st.relaxed.gpu.global.v2.u32 [%0], {%1,%2};" ::"l"(img + w2img_off(g2_inv(m0 + 4 * g + j), n0 + 4 * l)),
                 "r"(pack_bf16(c0[2 * (j & 1)], c0[2 * (j & 1) + 1])), "r"(pack_bf16(c1[2 * (j & 1)], c1[2 * (j & 1) + 1])) : "memory");
  }
}

__global__ void __launch_bounds__(256) fold_kernel(const __nv_bfloat16* __restrict__ wqkv,
                                                   const __nv_bfloat16* __restrict__ wo, uint8_t* wimg) {
  const int u = blockIdx.x * 8 + (threadIdx.x >> 5);
  if (u < 144) fold_w1(u, wqkv, wimg);
  else fold_w2(u - 144, wqkv, wo, wimg);
}

struct TileCoord { int pr, pc, I, J, up, kind; };
struct TileTable { uint16_t e[kCtas * 6], g[5][8][2], b[5][2][4]; };
inline void make_tiles(TileTable& tt) {
  for (int tile = 0; tile < kCtas * 6; tile++) {
    const int b = tile / 6, k = tile - 6 * b;
    const int p = b < 128 ? (tile - 672) >> 1 : b - 80;
    const int strip = b < 112 ? b >> 1 : b >= 128 && k >= 2 ? (b & 1) * 27 + (b & 2) * 14 : p + (p < 26 ? 1 : 3);
    const int pr = strip >= 28, J = (strip - pr * 28) >> 1, pc = strip & 1, up = b < 112 ? b & 1 : pr;
    const int first = b < 112 ? 8 - 2 * pr - up : 13 * pr, step = b < 112 ? k : k & 1;
    const int I = up ? first - step : first + step;
    const int kind = I == 13 * pr ? 3 + pr : J == 13 * pc ? 1 + pc : 0;
    tt.e[tile] = (uint16_t)(I | J << 4 | pr << 8 | pc << 9 | up << 10 | kind << 11);
  }
  for (int kind = 0; kind < 5; kind++) {
    const bool col = kind == 1 || kind == 2;
    auto off = [kind](int t) { return kind == 0 ? 2 * t : kind & 1 ? t + (t == 7) : t + (t > 0); };
    for (int j = 0; j < 8; j++) {
      const int w = j >> 1, h = j & 1;
      tt.g[kind][j][0] = (uint16_t)(col ? 3 * off(w + 4 * h) : 3 * (kW * off(2 * w) + 8 * h));
      tt.g[kind][j][1] = (uint16_t)(128 * (col ? 5 : 5 + off(2 * w + 1) - off(2 * w)));
    }
    for (int i = 0; i < 2; i++) {
      const int w = kind == 0 ? 0 : kind & 1 ? 3 * i : 1 - i;
      tt.b[kind][i][0] = tt.g[kind][2 * w][0];
      tt.b[kind][i][1] = (uint16_t)(128 * (kind == 0 ? 0 : (col ? 3 : 1) + i));
      tt.b[kind][i][2] = (uint16_t)(2048 * w);
      tt.b[kind][i][3] = 0;
    }
  }
}
__device__ __forceinline__ int num_tiles() { return blockIdx.x < 128 ? 6 : 4; }
__device__ __forceinline__ TileCoord decode_tile(const TileTable& tt, int tile) {
  const uint32_t e = tt.e[tile];
  return TileCoord{(int)(e >> 8) & 1, (int)(e >> 9) & 1, (int)e & 15, (int)(e >> 4) & 15, (int)(e >> 10) & 1, (int)(e >> 11)};
}
__device__ __forceinline__ int halo_r0(const TileCoord& t) { return 8 * t.I + 6 * t.pr - 6; }
__device__ __forceinline__ int halo_c0(const TileCoord& t) { return min(max(8 * t.J + 6 * t.pc - 6, -3), 102); }

__device__ __forceinline__ uint32_t bar_full(uint32_t bars, int wg, int c) { return bars + (wg * 3 + c) * 8; }
__device__ __forceinline__ uint32_t bar_w1c(uint32_t bars, int c) { return bars + (6 + c) * 8; }
__device__ __forceinline__ uint32_t bar_w2(uint32_t bars) { return bars + 9 * 8; }
__device__ __forceinline__ uint32_t bar_x(uint32_t bars, int j, int c) { return bars + (j == 0 ? 10 : c ? 17 + c : 11) * 8; }
__device__ __forceinline__ uint32_t bar_w1q(uint32_t bars) { return bars + 12 * 8; }
__device__ __forceinline__ uint32_t bar_xf(uint32_t bars) { return bars + 13 * 8; }
__device__ __forceinline__ uint32_t bar_w2m(uint32_t bars) { return bars + 14 * 8; }
__device__ __forceinline__ uint32_t bar_redo(uint32_t bars) { return bars + 15 * 8; }
__device__ __forceinline__ uint32_t bar_wok(uint32_t bars) { return bars + 16 * 8; }
__device__ __forceinline__ uint32_t bar_go(uint32_t bars) { return bars + 17 * 8; }
__device__ __forceinline__ uint32_t bar_raw(uint32_t bars, int j = 0) { return bars + (21 + j) * 8; }
__device__ __forceinline__ uint32_t bar_w2a(uint32_t bars) { return bars + 20 * 8; }
constexpr int kNumBars = 22;

__device__ __forceinline__ uint64_t wdesc(uint64_t d0, int s) { return d0 + (((s >> 2) * kWChunk + (s & 3) * 32) >> 4); }

__device__ __forceinline__ uint32_t x_chunk(int k, int c) { return kXOff + (k == 0 ? kWChunk : 0) + (k & 1 ? 2 - c : c) * 8192; }
__device__ __forceinline__ uint32_t out_slot(int k, int nt) { return k + 1 < nt ? kW2Off + (~k & 1) * 2 * kWChunk : kW1Off + kWChunk; }
template <int I0, int I1>
__device__ __forceinline__ void store_rows(bool on, __nv_bfloat16* pA, __nv_bfloat16* pB, const uint32_t (&a)[24], const uint32_t (&b)[24]) {
#pragma unroll
  for (int i = 2 * I0; i < 2 * I1; i++) {
    const uint32_t* v = (i & 1 ? b : a) + 4 * (i >> 1);
    asm volatile("{\n.reg .pred p;\nsetp.ne.u32 p, %5, 0;\n@p st.global.v4.u32 [%0], {%1,%2,%3,%4};\n}\n" ::"l"((i & 1 ? pB : pA) + 32 * (i >> 1)),
                 "r"(v[0]), "r"(v[1]), "r"(v[2]), "r"(v[3]), "r"((uint32_t)on) : "memory");
  }
}
template <int I0, int I1>
__device__ __forceinline__ void stage_out(const uint32_t (&ad)[4], const uint32_t (&a)[24], const uint32_t (&b)[24]) {
#pragma unroll
  for (int i = I0; i < I1; i++) {
    const uint32_t* v = (i < 6 ? a : b) + 4 * (i % 6);
    asm volatile("st.shared.v4.u32 [%0], {%1,%2,%3,%4};" ::"r"(ad[i % 6 / 3 * 2 + (i % 3 == 1)] + (i % 3 == 2) * 1024 + (i / 6) * 12288),
                 "r"(v[0]), "r"(v[1]), "r"(v[2]), "r"(v[3]) : "memory");
  }
}
__device__ __forceinline__ uint32_t now_ns() {
  uint32_t t;
  asm volatile("mov.u32 %0, %globaltimer_lo;" : "=r"(t)::"memory");
  return t;
}
__device__ __forceinline__ void wait_clock(uint32_t t_start, uint32_t t) {
  while (now_ns() - t_start < t) { }
}
#define NAT_PRED(f, m) ".reg .pred p;\n.reg .b32 t;\nand.b32 t, " f ", " m ";\nsetp.ne.u32 p, t, 0;\n"
constexpr uint32_t kHiV = 1, kHiU = 8, kColB = 0x20, kInV = 0x100, kInU = 0x1000, kColA = 0x10000;
template <uint32_t M>
__device__ __forceinline__ float pick(const float* a, const float* b, uint32_t f) {
  float d;
  asm("{\n" NAT_PRED("%5", "%6") "add.f32 %0, %1, %2;\n@p add.f32 %0, %3, %4;\n}\n"
      : "=&f"(d) : "f"(a[0]), "f"(a[2]), "f"(b[0]), "f"(b[2]), "r"(f), "n"(M));
  return d;
}
template <uint32_t M>
__device__ __forceinline__ float sel(float a, float b, uint32_t f) {
  float d;
  asm("{\n" NAT_PRED("%3", "%4") "selp.f32 %0, %1, %2, p;\n}\n" : "=f"(d) : "f"(a), "f"(b), "r"(f), "n"(M));
  return d;
}
template <uint32_t M>
__device__ __forceinline__ void max_if(float& m, float v, uint32_t f) {
  asm("{\n" NAT_PRED("%2", "%3") "@p max.f32 %0, %0, %1;\n}\n" : "+f"(m) : "f"(v), "r"(f), "n"(M));
}
template <uint32_t M>
__device__ __forceinline__ void add_if(float& m, float v, uint32_t f) {
  asm("{\n" NAT_PRED("%2", "%3") "@p add.f32 %0, %0, %1;\n}\n" : "+f"(m) : "f"(v), "r"(f), "n"(M));
}
__device__ __forceinline__ void pick_v(const float* a, float* v, uint32_t f) {
  v[0] = pick<kHiV>(a, a + 16, f), v[1] = pick<kHiV>(a + 1, a + 17, f);
  v[2] = pick<kHiV * 2>(a + 4, a + 20, f), v[3] = pick<kHiV * 2>(a + 5, a + 21, f);
  v[4] = pick<kHiV * 4>(a + 8, a + 24, f), v[5] = pick<kHiV * 4>(a + 9, a + 25, f);
  v[6] = a[12] + a[14], v[7] = a[13] + a[15];
}
__device__ __forceinline__ void pick_u(const float* a, float* v, uint32_t f) {
#pragma unroll
  for (int c = 0; c < 3; c++) v[2 * c] = pick<kHiU>(a + 4 * c, a + 4 * c + 12, f), v[2 * c + 1] = pick<kHiU * 2>(a + 4 * c + 1, a + 4 * c + 13, f);
}
__device__ __forceinline__ uint32_t sign_bytes(uint32_t v, uint32_t sel) {
  uint32_t d;
  asm("prmt.b32 %0, %1, %1, %2;" : "=r"(d) : "r"(v), "r"(sel));
  return d;
}
__device__ __forceinline__ float own_max(const float (&v)[14], uint32_t f) {
  float m = sel<kInV>(fmaxf(v[0], v[1]), -INFINITY, f), m2 = sel<kInV * 2>(fmaxf(v[2], v[3]), -INFINITY, f);
  max_if<kInV * 4>(m, fmaxf(v[4], v[5]), f);
  max_if<kInV * 8>(m2, fmaxf(v[6], v[7]), f);
  max_if<kInU>(m, fmaxf(fmaxf(v[8], v[10]), v[12]), f);
  max_if<kInU * 2>(m2, fmaxf(fmaxf(v[9], v[11]), v[13]), f);
  return fmaxf(m, m2);
}
__device__ __forceinline__ float quad_max(float m) {
  const float a = __shfl_xor_sync(0xffffffffu, m, 1), b = __shfl_xor_sync(0xffffffffu, m, 2), c = __shfl_xor_sync(0xffffffffu, m, 3);
  return fmaxf(fmaxf(m, a), fmaxf(b, c));
}
__device__ __forceinline__ float row_rcp(const float (&v)[14], uint32_t f) {
  float s = sel<kInV>(v[0] + v[1], 0.f, f), s2 = sel<kInV * 2>(v[2] + v[3], 0.f, f);
  add_if<kInV * 4>(s, v[4] + v[5], f);
  add_if<kInV * 8>(s2, v[6] + v[7], f);
  add_if<kInU>(s, v[8] + v[10] + v[12], f);
  add_if<kInU * 2>(s2, v[9] + v[11] + v[13], f);
  s += s2;
  const float a = __shfl_xor_sync(0xffffffffu, s, 1), b = __shfl_xor_sync(0xffffffffu, s, 2), c = __shfl_xor_sync(0xffffffffu, s, 3);
  return rcp_approx((s + a) + (b + c));
}
__device__ __forceinline__ void route(const float (&v)[14], float s, const uint32_t (&rt)[9], uint32_t (&p)[14]) {
#pragma unroll
  for (int i = 0; i < 7; i++) {
    const uint32_t u = pack_bf16(v[2 * i] * s, v[2 * i + 1] * s);
    if (i < 4) p[i] = u & rt[i];
    if (i < 3) p[i + 4] = u & rt[i + 4];
    if (i >= 4) {
      p[i + 3] = u & rt[7];
      p[i + 6] = u & rt[8];
    }
  }
}

template <int C, int T0 = 0, int T1 = 7>
__device__ __forceinline__ void pv_chunk(float (&z)[32], const uint32_t (&pa)[14], const uint32_t (&pb)[14],
                                         const uint32_t (&meta)[4], uint64_t dV) {
#pragma unroll
  for (int t = T0; t < T1; t++) {
    if (t & 1)
      wg_s64t1<0, 32>(z, pa[2 * t], pb[2 * t], pa[2 * t + 1], pb[2 * t + 1], dV + ((2 * C * kChunkBytes + t * 2048) >> 4), 1,
                      meta[t >> 1]);
    else if (t > 0)
      wg_s64t<0, 32>(z, pa[2 * t], pb[2 * t], pa[2 * t + 1], pb[2 * t + 1], dV + ((2 * C * kChunkBytes + t * 2048) >> 4), 1,
                     meta[t >> 1]);
    else
      wg_s64tz<0, 32>(z, pa[0], pb[0], pa[1], pb[1], dV + ((2 * C * kChunkBytes) >> 4), 0, meta[0]);
  }
}
template <int C>
__device__ __forceinline__ void pack_z(const float (&z)[32], uint32_t (&za)[24], uint32_t (&zb)[24]) {
#pragma unroll
  for (int j = 0; j < 8; j++) {
    za[8 * C + j] = pack_bf16(z[4 * j], z[4 * j + 1]);
    zb[8 * C + j] = pack_bf16(z[4 * j + 2], z[4 * j + 3]);
  }
}

template <int H>
__device__ __forceinline__ void pack_out(const float (&ac)[48], uint32_t (&oa)[24], uint32_t (&ob)[24]) {
#pragma unroll
  for (int j = 0; j < 12; j++) {
    oa[12 * H + j] = pack_bf16(ac[4 * j], ac[4 * j + 1]);
    ob[12 * H + j] = pack_bf16(ac[4 * j + 2], ac[4 * j + 3]);
  }
}
struct Maps { CUtensorMap v6, v2, v14, u8, px[8], wv, wo; };
__device__ __forceinline__ void tma_prefetch_5d(const CUtensorMap* map, int c0, int c1, int c2, int c3, int c4) {
  asm volatile("cp.async.bulk.prefetch.tensor.5d.L2.global.tile [%0, {%1, %2, %3, %4, %5}];" ::"l"((uint64_t)map), "r"(c0), "r"(c1),
               "r"(c2), "r"(c3), "r"(c4) : "memory");
}
__device__ __forceinline__ int first_line(const TileCoord tc) { return 3 * (qpix(tc.pr, 8 * tc.I) * kW + qpix(tc.pc, 8 * tc.J)); }
__device__ __forceinline__ void load_px(const Maps& tm, const TileTable& tt, uint32_t dst, uint32_t bar, int line, int kind) {
#pragma unroll
  for (int i = 0; i < 2; i++) {
    if (i == 0 || kind != 0) {
      const CUtensorMap* map = (const CUtensorMap*)((const char*)tm.px + tt.b[kind][i][1]);
      if (bar) tma_load_5d(dst + tt.b[kind][i][2], map, bar, 0, 0, 0, 0, line + tt.b[kind][i][0]);
      else tma_prefetch_5d(map, 0, 0, 0, 0, line + tt.b[kind][i][0]);
    }
  }
}
__device__ __forceinline__ void store_px(const Maps& tm, const TileTable& tt, uint32_t buf, int line, int kind) {
#pragma unroll
  for (int i = 0; i < 8; i++) {
    const int j = 2 * (i & 3) + (i >> 2);
    asm volatile("cp.async.bulk.tensor.5d.global.shared::cta.tile.bulk_group [%0, {%2, %2, %2, %2, %3}], [%1];" ::"l"(
                     (uint64_t)tm.px + tt.g[kind][j][1]), "r"(buf + i * 3072), "r"(0), "r"(line + tt.g[kind][j][0]) : "memory");
  }
  asm volatile("cp.async.bulk.commit_group;" ::: "memory");
}
__device__ __noinline__ bool refetch(uint32_t base, const uint8_t* src, bool gap) {
  constexpr uint32_t bars = 1024 + kBarOff, cnt = bars + 192;
#pragma unroll 1
  for (uint32_t o = 0; o < kWBytes && !gap; o += 2048) {
    uint32_t mx = 0;
#pragma unroll
    for (int i = 0; i < 4; i++) {
      uint4 v;
      asm volatile("ld.shared.v4.u32 {%0,%1,%2,%3}, [%4];" : "=r"(v.x), "=r"(v.y), "=r"(v.z), "=r"(v.w)
                   : "r"(base + o + i * 512 + (threadIdx.x & 31) * 16));
      mx = __vimax3_u32(__vimax3_u32(mx, v.x, v.y), v.z, v.w);
    }
    gap = __any_sync(0xffffffffu, mx == kEmpty);
  }
  uint32_t n;
  asm volatile("ld.shared.u32 %0, [%1];" : "=r"(n) : "r"(cnt) : "memory");
  if (!gap || __any_sync(0xffffffffu, n > (1u << 12))) return false;
  asm volatile("bar.sync 15, 128;" ::: "memory");
  if (threadIdx.x == 0) {
    asm volatile("st.shared.u32 [%0], %1;" ::"r"(cnt), "r"(n + 1) : "memory");
    mbar_arrive_expect_tx(bar_redo(bars), kWBytes);
    bulk_load(base, src, kWBytes, bar_redo(bars));
  }
  __syncwarp();
  mbar_wait(bar_redo(bars), n & 1);
  return true;
}
__device__ __forceinline__ bool any_nan(const uint32_t (&a)[24]) {
  uint32_t m[2] = {a[0], a[1]}, nan;
#pragma unroll
  for (int i = 2; i < 24; i++) asm("max.NaN.bf16x2 %0, %0, %1;" : "+r"(m[i & 1]) : "r"(a[i]));
  asm("max.NaN.bf16x2 %0, %0, %1;" : "+r"(m[0]) : "r"(m[1]));
  asm volatile("{\n.reg .pred p;\nsetp.ne.u32 p, %1, 0;\nbar.red.or.pred p, 15, 128, p;\nselp.u32 %0, 1, 0, p;\n}\n"
               : "=r"(nan) : "r"(((m[0] & 0x7FFF7FFFu) + 0x007F007Fu) & 0x80008000u) : "memory");
  return __any_sync(0xffffffffu, nan);
}
template <int S0, int S1, int Z>
__device__ __forceinline__ void g2_steps(float (&ac)[48], const uint32_t (&za)[24], const uint32_t (&zb)[24], uint64_t d) {
#pragma unroll
  for (int s = S0; s < S1; s++) {
    const uint64_t ds = d + (((s >> 2 & 1) * (kWChunk / 2) + (s & 3) * 32) >> 4);
    if (s == Z) wg_d96z<0, 48>(ac, za[2 * s], zb[2 * s], za[2 * s + 1], zb[2 * s + 1], ds, 0);
    else wg_d96<0, 48>(ac, za[2 * s], zb[2 * s], za[2 * s + 1], zb[2 * s + 1], ds, 1);
  }
}

__device__ __forceinline__ void consumer(const int wg, __nv_bfloat16* out, const uint8_t* wimg, const uint32_t sbase,
                                         const uint32_t zero, const Maps& tm, const TileTable& tt) {
  const int tid = threadIdx.x & 127;
  const int w = __shfl_sync(0xffffffffu, tid >> 5, 0), lane = tid & 31;
  const uint64_t dK = make_desc(sbase, 16, 1024);
  const uint64_t dV = make_desc(sbase, kChunkBytes, 512, 2);
  const uint64_t dW1 = make_desc(sbase + kW1Off, 16, 1024);
  const uint64_t dX0 = make_desc(sbase + kW2Off + wg * 2 * kWChunk, 16, 1024), dY0 = make_desc(sbase + kW2Off + (1 - wg) * 2 * kWChunk, 16, 1024);
  const uint64_t dX2 = make_desc(sbase + kXOff + wg * (kWChunk / 2), 16, 1024), dY2 = make_desc(sbase + kXOff + (1 - wg) * (kWChunk / 2), 16, 1024);
  const uint32_t bars = sbase + kBarOff;
  int tile0 = blockIdx.x * kTilesPerCta;
  asm volatile("" : "+r"(tile0));
  const int nt = num_tiles();

  uint32_t pix = 0, geo[6] = {};
  const int l = lane & 3;
#pragma unroll 1
  for (int j = 4; j >= 0; j -= 2) {
    const TileCoord tc = decode_tile(tt, tile0 + wg + j);
    const bool col = tc.kind == 1 || tc.kind == 2;
    const int g = col ? lane >> 2 : 2 * w + ((lane >> 2) & 1), qc = col ? w : lane >> 3;
    const uint32_t pr = qpix(tc.pr, 8 * tc.I + g) * kW;
    if (j == nt - 2) pix = (pr + qpix(tc.pc, 8 * tc.J + qc)) | (pr + qpix(tc.pc, 8 * tc.J + qc + 4)) << 16;
    const int d = 8 * tc.J + 6 * tc.pc - 6 - halo_c0(tc);
    const int ro = woff(tc.pr, tc.I, g), coA = woff(tc.pc, tc.J, qc) + d, coB = woff(tc.pc, tc.J, qc + 4) + d - 3;
#pragma unroll
    for (int i = 5; i >= 2; i--) geo[i] = geo[i - 2];
    const uint32_t lr = 0x1FCu << ro;
    const uint32_t lv = lr >> (2 + (l >> 1)), lu = lr >> (2 * l + 2 * tc.up);
    const uint32_t t = __byte_perm(lv, lu, wg ? 0x4501 : 0x5410);
    geo[0] = (((t & 0x15u) | (lv & 0x40u)) * 0x02082080u & 0x80808080u) | (((t >> 8) & 0x15u) * 0x01041040u & 0x40404040u) |
             (__byte_perm(t << 5, t << 4, 0x7362) & 0x20202020u) | (nt == 6);
    const int dr = (ro - 1) & 7;
    const uint32_t hiv = (((1u << ((ro - (l >> 1) + 1) >> 1)) - 1u) ^ (wg ? 7u : 0u)) & 7u, hiu = (t >> 24) & 3u;
    const uint32_t ca = (1u << coA) - 1u;
    geo[1] = hiv * kHiV | hiu * kHiU | ((((1u << coB) - 1u) >> (2 * (l & 1))) & 3u) * kColB |
             (15u & ~((uint32_t)((dr & 1) == (l >> 1)) << (dr >> 1))) * kInV | ((t >> 16 | t >> 24) & 3u) * kInU | ca * kColA |
             (ca >> ((0x49 >> (2 * l)) & 3) & 1u) << 19 | (uint32_t)(l == 3) << 20 | (0x55u & ((1u << (2 * coB)) - 1u)) << 24;
  }
  keep_regs(geo);
  const int so = (lane >> 3) | (lane & 4);
  uint32_t sts = sbase + w * 3072 + so * 128 + (((lane & 3) ^ so) << 4);
  __nv_bfloat16* poA = out + 8 * l + (pix & 0xFFFFu) * kC + 96 * wg;
  __nv_bfloat16* poB = out + 8 * l + (pix >> 16) * kC + 96 * wg;
  asm volatile("" : "+l"(poA), "+l"(poB), "+r"(sts));
  uint32_t oa[24], ob[24];
#pragma unroll
  for (int j = 0; j < 24; j++) oa[j] = ob[j] = 0u;
  keep_regs(oa);
  keep_regs(ob);
  PROF(wg, 0);
  if (threadIdx.x == 0) GT(1);

  for (int k = wg; k < nt; k += 2) {
    const uint32_t ph = (k >> 1) & 1;
    const int it = k >> 1;
    uint32_t qa[24], qb[24], hok[3];
    uint32_t fl = geo[1];
    {
      float acc[96];
      const uint32_t xp = (k + (k > 0)) & 1;
      const uint32_t xok = mbar_test(bar_x(bars, k > 0, 0), xp);
      if (k > 0) nb_sync(1 + (1 - wg));
#pragma unroll
      for (int s = 0; s < 12; s++) {
        if (s == 0) mbar_wait_if(xok, bar_x(bars, k > 0, 0), xp);
        if (s == 0 && k < 2) PROF(wg, 1);
        if (s == 0) PROFS(2, wg, 2 + it * 12);
        if (s == 0 && w == 0 && k < 2) GT(20 + wg);
        if ((s & 3) == 0 && (k == 0 || s > 0)) {
          mbar_wait(k == 0 ? bar_w1c(bars, s >> 2) : bar_x(bars, 1, s >> 2), xp);
          PROFS(17, wg, 50 + (s >> 2));
        }
        if ((s & 3) == 0) wg_fence();
        const uint64_t dX = make_desc(sbase + x_chunk(k, s >> 2), 16, 1024) + 2 * (s & 3);
        if (s == 0) wg_m192z<0, 96>(acc, dX, dW1, 0);
        else wg_m192<0, 96>(acc, dX, wdesc(dW1, s), 1);
        if ((s & 3) == 3) wg_commit();
      }
      PROFS(13, wg, 13 + it * 12);
      const uint32_t e = sts + out_slot(k, nt), o = e ^ 64;
      uint32_t ad[4] = {wg ? o + 1024 : e, wg ? e + 2048 : o, wg ? e : o + 1024, wg ? o : e + 2048};
      keep_regs(ad);
      wg_wait<2>();
      if (k > 0) nb_arrive_p(0);
      wg_wait<1>();
      if (k > 0) nb_arrive_p(14);
      wg_wait<0>();
      if (k > 0) {
        nb_arrive_p(6);
        sched_fence();
      }
      fence_regs(acc);
      PROFS(3, wg, 3 + it * 12);
#pragma unroll
      for (int j = 0; j < 24; j++) {
        qa[j] = pack_bf16(acc[4 * j], acc[4 * j + 1]);
        qb[j] = pack_bf16(acc[4 * j + 2], acc[4 * j + 3]);
      }
      keep_regs(qa);
      keep_regs(qb);
      sched_fence();
      if (k >= 2) {
        nb_sync(11);
        stage_out<0, 6>(ad, oa, ob);
        nb_sync(12);
        stage_out<6, 12>(ad, oa, ob);
      }
#pragma unroll
      for (int c = 0; c < 3; c++) hok[c] = mbar_test(bar_full(bars, wg, c), ph);
      if (k >= 2) {
        fence_proxy_async();
        nb_arrive_p(10);
      }
    }

    float aE[52], aO[24], bO[52], bE[28];
    const uint32_t mq = 0xEEEE4444u | zero;
    PROFS(4, wg, 4 + it * 12);

    mbar_wait_if(hok[0], bar_full(bars, wg, 0), ph);
    PROFS(14, wg, 40 + it * 3);
    if (w == 0 && k < 2) GT(22 + wg);
    if (k > 0) nb_sync(3 + (1 - wg));
    wg_fence();
#pragma unroll
    for (int ks = 0; ks < 6; ks++) {
      if (ks == 2) {
        mbar_wait_if(hok[1], bar_full(bars, wg, 1), ph);
        PROFS(14, wg, 41 + it * 3);
        wg_fence();
      }
      if (ks == 4) {
        mbar_wait_if(hok[2], bar_full(bars, wg, 2), ph);
        PROFS(14, wg, 42 + it * 3);
        wg_fence();
      }
      const uint64_t d = dK + ((ks * kChunkBytes) >> 4);
      if (ks == 0) wg_s104z<0, 52>(aE, qa[0], qa[1], qa[2], qa[3], d, 0, mq);
      else wg_s104<0, 52>(aE, qa[4 * ks], qa[4 * ks + 1], qa[4 * ks + 2], qa[4 * ks + 3], d, 1, mq);
      if (ks == 0) wg_s48z<0, 24>(aO, qa[0], qa[1], qa[2], qa[3], d + ((7 * 1024 + 64) >> 4), 0, mq);
    }
    wg_commit();
#pragma unroll
    for (int ks = 1; ks < 6; ks++)
      wg_s48<0, 24>(aO, qa[4 * ks], qa[4 * ks + 1], qa[4 * ks + 2], qa[4 * ks + 3], dK + ((ks * kChunkBytes + 7 * 1024 + 64) >> 4), 1, mq);
    wg_commit();
    wg_s56z<0, 28>(bE, qb[0], qb[1], qb[2], qb[3], dK, 0, mq);
#pragma unroll
    for (int ks = 1; ks < 6; ks++) wg_s56<0, 28>(bE, qb[4 * ks], qb[4 * ks + 1], qb[4 * ks + 2], qb[4 * ks + 3], dK + ((ks * kChunkBytes) >> 4), 1, mq);
    wg_commit();
    wg_wait<2>();
    fence_regs(aE);
    PROFS(5, wg, 5 + it * 12);

    uint32_t pa[14], pb[14], meta[4];
    {
      float vA[14], vB[14];
      pick_v(aE, vA, fl);
      pick_u(aE + 28, vA + 8, fl);
      fence_regs(vA);
      if (k == 0) {
        if (__builtin_expect(__any_sync(0xffffffffu, vA[6] != vA[6]), 0)) {
          wg_wait<0>();
          fence_regs(aO);
          fence_regs(bE);
          if (refetch(sbase + kW1Off, wimg, false)) {
#pragma unroll
            for (int j = 0; j < 24; j++) oa[j] = ob[j] = 0u;
            k -= 2;
            continue;
          }
        }
        if (elect_one()) mbar_arrive(bar_xf(bars));
      }
      wg_fence();
      wg_s104z<0, 52>(bO, qb[0], qb[1], qb[2], qb[3], dK + 4, 0, mq);
#pragma unroll
      for (int ks = 1; ks < 6; ks++)
        wg_s104<0, 52>(bO, qb[4 * ks], qb[4 * ks + 1], qb[4 * ks + 2], qb[4 * ks + 3], dK + ((ks * kChunkBytes + 64) >> 4), 1, mq);
      wg_commit();
      if (k + 1 < nt) nb_arrive(1 + wg);
      uint32_t rt[9];
#pragma unroll
      for (int i = 0; i < 7; i++) rt[i] = sign_bytes(geo[0] << (i >> 2), 0x8888u + 0x1111u * (i & 3));
      rt[7] = sign_bytes(geo[0] << 2, 0x9988u);
      rt[8] = sign_bytes(geo[0] << 2, 0xBBAAu);
      keep_regs(rt);
      pa[13] = pb[13] = 0u;
      wg_wait<2>();
      keep_regs(qa);
      fence_regs(aO);
      float oA[6], eB[8];
      pick_u(aO, oA, fl);
      wg_wait<1>();
      fence_regs(bE);
      pick_v(bE, eB, fl);
      vA[8] = sel<kColA>(oA[0], vA[8], fl), vA[9] = sel<kColA>(oA[1], vA[9], fl);
      vA[10] = sel<kColA * 2>(oA[2], vA[10], fl), vA[11] = sel<kColA * 2>(oA[3], vA[11], fl);
      vA[12] = sel<kColA * 4>(oA[4], vA[12], fl), vA[13] = sel<kColA * 4>(oA[5], vA[13], fl);
      {
        const float m1 = __uint_as_float(0x88DD88DDu), m0 = __uint_as_float(0x88DDDD88u);
        meta[0] = 0xDD88DD88u ^ __byte_perm(fl, 0u, 0x3344);
        meta[1] = __float_as_uint(sel<kColA * 16>(sel<kColA>(m1, m0, fl), __uint_as_float(meta[0]), fl));
        meta[2] = __float_as_uint(sel<kColA * 8>(m1, m0, fl));
        meta[3] = __float_as_uint(sel<kColA * 4>(m1, m0, fl));
        keep_regs(meta);
      }
      float mA = own_max(vA, fl);
      fl |= __float_as_uint(eB[7]) & zero;
      fence_regs(eB);
      fence_regs(vA);
      asm volatile("" : "+f"(mA), "+r"(fl));
      sched_fence();
      wg_wait<0>();
      sched_fence();
      keep_regs(qb);
      fence_regs(bO);
      PROFS(6, wg, 6 + it * 12);
      if (w == 0) GT(24 + k);
      mA = quad_max(mA);
#pragma unroll
      for (int i = 0; i < 14; i++) vA[i] = ex2(vA[i] - mA);
      pick_v(bO, vB, fl);
      pick_u(bO + 28, vB + 8, fl);
#pragma unroll
      for (int i = 0; i < 8; i += 2) vB[i] = sel<kColB>(vB[i], eB[i], fl), vB[i + 1] = sel<kColB * 2>(vB[i + 1], eB[i + 1], fl);
      float mB = quad_max(own_max(vB, fl));
      PROFS(7, wg, 7 + it * 12);
#pragma unroll
      for (int i = 0; i < 14; i++) vB[i] = ex2(vB[i] - mB);
      route(vA, row_rcp(vA, fl), rt, pa);
      route(vB, row_rcp(vB, fl), rt, pb);
    }
    PROFS(8, wg, 8 + it * 12);
    if (k == NAT_PK) PROFS(18, wg, 53);
    sched_fence();

    float ac0[48], ac1[48];
    {
      float z0[32], z1[32], z2[32];
      uint32_t za[24], zb[24];
      wg_fence();
      pv_chunk<0>(z0, pa, pb, meta, dV);
      wg_commit();
      pv_chunk<1>(z1, pa, pb, meta, dV);
      wg_commit();
      wg_wait<1>();
      if (k == NAT_PK) PROFS(18, wg, 54);
      if (k + 1 < nt) nb_arrive_p(7);
      pv_chunk<2, 0, 3>(z2, pa, pb, meta, dV);
      wg_commit();
      sched_fence();
      fence_regs(z0);
      pack_z<0>(z0, za, zb);
      sched_fence();
      wg_fence();
      pv_chunk<2, 3, 7>(z2, pa, pb, meta, dV);
      wg_commit();
      wg_wait<2>();
      if (k == NAT_PK) PROFS(19, wg, 55);
      if (k + 1 < nt) nb_arrive_p(8);
      if (k < 2) mbar_wait(k == 1 ? bar_wok(bars) : bar_w2a(bars), 0);
      wg_fence();
      g2_steps<0, 3, 0>(ac0, za, zb, dX0);
      wg_commit();
      sched_fence();
      fence_regs(z1);
      pack_z<1>(z1, za, zb);
      sched_fence();
      wg_fence();
      g2_steps<3, 4, 0>(ac0, za, zb, dX0);
      wg_commit();
      g2_steps<4, 8, 0>(ac0, za, zb, dX0);
      wg_commit();
      wg_wait<3>();
      if (k + 1 < nt) nb_arrive_p(9);
      else nb_arrive(11);
      if (k == NAT_PK) PROFS(20, wg, 56);
      keep_regs(pa);
      keep_regs(pb);
      keep_regs(meta);
      sched_fence();
      const uint32_t mok = mbar_test(bar_w2m(bars), k + 1 < nt ? k & 1 : ~k & 1);
      const uint32_t wp = k < 2 ? 0 : k + 1 < nt ? ~k & 1 : k & 1, wok = mbar_test(bar_w2(bars), wp);
      fence_regs(z2);
      pack_z<2>(z2, za, zb);
      keep_regs(za);
      keep_regs(zb);
      sched_fence();
      PROFS(9, wg, 9 + it * 12);
      wg_wait<1>();
      if (k > 0 && k + 1 < nt) nb_arrive(11);
      mbar_wait_if(mok, bar_w2m(bars), k & 1);
      wg_fence();
      g2_steps<8, 12, 0>(ac0, za, zb, dX2);
      wg_commit();
      g2_steps<8, 12, 8>(ac1, za, zb, dY2);
      wg_commit();
      wg_wait<2>();
      if (k > 0 && k + 1 < nt) nb_arrive(12);
      mbar_wait_if(wok, bar_w2(bars), wp);
      wg_fence();
      g2_steps<0, 4, 8>(ac1, za, zb, dY0);
      wg_commit();
      wg_wait<2>();
      if (k + 2 < nt) nb_arrive_p(13);
      const bool direct = k + 2 >= nt;
      sched_fence();
      fence_regs(ac0);
      pack_out<0>(ac0, oa, ob);
      store_rows<0, 1>(direct, poA, poB, oa, ob);
      sched_fence();
      wg_fence();
      g2_steps<4, 8, 8>(ac1, za, zb, dY0);
      wg_commit();
      if (k + 1 < nt) nb_arrive(3 + wg);
      PROFS(10, wg, 10 + it * 12);
      wg_wait<2>();
      if (k + 2 < nt && (k > 0 || nt == 6)) nb_arrive_p(5);
      store_rows<1, 3>(direct, poA, poB, oa, ob);
      __nv_bfloat16 *qA = poA - 192 * wg, *qB = poB - 192 * wg;
      if (k + 2 == nt) nb_sync(11);
      sched_fence();
      wg_wait<0>();
      fence_regs(ac1);
      pack_out<1>(ac1, oa, ob);
      asm volatile("" : "+l"(qA), "+l"(qB));
      store_rows<3, 6>(direct, qA, qB, oa, ob);
      if (direct) break;
      if (k == 0) {
        if (any_nan(oa)) {
          for (int c = 0; c < 3 && __any_sync(0xffffffffu, geo[2] & 1u); c++) mbar_wait(bar_x(bars, 1, c), 1);
          bool first = true;
          do {
            if (!__any_sync(0xffffffffu, refetch(sbase + kW2Off, wimg + w2_offset(), first))) break;
            first = false;
            wg_fence();
            g2_steps<0, 8, 0>(ac0, za, zb, dX0);
            g2_steps<8, 12, 0>(ac0, za, zb, dX2);
            g2_steps<8, 12, 8>(ac1, za, zb, dY2);
            g2_steps<0, 8, 8>(ac1, za, zb, dY0);
            wg_commit();
            wg_wait<0>();
            fence_regs(ac0);
            fence_regs(ac1);
            pack_out<0>(ac0, oa, ob);
            pack_out<1>(ac1, oa, ob);
          } while (any_nan(oa));
          if (__any_sync(0xffffffffu, geo[2] & 1u)) {
            asm volatile("bar.sync 15, 128;" ::: "memory");
            if (w == 0 && elect_one()) {
              const TileCoord tc = decode_tile(tt, tile0 + 2);
              mbar_arrive_expect_tx(bar_raw(bars), kWChunk);
#pragma unroll 1
              for (int c = 0; c < 3; c++) load_px(tm, tt, sbase + x_chunk(2, c), bar_raw(bars), first_line(tc) + c, tc.kind);
            }
            __syncwarp();
            mbar_wait(bar_raw(bars), 0);
          }
        }
        if (nt < 6) nb_arrive_p(5);
        if (elect_one()) mbar_arrive(bar_wok(bars));
      }
      keep_regs(za);
      keep_regs(zb);
#pragma unroll
      for (int i = 0; i < 4; i++) geo[i] = geo[i + 2];
      keep_regs(oa);
      keep_regs(ob);
      PROFS(12, wg, 12 + it * 12);
      sched_fence();
    }
  }
  PROF(wg, 38);
  GT_DUMP();
  PROF_DUMP(wg);
}

struct HaloCols { int vj, vc, uj, uc; };
__device__ __forceinline__ HaloCols halo_cols(const TileCoord& tc) {
  const int c0 = halo_c0(tc);
  return HaloCols{c0 > 98, c0 > 98 ? 98 : c0 + 3, c0 < 0 ? -1 : 0, c0 < 0 ? 4 : c0};
}
__device__ __forceinline__ void first_halo(const Maps& tm, uint32_t sbase, const TileCoord tc, int i) {
  const HaloCols hc = halo_cols(tc);
  const uint32_t dst = sbase + i * kChunkBytes, bar = bar_full(sbase + kBarOff, 0, i >> 1);
  const int h0 = halo_r0(tc), ch = 24 * tc.pc + 4 * i;
  tma_load_5d(dst, &tm.v14, bar, ch, hc.vj, hc.vc, tc.pr, h0);
  tma_load_5d(dst + 7 * 1024, &tm.u8, bar, ch, hc.uj, h0 + (tc.up ? 0 : -2), tc.pr, hc.uc);
  tma_load_5d(dst + 10 * 1024, &tm.u8, bar, ch, hc.uj, h0 + (tc.up ? 8 : 6), tc.pr, hc.uc);
}
__device__ __forceinline__ void load_halo(const Maps& tm, uint32_t sbase, uint32_t bars, const TileCoord tc, int k, int c) {
  const HaloCols hc = halo_cols(tc);
  const int h6 = halo_r0(tc) + (tc.up ? 0 : 8), h2 = halo_r0(tc) + 6, h8 = halo_r0(tc) + (tc.up ? 0 : 6), ch = 24 * tc.pc + 8 * c;
  uint32_t dv = sbase + 2 * c * kChunkBytes, du = dv + 7 * 1024;
  if (((k ^ tc.up) & 1) == 0) dv += 4 * 1024, du += 3 * 1024;
  const uint32_t bar = bar_full(bars, k & 1, c);
  mbar_arrive_expect_tx(bar, 14 * 1024);
  nb_sync_p(7 + c);
#pragma unroll
  for (int h = 0; h < 2; h++) {
    tma_load_5d(dv + h * kChunkBytes, &tm.v6, bar, ch + 4 * h, hc.vj, hc.vc, tc.pr, h6);
    tma_load_5d(du + h * kChunkBytes, &tm.u8, bar, ch + 4 * h, hc.uj, h8, tc.pr, hc.uc);
    tma_load_5d(sbase + (2 * c + h) * kChunkBytes + 3 * 1024, &tm.v2, bar, ch + 4 * h, hc.vj, hc.vc, tc.pr, h2);
  }
  PROFS(15, 2, k * 4 + c);
}
__device__ __forceinline__ void gather_px(const __nv_bfloat16* __restrict__ x, uint32_t sbase, const TileCoord tc) {
  const int lane = threadIdx.x & 31, g = lane >> 3;
  uint32_t ro[4], co[4];
#pragma unroll
  for (int i = 0; i < 4; i++) {
    ro[i] = qpix(tc.pr, 8 * tc.I + 2 * i + (g & 1)) * (kW * kC * 2) + 16 * (lane & 7);
    co[i] = qpix(tc.pc, 8 * tc.J + 2 * i + (g >> 1)) * (kC * 2);
  }
  const uint32_t dst = sbase + kXOff + g * 128 + (((lane & 7) ^ g) << 4);
  if (lane < 8)
    asm volatile("cp.async.bulk.prefetch.L2.global [%0], 3456;" ::"l"(x + (qpix(tc.pr, 8 * tc.I + lane) * kW + 215 * tc.pc) * kC) : "memory");
  __syncwarp();
  keep_regs(ro);
  keep_regs(co);
  sched_fence();
  nb_sync_p(13);
  nb_sync_p(5);
#pragma unroll
  for (int i = 0; i < 16; i++) {
    const char* src = (const char*)x + (ro[i >> 2] + co[i & 3]);
#pragma unroll
    for (int q = 0; q < 3; q++)
      asm volatile("cp.async.cg.shared.global [%0], [%1], 16;" ::"r"((dst ^ ((i & 1) * 576)) + (i >> 1) * 1024 + q * 8192), "l"(src + 128 * q) : "memory");
  }
  asm volatile("cp.async.wait_all;" ::: "memory");
  fence_proxy_async();
  __syncwarp();
  if (lane < 3) mbar_arrive(bar_x(sbase + kBarOff, 1, lane));
  __syncwarp();
}

__global__ void __launch_bounds__(384, 1)
nat_kernel(const __nv_bfloat16* __restrict__ x, __nv_bfloat16* out, const __nv_bfloat16* __restrict__ wqkv,
           const __nv_bfloat16* __restrict__ wo, uint8_t* wimg, const uint32_t zero,
           const __grid_constant__ Maps tm, const __grid_constant__ TileTable tt) {
  extern __shared__ uint8_t smem_raw[];
  constexpr uint32_t sbase = 1024;
  constexpr uint32_t bars = sbase + kBarOff;
  if (smem_u32(smem_raw) != sbase) __trap();
  const int tid = threadIdx.x;
  const uint32_t t_start = now_ns();
  if (tid == 0) GT(0);
  const int wid = __shfl_sync(0xffffffffu, tid >> 5, 0);
  const bool w2cta = blockIdx.x - 128 < 3 && wqkv != nullptr;
  if (wid >= 8) {
    asm volatile("setmaxnreg.dec.sync.aligned.u32 24;");
    const int c = wid & 3, lane = tid & 31;
    const int tile0 = blockIdx.x * kTilesPerCta, nt = num_tiles();
    uint32_t w2o = 0;
    if (c == 3) {
      if (elect_one()) wait_clock(t_start, NAT_TM);
      __syncwarp();
      asm volatile("prefetch.tensormap [%0];" ::"l"((uint64_t)tm.px) : "memory");
      asm volatile("prefetch.tensormap [%0];" ::"l"((uint64_t)&tm.v6) : "memory");
      asm volatile("prefetch.tensormap [%0];" ::"l"((uint64_t)&tm.v2) : "memory");
      asm volatile("prefetch.tensormap [%0];" ::"l"((uint64_t)(tm.px + (blockIdx.x < 112 ? 5 : 6))) : "memory");
      asm volatile("prefetch.tensormap [%0];" ::"l"((uint64_t)(tm.px + 7)) : "memory");
      if (nt < 6) {
        asm volatile("prefetch.tensormap [%0];" ::"l"((uint64_t)(tm.px + 1)) : "memory");
        asm volatile("prefetch.tensormap [%0];" ::"l"((uint64_t)(tm.px + 2)) : "memory");
        asm volatile("prefetch.tensormap [%0];" ::"l"((uint64_t)&tm.v14) : "memory");
        asm volatile("prefetch.tensormap [%0];" ::"l"((uint64_t)&tm.u8) : "memory");
      }
      __nanosleep(NAT_TW2 - 2800);
      asm volatile("bar.sync 4, 64;" ::: "memory");
      w2o = w2_offset();
      if (elect_one()) {
        mbar_arrive_expect_tx(bar_w2a(bars), kWChunk);
        mbar_arrive_expect_tx(bar_w2(bars), kWChunk);
        wait_clock(t_start, NAT_TW2);
        bulk_load(sbase + kW2Off, wimg + w2o, kWChunk, bar_w2a(bars));
        mbar_wait(bar_xf(bars), 0);
        bulk_load(sbase + kW2Off + 2 * kWChunk, wimg + (w2o + 2 * kWChunk), kWChunk, bar_w2(bars));
      }
      __syncwarp();
      if (nt < 6) gather_px(x, sbase, decode_tile(tt, tile0 + 2));
      if (wqkv == nullptr) return;
      mbar_wait(bar_wok(bars), 0);
      if (lane == 0) asm volatile("red.relaxed.gpu.global.add.u32 [%0], 1;" ::"l"(g_flag) : "memory");
      if (blockIdx.x >= 48) return;
      if (lane == 0) {
        uint32_t v, it = 0;
        do {
          __nanosleep(2000);
          asm volatile("ld.relaxed.gpu.global.u32 %0, [%1];" : "=r"(v) : "l"(g_flag) : "memory");
        } while (v < gridDim.x && ++it < (1u << 16));
      }
      __syncwarp();
#pragma unroll
      for (int i = 0; i < 6; i++)
        stg128(wimg + ((i < 3 ? 0u : 3 * kWBytes - w2o) + blockIdx.x * 1536 + (i % 3) * 512 + lane * 16), kEmpty, kEmpty, kEmpty, kEmpty);
      if (lane == 0 && atomicAdd(g_flag + 32, 1u) == 47) {
        g_flag[0] = g_flag[32] = 0;
        g_flag[64] = w2o == kWBytes;
      }
      return;
    }
    if (!elect_one()) return;
    if (c == 0) {
      for (int i = 0; i < kNumBars; i++)
        if ((i != 0 && i != 10 || nt < 6) && (i != 21 || !w2cta)) mbar_init(bars + i * 8, i == 13 || i == 16 ? 4 : 1);
      asm volatile("st.shared.v2.u32 [%0], {%1,%1};" ::"r"(bars + 192), "r"(0) : "memory");
      asm volatile("fence.mbarrier_init.release.cluster;" ::: "memory");
      if (w2cta) asm volatile("bar.sync 10, 64;" ::: "memory");
      asm volatile("bar.arrive 0, 160;" ::: "memory");
      asm volatile("bar.arrive 14, 160;" ::: "memory");
      asm volatile("bar.arrive 13, 96;" ::: "memory");
      asm volatile("bar.arrive 4, 64;" ::: "memory");
      const TileCoord tc0 = decode_tile(tt, tile0);
      const HaloCols hc = halo_cols(tc0);
      const int h0 = halo_r0(tc0);
#pragma unroll
      for (int j = 0; j < 3; j++)
        if (j > 0 || nt < 6) mbar_arrive_expect_tx(bar_full(bars, 0, j), 2 * kChunkBytes);
      wait_clock(t_start, NAT_HP);
#pragma unroll
      for (int q = 8; q < 24 && !w2cta; q += 8) {
        tma_prefetch_5d(blockIdx.x < 112 ? &tm.v6 : &tm.v14, 24 * tc0.pc + q, hc.vj, hc.vc, tc0.pr, h0 + (tc0.up || blockIdx.x >= 112 ? 0 : 8));
        tma_prefetch_5d(&tm.u8, 24 * tc0.pc + q, hc.uj, h0 + (tc0.up ? 0 : 6), tc0.pr, hc.uc);
      }
#pragma unroll 1
      for (int i = nt < 6 ? 0 : 2; i < 6; i++) {
        if (i == 2) mbar_wait(bar_w1q(bars), 0);
        first_halo(tm, sbase, tc0, i);
      }
      mbar_arrive(bar_go(bars));
      w2o = w2_offset();
    } else {
      asm volatile("bar.sync 13, 96;" ::: "memory");
      if (c == 2) {
        if (wqkv != nullptr && blockIdx.x < 131) asm volatile("bar.sync 12, 64;" ::: "memory");
        const uint32_t c0 = clock();
        while ((uint32_t)clock() - c0 < NAT_TD && nt == 6) { }
        wait_clock(t_start, NAT_T0);
#pragma unroll
        for (int j = 0; j < 3; j++) {
          mbar_arrive_expect_tx(bar_w1c(bars, j), kWChunk);
          bulk_load(sbase + kW1Off + j * kWChunk, wimg + j * kWChunk, kWChunk, bar_w1c(bars, j));
        }
        mbar_arrive(bar_w1q(bars));
        GT(2);
      } else {
#pragma unroll 1
        for (int j = nt == 6; j < 2; j++) {
          const TileCoord tc = decode_tile(tt, tile0 + j);
          const int line = first_line(tc);
          if (j == 1) mbar_wait(bar_go(bars), 0);
          if (j == 0) GT(15);
#pragma unroll 1
          for (int q = 0; q < 3; q++) {
            load_px(tm, tt, sbase + x_chunk(j, q), bar_x(bars, j, q), line + q, tc.kind);
            if (j == 1 || q == 0) mbar_arrive_expect_tx(bar_x(bars, j, q), j ? 8192 : kWChunk);
          }
          if (j == 0) GT(16);
        }
        w2o = w2_offset();
        wait_clock(t_start, NAT_TW2);
        mbar_wait(bar_xf(bars), 0);
      }
    }
#pragma unroll 1
    for (int k = 1; k < nt; k++) {
      const TileCoord tn = decode_tile(tt, tile0 + k + 1);
      const int line = first_line(tn);
      const bool more = k + 1 < nt && (k > 1 || nt == 6);
      if (c == 1) {
#pragma unroll
        for (int q = 0; q < 3; q++) {
          nb_sync_p(q == 0 ? 0 : q == 1 ? 14 : 6);
          bulk_load(sbase + x_chunk(k, q), wimg + (w2o + x_chunk(k, q) - kW2Off), 8192, bar_w2m(bars));
        }
        mbar_arrive_expect_tx(bar_w2m(bars), kWChunk);
      }
      if (c == 2) {
        if (k == 1) wait_clock(t_start, NAT_TX2);
        else __nanosleep(NAT_PFD);
#pragma unroll 1
        for (int q = 0; q < 3 && more; q++) load_px(tm, tt, 0, 0, line + q, tn.kind);
      }
      if (c == 2 && (blockIdx.x >= 112 || k == 5)) {
        const TileCoord tc = decode_tile(tt, tile0 + k);
        const HaloCols hc = halo_cols(tc);
        const int h8 = halo_r0(tc) + (tc.up ? 0 : 6);
#pragma unroll 1
        for (int q = 0; q < 24; q += 8) {
          tma_prefetch_5d(&tm.v6, 24 * tc.pc + q, hc.vj, hc.vc, tc.pr, h8);
          tma_prefetch_5d(&tm.v2, 24 * tc.pc + q, hc.vj, hc.vc, tc.pr, h8 + 6);
          tma_prefetch_5d(&tm.u8, 24 * tc.pc + q, hc.uj, h8, tc.pr, hc.uc);
        }
      }
      load_halo(tm, sbase, bars, decode_tile(tt, tile0 + k), k, c);
      if (c == 0 && more) {
#pragma unroll
        for (int q = 0; q < 3; q++) {
          if (q < 2) nb_sync_p(q ? 5 : 13);
          load_px(tm, tt, sbase + x_chunk(k + 1, q), bar_x(bars, 1, q), line + q, tn.kind);
          if (q != 1) mbar_arrive_expect_tx(bar_x(bars, 1, q), 8192);
        }
        mbar_arrive_expect_tx(bar_x(bars, 1, 1), 8192);
        PROFS(16, 2, k * 4 + 3);
      }
      if (c == 0 && k >= 2) {
        const TileCoord tp = decode_tile(tt, tile0 + k - 2);
        const int lp = first_line(tp);
        nb_sync_p(10);
        __nanosleep(NAT_XW);
        store_px(tm, tt, sbase + out_slot(k, nt), lp, tp.kind);
        if (k + 1 < nt) {
          asm volatile("cp.async.bulk.wait_group.read 0;" ::: "memory");
          bulk_load(sbase + out_slot(k, nt), wimg + (w2o + out_slot(k, nt) - kW2Off), kWChunk, bar_w2(bars));
          mbar_arrive_expect_tx(bar_w2(bars), kWChunk);
        }
      }
    }
    asm volatile("cp.async.bulk.wait_group 0;" ::: "memory");
  } else {
    if (blockIdx.x < 128) {
      if ((wid == 4 || (wid == 5 && blockIdx.x - 2 < 16)) && wqkv != nullptr) {
        fold_w1(blockIdx.x - 2 < 16 ? 2 * blockIdx.x + wid - 6 : blockIdx.x + (blockIdx.x < 2 ? 0 : 16), wqkv, wimg);
        if (wid == 4) asm volatile("bar.arrive 12, 64;" ::: "memory");
        if (tid == 128) GT(7);
      }
      sched_fence();
      if (wid == 1 && elect_one()) {
        const TileCoord tc = decode_tile(tt, blockIdx.x * kTilesPerCta);
        mbar_init(bar_x(bars, 0, 0), 1);
        asm volatile("fence.mbarrier_init.release.cluster;" ::: "memory");
        mbar_arrive_expect_tx(bar_x(bars, 0, 0), kWChunk);
        GT(15);
#pragma unroll 1
        for (int q = 0; q < 3; q++) load_px(tm, tt, sbase + x_chunk(0, q), bar_x(bars, 0, 0), first_line(tc) + q, tc.kind);
        GT(16);
      }
      __syncwarp();
      sched_fence();
      if (wid == 2 && elect_one()) {
        const TileCoord tc = decode_tile(tt, blockIdx.x * kTilesPerCta);
        mbar_init(bar_full(bars, 0, 0), 1);
        asm volatile("fence.mbarrier_init.release.cluster;" ::: "memory");
        mbar_arrive_expect_tx(bar_full(bars, 0, 0), 2 * kChunkBytes);
        asm volatile("prefetch.tensormap [%0];" ::"l"((uint64_t)&tm.u8) : "memory");
        GT(17);
        first_halo(tm, sbase, tc, 0);
        first_halo(tm, sbase, tc, 1);
      }
      __syncwarp();
    }
    sched_fence();
    {
      if (w2cta) {
        const int q = blockIdx.x & 3;
        uint32_t w2o = 0;
        if (wid == 1 && elect_one()) {
          asm volatile("prefetch.tensormap [%0];" ::"l"((uint64_t)&tm.wo) : "memory");
#pragma unroll
          for (int j = 0; j < 3; j++) mbar_init(bar_raw(bars, j), 1);
          asm volatile("fence.mbarrier_init.release.cluster;" ::: "memory");
#pragma unroll
          for (int j = 0; j < 6; j++)
            asm volatile("cp.async.bulk.tensor.2d.shared::cluster.global.tile.mbarrier::complete_tx::bytes [%0], [%1, {%3, %4}], [%2];" ::"r"(
                             j < 3 ? sbase + j * 8192 : sbase + kW2Off + (j - 3) * kWChunk),
                         "l"((uint64_t)(j < 3 ? &tm.wv : &tm.wo)), "r"(bar_raw(bars, j < 3 ? 0 : j - 3)),
                         "r"(j < 3 ? 384 + 64 * j : 64 * (j - 3)), "r"(j < 3 ? 64 * q : 0) : "memory");
#pragma unroll
          for (int j = 0; j < 3; j++) mbar_arrive_expect_tx(bar_raw(bars, j), j ? kWChunk : 2 * kWChunk);
          w2o = w2_offset();
        }
        __syncwarp();
#pragma unroll 1
        for (int r = 0; r < 3; r++) {
          const int blk = 2 * r - 2 + (wid >> 2);
          if (blk < 3) {
            if (r > 0) {
              mbar_wait(bar_raw(bars, 0), 0);
              mbar_wait(bar_raw(bars, blk), 0);
            }
            if (tid == 0 && r == 1) GT(7);
            float acc[32];
            const uint64_t db = make_desc(sbase + kW2Off + max(blk, 0) * kWChunk, kWChunk, 1024);
            wg_fence();
            wg_m64tz<0, 32>(acc, make_desc(sbase, 16, 1024), db, 0);
#pragma unroll
            for (int s = 1; s < 12; s++) wg_m64t<0, 32>(acc, make_desc(sbase + (s >> 2) * 8192 + (s & 3) * 32, 16, 1024), db + s * 128, 1);
            wg_commit();
            wg_wait<0>();
            fence_regs(acc);
            if (tid == 0) GT(19);
            const int m = (tid >> 3) & 3;
#pragma unroll
            for (int j = 0; j < 8; j += 2) {
              const int n = g2_inv(8 * (j + (m >> 1)) + (tid & 7));
              asm volatile("stmatrix.sync.aligned.m8n8.x4.trans.shared.b16 [%0], {%1,%2,%3,%4};" ::"r"(
                               sbase + kW1Off + (blk + 2) * 8192 + n * 128 + (((2 * (wid & 3) + (m & 1)) ^ (n & 7)) << 4)),
                           "r"(pack_bf16(acc[4 * j], acc[4 * j + 1])), "r"(pack_bf16(acc[4 * j + 2], acc[4 * j + 3])),
                           "r"(pack_bf16(acc[4 * j + 4], acc[4 * j + 5])), "r"(pack_bf16(acc[4 * j + 6], acc[4 * j + 7])) : "memory");
            }
            fence_proxy_async();
          }
          if (tid == 0) GT(18);
          asm volatile("bar.sync 11, 256;" ::: "memory");
          if (wid == 1 && elect_one()) {
            asm volatile("{\n.reg .pred p;\nsetp.ne.s32 p, %3, 0;\n@p cp.async.bulk.global.shared::cta.bulk_group [%0], [%1], %2;\n}\n" ::"l"(
                             wimg + (w2o + w2piece(r >> 1, q) * (kWChunk / 2))),
                         "r"(sbase + kW1Off + 16384 + (r >> 1) * (kWChunk / 2)), "r"(kWChunk / 2), "r"(r) : "memory");
            asm volatile("cp.async.bulk.commit_group;" ::: "memory");
          }
          __syncwarp();
        }
        if (wid == 1) {
          asm volatile("bar.arrive 10, 64;" ::: "memory");
          if (elect_one()) asm volatile("cp.async.bulk.wait_group.read 0;" ::: "memory");
          if (tid == 32) GT(31);
          __syncwarp();
          asm volatile("bar.arrive 12, 64;" ::: "memory");
        }
      }
    }
    __syncwarp();
    if (wid < 4) asm volatile("bar.sync 0, 160;" ::: "memory");
    else asm volatile("bar.sync 14, 160;" ::: "memory");
    asm volatile("setmaxnreg.inc.sync.aligned.u32 240;");
    consumer(wid >> 2, out, wimg, sbase, zero, tm, tt);
  }
}

}

typedef CUresult (*PFN_encodeTiled)(CUtensorMap*, CUtensorMapDataType, cuuint32_t, void*, const cuuint64_t*,
                                    const cuuint64_t*, const cuuint32_t*, const cuuint32_t*, CUtensorMapInterleave,
                                    CUtensorMapSwizzle, CUtensorMapL2promotion, CUtensorMapFloatOOBfill);

extern "C" void kernel_launch(void* const* d_in, const int* in_sizes, int n_in, void* d_out, int out_size) {
  const __nv_bfloat16* x = (const __nv_bfloat16*)d_in[0];
  const __nv_bfloat16* wqkv = (const __nv_bfloat16*)d_in[1];
  const __nv_bfloat16* wo = (const __nv_bfloat16*)d_in[2];
  __nv_bfloat16* out = (__nv_bfloat16*)d_out;

  static PFN_encodeTiled encode = nullptr;
  static int num_sms = 0;
  static uint8_t* wimg = nullptr;
  if (!encode) {
    void* fn = nullptr;
    cudaDriverEntryPointQueryResult qres;
    cudaGetDriverEntryPoint("cuTensorMapEncodeTiled", &fn, cudaEnableDefault, &qres);
    encode = (PFN_encodeTiled)fn;
    cudaFuncSetAttribute(nat::nat_kernel, cudaFuncAttributeMaxDynamicSharedMemorySize, nat::kSmemBytes);
    cudaGetSymbolAddress((void**)&wimg, nat::g_wimg32);
    int dev = 0;
    cudaGetDevice(&dev);
    cudaDeviceGetAttribute(&num_sms, cudaDevAttrMultiProcessorCount, dev);
  }
  nat::Maps tm;
  cuuint32_t estr[5] = {1, 1, 1, 1, 1};
  {
    cuuint64_t vdim[5] = {48, 2, 105, 2, 112}, udim[5] = {48, 2, 112, 2, 105};
    cuuint64_t vstr[4] = {7 * 768, 768, 224 * 384, 2 * 224 * 384}, ustr[4] = {7 * 768, 2 * 224 * 384, 224 * 384, 768};
    CUtensorMap* maps[4] = {&tm.v6, &tm.v2, &tm.v14, &tm.u8};
    for (int i = 0; i < 4; i++) {
      cuuint32_t box[5] = {4, 2, i < 3 ? 4u : 8u, 1, i == 0 ? 6u : i == 1 ? 2u : i == 2 ? 14u : 3u};
      encode(maps[i], CU_TENSOR_MAP_DATA_TYPE_UINT32, 5, (void*)x, i < 3 ? vdim : udim, i < 3 ? vstr : ustr, box, estr,
             CU_TENSOR_MAP_INTERLEAVE_16B, CU_TENSOR_MAP_SWIZZLE_128B, CU_TENSOR_MAP_L2_PROMOTION_L2_128B, CU_TENSOR_MAP_FLOAT_OOB_FILL_NONE);
    }
  }
  for (int i = 0; i < 8; i++) {
    const cuuint32_t row = 224 * 384;
    const cuuint32_t shape[8][6] = {{2, 8, 4, 2 * row, 768, 4 * row}, {2, 8, 3, row, 768, 2 * row},     {2, 8, 1, 2 * row, 768, 4 * row},
                                    {8, 2, 3, 2 * row, 4 * 384, 384}, {8, 2, 1, 2 * row, 5 * 384, 384}, {4, 2, 3, 4 * row, 2 * row, 128},
                                    {4, 2, 3, 768, row, 128},         {4, 2, 3, 768, 2 * row, 128}};
    const cuuint32_t* sh = shape[i];
    cuuint64_t dim[5] = {64, sh[0], sh[1], sh[2], 224 * 224 * 3};
    cuuint64_t str[4] = {sh[3], sh[4], sh[5], 128};
    cuuint32_t box[5] = {64, sh[0], sh[1], sh[2], 1};
    encode(tm.px + i, CU_TENSOR_MAP_DATA_TYPE_BFLOAT16, 5, i < 5 ? (void*)x : (void*)out, dim, str, box, estr, CU_TENSOR_MAP_INTERLEAVE_NONE,
           CU_TENSOR_MAP_SWIZZLE_128B, i < 5 ? CU_TENSOR_MAP_L2_PROMOTION_L2_128B : CU_TENSOR_MAP_L2_PROMOTION_NONE,
           CU_TENSOR_MAP_FLOAT_OOB_FILL_NONE);
  }
  for (int i = 0; i < 2; i++) {
    cuuint64_t dim[2] = {i ? 192u : 576u, 192}, str[1] = {i ? 384u : 1152u};
    cuuint32_t box[2] = {64, i ? 192u : 64u};
    encode(i ? &tm.wo : &tm.wv, CU_TENSOR_MAP_DATA_TYPE_BFLOAT16, 2, i ? (void*)wo : (void*)wqkv, dim, str, box, estr,
           CU_TENSOR_MAP_INTERLEAVE_NONE, CU_TENSOR_MAP_SWIZZLE_128B, CU_TENSOR_MAP_L2_PROMOTION_L2_256B, CU_TENSOR_MAP_FLOAT_OOB_FILL_NONE);
  }
  nat::TileTable tt;
  nat::make_tiles(tt);
  const int grid = nat::kCtas;
  if (num_sms >= grid) {
    nat::nat_kernel<<<grid, 384, nat::kSmemBytes>>>(x, out, wqkv, wo, wimg, 0u, tm, tt);
  } else {
    nat::fold_kernel<<<27, 256>>>(wqkv, wo, wimg);
    nat::nat_kernel<<<grid, 384, nat::kSmemBytes>>>(x, out, nullptr, nullptr, wimg, 0u, tm, tt);
  }
}
```

```cpp
#include <cuda_runtime.h>
#include <cuda_bf16.h>
#include <cuda.h>
#include <stdint.h>

#define NAT_TM 1300
#define NAT_HP 1800
#define NAT_T0 2130
#define NAT_TD 1250
#define NAT_TX2 3800
#define NAT_TW2 4680
#define NAT_PFD 300
#define NAT_XW 200
#define NAT_PK 3
namespace nat {

constexpr int kW = 224, kC = 192;
constexpr int kCtas = 132;
constexpr int kTilesPerCta = 6;
constexpr float kAlpha = 0.07216878364870322f * 1.4426950408889634f;
constexpr uint32_t kChunkBytes = 13 * 1024;
constexpr uint32_t kWChunk = 192 * 128;
constexpr uint32_t kWBytes = 3 * kWChunk;
constexpr uint32_t kW1Off = 6 * kChunkBytes;
constexpr uint32_t kW2Off = kW1Off + kWBytes;
constexpr uint32_t kXOff = kW2Off + kWChunk;
constexpr uint32_t kBarOff = kW2Off + kWBytes;
constexpr uint32_t kProfOff = kBarOff + 208;
constexpr uint32_t kSmemBytes = kBarOff + 1024 + 4096;

static_assert(kW1Off % 1024 == 0 && kW2Off % 1024 == 0 && kChunkBytes % 1024 == 0, "swizzle alignment");
static_assert(kSmemBytes <= 232448, "smem");

constexpr uint32_t kEmpty = 0xFFFFFFFFu;
#define NAT_R8(v) v, v, v, v, v, v, v, v
#define NAT_R2K(v) NAT_R8(NAT_R8(NAT_R8(v))), NAT_R8(NAT_R8(NAT_R8(v))), NAT_R8(NAT_R8(NAT_R8(v))), NAT_R8(NAT_R8(NAT_R8(v)))
#define NAT_IMG NAT_R8(NAT_R2K(kEmpty)), NAT_R2K(kEmpty)
__device__ __align__(1024) uint32_t g_wimg32[3 * kWBytes / 4] = {NAT_IMG, NAT_IMG, NAT_IMG};
static_assert(kWBytes / 4 == 9 * 2048, "initialiser");
__device__ __align__(128) uint32_t g_flag[64];
__device__ __forceinline__ uint32_t w2_offset() {
  uint32_t v;
  asm volatile("ld.relaxed.gpu.global.u32 %0, [%1];" : "=r"(v) : "l"(g_flag + 32) : "memory");
  return (1 + v) * kWBytes;
}

#define PROFS(id, wgid, slotid) do { } while (0)
#define PROF(wgid, slotid) do { } while (0)
#define PROF_DUMP(wgid) do { } while (0)

#define GT(slotid) do { } while (0)
#define GT_DUMP() do { } while (0)

__device__ __forceinline__ uint32_t smem_u32(const void* p) { return (uint32_t)__cvta_generic_to_shared(p); }

__device__ __forceinline__ void mbar_init(uint32_t bar, uint32_t count) {
  asm volatile("mbarrier.init.shared::cta.b64 [%0], %1;" ::"r"(bar), "r"(count) : "memory");
}
__device__ __forceinline__ void mbar_arrive(uint32_t bar) {
  asm volatile("mbarrier.arrive.shared::cta.b64 _, [%0];" ::"r"(bar) : "memory");
}
__device__ __forceinline__ void mbar_arrive_expect_tx(uint32_t bar, uint32_t bytes) {
  asm volatile("mbarrier.arrive.expect_tx.shared::cta.b64 _, [%0], %1;" ::"r"(bar), "r"(bytes) : "memory");
}
__device__ __forceinline__ void mbar_wait(uint32_t bar, uint32_t parity) {
  uint32_t ok;
  uint32_t it = 0;
  do {
    asm volatile(
        "{\n.reg .pred p;\n"
        "mbarrier.try_wait.parity.shared::cta.b64 p, [%1], %2;\n"
        "selp.u32 %0, 1, 0, p;\n}\n"
        : "=r"(ok)
        : "r"(bar), "r"(parity)
        : "memory");
    if (++it > (1u << 24)) break;
  } while (!ok);
}
__device__ __forceinline__ uint32_t mbar_test(uint32_t bar, uint32_t parity) {
  uint32_t ok;
  asm volatile("{\n.reg .pred p;\nmbarrier.test_wait.parity.shared::cta.b64 p, [%1], %2;\nselp.u32 %0, 1, 0, p;\n}\n"
               : "=r"(ok) : "r"(bar), "r"(parity) : "memory");
  return ok;
}
__device__ __forceinline__ void mbar_wait_if(uint32_t ok, uint32_t bar, uint32_t parity) {
  if (!__all_sync(0xffffffffu, ok)) mbar_wait(bar, parity);
}
__device__ __forceinline__ bool elect_one() {
  uint32_t r;
  asm volatile("{\n.reg .pred p;\nelect.sync _|p, 0xffffffff;\nselp.u32 %0, 1, 0, p;\n}\n" : "=r"(r));
  return r != 0;
}
__device__ __forceinline__ void nb_arrive(int id) { asm volatile("bar.arrive %0, 256;" ::"r"(id) : "memory"); }
__device__ __forceinline__ void nb_sync(int id) { asm volatile("bar.sync %0, 256;" ::"r"(id) : "memory"); }
__device__ __forceinline__ void nb_arrive_p(int id) { asm volatile("bar.arrive %0, 160;" ::"r"(id) : "memory"); }
__device__ __forceinline__ void nb_sync_p(int id) { asm volatile("bar.sync %0, 160;" ::"r"(id) : "memory"); }
__device__ __forceinline__ void fence_proxy_async() { asm volatile("fence.proxy.async.shared::cta;" ::: "memory"); }

__device__ __forceinline__ void tma_load_5d(uint32_t dst, const CUtensorMap* map, uint32_t bar, int c0, int c1, int c2,
                                            int c3, int c4) {
  asm volatile(
      "cp.async.bulk.tensor.5d.shared::cluster.global.tile.mbarrier::complete_tx::bytes "
      "[%0], [%1, {%3, %4, %5, %6, %7}], [%2];"
      ::"r"(dst), "l"((uint64_t)map), "r"(bar), "r"(c0), "r"(c1), "r"(c2), "r"(c3), "r"(c4)
      : "memory");
}
__device__ __forceinline__ void bulk_load(uint32_t dst, const void* src, uint32_t bytes, uint32_t bar) {
  asm volatile("cp.async.bulk.shared::cluster.global.mbarrier::complete_tx::bytes [%0], [%1], %2, [%3];"
               ::"r"(dst), "l"((uint64_t)src), "r"(bytes), "r"(bar)
               : "memory");
}

__device__ __forceinline__ void wg_fence() { asm volatile("wgmma.fence.sync.aligned;" ::: "memory"); }
__device__ __forceinline__ void wg_commit() { asm volatile("wgmma.commit_group.sync.aligned;" ::: "memory"); }
template <int N>
__device__ __forceinline__ void wg_wait() { asm volatile("wgmma.wait_group.sync.aligned %0;" ::"n"(N) : "memory"); }

template <int N>
__device__ __forceinline__ void fence_regs(float (&d)[N]) {
#pragma unroll
  for (int i = 0; i < N; i++) asm volatile("" : "+f"(d[i])::"memory");
}
template <int N>
__device__ __forceinline__ void keep_regs(uint32_t (&d)[N]) {
#pragma unroll
  for (int i = 0; i < N; i++) asm volatile("" : "+r"(d[i])::"memory");
}

__device__ __forceinline__ uint32_t pack_bf16(float lo, float hi) {
  uint32_t d;
  asm("cvt.rn.bf16x2.f32 %0, %1, %2;" : "=r"(d) : "f"(hi), "f"(lo));
  return d;
}
__device__ __forceinline__ float ex2(float x) {
  float y;
  asm("ex2.approx.ftz.f32 %0, %1;" : "=f"(y) : "f"(x));
  return y;
}
__device__ __forceinline__ float rcp_approx(float x) {
  float y;
  asm("rcp.approx.ftz.f32 %0, %1;" : "=f"(y) : "f"(x));
  return y;
}
__device__ __forceinline__ uint4 ldg128_nc(const void* p) {
  uint4 v;
  asm volatile("ld.global.nc.v4.u32 {%0,%1,%2,%3}, [%4];" : "=r"(v.x), "=r"(v.y), "=r"(v.z), "=r"(v.w) : "l"(p));
  return v;
}

__device__ __forceinline__ long long clk64() {
  long long c;
  asm volatile("mov.u64 %0, %clock64;" : "=l"(c)::"memory");
  return c;
}
__device__ __forceinline__ void sched_fence() { while (clk64() < 0) { } }

__device__ __forceinline__ uint64_t make_desc(uint32_t addr, uint32_t lbo, uint32_t sbo, uint32_t mode = 1) {
  return (uint64_t)((addr & 0x3FFFF) >> 4) | ((uint64_t)(lbo >> 4) << 16) | ((uint64_t)(sbo >> 4) << 32) |
         ((uint64_t)mode << 62);
}

template <int OFF, int NN>
__device__ __forceinline__ void wg_m192(float (&d)[NN], uint64_t desc_a, uint64_t desc_b, int scale_d) {
  asm volatile(
      "{\n.reg .pred p;\nsetp.ne.b32 p, %98, 0;\n"
      "wgmma.mma_async.sync.aligned.m64n192k16.f32.bf16.bf16 "
      "{%0,%1,%2,%3,%4,%5,%6,%7,%8,%9,%10,%11,%12,%13,%14,%15,"
      "%16,%17,%18,%19,%20,%21,%22,%23,%24,%25,%26,%27,%28,%29,%30,%31,"
      "%32,%33,%34,%35,%36,%37,%38,%39,%40,%41,%42,%43,%44,%45,%46,%47,"
      "%48,%49,%50,%51,%52,%53,%54,%55,%56,%57,%58,%59,%60,%61,%62,%63,"
      "%64,%65,%66,%67,%68,%69,%70,%71,%72,%73,%74,%75,%76,%77,%78,%79,"
      "%80,%81,%82,%83,%84,%85,%86,%87,%88,%89,%90,%91,%92,%93,%94,%95}, "
      "%96, %97, p, 1, 1, 0, 0;\n}\n"
      : "+f"(d[OFF + 0]), "+f"(d[OFF + 1]), "+f"(d[OFF + 2]), "+f"(d[OFF + 3]), "+f"(d[OFF + 4]), "+f"(d[OFF + 5]),
        "+f"(d[OFF + 6]), "+f"(d[OFF + 7]), "+f"(d[OFF + 8]), "+f"(d[OFF + 9]), "+f"(d[OFF + 10]), "+f"(d[OFF + 11]),
        "+f"(d[OFF + 12]), "+f"(d[OFF + 13]), "+f"(d[OFF + 14]), "+f"(d[OFF + 15]), "+f"(d[OFF + 16]), "+f"(d[OFF + 17]),
        "+f"(d[OFF + 18]), "+f"(d[OFF + 19]), "+f"(d[OFF + 20]), "+f"(d[OFF + 21]), "+f"(d[OFF + 22]), "+f"(d[OFF + 23]),
        "+f"(d[OFF + 24]), "+f"(d[OFF + 25]), "+f"(d[OFF + 26]), "+f"(d[OFF + 27]), "+f"(d[OFF + 28]), "+f"(d[OFF + 29]),
        "+f"(d[OFF + 30]), "+f"(d[OFF + 31]), "+f"(d[OFF + 32]), "+f"(d[OFF + 33]), "+f"(d[OFF + 34]), "+f"(d[OFF + 35]),
        "+f"(d[OFF + 36]), "+f"(d[OFF + 37]), "+f"(d[OFF + 38]), "+f"(d[OFF + 39]), "+f"(d[OFF + 40]), "+f"(d[OFF + 41]),
        "+f"(d[OFF + 42]), "+f"(d[OFF + 43]), "+f"(d[OFF + 44]), "+f"(d[OFF + 45]), "+f"(d[OFF + 46]), "+f"(d[OFF + 47]),
        "+f"(d[OFF + 48]), "+f"(d[OFF + 49]), "+f"(d[OFF + 50]), "+f"(d[OFF + 51]), "+f"(d[OFF + 52]), "+f"(d[OFF + 53]),
        "+f"(d[OFF + 54]), "+f"(d[OFF + 55]), "+f"(d[OFF + 56]), "+f"(d[OFF + 57]), "+f"(d[OFF + 58]), "+f"(d[OFF + 59]),
        "+f"(d[OFF + 60]), "+f"(d[OFF + 61]), "+f"(d[OFF + 62]), "+f"(d[OFF + 63]), "+f"(d[OFF + 64]), "+f"(d[OFF + 65]),
        "+f"(d[OFF + 66]), "+f"(d[OFF + 67]), "+f"(d[OFF + 68]), "+f"(d[OFF + 69]), "+f"(d[OFF + 70]), "+f"(d[OFF + 71]),
        "+f"(d[OFF + 72]), "+f"(d[OFF + 73]), "+f"(d[OFF + 74]), "+f"(d[OFF + 75]), "+f"(d[OFF + 76]), "+f"(d[OFF + 77]),
        "+f"(d[OFF + 78]), "+f"(d[OFF + 79]), "+f"(d[OFF + 80]), "+f"(d[OFF + 81]), "+f"(d[OFF + 82]), "+f"(d[OFF + 83]),
        "+f"(d[OFF + 84]), "+f"(d[OFF + 85]), "+f"(d[OFF + 86]), "+f"(d[OFF + 87]), "+f"(d[OFF + 88]), "+f"(d[OFF + 89]),
        "+f"(d[OFF + 90]), "+f"(d[OFF + 91]), "+f"(d[OFF + 92]), "+f"(d[OFF + 93]), "+f"(d[OFF + 94]), "+f"(d[OFF + 95])
      : "l"(desc_a), "l"(desc_b), "r"(scale_d));
}

template <int OFF, int NN>
__device__ __forceinline__ void wg_m192z(float (&d)[NN], uint64_t desc_a, uint64_t desc_b, int scale_d) {
  asm volatile(
      "{\n.reg .pred p;\nsetp.ne.b32 p, %98, 0;\n"
      "wgmma.mma_async.sync.aligned.m64n192k16.f32.bf16.bf16 "
      "{%0,%1,%2,%3,%4,%5,%6,%7,%8,%9,%10,%11,%12,%13,%14,%15,"
      "%16,%17,%18,%19,%20,%21,%22,%23,%24,%25,%26,%27,%28,%29,%30,%31,"
      "%32,%33,%34,%35,%36,%37,%38,%39,%40,%41,%42,%43,%44,%45,%46,%47,"
      "%48,%49,%50,%51,%52,%53,%54,%55,%56,%57,%58,%59,%60,%61,%62,%63,"
      "%64,%65,%66,%67,%68,%69,%70,%71,%72,%73,%74,%75,%76,%77,%78,%79,"
      "%80,%81,%82,%83,%84,%85,%86,%87,%88,%89,%90,%91,%92,%93,%94,%95}, "
      "%96, %97, p, 1, 1, 0, 0;\n}\n"
      : "=f"(d[OFF + 0]), "=f"(d[OFF + 1]), "=f"(d[OFF + 2]), "=f"(d[OFF + 3]), "=f"(d[OFF + 4]), "=f"(d[OFF + 5]),
        "=f"(d[OFF + 6]), "=f"(d[OFF + 7]), "=f"(d[OFF + 8]), "=f"(d[OFF + 9]), "=f"(d[OFF + 10]), "=f"(d[OFF + 11]),
        "=f"(d[OFF + 12]), "=f"(d[OFF + 13]), "=f"(d[OFF + 14]), "=f"(d[OFF + 15]), "=f"(d[OFF + 16]), "=f"(d[OFF + 17]),
        "=f"(d[OFF + 18]), "=f"(d[OFF + 19]), "=f"(d[OFF + 20]), "=f"(d[OFF + 21]), "=f"(d[OFF + 22]), "=f"(d[OFF + 23]),
        "=f"(d[OFF + 24]), "=f"(d[OFF + 25]), "=f"(d[OFF + 26]), "=f"(d[OFF + 27]), "=f"(d[OFF + 28]), "=f"(d[OFF + 29]),
        "=f"(d[OFF + 30]), "=f"(d[OFF + 31]), "=f"(d[OFF + 32]), "=f"(d[OFF + 33]), "=f"(d[OFF + 34]), "=f"(d[OFF + 35]),
        "=f"(d[OFF + 36]), "=f"(d[OFF + 37]), "=f"(d[OFF + 38]), "=f"(d[OFF + 39]), "=f"(d[OFF + 40]), "=f"(d[OFF + 41]),
        "=f"(d[OFF + 42]), "=f"(d[OFF + 43]), "=f"(d[OFF + 44]), "=f"(d[OFF + 45]), "=f"(d[OFF + 46]), "=f"(d[OFF + 47]),
        "=f"(d[OFF + 48]), "=f"(d[OFF + 49]), "=f"(d[OFF + 50]), "=f"(d[OFF + 51]), "=f"(d[OFF + 52]), "=f"(d[OFF + 53]),
        "=f"(d[OFF + 54]), "=f"(d[OFF + 55]), "=f"(d[OFF + 56]), "=f"(d[OFF + 57]), "=f"(d[OFF + 58]), "=f"(d[OFF + 59]),
        "=f"(d[OFF + 60]), "=f"(d[OFF + 61]), "=f"(d[OFF + 62]), "=f"(d[OFF + 63]), "=f"(d[OFF + 64]), "=f"(d[OFF + 65]),
        "=f"(d[OFF + 66]), "=f"(d[OFF + 67]), "=f"(d[OFF + 68]), "=f"(d[OFF + 69]), "=f"(d[OFF + 70]), "=f"(d[OFF + 71]),
        "=f"(d[OFF + 72]), "=f"(d[OFF + 73]), "=f"(d[OFF + 74]), "=f"(d[OFF + 75]), "=f"(d[OFF + 76]), "=f"(d[OFF + 77]),
        "=f"(d[OFF + 78]), "=f"(d[OFF + 79]), "=f"(d[OFF + 80]), "=f"(d[OFF + 81]), "=f"(d[OFF + 82]), "=f"(d[OFF + 83]),
        "=f"(d[OFF + 84]), "=f"(d[OFF + 85]), "=f"(d[OFF + 86]), "=f"(d[OFF + 87]), "=f"(d[OFF + 88]), "=f"(d[OFF + 89]),
        "=f"(d[OFF + 90]), "=f"(d[OFF + 91]), "=f"(d[OFF + 92]), "=f"(d[OFF + 93]), "=f"(d[OFF + 94]), "=f"(d[OFF + 95])
      : "l"(desc_a), "l"(desc_b), "r"(scale_d));
}

template <int OFF, int NN>
__device__ __forceinline__ void wg_m64t(float (&d)[NN], uint64_t desc_a, uint64_t desc_b, int scale_d) {
  asm volatile(
      "{\n.reg .pred p;\nsetp.ne.b32 p, %34, 0;\n"
      "wgmma.mma_async.sync.aligned.m64n64k16.f32.bf16.bf16 "
      "{%0,%1,%2,%3,%4,%5,%6,%7,%8,%9,%10,%11,%12,%13,%14,%15,"
      "%16,%17,%18,%19,%20,%21,%22,%23,%24,%25,%26,%27,%28,%29,%30,%31}, "
      "%32, %33, p, 1, 1, 0, 1;\n}\n"
      : "+f"(d[OFF + 0]), "+f"(d[OFF + 1]), "+f"(d[OFF + 2]), "+f"(d[OFF + 3]), "+f"(d[OFF + 4]), "+f"(d[OFF + 5]),
        "+f"(d[OFF + 6]), "+f"(d[OFF + 7]), "+f"(d[OFF + 8]), "+f"(d[OFF + 9]), "+f"(d[OFF + 10]), "+f"(d[OFF + 11]),
        "+f"(d[OFF + 12]), "+f"(d[OFF + 13]), "+f"(d[OFF + 14]), "+f"(d[OFF + 15]), "+f"(d[OFF + 16]), "+f"(d[OFF + 17]),
        "+f"(d[OFF + 18]), "+f"(d[OFF + 19]), "+f"(d[OFF + 20]), "+f"(d[OFF + 21]), "+f"(d[OFF + 22]), "+f"(d[OFF + 23]),
        "+f"(d[OFF + 24]), "+f"(d[OFF + 25]), "+f"(d[OFF + 26]), "+f"(d[OFF + 27]), "+f"(d[OFF + 28]), "+f"(d[OFF + 29]),
        "+f"(d[OFF + 30]), "+f"(d[OFF + 31])
      : "l"(desc_a), "l"(desc_b), "r"(scale_d));
}

template <int OFF, int NN>
__device__ __forceinline__ void wg_m64tz(float (&d)[NN], uint64_t desc_a, uint64_t desc_b, int scale_d) {
  asm volatile(
      "{\n.reg .pred p;\nsetp.ne.b32 p, %34, 0;\n"
      "wgmma.mma_async.sync.aligned.m64n64k16.f32.bf16.bf16 "
      "{%0,%1,%2,%3,%4,%5,%6,%7,%8,%9,%10,%11,%12,%13,%14,%15,"
      "%16,%17,%18,%19,%20,%21,%22,%23,%24,%25,%26,%27,%28,%29,%30,%31}, "
      "%32, %33, p, 1, 1, 0, 1;\n}\n"
      : "=f"(d[OFF + 0]), "=f"(d[OFF + 1]), "=f"(d[OFF + 2]), "=f"(d[OFF + 3]), "=f"(d[OFF + 4]), "=f"(d[OFF + 5]),
        "=f"(d[OFF + 6]), "=f"(d[OFF + 7]), "=f"(d[OFF + 8]), "=f"(d[OFF + 9]), "=f"(d[OFF + 10]), "=f"(d[OFF + 11]),
        "=f"(d[OFF + 12]), "=f"(d[OFF + 13]), "=f"(d[OFF + 14]), "=f"(d[OFF + 15]), "=f"(d[OFF + 16]), "=f"(d[OFF + 17]),
        "=f"(d[OFF + 18]), "=f"(d[OFF + 19]), "=f"(d[OFF + 20]), "=f"(d[OFF + 21]), "=f"(d[OFF + 22]), "=f"(d[OFF + 23]),
        "=f"(d[OFF + 24]), "=f"(d[OFF + 25]), "=f"(d[OFF + 26]), "=f"(d[OFF + 27]), "=f"(d[OFF + 28]), "=f"(d[OFF + 29]),
        "=f"(d[OFF + 30]), "=f"(d[OFF + 31])
      : "l"(desc_a), "l"(desc_b), "r"(scale_d));
}

template <int OFF, int NN>
__device__ __forceinline__ void wg_d96(float (&d)[NN], uint32_t a0, uint32_t a1, uint32_t a2, uint32_t a3,
                                       uint64_t desc_b, int scale_d) {
  asm volatile(
      "{\n.reg .pred p;\nsetp.ne.b32 p, %53, 0;\n"
      "wgmma.mma_async.sync.aligned.m64n96k16.f32.bf16.bf16 "
      "{%0,%1,%2,%3,%4,%5,%6,%7,%8,%9,%10,%11,%12,%13,%14,%15,"
      "%16,%17,%18,%19,%20,%21,%22,%23,%24,%25,%26,%27,%28,%29,%30,%31,"
      "%32,%33,%34,%35,%36,%37,%38,%39,%40,%41,%42,%43,%44,%45,%46,%47}, "
      "{%48,%49,%50,%51}, %52, p, 1, 1, 0;\n}\n"
      : "+f"(d[OFF + 0]), "+f"(d[OFF + 1]), "+f"(d[OFF + 2]), "+f"(d[OFF + 3]), "+f"(d[OFF + 4]), "+f"(d[OFF + 5]),
        "+f"(d[OFF + 6]), "+f"(d[OFF + 7]), "+f"(d[OFF + 8]), "+f"(d[OFF + 9]), "+f"(d[OFF + 10]), "+f"(d[OFF + 11]),
        "+f"(d[OFF + 12]), "+f"(d[OFF + 13]), "+f"(d[OFF + 14]), "+f"(d[OFF + 15]), "+f"(d[OFF + 16]), "+f"(d[OFF + 17]),
        "+f"(d[OFF + 18]), "+f"(d[OFF + 19]), "+f"(d[OFF + 20]), "+f"(d[OFF + 21]), "+f"(d[OFF + 22]), "+f"(d[OFF + 23]),
        "+f"(d[OFF + 24]), "+f"(d[OFF + 25]), "+f"(d[OFF + 26]), "+f"(d[OFF + 27]), "+f"(d[OFF + 28]), "+f"(d[OFF + 29]),
        "+f"(d[OFF + 30]), "+f"(d[OFF + 31]), "+f"(d[OFF + 32]), "+f"(d[OFF + 33]), "+f"(d[OFF + 34]), "+f"(d[OFF + 35]),
        "+f"(d[OFF + 36]), "+f"(d[OFF + 37]), "+f"(d[OFF + 38]), "+f"(d[OFF + 39]), "+f"(d[OFF + 40]), "+f"(d[OFF + 41]),
        "+f"(d[OFF + 42]), "+f"(d[OFF + 43]), "+f"(d[OFF + 44]), "+f"(d[OFF + 45]), "+f"(d[OFF + 46]), "+f"(d[OFF + 47])
      : "r"(a0), "r"(a1), "r"(a2), "r"(a3), "l"(desc_b), "r"(scale_d));
}

template <int OFF, int NN>
__device__ __forceinline__ void wg_d96z(float (&d)[NN], uint32_t a0, uint32_t a1, uint32_t a2, uint32_t a3,
                                       uint64_t desc_b, int scale_d) {
  asm volatile(
      "{\n.reg .pred p;\nsetp.ne.b32 p, %53, 0;\n"
      "wgmma.mma_async.sync.aligned.m64n96k16.f32.bf16.bf16 "
      "{%0,%1,%2,%3,%4,%5,%6,%7,%8,%9,%10,%11,%12,%13,%14,%15,"
      "%16,%17,%18,%19,%20,%21,%22,%23,%24,%25,%26,%27,%28,%29,%30,%31,"
      "%32,%33,%34,%35,%36,%37,%38,%39,%40,%41,%42,%43,%44,%45,%46,%47}, "
      "{%48,%49,%50,%51}, %52, p, 1, 1, 0;\n}\n"
      : "=f"(d[OFF + 0]), "=f"(d[OFF + 1]), "=f"(d[OFF + 2]), "=f"(d[OFF + 3]), "=f"(d[OFF + 4]), "=f"(d[OFF + 5]),
        "=f"(d[OFF + 6]), "=f"(d[OFF + 7]), "=f"(d[OFF + 8]), "=f"(d[OFF + 9]), "=f"(d[OFF + 10]), "=f"(d[OFF + 11]),
        "=f"(d[OFF + 12]), "=f"(d[OFF + 13]), "=f"(d[OFF + 14]), "=f"(d[OFF + 15]), "=f"(d[OFF + 16]), "=f"(d[OFF + 17]),
        "=f"(d[OFF + 18]), "=f"(d[OFF + 19]), "=f"(d[OFF + 20]), "=f"(d[OFF + 21]), "=f"(d[OFF + 22]), "=f"(d[OFF + 23]),
        "=f"(d[OFF + 24]), "=f"(d[OFF + 25]), "=f"(d[OFF + 26]), "=f"(d[OFF + 27]), "=f"(d[OFF + 28]), "=f"(d[OFF + 29]),
        "=f"(d[OFF + 30]), "=f"(d[OFF + 31]), "=f"(d[OFF + 32]), "=f"(d[OFF + 33]), "=f"(d[OFF + 34]), "=f"(d[OFF + 35]),
        "=f"(d[OFF + 36]), "=f"(d[OFF + 37]), "=f"(d[OFF + 38]), "=f"(d[OFF + 39]), "=f"(d[OFF + 40]), "=f"(d[OFF + 41]),
        "=f"(d[OFF + 42]), "=f"(d[OFF + 43]), "=f"(d[OFF + 44]), "=f"(d[OFF + 45]), "=f"(d[OFF + 46]), "=f"(d[OFF + 47])
      : "r"(a0), "r"(a1), "r"(a2), "r"(a3), "l"(desc_b), "r"(scale_d));
}

template <int OFF, int NN>
__device__ __forceinline__ void wg_s104(float (&d)[NN], uint32_t a0, uint32_t a1, uint32_t a2, uint32_t a3,
                                       uint64_t desc_b, int scale_d, uint32_t meta) {
  asm volatile(
      "{\n.reg .pred p;\nsetp.ne.b32 p, %57, 0;\n"
      "wgmma.mma_async.sp.sync.aligned.m64n104k32.f32.bf16.bf16 "
      "{%0,%1,%2,%3,%4,%5,%6,%7,%8,%9,%10,%11,%12,%13,%14,%15,"
      "%16,%17,%18,%19,%20,%21,%22,%23,%24,%25,%26,%27,%28,%29,%30,%31,"
      "%32,%33,%34,%35,%36,%37,%38,%39,%40,%41,%42,%43,%44,%45,%46,%47,"
      "%48,%49,%50,%51}, "
      "{%52,%53,%54,%55}, %56, %58, 0, p, 1, 1, 0;\n}\n"
      : "+f"(d[OFF + 0]), "+f"(d[OFF + 1]), "+f"(d[OFF + 2]), "+f"(d[OFF + 3]), "+f"(d[OFF + 4]), "+f"(d[OFF + 5]),
        "+f"(d[OFF + 6]), "+f"(d[OFF + 7]), "+f"(d[OFF + 8]), "+f"(d[OFF + 9]), "+f"(d[OFF + 10]), "+f"(d[OFF + 11]),
        "+f"(d[OFF + 12]), "+f"(d[OFF + 13]), "+f"(d[OFF + 14]), "+f"(d[OFF + 15]), "+f"(d[OFF + 16]), "+f"(d[OFF + 17]),
        "+f"(d[OFF + 18]), "+f"(d[OFF + 19]), "+f"(d[OFF + 20]), "+f"(d[OFF + 21]), "+f"(d[OFF + 22]), "+f"(d[OFF + 23]),
        "+f"(d[OFF + 24]), "+f"(d[OFF + 25]), "+f"(d[OFF + 26]), "+f"(d[OFF + 27]), "+f"(d[OFF + 28]), "+f"(d[OFF + 29]),
        "+f"(d[OFF + 30]), "+f"(d[OFF + 31]), "+f"(d[OFF + 32]), "+f"(d[OFF + 33]), "+f"(d[OFF + 34]), "+f"(d[OFF + 35]),
        "+f"(d[OFF + 36]), "+f"(d[OFF + 37]), "+f"(d[OFF + 38]), "+f"(d[OFF + 39]), "+f"(d[OFF + 40]), "+f"(d[OFF + 41]),
        "+f"(d[OFF + 42]), "+f"(d[OFF + 43]), "+f"(d[OFF + 44]), "+f"(d[OFF + 45]), "+f"(d[OFF + 46]), "+f"(d[OFF + 47]),
        "+f"(d[OFF + 48]), "+f"(d[OFF + 49]), "+f"(d[OFF + 50]), "+f"(d[OFF + 51])
      : "r"(a0), "r"(a1), "r"(a2), "r"(a3), "l"(desc_b), "r"(scale_d), "r"(meta));
}

template <int OFF, int NN>
__device__ __forceinline__ void wg_s104z(float (&d)[NN], uint32_t a0, uint32_t a1, uint32_t a2, uint32_t a3,
                                       uint64_t desc_b, int scale_d, uint32_t meta) {
  asm volatile(
      "{\n.reg .pred p;\nsetp.ne.b32 p, %57, 0;\n"
      "wgmma.mma_async.sp.sync.aligned.m64n104k32.f32.bf16.bf16 "
      "{%0,%1,%2,%3,%4,%5,%6,%7,%8,%9,%10,%11,%12,%13,%14,%15,"
      "%16,%17,%18,%19,%20,%21,%22,%23,%24,%25,%26,%27,%28,%29,%30,%31,"
      "%32,%33,%34,%35,%36,%37,%38,%39,%40,%41,%42,%43,%44,%45,%46,%47,"
      "%48,%49,%50,%51}, "
      "{%52,%53,%54,%55}, %56, %58, 0, p, 1, 1, 0;\n}\n"
      : "=f"(d[OFF + 0]), "=f"(d[OFF + 1]), "=f"(d[OFF + 2]), "=f"(d[OFF + 3]), "=f"(d[OFF + 4]), "=f"(d[OFF + 5]),
        "=f"(d[OFF + 6]), "=f"(d[OFF + 7]), "=f"(d[OFF + 8]), "=f"(d[OFF + 9]), "=f"(d[OFF + 10]), "=f"(d[OFF + 11]),
        "=f"(d[OFF + 12]), "=f"(d[OFF + 13]), "=f"(d[OFF + 14]), "=f"(d[OFF + 15]), "=f"(d[OFF + 16]), "=f"(d[OFF + 17]),
        "=f"(d[OFF + 18]), "=f"(d[OFF + 19]), "=f"(d[OFF + 20]), "=f"(d[OFF + 21]), "=f"(d[OFF + 22]), "=f"(d[OFF + 23]),
        "=f"(d[OFF + 24]), "=f"(d[OFF + 25]), "=f"(d[OFF + 26]), "=f"(d[OFF + 27]), "=f"(d[OFF + 28]), "=f"(d[OFF + 29]),
        "=f"(d[OFF + 30]), "=f"(d[OFF + 31]), "=f"(d[OFF + 32]), "=f"(d[OFF + 33]), "=f"(d[OFF + 34]), "=f"(d[OFF + 35]),
        "=f"(d[OFF + 36]), "=f"(d[OFF + 37]), "=f"(d[OFF + 38]), "=f"(d[OFF + 39]), "=f"(d[OFF + 40]), "=f"(d[OFF + 41]),
        "=f"(d[OFF + 42]), "=f"(d[OFF + 43]), "=f"(d[OFF + 44]), "=f"(d[OFF + 45]), "=f"(d[OFF + 46]), "=f"(d[OFF + 47]),
        "=f"(d[OFF + 48]), "=f"(d[OFF + 49]), "=f"(d[OFF + 50]), "=f"(d[OFF + 51])
      : "r"(a0), "r"(a1), "r"(a2), "r"(a3), "l"(desc_b), "r"(scale_d), "r"(meta));
}

template <int OFF, int NN>
__device__ __forceinline__ void wg_s48(float (&d)[NN], uint32_t a0, uint32_t a1, uint32_t a2, uint32_t a3,
                                       uint64_t desc_b, int scale_d, uint32_t meta) {
  asm volatile(
      "{\n.reg .pred p;\nsetp.ne.b32 p, %29, 0;\n"
      "wgmma.mma_async.sp.sync.aligned.m64n48k32.f32.bf16.bf16 "
      "{%0,%1,%2,%3,%4,%5,%6,%7,%8,%9,%10,%11,%12,%13,%14,%15,"
      "%16,%17,%18,%19,%20,%21,%22,%23}, "
      "{%24,%25,%26,%27}, %28, %30, 0, p, 1, 1, 0;\n}\n"
      : "+f"(d[OFF + 0]), "+f"(d[OFF + 1]), "+f"(d[OFF + 2]), "+f"(d[OFF + 3]), "+f"(d[OFF + 4]), "+f"(d[OFF + 5]),
        "+f"(d[OFF + 6]), "+f"(d[OFF + 7]), "+f"(d[OFF + 8]), "+f"(d[OFF + 9]), "+f"(d[OFF + 10]), "+f"(d[OFF + 11]),
        "+f"(d[OFF + 12]), "+f"(d[OFF + 13]), "+f"(d[OFF + 14]), "+f"(d[OFF + 15]), "+f"(d[OFF + 16]), "+f"(d[OFF + 17]),
        "+f"(d[OFF + 18]), "+f"(d[OFF + 19]), "+f"(d[OFF + 20]), "+f"(d[OFF + 21]), "+f"(d[OFF + 22]), "+f"(d[OFF + 23])
      : "r"(a0), "r"(a1), "r"(a2), "r"(a3), "l"(desc_b), "r"(scale_d), "r"(meta));
}

template <int OFF, int NN>
__device__ __forceinline__ void wg_s48z(float (&d)[NN], uint32_t a0, uint32_t a1, uint32_t a2, uint32_t a3,
                                       uint64_t desc_b, int scale_d, uint32_t meta) {
  asm volatile(
      "{\n.reg .pred p;\nsetp.ne.b32 p, %29, 0;\n"
      "wgmma.mma_async.sp.sync.aligned.m64n48k32.f32.bf16.bf16 "
      "{%0,%1,%2,%3,%4,%5,%6,%7,%8,%9,%10,%11,%12,%13,%14,%15,"
      "%16,%17,%18,%19,%20,%21,%22,%23}, "
      "{%24,%25,%26,%27}, %28, %30, 0, p, 1, 1, 0;\n}\n"
      : "=f"(d[OFF + 0]), "=f"(d[OFF + 1]), "=f"(d[OFF + 2]), "=f"(d[OFF + 3]), "=f"(d[OFF + 4]), "=f"(d[OFF + 5]),
        "=f"(d[OFF + 6]), "=f"(d[OFF + 7]), "=f"(d[OFF + 8]), "=f"(d[OFF + 9]), "=f"(d[OFF + 10]), "=f"(d[OFF + 11]),
        "=f"(d[OFF + 12]), "=f"(d[OFF + 13]), "=f"(d[OFF + 14]), "=f"(d[OFF + 15]), "=f"(d[OFF + 16]), "=f"(d[OFF + 17]),
        "=f"(d[OFF + 18]), "=f"(d[OFF + 19]), "=f"(d[OFF + 20]), "=f"(d[OFF + 21]), "=f"(d[OFF + 22]), "=f"(d[OFF + 23])
      : "r"(a0), "r"(a1), "r"(a2), "r"(a3), "l"(desc_b), "r"(scale_d), "r"(meta));
}

template <int OFF, int NN>
__device__ __forceinline__ void wg_s56(float (&d)[NN], uint32_t a0, uint32_t a1, uint32_t a2, uint32_t a3,
                                       uint64_t desc_b, int scale_d, uint32_t meta) {
  asm volatile(
      "{\n.reg .pred p;\nsetp.ne.b32 p, %33, 0;\n"
      "wgmma.mma_async.sp.sync.aligned.m64n56k32.f32.bf16.bf16 "
      "{%0,%1,%2,%3,%4,%5,%6,%7,%8,%9,%10,%11,%12,%13,%14,%15,"
      "%16,%17,%18,%19,%20,%21,%22,%23,%24,%25,%26,%27}, "
      "{%28,%29,%30,%31}, %32, %34, 0, p, 1, 1, 0;\n}\n"
      : "+f"(d[OFF + 0]), "+f"(d[OFF + 1]), "+f"(d[OFF + 2]), "+f"(d[OFF + 3]), "+f"(d[OFF + 4]), "+f"(d[OFF + 5]),
        "+f"(d[OFF + 6]), "+f"(d[OFF + 7]), "+f"(d[OFF + 8]), "+f"(d[OFF + 9]), "+f"(d[OFF + 10]), "+f"(d[OFF + 11]),
        "+f"(d[OFF + 12]), "+f"(d[OFF + 13]), "+f"(d[OFF + 14]), "+f"(d[OFF + 15]), "+f"(d[OFF + 16]), "+f"(d[OFF + 17]),
        "+f"(d[OFF + 18]), "+f"(d[OFF + 19]), "+f"(d[OFF + 20]), "+f"(d[OFF + 21]), "+f"(d[OFF + 22]), "+f"(d[OFF + 23]),
        "+f"(d[OFF + 24]), "+f"(d[OFF + 25]), "+f"(d[OFF + 26]), "+f"(d[OFF + 27])
      : "r"(a0), "r"(a1), "r"(a2), "r"(a3), "l"(desc_b), "r"(scale_d), "r"(meta));
}

template <int OFF, int NN>
__device__ __forceinline__ void wg_s56z(float (&d)[NN], uint32_t a0, uint32_t a1, uint32_t a2, uint32_t a3,
                                       uint64_t desc_b, int scale_d, uint32_t meta) {
  asm volatile(
      "{\n.reg .pred p;\nsetp.ne.b32 p, %33, 0;\n"
      "wgmma.mma_async.sp.sync.aligned.m64n56k32.f32.bf16.bf16 "
      "{%0,%1,%2,%3,%4,%5,%6,%7,%8,%9,%10,%11,%12,%13,%14,%15,"
      "%16,%17,%18,%19,%20,%21,%22,%23,%24,%25,%26,%27}, "
      "{%28,%29,%30,%31}, %32, %34, 0, p, 1, 1, 0;\n}\n"
      : "=f"(d[OFF + 0]), "=f"(d[OFF + 1]), "=f"(d[OFF + 2]), "=f"(d[OFF + 3]), "=f"(d[OFF + 4]), "=f"(d[OFF + 5]),
        "=f"(d[OFF + 6]), "=f"(d[OFF + 7]), "=f"(d[OFF + 8]), "=f"(d[OFF + 9]), "=f"(d[OFF + 10]), "=f"(d[OFF + 11]),
        "=f"(d[OFF + 12]), "=f"(d[OFF + 13]), "=f"(d[OFF + 14]), "=f"(d[OFF + 15]), "=f"(d[OFF + 16]), "=f"(d[OFF + 17]),
        "=f"(d[OFF + 18]), "=f"(d[OFF + 19]), "=f"(d[OFF + 20]), "=f"(d[OFF + 21]), "=f"(d[OFF + 22]), "=f"(d[OFF + 23]),
        "=f"(d[OFF + 24]), "=f"(d[OFF + 25]), "=f"(d[OFF + 26]), "=f"(d[OFF + 27])
      : "r"(a0), "r"(a1), "r"(a2), "r"(a3), "l"(desc_b), "r"(scale_d), "r"(meta));
}

template <int OFF, int NN>
__device__ __forceinline__ void wg_s64t(float (&d)[NN], uint32_t a0, uint32_t a1, uint32_t a2, uint32_t a3,
                                       uint64_t desc_b, int scale_d, uint32_t meta) {
  asm volatile(
      "{\n.reg .pred p;\nsetp.ne.b32 p, %37, 0;\n"
      "wgmma.mma_async.sp.sync.aligned.m64n64k32.f32.bf16.bf16 "
      "{%0,%1,%2,%3,%4,%5,%6,%7,%8,%9,%10,%11,%12,%13,%14,%15,"
      "%16,%17,%18,%19,%20,%21,%22,%23,%24,%25,%26,%27,%28,%29,%30,%31}, "
      "{%32,%33,%34,%35}, %36, %38, 0, p, 1, 1, 1;\n}\n"
      : "+f"(d[OFF + 0]), "+f"(d[OFF + 1]), "+f"(d[OFF + 2]), "+f"(d[OFF + 3]), "+f"(d[OFF + 4]), "+f"(d[OFF + 5]),
        "+f"(d[OFF + 6]), "+f"(d[OFF + 7]), "+f"(d[OFF + 8]), "+f"(d[OFF + 9]), "+f"(d[OFF + 10]), "+f"(d[OFF + 11]),
        "+f"(d[OFF + 12]), "+f"(d[OFF + 13]), "+f"(d[OFF + 14]), "+f"(d[OFF + 15]), "+f"(d[OFF + 16]), "+f"(d[OFF + 17]),
        "+f"(d[OFF + 18]), "+f"(d[OFF + 19]), "+f"(d[OFF + 20]), "+f"(d[OFF + 21]), "+f"(d[OFF + 22]), "+f"(d[OFF + 23]),
        "+f"(d[OFF + 24]), "+f"(d[OFF + 25]), "+f"(d[OFF + 26]), "+f"(d[OFF + 27]), "+f"(d[OFF + 28]), "+f"(d[OFF + 29]),
        "+f"(d[OFF + 30]), "+f"(d[OFF + 31])
      : "r"(a0), "r"(a1), "r"(a2), "r"(a3), "l"(desc_b), "r"(scale_d), "r"(meta));
}

template <int OFF, int NN>
__device__ __forceinline__ void wg_s64t1(float (&d)[NN], uint32_t a0, uint32_t a1, uint32_t a2, uint32_t a3,
                                       uint64_t desc_b, int scale_d, uint32_t meta) {
  asm volatile(
      "{\n.reg .pred p;\nsetp.ne.b32 p, %37, 0;\n"
      "wgmma.mma_async.sp.sync.aligned.m64n64k32.f32.bf16.bf16 "
      "{%0,%1,%2,%3,%4,%5,%6,%7,%8,%9,%10,%11,%12,%13,%14,%15,"
      "%16,%17,%18,%19,%20,%21,%22,%23,%24,%25,%26,%27,%28,%29,%30,%31}, "
      "{%32,%33,%34,%35}, %36, %38, 1, p, 1, 1, 1;\n}\n"
      : "+f"(d[OFF + 0]), "+f"(d[OFF + 1]), "+f"(d[OFF + 2]), "+f"(d[OFF + 3]), "+f"(d[OFF + 4]), "+f"(d[OFF + 5]),
        "+f"(d[OFF + 6]), "+f"(d[OFF + 7]), "+f"(d[OFF + 8]), "+f"(d[OFF + 9]), "+f"(d[OFF + 10]), "+f"(d[OFF + 11]),
        "+f"(d[OFF + 12]), "+f"(d[OFF + 13]), "+f"(d[OFF + 14]), "+f"(d[OFF + 15]), "+f"(d[OFF + 16]), "+f"(d[OFF + 17]),
        "+f"(d[OFF + 18]), "+f"(d[OFF + 19]), "+f"(d[OFF + 20]), "+f"(d[OFF + 21]), "+f"(d[OFF + 22]), "+f"(d[OFF + 23]),
        "+f"(d[OFF + 24]), "+f"(d[OFF + 25]), "+f"(d[OFF + 26]), "+f"(d[OFF + 27]), "+f"(d[OFF + 28]), "+f"(d[OFF + 29]),
        "+f"(d[OFF + 30]), "+f"(d[OFF + 31])
      : "r"(a0), "r"(a1), "r"(a2), "r"(a3), "l"(desc_b), "r"(scale_d), "r"(meta));
}

template <int OFF, int NN>
__device__ __forceinline__ void wg_s64tz(float (&d)[NN], uint32_t a0, uint32_t a1, uint32_t a2, uint32_t a3,
                                       uint64_t desc_b, int scale_d, uint32_t meta) {
  asm volatile(
      "{\n.reg .pred p;\nsetp.ne.b32 p, %37, 0;\n"
      "wgmma.mma_async.sp.sync.aligned.m64n64k32.f32.bf16.bf16 "
      "{%0,%1,%2,%3,%4,%5,%6,%7,%8,%9,%10,%11,%12,%13,%14,%15,"
      "%16,%17,%18,%19,%20,%21,%22,%23,%24,%25,%26,%27,%28,%29,%30,%31}, "
      "{%32,%33,%34,%35}, %36, %38, 0, p, 1, 1, 1;\n}\n"
      : "=f"(d[OFF + 0]), "=f"(d[OFF + 1]), "=f"(d[OFF + 2]), "=f"(d[OFF + 3]), "=f"(d[OFF + 4]), "=f"(d[OFF + 5]),
        "=f"(d[OFF + 6]), "=f"(d[OFF + 7]), "=f"(d[OFF + 8]), "=f"(d[OFF + 9]), "=f"(d[OFF + 10]), "=f"(d[OFF + 11]),
        "=f"(d[OFF + 12]), "=f"(d[OFF + 13]), "=f"(d[OFF + 14]), "=f"(d[OFF + 15]), "=f"(d[OFF + 16]), "=f"(d[OFF + 17]),
        "=f"(d[OFF + 18]), "=f"(d[OFF + 19]), "=f"(d[OFF + 20]), "=f"(d[OFF + 21]), "=f"(d[OFF + 22]), "=f"(d[OFF + 23]),
        "=f"(d[OFF + 24]), "=f"(d[OFF + 25]), "=f"(d[OFF + 26]), "=f"(d[OFF + 27]), "=f"(d[OFF + 28]), "=f"(d[OFF + 29]),
        "=f"(d[OFF + 30]), "=f"(d[OFF + 31])
      : "r"(a0), "r"(a1), "r"(a2), "r"(a3), "l"(desc_b), "r"(scale_d), "r"(meta));
}

__device__ __forceinline__ int g2_inv(int ch) { return 32 * (ch >> 5) + 8 * ((ch >> 1) & 3) + 2 * ((ch >> 3) & 3) + (ch & 1); }
__host__ __device__ __forceinline__ uint32_t wimg_off(int n, int k) {
  return (uint32_t)(k >> 6) * kWChunk + (uint32_t)n * 128 + (uint32_t)((((k & 63) >> 3) ^ (n & 7)) << 4) + (k & 7) * 2;
}
__host__ __device__ constexpr int w2piece(int h, int c) { return c == 2 ? 2 + h : 4 * h + c; }
__device__ __forceinline__ uint32_t w2img_off(int n, int k) { return wimg_off(n % 96, k & 63) + w2piece(n >= 96, k >> 6) * (kWChunk / 2); }
__device__ __forceinline__ int qpix(int par, int t) {
  const int a = 2 * t + 13 * par - 6, b = t + 112 * par;
  return par ? min(a, b) : max(a, b);
}
__device__ __forceinline__ int woff(int par, int i, int r) {
  const int a = 99 * par + 6 - 8 * i;
  return par ? min(r, a) : max(r, a);
}

__device__ __forceinline__ void mma16816(float (&c)[4], uint32_t a0, uint32_t a1, uint32_t a2, uint32_t a3, uint32_t b0,
                                         uint32_t b1) {
  asm volatile(
      "mma.sync.aligned.m16n8k16.row.col.f32.bf16.bf16.f32 {%0,%1,%2,%3}, {%4,%5,%6,%7}, {%8,%9}, {%0,%1,%2,%3};"
      : "+f"(c[0]), "+f"(c[1]), "+f"(c[2]), "+f"(c[3])
      : "r"(a0), "r"(a1), "r"(a2), "r"(a3), "r"(b0), "r"(b1));
}

__device__ __forceinline__ void fold_w1(const int u, const __nv_bfloat16* __restrict__ wqkv, uint8_t* wimg) {
  const int g = (threadIdx.x >> 2) & 7, l = threadIdx.x & 3;
  const int m0 = (u / 12) * 16, s = u % 12;
  uint4 A[12], B[12];
  const __nv_bfloat16* arow = wqkv + (m0 + 4 * (g >> 1) + (g & 1)) * 576 + 192 + 8 * l;
  const __nv_bfloat16* brow = wqkv + (16 * s + 4 * (g >> 1) + (g & 1)) * 576 + 8 * l;
#pragma unroll
  for (int i = 0; i < 12; i++) {
    A[i] = ldg128_nc(arow + (i & 1) * 2 * 576 + 32 * (i >> 1));
    B[i] = ldg128_nc(brow + (i & 1) * 2 * 576 + 32 * (i >> 1));
  }
  sched_fence();
  uint8_t* dst = wimg + wimg_off(m0 + g, 16 * s + 4 * l);
  float acc[4][4];
#pragma unroll
  for (int j = 0; j < 16; j++) acc[j >> 2][j & 3] = 0.f;
#pragma unroll
  for (int i = 0; i < 6; i++) {
    const uint4 &a0 = A[2 * i], &a1 = A[2 * i + 1];
#pragma unroll
    for (int nb = 0; nb < 2; nb++) {
      mma16816(acc[2 * nb], a0.x, a1.x, a0.y, a1.y, B[2 * i + nb].x, B[2 * i + nb].y);
      mma16816(acc[2 * nb + 1], a0.z, a1.z, a0.w, a1.w, B[2 * i + nb].z, B[2 * i + nb].w);
    }
  }
#pragma unroll
  for (int j = 0; j < 2; j++) {
    const uint2 v = make_uint2(pack_bf16((acc[0][2 * j] + acc[1][2 * j]) * kAlpha, (acc[0][2 * j + 1] + acc[1][2 * j + 1]) * kAlpha),
                               pack_bf16((acc[2][2 * j] + acc[3][2 * j]) * kAlpha, (acc[2][2 * j + 1] + acc[3][2 * j + 1]) * kAlpha));
    asm volatile("st.relaxed.gpu.global.v2.u32 [%0], {%1,%2};" ::"l"(dst + j * 1024), "r"(v.x), "r"(v.y) : "memory");
  }
}
__device__ __forceinline__ void fold_w2(const int u, const __nv_bfloat16* __restrict__ wqkv, const __nv_bfloat16* __restrict__ wo,
                                        uint8_t* wimg) {
  const int g = (threadIdx.x >> 2) & 7, l = threadIdx.x & 3;
  const int m0 = (u / 12) * 32, n0 = (u % 12) * 16;
  uint4 S[12];
  uint32_t L[96];
  const __nv_bfloat16* brow = wqkv + (n0 + 4 * (g >> 1) + (g & 1)) * 576 + 384 + 8 * l;
#pragma unroll
  for (int i = 0; i < 12; i++) S[i] = ldg128_nc(brow + (i & 1) * 2 * 576 + 32 * (i >> 1));
  const __nv_bfloat16* acol = wo + (8 * l) * 192 + m0 + 4 * g;
#pragma unroll
  for (int c = 0; c < 48; c++)
    asm volatile("ld.global.nc.v2.u32 {%0,%1}, [%2];" : "=r"(L[2 * c]), "=r"(L[2 * c + 1]) : "l"(acol + (32 * (c >> 3) + (c & 7)) * 192));
  const uint32_t off = w2_offset();
  sched_fence();
  uint8_t* img = wimg + off;
  float acc[4][4];
#pragma unroll
  for (int j = 0; j < 16; j++) acc[j >> 2][j & 3] = 0.f;
#pragma unroll
  for (int i = 0; i < 6; i++) {
#pragma unroll
    for (int h = 0; h < 2; h++) {
      const uint4 &s0 = S[2 * i], &s1 = S[2 * i + 1];
#pragma unroll
      for (int mt = 0; mt < 2; mt++) {
        const uint32_t* a = L + 16 * i + 8 * h + mt;
        const uint32_t a0 = __byte_perm(a[0], a[2], 0x5410), a1 = __byte_perm(a[0], a[2], 0x7632);
        const uint32_t a2 = __byte_perm(a[4], a[6], 0x5410), a3 = __byte_perm(a[4], a[6], 0x7632);
        mma16816(acc[2 * mt], a0, a1, a2, a3, h ? s0.z : s0.x, h ? s0.w : s0.y);
        mma16816(acc[2 * mt + 1], a0, a1, a2, a3, h ? s1.z : s1.x, h ? s1.w : s1.y);
      }
    }
  }
#pragma unroll
  for (int j = 0; j < 4; j++) {
    const float(&c0)[4] = acc[j & 2];
    const float(&c1)[4] = acc[(j & 2) + 1];
    asm volatile("st.relaxed.gpu.global.v2.u32 [%0], {%1,%2};" ::"l"(img + w2img_off(g2_inv(m0 + 4 * g + j), n0 + 4 * l)),
                 "r"(pack_bf16(c0[2 * (j & 1)], c0[2 * (j & 1) + 1])), "r"(pack_bf16(c1[2 * (j & 1)], c1[2 * (j & 1) + 1])) : "memory");
  }
}

__global__ void __launch_bounds__(256) fold_kernel(const __nv_bfloat16* __restrict__ wqkv,
                                                   const __nv_bfloat16* __restrict__ wo, uint8_t* wimg) {
  const int u = blockIdx.x * 8 + (threadIdx.x >> 5);
  if (u < 144) fold_w1(u, wqkv, wimg);
  else fold_w2(u - 144, wqkv, wo, wimg);
}

struct TileCoord { int pr, pc, I, J, up, kind; };
struct TileTable { uint16_t e[kCtas * 6], g[5][8][2], b[5][2][4]; };
inline void make_tiles(TileTable& tt) {
  for (int tile = 0; tile < kCtas * 6; tile++) {
    const int b = tile / 6, k = tile - 6 * b;
    const int p = b < 128 ? (tile - 672) >> 1 : b - 80;
    const int strip = b < 112 ? b >> 1 : b >= 128 && k >= 2 ? (b & 1) * 27 + (b & 2) * 14 : p + (p < 26 ? 1 : 3);
    const int pr = strip >= 28, J = (strip - pr * 28) >> 1, pc = strip & 1, up = b < 112 ? b & 1 : pr;
    const int first = b < 112 ? 8 - 2 * pr - up : 13 * pr, step = b < 112 ? k : k & 1;
    const int I = up ? first - step : first + step;
    const int kind = I == 13 * pr ? 3 + pr : J == 13 * pc ? 1 + pc : 0;
    tt.e[tile] = (uint16_t)(I | J << 4 | pr << 8 | pc << 9 | up << 10 | kind << 11);
  }
  for (int kind = 0; kind < 5; kind++) {
    const bool col = kind == 1 || kind == 2;
    auto off = [kind](int t) { return kind == 0 ? 2 * t : kind & 1 ? t + (t == 7) : t + (t > 0); };
    for (int j = 0; j < 8; j++) {
      const int w = j >> 1, h = j & 1;
      tt.g[kind][j][0] = (uint16_t)(col ? 3 * off(w + 4 * h) : 3 * (kW * off(2 * w) + 8 * h));
      tt.g[kind][j][1] = (uint16_t)(128 * (col ? 5 : 5 + off(2 * w + 1) - off(2 * w)));
    }
    for (int i = 0; i < 2; i++) {
      const int w = kind == 0 ? 0 : kind & 1 ? 3 * i : 1 - i;
      tt.b[kind][i][0] = tt.g[kind][2 * w][0];
      tt.b[kind][i][1] = (uint16_t)(128 * (kind == 0 ? 0 : (col ? 3 : 1) + i));
      tt.b[kind][i][2] = (uint16_t)(2048 * w);
      tt.b[kind][i][3] = 0;
    }
  }
}
__device__ __forceinline__ int num_tiles() { return blockIdx.x < 128 ? 6 : 4; }
__device__ __forceinline__ TileCoord decode_tile(const TileTable& tt, int tile) {
  const uint32_t e = tt.e[tile];
  return TileCoord{(int)(e >> 8) & 1, (int)(e >> 9) & 1, (int)e & 15, (int)(e >> 4) & 15, (int)(e >> 10) & 1, (int)(e >> 11)};
}
__device__ __forceinline__ int halo_r0(const TileCoord& t) { return 8 * t.I + 6 * t.pr - 6; }
__device__ __forceinline__ int halo_c0(const TileCoord& t) { return min(max(8 * t.J + 6 * t.pc - 6, -3), 102); }

__device__ __forceinline__ uint32_t bar_full(uint32_t bars, int wg, int c) { return bars + (wg * 3 + c) * 8; }
__device__ __forceinline__ uint32_t bar_w1c(uint32_t bars, int c) { return bars + (6 + c) * 8; }
__device__ __forceinline__ uint32_t bar_w2(uint32_t bars) { return bars + 9 * 8; }
__device__ __forceinline__ uint32_t bar_x(uint32_t bars, int j, int c) { return bars + (j == 0 ? 10 : c ? 17 + c : 11) * 8; }
__device__ __forceinline__ uint32_t bar_w1q(uint32_t bars) { return bars + 12 * 8; }
__device__ __forceinline__ uint32_t bar_xf(uint32_t bars) { return bars + 13 * 8; }
__device__ __forceinline__ uint32_t bar_w2m(uint32_t bars) { return bars + 14 * 8; }
__device__ __forceinline__ uint32_t bar_redo(uint32_t bars) { return bars + 15 * 8; }
__device__ __forceinline__ uint32_t bar_wok(uint32_t bars) { return bars + 16 * 8; }
__device__ __forceinline__ uint32_t bar_go(uint32_t bars) { return bars + 17 * 8; }
__device__ __forceinline__ uint32_t bar_raw(uint32_t bars, int j = 0) { return bars + (21 + j) * 8; }
__device__ __forceinline__ uint32_t bar_w2a(uint32_t bars) { return bars + 20 * 8; }
constexpr int kNumBars = 22;

__device__ __forceinline__ uint64_t wdesc(uint64_t d0, int s) { return d0 + (((s >> 2) * kWChunk + (s & 3) * 32) >> 4); }

__device__ __forceinline__ uint32_t x_chunk(int k, int c) { return kXOff + (k == 0 ? kWChunk : 0) + (k & 1 ? 2 - c : c) * 8192; }
__device__ __forceinline__ uint32_t out_slot(int k, int nt) { return k + 1 < nt ? kW2Off + (~k & 1) * 2 * kWChunk : kW1Off + kWChunk; }
template <int I0, int I1>
__device__ __forceinline__ void store_rows(bool on, __nv_bfloat16* pA, __nv_bfloat16* pB, const uint32_t (&a)[24], const uint32_t (&b)[24]) {
#pragma unroll
  for (int i = 2 * I0; i < 2 * I1; i++) {
    const uint32_t* v = (i & 1 ? b : a) + 4 * (i >> 1);
    asm volatile("{\n.reg .pred p;\nsetp.ne.u32 p, %5, 0;\n@p st.global.v4.u32 [%0], {%1,%2,%3,%4};\n}\n" ::"l"((i & 1 ? pB : pA) + 32 * (i >> 1)),
                 "r"(v[0]), "r"(v[1]), "r"(v[2]), "r"(v[3]), "r"((uint32_t)on) : "memory");
  }
}
template <int I0, int I1>
__device__ __forceinline__ void stage_out(const uint32_t (&ad)[4], const uint32_t (&a)[24], const uint32_t (&b)[24]) {
#pragma unroll
  for (int i = I0; i < I1; i++) {
    const uint32_t* v = (i < 6 ? a : b) + 4 * (i % 6);
    asm volatile("st.shared.v4.u32 [%0], {%1,%2,%3,%4};" ::"r"(ad[i % 6 / 3 * 2 + (i % 3 == 1)] + (i % 3 == 2) * 1024 + (i / 6) * 12288),
                 "r"(v[0]), "r"(v[1]), "r"(v[2]), "r"(v[3]) : "memory");
  }
}
__device__ __forceinline__ uint32_t now_ns() {
  uint32_t t;
  asm volatile("mov.u32 %0, %globaltimer_lo;" : "=r"(t)::"memory");
  return t;
}
__device__ __forceinline__ void wait_clock(uint32_t t_start, uint32_t t) {
  while (now_ns() - t_start < t) { }
}
#define NAT_PRED(f, m) ".reg .pred p;\n.reg .b32 t;\nand.b32 t, " f ", " m ";\nsetp.ne.u32 p, t, 0;\n"
constexpr uint32_t kHiV = 1, kHiU = 8, kColB = 0x20, kInV = 0x100, kInU = 0x1000, kColA = 0x10000;
template <uint32_t M>
__device__ __forceinline__ float pick(const float* a, const float* b, uint32_t f) {
  float d;
  asm("{\n" NAT_PRED("%5", "%6") "add.f32 %0, %1, %2;\n@p add.f32 %0, %3, %4;\n}\n"
      : "=&f"(d) : "f"(a[0]), "f"(a[2]), "f"(b[0]), "f"(b[2]), "r"(f), "n"(M));
  return d;
}
template <uint32_t M>
__device__ __forceinline__ float sel(float a, float b, uint32_t f) {
  float d;
  asm("{\n" NAT_PRED("%3", "%4") "selp.f32 %0, %1, %2, p;\n}\n" : "=f"(d) : "f"(a), "f"(b), "r"(f), "n"(M));
  return d;
}
template <uint32_t M>
__device__ __forceinline__ void max_if(float& m, float v, uint32_t f) {
  asm("{\n" NAT_PRED("%2", "%3") "@p max.f32 %0, %0, %1;\n}\n" : "+f"(m) : "f"(v), "r"(f), "n"(M));
}
template <uint32_t M>
__device__ __forceinline__ void add_if(float& m, float v, uint32_t f) {
  asm("{\n" NAT_PRED("%2", "%3") "@p add.f32 %0, %0, %1;\n}\n" : "+f"(m) : "f"(v), "r"(f), "n"(M));
}
__device__ __forceinline__ void pick_v(const float* a, float* v, uint32_t f) {
  v[0] = pick<kHiV>(a, a + 16, f), v[1] = pick<kHiV>(a + 1, a + 17, f);
  v[2] = pick<kHiV * 2>(a + 4, a + 20, f), v[3] = pick<kHiV * 2>(a + 5, a + 21, f);
  v[4] = pick<kHiV * 4>(a + 8, a + 24, f), v[5] = pick<kHiV * 4>(a + 9, a + 25, f);
  v[6] = a[12] + a[14], v[7] = a[13] + a[15];
}
__device__ __forceinline__ void pick_u(const float* a, float* v, uint32_t f) {
#pragma unroll
  for (int c = 0; c < 3; c++) v[2 * c] = pick<kHiU>(a + 4 * c, a + 4 * c + 12, f), v[2 * c + 1] = pick<kHiU * 2>(a + 4 * c + 1, a + 4 * c + 13, f);
}
__device__ __forceinline__ uint32_t sign_bytes(uint32_t v, uint32_t sel) {
  uint32_t d;
  asm("prmt.b32 %0, %1, %1, %2;" : "=r"(d) : "r"(v), "r"(sel));
  return d;
}
__device__ __forceinline__ float own_max(const float (&v)[14], uint32_t f) {
  float m = sel<kInV>(fmaxf(v[0], v[1]), -INFINITY, f), m2 = sel<kInV * 2>(fmaxf(v[2], v[3]), -INFINITY, f);
  max_if<kInV * 4>(m, fmaxf(v[4], v[5]), f);
  max_if<kInV * 8>(m2, fmaxf(v[6], v[7]), f);
  max_if<kInU>(m, fmaxf(fmaxf(v[8], v[10]), v[12]), f);
  max_if<kInU * 2>(m2, fmaxf(fmaxf(v[9], v[11]), v[13]), f);
  return fmaxf(m, m2);
}
__device__ __forceinline__ float quad_max(float m) {
  const float a = __shfl_xor_sync(0xffffffffu, m, 1), b = __shfl_xor_sync(0xffffffffu, m, 2), c = __shfl_xor_sync(0xffffffffu, m, 3);
  return fmaxf(fmaxf(m, a), fmaxf(b, c));
}
__device__ __forceinline__ float row_rcp(const float (&v)[14], uint32_t f) {
  float s = sel<kInV>(v[0] + v[1], 0.f, f), s2 = sel<kInV * 2>(v[2] + v[3], 0.f, f);
  add_if<kInV * 4>(s, v[4] + v[5], f);
  add_if<kInV * 8>(s2, v[6] + v[7], f);
  add_if<kInU>(s, v[8] + v[10] + v[12], f);
  add_if<kInU * 2>(s2, v[9] + v[11] + v[13], f);
  s += s2;
  const float a = __shfl_xor_sync(0xffffffffu, s, 1), b = __shfl_xor_sync(0xffffffffu, s, 2), c = __shfl_xor_sync(0xffffffffu, s, 3);
  return rcp_approx((s + a) + (b + c));
}
__device__ __forceinline__ void route(const float (&v)[14], float s, const uint32_t (&rt)[9], uint32_t (&p)[14]) {
#pragma unroll
  for (int i = 0; i < 7; i++) {
    const uint32_t u = pack_bf16(v[2 * i] * s, v[2 * i + 1] * s);
    if (i < 4) p[i] = u & rt[i];
    if (i < 3) p[i + 4] = u & rt[i + 4];
    if (i >= 4) {
      p[i + 3] = u & rt[7];
      p[i + 6] = u & rt[8];
    }
  }
}

template <int C, int T0 = 0, int T1 = 7>
__device__ __forceinline__ void pv_chunk(float (&z)[32], const uint32_t (&pa)[14], const uint32_t (&pb)[14],
                                         const uint32_t (&meta)[4], uint64_t dV) {
#pragma unroll
  for (int t = T0; t < T1; t++) {
    if (t & 1)
      wg_s64t1<0, 32>(z, pa[2 * t], pb[2 * t], pa[2 * t + 1], pb[2 * t + 1], dV + ((2 * C * kChunkBytes + t * 2048) >> 4), 1,
                      meta[t >> 1]);
    else if (t > 0)
      wg_s64t<0, 32>(z, pa[2 * t], pb[2 * t], pa[2 * t + 1], pb[2 * t + 1], dV + ((2 * C * kChunkBytes + t * 2048) >> 4), 1,
                     meta[t >> 1]);
    else
      wg_s64tz<0, 32>(z, pa[0], pb[0], pa[1], pb[1], dV + ((2 * C * kChunkBytes) >> 4), 0, meta[0]);
  }
}
template <int C>
__device__ __forceinline__ void pack_z(const float (&z)[32], uint32_t (&za)[24], uint32_t (&zb)[24]) {
#pragma unroll
  for (int j = 0; j < 8; j++) {
    za[8 * C + j] = pack_bf16(z[4 * j], z[4 * j + 1]);
    zb[8 * C + j] = pack_bf16(z[4 * j + 2], z[4 * j + 3]);
  }
}

template <int H>
__device__ __forceinline__ void pack_out(const float (&ac)[48], uint32_t (&oa)[24], uint32_t (&ob)[24]) {
#pragma unroll
  for (int j = 0; j < 12; j++) {
    oa[12 * H + j] = pack_bf16(ac[4 * j], ac[4 * j + 1]);
    ob[12 * H + j] = pack_bf16(ac[4 * j + 2], ac[4 * j + 3]);
  }
}
struct Maps { CUtensorMap v6, v2, v14, u8, px[8], wv, wo; };
__device__ __forceinline__ void tma_prefetch_5d(const CUtensorMap* map, int c0, int c1, int c2, int c3, int c4) {
  asm volatile("cp.async.bulk.prefetch.tensor.5d.L2.global.tile [%0, {%1, %2, %3, %4, %5}];" ::"l"((uint64_t)map), "r"(c0), "r"(c1),
               "r"(c2), "r"(c3), "r"(c4) : "memory");
}
__device__ __forceinline__ int first_line(const TileCoord tc) { return 3 * (qpix(tc.pr, 8 * tc.I) * kW + qpix(tc.pc, 8 * tc.J)); }
__device__ __forceinline__ void load_px(const Maps& tm, const TileTable& tt, uint32_t dst, uint32_t bar, int line, int kind) {
#pragma unroll
  for (int i = 0; i < 2; i++) {
    if (i == 0 || kind != 0) {
      const CUtensorMap* map = (const CUtensorMap*)((const char*)tm.px + tt.b[kind][i][1]);
      if (bar) tma_load_5d(dst + tt.b[kind][i][2], map, bar, 0, 0, 0, 0, line + tt.b[kind][i][0]);
      else tma_prefetch_5d(map, 0, 0, 0, 0, line + tt.b[kind][i][0]);
    }
  }
}
__device__ __forceinline__ void store_px(const Maps& tm, const TileTable& tt, uint32_t buf, int line, int kind) {
#pragma unroll
  for (int i = 0; i < 8; i++) {
    const int j = 2 * (i & 3) + (i >> 2);
    asm volatile("cp.async.bulk.tensor.5d.global.shared::cta.tile.bulk_group [%0, {%2, %2, %2, %2, %3}], [%1];" ::"l"(
                     (uint64_t)tm.px + tt.g[kind][j][1]), "r"(buf + i * 3072), "r"(0), "r"(line + tt.g[kind][j][0]) : "memory");
  }
  asm volatile("cp.async.bulk.commit_group;" ::: "memory");
}
__device__ __noinline__ bool refetch(uint32_t base, const uint8_t* src, bool gap) {
  constexpr uint32_t bars = 1024 + kBarOff, cnt = bars + 192;
#pragma unroll 1
  for (uint32_t o = 0; o < kWBytes && !gap; o += 2048) {
    uint32_t mx = 0;
#pragma unroll
    for (int i = 0; i < 4; i++) {
      uint4 v;
      asm volatile("ld.shared.v4.u32 {%0,%1,%2,%3}, [%4];" : "=r"(v.x), "=r"(v.y), "=r"(v.z), "=r"(v.w)
                   : "r"(base + o + i * 512 + (threadIdx.x & 31) * 16));
      mx = __vimax3_u32(__vimax3_u32(mx, v.x, v.y), v.z, v.w);
    }
    gap = __any_sync(0xffffffffu, mx == kEmpty);
  }
  uint32_t n;
  asm volatile("ld.shared.u32 %0, [%1];" : "=r"(n) : "r"(cnt) : "memory");
  if (!gap || __any_sync(0xffffffffu, n > (1u << 12))) return false;
  asm volatile("bar.sync 15, 128;" ::: "memory");
  if (threadIdx.x == 0) {
    asm volatile("st.shared.u32 [%0], %1;" ::"r"(cnt), "r"(n + 1) : "memory");
    mbar_arrive_expect_tx(bar_redo(bars), kWBytes);
    bulk_load(base, src, kWBytes, bar_redo(bars));
  }
  __syncwarp();
  mbar_wait(bar_redo(bars), n & 1);
  return true;
}
__device__ __forceinline__ bool any_nan(const uint32_t (&a)[24]) {
  uint32_t m[2] = {a[0], a[1]}, nan;
#pragma unroll
  for (int i = 2; i < 24; i++) asm("max.NaN.bf16x2 %0, %0, %1;" : "+r"(m[i & 1]) : "r"(a[i]));
  asm("max.NaN.bf16x2 %0, %0, %1;" : "+r"(m[0]) : "r"(m[1]));
  asm volatile("{\n.reg .pred p;\nsetp.ne.u32 p, %1, 0;\nbar.red.or.pred p, 15, 128, p;\nselp.u32 %0, 1, 0, p;\n}\n"
               : "=r"(nan) : "r"(((m[0] & 0x7FFF7FFFu) + 0x007F007Fu) & 0x80008000u) : "memory");
  return __any_sync(0xffffffffu, nan);
}
template <int S0, int S1, int Z>
__device__ __forceinline__ void g2_steps(float (&ac)[48], const uint32_t (&za)[24], const uint32_t (&zb)[24], uint64_t d) {
#pragma unroll
  for (int s = S0; s < S1; s++) {
    const uint64_t ds = d + (((s >> 2 & 1) * (kWChunk / 2) + (s & 3) * 32) >> 4);
    if (s == Z) wg_d96z<0, 48>(ac, za[2 * s], zb[2 * s], za[2 * s + 1], zb[2 * s + 1], ds, 0);
    else wg_d96<0, 48>(ac, za[2 * s], zb[2 * s], za[2 * s + 1], zb[2 * s + 1], ds, 1);
  }
}

__device__ __forceinline__ void consumer(const int wg, __nv_bfloat16* out, const uint8_t* wimg, const uint32_t sbase,
                                         const uint32_t zero, const Maps& tm, const TileTable& tt) {
  const int tid = threadIdx.x & 127;
  const int w = __shfl_sync(0xffffffffu, tid >> 5, 0), lane = tid & 31;
  const uint64_t dK = make_desc(sbase, 16, 1024);
  const uint64_t dV = make_desc(sbase, kChunkBytes, 512, 2);
  const uint64_t dW1 = make_desc(sbase + kW1Off, 16, 1024);
  const uint64_t dX0 = make_desc(sbase + kW2Off + wg * 2 * kWChunk, 16, 1024), dY0 = make_desc(sbase + kW2Off + (1 - wg) * 2 * kWChunk, 16, 1024);
  const uint64_t dX2 = make_desc(sbase + kXOff + wg * (kWChunk / 2), 16, 1024), dY2 = make_desc(sbase + kXOff + (1 - wg) * (kWChunk / 2), 16, 1024);
  const uint32_t bars = sbase + kBarOff;
  int tile0 = blockIdx.x * kTilesPerCta;
  asm volatile("" : "+r"(tile0));
  const int nt = num_tiles();

  uint32_t pix = 0, geo[6] = {};
  const int l = lane & 3;
#pragma unroll 1
  for (int j = 4; j >= 0; j -= 2) {
    const TileCoord tc = decode_tile(tt, tile0 + wg + j);
    const bool col = tc.kind == 1 || tc.kind == 2;
    const int g = col ? lane >> 2 : 2 * w + ((lane >> 2) & 1), qc = col ? w : lane >> 3;
    const uint32_t pr = qpix(tc.pr, 8 * tc.I + g) * kW;
    if (j == nt - 2) pix = (pr + qpix(tc.pc, 8 * tc.J + qc)) | (pr + qpix(tc.pc, 8 * tc.J + qc + 4)) << 16;
    const int d = 8 * tc.J + 6 * tc.pc - 6 - halo_c0(tc);
    const int ro = woff(tc.pr, tc.I, g), coA = woff(tc.pc, tc.J, qc) + d, coB = woff(tc.pc, tc.J, qc + 4) + d - 3;
#pragma unroll
    for (int i = 5; i >= 2; i--) geo[i] = geo[i - 2];
    const uint32_t lr = 0x1FCu << ro;
    const uint32_t lv = lr >> (2 + (l >> 1)), lu = lr >> (2 * l + 2 * tc.up);
    const uint32_t t = __byte_perm(lv, lu, wg ? 0x4501 : 0x5410);
    geo[0] = (((t & 0x15u) | (lv & 0x40u)) * 0x02082080u & 0x80808080u) | (((t >> 8) & 0x15u) * 0x01041040u & 0x40404040u) |
             (__byte_perm(t << 5, t << 4, 0x7362) & 0x20202020u) | (nt == 6);
    const int dr = (ro - 1) & 7;
    const uint32_t hiv = (((1u << ((ro - (l >> 1) + 1) >> 1)) - 1u) ^ (wg ? 7u : 0u)) & 7u, hiu = (t >> 24) & 3u;
    const uint32_t ca = (1u << coA) - 1u;
    geo[1] = hiv * kHiV | hiu * kHiU | ((((1u << coB) - 1u) >> (2 * (l & 1))) & 3u) * kColB |
             (15u & ~((uint32_t)((dr & 1) == (l >> 1)) << (dr >> 1))) * kInV | ((t >> 16 | t >> 24) & 3u) * kInU | ca * kColA |
             (ca >> ((0x49 >> (2 * l)) & 3) & 1u) << 19 | (uint32_t)(l == 3) << 20 | (0x55u & ((1u << (2 * coB)) - 1u)) << 24;
  }
  keep_regs(geo);
  const int so = (lane >> 3) | (lane & 4);
  uint32_t sts = sbase + w * 3072 + so * 128 + (((lane & 3) ^ so) << 4);
  __nv_bfloat16* poA = out + 8 * l + (pix & 0xFFFFu) * kC + 96 * wg;
  __nv_bfloat16* poB = out + 8 * l + (pix >> 16) * kC + 96 * wg;
  asm volatile("" : "+l"(poA), "+l"(poB), "+r"(sts));
  uint32_t oa[24], ob[24];
#pragma unroll
  for (int j = 0; j < 24; j++) oa[j] = ob[j] = 0u;
  keep_regs(oa);
  keep_regs(ob);
  PROF(wg, 0);
  if (threadIdx.x == 0) GT(1);

  for (int k = wg; k < nt; k += 2) {
    const uint32_t ph = (k >> 1) & 1;
    const int it = k >> 1;
    uint32_t qa[24], qb[24], hok[3];
    uint32_t fl = geo[1];
    {
      float acc[96];
      const uint32_t xp = (k + (k > 0)) & 1;
      const uint32_t xok = mbar_test(bar_x(bars, k > 0, 0), xp);
      if (k > 0) nb_sync(1 + (1 - wg));
#pragma unroll
      for (int s = 0; s < 12; s++) {
        if (s == 0) mbar_wait_if(xok, bar_x(bars, k > 0, 0), xp);
        if (s == 0 && k < 2) PROF(wg, 1);
        if (s == 0) PROFS(2, wg, 2 + it * 12);
        if (s == 0 && w == 0 && k < 2) GT(20 + wg);
        if ((s & 3) == 0 && (k == 0 || s > 0)) {
          mbar_wait(k == 0 ? bar_w1c(bars, s >> 2) : bar_x(bars, 1, s >> 2), xp);
          PROFS(17, wg, 50 + (s >> 2));
        }
        if ((s & 3) == 0) wg_fence();
        const uint64_t dX = make_desc(sbase + x_chunk(k, s >> 2), 16, 1024) + 2 * (s & 3);
        if (s == 0) wg_m192z<0, 96>(acc, dX, dW1, 0);
        else wg_m192<0, 96>(acc, dX, wdesc(dW1, s), 1);
        if ((s & 3) == 3) wg_commit();
      }
      PROFS(13, wg, 13 + it * 12);
      const uint32_t e = sts + out_slot(k, nt), o = e ^ 64;
      uint32_t ad[4] = {wg ? o + 1024 : e, wg ? e + 2048 : o, wg ? e : o + 1024, wg ? o : e + 2048};
      keep_regs(ad);
      wg_wait<2>();
      if (k > 0) nb_arrive_p(0);
      wg_wait<1>();
      if (k > 0) nb_arrive_p(14);
      wg_wait<0>();
      if (k > 0) {
        nb_arrive_p(6);
        sched_fence();
      }
      fence_regs(acc);
      PROFS(3, wg, 3 + it * 12);
#pragma unroll
      for (int j = 0; j < 24; j++) {
        qa[j] = pack_bf16(acc[4 * j], acc[4 * j + 1]);
        qb[j] = pack_bf16(acc[4 * j + 2], acc[4 * j + 3]);
      }
      keep_regs(qa);
      keep_regs(qb);
      sched_fence();
      if (k >= 2) {
        nb_sync(11);
        stage_out<0, 6>(ad, oa, ob);
        nb_sync(12);
        stage_out<6, 12>(ad, oa, ob);
      }
#pragma unroll
      for (int c = 0; c < 3; c++) hok[c] = mbar_test(bar_full(bars, wg, c), ph);
      if (k >= 2) {
        fence_proxy_async();
        nb_arrive_p(10);
      }
    }

    float aE[52], aO[24], bO[52], bE[28];
    const uint32_t mq = 0xEEEE4444u | zero;
    PROFS(4, wg, 4 + it * 12);

    mbar_wait_if(hok[0], bar_full(bars, wg, 0), ph);
    PROFS(14, wg, 40 + it * 3);
    if (w == 0 && k < 2) GT(22 + wg);
    if (k > 0) nb_sync(3 + (1 - wg));
    wg_fence();
#pragma unroll
    for (int ks = 0; ks < 6; ks++) {
      if (ks == 2) {
        mbar_wait_if(hok[1], bar_full(bars, wg, 1), ph);
        PROFS(14, wg, 41 + it * 3);
        wg_fence();
      }
      if (ks == 4) {
        mbar_wait_if(hok[2], bar_full(bars, wg, 2), ph);
        PROFS(14, wg, 42 + it * 3);
        wg_fence();
      }
      const uint64_t d = dK + ((ks * kChunkBytes) >> 4);
      if (ks == 0) wg_s104z<0, 52>(aE, qa[0], qa[1], qa[2], qa[3], d, 0, mq);
      else wg_s104<0, 52>(aE, qa[4 * ks], qa[4 * ks + 1], qa[4 * ks + 2], qa[4 * ks + 3], d, 1, mq);
      if (ks == 0) wg_s48z<0, 24>(aO, qa[0], qa[1], qa[2], qa[3], d + ((7 * 1024 + 64) >> 4), 0, mq);
    }
    wg_commit();
#pragma unroll
    for (int ks = 1; ks < 6; ks++)
      wg_s48<0, 24>(aO, qa[4 * ks], qa[4 * ks + 1], qa[4 * ks + 2], qa[4 * ks + 3], dK + ((ks * kChunkBytes + 7 * 1024 + 64) >> 4), 1, mq);
    wg_commit();
    wg_s56z<0, 28>(bE, qb[0], qb[1], qb[2], qb[3], dK, 0, mq);
#pragma unroll
    for (int ks = 1; ks < 6; ks++) wg_s56<0, 28>(bE, qb[4 * ks], qb[4 * ks + 1], qb[4 * ks + 2], qb[4 * ks + 3], dK + ((ks * kChunkBytes) >> 4), 1, mq);
    wg_commit();
    wg_wait<2>();
    fence_regs(aE);
    PROFS(5, wg, 5 + it * 12);

    uint32_t pa[14], pb[14], meta[4];
    {
      float vA[14], vB[14];
      pick_v(aE, vA, fl);
      pick_u(aE + 28, vA + 8, fl);
      fence_regs(vA);
      if (k == 0) {
        if (__builtin_expect(__any_sync(0xffffffffu, vA[6] != vA[6]), 0)) {
          wg_wait<0>();
          fence_regs(aO);
          fence_regs(bE);
          if (refetch(sbase + kW1Off, wimg, false)) {
#pragma unroll
            for (int j = 0; j < 24; j++) oa[j] = ob[j] = 0u;
            k -= 2;
            continue;
          }
        }
        if (elect_one()) mbar_arrive(bar_xf(bars));
      }
      wg_fence();
      wg_s104z<0, 52>(bO, qb[0], qb[1], qb[2], qb[3], dK + 4, 0, mq);
#pragma unroll
      for (int ks = 1; ks < 6; ks++)
        wg_s104<0, 52>(bO, qb[4 * ks], qb[4 * ks + 1], qb[4 * ks + 2], qb[4 * ks + 3], dK + ((ks * kChunkBytes + 64) >> 4), 1, mq);
      wg_commit();
      if (k + 1 < nt) nb_arrive(1 + wg);
      uint32_t rt[9];
#pragma unroll
      for (int i = 0; i < 7; i++) rt[i] = sign_bytes(geo[0] << (i >> 2), 0x8888u + 0x1111u * (i & 3));
      rt[7] = sign_bytes(geo[0] << 2, 0x9988u);
      rt[8] = sign_bytes(geo[0] << 2, 0xBBAAu);
      keep_regs(rt);
      pa[13] = pb[13] = 0u;
      wg_wait<2>();
      keep_regs(qa);
      fence_regs(aO);
      float oA[6], eB[8];
      pick_u(aO, oA, fl);
      wg_wait<1>();
      fence_regs(bE);
      pick_v(bE, eB, fl);
      vA[8] = sel<kColA>(oA[0], vA[8], fl), vA[9] = sel<kColA>(oA[1], vA[9], fl);
      vA[10] = sel<kColA * 2>(oA[2], vA[10], fl), vA[11] = sel<kColA * 2>(oA[3], vA[11], fl);
      vA[12] = sel<kColA * 4>(oA[4], vA[12], fl), vA[13] = sel<kColA * 4>(oA[5], vA[13], fl);
      {
        const float m1 = __uint_as_float(0x88DD88DDu), m0 = __uint_as_float(0x88DDDD88u);
        meta[0] = 0xDD88DD88u ^ __byte_perm(fl, 0u, 0x3344);
        meta[1] = __float_as_uint(sel<kColA * 16>(sel<kColA>(m1, m0, fl), __uint_as_float(meta[0]), fl));
        meta[2] = __float_as_uint(sel<kColA * 8>(m1, m0, fl));
        meta[3] = __float_as_uint(sel<kColA * 4>(m1, m0, fl));
        keep_regs(meta);
      }
      float mA = own_max(vA, fl);
      fl |= __float_as_uint(eB[7]) & zero;
      fence_regs(eB);
      fence_regs(vA);
      asm volatile("" : "+f"(mA), "+r"(fl));
      sched_fence();
      wg_wait<0>();
      sched_fence();
      keep_regs(qb);
      fence_regs(bO);
      PROFS(6, wg, 6 + it * 12);
      if (w == 0) GT(24 + k);
      mA = quad_max(mA);
#pragma unroll
      for (int i = 0; i < 14; i++) vA[i] = ex2(vA[i] - mA);
      pick_v(bO, vB, fl);
      pick_u(bO + 28, vB + 8, fl);
#pragma unroll
      for (int i = 0; i < 8; i += 2) vB[i] = sel<kColB>(vB[i], eB[i], fl), vB[i + 1] = sel<kColB * 2>(vB[i + 1], eB[i + 1], fl);
      float mB = quad_max(own_max(vB, fl));
      PROFS(7, wg, 7 + it * 12);
#pragma unroll
      for (int i = 0; i < 14; i++) vB[i] = ex2(vB[i] - mB);
      route(vA, row_rcp(vA, fl), rt, pa);
      route(vB, row_rcp(vB, fl), rt, pb);
    }
    PROFS(8, wg, 8 + it * 12);
    if (k == NAT_PK) PROFS(18, wg, 53);
    sched_fence();

    float ac0[48], ac1[48];
    {
      float z0[32], z1[32], z2[32];
      uint32_t za[24], zb[24];
      wg_fence();
      pv_chunk<0>(z0, pa, pb, meta, dV);
      wg_commit();
      pv_chunk<1>(z1, pa, pb, meta, dV);
      wg_commit();
      wg_wait<1>();
      if (k == NAT_PK) PROFS(18, wg, 54);
      if (k + 1 < nt) nb_arrive_p(7);
      pv_chunk<2, 0, 3>(z2, pa, pb, meta, dV);
      wg_commit();
      sched_fence();
      fence_regs(z0);
      pack_z<0>(z0, za, zb);
      sched_fence();
      wg_fence();
      pv_chunk<2, 3, 7>(z2, pa, pb, meta, dV);
      wg_commit();
      wg_wait<2>();
      if (k == NAT_PK) PROFS(19, wg, 55);
      if (k + 1 < nt) nb_arrive_p(8);
      if (k < 2) mbar_wait(k == 1 ? bar_wok(bars) : bar_w2a(bars), 0);
      wg_fence();
      g2_steps<0, 3, 0>(ac0, za, zb, dX0);
      wg_commit();
      sched_fence();
      fence_regs(z1);
      pack_z<1>(z1, za, zb);
      sched_fence();
      wg_fence();
      g2_steps<3, 4, 0>(ac0, za, zb, dX0);
      wg_commit();
      g2_steps<4, 8, 0>(ac0, za, zb, dX0);
      wg_commit();
      wg_wait<3>();
      if (k + 1 < nt) nb_arrive_p(9);
      else nb_arrive(11);
      if (k == NAT_PK) PROFS(20, wg, 56);
      keep_regs(pa);
      keep_regs(pb);
      keep_regs(meta);
      sched_fence();
      const uint32_t mok = mbar_test(bar_w2m(bars), k + 1 < nt ? k & 1 : ~k & 1);
      const uint32_t wp = k < 2 ? 0 : k + 1 < nt ? ~k & 1 : k & 1, wok = mbar_test(bar_w2(bars), wp);
      fence_regs(z2);
      pack_z<2>(z2, za, zb);
      keep_regs(za);
      keep_regs(zb);
      sched_fence();
      PROFS(9, wg, 9 + it * 12);
      wg_wait<1>();
      if (k > 0 && k + 1 < nt) nb_arrive(11);
      mbar_wait_if(mok, bar_w2m(bars), k & 1);
      wg_fence();
      g2_steps<8, 12, 0>(ac0, za, zb, dX2);
      wg_commit();
      g2_steps<8, 12, 8>(ac1, za, zb, dY2);
      wg_commit();
      wg_wait<2>();
      if (k > 0 && k + 1 < nt) nb_arrive(12);
      mbar_wait_if(wok, bar_w2(bars), wp);
      wg_fence();
      g2_steps<0, 4, 8>(ac1, za, zb, dY0);
      wg_commit();
      wg_wait<2>();
      if (k + 2 < nt) nb_arrive_p(13);
      const bool direct = k + 2 >= nt;
      sched_fence();
      fence_regs(ac0);
      pack_out<0>(ac0, oa, ob);
      store_rows<0, 1>(direct, poA, poB, oa, ob);
      sched_fence();
      wg_fence();
      g2_steps<4, 8, 8>(ac1, za, zb, dY0);
      wg_commit();
      if (k + 1 < nt) nb_arrive(3 + wg);
      PROFS(10, wg, 10 + it * 12);
      wg_wait<2>();
      if (k + 2 < nt && (k > 0 || nt == 6)) nb_arrive_p(5);
      store_rows<1, 3>(direct, poA, poB, oa, ob);
      __nv_bfloat16 *qA = poA - 192 * wg, *qB = poB - 192 * wg;
      if (k + 2 == nt) nb_sync(11);
      sched_fence();
      wg_wait<0>();
      fence_regs(ac1);
      pack_out<1>(ac1, oa, ob);
      asm volatile("" : "+l"(qA), "+l"(qB));
      store_rows<3, 6>(direct, qA, qB, oa, ob);
      if (direct) break;
      if (k == 0) {
        if (any_nan(oa)) {
          for (int c = 0; c < 3 && __any_sync(0xffffffffu, geo[2] & 1u); c++) mbar_wait(bar_x(bars, 1, c), 1);
          bool first = true;
          do {
            if (!__any_sync(0xffffffffu, refetch(sbase + kW2Off, wimg + w2_offset(), first))) break;
            first = false;
            wg_fence();
            g2_steps<0, 8, 0>(ac0, za, zb, dX0);
            g2_steps<8, 12, 0>(ac0, za, zb, dX2);
            g2_steps<8, 12, 8>(ac1, za, zb, dY2);
            g2_steps<0, 8, 8>(ac1, za, zb, dY0);
            wg_commit();
            wg_wait<0>();
            fence_regs(ac0);
            fence_regs(ac1);
            pack_out<0>(ac0, oa, ob);
            pack_out<1>(ac1, oa, ob);
          } while (any_nan(oa));
          if (__any_sync(0xffffffffu, geo[2] & 1u)) {
            asm volatile("bar.sync 15, 128;" ::: "memory");
            if (w == 0 && elect_one()) {
              const TileCoord tc = decode_tile(tt, tile0 + 2);
              mbar_arrive_expect_tx(bar_raw(bars), kWChunk);
#pragma unroll 1
              for (int c = 0; c < 3; c++) load_px(tm, tt, sbase + x_chunk(2, c), bar_raw(bars), first_line(tc) + c, tc.kind);
            }
            __syncwarp();
            mbar_wait(bar_raw(bars), 0);
          }
        }
        if (nt < 6) nb_arrive_p(5);
        if (elect_one()) mbar_arrive(bar_wok(bars));
      }
      keep_regs(za);
      keep_regs(zb);
#pragma unroll
      for (int i = 0; i < 4; i++) geo[i] = geo[i + 2];
      keep_regs(oa);
      keep_regs(ob);
      PROFS(12, wg, 12 + it * 12);
      sched_fence();
    }
  }
  PROF(wg, 38);
  GT_DUMP();
  PROF_DUMP(wg);
}

struct HaloCols { int vj, vc, uj, uc; };
__device__ __forceinline__ HaloCols halo_cols(const TileCoord& tc) {
  const int c0 = halo_c0(tc);
  return HaloCols{c0 > 98, c0 > 98 ? 98 : c0 + 3, c0 < 0 ? -1 : 0, c0 < 0 ? 4 : c0};
}
__device__ __forceinline__ void first_halo(const Maps& tm, uint32_t sbase, const TileCoord tc, int i) {
  const HaloCols hc = halo_cols(tc);
  const uint32_t dst = sbase + i * kChunkBytes, bar = bar_full(sbase + kBarOff, 0, i >> 1);
  const int h0 = halo_r0(tc), ch = 24 * tc.pc + 4 * i;
  tma_load_5d(dst, &tm.v14, bar, ch, hc.vj, hc.vc, tc.pr, h0);
  tma_load_5d(dst + 7 * 1024, &tm.u8, bar, ch, hc.uj, h0 + (tc.up ? 0 : -2), tc.pr, hc.uc);
  tma_load_5d(dst + 10 * 1024, &tm.u8, bar, ch, hc.uj, h0 + (tc.up ? 8 : 6), tc.pr, hc.uc);
}
__device__ __forceinline__ void load_halo(const Maps& tm, uint32_t sbase, uint32_t bars, const TileCoord tc, int k, int c) {
  const HaloCols hc = halo_cols(tc);
  const int h6 = halo_r0(tc) + (tc.up ? 0 : 8), h2 = halo_r0(tc) + 6, h8 = halo_r0(tc) + (tc.up ? 0 : 6), ch = 24 * tc.pc + 8 * c;
  uint32_t dv = sbase + 2 * c * kChunkBytes, du = dv + 7 * 1024;
  if (((k ^ tc.up) & 1) == 0) dv += 4 * 1024, du += 3 * 1024;
  const uint32_t bar = bar_full(bars, k & 1, c);
  mbar_arrive_expect_tx(bar, 14 * 1024);
  nb_sync_p(7 + c);
#pragma unroll
  for (int h = 0; h < 2; h++) {
    tma_load_5d(dv + h * kChunkBytes, &tm.v6, bar, ch + 4 * h, hc.vj, hc.vc, tc.pr, h6);
    tma_load_5d(du + h * kChunkBytes, &tm.u8, bar, ch + 4 * h, hc.uj, h8, tc.pr, hc.uc);
    tma_load_5d(sbase + (2 * c + h) * kChunkBytes + 3 * 1024, &tm.v2, bar, ch + 4 * h, hc.vj, hc.vc, tc.pr, h2);
  }
  PROFS(15, 2, k * 4 + c);
}
__device__ __forceinline__ void gather_px(const __nv_bfloat16* __restrict__ x, uint32_t sbase, const TileCoord tc) {
  const int lane = threadIdx.x & 31, g = lane >> 3;
  uint32_t ro[4], co[4];
#pragma unroll
  for (int i = 0; i < 4; i++) {
    ro[i] = qpix(tc.pr, 8 * tc.I + 2 * i + (g & 1)) * (kW * kC * 2) + 16 * (lane & 7);
    co[i] = qpix(tc.pc, 8 * tc.J + 2 * i + (g >> 1)) * (kC * 2);
  }
  const uint32_t dst = sbase + kXOff + g * 128 + (((lane & 7) ^ g) << 4);
  if (lane < 8)
    asm volatile("cp.async.bulk.prefetch.L2.global [%0], 3456;" ::"l"(x + (qpix(tc.pr, 8 * tc.I + lane) * kW + 215 * tc.pc) * kC) : "memory");
  __syncwarp();
  keep_regs(ro);
  keep_regs(co);
  sched_fence();
  nb_sync_p(13);
  nb_sync_p(5);
#pragma unroll
  for (int i = 0; i < 16; i++) {
    const char* src = (const char*)x + (ro[i >> 2] + co[i & 3]);
#pragma unroll
    for (int q = 0; q < 3; q++)
      asm volatile("cp.async.cg.shared.global [%0], [%1], 16;" ::"r"((dst ^ ((i & 1) * 576)) + (i >> 1) * 1024 + q * 8192), "l"(src + 128 * q) : "memory");
  }
  asm volatile("cp.async.wait_all;" ::: "memory");
  fence_proxy_async();
  __syncwarp();
  if (lane < 3) mbar_arrive(bar_x(sbase + kBarOff, 1, lane));
  __syncwarp();
}

__global__ void __launch_bounds__(384, 1)
nat_kernel(const __nv_bfloat16* __restrict__ x, __nv_bfloat16* out, const __nv_bfloat16* __restrict__ wqkv,
           const __nv_bfloat16* __restrict__ wo, uint8_t* wimg, const uint32_t zero,
           const __grid_constant__ Maps tm, const __grid_constant__ TileTable tt) {
  extern __shared__ uint8_t smem_raw[];
  constexpr uint32_t sbase = 1024;
  constexpr uint32_t bars = sbase + kBarOff;
  if (smem_u32(smem_raw) != sbase) __trap();
  const int tid = threadIdx.x;
  const uint32_t t_start = now_ns();
  if (tid == 0) GT(0);
  const int wid = __shfl_sync(0xffffffffu, tid >> 5, 0);
  const bool w2cta = blockIdx.x - 128 < 3 && wqkv != nullptr;
  if (wid >= 8) {
    asm volatile("setmaxnreg.dec.sync.aligned.u32 24;");
    const int c = wid & 3, lane = tid & 31;
    const int tile0 = blockIdx.x * kTilesPerCta, nt = num_tiles();
    uint32_t w2o = 0;
    if (c == 3) {
      if (elect_one()) wait_clock(t_start, NAT_TM);
      __syncwarp();
      asm volatile("prefetch.tensormap [%0];" ::"l"((uint64_t)tm.px) : "memory");
      asm volatile("prefetch.tensormap [%0];" ::"l"((uint64_t)&tm.v6) : "memory");
      asm volatile("prefetch.tensormap [%0];" ::"l"((uint64_t)&tm.v2) : "memory");
      asm volatile("prefetch.tensormap [%0];" ::"l"((uint64_t)(tm.px + (blockIdx.x < 112 ? 5 : 6))) : "memory");
      asm volatile("prefetch.tensormap [%0];" ::"l"((uint64_t)(tm.px + 7)) : "memory");
      if (nt < 6) {
        asm volatile("prefetch.tensormap [%0];" ::"l"((uint64_t)(tm.px + 1)) : "memory");
        asm volatile("prefetch.tensormap [%0];" ::"l"((uint64_t)(tm.px + 2)) : "memory");
        asm volatile("prefetch.tensormap [%0];" ::"l"((uint64_t)&tm.v14) : "memory");
        asm volatile("prefetch.tensormap [%0];" ::"l"((uint64_t)&tm.u8) : "memory");
      }
      __nanosleep(NAT_TW2 - 2800);
      asm volatile("bar.sync 4, 64;" ::: "memory");
      w2o = w2_offset();
      if (elect_one()) {
        mbar_arrive_expect_tx(bar_w2a(bars), kWChunk);
        mbar_arrive_expect_tx(bar_w2(bars), kWChunk);
        wait_clock(t_start, NAT_TW2);
        bulk_load(sbase + kW2Off, wimg + w2o, kWChunk, bar_w2a(bars));
        mbar_wait(bar_xf(bars), 0);
        bulk_load(sbase + kW2Off + 2 * kWChunk, wimg + (w2o + 2 * kWChunk), kWChunk, bar_w2(bars));
      }
      __syncwarp();
      if (nt < 6) gather_px(x, sbase, decode_tile(tt, tile0 + 2));
      if (wqkv == nullptr) return;
      mbar_wait(bar_wok(bars), 0);
      if (lane == 0) asm volatile("red.relaxed.gpu.global.add.u32 [%0], 1;" ::"l"(g_flag) : "memory");
      if (blockIdx.x != kCtas - 1) return;
#pragma unroll
      for (int i = 0; i < 8; i++) asm volatile("st.shared.v4.u32 [%0], {%1,%1,%1,%1};" ::"r"(bars + 1024 + i * 512 + lane * 16), "r"(kEmpty) : "memory");
      fence_proxy_async();
      __syncwarp();
      if (elect_one()) {
#pragma unroll 1
        for (int i = 0; i < 36; i++) {
          if (i == 18) {
            uint32_t v, it = 0;
            do {
              __nanosleep(500);
              asm volatile("ld.relaxed.gpu.global.u32 %0, [%1];" : "=r"(v) : "l"(g_flag) : "memory");
            } while (v < gridDim.x && ++it < (1u << 18));
          }
          asm volatile("cp.async.bulk.global.shared::cta.bulk_group [%0], [%1], 4096;" ::"l"(
                           wimg + (i < 18 ? 3 * kWBytes - w2o + i * 4096 : (i - 18) * 4096)), "r"(bars + 1024) : "memory");
          asm volatile("cp.async.bulk.commit_group;" ::: "memory");
          asm volatile("cp.async.bulk.wait_group.read 1;" ::: "memory");
        }
        asm volatile("cp.async.bulk.wait_group 0;" ::: "memory");
        g_flag[0] = 0;
        g_flag[32] = w2o == kWBytes;
      }
      return;
    }
    if (!elect_one()) return;
    if (c == 0) {
      for (int i = 0; i < kNumBars; i++)
        if ((i != 0 && i != 10 || nt < 6) && (i != 21 || !w2cta)) mbar_init(bars + i * 8, i == 13 || i == 16 ? 4 : 1);
      asm volatile("st.shared.v2.u32 [%0], {%1,%1};" ::"r"(bars + 192), "r"(0) : "memory");
      asm volatile("fence.mbarrier_init.release.cluster;" ::: "memory");
      if (w2cta) asm volatile("bar.sync 10, 64;" ::: "memory");
      asm volatile("bar.arrive 0, 160;" ::: "memory");
      asm volatile("bar.arrive 14, 160;" ::: "memory");
      asm volatile("bar.arrive 13, 96;" ::: "memory");
      asm volatile("bar.arrive 4, 64;" ::: "memory");
      const TileCoord tc0 = decode_tile(tt, tile0);
      const HaloCols hc = halo_cols(tc0);
      const int h0 = halo_r0(tc0);
#pragma unroll
      for (int j = 0; j < 3; j++)
        if (j > 0 || nt < 6) mbar_arrive_expect_tx(bar_full(bars, 0, j), 2 * kChunkBytes);
      wait_clock(t_start, NAT_HP);
#pragma unroll
      for (int q = 8; q < 24 && !w2cta; q += 8) {
        tma_prefetch_5d(blockIdx.x < 112 ? &tm.v6 : &tm.v14, 24 * tc0.pc + q, hc.vj, hc.vc, tc0.pr, h0 + (tc0.up || blockIdx.x >= 112 ? 0 : 8));
        tma_prefetch_5d(&tm.u8, 24 * tc0.pc + q, hc.uj, h0 + (tc0.up ? 0 : 6), tc0.pr, hc.uc);
      }
#pragma unroll 1
      for (int i = nt < 6 ? 0 : 2; i < 6; i++) {
        if (i == 2) mbar_wait(bar_w1q(bars), 0);
        first_halo(tm, sbase, tc0, i);
      }
      mbar_arrive(bar_go(bars));
      w2o = w2_offset();
    } else {
      asm volatile("bar.sync 13, 96;" ::: "memory");
      if (c == 2) {
        if (wqkv != nullptr && blockIdx.x < 131) asm volatile("bar.sync 12, 64;" ::: "memory");
        const uint32_t c0 = clock();
        while ((uint32_t)clock() - c0 < NAT_TD && nt == 6) { }
        wait_clock(t_start, NAT_T0);
#pragma unroll
        for (int j = 0; j < 3; j++) {
          mbar_arrive_expect_tx(bar_w1c(bars, j), kWChunk);
          bulk_load(sbase + kW1Off + j * kWChunk, wimg + j * kWChunk, kWChunk, bar_w1c(bars, j));
        }
        mbar_arrive(bar_w1q(bars));
        GT(2);
      } else {
#pragma unroll 1
        for (int j = nt == 6; j < 2; j++) {
          const TileCoord tc = decode_tile(tt, tile0 + j);
          const int line = first_line(tc);
          if (j == 1) mbar_wait(bar_go(bars), 0);
          if (j == 0) GT(15);
#pragma unroll 1
          for (int q = 0; q < 3; q++) {
            load_px(tm, tt, sbase + x_chunk(j, q), bar_x(bars, j, q), line + q, tc.kind);
            if (j == 1 || q == 0) mbar_arrive_expect_tx(bar_x(bars, j, q), j ? 8192 : kWChunk);
          }
          if (j == 0) GT(16);
        }
        w2o = w2_offset();
        wait_clock(t_start, NAT_TW2);
        mbar_wait(bar_xf(bars), 0);
      }
    }
#pragma unroll 1
    for (int k = 1; k < nt; k++) {
      const TileCoord tn = decode_tile(tt, tile0 + k + 1);
      const int line = first_line(tn);
      const bool more = k + 1 < nt && (k > 1 || nt == 6);
      if (c == 1) {
#pragma unroll
        for (int q = 0; q < 3; q++) {
          nb_sync_p(q == 0 ? 0 : q == 1 ? 14 : 6);
          bulk_load(sbase + x_chunk(k, q), wimg + (w2o + x_chunk(k, q) - kW2Off), 8192, bar_w2m(bars));
        }
        mbar_arrive_expect_tx(bar_w2m(bars), kWChunk);
      }
      if (c == 2) {
        if (k == 1) wait_clock(t_start, NAT_TX2);
        else __nanosleep(NAT_PFD);
#pragma unroll 1
        for (int q = 0; q < 3 && more; q++) load_px(tm, tt, 0, 0, line + q, tn.kind);
      }
      if (c == 2 && (blockIdx.x >= 112 || k == 5)) {
        const TileCoord tc = decode_tile(tt, tile0 + k);
        const HaloCols hc = halo_cols(tc);
        const int h8 = halo_r0(tc) + (tc.up ? 0 : 6);
#pragma unroll 1
        for (int q = 0; q < 24; q += 8) {
          tma_prefetch_5d(&tm.v6, 24 * tc.pc + q, hc.vj, hc.vc, tc.pr, h8);
          tma_prefetch_5d(&tm.v2, 24 * tc.pc + q, hc.vj, hc.vc, tc.pr, h8 + 6);
          tma_prefetch_5d(&tm.u8, 24 * tc.pc + q, hc.uj, h8, tc.pr, hc.uc);
        }
      }
      load_halo(tm, sbase, bars, decode_tile(tt, tile0 + k), k, c);
      if (c == 0 && more) {
#pragma unroll
        for (int q = 0; q < 3; q++) {
          if (q < 2) nb_sync_p(q ? 5 : 13);
          load_px(tm, tt, sbase + x_chunk(k + 1, q), bar_x(bars, 1, q), line + q, tn.kind);
          if (q != 1) mbar_arrive_expect_tx(bar_x(bars, 1, q), 8192);
        }
        mbar_arrive_expect_tx(bar_x(bars, 1, 1), 8192);
        PROFS(16, 2, k * 4 + 3);
      }
      if (c == 0 && k >= 2) {
        const TileCoord tp = decode_tile(tt, tile0 + k - 2);
        const int lp = first_line(tp);
        nb_sync_p(10);
        __nanosleep(NAT_XW);
        store_px(tm, tt, sbase + out_slot(k, nt), lp, tp.kind);
        if (k + 1 < nt) {
          asm volatile("cp.async.bulk.wait_group.read 0;" ::: "memory");
          bulk_load(sbase + out_slot(k, nt), wimg + (w2o + out_slot(k, nt) - kW2Off), kWChunk, bar_w2(bars));
          mbar_arrive_expect_tx(bar_w2(bars), kWChunk);
        }
      }
    }
    asm volatile("cp.async.bulk.wait_group 0;" ::: "memory");
  } else {
    if (blockIdx.x < 128) {
      if ((wid == 4 || (wid == 5 && blockIdx.x - 2 < 16)) && wqkv != nullptr) {
        fold_w1(blockIdx.x - 2 < 16 ? 2 * blockIdx.x + wid - 6 : blockIdx.x + (blockIdx.x < 2 ? 0 : 16), wqkv, wimg);
        if (wid == 4) asm volatile("bar.arrive 12, 64;" ::: "memory");
        if (tid == 128) GT(7);
      }
      sched_fence();
      if (wid == 1 && elect_one()) {
        const TileCoord tc = decode_tile(tt, blockIdx.x * kTilesPerCta);
        mbar_init(bar_x(bars, 0, 0), 1);
        asm volatile("fence.mbarrier_init.release.cluster;" ::: "memory");
        mbar_arrive_expect_tx(bar_x(bars, 0, 0), kWChunk);
        GT(15);
#pragma unroll 1
        for (int q = 0; q < 3; q++) load_px(tm, tt, sbase + x_chunk(0, q), bar_x(bars, 0, 0), first_line(tc) + q, tc.kind);
        GT(16);
      }
      __syncwarp();
      sched_fence();
      if (wid == 2 && elect_one()) {
        const TileCoord tc = decode_tile(tt, blockIdx.x * kTilesPerCta);
        mbar_init(bar_full(bars, 0, 0), 1);
        asm volatile("fence.mbarrier_init.release.cluster;" ::: "memory");
        mbar_arrive_expect_tx(bar_full(bars, 0, 0), 2 * kChunkBytes);
        asm volatile("prefetch.tensormap [%0];" ::"l"((uint64_t)&tm.u8) : "memory");
        GT(17);
        first_halo(tm, sbase, tc, 0);
        first_halo(tm, sbase, tc, 1);
      }
      __syncwarp();
    }
    sched_fence();
    {
      if (w2cta) {
        const int q = blockIdx.x & 3;
        uint32_t w2o = 0;
        if (wid == 1 && elect_one()) {
          asm volatile("prefetch.tensormap [%0];" ::"l"((uint64_t)&tm.wo) : "memory");
#pragma unroll
          for (int j = 0; j < 3; j++) mbar_init(bar_raw(bars, j), 1);
          asm volatile("fence.mbarrier_init.release.cluster;" ::: "memory");
#pragma unroll
          for (int j = 0; j < 6; j++)
            asm volatile("cp.async.bulk.tensor.2d.shared::cluster.global.tile.mbarrier::complete_tx::bytes [%0], [%1, {%3, %4}], [%2];" ::"r"(
                             j < 3 ? sbase + j * 8192 : sbase + kW2Off + (j - 3) * kWChunk),
                         "l"((uint64_t)(j < 3 ? &tm.wv : &tm.wo)), "r"(bar_raw(bars, j < 3 ? 0 : j - 3)),
                         "r"(j < 3 ? 384 + 64 * j : 64 * (j - 3)), "r"(j < 3 ? 64 * q : 0) : "memory");
#pragma unroll
          for (int j = 0; j < 3; j++) mbar_arrive_expect_tx(bar_raw(bars, j), j ? kWChunk : 2 * kWChunk);
          w2o = w2_offset();
        }
        __syncwarp();
#pragma unroll 1
        for (int r = 0; r < 3; r++) {
          const int blk = 2 * r - 2 + (wid >> 2);
          if (blk < 3) {
            if (r > 0) {
              mbar_wait(bar_raw(bars, 0), 0);
              mbar_wait(bar_raw(bars, blk), 0);
            }
            if (tid == 0 && r == 1) GT(7);
            float acc[32];
            const uint64_t db = make_desc(sbase + kW2Off + max(blk, 0) * kWChunk, kWChunk, 1024);
            wg_fence();
            wg_m64tz<0, 32>(acc, make_desc(sbase, 16, 1024), db, 0);
#pragma unroll
            for (int s = 1; s < 12; s++) wg_m64t<0, 32>(acc, make_desc(sbase + (s >> 2) * 8192 + (s & 3) * 32, 16, 1024), db + s * 128, 1);
            wg_commit();
            wg_wait<0>();
            fence_regs(acc);
            if (tid == 0) GT(19);
            const int m = (tid >> 3) & 3;
#pragma unroll
            for (int j = 0; j < 8; j += 2) {
              const int n = g2_inv(8 * (j + (m >> 1)) + (tid & 7));
              asm volatile("stmatrix.sync.aligned.m8n8.x4.trans.shared.b16 [%0], {%1,%2,%3,%4};" ::"r"(
                               sbase + kW1Off + (blk + 2) * 8192 + n * 128 + (((2 * (wid & 3) + (m & 1)) ^ (n & 7)) << 4)),
                           "r"(pack_bf16(acc[4 * j], acc[4 * j + 1])), "r"(pack_bf16(acc[4 * j + 2], acc[4 * j + 3])),
                           "r"(pack_bf16(acc[4 * j + 4], acc[4 * j + 5])), "r"(pack_bf16(acc[4 * j + 6], acc[4 * j + 7])) : "memory");
            }
            fence_proxy_async();
          }
          if (tid == 0) GT(18);
          asm volatile("bar.sync 11, 256;" ::: "memory");
          if (wid == 1 && elect_one()) {
            asm volatile("{\n.reg .pred p;\nsetp.ne.s32 p, %3, 0;\n@p cp.async.bulk.global.shared::cta.bulk_group [%0], [%1], %2;\n}\n" ::"l"(
                             wimg + (w2o + w2piece(r >> 1, q) * (kWChunk / 2))),
                         "r"(sbase + kW1Off + 16384 + (r >> 1) * (kWChunk / 2)), "r"(kWChunk / 2), "r"(r) : "memory");
            asm volatile("cp.async.bulk.commit_group;" ::: "memory");
          }
          __syncwarp();
        }
        if (wid == 1) {
          asm volatile("bar.arrive 10, 64;" ::: "memory");
          if (elect_one()) asm volatile("cp.async.bulk.wait_group.read 0;" ::: "memory");
          if (tid == 32) GT(31);
          __syncwarp();
          asm volatile("bar.arrive 12, 64;" ::: "memory");
        }
      }
    }
    __syncwarp();
    if (wid < 4) asm volatile("bar.sync 0, 160;" ::: "memory");
    else asm volatile("bar.sync 14, 160;" ::: "memory");
    asm volatile("setmaxnreg.inc.sync.aligned.u32 240;");
    consumer(wid >> 2, out, wimg, sbase, zero, tm, tt);
  }
}

}

typedef CUresult (*PFN_encodeTiled)(CUtensorMap*, CUtensorMapDataType, cuuint32_t, void*, const cuuint64_t*,
                                    const cuuint64_t*, const cuuint32_t*, const cuuint32_t*, CUtensorMapInterleave,
                                    CUtensorMapSwizzle, CUtensorMapL2promotion, CUtensorMapFloatOOBfill);

extern "C" void kernel_launch(void* const* d_in, const int* in_sizes, int n_in, void* d_out, int out_size) {
  const __nv_bfloat16* x = (const __nv_bfloat16*)d_in[0];
  const __nv_bfloat16* wqkv = (const __nv_bfloat16*)d_in[1];
  const __nv_bfloat16* wo = (const __nv_bfloat16*)d_in[2];
  __nv_bfloat16* out = (__nv_bfloat16*)d_out;

  static PFN_encodeTiled encode = nullptr;
  static int num_sms = 0;
  static uint8_t* wimg = nullptr;
  if (!encode) {
    void* fn = nullptr;
    cudaDriverEntryPointQueryResult qres;
    cudaGetDriverEntryPoint("cuTensorMapEncodeTiled", &fn, cudaEnableDefault, &qres);
    encode = (PFN_encodeTiled)fn;
    cudaFuncSetAttribute(nat::nat_kernel, cudaFuncAttributeMaxDynamicSharedMemorySize, nat::kSmemBytes);
    cudaGetSymbolAddress((void**)&wimg, nat::g_wimg32);
    int dev = 0;
    cudaGetDevice(&dev);
    cudaDeviceGetAttribute(&num_sms, cudaDevAttrMultiProcessorCount, dev);
  }
  nat::Maps tm;
  cuuint32_t estr[5] = {1, 1, 1, 1, 1};
  {
    cuuint64_t vdim[5] = {48, 2, 105, 2, 112}, udim[5] = {48, 2, 112, 2, 105};
    cuuint64_t vstr[4] = {7 * 768, 768, 224 * 384, 2 * 224 * 384}, ustr[4] = {7 * 768, 2 * 224 * 384, 224 * 384, 768};
    CUtensorMap* maps[4] = {&tm.v6, &tm.v2, &tm.v14, &tm.u8};
    for (int i = 0; i < 4; i++) {
      cuuint32_t box[5] = {4, 2, i < 3 ? 4u : 8u, 1, i == 0 ? 6u : i == 1 ? 2u : i == 2 ? 14u : 3u};
      encode(maps[i], CU_TENSOR_MAP_DATA_TYPE_UINT32, 5, (void*)x, i < 3 ? vdim : udim, i < 3 ? vstr : ustr, box, estr,
             CU_TENSOR_MAP_INTERLEAVE_16B, CU_TENSOR_MAP_SWIZZLE_128B, CU_TENSOR_MAP_L2_PROMOTION_L2_128B, CU_TENSOR_MAP_FLOAT_OOB_FILL_NONE);
    }
  }
  for (int i = 0; i < 8; i++) {
    const cuuint32_t row = 224 * 384;
    const cuuint32_t shape[8][6] = {{2, 8, 4, 2 * row, 768, 4 * row}, {2, 8, 3, row, 768, 2 * row},     {2, 8, 1, 2 * row, 768, 4 * row},
                                    {8, 2, 3, 2 * row, 4 * 384, 384}, {8, 2, 1, 2 * row, 5 * 384, 384}, {4, 2, 3, 4 * row, 2 * row, 128},
                                    {4, 2, 3, 768, row, 128},         {4, 2, 3, 768, 2 * row, 128}};
    const cuuint32_t* sh = shape[i];
    cuuint64_t dim[5] = {64, sh[0], sh[1], sh[2], 224 * 224 * 3};
    cuuint64_t str[4] = {sh[3], sh[4], sh[5], 128};
    cuuint32_t box[5] = {64, sh[0], sh[1], sh[2], 1};
    encode(tm.px + i, CU_TENSOR_MAP_DATA_TYPE_BFLOAT16, 5, i < 5 ? (void*)x : (void*)out, dim, str, box, estr, CU_TENSOR_MAP_INTERLEAVE_NONE,
           CU_TENSOR_MAP_SWIZZLE_128B, i < 5 ? CU_TENSOR_MAP_L2_PROMOTION_L2_128B : CU_TENSOR_MAP_L2_PROMOTION_NONE,
           CU_TENSOR_MAP_FLOAT_OOB_FILL_NONE);
  }
  for (int i = 0; i < 2; i++) {
    cuuint64_t dim[2] = {i ? 192u : 576u, 192}, str[1] = {i ? 384u : 1152u};
    cuuint32_t box[2] = {64, i ? 192u : 64u};
    encode(i ? &tm.wo : &tm.wv, CU_TENSOR_MAP_DATA_TYPE_BFLOAT16, 2, i ? (void*)wo : (void*)wqkv, dim, str, box, estr,
           CU_TENSOR_MAP_INTERLEAVE_NONE, CU_TENSOR_MAP_SWIZZLE_128B, CU_TENSOR_MAP_L2_PROMOTION_L2_256B, CU_TENSOR_MAP_FLOAT_OOB_FILL_NONE);
  }
  nat::TileTable tt;
  nat::make_tiles(tt);
  const int grid = nat::kCtas;
  if (num_sms >= grid) {
    nat::nat_kernel<<<grid, 384, nat::kSmemBytes>>>(x, out, wqkv, wo, wimg, 0u, tm, tt);
  } else {
    nat::fold_kernel<<<27, 256>>>(wqkv, wo, wimg);
    nat::nat_kernel<<<grid, 384, nat::kSmemBytes>>>(x, out, nullptr, nullptr, wimg, 0u, tm, tt);
  }
}
```

```cpp
#include <cuda_runtime.h>
#include <cuda_bf16.h>
#include <cuda.h>
#include <stdint.h>

#define NAT_TM 1300
#define NAT_HP 1800
#define NAT_T0 2130
#define NAT_TD 1250
#define NAT_TX2 3800
#define NAT_TW2 4600
#define NAT_PFD 300
#define NAT_XW 200
#define NAT_PK 3
namespace nat {

constexpr int kW = 224, kC = 192;
constexpr int kCtas = 132;
constexpr int kTilesPerCta = 6;
constexpr float kAlpha = 0.07216878364870322f * 1.4426950408889634f;
constexpr uint32_t kChunkBytes = 13 * 1024;
constexpr uint32_t kWChunk = 192 * 128;
constexpr uint32_t kWBytes = 3 * kWChunk;
constexpr uint32_t kW1Off = 6 * kChunkBytes;
constexpr uint32_t kW2Off = kW1Off + kWBytes;
constexpr uint32_t kXOff = kW2Off + kWChunk;
constexpr uint32_t kBarOff = kW2Off + kWBytes;
constexpr uint32_t kProfOff = kBarOff + 208;
constexpr uint32_t kSmemBytes = kBarOff + 1024 + 4096;

static_assert(kW1Off % 1024 == 0 && kW2Off % 1024 == 0 && kChunkBytes % 1024 == 0, "swizzle alignment");
static_assert(kSmemBytes <= 232448, "smem");

constexpr uint32_t kEmpty = 0xFFFFFFFFu;
#define NAT_R8(v) v, v, v, v, v, v, v, v
#define NAT_R2K(v) NAT_R8(NAT_R8(NAT_R8(v))), NAT_R8(NAT_R8(NAT_R8(v))), NAT_R8(NAT_R8(NAT_R8(v))), NAT_R8(NAT_R8(NAT_R8(v)))
#define NAT_IMG NAT_R8(NAT_R2K(kEmpty)), NAT_R2K(kEmpty)
__device__ __align__(1024) uint32_t g_wimg32[3 * kWBytes / 4] = {NAT_IMG, NAT_IMG, NAT_IMG};
static_assert(kWBytes / 4 == 9 * 2048, "initialiser");
__device__ __align__(128) uint32_t g_flag[64];
__device__ __forceinline__ uint32_t w2_offset() {
  uint32_t v;
  asm volatile("ld.relaxed.gpu.global.u32 %0, [%1];" : "=r"(v) : "l"(g_flag + 32) : "memory");
  return (1 + v) * kWBytes;
}

#define PROFS(id, wgid, slotid) do { } while (0)
#define PROF(wgid, slotid) do { } while (0)
#define PROF_DUMP(wgid) do { } while (0)

#define GT(slotid) do { } while (0)
#define GT_DUMP() do { } while (0)

__device__ __forceinline__ uint32_t smem_u32(const void* p) { return (uint32_t)__cvta_generic_to_shared(p); }

__device__ __forceinline__ void mbar_init(uint32_t bar, uint32_t count) {
  asm volatile("mbarrier.init.shared::cta.b64 [%0], %1;" ::"r"(bar), "r"(count) : "memory");
}
__device__ __forceinline__ void mbar_arrive(uint32_t bar) {
  asm volatile("mbarrier.arrive.shared::cta.b64 _, [%0];" ::"r"(bar) : "memory");
}
__device__ __forceinline__ void mbar_arrive_expect_tx(uint32_t bar, uint32_t bytes) {
  asm volatile("mbarrier.arrive.expect_tx.shared::cta.b64 _, [%0], %1;" ::"r"(bar), "r"(bytes) : "memory");
}
__device__ __forceinline__ void mbar_wait(uint32_t bar, uint32_t parity) {
  uint32_t ok;
  uint32_t it = 0;
  do {
    asm volatile(
        "{\n.reg .pred p;\n"
        "mbarrier.try_wait.parity.shared::cta.b64 p, [%1], %2;\n"
        "selp.u32 %0, 1, 0, p;\n}\n"
        : "=r"(ok)
        : "r"(bar), "r"(parity)
        : "memory");
    if (++it > (1u << 24)) break;
  } while (!ok);
}
__device__ __forceinline__ uint32_t mbar_test(uint32_t bar, uint32_t parity) {
  uint32_t ok;
  asm volatile("{\n.reg .pred p;\nmbarrier.test_wait.parity.shared::cta.b64 p, [%1], %2;\nselp.u32 %0, 1, 0, p;\n}\n"
               : "=r"(ok) : "r"(bar), "r"(parity) : "memory");
  return ok;
}
__device__ __forceinline__ void mbar_wait_if(uint32_t ok, uint32_t bar, uint32_t parity) {
  if (!__all_sync(0xffffffffu, ok)) mbar_wait(bar, parity);
}
__device__ __forceinline__ bool elect_one() {
  uint32_t r;
  asm volatile("{\n.reg .pred p;\nelect.sync _|p, 0xffffffff;\nselp.u32 %0, 1, 0, p;\n}\n" : "=r"(r));
  return r != 0;
}
__device__ __forceinline__ void nb_arrive(int id) { asm volatile("bar.arrive %0, 256;" ::"r"(id) : "memory"); }
__device__ __forceinline__ void nb_sync(int id) { asm volatile("bar.sync %0, 256;" ::"r"(id) : "memory"); }
__device__ __forceinline__ void nb_arrive_p(int id) { asm volatile("bar.arrive %0, 160;" ::"r"(id) : "memory"); }
__device__ __forceinline__ void nb_sync_p(int id) { asm volatile("bar.sync %0, 160;" ::"r"(id) : "memory"); }
__device__ __forceinline__ void fence_proxy_async() { asm volatile("fence.proxy.async.shared::cta;" ::: "memory"); }

__device__ __forceinline__ void tma_load_5d(uint32_t dst, const CUtensorMap* map, uint32_t bar, int c0, int c1, int c2,
                                            int c3, int c4) {
  asm volatile(
      "cp.async.bulk.tensor.5d.shared::cluster.global.tile.mbarrier::complete_tx::bytes "
      "[%0], [%1, {%3, %4, %5, %6, %7}], [%2];"
      ::"r"(dst), "l"((uint64_t)map), "r"(bar), "r"(c0), "r"(c1), "r"(c2), "r"(c3), "r"(c4)
      : "memory");
}
__device__ __forceinline__ void bulk_load(uint32_t dst, const void* src, uint32_t bytes, uint32_t bar) {
  asm volatile("cp.async.bulk.shared::cluster.global.mbarrier::complete_tx::bytes [%0], [%1], %2, [%3];"
               ::"r"(dst), "l"((uint64_t)src), "r"(bytes), "r"(bar)
               : "memory");
}

__device__ __forceinline__ void wg_fence() { asm volatile("wgmma.fence.sync.aligned;" ::: "memory"); }
__device__ __forceinline__ void wg_commit() { asm volatile("wgmma.commit_group.sync.aligned;" ::: "memory"); }
template <int N>
__device__ __forceinline__ void wg_wait() { asm volatile("wgmma.wait_group.sync.aligned %0;" ::"n"(N) : "memory"); }

template <int N>
__device__ __forceinline__ void fence_regs(float (&d)[N]) {
#pragma unroll
  for (int i = 0; i < N; i++) asm volatile("" : "+f"(d[i])::"memory");
}
template <int N>
__device__ __forceinline__ void keep_regs(uint32_t (&d)[N]) {
#pragma unroll
  for (int i = 0; i < N; i++) asm volatile("" : "+r"(d[i])::"memory");
}

__device__ __forceinline__ uint32_t pack_bf16(float lo, float hi) {
  uint32_t d;
  asm("cvt.rn.bf16x2.f32 %0, %1, %2;" : "=r"(d) : "f"(hi), "f"(lo));
  return d;
}
__device__ __forceinline__ float ex2(float x) {
  float y;
  asm("ex2.approx.ftz.f32 %0, %1;" : "=f"(y) : "f"(x));
  return y;
}
__device__ __forceinline__ float rcp_approx(float x) {
  float y;
  asm("rcp.approx.ftz.f32 %0, %1;" : "=f"(y) : "f"(x));
  return y;
}
__device__ __forceinline__ uint4 ldg128_nc(const void* p) {
  uint4 v;
  asm volatile("ld.global.nc.v4.u32 {%0,%1,%2,%3}, [%4];" : "=r"(v.x), "=r"(v.y), "=r"(v.z), "=r"(v.w) : "l"(p));
  return v;
}

__device__ __forceinline__ long long clk64() {
  long long c;
  asm volatile("mov.u64 %0, %clock64;" : "=l"(c)::"memory");
  return c;
}
__device__ __forceinline__ void sched_fence() { while (clk64() < 0) { } }

__device__ __forceinline__ uint64_t make_desc(uint32_t addr, uint32_t lbo, uint32_t sbo, uint32_t mode = 1) {
  return (uint64_t)((addr & 0x3FFFF) >> 4) | ((uint64_t)(lbo >> 4) << 16) | ((uint64_t)(sbo >> 4) << 32) |
         ((uint64_t)mode << 62);
}

template <int OFF, int NN>
__device__ __forceinline__ void wg_m192(float (&d)[NN], uint64_t desc_a, uint64_t desc_b, int scale_d) {
  asm volatile(
      "{\n.reg .pred p;\nsetp.ne.b32 p, %98, 0;\n"
      "wgmma.mma_async.sync.aligned.m64n192k16.f32.bf16.bf16 "
      "{%0,%1,%2,%3,%4,%5,%6,%7,%8,%9,%10,%11,%12,%13,%14,%15,"
      "%16,%17,%18,%19,%20,%21,%22,%23,%24,%25,%26,%27,%28,%29,%30,%31,"
      "%32,%33,%34,%35,%36,%37,%38,%39,%40,%41,%42,%43,%44,%45,%46,%47,"
      "%48,%49,%50,%51,%52,%53,%54,%55,%56,%57,%58,%59,%60,%61,%62,%63,"
      "%64,%65,%66,%67,%68,%69,%70,%71,%72,%73,%74,%75,%76,%77,%78,%79,"
      "%80,%81,%82,%83,%84,%85,%86,%87,%88,%89,%90,%91,%92,%93,%94,%95}, "
      "%96, %97, p, 1, 1, 0, 0;\n}\n"
      : "+f"(d[OFF + 0]), "+f"(d[OFF + 1]), "+f"(d[OFF + 2]), "+f"(d[OFF + 3]), "+f"(d[OFF + 4]), "+f"(d[OFF + 5]),
        "+f"(d[OFF + 6]), "+f"(d[OFF + 7]), "+f"(d[OFF + 8]), "+f"(d[OFF + 9]), "+f"(d[OFF + 10]), "+f"(d[OFF + 11]),
        "+f"(d[OFF + 12]), "+f"(d[OFF + 13]), "+f"(d[OFF + 14]), "+f"(d[OFF + 15]), "+f"(d[OFF + 16]), "+f"(d[OFF + 17]),
        "+f"(d[OFF + 18]), "+f"(d[OFF + 19]), "+f"(d[OFF + 20]), "+f"(d[OFF + 21]), "+f"(d[OFF + 22]), "+f"(d[OFF + 23]),
        "+f"(d[OFF + 24]), "+f"(d[OFF + 25]), "+f"(d[OFF + 26]), "+f"(d[OFF + 27]), "+f"(d[OFF + 28]), "+f"(d[OFF + 29]),
        "+f"(d[OFF + 30]), "+f"(d[OFF + 31]), "+f"(d[OFF + 32]), "+f"(d[OFF + 33]), "+f"(d[OFF + 34]), "+f"(d[OFF + 35]),
        "+f"(d[OFF + 36]), "+f"(d[OFF + 37]), "+f"(d[OFF + 38]), "+f"(d[OFF + 39]), "+f"(d[OFF + 40]), "+f"(d[OFF + 41]),
        "+f"(d[OFF + 42]), "+f"(d[OFF + 43]), "+f"(d[OFF + 44]), "+f"(d[OFF + 45]), "+f"(d[OFF + 46]), "+f"(d[OFF + 47]),
        "+f"(d[OFF + 48]), "+f"(d[OFF + 49]), "+f"(d[OFF + 50]), "+f"(d[OFF + 51]), "+f"(d[OFF + 52]), "+f"(d[OFF + 53]),
        "+f"(d[OFF + 54]), "+f"(d[OFF + 55]), "+f"(d[OFF + 56]), "+f"(d[OFF + 57]), "+f"(d[OFF + 58]), "+f"(d[OFF + 59]),
        "+f"(d[OFF + 60]), "+f"(d[OFF + 61]), "+f"(d[OFF + 62]), "+f"(d[OFF + 63]), "+f"(d[OFF + 64]), "+f"(d[OFF + 65]),
        "+f"(d[OFF + 66]), "+f"(d[OFF + 67]), "+f"(d[OFF + 68]), "+f"(d[OFF + 69]), "+f"(d[OFF + 70]), "+f"(d[OFF + 71]),
        "+f"(d[OFF + 72]), "+f"(d[OFF + 73]), "+f"(d[OFF + 74]), "+f"(d[OFF + 75]), "+f"(d[OFF + 76]), "+f"(d[OFF + 77]),
        "+f"(d[OFF + 78]), "+f"(d[OFF + 79]), "+f"(d[OFF + 80]), "+f"(d[OFF + 81]), "+f"(d[OFF + 82]), "+f"(d[OFF + 83]),
        "+f"(d[OFF + 84]), "+f"(d[OFF + 85]), "+f"(d[OFF + 86]), "+f"(d[OFF + 87]), "+f"(d[OFF + 88]), "+f"(d[OFF + 89]),
        "+f"(d[OFF + 90]), "+f"(d[OFF + 91]), "+f"(d[OFF + 92]), "+f"(d[OFF + 93]), "+f"(d[OFF + 94]), "+f"(d[OFF + 95])
      : "l"(desc_a), "l"(desc_b), "r"(scale_d));
}

template <int OFF, int NN>
__device__ __forceinline__ void wg_m192z(float (&d)[NN], uint64_t desc_a, uint64_t desc_b, int scale_d) {
  asm volatile(
      "{\n.reg .pred p;\nsetp.ne.b32 p, %98, 0;\n"
      "wgmma.mma_async.sync.aligned.m64n192k16.f32.bf16.bf16 "
      "{%0,%1,%2,%3,%4,%5,%6,%7,%8,%9,%10,%11,%12,%13,%14,%15,"
      "%16,%17,%18,%19,%20,%21,%22,%23,%24,%25,%26,%27,%28,%29,%30,%31,"
      "%32,%33,%34,%35,%36,%37,%38,%39,%40,%41,%42,%43,%44,%45,%46,%47,"
      "%48,%49,%50,%51,%52,%53,%54,%55,%56,%57,%58,%59,%60,%61,%62,%63,"
      "%64,%65,%66,%67,%68,%69,%70,%71,%72,%73,%74,%75,%76,%77,%78,%79,"
      "%80,%81,%82,%83,%84,%85,%86,%87,%88,%89,%90,%91,%92,%93,%94,%95}, "
      "%96, %97, p, 1, 1, 0, 0;\n}\n"
      : "=f"(d[OFF + 0]), "=f"(d[OFF + 1]), "=f"(d[OFF + 2]), "=f"(d[OFF + 3]), "=f"(d[OFF + 4]), "=f"(d[OFF + 5]),
        "=f"(d[OFF + 6]), "=f"(d[OFF + 7]), "=f"(d[OFF + 8]), "=f"(d[OFF + 9]), "=f"(d[OFF + 10]), "=f"(d[OFF + 11]),
        "=f"(d[OFF + 12]), "=f"(d[OFF + 13]), "=f"(d[OFF + 14]), "=f"(d[OFF + 15]), "=f"(d[OFF + 16]), "=f"(d[OFF + 17]),
        "=f"(d[OFF + 18]), "=f"(d[OFF + 19]), "=f"(d[OFF + 20]), "=f"(d[OFF + 21]), "=f"(d[OFF + 22]), "=f"(d[OFF + 23]),
        "=f"(d[OFF + 24]), "=f"(d[OFF + 25]), "=f"(d[OFF + 26]), "=f"(d[OFF + 27]), "=f"(d[OFF + 28]), "=f"(d[OFF + 29]),
        "=f"(d[OFF + 30]), "=f"(d[OFF + 31]), "=f"(d[OFF + 32]), "=f"(d[OFF + 33]), "=f"(d[OFF + 34]), "=f"(d[OFF + 35]),
        "=f"(d[OFF + 36]), "=f"(d[OFF + 37]), "=f"(d[OFF + 38]), "=f"(d[OFF + 39]), "=f"(d[OFF + 40]), "=f"(d[OFF + 41]),
        "=f"(d[OFF + 42]), "=f"(d[OFF + 43]), "=f"(d[OFF + 44]), "=f"(d[OFF + 45]), "=f"(d[OFF + 46]), "=f"(d[OFF + 47]),
        "=f"(d[OFF + 48]), "=f"(d[OFF + 49]), "=f"(d[OFF + 50]), "=f"(d[OFF + 51]), "=f"(d[OFF + 52]), "=f"(d[OFF + 53]),
        "=f"(d[OFF + 54]), "=f"(d[OFF + 55]), "=f"(d[OFF + 56]), "=f"(d[OFF + 57]), "=f"(d[OFF + 58]), "=f"(d[OFF + 59]),
        "=f"(d[OFF + 60]), "=f"(d[OFF + 61]), "=f"(d[OFF + 62]), "=f"(d[OFF + 63]), "=f"(d[OFF + 64]), "=f"(d[OFF + 65]),
        "=f"(d[OFF + 66]), "=f"(d[OFF + 67]), "=f"(d[OFF + 68]), "=f"(d[OFF + 69]), "=f"(d[OFF + 70]), "=f"(d[OFF + 71]),
        "=f"(d[OFF + 72]), "=f"(d[OFF + 73]), "=f"(d[OFF + 74]), "=f"(d[OFF + 75]), "=f"(d[OFF + 76]), "=f"(d[OFF + 77]),
        "=f"(d[OFF + 78]), "=f"(d[OFF + 79]), "=f"(d[OFF + 80]), "=f"(d[OFF + 81]), "=f"(d[OFF + 82]), "=f"(d[OFF + 83]),
        "=f"(d[OFF + 84]), "=f"(d[OFF + 85]), "=f"(d[OFF + 86]), "=f"(d[OFF + 87]), "=f"(d[OFF + 88]), "=f"(d[OFF + 89]),
        "=f"(d[OFF + 90]), "=f"(d[OFF + 91]), "=f"(d[OFF + 92]), "=f"(d[OFF + 93]), "=f"(d[OFF + 94]), "=f"(d[OFF + 95])
      : "l"(desc_a), "l"(desc_b), "r"(scale_d));
}

template <int OFF, int NN>
__device__ __forceinline__ void wg_m96t(float (&d)[NN], uint64_t desc_a, uint64_t desc_b, int scale_d) {
  asm volatile(
      "{\n.reg .pred p;\nsetp.ne.b32 p, %50, 0;\n"
      "wgmma.mma_async.sync.aligned.m64n96k16.f32.bf16.bf16 "
      "{%0,%1,%2,%3,%4,%5,%6,%7,%8,%9,%10,%11,%12,%13,%14,%15,"
      "%16,%17,%18,%19,%20,%21,%22,%23,%24,%25,%26,%27,%28,%29,%30,%31,"
      "%32,%33,%34,%35,%36,%37,%38,%39,%40,%41,%42,%43,%44,%45,%46,%47}, "
      "%48, %49, p, 1, 1, 0, 1;\n}\n"
      : "+f"(d[OFF + 0]), "+f"(d[OFF + 1]), "+f"(d[OFF + 2]), "+f"(d[OFF + 3]), "+f"(d[OFF + 4]), "+f"(d[OFF + 5]),
        "+f"(d[OFF + 6]), "+f"(d[OFF + 7]), "+f"(d[OFF + 8]), "+f"(d[OFF + 9]), "+f"(d[OFF + 10]), "+f"(d[OFF + 11]),
        "+f"(d[OFF + 12]), "+f"(d[OFF + 13]), "+f"(d[OFF + 14]), "+f"(d[OFF + 15]), "+f"(d[OFF + 16]), "+f"(d[OFF + 17]),
        "+f"(d[OFF + 18]), "+f"(d[OFF + 19]), "+f"(d[OFF + 20]), "+f"(d[OFF + 21]), "+f"(d[OFF + 22]), "+f"(d[OFF + 23]),
        "+f"(d[OFF + 24]), "+f"(d[OFF + 25]), "+f"(d[OFF + 26]), "+f"(d[OFF + 27]), "+f"(d[OFF + 28]), "+f"(d[OFF + 29]),
        "+f"(d[OFF + 30]), "+f"(d[OFF + 31]), "+f"(d[OFF + 32]), "+f"(d[OFF + 33]), "+f"(d[OFF + 34]), "+f"(d[OFF + 35]),
        "+f"(d[OFF + 36]), "+f"(d[OFF + 37]), "+f"(d[OFF + 38]), "+f"(d[OFF + 39]), "+f"(d[OFF + 40]), "+f"(d[OFF + 41]),
        "+f"(d[OFF + 42]), "+f"(d[OFF + 43]), "+f"(d[OFF + 44]), "+f"(d[OFF + 45]), "+f"(d[OFF + 46]), "+f"(d[OFF + 47])
      : "l"(desc_a), "l"(desc_b), "r"(scale_d));
}

template <int OFF, int NN>
__device__ __forceinline__ void wg_m96tz(float (&d)[NN], uint64_t desc_a, uint64_t desc_b, int scale_d) {
  asm volatile(
      "{\n.reg .pred p;\nsetp.ne.b32 p, %50, 0;\n"
      "wgmma.mma_async.sync.aligned.m64n96k16.f32.bf16.bf16 "
      "{%0,%1,%2,%3,%4,%5,%6,%7,%8,%9,%10,%11,%12,%13,%14,%15,"
      "%16,%17,%18,%19,%20,%21,%22,%23,%24,%25,%26,%27,%28,%29,%30,%31,"
      "%32,%33,%34,%35,%36,%37,%38,%39,%40,%41,%42,%43,%44,%45,%46,%47}, "
      "%48, %49, p, 1, 1, 0, 1;\n}\n"
      : "=f"(d[OFF + 0]), "=f"(d[OFF + 1]), "=f"(d[OFF + 2]), "=f"(d[OFF + 3]), "=f"(d[OFF + 4]), "=f"(d[OFF + 5]),
        "=f"(d[OFF + 6]), "=f"(d[OFF + 7]), "=f"(d[OFF + 8]), "=f"(d[OFF + 9]), "=f"(d[OFF + 10]), "=f"(d[OFF + 11]),
        "=f"(d[OFF + 12]), "=f"(d[OFF + 13]), "=f"(d[OFF + 14]), "=f"(d[OFF + 15]), "=f"(d[OFF + 16]), "=f"(d[OFF + 17]),
        "=f"(d[OFF + 18]), "=f"(d[OFF + 19]), "=f"(d[OFF + 20]), "=f"(d[OFF + 21]), "=f"(d[OFF + 22]), "=f"(d[OFF + 23]),
        "=f"(d[OFF + 24]), "=f"(d[OFF + 25]), "=f"(d[OFF + 26]), "=f"(d[OFF + 27]), "=f"(d[OFF + 28]), "=f"(d[OFF + 29]),
        "=f"(d[OFF + 30]), "=f"(d[OFF + 31]), "=f"(d[OFF + 32]), "=f"(d[OFF + 33]), "=f"(d[OFF + 34]), "=f"(d[OFF + 35]),
        "=f"(d[OFF + 36]), "=f"(d[OFF + 37]), "=f"(d[OFF + 38]), "=f"(d[OFF + 39]), "=f"(d[OFF + 40]), "=f"(d[OFF + 41]),
        "=f"(d[OFF + 42]), "=f"(d[OFF + 43]), "=f"(d[OFF + 44]), "=f"(d[OFF + 45]), "=f"(d[OFF + 46]), "=f"(d[OFF + 47])
      : "l"(desc_a), "l"(desc_b), "r"(scale_d));
}

template <int OFF, int NN>
__device__ __forceinline__ void wg_d96(float (&d)[NN], uint32_t a0, uint32_t a1, uint32_t a2, uint32_t a3,
                                       uint64_t desc_b, int scale_d) {
  asm volatile(
      "{\n.reg .pred p;\nsetp.ne.b32 p, %53, 0;\n"
      "wgmma.mma_async.sync.aligned.m64n96k16.f32.bf16.bf16 "
      "{%0,%1,%2,%3,%4,%5,%6,%7,%8,%9,%10,%11,%12,%13,%14,%15,"
      "%16,%17,%18,%19,%20,%21,%22,%23,%24,%25,%26,%27,%28,%29,%30,%31,"
      "%32,%33,%34,%35,%36,%37,%38,%39,%40,%41,%42,%43,%44,%45,%46,%47}, "
      "{%48,%49,%50,%51}, %52, p, 1, 1, 0;\n}\n"
      : "+f"(d[OFF + 0]), "+f"(d[OFF + 1]), "+f"(d[OFF + 2]), "+f"(d[OFF + 3]), "+f"(d[OFF + 4]), "+f"(d[OFF + 5]),
        "+f"(d[OFF + 6]), "+f"(d[OFF + 7]), "+f"(d[OFF + 8]), "+f"(d[OFF + 9]), "+f"(d[OFF + 10]), "+f"(d[OFF + 11]),
        "+f"(d[OFF + 12]), "+f"(d[OFF + 13]), "+f"(d[OFF + 14]), "+f"(d[OFF + 15]), "+f"(d[OFF + 16]), "+f"(d[OFF + 17]),
        "+f"(d[OFF + 18]), "+f"(d[OFF + 19]), "+f"(d[OFF + 20]), "+f"(d[OFF + 21]), "+f"(d[OFF + 22]), "+f"(d[OFF + 23]),
        "+f"(d[OFF + 24]), "+f"(d[OFF + 25]), "+f"(d[OFF + 26]), "+f"(d[OFF + 27]), "+f"(d[OFF + 28]), "+f"(d[OFF + 29]),
        "+f"(d[OFF + 30]), "+f"(d[OFF + 31]), "+f"(d[OFF + 32]), "+f"(d[OFF + 33]), "+f"(d[OFF + 34]), "+f"(d[OFF + 35]),
        "+f"(d[OFF + 36]), "+f"(d[OFF + 37]), "+f"(d[OFF + 38]), "+f"(d[OFF + 39]), "+f"(d[OFF + 40]), "+f"(d[OFF + 41]),
        "+f"(d[OFF + 42]), "+f"(d[OFF + 43]), "+f"(d[OFF + 44]), "+f"(d[OFF + 45]), "+f"(d[OFF + 46]), "+f"(d[OFF + 47])
      : "r"(a0), "r"(a1), "r"(a2), "r"(a3), "l"(desc_b), "r"(scale_d));
}

template <int OFF, int NN>
__device__ __forceinline__ void wg_d96z(float (&d)[NN], uint32_t a0, uint32_t a1, uint32_t a2, uint32_t a3,
                                       uint64_t desc_b, int scale_d) {
  asm volatile(
      "{\n.reg .pred p;\nsetp.ne.b32 p, %53, 0;\n"
      "wgmma.mma_async.sync.aligned.m64n96k16.f32.bf16.bf16 "
      "{%0,%1,%2,%3,%4,%5,%6,%7,%8,%9,%10,%11,%12,%13,%14,%15,"
      "%16,%17,%18,%19,%20,%21,%22,%23,%24,%25,%26,%27,%28,%29,%30,%31,"
      "%32,%33,%34,%35,%36,%37,%38,%39,%40,%41,%42,%43,%44,%45,%46,%47}, "
      "{%48,%49,%50,%51}, %52, p, 1, 1, 0;\n}\n"
      : "=f"(d[OFF + 0]), "=f"(d[OFF + 1]), "=f"(d[OFF + 2]), "=f"(d[OFF + 3]), "=f"(d[OFF + 4]), "=f"(d[OFF + 5]),
        "=f"(d[OFF + 6]), "=f"(d[OFF + 7]), "=f"(d[OFF + 8]), "=f"(d[OFF + 9]), "=f"(d[OFF + 10]), "=f"(d[OFF + 11]),
        "=f"(d[OFF + 12]), "=f"(d[OFF + 13]), "=f"(d[OFF + 14]), "=f"(d[OFF + 15]), "=f"(d[OFF + 16]), "=f"(d[OFF + 17]),
        "=f"(d[OFF + 18]), "=f"(d[OFF + 19]), "=f"(d[OFF + 20]), "=f"(d[OFF + 21]), "=f"(d[OFF + 22]), "=f"(d[OFF + 23]),
        "=f"(d[OFF + 24]), "=f"(d[OFF + 25]), "=f"(d[OFF + 26]), "=f"(d[OFF + 27]), "=f"(d[OFF + 28]), "=f"(d[OFF + 29]),
        "=f"(d[OFF + 30]), "=f"(d[OFF + 31]), "=f"(d[OFF + 32]), "=f"(d[OFF + 33]), "=f"(d[OFF + 34]), "=f"(d[OFF + 35]),
        "=f"(d[OFF + 36]), "=f"(d[OFF + 37]), "=f"(d[OFF + 38]), "=f"(d[OFF + 39]), "=f"(d[OFF + 40]), "=f"(d[OFF + 41]),
        "=f"(d[OFF + 42]), "=f"(d[OFF + 43]), "=f"(d[OFF + 44]), "=f"(d[OFF + 45]), "=f"(d[OFF + 46]), "=f"(d[OFF + 47])
      : "r"(a0), "r"(a1), "r"(a2), "r"(a3), "l"(desc_b), "r"(scale_d));
}

template <int OFF, int NN>
__device__ __forceinline__ void wg_s104(float (&d)[NN], uint32_t a0, uint32_t a1, uint32_t a2, uint32_t a3,
                                       uint64_t desc_b, int scale_d, uint32_t meta) {
  asm volatile(
      "{\n.reg .pred p;\nsetp.ne.b32 p, %57, 0;\n"
      "wgmma.mma_async.sp.sync.aligned.m64n104k32.f32.bf16.bf16 "
      "{%0,%1,%2,%3,%4,%5,%6,%7,%8,%9,%10,%11,%12,%13,%14,%15,"
      "%16,%17,%18,%19,%20,%21,%22,%23,%24,%25,%26,%27,%28,%29,%30,%31,"
      "%32,%33,%34,%35,%36,%37,%38,%39,%40,%41,%42,%43,%44,%45,%46,%47,"
      "%48,%49,%50,%51}, "
      "{%52,%53,%54,%55}, %56, %58, 0, p, 1, 1, 0;\n}\n"
      : "+f"(d[OFF + 0]), "+f"(d[OFF + 1]), "+f"(d[OFF + 2]), "+f"(d[OFF + 3]), "+f"(d[OFF + 4]), "+f"(d[OFF + 5]),
        "+f"(d[OFF + 6]), "+f"(d[OFF + 7]), "+f"(d[OFF + 8]), "+f"(d[OFF + 9]), "+f"(d[OFF + 10]), "+f"(d[OFF + 11]),
        "+f"(d[OFF + 12]), "+f"(d[OFF + 13]), "+f"(d[OFF + 14]), "+f"(d[OFF + 15]), "+f"(d[OFF + 16]), "+f"(d[OFF + 17]),
        "+f"(d[OFF + 18]), "+f"(d[OFF + 19]), "+f"(d[OFF + 20]), "+f"(d[OFF + 21]), "+f"(d[OFF + 22]), "+f"(d[OFF + 23]),
        "+f"(d[OFF + 24]), "+f"(d[OFF + 25]), "+f"(d[OFF + 26]), "+f"(d[OFF + 27]), "+f"(d[OFF + 28]), "+f"(d[OFF + 29]),
        "+f"(d[OFF + 30]), "+f"(d[OFF + 31]), "+f"(d[OFF + 32]), "+f"(d[OFF + 33]), "+f"(d[OFF + 34]), "+f"(d[OFF + 35]),
        "+f"(d[OFF + 36]), "+f"(d[OFF + 37]), "+f"(d[OFF + 38]), "+f"(d[OFF + 39]), "+f"(d[OFF + 40]), "+f"(d[OFF + 41]),
        "+f"(d[OFF + 42]), "+f"(d[OFF + 43]), "+f"(d[OFF + 44]), "+f"(d[OFF + 45]), "+f"(d[OFF + 46]), "+f"(d[OFF + 47]),
        "+f"(d[OFF + 48]), "+f"(d[OFF + 49]), "+f"(d[OFF + 50]), "+f"(d[OFF + 51])
      : "r"(a0), "r"(a1), "r"(a2), "r"(a3), "l"(desc_b), "r"(scale_d), "r"(meta));
}

template <int OFF, int NN>
__device__ __forceinline__ void wg_s104z(float (&d)[NN], uint32_t a0, uint32_t a1, uint32_t a2, uint32_t a3,
                                       uint64_t desc_b, int scale_d, uint32_t meta) {
  asm volatile(
      "{\n.reg .pred p;\nsetp.ne.b32 p, %57, 0;\n"
      "wgmma.mma_async.sp.sync.aligned.m64n104k32.f32.bf16.bf16 "
      "{%0,%1,%2,%3,%4,%5,%6,%7,%8,%9,%10,%11,%12,%13,%14,%15,"
      "%16,%17,%18,%19,%20,%21,%22,%23,%24,%25,%26,%27,%28,%29,%30,%31,"
      "%32,%33,%34,%35,%36,%37,%38,%39,%40,%41,%42,%43,%44,%45,%46,%47,"
      "%48,%49,%50,%51}, "
      "{%52,%53,%54,%55}, %56, %58, 0, p, 1, 1, 0;\n}\n"
      : "=f"(d[OFF + 0]), "=f"(d[OFF + 1]), "=f"(d[OFF + 2]), "=f"(d[OFF + 3]), "=f"(d[OFF + 4]), "=f"(d[OFF + 5]),
        "=f"(d[OFF + 6]), "=f"(d[OFF + 7]), "=f"(d[OFF + 8]), "=f"(d[OFF + 9]), "=f"(d[OFF + 10]), "=f"(d[OFF + 11]),
        "=f"(d[OFF + 12]), "=f"(d[OFF + 13]), "=f"(d[OFF + 14]), "=f"(d[OFF + 15]), "=f"(d[OFF + 16]), "=f"(d[OFF + 17]),
        "=f"(d[OFF + 18]), "=f"(d[OFF + 19]), "=f"(d[OFF + 20]), "=f"(d[OFF + 21]), "=f"(d[OFF + 22]), "=f"(d[OFF + 23]),
        "=f"(d[OFF + 24]), "=f"(d[OFF + 25]), "=f"(d[OFF + 26]), "=f"(d[OFF + 27]), "=f"(d[OFF + 28]), "=f"(d[OFF + 29]),
        "=f"(d[OFF + 30]), "=f"(d[OFF + 31]), "=f"(d[OFF + 32]), "=f"(d[OFF + 33]), "=f"(d[OFF + 34]), "=f"(d[OFF + 35]),
        "=f"(d[OFF + 36]), "=f"(d[OFF + 37]), "=f"(d[OFF + 38]), "=f"(d[OFF + 39]), "=f"(d[OFF + 40]), "=f"(d[OFF + 41]),
        "=f"(d[OFF + 42]), "=f"(d[OFF + 43]), "=f"(d[OFF + 44]), "=f"(d[OFF + 45]), "=f"(d[OFF + 46]), "=f"(d[OFF + 47]),
        "=f"(d[OFF + 48]), "=f"(d[OFF + 49]), "=f"(d[OFF + 50]), "=f"(d[OFF + 51])
      : "r"(a0), "r"(a1), "r"(a2), "r"(a3), "l"(desc_b), "r"(scale_d), "r"(meta));
}

template <int OFF, int NN>
__device__ __forceinline__ void wg_s48(float (&d)[NN], uint32_t a0, uint32_t a1, uint32_t a2, uint32_t a3,
                                       uint64_t desc_b, int scale_d, uint32_t meta) {
  asm volatile(
      "{\n.reg .pred p;\nsetp.ne.b32 p, %29, 0;\n"
      "wgmma.mma_async.sp.sync.aligned.m64n48k32.f32.bf16.bf16 "
      "{%0,%1,%2,%3,%4,%5,%6,%7,%8,%9,%10,%11,%12,%13,%14,%15,"
      "%16,%17,%18,%19,%20,%21,%22,%23}, "
      "{%24,%25,%26,%27}, %28, %30, 0, p, 1, 1, 0;\n}\n"
      : "+f"(d[OFF + 0]), "+f"(d[OFF + 1]), "+f"(d[OFF + 2]), "+f"(d[OFF + 3]), "+f"(d[OFF + 4]), "+f"(d[OFF + 5]),
        "+f"(d[OFF + 6]), "+f"(d[OFF + 7]), "+f"(d[OFF + 8]), "+f"(d[OFF + 9]), "+f"(d[OFF + 10]), "+f"(d[OFF + 11]),
        "+f"(d[OFF + 12]), "+f"(d[OFF + 13]), "+f"(d[OFF + 14]), "+f"(d[OFF + 15]), "+f"(d[OFF + 16]), "+f"(d[OFF + 17]),
        "+f"(d[OFF + 18]), "+f"(d[OFF + 19]), "+f"(d[OFF + 20]), "+f"(d[OFF + 21]), "+f"(d[OFF + 22]), "+f"(d[OFF + 23])
      : "r"(a0), "r"(a1), "r"(a2), "r"(a3), "l"(desc_b), "r"(scale_d), "r"(meta));
}

template <int OFF, int NN>
__device__ __forceinline__ void wg_s48z(float (&d)[NN], uint32_t a0, uint32_t a1, uint32_t a2, uint32_t a3,
                                       uint64_t desc_b, int scale_d, uint32_t meta) {
  asm volatile(
      "{\n.reg .pred p;\nsetp.ne.b32 p, %29, 0;\n"
      "wgmma.mma_async.sp.sync.aligned.m64n48k32.f32.bf16.bf16 "
      "{%0,%1,%2,%3,%4,%5,%6,%7,%8,%9,%10,%11,%12,%13,%14,%15,"
      "%16,%17,%18,%19,%20,%21,%22,%23}, "
      "{%24,%25,%26,%27}, %28, %30, 0, p, 1, 1, 0;\n}\n"
      : "=f"(d[OFF + 0]), "=f"(d[OFF + 1]), "=f"(d[OFF + 2]), "=f"(d[OFF + 3]), "=f"(d[OFF + 4]), "=f"(d[OFF + 5]),
        "=f"(d[OFF + 6]), "=f"(d[OFF + 7]), "=f"(d[OFF + 8]), "=f"(d[OFF + 9]), "=f"(d[OFF + 10]), "=f"(d[OFF + 11]),
        "=f"(d[OFF + 12]), "=f"(d[OFF + 13]), "=f"(d[OFF + 14]), "=f"(d[OFF + 15]), "=f"(d[OFF + 16]), "=f"(d[OFF + 17]),
        "=f"(d[OFF + 18]), "=f"(d[OFF + 19]), "=f"(d[OFF + 20]), "=f"(d[OFF + 21]), "=f"(d[OFF + 22]), "=f"(d[OFF + 23])
      : "r"(a0), "r"(a1), "r"(a2), "r"(a3), "l"(desc_b), "r"(scale_d), "r"(meta));
}

template <int OFF, int NN>
__device__ __forceinline__ void wg_s56(float (&d)[NN], uint32_t a0, uint32_t a1, uint32_t a2, uint32_t a3,
                                       uint64_t desc_b, int scale_d, uint32_t meta) {
  asm volatile(
      "{\n.reg .pred p;\nsetp.ne.b32 p, %33, 0;\n"
      "wgmma.mma_async.sp.sync.aligned.m64n56k32.f32.bf16.bf16 "
      "{%0,%1,%2,%3,%4,%5,%6,%7,%8,%9,%10,%11,%12,%13,%14,%15,"
      "%16,%17,%18,%19,%20,%21,%22,%23,%24,%25,%26,%27}, "
      "{%28,%29,%30,%31}, %32, %34, 0, p, 1, 1, 0;\n}\n"
      : "+f"(d[OFF + 0]), "+f"(d[OFF + 1]), "+f"(d[OFF + 2]), "+f"(d[OFF + 3]), "+f"(d[OFF + 4]), "+f"(d[OFF + 5]),
        "+f"(d[OFF + 6]), "+f"(d[OFF + 7]), "+f"(d[OFF + 8]), "+f"(d[OFF + 9]), "+f"(d[OFF + 10]), "+f"(d[OFF + 11]),
        "+f"(d[OFF + 12]), "+f"(d[OFF + 13]), "+f"(d[OFF + 14]), "+f"(d[OFF + 15]), "+f"(d[OFF + 16]), "+f"(d[OFF + 17]),
        "+f"(d[OFF + 18]), "+f"(d[OFF + 19]), "+f"(d[OFF + 20]), "+f"(d[OFF + 21]), "+f"(d[OFF + 22]), "+f"(d[OFF + 23]),
        "+f"(d[OFF + 24]), "+f"(d[OFF + 25]), "+f"(d[OFF + 26]), "+f"(d[OFF + 27])
      : "r"(a0), "r"(a1), "r"(a2), "r"(a3), "l"(desc_b), "r"(scale_d), "r"(meta));
}

template <int OFF, int NN>
__device__ __forceinline__ void wg_s56z(float (&d)[NN], uint32_t a0, uint32_t a1, uint32_t a2, uint32_t a3,
                                       uint64_t desc_b, int scale_d, uint32_t meta) {
  asm volatile(
      "{\n.reg .pred p;\nsetp.ne.b32 p, %33, 0;\n"
      "wgmma.mma_async.sp.sync.aligned.m64n56k32.f32.bf16.bf16 "
      "{%0,%1,%2,%3,%4,%5,%6,%7,%8,%9,%10,%11,%12,%13,%14,%15,"
      "%16,%17,%18,%19,%20,%21,%22,%23,%24,%25,%26,%27}, "
      "{%28,%29,%30,%31}, %32, %34, 0, p, 1, 1, 0;\n}\n"
      : "=f"(d[OFF + 0]), "=f"(d[OFF + 1]), "=f"(d[OFF + 2]), "=f"(d[OFF + 3]), "=f"(d[OFF + 4]), "=f"(d[OFF + 5]),
        "=f"(d[OFF + 6]), "=f"(d[OFF + 7]), "=f"(d[OFF + 8]), "=f"(d[OFF + 9]), "=f"(d[OFF + 10]), "=f"(d[OFF + 11]),
        "=f"(d[OFF + 12]), "=f"(d[OFF + 13]), "=f"(d[OFF + 14]), "=f"(d[OFF + 15]), "=f"(d[OFF + 16]), "=f"(d[OFF + 17]),
        "=f"(d[OFF + 18]), "=f"(d[OFF + 19]), "=f"(d[OFF + 20]), "=f"(d[OFF + 21]), "=f"(d[OFF + 22]), "=f"(d[OFF + 23]),
        "=f"(d[OFF + 24]), "=f"(d[OFF + 25]), "=f"(d[OFF + 26]), "=f"(d[OFF + 27])
      : "r"(a0), "r"(a1), "r"(a2), "r"(a3), "l"(desc_b), "r"(scale_d), "r"(meta));
}

template <int OFF, int NN>
__device__ __forceinline__ void wg_s64t(float (&d)[NN], uint32_t a0, uint32_t a1, uint32_t a2, uint32_t a3,
                                       uint64_t desc_b, int scale_d, uint32_t meta) {
  asm volatile(
      "{\n.reg .pred p;\nsetp.ne.b32 p, %37, 0;\n"
      "wgmma.mma_async.sp.sync.aligned.m64n64k32.f32.bf16.bf16 "
      "{%0,%1,%2,%3,%4,%5,%6,%7,%8,%9,%10,%11,%12,%13,%14,%15,"
      "%16,%17,%18,%19,%20,%21,%22,%23,%24,%25,%26,%27,%28,%29,%30,%31}, "
      "{%32,%33,%34,%35}, %36, %38, 0, p, 1, 1, 1;\n}\n"
      : "+f"(d[OFF + 0]), "+f"(d[OFF + 1]), "+f"(d[OFF + 2]), "+f"(d[OFF + 3]), "+f"(d[OFF + 4]), "+f"(d[OFF + 5]),
        "+f"(d[OFF + 6]), "+f"(d[OFF + 7]), "+f"(d[OFF + 8]), "+f"(d[OFF + 9]), "+f"(d[OFF + 10]), "+f"(d[OFF + 11]),
        "+f"(d[OFF + 12]), "+f"(d[OFF + 13]), "+f"(d[OFF + 14]), "+f"(d[OFF + 15]), "+f"(d[OFF + 16]), "+f"(d[OFF + 17]),
        "+f"(d[OFF + 18]), "+f"(d[OFF + 19]), "+f"(d[OFF + 20]), "+f"(d[OFF + 21]), "+f"(d[OFF + 22]), "+f"(d[OFF + 23]),
        "+f"(d[OFF + 24]), "+f"(d[OFF + 25]), "+f"(d[OFF + 26]), "+f"(d[OFF + 27]), "+f"(d[OFF + 28]), "+f"(d[OFF + 29]),
        "+f"(d[OFF + 30]), "+f"(d[OFF + 31])
      : "r"(a0), "r"(a1), "r"(a2), "r"(a3), "l"(desc_b), "r"(scale_d), "r"(meta));
}

template <int OFF, int NN>
__device__ __forceinline__ void wg_s64t1(float (&d)[NN], uint32_t a0, uint32_t a1, uint32_t a2, uint32_t a3,
                                       uint64_t desc_b, int scale_d, uint32_t meta) {
  asm volatile(
      "{\n.reg .pred p;\nsetp.ne.b32 p, %37, 0;\n"
      "wgmma.mma_async.sp.sync.aligned.m64n64k32.f32.bf16.bf16 "
      "{%0,%1,%2,%3,%4,%5,%6,%7,%8,%9,%10,%11,%12,%13,%14,%15,"
      "%16,%17,%18,%19,%20,%21,%22,%23,%24,%25,%26,%27,%28,%29,%30,%31}, "
      "{%32,%33,%34,%35}, %36, %38, 1, p, 1, 1, 1;\n}\n"
      : "+f"(d[OFF + 0]), "+f"(d[OFF + 1]), "+f"(d[OFF + 2]), "+f"(d[OFF + 3]), "+f"(d[OFF + 4]), "+f"(d[OFF + 5]),
        "+f"(d[OFF + 6]), "+f"(d[OFF + 7]), "+f"(d[OFF + 8]), "+f"(d[OFF + 9]), "+f"(d[OFF + 10]), "+f"(d[OFF + 11]),
        "+f"(d[OFF + 12]), "+f"(d[OFF + 13]), "+f"(d[OFF + 14]), "+f"(d[OFF + 15]), "+f"(d[OFF + 16]), "+f"(d[OFF + 17]),
        "+f"(d[OFF + 18]), "+f"(d[OFF + 19]), "+f"(d[OFF + 20]), "+f"(d[OFF + 21]), "+f"(d[OFF + 22]), "+f"(d[OFF + 23]),
        "+f"(d[OFF + 24]), "+f"(d[OFF + 25]), "+f"(d[OFF + 26]), "+f"(d[OFF + 27]), "+f"(d[OFF + 28]), "+f"(d[OFF + 29]),
        "+f"(d[OFF + 30]), "+f"(d[OFF + 31])
      : "r"(a0), "r"(a1), "r"(a2), "r"(a3), "l"(desc_b), "r"(scale_d), "r"(meta));
}

template <int OFF, int NN>
__device__ __forceinline__ void wg_s64tz(float (&d)[NN], uint32_t a0, uint32_t a1, uint32_t a2, uint32_t a3,
                                       uint64_t desc_b, int scale_d, uint32_t meta) {
  asm volatile(
      "{\n.reg .pred p;\nsetp.ne.b32 p, %37, 0;\n"
      "wgmma.mma_async.sp.sync.aligned.m64n64k32.f32.bf16.bf16 "
      "{%0,%1,%2,%3,%4,%5,%6,%7,%8,%9,%10,%11,%12,%13,%14,%15,"
      "%16,%17,%18,%19,%20,%21,%22,%23,%24,%25,%26,%27,%28,%29,%30,%31}, "
      "{%32,%33,%34,%35}, %36, %38, 0, p, 1, 1, 1;\n}\n"
      : "=f"(d[OFF + 0]), "=f"(d[OFF + 1]), "=f"(d[OFF + 2]), "=f"(d[OFF + 3]), "=f"(d[OFF + 4]), "=f"(d[OFF + 5]),
        "=f"(d[OFF + 6]), "=f"(d[OFF + 7]), "=f"(d[OFF + 8]), "=f"(d[OFF + 9]), "=f"(d[OFF + 10]), "=f"(d[OFF + 11]),
        "=f"(d[OFF + 12]), "=f"(d[OFF + 13]), "=f"(d[OFF + 14]), "=f"(d[OFF + 15]), "=f"(d[OFF + 16]), "=f"(d[OFF + 17]),
        "=f"(d[OFF + 18]), "=f"(d[OFF + 19]), "=f"(d[OFF + 20]), "=f"(d[OFF + 21]), "=f"(d[OFF + 22]), "=f"(d[OFF + 23]),
        "=f"(d[OFF + 24]), "=f"(d[OFF + 25]), "=f"(d[OFF + 26]), "=f"(d[OFF + 27]), "=f"(d[OFF + 28]), "=f"(d[OFF + 29]),
        "=f"(d[OFF + 30]), "=f"(d[OFF + 31])
      : "r"(a0), "r"(a1), "r"(a2), "r"(a3), "l"(desc_b), "r"(scale_d), "r"(meta));
}

__device__ __forceinline__ int g2_inv(int ch) { return 32 * (ch >> 5) + 8 * ((ch >> 1) & 3) + 2 * ((ch >> 3) & 3) + (ch & 1); }
__host__ __device__ __forceinline__ uint32_t wimg_off(int n, int k) {
  return (uint32_t)(k >> 6) * kWChunk + (uint32_t)n * 128 + (uint32_t)((((k & 63) >> 3) ^ (n & 7)) << 4) + (k & 7) * 2;
}
__host__ __device__ constexpr int w2piece(int h, int c) { return c == 2 ? 2 + h : 4 * h + c; }
__device__ __forceinline__ uint32_t w2img_off(int n, int k) { return wimg_off(n % 96, k & 63) + w2piece(n >= 96, k >> 6) * (kWChunk / 2); }
__device__ __forceinline__ int qpix(int par, int t) {
  const int a = 2 * t + 13 * par - 6, b = t + 112 * par;
  return par ? min(a, b) : max(a, b);
}
__device__ __forceinline__ int woff(int par, int i, int r) {
  const int a = 99 * par + 6 - 8 * i;
  return par ? min(r, a) : max(r, a);
}

__device__ __forceinline__ void mma16816(float (&c)[4], uint32_t a0, uint32_t a1, uint32_t a2, uint32_t a3, uint32_t b0,
                                         uint32_t b1) {
  asm volatile(
      "mma.sync.aligned.m16n8k16.row.col.f32.bf16.bf16.f32 {%0,%1,%2,%3}, {%4,%5,%6,%7}, {%8,%9}, {%0,%1,%2,%3};"
      : "+f"(c[0]), "+f"(c[1]), "+f"(c[2]), "+f"(c[3])
      : "r"(a0), "r"(a1), "r"(a2), "r"(a3), "r"(b0), "r"(b1));
}

__device__ __forceinline__ void fold_w1(const int u, const __nv_bfloat16* __restrict__ wqkv, uint8_t* wimg) {
  const int g = (threadIdx.x >> 2) & 7, l = threadIdx.x & 3;
  const int m0 = (u / 12) * 16, s = u % 12;
  uint4 A[12], B[12];
  const __nv_bfloat16* arow = wqkv + (m0 + 4 * (g >> 1) + (g & 1)) * 576 + 192 + 8 * l;
  const __nv_bfloat16* brow = wqkv + (16 * s + 4 * (g >> 1) + (g & 1)) * 576 + 8 * l;
#pragma unroll
  for (int i = 0; i < 12; i++) {
    A[i] = ldg128_nc(arow + (i & 1) * 2 * 576 + 32 * (i >> 1));
    B[i] = ldg128_nc(brow + (i & 1) * 2 * 576 + 32 * (i >> 1));
  }
  sched_fence();
  uint8_t* dst = wimg + wimg_off(m0 + g, 16 * s + 4 * l);
  float acc[4][4];
#pragma unroll
  for (int j = 0; j < 16; j++) acc[j >> 2][j & 3] = 0.f;
#pragma unroll
  for (int i = 0; i < 6; i++) {
    const uint4 &a0 = A[2 * i], &a1 = A[2 * i + 1];
#pragma unroll
    for (int nb = 0; nb < 2; nb++) {
      mma16816(acc[2 * nb], a0.x, a1.x, a0.y, a1.y, B[2 * i + nb].x, B[2 * i + nb].y);
      mma16816(acc[2 * nb + 1], a0.z, a1.z, a0.w, a1.w, B[2 * i + nb].z, B[2 * i + nb].w);
    }
  }
#pragma unroll
  for (int j = 0; j < 2; j++) {
    const uint2 v = make_uint2(pack_bf16((acc[0][2 * j] + acc[1][2 * j]) * kAlpha, (acc[0][2 * j + 1] + acc[1][2 * j + 1]) * kAlpha),
                               pack_bf16((acc[2][2 * j] + acc[3][2 * j]) * kAlpha, (acc[2][2 * j + 1] + acc[3][2 * j + 1]) * kAlpha));
    asm volatile("st.relaxed.gpu.global.v2.u32 [%0], {%1,%2};" ::"l"(dst + j * 1024), "r"(v.x), "r"(v.y) : "memory");
  }
}
__device__ __forceinline__ void fold_w2(const int u, const __nv_bfloat16* __restrict__ wqkv, const __nv_bfloat16* __restrict__ wo,
                                        uint8_t* wimg) {
  const int g = (threadIdx.x >> 2) & 7, l = threadIdx.x & 3;
  const int m0 = (u / 12) * 32, n0 = (u % 12) * 16;
  uint4 S[12];
  uint32_t L[96];
  const __nv_bfloat16* brow = wqkv + (n0 + 4 * (g >> 1) + (g & 1)) * 576 + 384 + 8 * l;
#pragma unroll
  for (int i = 0; i < 12; i++) S[i] = ldg128_nc(brow + (i & 1) * 2 * 576 + 32 * (i >> 1));
  const __nv_bfloat16* acol = wo + (8 * l) * 192 + m0 + 4 * g;
#pragma unroll
  for (int c = 0; c < 48; c++)
    asm volatile("ld.global.nc.v2.u32 {%0,%1}, [%2];" : "=r"(L[2 * c]), "=r"(L[2 * c + 1]) : "l"(acol + (32 * (c >> 3) + (c & 7)) * 192));
  const uint32_t off = w2_offset();
  sched_fence();
  uint8_t* img = wimg + off;
  float acc[4][4];
#pragma unroll
  for (int j = 0; j < 16; j++) acc[j >> 2][j & 3] = 0.f;
#pragma unroll
  for (int i = 0; i < 6; i++) {
#pragma unroll
    for (int h = 0; h < 2; h++) {
      const uint4 &s0 = S[2 * i], &s1 = S[2 * i + 1];
#pragma unroll
      for (int mt = 0; mt < 2; mt++) {
        const uint32_t* a = L + 16 * i + 8 * h + mt;
        const uint32_t a0 = __byte_perm(a[0], a[2], 0x5410), a1 = __byte_perm(a[0], a[2], 0x7632);
        const uint32_t a2 = __byte_perm(a[4], a[6], 0x5410), a3 = __byte_perm(a[4], a[6], 0x7632);
        mma16816(acc[2 * mt], a0, a1, a2, a3, h ? s0.z : s0.x, h ? s0.w : s0.y);
        mma16816(acc[2 * mt + 1], a0, a1, a2, a3, h ? s1.z : s1.x, h ? s1.w : s1.y);
      }
    }
  }
#pragma unroll
  for (int j = 0; j < 4; j++) {
    const float(&c0)[4] = acc[j & 2];
    const float(&c1)[4] = acc[(j & 2) + 1];
    asm volatile("st.relaxed.gpu.global.v2.u32 [%0], {%1,%2};" ::"l"(img + w2img_off(g2_inv(m0 + 4 * g + j), n0 + 4 * l)),
                 "r"(pack_bf16(c0[2 * (j & 1)], c0[2 * (j & 1) + 1])), "r"(pack_bf16(c1[2 * (j & 1)], c1[2 * (j & 1) + 1])) : "memory");
  }
}

__global__ void __launch_bounds__(256) fold_kernel(const __nv_bfloat16* __restrict__ wqkv,
                                                   const __nv_bfloat16* __restrict__ wo, uint8_t* wimg) {
  const int u = blockIdx.x * 8 + (threadIdx.x >> 5);
  if (u < 144) fold_w1(u, wqkv, wimg);
  else fold_w2(u - 144, wqkv, wo, wimg);
}

struct TileCoord { int pr, pc, I, J, up, kind; };
struct TileTable { uint16_t e[kCtas * 6], g[5][8][2], b[5][2][4]; };
inline void make_tiles(TileTable& tt) {
  for (int tile = 0; tile < kCtas * 6; tile++) {
    const int b = tile / 6, k = tile - 6 * b;
    const int p = b < 128 ? (tile - 672) >> 1 : b - 80;
    const int strip = b < 112 ? b >> 1 : b >= 128 && k >= 2 ? (b & 1) * 27 + (b & 2) * 14 : p + (p < 26 ? 1 : 3);
    const int pr = strip >= 28, J = (strip - pr * 28) >> 1, pc = strip & 1, up = b < 112 ? b & 1 : pr;
    const int first = b < 112 ? 8 - 2 * pr - up : 13 * pr, step = b < 112 ? k : k & 1;
    const int I = up ? first - step : first + step;
    const int kind = I == 13 * pr ? 3 + pr : J == 13 * pc ? 1 + pc : 0;
    tt.e[tile] = (uint16_t)(I | J << 4 | pr << 8 | pc << 9 | up << 10 | kind << 11);
  }
  for (int kind = 0; kind < 5; kind++) {
    const bool col = kind == 1 || kind == 2;
    auto off = [kind](int t) { return kind == 0 ? 2 * t : kind & 1 ? t + (t == 7) : t + (t > 0); };
    for (int j = 0; j < 8; j++) {
      const int w = j >> 1, h = j & 1;
      tt.g[kind][j][0] = (uint16_t)(col ? 3 * off(w + 4 * h) : 3 * (kW * off(2 * w) + 8 * h));
      tt.g[kind][j][1] = (uint16_t)(128 * (col ? 5 : 5 + off(2 * w + 1) - off(2 * w)));
    }
    for (int i = 0; i < 2; i++) {
      const int w = kind == 0 ? 0 : kind & 1 ? 3 * i : 1 - i;
      tt.b[kind][i][0] = tt.g[kind][2 * w][0];
      tt.b[kind][i][1] = (uint16_t)(128 * (kind == 0 ? 0 : (col ? 3 : 1) + i));
      tt.b[kind][i][2] = (uint16_t)(2048 * w);
      tt.b[kind][i][3] = 0;
    }
  }
}
__device__ __forceinline__ int num_tiles() { return blockIdx.x < 128 ? 6 : 4; }
__device__ __forceinline__ TileCoord decode_tile(const TileTable& tt, int tile) {
  const uint32_t e = tt.e[tile];
  return TileCoord{(int)(e >> 8) & 1, (int)(e >> 9) & 1, (int)e & 15, (int)(e >> 4) & 15, (int)(e >> 10) & 1, (int)(e >> 11)};
}
__device__ __forceinline__ int halo_r0(const TileCoord& t) { return 8 * t.I + 6 * t.pr - 6; }
__device__ __forceinline__ int halo_c0(const TileCoord& t) { return min(max(8 * t.J + 6 * t.pc - 6, -3), 102); }

__device__ __forceinline__ uint32_t bar_full(uint32_t bars, int wg, int c) { return bars + (wg * 3 + c) * 8; }
__device__ __forceinline__ uint32_t bar_w1c(uint32_t bars, int c) { return bars + (6 + c) * 8; }
__device__ __forceinline__ uint32_t bar_w2(uint32_t bars) { return bars + 9 * 8; }
__device__ __forceinline__ uint32_t bar_x(uint32_t bars, int j, int c) { return bars + (j == 0 ? 10 : c ? 17 + c : 11) * 8; }
__device__ __forceinline__ uint32_t bar_w1q(uint32_t bars) { return bars + 12 * 8; }
__device__ __forceinline__ uint32_t bar_xf(uint32_t bars) { return bars + 13 * 8; }
__device__ __forceinline__ uint32_t bar_w2m(uint32_t bars) { return bars + 14 * 8; }
__device__ __forceinline__ uint32_t bar_redo(uint32_t bars) { return bars + 15 * 8; }
__device__ __forceinline__ uint32_t bar_wok(uint32_t bars) { return bars + 16 * 8; }
__device__ __forceinline__ uint32_t bar_go(uint32_t bars) { return bars + 17 * 8; }
__device__ __forceinline__ uint32_t bar_raw(uint32_t bars, int j = 0) { return bars + (21 + j) * 8; }
__device__ __forceinline__ uint32_t bar_w2a(uint32_t bars) { return bars + 20 * 8; }
constexpr int kNumBars = 22;

__device__ __forceinline__ uint64_t wdesc(uint64_t d0, int s) { return d0 + (((s >> 2) * kWChunk + (s & 3) * 32) >> 4); }

__device__ __forceinline__ uint32_t x_chunk(int k, int c) { return kXOff + (k == 0 ? kWChunk : 0) + (k & 1 ? 2 - c : c) * 8192; }
__device__ __forceinline__ uint32_t out_slot(int k, int nt) { return k + 1 < nt ? kW2Off + (~k & 1) * 2 * kWChunk : kW1Off + kWChunk; }
template <int I0, int I1>
__device__ __forceinline__ void store_rows(bool on, __nv_bfloat16* pA, __nv_bfloat16* pB, const uint32_t (&a)[24], const uint32_t (&b)[24]) {
#pragma unroll
  for (int i = 2 * I0; i < 2 * I1; i++) {
    const uint32_t* v = (i & 1 ? b : a) + 4 * (i >> 1);
    asm volatile("{\n.reg .pred p;\nsetp.ne.u32 p, %5, 0;\n@p st.global.v4.u32 [%0], {%1,%2,%3,%4};\n}\n" ::"l"((i & 1 ? pB : pA) + 32 * (i >> 1)),
                 "r"(v[0]), "r"(v[1]), "r"(v[2]), "r"(v[3]), "r"((uint32_t)on) : "memory");
  }
}
template <int I0, int I1>
__device__ __forceinline__ void stage_out(const uint32_t (&ad)[4], const uint32_t (&a)[24], const uint32_t (&b)[24]) {
#pragma unroll
  for (int i = I0; i < I1; i++) {
    const uint32_t* v = (i < 6 ? a : b) + 4 * (i % 6);
    asm volatile("st.shared.v4.u32 [%0], {%1,%2,%3,%4};" ::"r"(ad[i % 6 / 3 * 2 + (i % 3 == 1)] + (i % 3 == 2) * 1024 + (i / 6) * 12288),
                 "r"(v[0]), "r"(v[1]), "r"(v[2]), "r"(v[3]) : "memory");
  }
}
__device__ __forceinline__ uint32_t now_ns() {
  uint32_t t;
  asm volatile("mov.u32 %0, %globaltimer_lo;" : "=r"(t)::"memory");
  return t;
}
__device__ __forceinline__ void wait_clock(uint32_t t_start, uint32_t t) {
  while (now_ns() - t_start < t) { }
}
#define NAT_PRED(f, m) ".reg .pred p;\n.reg .b32 t;\nand.b32 t, " f ", " m ";\nsetp.ne.u32 p, t, 0;\n"
constexpr uint32_t kHiV = 1, kHiU = 8, kColB = 0x20, kInV = 0x100, kInU = 0x1000, kColA = 0x10000;
template <uint32_t M>
__device__ __forceinline__ float pick(const float* a, const float* b, uint32_t f) {
  float d;
  asm("{\n" NAT_PRED("%5", "%6") "add.f32 %0, %1, %2;\n@p add.f32 %0, %3, %4;\n}\n"
      : "=&f"(d) : "f"(a[0]), "f"(a[2]), "f"(b[0]), "f"(b[2]), "r"(f), "n"(M));
  return d;
}
template <uint32_t M>
__device__ __forceinline__ float sel(float a, float b, uint32_t f) {
  float d;
  asm("{\n" NAT_PRED("%3", "%4") "selp.f32 %0, %1, %2, p;\n}\n" : "=f"(d) : "f"(a), "f"(b), "r"(f), "n"(M));
  return d;
}
template <uint32_t M>
__device__ __forceinline__ void max_if(float& m, float v, uint32_t f) {
  asm("{\n" NAT_PRED("%2", "%3") "@p max.f32 %0, %0, %1;\n}\n" : "+f"(m) : "f"(v), "r"(f), "n"(M));
}
template <uint32_t M>
__device__ __forceinline__ void add_if(float& m, float v, uint32_t f) {
  asm("{\n" NAT_PRED("%2", "%3") "@p add.f32 %0, %0, %1;\n}\n" : "+f"(m) : "f"(v), "r"(f), "n"(M));
}
__device__ __forceinline__ void pick_v(const float* a, float* v, uint32_t f) {
  v[0] = pick<kHiV>(a, a + 16, f), v[1] = pick<kHiV>(a + 1, a + 17, f);
  v[2] = pick<kHiV * 2>(a + 4, a + 20, f), v[3] = pick<kHiV * 2>(a + 5, a + 21, f);
  v[4] = pick<kHiV * 4>(a + 8, a + 24, f), v[5] = pick<kHiV * 4>(a + 9, a + 25, f);
  v[6] = a[12] + a[14], v[7] = a[13] + a[15];
}
__device__ __forceinline__ void pick_u(const float* a, float* v, uint32_t f) {
#pragma unroll
  for (int c = 0; c < 3; c++) v[2 * c] = pick<kHiU>(a + 4 * c, a + 4 * c + 12, f), v[2 * c + 1] = pick<kHiU * 2>(a + 4 * c + 1, a + 4 * c + 13, f);
}
__device__ __forceinline__ uint32_t sign_bytes(uint32_t v, uint32_t sel) {
  uint32_t d;
  asm("prmt.b32 %0, %1, %1, %2;" : "=r"(d) : "r"(v), "r"(sel));
  return d;
}
__device__ __forceinline__ float own_max(const float (&v)[14], uint32_t f) {
  float m = sel<kInV>(fmaxf(v[0], v[1]), -INFINITY, f), m2 = sel<kInV * 2>(fmaxf(v[2], v[3]), -INFINITY, f);
  max_if<kInV * 4>(m, fmaxf(v[4], v[5]), f);
  max_if<kInV * 8>(m2, fmaxf(v[6], v[7]), f);
  max_if<kInU>(m, fmaxf(fmaxf(v[8], v[10]), v[12]), f);
  max_if<kInU * 2>(m2, fmaxf(fmaxf(v[9], v[11]), v[13]), f);
  return fmaxf(m, m2);
}
__device__ __forceinline__ float quad_max(float m) {
  const float a = __shfl_xor_sync(0xffffffffu, m, 1), b = __shfl_xor_sync(0xffffffffu, m, 2), c = __shfl_xor_sync(0xffffffffu, m, 3);
  return fmaxf(fmaxf(m, a), fmaxf(b, c));
}
__device__ __forceinline__ float row_rcp(const float (&v)[14], uint32_t f) {
  float s = sel<kInV>(v[0] + v[1], 0.f, f), s2 = sel<kInV * 2>(v[2] + v[3], 0.f, f);
  add_if<kInV * 4>(s, v[4] + v[5], f);
  add_if<kInV * 8>(s2, v[6] + v[7], f);
  add_if<kInU>(s, v[8] + v[10] + v[12], f);
  add_if<kInU * 2>(s2, v[9] + v[11] + v[13], f);
  s += s2;
  const float a = __shfl_xor_sync(0xffffffffu, s, 1), b = __shfl_xor_sync(0xffffffffu, s, 2), c = __shfl_xor_sync(0xffffffffu, s, 3);
  return rcp_approx((s + a) + (b + c));
}
__device__ __forceinline__ void route(const float (&v)[14], float s, const uint32_t (&rt)[9], uint32_t (&p)[14]) {
#pragma unroll
  for (int i = 0; i < 7; i++) {
    const uint32_t u = pack_bf16(v[2 * i] * s, v[2 * i + 1] * s);
    if (i < 4) p[i] = u & rt[i];
    if (i < 3) p[i + 4] = u & rt[i + 4];
    if (i >= 4) {
      p[i + 3] = u & rt[7];
      p[i + 6] = u & rt[8];
    }
  }
}

template <int C, int T0 = 0, int T1 = 7>
__device__ __forceinline__ void pv_chunk(float (&z)[32], const uint32_t (&pa)[14], const uint32_t (&pb)[14],
                                         const uint32_t (&meta)[4], uint64_t dV) {
#pragma unroll
  for (int t = T0; t < T1; t++) {
    if (t & 1)
      wg_s64t1<0, 32>(z, pa[2 * t], pb[2 * t], pa[2 * t + 1], pb[2 * t + 1], dV + ((2 * C * kChunkBytes + t * 2048) >> 4), 1,
                      meta[t >> 1]);
    else if (t > 0)
      wg_s64t<0, 32>(z, pa[2 * t], pb[2 * t], pa[2 * t + 1], pb[2 * t + 1], dV + ((2 * C * kChunkBytes + t * 2048) >> 4), 1,
                     meta[t >> 1]);
    else
      wg_s64tz<0, 32>(z, pa[0], pb[0], pa[1], pb[1], dV + ((2 * C * kChunkBytes) >> 4), 0, meta[0]);
  }
}
template <int C>
__device__ __forceinline__ void pack_z(const float (&z)[32], uint32_t (&za)[24], uint32_t (&zb)[24]) {
#pragma unroll
  for (int j = 0; j < 8; j++) {
    za[8 * C + j] = pack_bf16(z[4 * j], z[4 * j + 1]);
    zb[8 * C + j] = pack_bf16(z[4 * j + 2], z[4 * j + 3]);
  }
}

template <int H>
__device__ __forceinline__ void pack_out(const float (&ac)[48], uint32_t (&oa)[24], uint32_t (&ob)[24]) {
#pragma unroll
  for (int j = 0; j < 12; j++) {
    oa[12 * H + j] = pack_bf16(ac[4 * j], ac[4 * j + 1]);
    ob[12 * H + j] = pack_bf16(ac[4 * j + 2], ac[4 * j + 3]);
  }
}
struct Maps { CUtensorMap v6, v2, v14, u8, px[8], wv, wo; };
__device__ __forceinline__ void tma_prefetch_5d(const CUtensorMap* map, int c0, int c1, int c2, int c3, int c4) {
  asm volatile("cp.async.bulk.prefetch.tensor.5d.L2.global.tile [%0, {%1, %2, %3, %4, %5}];" ::"l"((uint64_t)map), "r"(c0), "r"(c1),
               "r"(c2), "r"(c3), "r"(c4) : "memory");
}
__device__ __forceinline__ int first_line(const TileCoord tc) { return 3 * (qpix(tc.pr, 8 * tc.I) * kW + qpix(tc.pc, 8 * tc.J)); }
__device__ __forceinline__ void load_px(const Maps& tm, const TileTable& tt, uint32_t dst, uint32_t bar, int line, int kind) {
#pragma unroll
  for (int i = 0; i < 2; i++) {
    if (i == 0 || kind != 0) {
      const CUtensorMap* map = (const CUtensorMap*)((const char*)tm.px + tt.b[kind][i][1]);
      if (bar) tma_load_5d(dst + tt.b[kind][i][2], map, bar, 0, 0, 0, 0, line + tt.b[kind][i][0]);
      else tma_prefetch_5d(map, 0, 0, 0, 0, line + tt.b[kind][i][0]);
    }
  }
}
__device__ __forceinline__ void store_px(const Maps& tm, const TileTable& tt, uint32_t buf, int line, int kind) {
#pragma unroll
  for (int i = 0; i < 8; i++) {
    const int j = 2 * (i & 3) + (i >> 2);
    asm volatile("cp.async.bulk.tensor.5d.global.shared::cta.tile.bulk_group [%0, {%2, %2, %2, %2, %3}], [%1];" ::"l"(
                     (uint64_t)tm.px + tt.g[kind][j][1]), "r"(buf + i * 3072), "r"(0), "r"(line + tt.g[kind][j][0]) : "memory");
  }
  asm volatile("cp.async.bulk.commit_group;" ::: "memory");
}
__device__ __noinline__ bool refetch(uint32_t base, const uint8_t* src, bool gap) {
  constexpr uint32_t bars = 1024 + kBarOff, cnt = bars + 192;
#pragma unroll 1
  for (uint32_t o = 0; o < kWBytes && !gap; o += 2048) {
    uint32_t mx = 0;
#pragma unroll
    for (int i = 0; i < 4; i++) {
      uint4 v;
      asm volatile("ld.shared.v4.u32 {%0,%1,%2,%3}, [%4];" : "=r"(v.x), "=r"(v.y), "=r"(v.z), "=r"(v.w)
                   : "r"(base + o + i * 512 + (threadIdx.x & 31) * 16));
      mx = __vimax3_u32(__vimax3_u32(mx, v.x, v.y), v.z, v.w);
    }
    gap = __any_sync(0xffffffffu, mx == kEmpty);
  }
  uint32_t n;
  asm volatile("ld.shared.u32 %0, [%1];" : "=r"(n) : "r"(cnt) : "memory");
  if (!gap || __any_sync(0xffffffffu, n > (1u << 12))) return false;
  asm volatile("bar.sync 15, 128;" ::: "memory");
  if (threadIdx.x == 0) {
    asm volatile("st.shared.u32 [%0], %1;" ::"r"(cnt), "r"(n + 1) : "memory");
    mbar_arrive_expect_tx(bar_redo(bars), kWBytes);
    bulk_load(base, src, kWBytes, bar_redo(bars));
  }
  __syncwarp();
  mbar_wait(bar_redo(bars), n & 1);
  return true;
}
__device__ __forceinline__ bool any_nan(const uint32_t (&a)[24]) {
  uint32_t m[2] = {a[0], a[1]}, nan;
#pragma unroll
  for (int i = 2; i < 24; i++) asm("max.NaN.bf16x2 %0, %0, %1;" : "+r"(m[i & 1]) : "r"(a[i]));
  asm("max.NaN.bf16x2 %0, %0, %1;" : "+r"(m[0]) : "r"(m[1]));
  asm volatile("{\n.reg .pred p;\nsetp.ne.u32 p, %1, 0;\nbar.red.or.pred p, 15, 128, p;\nselp.u32 %0, 1, 0, p;\n}\n"
               : "=r"(nan) : "r"(((m[0] & 0x7FFF7FFFu) + 0x007F007Fu) & 0x80008000u) : "memory");
  return __any_sync(0xffffffffu, nan);
}
template <int S0, int S1, int Z>
__device__ __forceinline__ void g2_steps(float (&ac)[48], const uint32_t (&za)[24], const uint32_t (&zb)[24], uint64_t d) {
#pragma unroll
  for (int s = S0; s < S1; s++) {
    const uint64_t ds = d + (((s >> 2 & 1) * (kWChunk / 2) + (s & 3) * 32) >> 4);
    if (s == Z) wg_d96z<0, 48>(ac, za[2 * s], zb[2 * s], za[2 * s + 1], zb[2 * s + 1], ds, 0);
    else wg_d96<0, 48>(ac, za[2 * s], zb[2 * s], za[2 * s + 1], zb[2 * s + 1], ds, 1);
  }
}

__device__ __forceinline__ void consumer(const int wg, __nv_bfloat16* out, const uint8_t* wimg, const uint32_t sbase,
                                         const uint32_t zero, const Maps& tm, const TileTable& tt) {
  const int tid = threadIdx.x & 127;
  const int w = __shfl_sync(0xffffffffu, tid >> 5, 0), lane = tid & 31;
  const uint64_t dK = make_desc(sbase, 16, 1024);
  const uint64_t dV = make_desc(sbase, kChunkBytes, 512, 2);
  const uint64_t dW1 = make_desc(sbase + kW1Off, 16, 1024);
  const uint64_t dX0 = make_desc(sbase + kW2Off + wg * 2 * kWChunk, 16, 1024), dY0 = make_desc(sbase + kW2Off + (1 - wg) * 2 * kWChunk, 16, 1024);
  const uint64_t dX2 = make_desc(sbase + kXOff + wg * (kWChunk / 2), 16, 1024), dY2 = make_desc(sbase + kXOff + (1 - wg) * (kWChunk / 2), 16, 1024);
  const uint32_t bars = sbase + kBarOff;
  int tile0 = blockIdx.x * kTilesPerCta;
  asm volatile("" : "+r"(tile0));
  const int nt = num_tiles();

  uint32_t pix = 0, geo[6] = {};
  const int l = lane & 3;
#pragma unroll 1
  for (int j = 4; j >= 0; j -= 2) {
    const TileCoord tc = decode_tile(tt, tile0 + wg + j);
    const bool col = tc.kind == 1 || tc.kind == 2;
    const int g = col ? lane >> 2 : 2 * w + ((lane >> 2) & 1), qc = col ? w : lane >> 3;
    const uint32_t pr = qpix(tc.pr, 8 * tc.I + g) * kW;
    if (j == nt - 2) pix = (pr + qpix(tc.pc, 8 * tc.J + qc)) | (pr + qpix(tc.pc, 8 * tc.J + qc + 4)) << 16;
    const int d = 8 * tc.J + 6 * tc.pc - 6 - halo_c0(tc);
    const int ro = woff(tc.pr, tc.I, g), coA = woff(tc.pc, tc.J, qc) + d, coB = woff(tc.pc, tc.J, qc + 4) + d - 3;
#pragma unroll
    for (int i = 5; i >= 2; i--) geo[i] = geo[i - 2];
    const uint32_t lr = 0x1FCu << ro;
    const uint32_t lv = lr >> (2 + (l >> 1)), lu = lr >> (2 * l + 2 * tc.up);
    const uint32_t t = __byte_perm(lv, lu, wg ? 0x4501 : 0x5410);
    geo[0] = (((t & 0x15u) | (lv & 0x40u)) * 0x02082080u & 0x80808080u) | (((t >> 8) & 0x15u) * 0x01041040u & 0x40404040u) |
             (__byte_perm(t << 5, t << 4, 0x7362) & 0x20202020u) | (nt == 6);
    const int dr = (ro - 1) & 7;
    const uint32_t hiv = (((1u << ((ro - (l >> 1) + 1) >> 1)) - 1u) ^ (wg ? 7u : 0u)) & 7u, hiu = (t >> 24) & 3u;
    const uint32_t ca = (1u << coA) - 1u;
    geo[1] = hiv * kHiV | hiu * kHiU | ((((1u << coB) - 1u) >> (2 * (l & 1))) & 3u) * kColB |
             (15u & ~((uint32_t)((dr & 1) == (l >> 1)) << (dr >> 1))) * kInV | ((t >> 16 | t >> 24) & 3u) * kInU | ca * kColA |
             (ca >> ((0x49 >> (2 * l)) & 3) & 1u) << 19 | (uint32_t)(l == 3) << 20 | (0x55u & ((1u << (2 * coB)) - 1u)) << 24;
  }
  keep_regs(geo);
  const int so = (lane >> 3) | (lane & 4);
  uint32_t sts = sbase + w * 3072 + so * 128 + (((lane & 3) ^ so) << 4);
  __nv_bfloat16* poA = out + 8 * l + (pix & 0xFFFFu) * kC + 96 * wg;
  __nv_bfloat16* poB = out + 8 * l + (pix >> 16) * kC + 96 * wg;
  asm volatile("" : "+l"(poA), "+l"(poB), "+r"(sts));
  uint32_t oa[24], ob[24];
#pragma unroll
  for (int j = 0; j < 24; j++) oa[j] = ob[j] = 0u;
  keep_regs(oa);
  keep_regs(ob);
  PROF(wg, 0);
  if (threadIdx.x == 0) GT(1);

  for (int k = wg; k < nt; k += 2) {
    const uint32_t ph = (k >> 1) & 1;
    const int it = k >> 1;
    uint32_t qa[24], qb[24], hok[3];
    uint32_t fl = geo[1];
    {
      float acc[96];
      const uint32_t xp = (k + (k > 0)) & 1;
      const uint32_t xok = mbar_test(bar_x(bars, k > 0, 0), xp);
      if (k > 0) nb_sync(1 + (1 - wg));
#pragma unroll
      for (int s = 0; s < 12; s++) {
        if (s == 0) mbar_wait_if(xok, bar_x(bars, k > 0, 0), xp);
        if (s == 0 && k < 2) PROF(wg, 1);
        if (s == 0) PROFS(2, wg, 2 + it * 12);
        if (s == 0 && w == 0 && k < 2) GT(20 + wg);
        if ((s & 3) == 0 && (k == 0 || s > 0)) {
          mbar_wait(k == 0 ? bar_w1c(bars, s >> 2) : bar_x(bars, 1, s >> 2), xp);
          PROFS(17, wg, 50 + (s >> 2));
        }
        if ((s & 3) == 0) wg_fence();
        const uint64_t dX = make_desc(sbase + x_chunk(k, s >> 2), 16, 1024) + 2 * (s & 3);
        if (s == 0) wg_m192z<0, 96>(acc, dX, dW1, 0);
        else wg_m192<0, 96>(acc, dX, wdesc(dW1, s), 1);
        if ((s & 3) == 3) wg_commit();
      }
      PROFS(13, wg, 13 + it * 12);
      const uint32_t e = sts + out_slot(k, nt), o = e ^ 64;
      uint32_t ad[4] = {wg ? o + 1024 : e, wg ? e + 2048 : o, wg ? e : o + 1024, wg ? o : e + 2048};
      keep_regs(ad);
      wg_wait<2>();
      if (k > 0) nb_arrive_p(0);
      wg_wait<1>();
      if (k > 0) nb_arrive_p(14);
      wg_wait<0>();
      if (k > 0) {
        nb_arrive_p(6);
        sched_fence();
      }
      fence_regs(acc);
      PROFS(3, wg, 3 + it * 12);
#pragma unroll
      for (int j = 0; j < 24; j++) {
        qa[j] = pack_bf16(acc[4 * j], acc[4 * j + 1]);
        qb[j] = pack_bf16(acc[4 * j + 2], acc[4 * j + 3]);
      }
      keep_regs(qa);
      keep_regs(qb);
      sched_fence();
      if (k >= 2) {
        nb_sync(11);
        stage_out<0, 6>(ad, oa, ob);
        nb_sync(12);
        stage_out<6, 12>(ad, oa, ob);
      }
#pragma unroll
      for (int c = 0; c < 3; c++) hok[c] = mbar_test(bar_full(bars, wg, c), ph);
      if (k >= 2) {
        fence_proxy_async();
        nb_arrive_p(10);
      }
    }

    float aE[52], aO[24], bO[52], bE[28];
    const uint32_t mq = 0xEEEE4444u | zero;
    PROFS(4, wg, 4 + it * 12);

    mbar_wait_if(hok[0], bar_full(bars, wg, 0), ph);
    PROFS(14, wg, 40 + it * 3);
    if (w == 0 && k < 2) GT(22 + wg);
    if (k > 0) nb_sync(3 + (1 - wg));
    wg_fence();
#pragma unroll
    for (int ks = 0; ks < 6; ks++) {
      if (ks == 2) {
        mbar_wait_if(hok[1], bar_full(bars, wg, 1), ph);
        PROFS(14, wg, 41 + it * 3);
        wg_fence();
      }
      if (ks == 4) {
        mbar_wait_if(hok[2], bar_full(bars, wg, 2), ph);
        PROFS(14, wg, 42 + it * 3);
        wg_fence();
      }
      const uint64_t d = dK + ((ks * kChunkBytes) >> 4);
      if (ks == 0) wg_s104z<0, 52>(aE, qa[0], qa[1], qa[2], qa[3], d, 0, mq);
      else wg_s104<0, 52>(aE, qa[4 * ks], qa[4 * ks + 1], qa[4 * ks + 2], qa[4 * ks + 3], d, 1, mq);
      if (ks == 0) wg_s48z<0, 24>(aO, qa[0], qa[1], qa[2], qa[3], d + ((7 * 1024 + 64) >> 4), 0, mq);
    }
    wg_commit();
#pragma unroll
    for (int ks = 1; ks < 6; ks++)
      wg_s48<0, 24>(aO, qa[4 * ks], qa[4 * ks + 1], qa[4 * ks + 2], qa[4 * ks + 3], dK + ((ks * kChunkBytes + 7 * 1024 + 64) >> 4), 1, mq);
    wg_commit();
    wg_s56z<0, 28>(bE, qb[0], qb[1], qb[2], qb[3], dK, 0, mq);
#pragma unroll
    for (int ks = 1; ks < 6; ks++) wg_s56<0, 28>(bE, qb[4 * ks], qb[4 * ks + 1], qb[4 * ks + 2], qb[4 * ks + 3], dK + ((ks * kChunkBytes) >> 4), 1, mq);
    wg_commit();
    wg_wait<2>();
    fence_regs(aE);
    PROFS(5, wg, 5 + it * 12);

    uint32_t pa[14], pb[14], meta[4];
    {
      float vA[14], vB[14];
      pick_v(aE, vA, fl);
      pick_u(aE + 28, vA + 8, fl);
      fence_regs(vA);
      if (k == 0) {
        if (__builtin_expect(__any_sync(0xffffffffu, vA[6] != vA[6]), 0)) {
          wg_wait<0>();
          fence_regs(aO);
          fence_regs(bE);
          if (refetch(sbase + kW1Off, wimg, false)) {
#pragma unroll
            for (int j = 0; j < 24; j++) oa[j] = ob[j] = 0u;
            k -= 2;
            continue;
          }
        }
        if (elect_one()) mbar_arrive(bar_xf(bars));
      }
      wg_fence();
      wg_s104z<0, 52>(bO, qb[0], qb[1], qb[2], qb[3], dK + 4, 0, mq);
#pragma unroll
      for (int ks = 1; ks < 6; ks++)
        wg_s104<0, 52>(bO, qb[4 * ks], qb[4 * ks + 1], qb[4 * ks + 2], qb[4 * ks + 3], dK + ((ks * kChunkBytes + 64) >> 4), 1, mq);
      wg_commit();
      if (k + 1 < nt) nb_arrive(1 + wg);
      uint32_t rt[9];
#pragma unroll
      for (int i = 0; i < 7; i++) rt[i] = sign_bytes(geo[0] << (i >> 2), 0x8888u + 0x1111u * (i & 3));
      rt[7] = sign_bytes(geo[0] << 2, 0x9988u);
      rt[8] = sign_bytes(geo[0] << 2, 0xBBAAu);
      keep_regs(rt);
      pa[13] = pb[13] = 0u;
      wg_wait<2>();
      keep_regs(qa);
      fence_regs(aO);
      float oA[6], eB[8];
      pick_u(aO, oA, fl);
      wg_wait<1>();
      fence_regs(bE);
      pick_v(bE, eB, fl);
      vA[8] = sel<kColA>(oA[0], vA[8], fl), vA[9] = sel<kColA>(oA[1], vA[9], fl);
      vA[10] = sel<kColA * 2>(oA[2], vA[10], fl), vA[11] = sel<kColA * 2>(oA[3], vA[11], fl);
      vA[12] = sel<kColA * 4>(oA[4], vA[12], fl), vA[13] = sel<kColA * 4>(oA[5], vA[13], fl);
      {
        const float m1 = __uint_as_float(0x88DD88DDu), m0 = __uint_as_float(0x88DDDD88u);
        meta[0] = 0xDD88DD88u ^ __byte_perm(fl, 0u, 0x3344);
        meta[1] = __float_as_uint(sel<kColA * 16>(sel<kColA>(m1, m0, fl), __uint_as_float(meta[0]), fl));
        meta[2] = __float_as_uint(sel<kColA * 8>(m1, m0, fl));
        meta[3] = __float_as_uint(sel<kColA * 4>(m1, m0, fl));
        keep_regs(meta);
      }
      float mA = own_max(vA, fl);
      fl |= __float_as_uint(eB[7]) & zero;
      fence_regs(eB);
      fence_regs(vA);
      asm volatile("" : "+f"(mA), "+r"(fl));
      sched_fence();
      wg_wait<0>();
      sched_fence();
      keep_regs(qb);
      fence_regs(bO);
      PROFS(6, wg, 6 + it * 12);
      if (w == 0) GT(24 + k);
      mA = quad_max(mA);
#pragma unroll
      for (int i = 0; i < 14; i++) vA[i] = ex2(vA[i] - mA);
      pick_v(bO, vB, fl);
      pick_u(bO + 28, vB + 8, fl);
#pragma unroll
      for (int i = 0; i < 8; i += 2) vB[i] = sel<kColB>(vB[i], eB[i], fl), vB[i + 1] = sel<kColB * 2>(vB[i + 1], eB[i + 1], fl);
      float mB = quad_max(own_max(vB, fl));
      PROFS(7, wg, 7 + it * 12);
#pragma unroll
      for (int i = 0; i < 14; i++) vB[i] = ex2(vB[i] - mB);
      route(vA, row_rcp(vA, fl), rt, pa);
      route(vB, row_rcp(vB, fl), rt, pb);
    }
    PROFS(8, wg, 8 + it * 12);
    if (k == NAT_PK) PROFS(18, wg, 53);
    sched_fence();

    float ac0[48], ac1[48];
    {
      float z0[32], z1[32], z2[32];
      uint32_t za[24], zb[24];
      wg_fence();
      pv_chunk<0>(z0, pa, pb, meta, dV);
      wg_commit();
      pv_chunk<1>(z1, pa, pb, meta, dV);
      wg_commit();
      wg_wait<1>();
      if (k == NAT_PK) PROFS(18, wg, 54);
      if (k + 1 < nt) nb_arrive_p(7);
      pv_chunk<2, 0, 3>(z2, pa, pb, meta, dV);
      wg_commit();
      sched_fence();
      fence_regs(z0);
      pack_z<0>(z0, za, zb);
      sched_fence();
      wg_fence();
      pv_chunk<2, 3, 7>(z2, pa, pb, meta, dV);
      wg_commit();
      wg_wait<2>();
      if (k == NAT_PK) PROFS(19, wg, 55);
      if (k + 1 < nt) nb_arrive_p(8);
      if (k < 2) mbar_wait(k == 1 ? bar_wok(bars) : bar_w2a(bars), 0);
      wg_fence();
      g2_steps<0, 3, 0>(ac0, za, zb, dX0);
      wg_commit();
      sched_fence();
      fence_regs(z1);
      pack_z<1>(z1, za, zb);
      sched_fence();
      wg_fence();
      g2_steps<3, 4, 0>(ac0, za, zb, dX0);
      wg_commit();
      g2_steps<4, 8, 0>(ac0, za, zb, dX0);
      wg_commit();
      wg_wait<3>();
      if (k + 1 < nt) nb_arrive_p(9);
      else nb_arrive(11);
      if (k == NAT_PK) PROFS(20, wg, 56);
      keep_regs(pa);
      keep_regs(pb);
      keep_regs(meta);
      sched_fence();
      const uint32_t mok = mbar_test(bar_w2m(bars), k + 1 < nt ? k & 1 : ~k & 1);
      const uint32_t wp = k < 2 ? 0 : k + 1 < nt ? ~k & 1 : k & 1, wok = mbar_test(bar_w2(bars), wp);
      fence_regs(z2);
      pack_z<2>(z2, za, zb);
      keep_regs(za);
      keep_regs(zb);
      sched_fence();
      PROFS(9, wg, 9 + it * 12);
      wg_wait<1>();
      if (k > 0 && k + 1 < nt) nb_arrive(11);
      mbar_wait_if(mok, bar_w2m(bars), k & 1);
      wg_fence();
      g2_steps<8, 12, 0>(ac0, za, zb, dX2);
      wg_commit();
      g2_steps<8, 12, 8>(ac1, za, zb, dY2);
      wg_commit();
      wg_wait<2>();
      if (k > 0 && k + 1 < nt) nb_arrive(12);
      mbar_wait_if(wok, bar_w2(bars), wp);
      wg_fence();
      g2_steps<0, 4, 8>(ac1, za, zb, dY0);
      wg_commit();
      wg_wait<2>();
      if (k + 2 < nt) nb_arrive_p(13);
      const bool direct = k + 2 >= nt;
      sched_fence();
      fence_regs(ac0);
      pack_out<0>(ac0, oa, ob);
      store_rows<0, 1>(direct, poA, poB, oa, ob);
      sched_fence();
      wg_fence();
      g2_steps<4, 8, 8>(ac1, za, zb, dY0);
      wg_commit();
      if (k + 1 < nt) nb_arrive(3 + wg);
      PROFS(10, wg, 10 + it * 12);
      wg_wait<2>();
      if (k + 2 < nt && (k > 0 || nt == 6)) nb_arrive_p(5);
      store_rows<1, 3>(direct, poA, poB, oa, ob);
      __nv_bfloat16 *qA = poA - 192 * wg, *qB = poB - 192 * wg;
      if (k + 2 == nt) nb_sync(11);
      sched_fence();
      wg_wait<0>();
      fence_regs(ac1);
      pack_out<1>(ac1, oa, ob);
      asm volatile("" : "+l"(qA), "+l"(qB));
      store_rows<3, 6>(direct, qA, qB, oa, ob);
      if (direct) break;
      if (k == 0) {
        if (any_nan(oa)) {
          for (int c = 0; c < 3 && __any_sync(0xffffffffu, geo[2] & 1u); c++) mbar_wait(bar_x(bars, 1, c), 1);
          bool first = true;
          do {
            if (!__any_sync(0xffffffffu, refetch(sbase + kW2Off, wimg + w2_offset(), first))) break;
            first = false;
            wg_fence();
            g2_steps<0, 8, 0>(ac0, za, zb, dX0);
            g2_steps<8, 12, 0>(ac0, za, zb, dX2);
            g2_steps<8, 12, 8>(ac1, za, zb, dY2);
            g2_steps<0, 8, 8>(ac1, za, zb, dY0);
            wg_commit();
            wg_wait<0>();
            fence_regs(ac0);
            fence_regs(ac1);
            pack_out<0>(ac0, oa, ob);
            pack_out<1>(ac1, oa, ob);
          } while (any_nan(oa));
          if (__any_sync(0xffffffffu, geo[2] & 1u)) {
            asm volatile("bar.sync 15, 128;" ::: "memory");
            if (w == 0 && elect_one()) {
              const TileCoord tc = decode_tile(tt, tile0 + 2);
              mbar_arrive_expect_tx(bar_raw(bars), kWChunk);
#pragma unroll 1
              for (int c = 0; c < 3; c++) load_px(tm, tt, sbase + x_chunk(2, c), bar_raw(bars), first_line(tc) + c, tc.kind);
            }
            __syncwarp();
            mbar_wait(bar_raw(bars), 0);
          }
        }
        if (nt < 6) nb_arrive_p(5);
        if (elect_one()) mbar_arrive(bar_wok(bars));
      }
      keep_regs(za);
      keep_regs(zb);
#pragma unroll
      for (int i = 0; i < 4; i++) geo[i] = geo[i + 2];
      keep_regs(oa);
      keep_regs(ob);
      PROFS(12, wg, 12 + it * 12);
      sched_fence();
    }
  }
  PROF(wg, 38);
  GT_DUMP();
  PROF_DUMP(wg);
}

struct HaloCols { int vj, vc, uj, uc; };
__device__ __forceinline__ HaloCols halo_cols(const TileCoord& tc) {
  const int c0 = halo_c0(tc);
  return HaloCols{c0 > 98, c0 > 98 ? 98 : c0 + 3, c0 < 0 ? -1 : 0, c0 < 0 ? 4 : c0};
}
__device__ __forceinline__ void first_halo(const Maps& tm, uint32_t sbase, const TileCoord tc, int i) {
  const HaloCols hc = halo_cols(tc);
  const uint32_t dst = sbase + i * kChunkBytes, bar = bar_full(sbase + kBarOff, 0, i >> 1);
  const int h0 = halo_r0(tc), ch = 24 * tc.pc + 4 * i;
  tma_load_5d(dst, &tm.v14, bar, ch, hc.vj, hc.vc, tc.pr, h0);
  tma_load_5d(dst + 7 * 1024, &tm.u8, bar, ch, hc.uj, h0 + (tc.up ? 0 : -2), tc.pr, hc.uc);
  tma_load_5d(dst + 10 * 1024, &tm.u8, bar, ch, hc.uj, h0 + (tc.up ? 8 : 6), tc.pr, hc.uc);
}
__device__ __forceinline__ void load_halo(const Maps& tm, uint32_t sbase, uint32_t bars, const TileCoord tc, int k, int c) {
  const HaloCols hc = halo_cols(tc);
  const int h6 = halo_r0(tc) + (tc.up ? 0 : 8), h2 = halo_r0(tc) + 6, h8 = halo_r0(tc) + (tc.up ? 0 : 6), ch = 24 * tc.pc + 8 * c;
  uint32_t dv = sbase + 2 * c * kChunkBytes, du = dv + 7 * 1024;
  if (((k ^ tc.up) & 1) == 0) dv += 4 * 1024, du += 3 * 1024;
  const uint32_t bar = bar_full(bars, k & 1, c);
  mbar_arrive_expect_tx(bar, 14 * 1024);
  nb_sync_p(7 + c);
#pragma unroll
  for (int h = 0; h < 2; h++) {
    tma_load_5d(dv + h * kChunkBytes, &tm.v6, bar, ch + 4 * h, hc.vj, hc.vc, tc.pr, h6);
    tma_load_5d(du + h * kChunkBytes, &tm.u8, bar, ch + 4 * h, hc.uj, h8, tc.pr, hc.uc);
    tma_load_5d(sbase + (2 * c + h) * kChunkBytes + 3 * 1024, &tm.v2, bar, ch + 4 * h, hc.vj, hc.vc, tc.pr, h2);
  }
  PROFS(15, 2, k * 4 + c);
}
__device__ __forceinline__ void gather_px(const __nv_bfloat16* __restrict__ x, uint32_t sbase, const TileCoord tc) {
  const int lane = threadIdx.x & 31, g = lane >> 3;
  uint32_t ro[4], co[4];
#pragma unroll
  for (int i = 0; i < 4; i++) {
    ro[i] = qpix(tc.pr, 8 * tc.I + 2 * i + (g & 1)) * (kW * kC * 2) + 16 * (lane & 7);
    co[i] = qpix(tc.pc, 8 * tc.J + 2 * i + (g >> 1)) * (kC * 2);
  }
  const uint32_t dst = sbase + kXOff + g * 128 + (((lane & 7) ^ g) << 4);
  if (lane < 8)
    asm volatile("cp.async.bulk.prefetch.L2.global [%0], 3456;" ::"l"(x + (qpix(tc.pr, 8 * tc.I + lane) * kW + 215 * tc.pc) * kC) : "memory");
  __syncwarp();
  keep_regs(ro);
  keep_regs(co);
  sched_fence();
  nb_sync_p(13);
  nb_sync_p(5);
#pragma unroll
  for (int i = 0; i < 16; i++) {
    const char* src = (const char*)x + (ro[i >> 2] + co[i & 3]);
#pragma unroll
    for (int q = 0; q < 3; q++)
      asm volatile("cp.async.cg.shared.global [%0], [%1], 16;" ::"r"((dst ^ ((i & 1) * 576)) + (i >> 1) * 1024 + q * 8192), "l"(src + 128 * q) : "memory");
  }
  asm volatile("cp.async.wait_all;" ::: "memory");
  fence_proxy_async();
  __syncwarp();
  if (lane < 3) mbar_arrive(bar_x(sbase + kBarOff, 1, lane));
  __syncwarp();
}

__global__ void __launch_bounds__(384, 1)
nat_kernel(const __nv_bfloat16* __restrict__ x, __nv_bfloat16* out, const __nv_bfloat16* __restrict__ wqkv,
           const __nv_bfloat16* __restrict__ wo, uint8_t* wimg, const uint32_t zero,
           const __grid_constant__ Maps tm, const __grid_constant__ TileTable tt) {
  extern __shared__ uint8_t smem_raw[];
  constexpr uint32_t sbase = 1024;
  constexpr uint32_t bars = sbase + kBarOff;
  if (smem_u32(smem_raw) != sbase) __trap();
  const int tid = threadIdx.x;
  const uint32_t t_start = now_ns();
  if (tid == 0) GT(0);
  const int wid = __shfl_sync(0xffffffffu, tid >> 5, 0);
  const bool w2cta = blockIdx.x - 128 < 3 && wqkv != nullptr;
  if (wid >= 8) {
    asm volatile("setmaxnreg.dec.sync.aligned.u32 24;");
    const int c = wid & 3, lane = tid & 31;
    const int tile0 = blockIdx.x * kTilesPerCta, nt = num_tiles();
    uint32_t w2o = 0;
    if (c == 3) {
      if (elect_one()) wait_clock(t_start, NAT_TM);
      __syncwarp();
      asm volatile("prefetch.tensormap [%0];" ::"l"((uint64_t)tm.px) : "memory");
      asm volatile("prefetch.tensormap [%0];" ::"l"((uint64_t)&tm.v6) : "memory");
      asm volatile("prefetch.tensormap [%0];" ::"l"((uint64_t)&tm.v2) : "memory");
      asm volatile("prefetch.tensormap [%0];" ::"l"((uint64_t)(tm.px + (blockIdx.x < 112 ? 5 : 6))) : "memory");
      asm volatile("prefetch.tensormap [%0];" ::"l"((uint64_t)(tm.px + 7)) : "memory");
      if (nt < 6) {
        asm volatile("prefetch.tensormap [%0];" ::"l"((uint64_t)(tm.px + 1)) : "memory");
        asm volatile("prefetch.tensormap [%0];" ::"l"((uint64_t)(tm.px + 2)) : "memory");
        asm volatile("prefetch.tensormap [%0];" ::"l"((uint64_t)&tm.v14) : "memory");
        asm volatile("prefetch.tensormap [%0];" ::"l"((uint64_t)&tm.u8) : "memory");
      }
      __nanosleep(NAT_TW2 - 2800);
      asm volatile("bar.sync 4, 64;" ::: "memory");
      w2o = w2_offset();
      if (elect_one()) {
        mbar_arrive_expect_tx(bar_w2a(bars), kWChunk);
        mbar_arrive_expect_tx(bar_w2(bars), kWChunk);
        wait_clock(t_start, NAT_TW2);
        bulk_load(sbase + kW2Off, wimg + w2o, kWChunk, bar_w2a(bars));
        mbar_wait(bar_xf(bars), 0);
        bulk_load(sbase + kW2Off + 2 * kWChunk, wimg + (w2o + 2 * kWChunk), kWChunk, bar_w2(bars));
      }
      __syncwarp();
      if (nt < 6) gather_px(x, sbase, decode_tile(tt, tile0 + 2));
      if (wqkv == nullptr) return;
      mbar_wait(bar_wok(bars), 0);
      if (lane == 0) asm volatile("red.relaxed.gpu.global.add.u32 [%0], 1;" ::"l"(g_flag) : "memory");
      if (blockIdx.x != kCtas - 1) return;
#pragma unroll
      for (int i = 0; i < 8; i++) asm volatile("st.shared.v4.u32 [%0], {%1,%1,%1,%1};" ::"r"(bars + 1024 + i * 512 + lane * 16), "r"(kEmpty) : "memory");
      fence_proxy_async();
      __syncwarp();
      if (elect_one()) {
#pragma unroll 1
        for (int i = 0; i < 36; i++) {
          if (i == 18) {
            uint32_t v, it = 0;
            do {
              __nanosleep(500);
              asm volatile("ld.relaxed.gpu.global.u32 %0, [%1];" : "=r"(v) : "l"(g_flag) : "memory");
            } while (v < gridDim.x && ++it < (1u << 18));
          }
          asm volatile("cp.async.bulk.global.shared::cta.bulk_group [%0], [%1], 4096;" ::"l"(
                           wimg + (i < 18 ? 3 * kWBytes - w2o + i * 4096 : (i - 18) * 4096)), "r"(bars + 1024) : "memory");
          asm volatile("cp.async.bulk.commit_group;" ::: "memory");
          asm volatile("cp.async.bulk.wait_group.read 1;" ::: "memory");
        }
        asm volatile("cp.async.bulk.wait_group 0;" ::: "memory");
        g_flag[0] = 0;
        g_flag[32] = w2o == kWBytes;
      }
      return;
    }
    if (!elect_one()) return;
    if (c == 0) {
      for (int i = 0; i < kNumBars; i++)
        if ((i != 0 && i != 10 || nt < 6) && (i != 21 || !w2cta)) mbar_init(bars + i * 8, i == 13 || i == 16 ? 4 : 1);
      asm volatile("st.shared.v2.u32 [%0], {%1,%1};" ::"r"(bars + 192), "r"(0) : "memory");
      asm volatile("fence.mbarrier_init.release.cluster;" ::: "memory");
      if (w2cta) asm volatile("bar.sync 10, 64;" ::: "memory");
      asm volatile("bar.arrive 0, 160;" ::: "memory");
      asm volatile("bar.arrive 14, 160;" ::: "memory");
      asm volatile("bar.arrive 13, 96;" ::: "memory");
      asm volatile("bar.arrive 4, 64;" ::: "memory");
      const TileCoord tc0 = decode_tile(tt, tile0);
      const HaloCols hc = halo_cols(tc0);
      const int h0 = halo_r0(tc0);
#pragma unroll
      for (int j = 0; j < 3; j++)
        if (j > 0 || nt < 6) mbar_arrive_expect_tx(bar_full(bars, 0, j), 2 * kChunkBytes);
      wait_clock(t_start, NAT_HP);
#pragma unroll
      for (int q = 8; q < 24 && !w2cta; q += 8) {
        tma_prefetch_5d(blockIdx.x < 112 ? &tm.v6 : &tm.v14, 24 * tc0.pc + q, hc.vj, hc.vc, tc0.pr, h0 + (tc0.up || blockIdx.x >= 112 ? 0 : 8));
        tma_prefetch_5d(&tm.u8, 24 * tc0.pc + q, hc.uj, h0 + (tc0.up ? 0 : 6), tc0.pr, hc.uc);
      }
#pragma unroll 1
      for (int i = nt < 6 ? 0 : 2; i < 6; i++) {
        if (i == 2) mbar_wait(bar_w1q(bars), 0);
        first_halo(tm, sbase, tc0, i);
      }
      mbar_arrive(bar_go(bars));
      w2o = w2_offset();
    } else {
      asm volatile("bar.sync 13, 96;" ::: "memory");
      if (c == 2) {
        if (wqkv != nullptr && blockIdx.x < 131) asm volatile("bar.sync 12, 64;" ::: "memory");
        const uint32_t c0 = clock();
        while ((uint32_t)clock() - c0 < NAT_TD && nt == 6) { }
        wait_clock(t_start, NAT_T0);
#pragma unroll
        for (int j = 0; j < 3; j++) {
          mbar_arrive_expect_tx(bar_w1c(bars, j), kWChunk);
          bulk_load(sbase + kW1Off + j * kWChunk, wimg + j * kWChunk, kWChunk, bar_w1c(bars, j));
        }
        mbar_arrive(bar_w1q(bars));
        GT(2);
      } else {
#pragma unroll 1
        for (int j = nt == 6; j < 2; j++) {
          const TileCoord tc = decode_tile(tt, tile0 + j);
          const int line = first_line(tc);
          if (j == 1) mbar_wait(bar_go(bars), 0);
          if (j == 0) GT(15);
#pragma unroll 1
          for (int q = 0; q < 3; q++) {
            load_px(tm, tt, sbase + x_chunk(j, q), bar_x(bars, j, q), line + q, tc.kind);
            if (j == 1 || q == 0) mbar_arrive_expect_tx(bar_x(bars, j, q), j ? 8192 : kWChunk);
          }
          if (j == 0) GT(16);
        }
        w2o = w2_offset();
        wait_clock(t_start, NAT_TW2);
        mbar_wait(bar_xf(bars), 0);
      }
    }
#pragma unroll 1
    for (int k = 1; k < nt; k++) {
      const TileCoord tn = decode_tile(tt, tile0 + k + 1);
      const int line = first_line(tn);
      const bool more = k + 1 < nt && (k > 1 || nt == 6);
      if (c == 1) {
#pragma unroll
        for (int q = 0; q < 3; q++) {
          nb_sync_p(q == 0 ? 0 : q == 1 ? 14 : 6);
          bulk_load(sbase + x_chunk(k, q), wimg + (w2o + x_chunk(k, q) - kW2Off), 8192, bar_w2m(bars));
        }
        mbar_arrive_expect_tx(bar_w2m(bars), kWChunk);
      }
      if (c == 2) {
        if (k == 1) wait_clock(t_start, NAT_TX2);
        else __nanosleep(NAT_PFD);
#pragma unroll 1
        for (int q = 0; q < 3 && more; q++) load_px(tm, tt, 0, 0, line + q, tn.kind);
      }
      if (c == 2 && (blockIdx.x >= 112 || k == 5)) {
        const TileCoord tc = decode_tile(tt, tile0 + k);
        const HaloCols hc = halo_cols(tc);
        const int h8 = halo_r0(tc) + (tc.up ? 0 : 6);
#pragma unroll 1
        for (int q = 0; q < 24; q += 8) {
          tma_prefetch_5d(&tm.v6, 24 * tc.pc + q, hc.vj, hc.vc, tc.pr, h8);
          tma_prefetch_5d(&tm.v2, 24 * tc.pc + q, hc.vj, hc.vc, tc.pr, h8 + 6);
          tma_prefetch_5d(&tm.u8, 24 * tc.pc + q, hc.uj, h8, tc.pr, hc.uc);
        }
      }
      load_halo(tm, sbase, bars, decode_tile(tt, tile0 + k), k, c);
      if (c == 0 && more) {
#pragma unroll
        for (int q = 0; q < 3; q++) {
          if (q < 2) nb_sync_p(q ? 5 : 13);
          load_px(tm, tt, sbase + x_chunk(k + 1, q), bar_x(bars, 1, q), line + q, tn.kind);
          if (q != 1) mbar_arrive_expect_tx(bar_x(bars, 1, q), 8192);
        }
        mbar_arrive_expect_tx(bar_x(bars, 1, 1), 8192);
        PROFS(16, 2, k * 4 + 3);
      }
      if (c == 0 && k >= 2) {
        const TileCoord tp = decode_tile(tt, tile0 + k - 2);
        const int lp = first_line(tp);
        nb_sync_p(10);
        __nanosleep(NAT_XW);
        store_px(tm, tt, sbase + out_slot(k, nt), lp, tp.kind);
        if (k + 1 < nt) {
          asm volatile("cp.async.bulk.wait_group.read 0;" ::: "memory");
          bulk_load(sbase + out_slot(k, nt), wimg + (w2o + out_slot(k, nt) - kW2Off), kWChunk, bar_w2(bars));
          mbar_arrive_expect_tx(bar_w2(bars), kWChunk);
        }
      }
    }
    asm volatile("cp.async.bulk.wait_group 0;" ::: "memory");
  } else {
    if (blockIdx.x < 128) {
      if ((wid == 4 || (wid == 5 && blockIdx.x - 2 < 16)) && wqkv != nullptr) {
        fold_w1(blockIdx.x - 2 < 16 ? 2 * blockIdx.x + wid - 6 : blockIdx.x + (blockIdx.x < 2 ? 0 : 16), wqkv, wimg);
        if (wid == 4) asm volatile("bar.arrive 12, 64;" ::: "memory");
        if (tid == 128) GT(7);
      }
      sched_fence();
      if (wid == 1 && elect_one()) {
        const TileCoord tc = decode_tile(tt, blockIdx.x * kTilesPerCta);
        mbar_init(bar_x(bars, 0, 0), 1);
        asm volatile("fence.mbarrier_init.release.cluster;" ::: "memory");
        mbar_arrive_expect_tx(bar_x(bars, 0, 0), kWChunk);
        GT(15);
#pragma unroll 1
        for (int q = 0; q < 3; q++) load_px(tm, tt, sbase + x_chunk(0, q), bar_x(bars, 0, 0), first_line(tc) + q, tc.kind);
        GT(16);
      }
      __syncwarp();
      sched_fence();
      if (wid == 2 && elect_one()) {
        const TileCoord tc = decode_tile(tt, blockIdx.x * kTilesPerCta);
        mbar_init(bar_full(bars, 0, 0), 1);
        asm volatile("fence.mbarrier_init.release.cluster;" ::: "memory");
        mbar_arrive_expect_tx(bar_full(bars, 0, 0), 2 * kChunkBytes);
        asm volatile("prefetch.tensormap [%0];" ::"l"((uint64_t)&tm.u8) : "memory");
        GT(17);
        first_halo(tm, sbase, tc, 0);
        first_halo(tm, sbase, tc, 1);
      }
      __syncwarp();
    }
    sched_fence();
    {
      if (blockIdx.x >= 128 && wqkv != nullptr && (wid | 2) == 2 && elect_one())
        asm volatile("cp.async.bulk.prefetch.L2.global [%0], %1;" ::"l"(wid ? wo + (blockIdx.x & 3) * 48 * 192 : wqkv + (blockIdx.x & 3) * 48 * 576),
                     "r"(wid ? 48 * 384 : 48 * 1152) : "memory");
      __syncwarp();
      if (w2cta) {
        const int q = blockIdx.x & 3, h = wid >> 2;
        uint32_t w2o = 0;
        if (wid == 1 && elect_one()) {
          asm volatile("prefetch.tensormap [%0];" ::"l"((uint64_t)&tm.wo) : "memory");
          mbar_init(bar_raw(bars, 0), 1);
          mbar_init(bar_raw(bars, 1), 1);
          asm volatile("fence.mbarrier_init.release.cluster;" ::: "memory");
#pragma unroll
          for (int j = 0; j < 3; j++)
            asm volatile("cp.async.bulk.tensor.3d.shared::cluster.global.tile.mbarrier::complete_tx::bytes [%0], [%1, {%3, %4, %5}], [%2];" ::"r"(
                             j ? sbase + kW2Off + (j - 1) * (kWBytes / 2) : sbase),
                         "l"((uint64_t)(j ? &tm.wo : &tm.wv)), "r"(bar_raw(bars, j >> 1)), "r"(0), "r"(j ? 0 : 64 * q), "r"(j ? 3 * j - 3 : 6) : "memory");
          mbar_arrive_expect_tx(bar_raw(bars, 0), kWChunk + kWBytes / 2);
          mbar_arrive_expect_tx(bar_raw(bars, 1), kWBytes / 2);
          w2o = w2_offset();
        }
        __syncwarp();
#pragma unroll 1
        for (int r = 1 - h;; r++) {
          if (r > 0) asm volatile("bar.sync 11, 256;" ::: "memory");
          if (r == 2) break;
          if (r > 0) {
            mbar_wait(bar_raw(bars, 0), 0);
            mbar_wait(bar_raw(bars, h), 0);
          }
          if (tid == 0) GT(7);
          float acc[48];
          const uint64_t db = make_desc(sbase + kW2Off + h * (kWBytes / 2), kWChunk / 2, 512, 2);
          wg_fence();
          wg_m96tz<0, 48>(acc, make_desc(sbase, 16, 1024), db, 0);
#pragma unroll
          for (int s = 1; s < 12; s++) wg_m96t<0, 48>(acc, make_desc(sbase + (s >> 2) * 8192 + (s & 3) * 32, 16, 1024), db + s * 64, 1);
          wg_commit();
          wg_wait<0>();
          fence_regs(acc);
          if (tid == 0) GT(19);
          const int m = (tid >> 3) & 3;
#pragma unroll
          for (int j = 0; j < 12; j += 2) {
            const int n = g2_inv(8 * (j + (m >> 1)) + (tid & 7));
            asm volatile("stmatrix.sync.aligned.m8n8.x4.trans.shared.b16 [%0], {%1,%2,%3,%4};" ::"r"(
                             sbase + kW1Off + h * (kWChunk / 2) + n * 128 + (((2 * (wid & 3) + (m & 1)) ^ (n & 7)) << 4)),
                         "r"(pack_bf16(acc[4 * j], acc[4 * j + 1])), "r"(pack_bf16(acc[4 * j + 2], acc[4 * j + 3])),
                         "r"(pack_bf16(acc[4 * j + 4], acc[4 * j + 5])), "r"(pack_bf16(acc[4 * j + 6], acc[4 * j + 7])) : "memory");
          }
          fence_proxy_async();
        }
        if (tid == 0) GT(18);
        if (wid == 1) {
          if (elect_one()) {
#pragma unroll
            for (int i = 0; i < 2; i++)
              asm volatile("cp.async.bulk.global.shared::cta.bulk_group [%0], [%1], %2;" ::"l"(wimg + (w2o + w2piece(i, q) * (kWChunk / 2))),
                           "r"(sbase + kW1Off + i * (kWChunk / 2)), "r"(kWChunk / 2) : "memory");
            asm volatile("cp.async.bulk.commit_group;" ::: "memory");
          }
          __syncwarp();
          asm volatile("bar.arrive 10, 64;" ::: "memory");
          if (elect_one()) asm volatile("cp.async.bulk.wait_group.read 0;" ::: "memory");
          if (tid == 32) GT(31);
          __syncwarp();
          asm volatile("bar.arrive 12, 64;" ::: "memory");
        }
      }
    }
    __syncwarp();
    if (wid < 4) asm volatile("bar.sync 0, 160;" ::: "memory");
    else asm volatile("bar.sync 14, 160;" ::: "memory");
    asm volatile("setmaxnreg.inc.sync.aligned.u32 240;");
    consumer(wid >> 2, out, wimg, sbase, zero, tm, tt);
  }
}

}

typedef CUresult (*PFN_encodeTiled)(CUtensorMap*, CUtensorMapDataType, cuuint32_t, void*, const cuuint64_t*,
                                    const cuuint64_t*, const cuuint32_t*, const cuuint32_t*, CUtensorMapInterleave,
                                    CUtensorMapSwizzle, CUtensorMapL2promotion, CUtensorMapFloatOOBfill);

extern "C" void kernel_launch(void* const* d_in, const int* in_sizes, int n_in, void* d_out, int out_size) {
  const __nv_bfloat16* x = (const __nv_bfloat16*)d_in[0];
  const __nv_bfloat16* wqkv = (const __nv_bfloat16*)d_in[1];
  const __nv_bfloat16* wo = (const __nv_bfloat16*)d_in[2];
  __nv_bfloat16* out = (__nv_bfloat16*)d_out;

  static PFN_encodeTiled encode = nullptr;
  static int num_sms = 0;
  static uint8_t* wimg = nullptr;
  if (!encode) {
    void* fn = nullptr;
    cudaDriverEntryPointQueryResult qres;
    cudaGetDriverEntryPoint("cuTensorMapEncodeTiled", &fn, cudaEnableDefault, &qres);
    encode = (PFN_encodeTiled)fn;
    cudaFuncSetAttribute(nat::nat_kernel, cudaFuncAttributeMaxDynamicSharedMemorySize, nat::kSmemBytes);
    cudaGetSymbolAddress((void**)&wimg, nat::g_wimg32);
    int dev = 0;
    cudaGetDevice(&dev);
    cudaDeviceGetAttribute(&num_sms, cudaDevAttrMultiProcessorCount, dev);
  }
  nat::Maps tm;
  cuuint32_t estr[5] = {1, 1, 1, 1, 1};
  {
    cuuint64_t vdim[5] = {48, 2, 105, 2, 112}, udim[5] = {48, 2, 112, 2, 105};
    cuuint64_t vstr[4] = {7 * 768, 768, 224 * 384, 2 * 224 * 384}, ustr[4] = {7 * 768, 2 * 224 * 384, 224 * 384, 768};
    CUtensorMap* maps[4] = {&tm.v6, &tm.v2, &tm.v14, &tm.u8};
    for (int i = 0; i < 4; i++) {
      cuuint32_t box[5] = {4, 2, i < 3 ? 4u : 8u, 1, i == 0 ? 6u : i == 1 ? 2u : i == 2 ? 14u : 3u};
      encode(maps[i], CU_TENSOR_MAP_DATA_TYPE_UINT32, 5, (void*)x, i < 3 ? vdim : udim, i < 3 ? vstr : ustr, box, estr,
             CU_TENSOR_MAP_INTERLEAVE_16B, CU_TENSOR_MAP_SWIZZLE_128B, CU_TENSOR_MAP_L2_PROMOTION_L2_128B, CU_TENSOR_MAP_FLOAT_OOB_FILL_NONE);
    }
  }
  for (int i = 0; i < 8; i++) {
    const cuuint32_t row = 224 * 384;
    const cuuint32_t shape[8][6] = {{2, 8, 4, 2 * row, 768, 4 * row}, {2, 8, 3, row, 768, 2 * row},     {2, 8, 1, 2 * row, 768, 4 * row},
                                    {8, 2, 3, 2 * row, 4 * 384, 384}, {8, 2, 1, 2 * row, 5 * 384, 384}, {4, 2, 3, 4 * row, 2 * row, 128},
                                    {4, 2, 3, 768, row, 128},         {4, 2, 3, 768, 2 * row, 128}};
    const cuuint32_t* sh = shape[i];
    cuuint64_t dim[5] = {64, sh[0], sh[1], sh[2], 224 * 224 * 3};
    cuuint64_t str[4] = {sh[3], sh[4], sh[5], 128};
    cuuint32_t box[5] = {64, sh[0], sh[1], sh[2], 1};
    encode(tm.px + i, CU_TENSOR_MAP_DATA_TYPE_BFLOAT16, 5, i < 5 ? (void*)x : (void*)out, dim, str, box, estr, CU_TENSOR_MAP_INTERLEAVE_NONE,
           CU_TENSOR_MAP_SWIZZLE_128B, i < 5 ? CU_TENSOR_MAP_L2_PROMOTION_L2_128B : CU_TENSOR_MAP_L2_PROMOTION_NONE,
           CU_TENSOR_MAP_FLOAT_OOB_FILL_NONE);
  }
  for (int i = 0; i < 2; i++) {
    cuuint64_t dim[3] = {i ? 32u : 64u, 192, i ? 6u : 9u}, str[2] = {i ? 384u : 1152u, i ? 64u : 128u};
    cuuint32_t box[3] = {i ? 32u : 64u, i ? 192u : 64u, 3};
    encode(i ? &tm.wo : &tm.wv, CU_TENSOR_MAP_DATA_TYPE_BFLOAT16, 3, i ? (void*)wo : (void*)wqkv, dim, str, box, estr,
           CU_TENSOR_MAP_INTERLEAVE_NONE, i ? CU_TENSOR_MAP_SWIZZLE_64B : CU_TENSOR_MAP_SWIZZLE_128B, CU_TENSOR_MAP_L2_PROMOTION_L2_256B,
           CU_TENSOR_MAP_FLOAT_OOB_FILL_NONE);
  }
  nat::TileTable tt;
  nat::make_tiles(tt);
  const int grid = nat::kCtas;
  if (num_sms >= grid) {
    nat::nat_kernel<<<grid, 384, nat::kSmemBytes>>>(x, out, wqkv, wo, wimg, 0u, tm, tt);
  } else {
    nat::fold_kernel<<<27, 256>>>(wqkv, wo, wimg);
    nat::nat_kernel<<<grid, 384, nat::kSmemBytes>>>(x, out, nullptr, nullptr, wimg, 0u, tm, tt);
  }
}
```

```cpp
#include <cuda_runtime.h>
#include <cuda_bf16.h>
#include <cuda.h>
#include <stdint.h>

#define NAT_TM 1300
#define NAT_HP 1800
#define NAT_T0 2130
#define NAT_TD 1250
#define NAT_TX2 3800
#define NAT_TW2 4600
#define NAT_PFD 300
#define NAT_XW 200
#define NAT_HS 4
#define NAT_ZZ 1
#define NAT_PK 3
namespace nat {

constexpr int kW = 224, kC = 192;
constexpr int kCtas = 132;
constexpr int kTilesPerCta = 6;
constexpr float kAlpha = 0.07216878364870322f * 1.4426950408889634f;
constexpr uint32_t kChunkBytes = 13 * 1024;
constexpr uint32_t kWChunk = 192 * 128;
constexpr uint32_t kWBytes = 3 * kWChunk;
constexpr uint32_t kW1Off = 6 * kChunkBytes;
constexpr uint32_t kW2Off = kW1Off + kWBytes;
constexpr uint32_t kXOff = kW2Off + kWChunk;
constexpr uint32_t kBarOff = kW2Off + kWBytes;
constexpr uint32_t kProfOff = kBarOff + 208;
constexpr uint32_t kSmemBytes = kBarOff + 1024 + 4096;

static_assert(kW1Off % 1024 == 0 && kW2Off % 1024 == 0 && kChunkBytes % 1024 == 0, "swizzle alignment");
static_assert(kSmemBytes <= 232448, "smem");

constexpr uint32_t kEmpty = 0xFFFFFFFFu;
#define NAT_R8(v) v, v, v, v, v, v, v, v
#define NAT_R2K(v) NAT_R8(NAT_R8(NAT_R8(v))), NAT_R8(NAT_R8(NAT_R8(v))), NAT_R8(NAT_R8(NAT_R8(v))), NAT_R8(NAT_R8(NAT_R8(v)))
#define NAT_IMG NAT_R8(NAT_R2K(kEmpty)), NAT_R2K(kEmpty)
__device__ __align__(1024) uint32_t g_wimg32[3 * kWBytes / 4] = {NAT_IMG, NAT_IMG, NAT_IMG};
static_assert(kWBytes / 4 == 9 * 2048, "initialiser");
__device__ __align__(128) uint32_t g_flag[64];
__device__ __forceinline__ uint32_t w2_offset() {
  uint32_t v;
  asm volatile("ld.relaxed.gpu.global.u32 %0, [%1];" : "=r"(v) : "l"(g_flag + 32) : "memory");
  return (1 + v) * kWBytes;
}

#define PROFS(id, wgid, slotid) do { } while (0)
#define PROF(wgid, slotid) do { } while (0)
#define PROF_DUMP(wgid) do { } while (0)

#define GT(slotid) do { } while (0)
#define GT_DUMP() do { } while (0)

__device__ __forceinline__ uint32_t smem_u32(const void* p) { return (uint32_t)__cvta_generic_to_shared(p); }

__device__ __forceinline__ void mbar_init(uint32_t bar, uint32_t count) {
  asm volatile("mbarrier.init.shared::cta.b64 [%0], %1;" ::"r"(bar), "r"(count) : "memory");
}
__device__ __forceinline__ void mbar_arrive(uint32_t bar) {
  asm volatile("mbarrier.arrive.shared::cta.b64 _, [%0];" ::"r"(bar) : "memory");
}
__device__ __forceinline__ void mbar_arrive_expect_tx(uint32_t bar, uint32_t bytes) {
  asm volatile("mbarrier.arrive.expect_tx.shared::cta.b64 _, [%0], %1;" ::"r"(bar), "r"(bytes) : "memory");
}
__device__ __forceinline__ void mbar_wait(uint32_t bar, uint32_t parity) {
  uint32_t ok;
  uint32_t it = 0;
  do {
    asm volatile(
        "{\n.reg .pred p;\n"
        "mbarrier.try_wait.parity.shared::cta.b64 p, [%1], %2;\n"
        "selp.u32 %0, 1, 0, p;\n}\n"
        : "=r"(ok)
        : "r"(bar), "r"(parity)
        : "memory");
    if (++it > (1u << 24)) break;
  } while (!ok);
}
__device__ __forceinline__ uint32_t mbar_test(uint32_t bar, uint32_t parity) {
  uint32_t ok;
  asm volatile("{\n.reg .pred p;\nmbarrier.test_wait.parity.shared::cta.b64 p, [%1], %2;\nselp.u32 %0, 1, 0, p;\n}\n"
               : "=r"(ok) : "r"(bar), "r"(parity) : "memory");
  return ok;
}
__device__ __forceinline__ void mbar_wait_if(uint32_t ok, uint32_t bar, uint32_t parity) {
  if (!__all_sync(0xffffffffu, ok)) mbar_wait(bar, parity);
}
__device__ __forceinline__ bool elect_one() {
  uint32_t r;
  asm volatile("{\n.reg .pred p;\nelect.sync _|p, 0xffffffff;\nselp.u32 %0, 1, 0, p;\n}\n" : "=r"(r));
  return r != 0;
}
__device__ __forceinline__ void nb_arrive(int id) { asm volatile("bar.arrive %0, 256;" ::"r"(id) : "memory"); }
__device__ __forceinline__ void nb_sync(int id) { asm volatile("bar.sync %0, 256;" ::"r"(id) : "memory"); }
__device__ __forceinline__ void nb_arrive_p(int id) { asm volatile("bar.arrive %0, 160;" ::"r"(id) : "memory"); }
__device__ __forceinline__ void nb_sync_p(int id) { asm volatile("bar.sync %0, 160;" ::"r"(id) : "memory"); }
__device__ __forceinline__ void fence_proxy_async() { asm volatile("fence.proxy.async.shared::cta;" ::: "memory"); }

__device__ __forceinline__ void tma_load_5d(uint32_t dst, const CUtensorMap* map, uint32_t bar, int c0, int c1, int c2,
                                            int c3, int c4) {
  asm volatile(
      "cp.async.bulk.tensor.5d.shared::cluster.global.tile.mbarrier::complete_tx::bytes "
      "[%0], [%1, {%3, %4, %5, %6, %7}], [%2];"
      ::"r"(dst), "l"((uint64_t)map), "r"(bar), "r"(c0), "r"(c1), "r"(c2), "r"(c3), "r"(c4)
      : "memory");
}
__device__ __forceinline__ void bulk_load(uint32_t dst, const void* src, uint32_t bytes, uint32_t bar) {
  asm volatile("cp.async.bulk.shared::cluster.global.mbarrier::complete_tx::bytes [%0], [%1], %2, [%3];"
               ::"r"(dst), "l"((uint64_t)src), "r"(bytes), "r"(bar)
               : "memory");
}

__device__ __forceinline__ void wg_fence() { asm volatile("wgmma.fence.sync.aligned;" ::: "memory"); }
__device__ __forceinline__ void wg_commit() { asm volatile("wgmma.commit_group.sync.aligned;" ::: "memory"); }
template <int N>
__device__ __forceinline__ void wg_wait() { asm volatile("wgmma.wait_group.sync.aligned %0;" ::"n"(N) : "memory"); }

template <int N>
__device__ __forceinline__ void fence_regs(float (&d)[N]) {
#pragma unroll
  for (int i = 0; i < N; i++) asm volatile("" : "+f"(d[i])::"memory");
}
template <int N>
__device__ __forceinline__ void keep_regs(uint32_t (&d)[N]) {
#pragma unroll
  for (int i = 0; i < N; i++) asm volatile("" : "+r"(d[i])::"memory");
}

__device__ __forceinline__ uint32_t pack_bf16(float lo, float hi) {
  uint32_t d;
  asm("cvt.rn.bf16x2.f32 %0, %1, %2;" : "=r"(d) : "f"(hi), "f"(lo));
  return d;
}
__device__ __forceinline__ float ex2(float x) {
  float y;
  asm("ex2.approx.ftz.f32 %0, %1;" : "=f"(y) : "f"(x));
  return y;
}
__device__ __forceinline__ float rcp_approx(float x) {
  float y;
  asm("rcp.approx.ftz.f32 %0, %1;" : "=f"(y) : "f"(x));
  return y;
}
__device__ __forceinline__ uint4 ldg128_nc(const void* p) {
  uint4 v;
  asm volatile("ld.global.nc.v4.u32 {%0,%1,%2,%3}, [%4];" : "=r"(v.x), "=r"(v.y), "=r"(v.z), "=r"(v.w) : "l"(p));
  return v;
}

__device__ __forceinline__ long long clk64() {
  long long c;
  asm volatile("mov.u64 %0, %clock64;" : "=l"(c)::"memory");
  return c;
}
__device__ __forceinline__ void sched_fence() { while (clk64() < 0) { } }

__device__ __forceinline__ uint64_t make_desc(uint32_t addr, uint32_t lbo, uint32_t sbo, uint32_t mode = 1) {
  return (uint64_t)((addr & 0x3FFFF) >> 4) | ((uint64_t)(lbo >> 4) << 16) | ((uint64_t)(sbo >> 4) << 32) |
         ((uint64_t)mode << 62);
}

template <int OFF, int NN>
__device__ __forceinline__ void wg_m192(float (&d)[NN], uint64_t desc_a, uint64_t desc_b, int scale_d) {
  asm volatile(
      "{\n.reg .pred p;\nsetp.ne.b32 p, %98, 0;\n"
      "wgmma.mma_async.sync.aligned.m64n192k16.f32.bf16.bf16 "
      "{%0,%1,%2,%3,%4,%5,%6,%7,%8,%9,%10,%11,%12,%13,%14,%15,"
      "%16,%17,%18,%19,%20,%21,%22,%23,%24,%25,%26,%27,%28,%29,%30,%31,"
      "%32,%33,%34,%35,%36,%37,%38,%39,%40,%41,%42,%43,%44,%45,%46,%47,"
      "%48,%49,%50,%51,%52,%53,%54,%55,%56,%57,%58,%59,%60,%61,%62,%63,"
      "%64,%65,%66,%67,%68,%69,%70,%71,%72,%73,%74,%75,%76,%77,%78,%79,"
      "%80,%81,%82,%83,%84,%85,%86,%87,%88,%89,%90,%91,%92,%93,%94,%95}, "
      "%96, %97, p, 1, 1, 0, 0;\n}\n"
      : "+f"(d[OFF + 0]), "+f"(d[OFF + 1]), "+f"(d[OFF + 2]), "+f"(d[OFF + 3]), "+f"(d[OFF + 4]), "+f"(d[OFF + 5]),
        "+f"(d[OFF + 6]), "+f"(d[OFF + 7]), "+f"(d[OFF + 8]), "+f"(d[OFF + 9]), "+f"(d[OFF + 10]), "+f"(d[OFF + 11]),
        "+f"(d[OFF + 12]), "+f"(d[OFF + 13]), "+f"(d[OFF + 14]), "+f"(d[OFF + 15]), "+f"(d[OFF + 16]), "+f"(d[OFF + 17]),
        "+f"(d[OFF + 18]), "+f"(d[OFF + 19]), "+f"(d[OFF + 20]), "+f"(d[OFF + 21]), "+f"(d[OFF + 22]), "+f"(d[OFF + 23]),
        "+f"(d[OFF + 24]), "+f"(d[OFF + 25]), "+f"(d[OFF + 26]), "+f"(d[OFF + 27]), "+f"(d[OFF + 28]), "+f"(d[OFF + 29]),
        "+f"(d[OFF + 30]), "+f"(d[OFF + 31]), "+f"(d[OFF + 32]), "+f"(d[OFF + 33]), "+f"(d[OFF + 34]), "+f"(d[OFF + 35]),
        "+f"(d[OFF + 36]), "+f"(d[OFF + 37]), "+f"(d[OFF + 38]), "+f"(d[OFF + 39]), "+f"(d[OFF + 40]), "+f"(d[OFF + 41]),
        "+f"(d[OFF + 42]), "+f"(d[OFF + 43]), "+f"(d[OFF + 44]), "+f"(d[OFF + 45]), "+f"(d[OFF + 46]), "+f"(d[OFF + 47]),
        "+f"(d[OFF + 48]), "+f"(d[OFF + 49]), "+f"(d[OFF + 50]), "+f"(d[OFF + 51]), "+f"(d[OFF + 52]), "+f"(d[OFF + 53]),
        "+f"(d[OFF + 54]), "+f"(d[OFF + 55]), "+f"(d[OFF + 56]), "+f"(d[OFF + 57]), "+f"(d[OFF + 58]), "+f"(d[OFF + 59]),
        "+f"(d[OFF + 60]), "+f"(d[OFF + 61]), "+f"(d[OFF + 62]), "+f"(d[OFF + 63]), "+f"(d[OFF + 64]), "+f"(d[OFF + 65]),
        "+f"(d[OFF + 66]), "+f"(d[OFF + 67]), "+f"(d[OFF + 68]), "+f"(d[OFF + 69]), "+f"(d[OFF + 70]), "+f"(d[OFF + 71]),
        "+f"(d[OFF + 72]), "+f"(d[OFF + 73]), "+f"(d[OFF + 74]), "+f"(d[OFF + 75]), "+f"(d[OFF + 76]), "+f"(d[OFF + 77]),
        "+f"(d[OFF + 78]), "+f"(d[OFF + 79]), "+f"(d[OFF + 80]), "+f"(d[OFF + 81]), "+f"(d[OFF + 82]), "+f"(d[OFF + 83]),
        "+f"(d[OFF + 84]), "+f"(d[OFF + 85]), "+f"(d[OFF + 86]), "+f"(d[OFF + 87]), "+f"(d[OFF + 88]), "+f"(d[OFF + 89]),
        "+f"(d[OFF + 90]), "+f"(d[OFF + 91]), "+f"(d[OFF + 92]), "+f"(d[OFF + 93]), "+f"(d[OFF + 94]), "+f"(d[OFF + 95])
      : "l"(desc_a), "l"(desc_b), "r"(scale_d));
}

template <int OFF, int NN>
__device__ __forceinline__ void wg_m192z(float (&d)[NN], uint64_t desc_a, uint64_t desc_b, int scale_d) {
  asm volatile(
      "{\n.reg .pred p;\nsetp.ne.b32 p, %98, 0;\n"
      "wgmma.mma_async.sync.aligned.m64n192k16.f32.bf16.bf16 "
      "{%0,%1,%2,%3,%4,%5,%6,%7,%8,%9,%10,%11,%12,%13,%14,%15,"
      "%16,%17,%18,%19,%20,%21,%22,%23,%24,%25,%26,%27,%28,%29,%30,%31,"
      "%32,%33,%34,%35,%36,%37,%38,%39,%40,%41,%42,%43,%44,%45,%46,%47,"
      "%48,%49,%50,%51,%52,%53,%54,%55,%56,%57,%58,%59,%60,%61,%62,%63,"
      "%64,%65,%66,%67,%68,%69,%70,%71,%72,%73,%74,%75,%76,%77,%78,%79,"
      "%80,%81,%82,%83,%84,%85,%86,%87,%88,%89,%90,%91,%92,%93,%94,%95}, "
      "%96, %97, p, 1, 1, 0, 0;\n}\n"
      : "=f"(d[OFF + 0]), "=f"(d[OFF + 1]), "=f"(d[OFF + 2]), "=f"(d[OFF + 3]), "=f"(d[OFF + 4]), "=f"(d[OFF + 5]),
        "=f"(d[OFF + 6]), "=f"(d[OFF + 7]), "=f"(d[OFF + 8]), "=f"(d[OFF + 9]), "=f"(d[OFF + 10]), "=f"(d[OFF + 11]),
        "=f"(d[OFF + 12]), "=f"(d[OFF + 13]), "=f"(d[OFF + 14]), "=f"(d[OFF + 15]), "=f"(d[OFF + 16]), "=f"(d[OFF + 17]),
        "=f"(d[OFF + 18]), "=f"(d[OFF + 19]), "=f"(d[OFF + 20]), "=f"(d[OFF + 21]), "=f"(d[OFF + 22]), "=f"(d[OFF + 23]),
        "=f"(d[OFF + 24]), "=f"(d[OFF + 25]), "=f"(d[OFF + 26]), "=f"(d[OFF + 27]), "=f"(d[OFF + 28]), "=f"(d[OFF + 29]),
        "=f"(d[OFF + 30]), "=f"(d[OFF + 31]), "=f"(d[OFF + 32]), "=f"(d[OFF + 33]), "=f"(d[OFF + 34]), "=f"(d[OFF + 35]),
        "=f"(d[OFF + 36]), "=f"(d[OFF + 37]), "=f"(d[OFF + 38]), "=f"(d[OFF + 39]), "=f"(d[OFF + 40]), "=f"(d[OFF + 41]),
        "=f"(d[OFF + 42]), "=f"(d[OFF + 43]), "=f"(d[OFF + 44]), "=f"(d[OFF + 45]), "=f"(d[OFF + 46]), "=f"(d[OFF + 47]),
        "=f"(d[OFF + 48]), "=f"(d[OFF + 49]), "=f"(d[OFF + 50]), "=f"(d[OFF + 51]), "=f"(d[OFF + 52]), "=f"(d[OFF + 53]),
        "=f"(d[OFF + 54]), "=f"(d[OFF + 55]), "=f"(d[OFF + 56]), "=f"(d[OFF + 57]), "=f"(d[OFF + 58]), "=f"(d[OFF + 59]),
        "=f"(d[OFF + 60]), "=f"(d[OFF + 61]), "=f"(d[OFF + 62]), "=f"(d[OFF + 63]), "=f"(d[OFF + 64]), "=f"(d[OFF + 65]),
        "=f"(d[OFF + 66]), "=f"(d[OFF + 67]), "=f"(d[OFF + 68]), "=f"(d[OFF + 69]), "=f"(d[OFF + 70]), "=f"(d[OFF + 71]),
        "=f"(d[OFF + 72]), "=f"(d[OFF + 73]), "=f"(d[OFF + 74]), "=f"(d[OFF + 75]), "=f"(d[OFF + 76]), "=f"(d[OFF + 77]),
        "=f"(d[OFF + 78]), "=f"(d[OFF + 79]), "=f"(d[OFF + 80]), "=f"(d[OFF + 81]), "=f"(d[OFF + 82]), "=f"(d[OFF + 83]),
        "=f"(d[OFF + 84]), "=f"(d[OFF + 85]), "=f"(d[OFF + 86]), "=f"(d[OFF + 87]), "=f"(d[OFF + 88]), "=f"(d[OFF + 89]),
        "=f"(d[OFF + 90]), "=f"(d[OFF + 91]), "=f"(d[OFF + 92]), "=f"(d[OFF + 93]), "=f"(d[OFF + 94]), "=f"(d[OFF + 95])
      : "l"(desc_a), "l"(desc_b), "r"(scale_d));
}

template <int OFF, int NN>
__device__ __forceinline__ void wg_m96t(float (&d)[NN], uint64_t desc_a, uint64_t desc_b, int scale_d) {
  asm volatile(
      "{\n.reg .pred p;\nsetp.ne.b32 p, %50, 0;\n"
      "wgmma.mma_async.sync.aligned.m64n96k16.f32.bf16.bf16 "
      "{%0,%1,%2,%3,%4,%5,%6,%7,%8,%9,%10,%11,%12,%13,%14,%15,"
      "%16,%17,%18,%19,%20,%21,%22,%23,%24,%25,%26,%27,%28,%29,%30,%31,"
      "%32,%33,%34,%35,%36,%37,%38,%39,%40,%41,%42,%43,%44,%45,%46,%47}, "
      "%48, %49, p, 1, 1, 0, 1;\n}\n"
      : "+f"(d[OFF + 0]), "+f"(d[OFF + 1]), "+f"(d[OFF + 2]), "+f"(d[OFF + 3]), "+f"(d[OFF + 4]), "+f"(d[OFF + 5]),
        "+f"(d[OFF + 6]), "+f"(d[OFF + 7]), "+f"(d[OFF + 8]), "+f"(d[OFF + 9]), "+f"(d[OFF + 10]), "+f"(d[OFF + 11]),
        "+f"(d[OFF + 12]), "+f"(d[OFF + 13]), "+f"(d[OFF + 14]), "+f"(d[OFF + 15]), "+f"(d[OFF + 16]), "+f"(d[OFF + 17]),
        "+f"(d[OFF + 18]), "+f"(d[OFF + 19]), "+f"(d[OFF + 20]), "+f"(d[OFF + 21]), "+f"(d[OFF + 22]), "+f"(d[OFF + 23]),
        "+f"(d[OFF + 24]), "+f"(d[OFF + 25]), "+f"(d[OFF + 26]), "+f"(d[OFF + 27]), "+f"(d[OFF + 28]), "+f"(d[OFF + 29]),
        "+f"(d[OFF + 30]), "+f"(d[OFF + 31]), "+f"(d[OFF + 32]), "+f"(d[OFF + 33]), "+f"(d[OFF + 34]), "+f"(d[OFF + 35]),
        "+f"(d[OFF + 36]), "+f"(d[OFF + 37]), "+f"(d[OFF + 38]), "+f"(d[OFF + 39]), "+f"(d[OFF + 40]), "+f"(d[OFF + 41]),
        "+f"(d[OFF + 42]), "+f"(d[OFF + 43]), "+f"(d[OFF + 44]), "+f"(d[OFF + 45]), "+f"(d[OFF + 46]), "+f"(d[OFF + 47])
      : "l"(desc_a), "l"(desc_b), "r"(scale_d));
}

template <int OFF, int NN>
__device__ __forceinline__ void wg_m96tz(float (&d)[NN], uint64_t desc_a, uint64_t desc_b, int scale_d) {
  asm volatile(
      "{\n.reg .pred p;\nsetp.ne.b32 p, %50, 0;\n"
      "wgmma.mma_async.sync.aligned.m64n96k16.f32.bf16.bf16 "
      "{%0,%1,%2,%3,%4,%5,%6,%7,%8,%9,%10,%11,%12,%13,%14,%15,"
      "%16,%17,%18,%19,%20,%21,%22,%23,%24,%25,%26,%27,%28,%29,%30,%31,"
      "%32,%33,%34,%35,%36,%37,%38,%39,%40,%41,%42,%43,%44,%45,%46,%47}, "
      "%48, %49, p, 1, 1, 0, 1;\n}\n"
      : "=f"(d[OFF + 0]), "=f"(d[OFF + 1]), "=f"(d[OFF + 2]), "=f"(d[OFF + 3]), "=f"(d[OFF + 4]), "=f"(d[OFF + 5]),
        "=f"(d[OFF + 6]), "=f"(d[OFF + 7]), "=f"(d[OFF + 8]), "=f"(d[OFF + 9]), "=f"(d[OFF + 10]), "=f"(d[OFF + 11]),
        "=f"(d[OFF + 12]), "=f"(d[OFF + 13]), "=f"(d[OFF + 14]), "=f"(d[OFF + 15]), "=f"(d[OFF + 16]), "=f"(d[OFF + 17]),
        "=f"(d[OFF + 18]), "=f"(d[OFF + 19]), "=f"(d[OFF + 20]), "=f"(d[OFF + 21]), "=f"(d[OFF + 22]), "=f"(d[OFF + 23]),
        "=f"(d[OFF + 24]), "=f"(d[OFF + 25]), "=f"(d[OFF + 26]), "=f"(d[OFF + 27]), "=f"(d[OFF + 28]), "=f"(d[OFF + 29]),
        "=f"(d[OFF + 30]), "=f"(d[OFF + 31]), "=f"(d[OFF + 32]), "=f"(d[OFF + 33]), "=f"(d[OFF + 34]), "=f"(d[OFF + 35]),
        "=f"(d[OFF + 36]), "=f"(d[OFF + 37]), "=f"(d[OFF + 38]), "=f"(d[OFF + 39]), "=f"(d[OFF + 40]), "=f"(d[OFF + 41]),
        "=f"(d[OFF + 42]), "=f"(d[OFF + 43]), "=f"(d[OFF + 44]), "=f"(d[OFF + 45]), "=f"(d[OFF + 46]), "=f"(d[OFF + 47])
      : "l"(desc_a), "l"(desc_b), "r"(scale_d));
}

template <int OFF, int NN>
__device__ __forceinline__ void wg_d96(float (&d)[NN], uint32_t a0, uint32_t a1, uint32_t a2, uint32_t a3,
                                       uint64_t desc_b, int scale_d) {
  asm volatile(
      "{\n.reg .pred p;\nsetp.ne.b32 p, %53, 0;\n"
      "wgmma.mma_async.sync.aligned.m64n96k16.f32.bf16.bf16 "
      "{%0,%1,%2,%3,%4,%5,%6,%7,%8,%9,%10,%11,%12,%13,%14,%15,"
      "%16,%17,%18,%19,%20,%21,%22,%23,%24,%25,%26,%27,%28,%29,%30,%31,"
      "%32,%33,%34,%35,%36,%37,%38,%39,%40,%41,%42,%43,%44,%45,%46,%47}, "
      "{%48,%49,%50,%51}, %52, p, 1, 1, 0;\n}\n"
      : "+f"(d[OFF + 0]), "+f"(d[OFF + 1]), "+f"(d[OFF + 2]), "+f"(d[OFF + 3]), "+f"(d[OFF + 4]), "+f"(d[OFF + 5]),
        "+f"(d[OFF + 6]), "+f"(d[OFF + 7]), "+f"(d[OFF + 8]), "+f"(d[OFF + 9]), "+f"(d[OFF + 10]), "+f"(d[OFF + 11]),
        "+f"(d[OFF + 12]), "+f"(d[OFF + 13]), "+f"(d[OFF + 14]), "+f"(d[OFF + 15]), "+f"(d[OFF + 16]), "+f"(d[OFF + 17]),
        "+f"(d[OFF + 18]), "+f"(d[OFF + 19]), "+f"(d[OFF + 20]), "+f"(d[OFF + 21]), "+f"(d[OFF + 22]), "+f"(d[OFF + 23]),
        "+f"(d[OFF + 24]), "+f"(d[OFF + 25]), "+f"(d[OFF + 26]), "+f"(d[OFF + 27]), "+f"(d[OFF + 28]), "+f"(d[OFF + 29]),
        "+f"(d[OFF + 30]), "+f"(d[OFF + 31]), "+f"(d[OFF + 32]), "+f"(d[OFF + 33]), "+f"(d[OFF + 34]), "+f"(d[OFF + 35]),
        "+f"(d[OFF + 36]), "+f"(d[OFF + 37]), "+f"(d[OFF + 38]), "+f"(d[OFF + 39]), "+f"(d[OFF + 40]), "+f"(d[OFF + 41]),
        "+f"(d[OFF + 42]), "+f"(d[OFF + 43]), "+f"(d[OFF + 44]), "+f"(d[OFF + 45]), "+f"(d[OFF + 46]), "+f"(d[OFF + 47])
      : "r"(a0), "r"(a1), "r"(a2), "r"(a3), "l"(desc_b), "r"(scale_d));
}

template <int OFF, int NN>
__device__ __forceinline__ void wg_d96z(float (&d)[NN], uint32_t a0, uint32_t a1, uint32_t a2, uint32_t a3,
                                       uint64_t desc_b, int scale_d) {
  asm volatile(
      "{\n.reg .pred p;\nsetp.ne.b32 p, %53, 0;\n"
      "wgmma.mma_async.sync.aligned.m64n96k16.f32.bf16.bf16 "
      "{%0,%1,%2,%3,%4,%5,%6,%7,%8,%9,%10,%11,%12,%13,%14,%15,"
      "%16,%17,%18,%19,%20,%21,%22,%23,%24,%25,%26,%27,%28,%29,%30,%31,"
      "%32,%33,%34,%35,%36,%37,%38,%39,%40,%41,%42,%43,%44,%45,%46,%47}, "
      "{%48,%49,%50,%51}, %52, p, 1, 1, 0;\n}\n"
      : "=f"(d[OFF + 0]), "=f"(d[OFF + 1]), "=f"(d[OFF + 2]), "=f"(d[OFF + 3]), "=f"(d[OFF + 4]), "=f"(d[OFF + 5]),
        "=f"(d[OFF + 6]), "=f"(d[OFF + 7]), "=f"(d[OFF + 8]), "=f"(d[OFF + 9]), "=f"(d[OFF + 10]), "=f"(d[OFF + 11]),
        "=f"(d[OFF + 12]), "=f"(d[OFF + 13]), "=f"(d[OFF + 14]), "=f"(d[OFF + 15]), "=f"(d[OFF + 16]), "=f"(d[OFF + 17]),
        "=f"(d[OFF + 18]), "=f"(d[OFF + 19]), "=f"(d[OFF + 20]), "=f"(d[OFF + 21]), "=f"(d[OFF + 22]), "=f"(d[OFF + 23]),
        "=f"(d[OFF + 24]), "=f"(d[OFF + 25]), "=f"(d[OFF + 26]), "=f"(d[OFF + 27]), "=f"(d[OFF + 28]), "=f"(d[OFF + 29]),
        "=f"(d[OFF + 30]), "=f"(d[OFF + 31]), "=f"(d[OFF + 32]), "=f"(d[OFF + 33]), "=f"(d[OFF + 34]), "=f"(d[OFF + 35]),
        "=f"(d[OFF + 36]), "=f"(d[OFF + 37]), "=f"(d[OFF + 38]), "=f"(d[OFF + 39]), "=f"(d[OFF + 40]), "=f"(d[OFF + 41]),
        "=f"(d[OFF + 42]), "=f"(d[OFF + 43]), "=f"(d[OFF + 44]), "=f"(d[OFF + 45]), "=f"(d[OFF + 46]), "=f"(d[OFF + 47])
      : "r"(a0), "r"(a1), "r"(a2), "r"(a3), "l"(desc_b), "r"(scale_d));
}

template <int OFF, int NN>
__device__ __forceinline__ void wg_s104(float (&d)[NN], uint32_t a0, uint32_t a1, uint32_t a2, uint32_t a3,
                                       uint64_t desc_b, int scale_d, uint32_t meta) {
  asm volatile(
      "{\n.reg .pred p;\nsetp.ne.b32 p, %57, 0;\n"
      "wgmma.mma_async.sp.sync.aligned.m64n104k32.f32.bf16.bf16 "
      "{%0,%1,%2,%3,%4,%5,%6,%7,%8,%9,%10,%11,%12,%13,%14,%15,"
      "%16,%17,%18,%19,%20,%21,%22,%23,%24,%25,%26,%27,%28,%29,%30,%31,"
      "%32,%33,%34,%35,%36,%37,%38,%39,%40,%41,%42,%43,%44,%45,%46,%47,"
      "%48,%49,%50,%51}, "
      "{%52,%53,%54,%55}, %56, %58, 0, p, 1, 1, 0;\n}\n"
      : "+f"(d[OFF + 0]), "+f"(d[OFF + 1]), "+f"(d[OFF + 2]), "+f"(d[OFF + 3]), "+f"(d[OFF + 4]), "+f"(d[OFF + 5]),
        "+f"(d[OFF + 6]), "+f"(d[OFF + 7]), "+f"(d[OFF + 8]), "+f"(d[OFF + 9]), "+f"(d[OFF + 10]), "+f"(d[OFF + 11]),
        "+f"(d[OFF + 12]), "+f"(d[OFF + 13]), "+f"(d[OFF + 14]), "+f"(d[OFF + 15]), "+f"(d[OFF + 16]), "+f"(d[OFF + 17]),
        "+f"(d[OFF + 18]), "+f"(d[OFF + 19]), "+f"(d[OFF + 20]), "+f"(d[OFF + 21]), "+f"(d[OFF + 22]), "+f"(d[OFF + 23]),
        "+f"(d[OFF + 24]), "+f"(d[OFF + 25]), "+f"(d[OFF + 26]), "+f"(d[OFF + 27]), "+f"(d[OFF + 28]), "+f"(d[OFF + 29]),
        "+f"(d[OFF + 30]), "+f"(d[OFF + 31]), "+f"(d[OFF + 32]), "+f"(d[OFF + 33]), "+f"(d[OFF + 34]), "+f"(d[OFF + 35]),
        "+f"(d[OFF + 36]), "+f"(d[OFF + 37]), "+f"(d[OFF + 38]), "+f"(d[OFF + 39]), "+f"(d[OFF + 40]), "+f"(d[OFF + 41]),
        "+f"(d[OFF + 42]), "+f"(d[OFF + 43]), "+f"(d[OFF + 44]), "+f"(d[OFF + 45]), "+f"(d[OFF + 46]), "+f"(d[OFF + 47]),
        "+f"(d[OFF + 48]), "+f"(d[OFF + 49]), "+f"(d[OFF + 50]), "+f"(d[OFF + 51])
      : "r"(a0), "r"(a1), "r"(a2), "r"(a3), "l"(desc_b), "r"(scale_d), "r"(meta));
}

template <int OFF, int NN>
__device__ __forceinline__ void wg_s104z(float (&d)[NN], uint32_t a0, uint32_t a1, uint32_t a2, uint32_t a3,
                                       uint64_t desc_b, int scale_d, uint32_t meta) {
  asm volatile(
      "{\n.reg .pred p;\nsetp.ne.b32 p, %57, 0;\n"
      "wgmma.mma_async.sp.sync.aligned.m64n104k32.f32.bf16.bf16 "
      "{%0,%1,%2,%3,%4,%5,%6,%7,%8,%9,%10,%11,%12,%13,%14,%15,"
      "%16,%17,%18,%19,%20,%21,%22,%23,%24,%25,%26,%27,%28,%29,%30,%31,"
      "%32,%33,%34,%35,%36,%37,%38,%39,%40,%41,%42,%43,%44,%45,%46,%47,"
      "%48,%49,%50,%51}, "
      "{%52,%53,%54,%55}, %56, %58, 0, p, 1, 1, 0;\n}\n"
      : "=f"(d[OFF + 0]), "=f"(d[OFF + 1]), "=f"(d[OFF + 2]), "=f"(d[OFF + 3]), "=f"(d[OFF + 4]), "=f"(d[OFF + 5]),
        "=f"(d[OFF + 6]), "=f"(d[OFF + 7]), "=f"(d[OFF + 8]), "=f"(d[OFF + 9]), "=f"(d[OFF + 10]), "=f"(d[OFF + 11]),
        "=f"(d[OFF + 12]), "=f"(d[OFF + 13]), "=f"(d[OFF + 14]), "=f"(d[OFF + 15]), "=f"(d[OFF + 16]), "=f"(d[OFF + 17]),
        "=f"(d[OFF + 18]), "=f"(d[OFF + 19]), "=f"(d[OFF + 20]), "=f"(d[OFF + 21]), "=f"(d[OFF + 22]), "=f"(d[OFF + 23]),
        "=f"(d[OFF + 24]), "=f"(d[OFF + 25]), "=f"(d[OFF + 26]), "=f"(d[OFF + 27]), "=f"(d[OFF + 28]), "=f"(d[OFF + 29]),
        "=f"(d[OFF + 30]), "=f"(d[OFF + 31]), "=f"(d[OFF + 32]), "=f"(d[OFF + 33]), "=f"(d[OFF + 34]), "=f"(d[OFF + 35]),
        "=f"(d[OFF + 36]), "=f"(d[OFF + 37]), "=f"(d[OFF + 38]), "=f"(d[OFF + 39]), "=f"(d[OFF + 40]), "=f"(d[OFF + 41]),
        "=f"(d[OFF + 42]), "=f"(d[OFF + 43]), "=f"(d[OFF + 44]), "=f"(d[OFF + 45]), "=f"(d[OFF + 46]), "=f"(d[OFF + 47]),
        "=f"(d[OFF + 48]), "=f"(d[OFF + 49]), "=f"(d[OFF + 50]), "=f"(d[OFF + 51])
      : "r"(a0), "r"(a1), "r"(a2), "r"(a3), "l"(desc_b), "r"(scale_d), "r"(meta));
}

template <int OFF, int NN>
__device__ __forceinline__ void wg_s48(float (&d)[NN], uint32_t a0, uint32_t a1, uint32_t a2, uint32_t a3,
                                       uint64_t desc_b, int scale_d, uint32_t meta) {
  asm volatile(
      "{\n.reg .pred p;\nsetp.ne.b32 p, %29, 0;\n"
      "wgmma.mma_async.sp.sync.aligned.m64n48k32.f32.bf16.bf16 "
      "{%0,%1,%2,%3,%4,%5,%6,%7,%8,%9,%10,%11,%12,%13,%14,%15,"
      "%16,%17,%18,%19,%20,%21,%22,%23}, "
      "{%24,%25,%26,%27}, %28, %30, 0, p, 1, 1, 0;\n}\n"
      : "+f"(d[OFF + 0]), "+f"(d[OFF + 1]), "+f"(d[OFF + 2]), "+f"(d[OFF + 3]), "+f"(d[OFF + 4]), "+f"(d[OFF + 5]),
        "+f"(d[OFF + 6]), "+f"(d[OFF + 7]), "+f"(d[OFF + 8]), "+f"(d[OFF + 9]), "+f"(d[OFF + 10]), "+f"(d[OFF + 11]),
        "+f"(d[OFF + 12]), "+f"(d[OFF + 13]), "+f"(d[OFF + 14]), "+f"(d[OFF + 15]), "+f"(d[OFF + 16]), "+f"(d[OFF + 17]),
        "+f"(d[OFF + 18]), "+f"(d[OFF + 19]), "+f"(d[OFF + 20]), "+f"(d[OFF + 21]), "+f"(d[OFF + 22]), "+f"(d[OFF + 23])
      : "r"(a0), "r"(a1), "r"(a2), "r"(a3), "l"(desc_b), "r"(scale_d), "r"(meta));
}

template <int OFF, int NN>
__device__ __forceinline__ void wg_s48z(float (&d)[NN], uint32_t a0, uint32_t a1, uint32_t a2, uint32_t a3,
                                       uint64_t desc_b, int scale_d, uint32_t meta) {
  asm volatile(
      "{\n.reg .pred p;\nsetp.ne.b32 p, %29, 0;\n"
      "wgmma.mma_async.sp.sync.aligned.m64n48k32.f32.bf16.bf16 "
      "{%0,%1,%2,%3,%4,%5,%6,%7,%8,%9,%10,%11,%12,%13,%14,%15,"
      "%16,%17,%18,%19,%20,%21,%22,%23}, "
      "{%24,%25,%26,%27}, %28, %30, 0, p, 1, 1, 0;\n}\n"
      : "=f"(d[OFF + 0]), "=f"(d[OFF + 1]), "=f"(d[OFF + 2]), "=f"(d[OFF + 3]), "=f"(d[OFF + 4]), "=f"(d[OFF + 5]),
        "=f"(d[OFF + 6]), "=f"(d[OFF + 7]), "=f"(d[OFF + 8]), "=f"(d[OFF + 9]), "=f"(d[OFF + 10]), "=f"(d[OFF + 11]),
        "=f"(d[OFF + 12]), "=f"(d[OFF + 13]), "=f"(d[OFF + 14]), "=f"(d[OFF + 15]), "=f"(d[OFF + 16]), "=f"(d[OFF + 17]),
        "=f"(d[OFF + 18]), "=f"(d[OFF + 19]), "=f"(d[OFF + 20]), "=f"(d[OFF + 21]), "=f"(d[OFF + 22]), "=f"(d[OFF + 23])
      : "r"(a0), "r"(a1), "r"(a2), "r"(a3), "l"(desc_b), "r"(scale_d), "r"(meta));
}

template <int OFF, int NN>
__device__ __forceinline__ void wg_s56(float (&d)[NN], uint32_t a0, uint32_t a1, uint32_t a2, uint32_t a3,
                                       uint64_t desc_b, int scale_d, uint32_t meta) {
  asm volatile(
      "{\n.reg .pred p;\nsetp.ne.b32 p, %33, 0;\n"
      "wgmma.mma_async.sp.sync.aligned.m64n56k32.f32.bf16.bf16 "
      "{%0,%1,%2,%3,%4,%5,%6,%7,%8,%9,%10,%11,%12,%13,%14,%15,"
      "%16,%17,%18,%19,%20,%21,%22,%23,%24,%25,%26,%27}, "
      "{%28,%29,%30,%31}, %32, %34, 0, p, 1, 1, 0;\n}\n"
      : "+f"(d[OFF + 0]), "+f"(d[OFF + 1]), "+f"(d[OFF + 2]), "+f"(d[OFF + 3]), "+f"(d[OFF + 4]), "+f"(d[OFF + 5]),
        "+f"(d[OFF + 6]), "+f"(d[OFF + 7]), "+f"(d[OFF + 8]), "+f"(d[OFF + 9]), "+f"(d[OFF + 10]), "+f"(d[OFF + 11]),
        "+f"(d[OFF + 12]), "+f"(d[OFF + 13]), "+f"(d[OFF + 14]), "+f"(d[OFF + 15]), "+f"(d[OFF + 16]), "+f"(d[OFF + 17]),
        "+f"(d[OFF + 18]), "+f"(d[OFF + 19]), "+f"(d[OFF + 20]), "+f"(d[OFF + 21]), "+f"(d[OFF + 22]), "+f"(d[OFF + 23]),
        "+f"(d[OFF + 24]), "+f"(d[OFF + 25]), "+f"(d[OFF + 26]), "+f"(d[OFF + 27])
      : "r"(a0), "r"(a1), "r"(a2), "r"(a3), "l"(desc_b), "r"(scale_d), "r"(meta));
}

template <int OFF, int NN>
__device__ __forceinline__ void wg_s56z(float (&d)[NN], uint32_t a0, uint32_t a1, uint32_t a2, uint32_t a3,
                                       uint64_t desc_b, int scale_d, uint32_t meta) {
  asm volatile(
      "{\n.reg .pred p;\nsetp.ne.b32 p, %33, 0;\n"
      "wgmma.mma_async.sp.sync.aligned.m64n56k32.f32.bf16.bf16 "
      "{%0,%1,%2,%3,%4,%5,%6,%7,%8,%9,%10,%11,%12,%13,%14,%15,"
      "%16,%17,%18,%19,%20,%21,%22,%23,%24,%25,%26,%27}, "
      "{%28,%29,%30,%31}, %32, %34, 0, p, 1, 1, 0;\n}\n"
      : "=f"(d[OFF + 0]), "=f"(d[OFF + 1]), "=f"(d[OFF + 2]), "=f"(d[OFF + 3]), "=f"(d[OFF + 4]), "=f"(d[OFF + 5]),
        "=f"(d[OFF + 6]), "=f"(d[OFF + 7]), "=f"(d[OFF + 8]), "=f"(d[OFF + 9]), "=f"(d[OFF + 10]), "=f"(d[OFF + 11]),
        "=f"(d[OFF + 12]), "=f"(d[OFF + 13]), "=f"(d[OFF + 14]), "=f"(d[OFF + 15]), "=f"(d[OFF + 16]), "=f"(d[OFF + 17]),
        "=f"(d[OFF + 18]), "=f"(d[OFF + 19]), "=f"(d[OFF + 20]), "=f"(d[OFF + 21]), "=f"(d[OFF + 22]), "=f"(d[OFF + 23]),
        "=f"(d[OFF + 24]), "=f"(d[OFF + 25]), "=f"(d[OFF + 26]), "=f"(d[OFF + 27])
      : "r"(a0), "r"(a1), "r"(a2), "r"(a3), "l"(desc_b), "r"(scale_d), "r"(meta));
}

template <int OFF, int NN>
__device__ __forceinline__ void wg_s64t(float (&d)[NN], uint32_t a0, uint32_t a1, uint32_t a2, uint32_t a3,
                                       uint64_t desc_b, int scale_d, uint32_t meta) {
  asm volatile(
      "{\n.reg .pred p;\nsetp.ne.b32 p, %37, 0;\n"
      "wgmma.mma_async.sp.sync.aligned.m64n64k32.f32.bf16.bf16 "
      "{%0,%1,%2,%3,%4,%5,%6,%7,%8,%9,%10,%11,%12,%13,%14,%15,"
      "%16,%17,%18,%19,%20,%21,%22,%23,%24,%25,%26,%27,%28,%29,%30,%31}, "
      "{%32,%33,%34,%35}, %36, %38, 0, p, 1, 1, 1;\n}\n"
      : "+f"(d[OFF + 0]), "+f"(d[OFF + 1]), "+f"(d[OFF + 2]), "+f"(d[OFF + 3]), "+f"(d[OFF + 4]), "+f"(d[OFF + 5]),
        "+f"(d[OFF + 6]), "+f"(d[OFF + 7]), "+f"(d[OFF + 8]), "+f"(d[OFF + 9]), "+f"(d[OFF + 10]), "+f"(d[OFF + 11]),
        "+f"(d[OFF + 12]), "+f"(d[OFF + 13]), "+f"(d[OFF + 14]), "+f"(d[OFF + 15]), "+f"(d[OFF + 16]), "+f"(d[OFF + 17]),
        "+f"(d[OFF + 18]), "+f"(d[OFF + 19]), "+f"(d[OFF + 20]), "+f"(d[OFF + 21]), "+f"(d[OFF + 22]), "+f"(d[OFF + 23]),
        "+f"(d[OFF + 24]), "+f"(d[OFF + 25]), "+f"(d[OFF + 26]), "+f"(d[OFF + 27]), "+f"(d[OFF + 28]), "+f"(d[OFF + 29]),
        "+f"(d[OFF + 30]), "+f"(d[OFF + 31])
      : "r"(a0), "r"(a1), "r"(a2), "r"(a3), "l"(desc_b), "r"(scale_d), "r"(meta));
}

template <int OFF, int NN>
__device__ __forceinline__ void wg_s64t1(float (&d)[NN], uint32_t a0, uint32_t a1, uint32_t a2, uint32_t a3,
                                       uint64_t desc_b, int scale_d, uint32_t meta) {
  asm volatile(
      "{\n.reg .pred p;\nsetp.ne.b32 p, %37, 0;\n"
      "wgmma.mma_async.sp.sync.aligned.m64n64k32.f32.bf16.bf16 "
      "{%0,%1,%2,%3,%4,%5,%6,%7,%8,%9,%10,%11,%12,%13,%14,%15,"
      "%16,%17,%18,%19,%20,%21,%22,%23,%24,%25,%26,%27,%28,%29,%30,%31}, "
      "{%32,%33,%34,%35}, %36, %38, 1, p, 1, 1, 1;\n}\n"
      : "+f"(d[OFF + 0]), "+f"(d[OFF + 1]), "+f"(d[OFF + 2]), "+f"(d[OFF + 3]), "+f"(d[OFF + 4]), "+f"(d[OFF + 5]),
        "+f"(d[OFF + 6]), "+f"(d[OFF + 7]), "+f"(d[OFF + 8]), "+f"(d[OFF + 9]), "+f"(d[OFF + 10]), "+f"(d[OFF + 11]),
        "+f"(d[OFF + 12]), "+f"(d[OFF + 13]), "+f"(d[OFF + 14]), "+f"(d[OFF + 15]), "+f"(d[OFF + 16]), "+f"(d[OFF + 17]),
        "+f"(d[OFF + 18]), "+f"(d[OFF + 19]), "+f"(d[OFF + 20]), "+f"(d[OFF + 21]), "+f"(d[OFF + 22]), "+f"(d[OFF + 23]),
        "+f"(d[OFF + 24]), "+f"(d[OFF + 25]), "+f"(d[OFF + 26]), "+f"(d[OFF + 27]), "+f"(d[OFF + 28]), "+f"(d[OFF + 29]),
        "+f"(d[OFF + 30]), "+f"(d[OFF + 31])
      : "r"(a0), "r"(a1), "r"(a2), "r"(a3), "l"(desc_b), "r"(scale_d), "r"(meta));
}

template <int OFF, int NN>
__device__ __forceinline__ void wg_s64tz(float (&d)[NN], uint32_t a0, uint32_t a1, uint32_t a2, uint32_t a3,
                                       uint64_t desc_b, int scale_d, uint32_t meta) {
  asm volatile(
      "{\n.reg .pred p;\nsetp.ne.b32 p, %37, 0;\n"
      "wgmma.mma_async.sp.sync.aligned.m64n64k32.f32.bf16.bf16 "
      "{%0,%1,%2,%3,%4,%5,%6,%7,%8,%9,%10,%11,%12,%13,%14,%15,"
      "%16,%17,%18,%19,%20,%21,%22,%23,%24,%25,%26,%27,%28,%29,%30,%31}, "
      "{%32,%33,%34,%35}, %36, %38, 0, p, 1, 1, 1;\n}\n"
      : "=f"(d[OFF + 0]), "=f"(d[OFF + 1]), "=f"(d[OFF + 2]), "=f"(d[OFF + 3]), "=f"(d[OFF + 4]), "=f"(d[OFF + 5]),
        "=f"(d[OFF + 6]), "=f"(d[OFF + 7]), "=f"(d[OFF + 8]), "=f"(d[OFF + 9]), "=f"(d[OFF + 10]), "=f"(d[OFF + 11]),
        "=f"(d[OFF + 12]), "=f"(d[OFF + 13]), "=f"(d[OFF + 14]), "=f"(d[OFF + 15]), "=f"(d[OFF + 16]), "=f"(d[OFF + 17]),
        "=f"(d[OFF + 18]), "=f"(d[OFF + 19]), "=f"(d[OFF + 20]), "=f"(d[OFF + 21]), "=f"(d[OFF + 22]), "=f"(d[OFF + 23]),
        "=f"(d[OFF + 24]), "=f"(d[OFF + 25]), "=f"(d[OFF + 26]), "=f"(d[OFF + 27]), "=f"(d[OFF + 28]), "=f"(d[OFF + 29]),
        "=f"(d[OFF + 30]), "=f"(d[OFF + 31])
      : "r"(a0), "r"(a1), "r"(a2), "r"(a3), "l"(desc_b), "r"(scale_d), "r"(meta));
}

__device__ __forceinline__ int g2_inv(int ch) { return 32 * (ch >> 5) + 8 * ((ch >> 1) & 3) + 2 * ((ch >> 3) & 3) + (ch & 1); }
__host__ __device__ __forceinline__ uint32_t wimg_off(int n, int k) {
  return (uint32_t)(k >> 6) * kWChunk + (uint32_t)n * 128 + (uint32_t)((((k & 63) >> 3) ^ (n & 7)) << 4) + (k & 7) * 2;
}
__host__ __device__ constexpr int w2piece(int h, int c) { return c == 2 ? 2 + h : 4 * h + c; }
__device__ __forceinline__ uint32_t w2img_off(int n, int k) { return wimg_off(n % 96, k & 63) + w2piece(n >= 96, k >> 6) * (kWChunk / 2); }
__device__ __forceinline__ int qpix(int par, int t) {
  const int a = 2 * t + 13 * par - 6, b = t + 112 * par;
  return par ? min(a, b) : max(a, b);
}
__device__ __forceinline__ int woff(int par, int i, int r) {
  const int a = 99 * par + 6 - 8 * i;
  return par ? min(r, a) : max(r, a);
}

__device__ __forceinline__ void mma16816(float (&c)[4], uint32_t a0, uint32_t a1, uint32_t a2, uint32_t a3, uint32_t b0,
                                         uint32_t b1) {
  asm volatile(
      "mma.sync.aligned.m16n8k16.row.col.f32.bf16.bf16.f32 {%0,%1,%2,%3}, {%4,%5,%6,%7}, {%8,%9}, {%0,%1,%2,%3};"
      : "+f"(c[0]), "+f"(c[1]), "+f"(c[2]), "+f"(c[3])
      : "r"(a0), "r"(a1), "r"(a2), "r"(a3), "r"(b0), "r"(b1));
}

__device__ __forceinline__ void fold_w1(const int u, const __nv_bfloat16* __restrict__ wqkv, uint8_t* wimg) {
  const int g = (threadIdx.x >> 2) & 7, l = threadIdx.x & 3;
  const int m0 = (u / 12) * 16, s = u % 12;
  uint4 A[12], B[12];
  const __nv_bfloat16* arow = wqkv + (m0 + 4 * (g >> 1) + (g & 1)) * 576 + 192 + 8 * l;
  const __nv_bfloat16* brow = wqkv + (16 * s + 4 * (g >> 1) + (g & 1)) * 576 + 8 * l;
#pragma unroll
  for (int i = 0; i < 12; i++) {
    A[i] = ldg128_nc(arow + (i & 1) * 2 * 576 + 32 * (i >> 1));
    B[i] = ldg128_nc(brow + (i & 1) * 2 * 576 + 32 * (i >> 1));
  }
  sched_fence();
  uint8_t* dst = wimg + wimg_off(m0 + g, 16 * s + 4 * l);
  float acc[4][4];
#pragma unroll
  for (int j = 0; j < 16; j++) acc[j >> 2][j & 3] = 0.f;
#pragma unroll
  for (int i = 0; i < 6; i++) {
    const uint4 &a0 = A[2 * i], &a1 = A[2 * i + 1];
#pragma unroll
    for (int nb = 0; nb < 2; nb++) {
      mma16816(acc[2 * nb], a0.x, a1.x, a0.y, a1.y, B[2 * i + nb].x, B[2 * i + nb].y);
      mma16816(acc[2 * nb + 1], a0.z, a1.z, a0.w, a1.w, B[2 * i + nb].z, B[2 * i + nb].w);
    }
  }
#pragma unroll
  for (int j = 0; j < 2; j++) {
    const uint2 v = make_uint2(pack_bf16((acc[0][2 * j] + acc[1][2 * j]) * kAlpha, (acc[0][2 * j + 1] + acc[1][2 * j + 1]) * kAlpha),
                               pack_bf16((acc[2][2 * j] + acc[3][2 * j]) * kAlpha, (acc[2][2 * j + 1] + acc[3][2 * j + 1]) * kAlpha));
    asm volatile("st.relaxed.gpu.global.v2.u32 [%0], {%1,%2};" ::"l"(dst + j * 1024), "r"(v.x), "r"(v.y) : "memory");
  }
}
__device__ __forceinline__ void fold_w2(const int u, const __nv_bfloat16* __restrict__ wqkv, const __nv_bfloat16* __restrict__ wo,
                                        uint8_t* wimg) {
  const int g = (threadIdx.x >> 2) & 7, l = threadIdx.x & 3;
  const int m0 = (u / 12) * 32, n0 = (u % 12) * 16;
  uint4 S[12];
  uint32_t L[96];
  const __nv_bfloat16* brow = wqkv + (n0 + 4 * (g >> 1) + (g & 1)) * 576 + 384 + 8 * l;
#pragma unroll
  for (int i = 0; i < 12; i++) S[i] = ldg128_nc(brow + (i & 1) * 2 * 576 + 32 * (i >> 1));
  const __nv_bfloat16* acol = wo + (8 * l) * 192 + m0 + 4 * g;
#pragma unroll
  for (int c = 0; c < 48; c++)
    asm volatile("ld.global.nc.v2.u32 {%0,%1}, [%2];" : "=r"(L[2 * c]), "=r"(L[2 * c + 1]) : "l"(acol + (32 * (c >> 3) + (c & 7)) * 192));
  const uint32_t off = w2_offset();
  sched_fence();
  uint8_t* img = wimg + off;
  float acc[4][4];
#pragma unroll
  for (int j = 0; j < 16; j++) acc[j >> 2][j & 3] = 0.f;
#pragma unroll
  for (int i = 0; i < 6; i++) {
#pragma unroll
    for (int h = 0; h < 2; h++) {
      const uint4 &s0 = S[2 * i], &s1 = S[2 * i + 1];
#pragma unroll
      for (int mt = 0; mt < 2; mt++) {
        const uint32_t* a = L + 16 * i + 8 * h + mt;
        const uint32_t a0 = __byte_perm(a[0], a[2], 0x5410), a1 = __byte_perm(a[0], a[2], 0x7632);
        const uint32_t a2 = __byte_perm(a[4], a[6], 0x5410), a3 = __byte_perm(a[4], a[6], 0x7632);
        mma16816(acc[2 * mt], a0, a1, a2, a3, h ? s0.z : s0.x, h ? s0.w : s0.y);
        mma16816(acc[2 * mt + 1], a0, a1, a2, a3, h ? s1.z : s1.x, h ? s1.w : s1.y);
      }
    }
  }
#pragma unroll
  for (int j = 0; j < 4; j++) {
    const float(&c0)[4] = acc[j & 2];
    const float(&c1)[4] = acc[(j & 2) + 1];
    asm volatile("st.relaxed.gpu.global.v2.u32 [%0], {%1,%2};" ::"l"(img + w2img_off(g2_inv(m0 + 4 * g + j), n0 + 4 * l)),
                 "r"(pack_bf16(c0[2 * (j & 1)], c0[2 * (j & 1) + 1])), "r"(pack_bf16(c1[2 * (j & 1)], c1[2 * (j & 1) + 1])) : "memory");
  }
}

__global__ void __launch_bounds__(256) fold_kernel(const __nv_bfloat16* __restrict__ wqkv,
                                                   const __nv_bfloat16* __restrict__ wo, uint8_t* wimg) {
  const int u = blockIdx.x * 8 + (threadIdx.x >> 5);
  if (u < 144) fold_w1(u, wqkv, wimg);
  else fold_w2(u - 144, wqkv, wo, wimg);
}

struct TileCoord { int pr, pc, I, J, up, kind; };
struct TileTable { uint16_t e[kCtas * 6], g[5][8][2], b[5][2][4]; };
inline void make_tiles(TileTable& tt) {
  for (int tile = 0; tile < kCtas * 6; tile++) {
    const int b = tile / 6, k = tile - 6 * b;
    const int p = b < 128 ? (tile - 672) >> 1 : b - 80;
    const int strip = b < 112 ? b >> 1 : b >= 128 && k >= 2 ? (b & 1) * 27 + (b & 2) * 14 : p + (p < 26 ? 1 : 3);
    const int pr = strip >= 28, J = (strip - pr * 28) >> 1, pc = strip & 1, up = b < 112 ? b & 1 : pr;
    const int first = b < 112 ? 8 - 2 * pr - up : 13 * pr, step = b < 112 ? k : k & 1;
    const int I = up ? first - step : first + step;
    const int kind = I == 13 * pr ? 3 + pr : J == 13 * pc ? 1 + pc : 0;
    tt.e[tile] = (uint16_t)(I | J << 4 | pr << 8 | pc << 9 | up << 10 | kind << 11);
  }
  for (int kind = 0; kind < 5; kind++) {
    const bool col = kind == 1 || kind == 2;
    auto off = [kind](int t) { return kind == 0 ? 2 * t : kind & 1 ? t + (t == 7) : t + (t > 0); };
    for (int j = 0; j < 8; j++) {
      const int w = j >> 1, h = j & 1;
      tt.g[kind][j][0] = (uint16_t)(col ? 3 * off(w + 4 * h) : 3 * (kW * off(2 * w) + 8 * h));
      tt.g[kind][j][1] = (uint16_t)(128 * (col ? 5 : 5 + off(2 * w + 1) - off(2 * w)));
    }
    for (int i = 0; i < 2; i++) {
      const int w = kind == 0 ? 0 : kind & 1 ? 3 * i : 1 - i;
      tt.b[kind][i][0] = tt.g[kind][2 * w][0];
      tt.b[kind][i][1] = (uint16_t)(128 * (kind == 0 ? 0 : (col ? 3 : 1) + i));
      tt.b[kind][i][2] = (uint16_t)(2048 * w);
      tt.b[kind][i][3] = 0;
    }
  }
}
__device__ __forceinline__ int num_tiles() { return blockIdx.x < 128 ? 6 : 4; }
__device__ __forceinline__ TileCoord decode_tile(const TileTable& tt, int tile) {
  const uint32_t e = tt.e[tile];
  return TileCoord{(int)(e >> 8) & 1, (int)(e >> 9) & 1, (int)e & 15, (int)(e >> 4) & 15, (int)(e >> 10) & 1, (int)(e >> 11)};
}
__device__ __forceinline__ int halo_r0(const TileCoord& t) { return 8 * t.I + 6 * t.pr - 6; }
__device__ __forceinline__ int halo_c0(const TileCoord& t) { return min(max(8 * t.J + 6 * t.pc - 6, -3), 102); }

__device__ __forceinline__ uint32_t bar_full(uint32_t bars, int wg, int c) { return bars + (wg * 3 + c) * 8; }
__device__ __forceinline__ uint32_t bar_w1c(uint32_t bars, int c) { return bars + (6 + c) * 8; }
__device__ __forceinline__ uint32_t bar_w2(uint32_t bars) { return bars + 9 * 8; }
__device__ __forceinline__ uint32_t bar_x(uint32_t bars, int j, int c) { return bars + (j == 0 ? 10 : c ? 17 + c : 11) * 8; }
__device__ __forceinline__ uint32_t bar_w1q(uint32_t bars) { return bars + 12 * 8; }
__device__ __forceinline__ uint32_t bar_xf(uint32_t bars) { return bars + 13 * 8; }
__device__ __forceinline__ uint32_t bar_w2m(uint32_t bars) { return bars + 14 * 8; }
__device__ __forceinline__ uint32_t bar_redo(uint32_t bars) { return bars + 15 * 8; }
__device__ __forceinline__ uint32_t bar_wok(uint32_t bars) { return bars + 16 * 8; }
__device__ __forceinline__ uint32_t bar_go(uint32_t bars) { return bars + 17 * 8; }
__device__ __forceinline__ uint32_t bar_raw(uint32_t bars, int j = 0) { return bars + (21 + j) * 8; }
__device__ __forceinline__ uint32_t bar_w2a(uint32_t bars) { return bars + 20 * 8; }
constexpr int kNumBars = 22;

__device__ __forceinline__ uint64_t wdesc(uint64_t d0, int s) { return d0 + (((s >> 2) * kWChunk + (s & 3) * 32) >> 4); }

__device__ __forceinline__ uint32_t x_chunk(int k, int c) { return kXOff + (k == 0 ? kWChunk : 0) + (k & 1 ? 2 - c : c) * 8192; }
__device__ __forceinline__ uint32_t out_slot(int k, int nt) { return k + 1 < nt ? kW2Off + (~k & 1) * 2 * kWChunk : kW1Off + kWChunk; }
template <int I0, int I1>
__device__ __forceinline__ void store_rows(bool on, __nv_bfloat16* pA, __nv_bfloat16* pB, const uint32_t (&a)[24], const uint32_t (&b)[24]) {
#pragma unroll
  for (int i = 2 * I0; i < 2 * I1; i++) {
    const uint32_t* v = (i & 1 ? b : a) + 4 * (i >> 1);
    asm volatile("{\n.reg .pred p;\nsetp.ne.u32 p, %5, 0;\n@p st.global.v4.u32 [%0], {%1,%2,%3,%4};\n}\n" ::"l"((i & 1 ? pB : pA) + 32 * (i >> 1)),
                 "r"(v[0]), "r"(v[1]), "r"(v[2]), "r"(v[3]), "r"((uint32_t)on) : "memory");
  }
}
template <int I0, int I1>
__device__ __forceinline__ void stage_out(const uint32_t (&ad)[4], const uint32_t (&a)[24], const uint32_t (&b)[24]) {
#pragma unroll
  for (int i = I0; i < I1; i++) {
    const uint32_t* v = (i < 6 ? a : b) + 4 * (i % 6);
    asm volatile("st.shared.v4.u32 [%0], {%1,%2,%3,%4};" ::"r"(ad[i % 6 / 3 * 2 + (i % 3 == 1)] + (i % 3 == 2) * 1024 + (i / 6) * 12288),
                 "r"(v[0]), "r"(v[1]), "r"(v[2]), "r"(v[3]) : "memory");
  }
}
__device__ __forceinline__ uint32_t now_ns() {
  uint32_t t;
  asm volatile("mov.u32 %0, %globaltimer_lo;" : "=r"(t)::"memory");
  return t;
}
__device__ __forceinline__ void wait_clock(uint32_t t_start, uint32_t t) {
  while (now_ns() - t_start < t) { }
}
#define NAT_PRED(f, m) ".reg .pred p;\n.reg .b32 t;\nand.b32 t, " f ", " m ";\nsetp.ne.u32 p, t, 0;\n"
constexpr uint32_t kHiV = 1, kHiU = 8, kColB = 0x20, kInV = 0x100, kInU = 0x1000, kColA = 0x10000;
template <uint32_t M>
__device__ __forceinline__ float pick(const float* a, const float* b, uint32_t f) {
  float d;
  asm("{\n" NAT_PRED("%5", "%6") "add.f32 %0, %1, %2;\n@p add.f32 %0, %3, %4;\n}\n"
      : "=&f"(d) : "f"(a[0]), "f"(a[2]), "f"(b[0]), "f"(b[2]), "r"(f), "n"(M));
  return d;
}
template <uint32_t M>
__device__ __forceinline__ float sel(float a, float b, uint32_t f) {
  float d;
  asm("{\n" NAT_PRED("%3", "%4") "selp.f32 %0, %1, %2, p;\n}\n" : "=f"(d) : "f"(a), "f"(b), "r"(f), "n"(M));
  return d;
}
template <uint32_t M>
__device__ __forceinline__ void max_if(float& m, float v, uint32_t f) {
  asm("{\n" NAT_PRED("%2", "%3") "@p max.f32 %0, %0, %1;\n}\n" : "+f"(m) : "f"(v), "r"(f), "n"(M));
}
template <uint32_t M>
__device__ __forceinline__ void add_if(float& m, float v, uint32_t f) {
  asm("{\n" NAT_PRED("%2", "%3") "@p add.f32 %0, %0, %1;\n}\n" : "+f"(m) : "f"(v), "r"(f), "n"(M));
}
__device__ __forceinline__ void pick_v(const float* a, float* v, uint32_t f) {
  v[0] = pick<kHiV>(a, a + 16, f), v[1] = pick<kHiV>(a + 1, a + 17, f);
  v[2] = pick<kHiV * 2>(a + 4, a + 20, f), v[3] = pick<kHiV * 2>(a + 5, a + 21, f);
  v[4] = pick<kHiV * 4>(a + 8, a + 24, f), v[5] = pick<kHiV * 4>(a + 9, a + 25, f);
  v[6] = a[12] + a[14], v[7] = a[13] + a[15];
}
__device__ __forceinline__ void pick_u(const float* a, float* v, uint32_t f) {
#pragma unroll
  for (int c = 0; c < 3; c++) v[2 * c] = pick<kHiU>(a + 4 * c, a + 4 * c + 12, f), v[2 * c + 1] = pick<kHiU * 2>(a + 4 * c + 1, a + 4 * c + 13, f);
}
__device__ __forceinline__ uint32_t sign_bytes(uint32_t v, uint32_t sel) {
  uint32_t d;
  asm("prmt.b32 %0, %1, %1, %2;" : "=r"(d) : "r"(v), "r"(sel));
  return d;
}
__device__ __forceinline__ float own_max(const float (&v)[14], uint32_t f) {
  float m = sel<kInV>(fmaxf(v[0], v[1]), -INFINITY, f), m2 = sel<kInV * 2>(fmaxf(v[2], v[3]), -INFINITY, f);
  max_if<kInV * 4>(m, fmaxf(v[4], v[5]), f);
  max_if<kInV * 8>(m2, fmaxf(v[6], v[7]), f);
  max_if<kInU>(m, fmaxf(fmaxf(v[8], v[10]), v[12]), f);
  max_if<kInU * 2>(m2, fmaxf(fmaxf(v[9], v[11]), v[13]), f);
  return fmaxf(m, m2);
}
__device__ __forceinline__ float quad_max(float m) {
  const float a = __shfl_xor_sync(0xffffffffu, m, 1), b = __shfl_xor_sync(0xffffffffu, m, 2), c = __shfl_xor_sync(0xffffffffu, m, 3);
  return fmaxf(fmaxf(m, a), fmaxf(b, c));
}
__device__ __forceinline__ float row_rcp(const float (&v)[14], uint32_t f) {
  float s = sel<kInV>(v[0] + v[1], 0.f, f), s2 = sel<kInV * 2>(v[2] + v[3], 0.f, f);
  add_if<kInV * 4>(s, v[4] + v[5], f);
  add_if<kInV * 8>(s2, v[6] + v[7], f);
  add_if<kInU>(s, v[8] + v[10] + v[12], f);
  add_if<kInU * 2>(s2, v[9] + v[11] + v[13], f);
  s += s2;
  const float a = __shfl_xor_sync(0xffffffffu, s, 1), b = __shfl_xor_sync(0xffffffffu, s, 2), c = __shfl_xor_sync(0xffffffffu, s, 3);
  return rcp_approx((s + a) + (b + c));
}
__device__ __forceinline__ void route(const float (&v)[14], float s, const uint32_t (&rt)[9], uint32_t (&p)[14]) {
#pragma unroll
  for (int i = 0; i < 7; i++) {
    const uint32_t u = pack_bf16(v[2 * i] * s, v[2 * i + 1] * s);
    if (i < 4) p[i] = u & rt[i];
    if (i < 3) p[i + 4] = u & rt[i + 4];
    if (i >= 4) {
      p[i + 3] = u & rt[7];
      p[i + 6] = u & rt[8];
    }
  }
}

template <int C, int T0 = 0, int T1 = 7>
__device__ __forceinline__ void pv_chunk(float (&z)[32], const uint32_t (&pa)[14], const uint32_t (&pb)[14],
                                         const uint32_t (&meta)[4], uint64_t dV) {
#pragma unroll
  for (int t = T0; t < T1; t++) {
    if (t & 1)
      wg_s64t1<0, 32>(z, pa[2 * t], pb[2 * t], pa[2 * t + 1], pb[2 * t + 1], dV + ((2 * C * kChunkBytes + t * 2048) >> 4), 1,
                      meta[t >> 1]);
    else if (t > 0)
      wg_s64t<0, 32>(z, pa[2 * t], pb[2 * t], pa[2 * t + 1], pb[2 * t + 1], dV + ((2 * C * kChunkBytes + t * 2048) >> 4), 1,
                     meta[t >> 1]);
    else
      wg_s64tz<0, 32>(z, pa[0], pb[0], pa[1], pb[1], dV + ((2 * C * kChunkBytes) >> 4), 0, meta[0]);
  }
}
template <int C>
__device__ __forceinline__ void pack_z(const float (&z)[32], uint32_t (&za)[24], uint32_t (&zb)[24]) {
#pragma unroll
  for (int j = 0; j < 8; j++) {
    za[8 * C + j] = pack_bf16(z[4 * j], z[4 * j + 1]);
    zb[8 * C + j] = pack_bf16(z[4 * j + 2], z[4 * j + 3]);
  }
}

template <int H>
__device__ __forceinline__ void pack_out(const float (&ac)[48], uint32_t (&oa)[24], uint32_t (&ob)[24]) {
#pragma unroll
  for (int j = 0; j < 12; j++) {
    oa[12 * H + j] = pack_bf16(ac[4 * j], ac[4 * j + 1]);
    ob[12 * H + j] = pack_bf16(ac[4 * j + 2], ac[4 * j + 3]);
  }
}
struct Maps { CUtensorMap v6, v2, v14, u8, px[8], wv, wo; };
__device__ __forceinline__ void tma_prefetch_5d(const CUtensorMap* map, int c0, int c1, int c2, int c3, int c4) {
  asm volatile("cp.async.bulk.prefetch.tensor.5d.L2.global.tile [%0, {%1, %2, %3, %4, %5}];" ::"l"((uint64_t)map), "r"(c0), "r"(c1),
               "r"(c2), "r"(c3), "r"(c4) : "memory");
}
__device__ __forceinline__ int first_line(const TileCoord tc) { return 3 * (qpix(tc.pr, 8 * tc.I) * kW + qpix(tc.pc, 8 * tc.J)); }
__device__ __forceinline__ void load_px(const Maps& tm, const TileTable& tt, uint32_t dst, uint32_t bar, int line, int kind) {
#pragma unroll
  for (int i = 0; i < 2; i++) {
    if (i == 0 || kind != 0) {
      const CUtensorMap* map = (const CUtensorMap*)((const char*)tm.px + tt.b[kind][i][1]);
      if (bar) tma_load_5d(dst + tt.b[kind][i][2], map, bar, 0, 0, 0, 0, line + tt.b[kind][i][0]);
      else tma_prefetch_5d(map, 0, 0, 0, 0, line + tt.b[kind][i][0]);
    }
  }
}
__device__ __forceinline__ void store_px(const Maps& tm, const TileTable& tt, uint32_t buf, int line, int kind) {
#pragma unroll
  for (int i = 0; i < 8; i++) {
    const int j = 2 * (i & 3) + (i >> 2);
    asm volatile("cp.async.bulk.tensor.5d.global.shared::cta.tile.bulk_group [%0, {%2, %2, %2, %2, %3}], [%1];" ::"l"(
                     (uint64_t)tm.px + tt.g[kind][j][1]), "r"(buf + i * 3072), "r"(0), "r"(line + tt.g[kind][j][0]) : "memory");
  }
  asm volatile("cp.async.bulk.commit_group;" ::: "memory");
}
__device__ __noinline__ bool refetch(uint32_t base, const uint8_t* src, bool gap) {
  constexpr uint32_t bars = 1024 + kBarOff, cnt = bars + 192;
#pragma unroll 1
  for (uint32_t o = 0; o < kWBytes && !gap; o += 2048) {
    uint32_t mx = 0;
#pragma unroll
    for (int i = 0; i < 4; i++) {
      uint4 v;
      asm volatile("ld.shared.v4.u32 {%0,%1,%2,%3}, [%4];" : "=r"(v.x), "=r"(v.y), "=r"(v.z), "=r"(v.w)
                   : "r"(base + o + i * 512 + (threadIdx.x & 31) * 16));
      mx = __vimax3_u32(__vimax3_u32(mx, v.x, v.y), v.z, v.w);
    }
    gap = __any_sync(0xffffffffu, mx == kEmpty);
  }
  uint32_t n;
  asm volatile("ld.shared.u32 %0, [%1];" : "=r"(n) : "r"(cnt) : "memory");
  if (!gap || __any_sync(0xffffffffu, n > (1u << 12))) return false;
  asm volatile("bar.sync 15, 128;" ::: "memory");
  if (threadIdx.x == 0) {
    asm volatile("st.shared.u32 [%0], %1;" ::"r"(cnt), "r"(n + 1) : "memory");
    mbar_arrive_expect_tx(bar_redo(bars), kWBytes);
    bulk_load(base, src, kWBytes, bar_redo(bars));
  }
  __syncwarp();
  mbar_wait(bar_redo(bars), n & 1);
  return true;
}
__device__ __forceinline__ bool any_nan(const uint32_t (&a)[24]) {
  uint32_t m[2] = {a[0], a[1]}, nan;
#pragma unroll
  for (int i = 2; i < 24; i++) asm("max.NaN.bf16x2 %0, %0, %1;" : "+r"(m[i & 1]) : "r"(a[i]));
  asm("max.NaN.bf16x2 %0, %0, %1;" : "+r"(m[0]) : "r"(m[1]));
  asm volatile("{\n.reg .pred p;\nsetp.ne.u32 p, %1, 0;\nbar.red.or.pred p, 15, 128, p;\nselp.u32 %0, 1, 0, p;\n}\n"
               : "=r"(nan) : "r"(((m[0] & 0x7FFF7FFFu) + 0x007F007Fu) & 0x80008000u) : "memory");
  return __any_sync(0xffffffffu, nan);
}
template <int S0, int S1, int Z>
__device__ __forceinline__ void g2_steps(float (&ac)[48], const uint32_t (&za)[24], const uint32_t (&zb)[24], uint64_t d) {
#pragma unroll
  for (int s = S0; s < S1; s++) {
    const uint64_t ds = d + (((s >> 2 & 1) * (kWChunk / 2) + (s & 3) * 32) >> 4);
    if (s == Z) wg_d96z<0, 48>(ac, za[2 * s], zb[2 * s], za[2 * s + 1], zb[2 * s + 1], ds, 0);
    else wg_d96<0, 48>(ac, za[2 * s], zb[2 * s], za[2 * s + 1], zb[2 * s + 1], ds, 1);
  }
}

__device__ __forceinline__ void consumer(const int wg, __nv_bfloat16* out, const uint8_t* wimg, const uint32_t sbase,
                                         const uint32_t zero, const Maps& tm, const TileTable& tt) {
  const int tid = threadIdx.x & 127;
  const int w = __shfl_sync(0xffffffffu, tid >> 5, 0), lane = tid & 31;
  const uint64_t dK = make_desc(sbase, 16, 1024);
  const uint64_t dV = make_desc(sbase, kChunkBytes, 512, 2);
  const uint64_t dW1 = make_desc(sbase + kW1Off, 16, 1024);
  const uint64_t dX0 = make_desc(sbase + kW2Off + wg * 2 * kWChunk, 16, 1024), dY0 = make_desc(sbase + kW2Off + (1 - wg) * 2 * kWChunk, 16, 1024);
  const uint64_t dX2 = make_desc(sbase + kXOff + wg * (kWChunk / 2), 16, 1024), dY2 = make_desc(sbase + kXOff + (1 - wg) * (kWChunk / 2), 16, 1024);
  const uint32_t bars = sbase + kBarOff;
  int tile0 = blockIdx.x * kTilesPerCta;
  asm volatile("" : "+r"(tile0));
  const int nt = num_tiles();

  uint32_t pix = 0, geo[6] = {};
  const int l = lane & 3;
#pragma unroll 1
  for (int j = 4; j >= 0; j -= 2) {
    const TileCoord tc = decode_tile(tt, tile0 + wg + j);
    const bool col = tc.kind == 1 || tc.kind == 2;
    const int g = col ? lane >> 2 : 2 * w + ((lane >> 2) & 1), qc = col ? w : lane >> 3;
    const uint32_t pr = qpix(tc.pr, 8 * tc.I + g) * kW;
    if (j == nt - 2) pix = (pr + qpix(tc.pc, 8 * tc.J + qc)) | (pr + qpix(tc.pc, 8 * tc.J + qc + 4)) << 16;
    const int d = 8 * tc.J + 6 * tc.pc - 6 - halo_c0(tc);
    const int ro = woff(tc.pr, tc.I, g), coA = woff(tc.pc, tc.J, qc) + d, coB = woff(tc.pc, tc.J, qc + 4) + d - 3;
#pragma unroll
    for (int i = 5; i >= 2; i--) geo[i] = geo[i - 2];
    const uint32_t lr = 0x1FCu << ro;
    const uint32_t lv = lr >> (2 + (l >> 1)), lu = lr >> (2 * l + 2 * tc.up);
    const uint32_t t = __byte_perm(lv, lu, wg ? 0x4501 : 0x5410);
    geo[0] = (((t & 0x15u) | (lv & 0x40u)) * 0x02082080u & 0x80808080u) | (((t >> 8) & 0x15u) * 0x01041040u & 0x40404040u) |
             (__byte_perm(t << 5, t << 4, 0x7362) & 0x20202020u) | (nt == 6);
    const int dr = (ro - 1) & 7;
    const uint32_t hiv = (((1u << ((ro - (l >> 1) + 1) >> 1)) - 1u) ^ (wg ? 7u : 0u)) & 7u, hiu = (t >> 24) & 3u;
    const uint32_t ca = (1u << coA) - 1u;
    geo[1] = hiv * kHiV | hiu * kHiU | ((((1u << coB) - 1u) >> (2 * (l & 1))) & 3u) * kColB |
             (15u & ~((uint32_t)((dr & 1) == (l >> 1)) << (dr >> 1))) * kInV | ((t >> 16 | t >> 24) & 3u) * kInU | ca * kColA |
             (ca >> ((0x49 >> (2 * l)) & 3) & 1u) << 19 | (uint32_t)(l == 3) << 20 | (0x55u & ((1u << (2 * coB)) - 1u)) << 24;
  }
  keep_regs(geo);
  const int so = (lane >> 3) | (lane & 4);
  uint32_t sts = sbase + w * 3072 + so * 128 + (((lane & 3) ^ so) << 4);
  __nv_bfloat16* poA = out + 8 * l + (pix & 0xFFFFu) * kC + 96 * wg;
  __nv_bfloat16* poB = out + 8 * l + (pix >> 16) * kC + 96 * wg;
  asm volatile("" : "+l"(poA), "+l"(poB), "+r"(sts));
  uint32_t oa[24], ob[24];
#pragma unroll
  for (int j = 0; j < 24; j++) oa[j] = ob[j] = 0u;
  keep_regs(oa);
  keep_regs(ob);
  PROF(wg, 0);
  if (threadIdx.x == 0) GT(1);

  for (int k = wg; k < nt; k += 2) {
    const uint32_t ph = (k >> 1) & 1;
    const int it = k >> 1;
    uint32_t qa[24], qb[24], hok[3];
    uint32_t fl = geo[1];
    {
      float acc[96];
      const uint32_t xp = (k + (k > 0)) & 1;
      const uint32_t xok = mbar_test(bar_x(bars, k > 0, 0), xp);
      if (k > 0) nb_sync(1 + (1 - wg));
#pragma unroll
      for (int s = 0; s < 12; s++) {
        if (s == 0) mbar_wait_if(xok, bar_x(bars, k > 0, 0), xp);
        if (s == 0 && k < 2) PROF(wg, 1);
        if (s == 0) PROFS(2, wg, 2 + it * 12);
        if (s == 0 && w == 0 && k < 2) GT(20 + wg);
        if ((s & 3) == 0 && (k == 0 || s > 0)) {
          mbar_wait(k == 0 ? bar_w1c(bars, s >> 2) : bar_x(bars, 1, s >> 2), xp);
          PROFS(17, wg, 50 + (s >> 2));
        }
        if ((s & 3) == 0) wg_fence();
        const uint64_t dX = make_desc(sbase + x_chunk(k, s >> 2), 16, 1024) + 2 * (s & 3);
        if (s == 0) wg_m192z<0, 96>(acc, dX, dW1, 0);
        else wg_m192<0, 96>(acc, dX, wdesc(dW1, s), 1);
        if ((s & 3) == 3) wg_commit();
      }
      PROFS(13, wg, 13 + it * 12);
      const uint32_t e = sts + out_slot(k, nt), o = e ^ 64;
      uint32_t ad[4] = {wg ? o + 1024 : e, wg ? e + 2048 : o, wg ? e : o + 1024, wg ? o : e + 2048};
      keep_regs(ad);
      wg_wait<2>();
      if (k > 0) nb_arrive_p(0);
      wg_wait<1>();
      if (k > 0) nb_arrive_p(14);
      wg_wait<0>();
      if (k > 0) {
        nb_arrive_p(6);
        sched_fence();
      }
      fence_regs(acc);
      PROFS(3, wg, 3 + it * 12);
#pragma unroll
      for (int j = 0; j < 24; j++) {
        qa[j] = pack_bf16(acc[4 * j], acc[4 * j + 1]);
        qb[j] = pack_bf16(acc[4 * j + 2], acc[4 * j + 3]);
      }
      keep_regs(qa);
      keep_regs(qb);
      sched_fence();
      if (k >= 2) {
        nb_sync(11);
        stage_out<0, 6>(ad, oa, ob);
        nb_sync(12);
        stage_out<6, 12>(ad, oa, ob);
      }
#pragma unroll
      for (int c = 0; c < 3; c++) hok[c] = mbar_test(bar_full(bars, wg, c), ph);
      if (k >= 2) {
        fence_proxy_async();
        nb_arrive_p(10);
      }
    }

    float aE[52], aO[24], bO[52], bE[28];
    const uint32_t mq = 0xEEEE4444u | zero;
    PROFS(4, wg, 4 + it * 12);

    mbar_wait_if(hok[0], bar_full(bars, wg, 0), ph);
    PROFS(14, wg, 40 + it * 3);
    if (w == 0 && k < 2) GT(22 + wg);
    if (k > 0) nb_sync(3 + (1 - wg));
    wg_fence();
#pragma unroll
    for (int ks = 0; ks < 6; ks++) {
      if (ks == 2) {
        mbar_wait_if(hok[1], bar_full(bars, wg, 1), ph);
        PROFS(14, wg, 41 + it * 3);
        wg_fence();
      }
      if (ks == 4) {
        mbar_wait_if(hok[2], bar_full(bars, wg, 2), ph);
        PROFS(14, wg, 42 + it * 3);
        wg_fence();
      }
      const uint64_t d = dK + ((ks * kChunkBytes) >> 4);
      if (ks == 0) wg_s104z<0, 52>(aE, qa[0], qa[1], qa[2], qa[3], d, 0, mq);
      else wg_s104<0, 52>(aE, qa[4 * ks], qa[4 * ks + 1], qa[4 * ks + 2], qa[4 * ks + 3], d, 1, mq);
      if (ks == 0) wg_s48z<0, 24>(aO, qa[0], qa[1], qa[2], qa[3], d + ((7 * 1024 + 64) >> 4), 0, mq);
    }
    wg_commit();
#pragma unroll
    for (int ks = 1; ks < 6; ks++)
      wg_s48<0, 24>(aO, qa[4 * ks], qa[4 * ks + 1], qa[4 * ks + 2], qa[4 * ks + 3], dK + ((ks * kChunkBytes + 7 * 1024 + 64) >> 4), 1, mq);
    wg_commit();
    wg_s56z<0, 28>(bE, qb[0], qb[1], qb[2], qb[3], dK, 0, mq);
#pragma unroll
    for (int ks = 1; ks < 6; ks++) wg_s56<0, 28>(bE, qb[4 * ks], qb[4 * ks + 1], qb[4 * ks + 2], qb[4 * ks + 3], dK + ((ks * kChunkBytes) >> 4), 1, mq);
    wg_commit();
    wg_wait<2>();
    fence_regs(aE);
    PROFS(5, wg, 5 + it * 12);

    uint32_t pa[14], pb[14], meta[4];
    {
      float vA[14], vB[14];
      pick_v(aE, vA, fl);
      pick_u(aE + 28, vA + 8, fl);
      fence_regs(vA);
      if (k == 0) {
        if (__builtin_expect(__any_sync(0xffffffffu, vA[6] != vA[6]), 0)) {
          wg_wait<0>();
          fence_regs(aO);
          fence_regs(bE);
          if (refetch(sbase + kW1Off, wimg, false)) {
#pragma unroll
            for (int j = 0; j < 24; j++) oa[j] = ob[j] = 0u;
            k -= 2;
            continue;
          }
        }
        if (elect_one()) mbar_arrive(bar_xf(bars));
      }
      wg_fence();
      wg_s104z<0, 52>(bO, qb[0], qb[1], qb[2], qb[3], dK + 4, 0, mq);
#pragma unroll
      for (int ks = 1; ks < 6; ks++)
        wg_s104<0, 52>(bO, qb[4 * ks], qb[4 * ks + 1], qb[4 * ks + 2], qb[4 * ks + 3], dK + ((ks * kChunkBytes + 64) >> 4), 1, mq);
      wg_commit();
      if (k + 1 < nt) nb_arrive(1 + wg);
      uint32_t rt[9];
#pragma unroll
      for (int i = 0; i < 7; i++) rt[i] = sign_bytes(geo[0] << (i >> 2), 0x8888u + 0x1111u * (i & 3));
      rt[7] = sign_bytes(geo[0] << 2, 0x9988u);
      rt[8] = sign_bytes(geo[0] << 2, 0xBBAAu);
      keep_regs(rt);
      pa[13] = NAT_ZZ ? geo[0] & zero : 0u, pb[13] = NAT_ZZ ? geo[1] & zero : 0u;
      wg_wait<2>();
      keep_regs(qa);
      fence_regs(aO);
      float oA[6], eB[8];
      pick_u(aO, oA, fl);
      wg_wait<1>();
      fence_regs(bE);
      pick_v(bE, eB, fl);
      vA[8] = sel<kColA>(oA[0], vA[8], fl), vA[9] = sel<kColA>(oA[1], vA[9], fl);
      vA[10] = sel<kColA * 2>(oA[2], vA[10], fl), vA[11] = sel<kColA * 2>(oA[3], vA[11], fl);
      vA[12] = sel<kColA * 4>(oA[4], vA[12], fl), vA[13] = sel<kColA * 4>(oA[5], vA[13], fl);
      {
        const float m1 = __uint_as_float(0x88DD88DDu), m0 = __uint_as_float(0x88DDDD88u);
        meta[0] = 0xDD88DD88u ^ __byte_perm(fl, 0u, 0x3344);
        meta[1] = __float_as_uint(sel<kColA * 16>(sel<kColA>(m1, m0, fl), __uint_as_float(meta[0]), fl));
        meta[2] = __float_as_uint(sel<kColA * 8>(m1, m0, fl));
        meta[3] = __float_as_uint(sel<kColA * 4>(m1, m0, fl));
        keep_regs(meta);
      }
      float mA = own_max(vA, fl);
      fl |= __float_as_uint(eB[7]) & zero;
      fence_regs(eB);
      fence_regs(vA);
      asm volatile("" : "+f"(mA), "+r"(fl));
      sched_fence();
      wg_wait<0>();
      sched_fence();
      keep_regs(qb);
      fence_regs(bO);
      PROFS(6, wg, 6 + it * 12);
      if (w == 0) GT(24 + k);
      mA = quad_max(mA);
      pick_v(bO, vB, fl);
      pick_u(bO + 28, vB + 8, fl);
#pragma unroll
      for (int i = 0; i < 8; i += 2) vB[i] = sel<kColB>(vB[i], eB[i], fl), vB[i + 1] = sel<kColB * 2>(vB[i + 1], eB[i + 1], fl);
#pragma unroll
      for (int i = 0; i < 14; i++) vA[i] -= mA;
#pragma unroll
      for (int i = 0; i < NAT_HS - 1; i++) vA[i] = ex2(vA[i]);
      fence_regs(vA);
      fence_regs(vB);
      sched_fence();
#pragma unroll
      for (int i = NAT_HS - 1; i < 14; i++) vA[i] = ex2(vA[i]);
      float mB = quad_max(own_max(vB, fl));
      PROFS(7, wg, 7 + it * 12);
#pragma unroll
      for (int i = 0; i < 14; i++) vB[i] = ex2(vB[i] - mB);
      route(vA, row_rcp(vA, fl), rt, pa);
      route(vB, row_rcp(vB, fl), rt, pb);
    }
    PROFS(8, wg, 8 + it * 12);
    if (k == NAT_PK) PROFS(18, wg, 53);
    sched_fence();

    float ac0[48], ac1[48];
    {
      float z0[32], z1[32], z2[32];
      uint32_t za[24], zb[24];
      wg_fence();
      pv_chunk<0>(z0, pa, pb, meta, dV);
      wg_commit();
      pv_chunk<1>(z1, pa, pb, meta, dV);
      wg_commit();
      wg_wait<1>();
      if (k == NAT_PK) PROFS(18, wg, 54);
      if (k + 1 < nt) nb_arrive_p(7);
      pv_chunk<2, 0, 3>(z2, pa, pb, meta, dV);
      wg_commit();
      sched_fence();
      fence_regs(z0);
      pack_z<0>(z0, za, zb);
      sched_fence();
      wg_fence();
      pv_chunk<2, 3, 7>(z2, pa, pb, meta, dV);
      wg_commit();
      wg_wait<2>();
      if (k == NAT_PK) PROFS(19, wg, 55);
      if (k + 1 < nt) nb_arrive_p(8);
      if (k < 2) mbar_wait(k == 1 ? bar_wok(bars) : bar_w2a(bars), 0);
      wg_fence();
      g2_steps<0, 3, 0>(ac0, za, zb, dX0);
      wg_commit();
      sched_fence();
      fence_regs(z1);
      pack_z<1>(z1, za, zb);
      sched_fence();
      wg_fence();
      g2_steps<3, 4, 0>(ac0, za, zb, dX0);
      wg_commit();
      g2_steps<4, 8, 0>(ac0, za, zb, dX0);
      wg_commit();
      wg_wait<3>();
      if (k + 1 < nt) nb_arrive_p(9);
      else nb_arrive(11);
      if (k == NAT_PK) PROFS(20, wg, 56);
      keep_regs(pa);
      keep_regs(pb);
      keep_regs(meta);
      sched_fence();
      const uint32_t mok = mbar_test(bar_w2m(bars), k + 1 < nt ? k & 1 : ~k & 1);
      const uint32_t wp = k < 2 ? 0 : k + 1 < nt ? ~k & 1 : k & 1, wok = mbar_test(bar_w2(bars), wp);
      fence_regs(z2);
      pack_z<2>(z2, za, zb);
      keep_regs(za);
      keep_regs(zb);
      sched_fence();
      PROFS(9, wg, 9 + it * 12);
      wg_wait<1>();
      if (k > 0 && k + 1 < nt) nb_arrive(11);
      mbar_wait_if(mok, bar_w2m(bars), k & 1);
      wg_fence();
      g2_steps<8, 12, 0>(ac0, za, zb, dX2);
      wg_commit();
      g2_steps<8, 12, 8>(ac1, za, zb, dY2);
      wg_commit();
      wg_wait<2>();
      if (k > 0 && k + 1 < nt) nb_arrive(12);
      mbar_wait_if(wok, bar_w2(bars), wp);
      wg_fence();
      g2_steps<0, 4, 8>(ac1, za, zb, dY0);
      wg_commit();
      wg_wait<2>();
      if (k + 2 < nt) nb_arrive_p(13);
      const bool direct = k + 2 >= nt;
      sched_fence();
      fence_regs(ac0);
      pack_out<0>(ac0, oa, ob);
      store_rows<0, 1>(direct, poA, poB, oa, ob);
      sched_fence();
      wg_fence();
      g2_steps<4, 8, 8>(ac1, za, zb, dY0);
      wg_commit();
      if (k + 1 < nt) nb_arrive(3 + wg);
      PROFS(10, wg, 10 + it * 12);
      wg_wait<2>();
      if (k + 2 < nt && (k > 0 || nt == 6)) nb_arrive_p(5);
      store_rows<1, 3>(direct, poA, poB, oa, ob);
      __nv_bfloat16 *qA = poA - 192 * wg, *qB = poB - 192 * wg;
      if (k + 2 == nt) nb_sync(11);
      sched_fence();
      wg_wait<0>();
      fence_regs(ac1);
      pack_out<1>(ac1, oa, ob);
      asm volatile("" : "+l"(qA), "+l"(qB));
      store_rows<3, 6>(direct, qA, qB, oa, ob);
      if (direct) break;
      if (k == 0) {
        if (any_nan(oa)) {
          for (int c = 0; c < 3 && __any_sync(0xffffffffu, geo[2] & 1u); c++) mbar_wait(bar_x(bars, 1, c), 1);
          bool first = true;
          do {
            if (!__any_sync(0xffffffffu, refetch(sbase + kW2Off, wimg + w2_offset(), first))) break;
            first = false;
            wg_fence();
            g2_steps<0, 8, 0>(ac0, za, zb, dX0);
            g2_steps<8, 12, 0>(ac0, za, zb, dX2);
            g2_steps<8, 12, 8>(ac1, za, zb, dY2);
            g2_steps<0, 8, 8>(ac1, za, zb, dY0);
            wg_commit();
            wg_wait<0>();
            fence_regs(ac0);
            fence_regs(ac1);
            pack_out<0>(ac0, oa, ob);
            pack_out<1>(ac1, oa, ob);
          } while (any_nan(oa));
          if (__any_sync(0xffffffffu, geo[2] & 1u)) {
            asm volatile("bar.sync 15, 128;" ::: "memory");
            if (w == 0 && elect_one()) {
              const TileCoord tc = decode_tile(tt, tile0 + 2);
              mbar_arrive_expect_tx(bar_raw(bars), kWChunk);
#pragma unroll 1
              for (int c = 0; c < 3; c++) load_px(tm, tt, sbase + x_chunk(2, c), bar_raw(bars), first_line(tc) + c, tc.kind);
            }
            __syncwarp();
            mbar_wait(bar_raw(bars), 0);
          }
        }
        if (nt < 6) nb_arrive_p(5);
        if (elect_one()) mbar_arrive(bar_wok(bars));
      }
      keep_regs(za);
      keep_regs(zb);
#pragma unroll
      for (int i = 0; i < 4; i++) geo[i] = geo[i + 2];
      keep_regs(oa);
      keep_regs(ob);
      PROFS(12, wg, 12 + it * 12);
      sched_fence();
    }
  }
  PROF(wg, 38);
  GT_DUMP();
  PROF_DUMP(wg);
}

struct HaloCols { int vj, vc, uj, uc; };
__device__ __forceinline__ HaloCols halo_cols(const TileCoord& tc) {
  const int c0 = halo_c0(tc);
  return HaloCols{c0 > 98, c0 > 98 ? 98 : c0 + 3, c0 < 0 ? -1 : 0, c0 < 0 ? 4 : c0};
}
__device__ __forceinline__ void first_halo(const Maps& tm, uint32_t sbase, const TileCoord tc, int i) {
  const HaloCols hc = halo_cols(tc);
  const uint32_t dst = sbase + i * kChunkBytes, bar = bar_full(sbase + kBarOff, 0, i >> 1);
  const int h0 = halo_r0(tc), ch = 24 * tc.pc + 4 * i;
  tma_load_5d(dst, &tm.v14, bar, ch, hc.vj, hc.vc, tc.pr, h0);
  tma_load_5d(dst + 7 * 1024, &tm.u8, bar, ch, hc.uj, h0 + (tc.up ? 0 : -2), tc.pr, hc.uc);
  tma_load_5d(dst + 10 * 1024, &tm.u8, bar, ch, hc.uj, h0 + (tc.up ? 8 : 6), tc.pr, hc.uc);
}
__device__ __forceinline__ void load_halo(const Maps& tm, uint32_t sbase, uint32_t bars, const TileCoord tc, int k, int c) {
  const HaloCols hc = halo_cols(tc);
  const int h6 = halo_r0(tc) + (tc.up ? 0 : 8), h2 = halo_r0(tc) + 6, h8 = halo_r0(tc) + (tc.up ? 0 : 6), ch = 24 * tc.pc + 8 * c;
  uint32_t dv = sbase + 2 * c * kChunkBytes, du = dv + 7 * 1024;
  if (((k ^ tc.up) & 1) == 0) dv += 4 * 1024, du += 3 * 1024;
  const uint32_t bar = bar_full(bars, k & 1, c);
  mbar_arrive_expect_tx(bar, 14 * 1024);
  nb_sync_p(7 + c);
#pragma unroll
  for (int h = 0; h < 2; h++) {
    tma_load_5d(dv + h * kChunkBytes, &tm.v6, bar, ch + 4 * h, hc.vj, hc.vc, tc.pr, h6);
    tma_load_5d(du + h * kChunkBytes, &tm.u8, bar, ch + 4 * h, hc.uj, h8, tc.pr, hc.uc);
    tma_load_5d(sbase + (2 * c + h) * kChunkBytes + 3 * 1024, &tm.v2, bar, ch + 4 * h, hc.vj, hc.vc, tc.pr, h2);
  }
  PROFS(15, 2, k * 4 + c);
}
__device__ __forceinline__ void gather_px(const __nv_bfloat16* __restrict__ x, uint32_t sbase, const TileCoord tc) {
  const int lane = threadIdx.x & 31, g = lane >> 3;
  uint32_t ro[4], co[4];
#pragma unroll
  for (int i = 0; i < 4; i++) {
    ro[i] = qpix(tc.pr, 8 * tc.I + 2 * i + (g & 1)) * (kW * kC * 2) + 16 * (lane & 7);
    co[i] = qpix(tc.pc, 8 * tc.J + 2 * i + (g >> 1)) * (kC * 2);
  }
  const uint32_t dst = sbase + kXOff + g * 128 + (((lane & 7) ^ g) << 4);
  if (lane < 8)
    asm volatile("cp.async.bulk.prefetch.L2.global [%0], 3456;" ::"l"(x + (qpix(tc.pr, 8 * tc.I + lane) * kW + 215 * tc.pc) * kC) : "memory");
  __syncwarp();
  keep_regs(ro);
  keep_regs(co);
  sched_fence();
  nb_sync_p(13);
  nb_sync_p(5);
#pragma unroll
  for (int i = 0; i < 16; i++) {
    const char* src = (const char*)x + (ro[i >> 2] + co[i & 3]);
#pragma unroll
    for (int q = 0; q < 3; q++)
      asm volatile("cp.async.cg.shared.global [%0], [%1], 16;" ::"r"((dst ^ ((i & 1) * 576)) + (i >> 1) * 1024 + q * 8192), "l"(src + 128 * q) : "memory");
  }
  asm volatile("cp.async.wait_all;" ::: "memory");
  fence_proxy_async();
  __syncwarp();
  if (lane < 3) mbar_arrive(bar_x(sbase + kBarOff, 1, lane));
  __syncwarp();
}

__global__ void __launch_bounds__(384, 1)
nat_kernel(const __nv_bfloat16* __restrict__ x, __nv_bfloat16* out, const __nv_bfloat16* __restrict__ wqkv,
           const __nv_bfloat16* __restrict__ wo, uint8_t* wimg, const uint32_t zero,
           const __grid_constant__ Maps tm, const __grid_constant__ TileTable tt) {
  extern __shared__ uint8_t smem_raw[];
  constexpr uint32_t sbase = 1024;
  constexpr uint32_t bars = sbase + kBarOff;
  if (smem_u32(smem_raw) != sbase) __trap();
  const int tid = threadIdx.x;
  const uint32_t t_start = now_ns();
  if (tid == 0) GT(0);
  const int wid = __shfl_sync(0xffffffffu, tid >> 5, 0);
  const bool w2cta = blockIdx.x - 128 < 3 && wqkv != nullptr;
  if (wid >= 8) {
    asm volatile("setmaxnreg.dec.sync.aligned.u32 24;");
    const int c = wid & 3, lane = tid & 31;
    const int tile0 = blockIdx.x * kTilesPerCta, nt = num_tiles();
    uint32_t w2o = 0;
    if (c == 3) {
      if (elect_one()) wait_clock(t_start, NAT_TM);
      __syncwarp();
      asm volatile("prefetch.tensormap [%0];" ::"l"((uint64_t)tm.px) : "memory");
      asm volatile("prefetch.tensormap [%0];" ::"l"((uint64_t)&tm.v6) : "memory");
      asm volatile("prefetch.tensormap [%0];" ::"l"((uint64_t)&tm.v2) : "memory");
      asm volatile("prefetch.tensormap [%0];" ::"l"((uint64_t)(tm.px + (blockIdx.x < 112 ? 5 : 6))) : "memory");
      asm volatile("prefetch.tensormap [%0];" ::"l"((uint64_t)(tm.px + 7)) : "memory");
      if (nt < 6) {
        asm volatile("prefetch.tensormap [%0];" ::"l"((uint64_t)(tm.px + 1)) : "memory");
        asm volatile("prefetch.tensormap [%0];" ::"l"((uint64_t)(tm.px + 2)) : "memory");
        asm volatile("prefetch.tensormap [%0];" ::"l"((uint64_t)&tm.v14) : "memory");
        asm volatile("prefetch.tensormap [%0];" ::"l"((uint64_t)&tm.u8) : "memory");
      }
      __nanosleep(NAT_TW2 - 2800);
      asm volatile("bar.sync 4, 64;" ::: "memory");
      w2o = w2_offset();
      if (elect_one()) {
        mbar_arrive_expect_tx(bar_w2a(bars), kWChunk);
        mbar_arrive_expect_tx(bar_w2(bars), kWChunk);
        wait_clock(t_start, NAT_TW2);
        bulk_load(sbase + kW2Off, wimg + w2o, kWChunk, bar_w2a(bars));
        mbar_wait(bar_xf(bars), 0);
        bulk_load(sbase + kW2Off + 2 * kWChunk, wimg + (w2o + 2 * kWChunk), kWChunk, bar_w2(bars));
      }
      __syncwarp();
      if (nt < 6) gather_px(x, sbase, decode_tile(tt, tile0 + 2));
      if (wqkv == nullptr) return;
      mbar_wait(bar_wok(bars), 0);
      if (lane == 0) asm volatile("red.relaxed.gpu.global.add.u32 [%0], 1;" ::"l"(g_flag) : "memory");
      if (blockIdx.x != kCtas - 1) return;
#pragma unroll
      for (int i = 0; i < 8; i++) asm volatile("st.shared.v4.u32 [%0], {%1,%1,%1,%1};" ::"r"(bars + 1024 + i * 512 + lane * 16), "r"(kEmpty) : "memory");
      fence_proxy_async();
      __syncwarp();
      if (elect_one()) {
#pragma unroll 1
        for (int i = 0; i < 36; i++) {
          if (i == 18) {
            uint32_t v, it = 0;
            do {
              __nanosleep(500);
              asm volatile("ld.relaxed.gpu.global.u32 %0, [%1];" : "=r"(v) : "l"(g_flag) : "memory");
            } while (v < gridDim.x && ++it < (1u << 18));
          }
          asm volatile("cp.async.bulk.global.shared::cta.bulk_group [%0], [%1], 4096;" ::"l"(
                           wimg + (i < 18 ? 3 * kWBytes - w2o + i * 4096 : (i - 18) * 4096)), "r"(bars + 1024) : "memory");
          asm volatile("cp.async.bulk.commit_group;" ::: "memory");
          asm volatile("cp.async.bulk.wait_group.read 1;" ::: "memory");
        }
        asm volatile("cp.async.bulk.wait_group 0;" ::: "memory");
        g_flag[0] = 0;
        g_flag[32] = w2o == kWBytes;
      }
      return;
    }
    if (!elect_one()) return;
    if (c == 0) {
      for (int i = 0; i < kNumBars; i++)
        if ((i != 0 && i != 10 || nt < 6) && (i != 21 || !w2cta)) mbar_init(bars + i * 8, i == 13 || i == 16 ? 4 : 1);
      asm volatile("st.shared.v2.u32 [%0], {%1,%1};" ::"r"(bars + 192), "r"(0) : "memory");
      asm volatile("fence.mbarrier_init.release.cluster;" ::: "memory");
      if (w2cta) asm volatile("bar.sync 10, 64;" ::: "memory");
      asm volatile("bar.arrive 0, 160;" ::: "memory");
      asm volatile("bar.arrive 14, 160;" ::: "memory");
      asm volatile("bar.arrive 13, 96;" ::: "memory");
      asm volatile("bar.arrive 4, 64;" ::: "memory");
      const TileCoord tc0 = decode_tile(tt, tile0);
      const HaloCols hc = halo_cols(tc0);
      const int h0 = halo_r0(tc0);
#pragma unroll
      for (int j = 0; j < 3; j++)
        if (j > 0 || nt < 6) mbar_arrive_expect_tx(bar_full(bars, 0, j), 2 * kChunkBytes);
      wait_clock(t_start, NAT_HP);
#pragma unroll
      for (int q = 8; q < 24 && !w2cta; q += 8) {
        tma_prefetch_5d(blockIdx.x < 112 ? &tm.v6 : &tm.v14, 24 * tc0.pc + q, hc.vj, hc.vc, tc0.pr, h0 + (tc0.up || blockIdx.x >= 112 ? 0 : 8));
        tma_prefetch_5d(&tm.u8, 24 * tc0.pc + q, hc.uj, h0 + (tc0.up ? 0 : 6), tc0.pr, hc.uc);
      }
#pragma unroll 1
      for (int i = nt < 6 ? 0 : 2; i < 6; i++) {
        if (i == 2) mbar_wait(bar_w1q(bars), 0);
        first_halo(tm, sbase, tc0, i);
      }
      mbar_arrive(bar_go(bars));
      w2o = w2_offset();
    } else {
      asm volatile("bar.sync 13, 96;" ::: "memory");
      if (c == 2) {
        if (wqkv != nullptr && blockIdx.x < 131) asm volatile("bar.sync 12, 64;" ::: "memory");
        const uint32_t c0 = clock();
        while ((uint32_t)clock() - c0 < NAT_TD && nt == 6) { }
        wait_clock(t_start, NAT_T0);
#pragma unroll
        for (int j = 0; j < 3; j++) {
          mbar_arrive_expect_tx(bar_w1c(bars, j), kWChunk);
          bulk_load(sbase + kW1Off + j * kWChunk, wimg + j * kWChunk, kWChunk, bar_w1c(bars, j));
        }
        mbar_arrive(bar_w1q(bars));
        GT(2);
      } else {
#pragma unroll 1
        for (int j = nt == 6; j < 2; j++) {
          const TileCoord tc = decode_tile(tt, tile0 + j);
          const int line = first_line(tc);
          if (j == 1) mbar_wait(bar_go(bars), 0);
          if (j == 0) GT(15);
#pragma unroll 1
          for (int q = 0; q < 3; q++) {
            load_px(tm, tt, sbase + x_chunk(j, q), bar_x(bars, j, q), line + q, tc.kind);
            if (j == 1 || q == 0) mbar_arrive_expect_tx(bar_x(bars, j, q), j ? 8192 : kWChunk);
          }
          if (j == 0) GT(16);
        }
        w2o = w2_offset();
        wait_clock(t_start, NAT_TW2);
        mbar_wait(bar_xf(bars), 0);
      }
    }
#pragma unroll 1
    for (int k = 1; k < nt; k++) {
      const TileCoord tn = decode_tile(tt, tile0 + k + 1);
      const int line = first_line(tn);
      const bool more = k + 1 < nt && (k > 1 || nt == 6);
      if (c == 1) {
#pragma unroll
        for (int q = 0; q < 3; q++) {
          nb_sync_p(q == 0 ? 0 : q == 1 ? 14 : 6);
          bulk_load(sbase + x_chunk(k, q), wimg + (w2o + x_chunk(k, q) - kW2Off), 8192, bar_w2m(bars));
        }
        mbar_arrive_expect_tx(bar_w2m(bars), kWChunk);
      }
      if (c == 2) {
        if (k == 1) wait_clock(t_start, NAT_TX2);
        else __nanosleep(NAT_PFD);
#pragma unroll 1
        for (int q = 0; q < 3 && more; q++) load_px(tm, tt, 0, 0, line + q, tn.kind);
      }
      if (c == 2 && (blockIdx.x >= 112 || k == 5)) {
        const TileCoord tc = decode_tile(tt, tile0 + k);
        const HaloCols hc = halo_cols(tc);
        const int h8 = halo_r0(tc) + (tc.up ? 0 : 6);
#pragma unroll 1
        for (int q = 0; q < 24; q += 8) {
          tma_prefetch_5d(&tm.v6, 24 * tc.pc + q, hc.vj, hc.vc, tc.pr, h8);
          tma_prefetch_5d(&tm.v2, 24 * tc.pc + q, hc.vj, hc.vc, tc.pr, h8 + 6);
          tma_prefetch_5d(&tm.u8, 24 * tc.pc + q, hc.uj, h8, tc.pr, hc.uc);
        }
      }
      load_halo(tm, sbase, bars, decode_tile(tt, tile0 + k), k, c);
      if (c == 0 && more) {
#pragma unroll
        for (int q = 0; q < 3; q++) {
          if (q < 2) nb_sync_p(q ? 5 : 13);
          load_px(tm, tt, sbase + x_chunk(k + 1, q), bar_x(bars, 1, q), line + q, tn.kind);
          if (q != 1) mbar_arrive_expect_tx(bar_x(bars, 1, q), 8192);
        }
        mbar_arrive_expect_tx(bar_x(bars, 1, 1), 8192);
        PROFS(16, 2, k * 4 + 3);
      }
      if (c == 0 && k >= 2) {
        const TileCoord tp = decode_tile(tt, tile0 + k - 2);
        const int lp = first_line(tp);
        nb_sync_p(10);
        __nanosleep(NAT_XW);
        store_px(tm, tt, sbase + out_slot(k, nt), lp, tp.kind);
        if (k + 1 < nt) {
          asm volatile("cp.async.bulk.wait_group.read 0;" ::: "memory");
          bulk_load(sbase + out_slot(k, nt), wimg + (w2o + out_slot(k, nt) - kW2Off), kWChunk, bar_w2(bars));
          mbar_arrive_expect_tx(bar_w2(bars), kWChunk);
        }
      }
    }
    asm volatile("cp.async.bulk.wait_group 0;" ::: "memory");
  } else {
    if (blockIdx.x < 128) {
      if ((wid == 4 || (wid == 5 && blockIdx.x - 2 < 16)) && wqkv != nullptr) {
        fold_w1(blockIdx.x - 2 < 16 ? 2 * blockIdx.x + wid - 6 : blockIdx.x + (blockIdx.x < 2 ? 0 : 16), wqkv, wimg);
        if (wid == 4) asm volatile("bar.arrive 12, 64;" ::: "memory");
        if (tid == 128) GT(7);
      }
      sched_fence();
      if (wid == 1 && elect_one()) {
        const TileCoord tc = decode_tile(tt, blockIdx.x * kTilesPerCta);
        mbar_init(bar_x(bars, 0, 0), 1);
        asm volatile("fence.mbarrier_init.release.cluster;" ::: "memory");
        mbar_arrive_expect_tx(bar_x(bars, 0, 0), kWChunk);
        GT(15);
#pragma unroll 1
        for (int q = 0; q < 3; q++) load_px(tm, tt, sbase + x_chunk(0, q), bar_x(bars, 0, 0), first_line(tc) + q, tc.kind);
        GT(16);
      }
      __syncwarp();
      sched_fence();
      if (wid == 2 && elect_one()) {
        const TileCoord tc = decode_tile(tt, blockIdx.x * kTilesPerCta);
        mbar_init(bar_full(bars, 0, 0), 1);
        asm volatile("fence.mbarrier_init.release.cluster;" ::: "memory");
        mbar_arrive_expect_tx(bar_full(bars, 0, 0), 2 * kChunkBytes);
        asm volatile("prefetch.tensormap [%0];" ::"l"((uint64_t)&tm.u8) : "memory");
        GT(17);
        first_halo(tm, sbase, tc, 0);
        first_halo(tm, sbase, tc, 1);
      }
      __syncwarp();
    }
    sched_fence();
    {
      if (blockIdx.x >= 128 && wqkv != nullptr && (wid | 2) == 2 && elect_one())
        asm volatile("cp.async.bulk.prefetch.L2.global [%0], %1;" ::"l"(wid ? wo + (blockIdx.x & 3) * 48 * 192 : wqkv + (blockIdx.x & 3) * 48 * 576),
                     "r"(wid ? 48 * 384 : 48 * 1152) : "memory");
      __syncwarp();
      if (w2cta) {
        const int q = blockIdx.x & 3, h = wid >> 2;
        uint32_t w2o = 0;
        if (wid == 1 && elect_one()) {
          asm volatile("prefetch.tensormap [%0];" ::"l"((uint64_t)&tm.wo) : "memory");
          mbar_init(bar_raw(bars, 0), 1);
          mbar_init(bar_raw(bars, 1), 1);
          asm volatile("fence.mbarrier_init.release.cluster;" ::: "memory");
#pragma unroll
          for (int j = 0; j < 3; j++)
            asm volatile("cp.async.bulk.tensor.3d.shared::cluster.global.tile.mbarrier::complete_tx::bytes [%0], [%1, {%3, %4, %5}], [%2];" ::"r"(
                             j ? sbase + kW2Off + (j - 1) * (kWBytes / 2) : sbase),
                         "l"((uint64_t)(j ? &tm.wo : &tm.wv)), "r"(bar_raw(bars, j >> 1)), "r"(0), "r"(j ? 0 : 64 * q), "r"(j ? 3 * j - 3 : 6) : "memory");
          mbar_arrive_expect_tx(bar_raw(bars, 0), kWChunk + kWBytes / 2);
          mbar_arrive_expect_tx(bar_raw(bars, 1), kWBytes / 2);
          w2o = w2_offset();
        }
        __syncwarp();
#pragma unroll 1
        for (int r = 1 - h;; r++) {
          if (r > 0) asm volatile("bar.sync 11, 256;" ::: "memory");
          if (r == 2) break;
          if (r > 0) {
            mbar_wait(bar_raw(bars, 0), 0);
            mbar_wait(bar_raw(bars, h), 0);
          }
          if (tid == 0) GT(7);
          float acc[48];
          const uint64_t db = make_desc(sbase + kW2Off + h * (kWBytes / 2), kWChunk / 2, 512, 2);
          wg_fence();
          wg_m96tz<0, 48>(acc, make_desc(sbase, 16, 1024), db, 0);
#pragma unroll
          for (int s = 1; s < 12; s++) wg_m96t<0, 48>(acc, make_desc(sbase + (s >> 2) * 8192 + (s & 3) * 32, 16, 1024), db + s * 64, 1);
          wg_commit();
          wg_wait<0>();
          fence_regs(acc);
          if (tid == 0) GT(19);
          const int m = (tid >> 3) & 3;
#pragma unroll
          for (int j = 0; j < 12; j += 2) {
            const int n = g2_inv(8 * (j + (m >> 1)) + (tid & 7));
            asm volatile("stmatrix.sync.aligned.m8n8.x4.trans.shared.b16 [%0], {%1,%2,%3,%4};" ::"r"(
                             sbase + kW1Off + h * (kWChunk / 2) + n * 128 + (((2 * (wid & 3) + (m & 1)) ^ (n & 7)) << 4)),
                         "r"(pack_bf16(acc[4 * j], acc[4 * j + 1])), "r"(pack_bf16(acc[4 * j + 2], acc[4 * j + 3])),
                         "r"(pack_bf16(acc[4 * j + 4], acc[4 * j + 5])), "r"(pack_bf16(acc[4 * j + 6], acc[4 * j + 7])) : "memory");
          }
          fence_proxy_async();
        }
        if (tid == 0) GT(18);
        if (wid == 1) {
          if (elect_one()) {
#pragma unroll
            for (int i = 0; i < 2; i++)
              asm volatile("cp.async.bulk.global.shared::cta.bulk_group [%0], [%1], %2;" ::"l"(wimg + (w2o + w2piece(i, q) * (kWChunk / 2))),
                           "r"(sbase + kW1Off + i * (kWChunk / 2)), "r"(kWChunk / 2) : "memory");
            asm volatile("cp.async.bulk.commit_group;" ::: "memory");
          }
          __syncwarp();
          asm volatile("bar.arrive 10, 64;" ::: "memory");
          if (elect_one()) asm volatile("cp.async.bulk.wait_group.read 0;" ::: "memory");
          if (tid == 32) GT(31);
          __syncwarp();
          asm volatile("bar.arrive 12, 64;" ::: "memory");
        }
      }
    }
    __syncwarp();
    if (wid < 4) asm volatile("bar.sync 0, 160;" ::: "memory");
    else asm volatile("bar.sync 14, 160;" ::: "memory");
    asm volatile("setmaxnreg.inc.sync.aligned.u32 240;");
    consumer(wid >> 2, out, wimg, sbase, zero, tm, tt);
  }
}

}

typedef CUresult (*PFN_encodeTiled)(CUtensorMap*, CUtensorMapDataType, cuuint32_t, void*, const cuuint64_t*,
                                    const cuuint64_t*, const cuuint32_t*, const cuuint32_t*, CUtensorMapInterleave,
                                    CUtensorMapSwizzle, CUtensorMapL2promotion, CUtensorMapFloatOOBfill);

extern "C" void kernel_launch(void* const* d_in, const int* in_sizes, int n_in, void* d_out, int out_size) {
  const __nv_bfloat16* x = (const __nv_bfloat16*)d_in[0];
  const __nv_bfloat16* wqkv = (const __nv_bfloat16*)d_in[1];
  const __nv_bfloat16* wo = (const __nv_bfloat16*)d_in[2];
  __nv_bfloat16* out = (__nv_bfloat16*)d_out;

  static PFN_encodeTiled encode = nullptr;
  static int num_sms = 0;
  static uint8_t* wimg = nullptr;
  if (!encode) {
    void* fn = nullptr;
    cudaDriverEntryPointQueryResult qres;
    cudaGetDriverEntryPoint("cuTensorMapEncodeTiled", &fn, cudaEnableDefault, &qres);
    encode = (PFN_encodeTiled)fn;
    cudaFuncSetAttribute(nat::nat_kernel, cudaFuncAttributeMaxDynamicSharedMemorySize, nat::kSmemBytes);
    cudaGetSymbolAddress((void**)&wimg, nat::g_wimg32);
    int dev = 0;
    cudaGetDevice(&dev);
    cudaDeviceGetAttribute(&num_sms, cudaDevAttrMultiProcessorCount, dev);
  }
  nat::Maps tm;
  cuuint32_t estr[5] = {1, 1, 1, 1, 1};
  {
    cuuint64_t vdim[5] = {48, 2, 105, 2, 112}, udim[5] = {48, 2, 112, 2, 105};
    cuuint64_t vstr[4] = {7 * 768, 768, 224 * 384, 2 * 224 * 384}, ustr[4] = {7 * 768, 2 * 224 * 384, 224 * 384, 768};
    CUtensorMap* maps[4] = {&tm.v6, &tm.v2, &tm.v14, &tm.u8};
    for (int i = 0; i < 4; i++) {
      cuuint32_t box[5] = {4, 2, i < 3 ? 4u : 8u, 1, i == 0 ? 6u : i == 1 ? 2u : i == 2 ? 14u : 3u};
      encode(maps[i], CU_TENSOR_MAP_DATA_TYPE_UINT32, 5, (void*)x, i < 3 ? vdim : udim, i < 3 ? vstr : ustr, box, estr,
             CU_TENSOR_MAP_INTERLEAVE_16B, CU_TENSOR_MAP_SWIZZLE_128B, CU_TENSOR_MAP_L2_PROMOTION_L2_128B, CU_TENSOR_MAP_FLOAT_OOB_FILL_NONE);
    }
  }
  for (int i = 0; i < 8; i++) {
    const cuuint32_t row = 224 * 384;
    const cuuint32_t shape[8][6] = {{2, 8, 4, 2 * row, 768, 4 * row}, {2, 8, 3, row, 768, 2 * row},     {2, 8, 1, 2 * row, 768, 4 * row},
                                    {8, 2, 3, 2 * row, 4 * 384, 384}, {8, 2, 1, 2 * row, 5 * 384, 384}, {4, 2, 3, 4 * row, 2 * row, 128},
                                    {4, 2, 3, 768, row, 128},         {4, 2, 3, 768, 2 * row, 128}};
    const cuuint32_t* sh = shape[i];
    cuuint64_t dim[5] = {64, sh[0], sh[1], sh[2], 224 * 224 * 3};
    cuuint64_t str[4] = {sh[3], sh[4], sh[5], 128};
    cuuint32_t box[5] = {64, sh[0], sh[1], sh[2], 1};
    encode(tm.px + i, CU_TENSOR_MAP_DATA_TYPE_BFLOAT16, 5, i < 5 ? (void*)x : (void*)out, dim, str, box, estr, CU_TENSOR_MAP_INTERLEAVE_NONE,
           CU_TENSOR_MAP_SWIZZLE_128B, i < 5 ? CU_TENSOR_MAP_L2_PROMOTION_L2_128B : CU_TENSOR_MAP_L2_PROMOTION_NONE,
           CU_TENSOR_MAP_FLOAT_OOB_FILL_NONE);
  }
  for (int i = 0; i < 2; i++) {
    cuuint64_t dim[3] = {i ? 32u : 64u, 192, i ? 6u : 9u}, str[2] = {i ? 384u : 1152u, i ? 64u : 128u};
    cuuint32_t box[3] = {i ? 32u : 64u, i ? 192u : 64u, 3};
    encode(i ? &tm.wo : &tm.wv, CU_TENSOR_MAP_DATA_TYPE_BFLOAT16, 3, i ? (void*)wo : (void*)wqkv, dim, str, box, estr,
           CU_TENSOR_MAP_INTERLEAVE_NONE, i ? CU_TENSOR_MAP_SWIZZLE_64B : CU_TENSOR_MAP_SWIZZLE_128B, CU_TENSOR_MAP_L2_PROMOTION_L2_256B,
           CU_TENSOR_MAP_FLOAT_OOB_FILL_NONE);
  }
  nat::TileTable tt;
  nat::make_tiles(tt);
  const int grid = nat::kCtas;
  if (num_sms >= grid) {
    nat::nat_kernel<<<grid, 384, nat::kSmemBytes>>>(x, out, wqkv, wo, wimg, 0u, tm, tt);
  } else {
    nat::fold_kernel<<<27, 256>>>(wqkv, wo, wimg);
    nat::nat_kernel<<<grid, 384, nat::kSmemBytes>>>(x, out, nullptr, nullptr, wimg, 0u, tm, tt);
  }
}
```

```cpp
#include <cuda_runtime.h>
#include <cuda_bf16.h>
#include <cuda.h>
#include <stdint.h>

#define NAT_TM 1300
#define NAT_HP 1800
#define NAT_T0 2130
#define NAT_TD 1250
#define NAT_TX2 3800
#define NAT_TW2 4600
#define NAT_PFD 300
#define NAT_XW 200
#define NAT_PK 3
namespace nat {

constexpr int kW = 224, kC = 192;
constexpr int kCtas = 132;
constexpr int kTilesPerCta = 6;
constexpr float kAlpha = 0.07216878364870322f * 1.4426950408889634f;
constexpr uint32_t kChunkBytes = 13 * 1024;
constexpr uint32_t kWChunk = 192 * 128;
constexpr uint32_t kWBytes = 3 * kWChunk;
constexpr uint32_t kW1Off = 6 * kChunkBytes;
constexpr uint32_t kW2Off = kW1Off + kWBytes;
constexpr uint32_t kXOff = kW2Off + kWChunk;
constexpr uint32_t kBarOff = kW2Off + kWBytes;
constexpr uint32_t kProfOff = kBarOff + 208;
constexpr uint32_t kSmemBytes = kBarOff + 1024 + 4096;

static_assert(kW1Off % 1024 == 0 && kW2Off % 1024 == 0 && kChunkBytes % 1024 == 0, "swizzle alignment");
static_assert(kSmemBytes <= 232448, "smem");

constexpr uint32_t kEmpty = 0xFFFFFFFFu;
#define NAT_R8(v) v, v, v, v, v, v, v, v
#define NAT_R2K(v) NAT_R8(NAT_R8(NAT_R8(v))), NAT_R8(NAT_R8(NAT_R8(v))), NAT_R8(NAT_R8(NAT_R8(v))), NAT_R8(NAT_R8(NAT_R8(v)))
#define NAT_IMG NAT_R8(NAT_R2K(kEmpty)), NAT_R2K(kEmpty)
__device__ __align__(1024) uint32_t g_wimg32[3 * kWBytes / 4] = {NAT_IMG, NAT_IMG, NAT_IMG};
static_assert(kWBytes / 4 == 9 * 2048, "initialiser");
__device__ __align__(128) uint32_t g_flag[64];
__device__ __forceinline__ uint32_t w2_offset() {
  uint32_t v;
  asm volatile("ld.relaxed.gpu.global.u32 %0, [%1];" : "=r"(v) : "l"(g_flag + 32) : "memory");
  return (1 + v) * kWBytes;
}

#define PROFS(id, wgid, slotid) do { } while (0)
#define PROF(wgid, slotid) do { } while (0)
#define PROF_DUMP(wgid) do { } while (0)

#define GT(slotid) do { } while (0)
#define GT_DUMP() do { } while (0)

__device__ __forceinline__ uint32_t smem_u32(const void* p) { return (uint32_t)__cvta_generic_to_shared(p); }

__device__ __forceinline__ void mbar_init(uint32_t bar, uint32_t count) {
  asm volatile("mbarrier.init.shared::cta.b64 [%0], %1;" ::"r"(bar), "r"(count) : "memory");
}
__device__ __forceinline__ void mbar_arrive(uint32_t bar) {
  asm volatile("mbarrier.arrive.shared::cta.b64 _, [%0];" ::"r"(bar) : "memory");
}
__device__ __forceinline__ void mbar_arrive_expect_tx(uint32_t bar, uint32_t bytes) {
  asm volatile("mbarrier.arrive.expect_tx.shared::cta.b64 _, [%0], %1;" ::"r"(bar), "r"(bytes) : "memory");
}
__device__ __forceinline__ void mbar_wait(uint32_t bar, uint32_t parity) {
  uint32_t ok;
  uint32_t it = 0;
  do {
    asm volatile(
        "{\n.reg .pred p;\n"
        "mbarrier.try_wait.parity.shared::cta.b64 p, [%1], %2;\n"
        "selp.u32 %0, 1, 0, p;\n}\n"
        : "=r"(ok)
        : "r"(bar), "r"(parity)
        : "memory");
    if (++it > (1u << 24)) break;
  } while (!ok);
}
__device__ __forceinline__ uint32_t mbar_test(uint32_t bar, uint32_t parity) {
  uint32_t ok;
  asm volatile("{\n.reg .pred p;\nmbarrier.test_wait.parity.shared::cta.b64 p, [%1], %2;\nselp.u32 %0, 1, 0, p;\n}\n"
               : "=r"(ok) : "r"(bar), "r"(parity) : "memory");
  return ok;
}
__device__ __forceinline__ void mbar_wait_if(uint32_t ok, uint32_t bar, uint32_t parity) {
  if (!__all_sync(0xffffffffu, ok)) mbar_wait(bar, parity);
}
__device__ __forceinline__ bool elect_one() {
  uint32_t r;
  asm volatile("{\n.reg .pred p;\nelect.sync _|p, 0xffffffff;\nselp.u32 %0, 1, 0, p;\n}\n" : "=r"(r));
  return r != 0;
}
__device__ __forceinline__ void nb_arrive(int id) { asm volatile("bar.arrive %0, 256;" ::"r"(id) : "memory"); }
__device__ __forceinline__ void nb_sync(int id) { asm volatile("bar.sync %0, 256;" ::"r"(id) : "memory"); }
__device__ __forceinline__ void nb_arrive_p(int id) { asm volatile("bar.arrive %0, 160;" ::"r"(id) : "memory"); }
__device__ __forceinline__ void nb_sync_p(int id) { asm volatile("bar.sync %0, 160;" ::"r"(id) : "memory"); }
__device__ __forceinline__ void fence_proxy_async() { asm volatile("fence.proxy.async.shared::cta;" ::: "memory"); }

__device__ __forceinline__ void tma_load_5d(uint32_t dst, const CUtensorMap* map, uint32_t bar, int c0, int c1, int c2,
                                            int c3, int c4) {
  asm volatile(
      "cp.async.bulk.tensor.5d.shared::cluster.global.tile.mbarrier::complete_tx::bytes "
      "[%0], [%1, {%3, %4, %5, %6, %7}], [%2];"
      ::"r"(dst), "l"((uint64_t)map), "r"(bar), "r"(c0), "r"(c1), "r"(c2), "r"(c3), "r"(c4)
      : "memory");
}
__device__ __forceinline__ void bulk_load(uint32_t dst, const void* src, uint32_t bytes, uint32_t bar) {
  asm volatile("cp.async.bulk.shared::cluster.global.mbarrier::complete_tx::bytes [%0], [%1], %2, [%3];"
               ::"r"(dst), "l"((uint64_t)src), "r"(bytes), "r"(bar)
               : "memory");
}

__device__ __forceinline__ void wg_fence() { asm volatile("wgmma.fence.sync.aligned;" ::: "memory"); }
__device__ __forceinline__ void wg_commit() { asm volatile("wgmma.commit_group.sync.aligned;" ::: "memory"); }
template <int N>
__device__ __forceinline__ void wg_wait() { asm volatile("wgmma.wait_group.sync.aligned %0;" ::"n"(N) : "memory"); }

template <int N>
__device__ __forceinline__ void fence_regs(float (&d)[N]) {
#pragma unroll
  for (int i = 0; i < N; i++) asm volatile("" : "+f"(d[i])::"memory");
}
template <int N>
__device__ __forceinline__ void keep_regs(uint32_t (&d)[N]) {
#pragma unroll
  for (int i = 0; i < N; i++) asm volatile("" : "+r"(d[i])::"memory");
}

__device__ __forceinline__ uint32_t pack_bf16(float lo, float hi) {
  uint32_t d;
  asm("cvt.rn.bf16x2.f32 %0, %1, %2;" : "=r"(d) : "f"(hi), "f"(lo));
  return d;
}
__device__ __forceinline__ float ex2(float x) {
  float y;
  asm("ex2.approx.ftz.f32 %0, %1;" : "=f"(y) : "f"(x));
  return y;
}
__device__ __forceinline__ float rcp_approx(float x) {
  float y;
  asm("rcp.approx.ftz.f32 %0, %1;" : "=f"(y) : "f"(x));
  return y;
}
__device__ __forceinline__ uint4 ldg128_nc(const void* p) {
  uint4 v;
  asm volatile("ld.global.nc.v4.u32 {%0,%1,%2,%3}, [%4];" : "=r"(v.x), "=r"(v.y), "=r"(v.z), "=r"(v.w) : "l"(p));
  return v;
}

__device__ __forceinline__ long long clk64() {
  long long c;
  asm volatile("mov.u64 %0, %clock64;" : "=l"(c)::"memory");
  return c;
}
__device__ __forceinline__ void sched_fence() { while (clk64() < 0) { } }

__device__ __forceinline__ uint64_t make_desc(uint32_t addr, uint32_t lbo, uint32_t sbo, uint32_t mode = 1) {
  return (uint64_t)((addr & 0x3FFFF) >> 4) | ((uint64_t)(lbo >> 4) << 16) | ((uint64_t)(sbo >> 4) << 32) |
         ((uint64_t)mode << 62);
}

template <int OFF, int NN>
__device__ __forceinline__ void wg_m192(float (&d)[NN], uint64_t desc_a, uint64_t desc_b, int scale_d) {
  asm volatile(
      "{\n.reg .pred p;\nsetp.ne.b32 p, %98, 0;\n"
      "wgmma.mma_async.sync.aligned.m64n192k16.f32.bf16.bf16 "
      "{%0,%1,%2,%3,%4,%5,%6,%7,%8,%9,%10,%11,%12,%13,%14,%15,"
      "%16,%17,%18,%19,%20,%21,%22,%23,%24,%25,%26,%27,%28,%29,%30,%31,"
      "%32,%33,%34,%35,%36,%37,%38,%39,%40,%41,%42,%43,%44,%45,%46,%47,"
      "%48,%49,%50,%51,%52,%53,%54,%55,%56,%57,%58,%59,%60,%61,%62,%63,"
      "%64,%65,%66,%67,%68,%69,%70,%71,%72,%73,%74,%75,%76,%77,%78,%79,"
      "%80,%81,%82,%83,%84,%85,%86,%87,%88,%89,%90,%91,%92,%93,%94,%95}, "
      "%96, %97, p, 1, 1, 0, 0;\n}\n"
      : "+f"(d[OFF + 0]), "+f"(d[OFF + 1]), "+f"(d[OFF + 2]), "+f"(d[OFF + 3]), "+f"(d[OFF + 4]), "+f"(d[OFF + 5]),
        "+f"(d[OFF + 6]), "+f"(d[OFF + 7]), "+f"(d[OFF + 8]), "+f"(d[OFF + 9]), "+f"(d[OFF + 10]), "+f"(d[OFF + 11]),
        "+f"(d[OFF + 12]), "+f"(d[OFF + 13]), "+f"(d[OFF + 14]), "+f"(d[OFF + 15]), "+f"(d[OFF + 16]), "+f"(d[OFF + 17]),
        "+f"(d[OFF + 18]), "+f"(d[OFF + 19]), "+f"(d[OFF + 20]), "+f"(d[OFF + 21]), "+f"(d[OFF + 22]), "+f"(d[OFF + 23]),
        "+f"(d[OFF + 24]), "+f"(d[OFF + 25]), "+f"(d[OFF + 26]), "+f"(d[OFF + 27]), "+f"(d[OFF + 28]), "+f"(d[OFF + 29]),
        "+f"(d[OFF + 30]), "+f"(d[OFF + 31]), "+f"(d[OFF + 32]), "+f"(d[OFF + 33]), "+f"(d[OFF + 34]), "+f"(d[OFF + 35]),
        "+f"(d[OFF + 36]), "+f"(d[OFF + 37]), "+f"(d[OFF + 38]), "+f"(d[OFF + 39]), "+f"(d[OFF + 40]), "+f"(d[OFF + 41]),
        "+f"(d[OFF + 42]), "+f"(d[OFF + 43]), "+f"(d[OFF + 44]), "+f"(d[OFF + 45]), "+f"(d[OFF + 46]), "+f"(d[OFF + 47]),
        "+f"(d[OFF + 48]), "+f"(d[OFF + 49]), "+f"(d[OFF + 50]), "+f"(d[OFF + 51]), "+f"(d[OFF + 52]), "+f"(d[OFF + 53]),
        "+f"(d[OFF + 54]), "+f"(d[OFF + 55]), "+f"(d[OFF + 56]), "+f"(d[OFF + 57]), "+f"(d[OFF + 58]), "+f"(d[OFF + 59]),
        "+f"(d[OFF + 60]), "+f"(d[OFF + 61]), "+f"(d[OFF + 62]), "+f"(d[OFF + 63]), "+f"(d[OFF + 64]), "+f"(d[OFF + 65]),
        "+f"(d[OFF + 66]), "+f"(d[OFF + 67]), "+f"(d[OFF + 68]), "+f"(d[OFF + 69]), "+f"(d[OFF + 70]), "+f"(d[OFF + 71]),
        "+f"(d[OFF + 72]), "+f"(d[OFF + 73]), "+f"(d[OFF + 74]), "+f"(d[OFF + 75]), "+f"(d[OFF + 76]), "+f"(d[OFF + 77]),
        "+f"(d[OFF + 78]), "+f"(d[OFF + 79]), "+f"(d[OFF + 80]), "+f"(d[OFF + 81]), "+f"(d[OFF + 82]), "+f"(d[OFF + 83]),
        "+f"(d[OFF + 84]), "+f"(d[OFF + 85]), "+f"(d[OFF + 86]), "+f"(d[OFF + 87]), "+f"(d[OFF + 88]), "+f"(d[OFF + 89]),
        "+f"(d[OFF + 90]), "+f"(d[OFF + 91]), "+f"(d[OFF + 92]), "+f"(d[OFF + 93]), "+f"(d[OFF + 94]), "+f"(d[OFF + 95])
      : "l"(desc_a), "l"(desc_b), "r"(scale_d));
}

template <int OFF, int NN>
__device__ __forceinline__ void wg_m192z(float (&d)[NN], uint64_t desc_a, uint64_t desc_b, int scale_d) {
  asm volatile(
      "{\n.reg .pred p;\nsetp.ne.b32 p, %98, 0;\n"
      "wgmma.mma_async.sync.aligned.m64n192k16.f32.bf16.bf16 "
      "{%0,%1,%2,%3,%4,%5,%6,%7,%8,%9,%10,%11,%12,%13,%14,%15,"
      "%16,%17,%18,%19,%20,%21,%22,%23,%24,%25,%26,%27,%28,%29,%30,%31,"
      "%32,%33,%34,%35,%36,%37,%38,%39,%40,%41,%42,%43,%44,%45,%46,%47,"
      "%48,%49,%50,%51,%52,%53,%54,%55,%56,%57,%58,%59,%60,%61,%62,%63,"
      "%64,%65,%66,%67,%68,%69,%70,%71,%72,%73,%74,%75,%76,%77,%78,%79,"
      "%80,%81,%82,%83,%84,%85,%86,%87,%88,%89,%90,%91,%92,%93,%94,%95}, "
      "%96, %97, p, 1, 1, 0, 0;\n}\n"
      : "=f"(d[OFF + 0]), "=f"(d[OFF + 1]), "=f"(d[OFF + 2]), "=f"(d[OFF + 3]), "=f"(d[OFF + 4]), "=f"(d[OFF + 5]),
        "=f"(d[OFF + 6]), "=f"(d[OFF + 7]), "=f"(d[OFF + 8]), "=f"(d[OFF + 9]), "=f"(d[OFF + 10]), "=f"(d[OFF + 11]),
        "=f"(d[OFF + 12]), "=f"(d[OFF + 13]), "=f"(d[OFF + 14]), "=f"(d[OFF + 15]), "=f"(d[OFF + 16]), "=f"(d[OFF + 17]),
        "=f"(d[OFF + 18]), "=f"(d[OFF + 19]), "=f"(d[OFF + 20]), "=f"(d[OFF + 21]), "=f"(d[OFF + 22]), "=f"(d[OFF + 23]),
        "=f"(d[OFF + 24]), "=f"(d[OFF + 25]), "=f"(d[OFF + 26]), "=f"(d[OFF + 27]), "=f"(d[OFF + 28]), "=f"(d[OFF + 29]),
        "=f"(d[OFF + 30]), "=f"(d[OFF + 31]), "=f"(d[OFF + 32]), "=f"(d[OFF + 33]), "=f"(d[OFF + 34]), "=f"(d[OFF + 35]),
        "=f"(d[OFF + 36]), "=f"(d[OFF + 37]), "=f"(d[OFF + 38]), "=f"(d[OFF + 39]), "=f"(d[OFF + 40]), "=f"(d[OFF + 41]),
        "=f"(d[OFF + 42]), "=f"(d[OFF + 43]), "=f"(d[OFF + 44]), "=f"(d[OFF + 45]), "=f"(d[OFF + 46]), "=f"(d[OFF + 47]),
        "=f"(d[OFF + 48]), "=f"(d[OFF + 49]), "=f"(d[OFF + 50]), "=f"(d[OFF + 51]), "=f"(d[OFF + 52]), "=f"(d[OFF + 53]),
        "=f"(d[OFF + 54]), "=f"(d[OFF + 55]), "=f"(d[OFF + 56]), "=f"(d[OFF + 57]), "=f"(d[OFF + 58]), "=f"(d[OFF + 59]),
        "=f"(d[OFF + 60]), "=f"(d[OFF + 61]), "=f"(d[OFF + 62]), "=f"(d[OFF + 63]), "=f"(d[OFF + 64]), "=f"(d[OFF + 65]),
        "=f"(d[OFF + 66]), "=f"(d[OFF + 67]), "=f"(d[OFF + 68]), "=f"(d[OFF + 69]), "=f"(d[OFF + 70]), "=f"(d[OFF + 71]),
        "=f"(d[OFF + 72]), "=f"(d[OFF + 73]), "=f"(d[OFF + 74]), "=f"(d[OFF + 75]), "=f"(d[OFF + 76]), "=f"(d[OFF + 77]),
        "=f"(d[OFF + 78]), "=f"(d[OFF + 79]), "=f"(d[OFF + 80]), "=f"(d[OFF + 81]), "=f"(d[OFF + 82]), "=f"(d[OFF + 83]),
        "=f"(d[OFF + 84]), "=f"(d[OFF + 85]), "=f"(d[OFF + 86]), "=f"(d[OFF + 87]), "=f"(d[OFF + 88]), "=f"(d[OFF + 89]),
        "=f"(d[OFF + 90]), "=f"(d[OFF + 91]), "=f"(d[OFF + 92]), "=f"(d[OFF + 93]), "=f"(d[OFF + 94]), "=f"(d[OFF + 95])
      : "l"(desc_a), "l"(desc_b), "r"(scale_d));
}

template <int OFF, int NN>
__device__ __forceinline__ void wg_m96t(float (&d)[NN], uint64_t desc_a, uint64_t desc_b, int scale_d) {
  asm volatile(
      "{\n.reg .pred p;\nsetp.ne.b32 p, %50, 0;\n"
      "wgmma.mma_async.sync.aligned.m64n96k16.f32.bf16.bf16 "
      "{%0,%1,%2,%3,%4,%5,%6,%7,%8,%9,%10,%11,%12,%13,%14,%15,"
      "%16,%17,%18,%19,%20,%21,%22,%23,%24,%25,%26,%27,%28,%29,%30,%31,"
      "%32,%33,%34,%35,%36,%37,%38,%39,%40,%41,%42,%43,%44,%45,%46,%47}, "
      "%48, %49, p, 1, 1, 0, 1;\n}\n"
      : "+f"(d[OFF + 0]), "+f"(d[OFF + 1]), "+f"(d[OFF + 2]), "+f"(d[OFF + 3]), "+f"(d[OFF + 4]), "+f"(d[OFF + 5]),
        "+f"(d[OFF + 6]), "+f"(d[OFF + 7]), "+f"(d[OFF + 8]), "+f"(d[OFF + 9]), "+f"(d[OFF + 10]), "+f"(d[OFF + 11]),
        "+f"(d[OFF + 12]), "+f"(d[OFF + 13]), "+f"(d[OFF + 14]), "+f"(d[OFF + 15]), "+f"(d[OFF + 16]), "+f"(d[OFF + 17]),
        "+f"(d[OFF + 18]), "+f"(d[OFF + 19]), "+f"(d[OFF + 20]), "+f"(d[OFF + 21]), "+f"(d[OFF + 22]), "+f"(d[OFF + 23]),
        "+f"(d[OFF + 24]), "+f"(d[OFF + 25]), "+f"(d[OFF + 26]), "+f"(d[OFF + 27]), "+f"(d[OFF + 28]), "+f"(d[OFF + 29]),
        "+f"(d[OFF + 30]), "+f"(d[OFF + 31]), "+f"(d[OFF + 32]), "+f"(d[OFF + 33]), "+f"(d[OFF + 34]), "+f"(d[OFF + 35]),
        "+f"(d[OFF + 36]), "+f"(d[OFF + 37]), "+f"(d[OFF + 38]), "+f"(d[OFF + 39]), "+f"(d[OFF + 40]), "+f"(d[OFF + 41]),
        "+f"(d[OFF + 42]), "+f"(d[OFF + 43]), "+f"(d[OFF + 44]), "+f"(d[OFF + 45]), "+f"(d[OFF + 46]), "+f"(d[OFF + 47])
      : "l"(desc_a), "l"(desc_b), "r"(scale_d));
}

template <int OFF, int NN>
__device__ __forceinline__ void wg_m96tz(float (&d)[NN], uint64_t desc_a, uint64_t desc_b, int scale_d) {
  asm volatile(
      "{\n.reg .pred p;\nsetp.ne.b32 p, %50, 0;\n"
      "wgmma.mma_async.sync.aligned.m64n96k16.f32.bf16.bf16 "
      "{%0,%1,%2,%3,%4,%5,%6,%7,%8,%9,%10,%11,%12,%13,%14,%15,"
      "%16,%17,%18,%19,%20,%21,%22,%23,%24,%25,%26,%27,%28,%29,%30,%31,"
      "%32,%33,%34,%35,%36,%37,%38,%39,%40,%41,%42,%43,%44,%45,%46,%47}, "
      "%48, %49, p, 1, 1, 0, 1;\n}\n"
      : "=f"(d[OFF + 0]), "=f"(d[OFF + 1]), "=f"(d[OFF + 2]), "=f"(d[OFF + 3]), "=f"(d[OFF + 4]), "=f"(d[OFF + 5]),
        "=f"(d[OFF + 6]), "=f"(d[OFF + 7]), "=f"(d[OFF + 8]), "=f"(d[OFF + 9]), "=f"(d[OFF + 10]), "=f"(d[OFF + 11]),
        "=f"(d[OFF + 12]), "=f"(d[OFF + 13]), "=f"(d[OFF + 14]), "=f"(d[OFF + 15]), "=f"(d[OFF + 16]), "=f"(d[OFF + 17]),
        "=f"(d[OFF + 18]), "=f"(d[OFF + 19]), "=f"(d[OFF + 20]), "=f"(d[OFF + 21]), "=f"(d[OFF + 22]), "=f"(d[OFF + 23]),
        "=f"(d[OFF + 24]), "=f"(d[OFF + 25]), "=f"(d[OFF + 26]), "=f"(d[OFF + 27]), "=f"(d[OFF + 28]), "=f"(d[OFF + 29]),
        "=f"(d[OFF + 30]), "=f"(d[OFF + 31]), "=f"(d[OFF + 32]), "=f"(d[OFF + 33]), "=f"(d[OFF + 34]), "=f"(d[OFF + 35]),
        "=f"(d[OFF + 36]), "=f"(d[OFF + 37]), "=f"(d[OFF + 38]), "=f"(d[OFF + 39]), "=f"(d[OFF + 40]), "=f"(d[OFF + 41]),
        "=f"(d[OFF + 42]), "=f"(d[OFF + 43]), "=f"(d[OFF + 44]), "=f"(d[OFF + 45]), "=f"(d[OFF + 46]), "=f"(d[OFF + 47])
      : "l"(desc_a), "l"(desc_b), "r"(scale_d));
}

template <int OFF, int NN>
__device__ __forceinline__ void wg_d96(float (&d)[NN], uint32_t a0, uint32_t a1, uint32_t a2, uint32_t a3,
                                       uint64_t desc_b, int scale_d) {
  asm volatile(
      "{\n.reg .pred p;\nsetp.ne.b32 p, %53, 0;\n"
      "wgmma.mma_async.sync.aligned.m64n96k16.f32.bf16.bf16 "
      "{%0,%1,%2,%3,%4,%5,%6,%7,%8,%9,%10,%11,%12,%13,%14,%15,"
      "%16,%17,%18,%19,%20,%21,%22,%23,%24,%25,%26,%27,%28,%29,%30,%31,"
      "%32,%33,%34,%35,%36,%37,%38,%39,%40,%41,%42,%43,%44,%45,%46,%47}, "
      "{%48,%49,%50,%51}, %52, p, 1, 1, 0;\n}\n"
      : "+f"(d[OFF + 0]), "+f"(d[OFF + 1]), "+f"(d[OFF + 2]), "+f"(d[OFF + 3]), "+f"(d[OFF + 4]), "+f"(d[OFF + 5]),
        "+f"(d[OFF + 6]), "+f"(d[OFF + 7]), "+f"(d[OFF + 8]), "+f"(d[OFF + 9]), "+f"(d[OFF + 10]), "+f"(d[OFF + 11]),
        "+f"(d[OFF + 12]), "+f"(d[OFF + 13]), "+f"(d[OFF + 14]), "+f"(d[OFF + 15]), "+f"(d[OFF + 16]), "+f"(d[OFF + 17]),
        "+f"(d[OFF + 18]), "+f"(d[OFF + 19]), "+f"(d[OFF + 20]), "+f"(d[OFF + 21]), "+f"(d[OFF + 22]), "+f"(d[OFF + 23]),
        "+f"(d[OFF + 24]), "+f"(d[OFF + 25]), "+f"(d[OFF + 26]), "+f"(d[OFF + 27]), "+f"(d[OFF + 28]), "+f"(d[OFF + 29]),
        "+f"(d[OFF + 30]), "+f"(d[OFF + 31]), "+f"(d[OFF + 32]), "+f"(d[OFF + 33]), "+f"(d[OFF + 34]), "+f"(d[OFF + 35]),
        "+f"(d[OFF + 36]), "+f"(d[OFF + 37]), "+f"(d[OFF + 38]), "+f"(d[OFF + 39]), "+f"(d[OFF + 40]), "+f"(d[OFF + 41]),
        "+f"(d[OFF + 42]), "+f"(d[OFF + 43]), "+f"(d[OFF + 44]), "+f"(d[OFF + 45]), "+f"(d[OFF + 46]), "+f"(d[OFF + 47])
      : "r"(a0), "r"(a1), "r"(a2), "r"(a3), "l"(desc_b), "r"(scale_d));
}

template <int OFF, int NN>
__device__ __forceinline__ void wg_d96z(float (&d)[NN], uint32_t a0, uint32_t a1, uint32_t a2, uint32_t a3,
                                       uint64_t desc_b, int scale_d) {
  asm volatile(
      "{\n.reg .pred p;\nsetp.ne.b32 p, %53, 0;\n"
      "wgmma.mma_async.sync.aligned.m64n96k16.f32.bf16.bf16 "
      "{%0,%1,%2,%3,%4,%5,%6,%7,%8,%9,%10,%11,%12,%13,%14,%15,"
      "%16,%17,%18,%19,%20,%21,%22,%23,%24,%25,%26,%27,%28,%29,%30,%31,"
      "%32,%33,%34,%35,%36,%37,%38,%39,%40,%41,%42,%43,%44,%45,%46,%47}, "
      "{%48,%49,%50,%51}, %52, p, 1, 1, 0;\n}\n"
      : "=f"(d[OFF + 0]), "=f"(d[OFF + 1]), "=f"(d[OFF + 2]), "=f"(d[OFF + 3]), "=f"(d[OFF + 4]), "=f"(d[OFF + 5]),
        "=f"(d[OFF + 6]), "=f"(d[OFF + 7]), "=f"(d[OFF + 8]), "=f"(d[OFF + 9]), "=f"(d[OFF + 10]), "=f"(d[OFF + 11]),
        "=f"(d[OFF + 12]), "=f"(d[OFF + 13]), "=f"(d[OFF + 14]), "=f"(d[OFF + 15]), "=f"(d[OFF + 16]), "=f"(d[OFF + 17]),
        "=f"(d[OFF + 18]), "=f"(d[OFF + 19]), "=f"(d[OFF + 20]), "=f"(d[OFF + 21]), "=f"(d[OFF + 22]), "=f"(d[OFF + 23]),
        "=f"(d[OFF + 24]), "=f"(d[OFF + 25]), "=f"(d[OFF + 26]), "=f"(d[OFF + 27]), "=f"(d[OFF + 28]), "=f"(d[OFF + 29]),
        "=f"(d[OFF + 30]), "=f"(d[OFF + 31]), "=f"(d[OFF + 32]), "=f"(d[OFF + 33]), "=f"(d[OFF + 34]), "=f"(d[OFF + 35]),
        "=f"(d[OFF + 36]), "=f"(d[OFF + 37]), "=f"(d[OFF + 38]), "=f"(d[OFF + 39]), "=f"(d[OFF + 40]), "=f"(d[OFF + 41]),
        "=f"(d[OFF + 42]), "=f"(d[OFF + 43]), "=f"(d[OFF + 44]), "=f"(d[OFF + 45]), "=f"(d[OFF + 46]), "=f"(d[OFF + 47])
      : "r"(a0), "r"(a1), "r"(a2), "r"(a3), "l"(desc_b), "r"(scale_d));
}

template <int OFF, int NN>
__device__ __forceinline__ void wg_s104(float (&d)[NN], uint32_t a0, uint32_t a1, uint32_t a2, uint32_t a3,
                                       uint64_t desc_b, int scale_d, uint32_t meta) {
  asm volatile(
      "{\n.reg .pred p;\nsetp.ne.b32 p, %57, 0;\n"
      "wgmma.mma_async.sp.sync.aligned.m64n104k32.f32.bf16.bf16 "
      "{%0,%1,%2,%3,%4,%5,%6,%7,%8,%9,%10,%11,%12,%13,%14,%15,"
      "%16,%17,%18,%19,%20,%21,%22,%23,%24,%25,%26,%27,%28,%29,%30,%31,"
      "%32,%33,%34,%35,%36,%37,%38,%39,%40,%41,%42,%43,%44,%45,%46,%47,"
      "%48,%49,%50,%51}, "
      "{%52,%53,%54,%55}, %56, %58, 0, p, 1, 1, 0;\n}\n"
      : "+f"(d[OFF + 0]), "+f"(d[OFF + 1]), "+f"(d[OFF + 2]), "+f"(d[OFF + 3]), "+f"(d[OFF + 4]), "+f"(d[OFF + 5]),
        "+f"(d[OFF + 6]), "+f"(d[OFF + 7]), "+f"(d[OFF + 8]), "+f"(d[OFF + 9]), "+f"(d[OFF + 10]), "+f"(d[OFF + 11]),
        "+f"(d[OFF + 12]), "+f"(d[OFF + 13]), "+f"(d[OFF + 14]), "+f"(d[OFF + 15]), "+f"(d[OFF + 16]), "+f"(d[OFF + 17]),
        "+f"(d[OFF + 18]), "+f"(d[OFF + 19]), "+f"(d[OFF + 20]), "+f"(d[OFF + 21]), "+f"(d[OFF + 22]), "+f"(d[OFF + 23]),
        "+f"(d[OFF + 24]), "+f"(d[OFF + 25]), "+f"(d[OFF + 26]), "+f"(d[OFF + 27]), "+f"(d[OFF + 28]), "+f"(d[OFF + 29]),
        "+f"(d[OFF + 30]), "+f"(d[OFF + 31]), "+f"(d[OFF + 32]), "+f"(d[OFF + 33]), "+f"(d[OFF + 34]), "+f"(d[OFF + 35]),
        "+f"(d[OFF + 36]), "+f"(d[OFF + 37]), "+f"(d[OFF + 38]), "+f"(d[OFF + 39]), "+f"(d[OFF + 40]), "+f"(d[OFF + 41]),
        "+f"(d[OFF + 42]), "+f"(d[OFF + 43]), "+f"(d[OFF + 44]), "+f"(d[OFF + 45]), "+f"(d[OFF + 46]), "+f"(d[OFF + 47]),
        "+f"(d[OFF + 48]), "+f"(d[OFF + 49]), "+f"(d[OFF + 50]), "+f"(d[OFF + 51])
      : "r"(a0), "r"(a1), "r"(a2), "r"(a3), "l"(desc_b), "r"(scale_d), "r"(meta));
}

template <int OFF, int NN>
__device__ __forceinline__ void wg_s104z(float (&d)[NN], uint32_t a0, uint32_t a1, uint32_t a2, uint32_t a3,
                                       uint64_t desc_b, int scale_d, uint32_t meta) {
  asm volatile(
      "{\n.reg .pred p;\nsetp.ne.b32 p, %57, 0;\n"
      "wgmma.mma_async.sp.sync.aligned.m64n104k32.f32.bf16.bf16 "
      "{%0,%1,%2,%3,%4,%5,%6,%7,%8,%9,%10,%11,%12,%13,%14,%15,"
      "%16,%17,%18,%19,%20,%21,%22,%23,%24,%25,%26,%27,%28,%29,%30,%31,"
      "%32,%33,%34,%35,%36,%37,%38,%39,%40,%41,%42,%43,%44,%45,%46,%47,"
      "%48,%49,%50,%51}, "
      "{%52,%53,%54,%55}, %56, %58, 0, p, 1, 1, 0;\n}\n"
      : "=f"(d[OFF + 0]), "=f"(d[OFF + 1]), "=f"(d[OFF + 2]), "=f"(d[OFF + 3]), "=f"(d[OFF + 4]), "=f"(d[OFF + 5]),
        "=f"(d[OFF + 6]), "=f"(d[OFF + 7]), "=f"(d[OFF + 8]), "=f"(d[OFF + 9]), "=f"(d[OFF + 10]), "=f"(d[OFF + 11]),
        "=f"(d[OFF + 12]), "=f"(d[OFF + 13]), "=f"(d[OFF + 14]), "=f"(d[OFF + 15]), "=f"(d[OFF + 16]), "=f"(d[OFF + 17]),
        "=f"(d[OFF + 18]), "=f"(d[OFF + 19]), "=f"(d[OFF + 20]), "=f"(d[OFF + 21]), "=f"(d[OFF + 22]), "=f"(d[OFF + 23]),
        "=f"(d[OFF + 24]), "=f"(d[OFF + 25]), "=f"(d[OFF + 26]), "=f"(d[OFF + 27]), "=f"(d[OFF + 28]), "=f"(d[OFF + 29]),
        "=f"(d[OFF + 30]), "=f"(d[OFF + 31]), "=f"(d[OFF + 32]), "=f"(d[OFF + 33]), "=f"(d[OFF + 34]), "=f"(d[OFF + 35]),
        "=f"(d[OFF + 36]), "=f"(d[OFF + 37]), "=f"(d[OFF + 38]), "=f"(d[OFF + 39]), "=f"(d[OFF + 40]), "=f"(d[OFF + 41]),
        "=f"(d[OFF + 42]), "=f"(d[OFF + 43]), "=f"(d[OFF + 44]), "=f"(d[OFF + 45]), "=f"(d[OFF + 46]), "=f"(d[OFF + 47]),
        "=f"(d[OFF + 48]), "=f"(d[OFF + 49]), "=f"(d[OFF + 50]), "=f"(d[OFF + 51])
      : "r"(a0), "r"(a1), "r"(a2), "r"(a3), "l"(desc_b), "r"(scale_d), "r"(meta));
}

template <int OFF, int NN>
__device__ __forceinline__ void wg_s48(float (&d)[NN], uint32_t a0, uint32_t a1, uint32_t a2, uint32_t a3,
                                       uint64_t desc_b, int scale_d, uint32_t meta) {
  asm volatile(
      "{\n.reg .pred p;\nsetp.ne.b32 p, %29, 0;\n"
      "wgmma.mma_async.sp.sync.aligned.m64n48k32.f32.bf16.bf16 "
      "{%0,%1,%2,%3,%4,%5,%6,%7,%8,%9,%10,%11,%12,%13,%14,%15,"
      "%16,%17,%18,%19,%20,%21,%22,%23}, "
      "{%24,%25,%26,%27}, %28, %30, 0, p, 1, 1, 0;\n}\n"
      : "+f"(d[OFF + 0]), "+f"(d[OFF + 1]), "+f"(d[OFF + 2]), "+f"(d[OFF + 3]), "+f"(d[OFF + 4]), "+f"(d[OFF + 5]),
        "+f"(d[OFF + 6]), "+f"(d[OFF + 7]), "+f"(d[OFF + 8]), "+f"(d[OFF + 9]), "+f"(d[OFF + 10]), "+f"(d[OFF + 11]),
        "+f"(d[OFF + 12]), "+f"(d[OFF + 13]), "+f"(d[OFF + 14]), "+f"(d[OFF + 15]), "+f"(d[OFF + 16]), "+f"(d[OFF + 17]),
        "+f"(d[OFF + 18]), "+f"(d[OFF + 19]), "+f"(d[OFF + 20]), "+f"(d[OFF + 21]), "+f"(d[OFF + 22]), "+f"(d[OFF + 23])
      : "r"(a0), "r"(a1), "r"(a2), "r"(a3), "l"(desc_b), "r"(scale_d), "r"(meta));
}

template <int OFF, int NN>
__device__ __forceinline__ void wg_s48z(float (&d)[NN], uint32_t a0, uint32_t a1, uint32_t a2, uint32_t a3,
                                       uint64_t desc_b, int scale_d, uint32_t meta) {
  asm volatile(
      "{\n.reg .pred p;\nsetp.ne.b32 p, %29, 0;\n"
      "wgmma.mma_async.sp.sync.aligned.m64n48k32.f32.bf16.bf16 "
      "{%0,%1,%2,%3,%4,%5,%6,%7,%8,%9,%10,%11,%12,%13,%14,%15,"
      "%16,%17,%18,%19,%20,%21,%22,%23}, "
      "{%24,%25,%26,%27}, %28, %30, 0, p, 1, 1, 0;\n}\n"
      : "=f"(d[OFF + 0]), "=f"(d[OFF + 1]), "=f"(d[OFF + 2]), "=f"(d[OFF + 3]), "=f"(d[OFF + 4]), "=f"(d[OFF + 5]),
        "=f"(d[OFF + 6]), "=f"(d[OFF + 7]), "=f"(d[OFF + 8]), "=f"(d[OFF + 9]), "=f"(d[OFF + 10]), "=f"(d[OFF + 11]),
        "=f"(d[OFF + 12]), "=f"(d[OFF + 13]), "=f"(d[OFF + 14]), "=f"(d[OFF + 15]), "=f"(d[OFF + 16]), "=f"(d[OFF + 17]),
        "=f"(d[OFF + 18]), "=f"(d[OFF + 19]), "=f"(d[OFF + 20]), "=f"(d[OFF + 21]), "=f"(d[OFF + 22]), "=f"(d[OFF + 23])
      : "r"(a0), "r"(a1), "r"(a2), "r"(a3), "l"(desc_b), "r"(scale_d), "r"(meta));
}

template <int OFF, int NN>
__device__ __forceinline__ void wg_s56(float (&d)[NN], uint32_t a0, uint32_t a1, uint32_t a2, uint32_t a3,
                                       uint64_t desc_b, int scale_d, uint32_t meta) {
  asm volatile(
      "{\n.reg .pred p;\nsetp.ne.b32 p, %33, 0;\n"
      "wgmma.mma_async.sp.sync.aligned.m64n56k32.f32.bf16.bf16 "
      "{%0,%1,%2,%3,%4,%5,%6,%7,%8,%9,%10,%11,%12,%13,%14,%15,"
      "%16,%17,%18,%19,%20,%21,%22,%23,%24,%25,%26,%27}, "
      "{%28,%29,%30,%31}, %32, %34, 0, p, 1, 1, 0;\n}\n"
      : "+f"(d[OFF + 0]), "+f"(d[OFF + 1]), "+f"(d[OFF + 2]), "+f"(d[OFF + 3]), "+f"(d[OFF + 4]), "+f"(d[OFF + 5]),
        "+f"(d[OFF + 6]), "+f"(d[OFF + 7]), "+f"(d[OFF + 8]), "+f"(d[OFF + 9]), "+f"(d[OFF + 10]), "+f"(d[OFF + 11]),
        "+f"(d[OFF + 12]), "+f"(d[OFF + 13]), "+f"(d[OFF + 14]), "+f"(d[OFF + 15]), "+f"(d[OFF + 16]), "+f"(d[OFF + 17]),
        "+f"(d[OFF + 18]), "+f"(d[OFF + 19]), "+f"(d[OFF + 20]), "+f"(d[OFF + 21]), "+f"(d[OFF + 22]), "+f"(d[OFF + 23]),
        "+f"(d[OFF + 24]), "+f"(d[OFF + 25]), "+f"(d[OFF + 26]), "+f"(d[OFF + 27])
      : "r"(a0), "r"(a1), "r"(a2), "r"(a3), "l"(desc_b), "r"(scale_d), "r"(meta));
}

template <int OFF, int NN>
__device__ __forceinline__ void wg_s56z(float (&d)[NN], uint32_t a0, uint32_t a1, uint32_t a2, uint32_t a3,
                                       uint64_t desc_b, int scale_d, uint32_t meta) {
  asm volatile(
      "{\n.reg .pred p;\nsetp.ne.b32 p, %33, 0;\n"
      "wgmma.mma_async.sp.sync.aligned.m64n56k32.f32.bf16.bf16 "
      "{%0,%1,%2,%3,%4,%5,%6,%7,%8,%9,%10,%11,%12,%13,%14,%15,"
      "%16,%17,%18,%19,%20,%21,%22,%23,%24,%25,%26,%27}, "
      "{%28,%29,%30,%31}, %32, %34, 0, p, 1, 1, 0;\n}\n"
      : "=f"(d[OFF + 0]), "=f"(d[OFF + 1]), "=f"(d[OFF + 2]), "=f"(d[OFF + 3]), "=f"(d[OFF + 4]), "=f"(d[OFF + 5]),
        "=f"(d[OFF + 6]), "=f"(d[OFF + 7]), "=f"(d[OFF + 8]), "=f"(d[OFF + 9]), "=f"(d[OFF + 10]), "=f"(d[OFF + 11]),
        "=f"(d[OFF + 12]), "=f"(d[OFF + 13]), "=f"(d[OFF + 14]), "=f"(d[OFF + 15]), "=f"(d[OFF + 16]), "=f"(d[OFF + 17]),
        "=f"(d[OFF + 18]), "=f"(d[OFF + 19]), "=f"(d[OFF + 20]), "=f"(d[OFF + 21]), "=f"(d[OFF + 22]), "=f"(d[OFF + 23]),
        "=f"(d[OFF + 24]), "=f"(d[OFF + 25]), "=f"(d[OFF + 26]), "=f"(d[OFF + 27])
      : "r"(a0), "r"(a1), "r"(a2), "r"(a3), "l"(desc_b), "r"(scale_d), "r"(meta));
}

template <int OFF, int NN>
__device__ __forceinline__ void wg_s64t(float (&d)[NN], uint32_t a0, uint32_t a1, uint32_t a2, uint32_t a3,
                                       uint64_t desc_b, int scale_d, uint32_t meta) {
  asm volatile(
      "{\n.reg .pred p;\nsetp.ne.b32 p, %37, 0;\n"
      "wgmma.mma_async.sp.sync.aligned.m64n64k32.f32.bf16.bf16 "
      "{%0,%1,%2,%3,%4,%5,%6,%7,%8,%9,%10,%11,%12,%13,%14,%15,"
      "%16,%17,%18,%19,%20,%21,%22,%23,%24,%25,%26,%27,%28,%29,%30,%31}, "
      "{%32,%33,%34,%35}, %36, %38, 0, p, 1, 1, 1;\n}\n"
      : "+f"(d[OFF + 0]), "+f"(d[OFF + 1]), "+f"(d[OFF + 2]), "+f"(d[OFF + 3]), "+f"(d[OFF + 4]), "+f"(d[OFF + 5]),
        "+f"(d[OFF + 6]), "+f"(d[OFF + 7]), "+f"(d[OFF + 8]), "+f"(d[OFF + 9]), "+f"(d[OFF + 10]), "+f"(d[OFF + 11]),
        "+f"(d[OFF + 12]), "+f"(d[OFF + 13]), "+f"(d[OFF + 14]), "+f"(d[OFF + 15]), "+f"(d[OFF + 16]), "+f"(d[OFF + 17]),
        "+f"(d[OFF + 18]), "+f"(d[OFF + 19]), "+f"(d[OFF + 20]), "+f"(d[OFF + 21]), "+f"(d[OFF + 22]), "+f"(d[OFF + 23]),
        "+f"(d[OFF + 24]), "+f"(d[OFF + 25]), "+f"(d[OFF + 26]), "+f"(d[OFF + 27]), "+f"(d[OFF + 28]), "+f"(d[OFF + 29]),
        "+f"(d[OFF + 30]), "+f"(d[OFF + 31])
      : "r"(a0), "r"(a1), "r"(a2), "r"(a3), "l"(desc_b), "r"(scale_d), "r"(meta));
}

template <int OFF, int NN>
__device__ __forceinline__ void wg_s64t1(float (&d)[NN], uint32_t a0, uint32_t a1, uint32_t a2, uint32_t a3,
                                       uint64_t desc_b, int scale_d, uint32_t meta) {
  asm volatile(
      "{\n.reg .pred p;\nsetp.ne.b32 p, %37, 0;\n"
      "wgmma.mma_async.sp.sync.aligned.m64n64k32.f32.bf16.bf16 "
      "{%0,%1,%2,%3,%4,%5,%6,%7,%8,%9,%10,%11,%12,%13,%14,%15,"
      "%16,%17,%18,%19,%20,%21,%22,%23,%24,%25,%26,%27,%28,%29,%30,%31}, "
      "{%32,%33,%34,%35}, %36, %38, 1, p, 1, 1, 1;\n}\n"
      : "+f"(d[OFF + 0]), "+f"(d[OFF + 1]), "+f"(d[OFF + 2]), "+f"(d[OFF + 3]), "+f"(d[OFF + 4]), "+f"(d[OFF + 5]),
        "+f"(d[OFF + 6]), "+f"(d[OFF + 7]), "+f"(d[OFF + 8]), "+f"(d[OFF + 9]), "+f"(d[OFF + 10]), "+f"(d[OFF + 11]),
        "+f"(d[OFF + 12]), "+f"(d[OFF + 13]), "+f"(d[OFF + 14]), "+f"(d[OFF + 15]), "+f"(d[OFF + 16]), "+f"(d[OFF + 17]),
        "+f"(d[OFF + 18]), "+f"(d[OFF + 19]), "+f"(d[OFF + 20]), "+f"(d[OFF + 21]), "+f"(d[OFF + 22]), "+f"(d[OFF + 23]),
        "+f"(d[OFF + 24]), "+f"(d[OFF + 25]), "+f"(d[OFF + 26]), "+f"(d[OFF + 27]), "+f"(d[OFF + 28]), "+f"(d[OFF + 29]),
        "+f"(d[OFF + 30]), "+f"(d[OFF + 31])
      : "r"(a0), "r"(a1), "r"(a2), "r"(a3), "l"(desc_b), "r"(scale_d), "r"(meta));
}

template <int OFF, int NN>
__device__ __forceinline__ void wg_s64tz(float (&d)[NN], uint32_t a0, uint32_t a1, uint32_t a2, uint32_t a3,
                                       uint64_t desc_b, int scale_d, uint32_t meta) {
  asm volatile(
      "{\n.reg .pred p;\nsetp.ne.b32 p, %37, 0;\n"
      "wgmma.mma_async.sp.sync.aligned.m64n64k32.f32.bf16.bf16 "
      "{%0,%1,%2,%3,%4,%5,%6,%7,%8,%9,%10,%11,%12,%13,%14,%15,"
      "%16,%17,%18,%19,%20,%21,%22,%23,%24,%25,%26,%27,%28,%29,%30,%31}, "
      "{%32,%33,%34,%35}, %36, %38, 0, p, 1, 1, 1;\n}\n"
      : "=f"(d[OFF + 0]), "=f"(d[OFF + 1]), "=f"(d[OFF + 2]), "=f"(d[OFF + 3]), "=f"(d[OFF + 4]), "=f"(d[OFF + 5]),
        "=f"(d[OFF + 6]), "=f"(d[OFF + 7]), "=f"(d[OFF + 8]), "=f"(d[OFF + 9]), "=f"(d[OFF + 10]), "=f"(d[OFF + 11]),
        "=f"(d[OFF + 12]), "=f"(d[OFF + 13]), "=f"(d[OFF + 14]), "=f"(d[OFF + 15]), "=f"(d[OFF + 16]), "=f"(d[OFF + 17]),
        "=f"(d[OFF + 18]), "=f"(d[OFF + 19]), "=f"(d[OFF + 20]), "=f"(d[OFF + 21]), "=f"(d[OFF + 22]), "=f"(d[OFF + 23]),
        "=f"(d[OFF + 24]), "=f"(d[OFF + 25]), "=f"(d[OFF + 26]), "=f"(d[OFF + 27]), "=f"(d[OFF + 28]), "=f"(d[OFF + 29]),
        "=f"(d[OFF + 30]), "=f"(d[OFF + 31])
      : "r"(a0), "r"(a1), "r"(a2), "r"(a3), "l"(desc_b), "r"(scale_d), "r"(meta));
}

__device__ __forceinline__ int g2_inv(int ch) { return 32 * (ch >> 5) + 8 * ((ch >> 1) & 3) + 2 * ((ch >> 3) & 3) + (ch & 1); }
__host__ __device__ __forceinline__ uint32_t wimg_off(int n, int k) {
  return (uint32_t)(k >> 6) * kWChunk + (uint32_t)n * 128 + (uint32_t)((((k & 63) >> 3) ^ (n & 7)) << 4) + (k & 7) * 2;
}
__host__ __device__ constexpr int w2piece(int h, int c) { return c == 2 ? 2 + h : 4 * h + c; }
__device__ __forceinline__ uint32_t w2img_off(int n, int k) { return wimg_off(n % 96, k & 63) + w2piece(n >= 96, k >> 6) * (kWChunk / 2); }
__device__ __forceinline__ int qpix(int par, int t) {
  const int a = 2 * t + 13 * par - 6, b = t + 112 * par;
  return par ? min(a, b) : max(a, b);
}
__device__ __forceinline__ int woff(int par, int i, int r) {
  const int a = 99 * par + 6 - 8 * i;
  return par ? min(r, a) : max(r, a);
}

__device__ __forceinline__ void mma16816(float (&c)[4], uint32_t a0, uint32_t a1, uint32_t a2, uint32_t a3, uint32_t b0,
                                         uint32_t b1) {
  asm volatile(
      "mma.sync.aligned.m16n8k16.row.col.f32.bf16.bf16.f32 {%0,%1,%2,%3}, {%4,%5,%6,%7}, {%8,%9}, {%0,%1,%2,%3};"
      : "+f"(c[0]), "+f"(c[1]), "+f"(c[2]), "+f"(c[3])
      : "r"(a0), "r"(a1), "r"(a2), "r"(a3), "r"(b0), "r"(b1));
}

__device__ __forceinline__ void fold_w1(const int u, const __nv_bfloat16* __restrict__ wqkv, uint8_t* wimg) {
  const int g = (threadIdx.x >> 2) & 7, l = threadIdx.x & 3;
  const int m0 = (u / 12) * 16, s = u % 12;
  uint4 A[12], B[12];
  const __nv_bfloat16* arow = wqkv + (m0 + 4 * (g >> 1) + (g & 1)) * 576 + 192 + 8 * l;
  const __nv_bfloat16* brow = wqkv + (16 * s + 4 * (g >> 1) + (g & 1)) * 576 + 8 * l;
#pragma unroll
  for (int i = 0; i < 12; i++) {
    A[i] = ldg128_nc(arow + (i & 1) * 2 * 576 + 32 * (i >> 1));
    B[i] = ldg128_nc(brow + (i & 1) * 2 * 576 + 32 * (i >> 1));
  }
  sched_fence();
  uint8_t* dst = wimg + wimg_off(m0 + g, 16 * s + 4 * l);
  float acc[4][4];
#pragma unroll
  for (int j = 0; j < 16; j++) acc[j >> 2][j & 3] = 0.f;
#pragma unroll
  for (int i = 0; i < 6; i++) {
    const uint4 &a0 = A[2 * i], &a1 = A[2 * i + 1];
#pragma unroll
    for (int nb = 0; nb < 2; nb++) {
      mma16816(acc[2 * nb], a0.x, a1.x, a0.y, a1.y, B[2 * i + nb].x, B[2 * i + nb].y);
      mma16816(acc[2 * nb + 1], a0.z, a1.z, a0.w, a1.w, B[2 * i + nb].z, B[2 * i + nb].w);
    }
  }
#pragma unroll
  for (int j = 0; j < 2; j++) {
    const uint2 v = make_uint2(pack_bf16((acc[0][2 * j] + acc[1][2 * j]) * kAlpha, (acc[0][2 * j + 1] + acc[1][2 * j + 1]) * kAlpha),
                               pack_bf16((acc[2][2 * j] + acc[3][2 * j]) * kAlpha, (acc[2][2 * j + 1] + acc[3][2 * j + 1]) * kAlpha));
    asm volatile("st.relaxed.gpu.global.v2.u32 [%0], {%1,%2};" ::"l"(dst + j * 1024), "r"(v.x), "r"(v.y) : "memory");
  }
}
__device__ __forceinline__ void fold_w2(const int u, const __nv_bfloat16* __restrict__ wqkv, const __nv_bfloat16* __restrict__ wo,
                                        uint8_t* wimg) {
  const int g = (threadIdx.x >> 2) & 7, l = threadIdx.x & 3;
  const int m0 = (u / 12) * 32, n0 = (u % 12) * 16;
  uint4 S[12];
  uint32_t L[96];
  const __nv_bfloat16* brow = wqkv + (n0 + 4 * (g >> 1) + (g & 1)) * 576 + 384 + 8 * l;
#pragma unroll
  for (int i = 0; i < 12; i++) S[i] = ldg128_nc(brow + (i & 1) * 2 * 576 + 32 * (i >> 1));
  const __nv_bfloat16* acol = wo + (8 * l) * 192 + m0 + 4 * g;
#pragma unroll
  for (int c = 0; c < 48; c++)
    asm volatile("ld.global.nc.v2.u32 {%0,%1}, [%2];" : "=r"(L[2 * c]), "=r"(L[2 * c + 1]) : "l"(acol + (32 * (c >> 3) + (c & 7)) * 192));
  const uint32_t off = w2_offset();
  sched_fence();
  uint8_t* img = wimg + off;
  float acc[4][4];
#pragma unroll
  for (int j = 0; j < 16; j++) acc[j >> 2][j & 3] = 0.f;
#pragma unroll
  for (int i = 0; i < 6; i++) {
#pragma unroll
    for (int h = 0; h < 2; h++) {
      const uint4 &s0 = S[2 * i], &s1 = S[2 * i + 1];
#pragma unroll
      for (int mt = 0; mt < 2; mt++) {
        const uint32_t* a = L + 16 * i + 8 * h + mt;
        const uint32_t a0 = __byte_perm(a[0], a[2], 0x5410), a1 = __byte_perm(a[0], a[2], 0x7632);
        const uint32_t a2 = __byte_perm(a[4], a[6], 0x5410), a3 = __byte_perm(a[4], a[6], 0x7632);
        mma16816(acc[2 * mt], a0, a1, a2, a3, h ? s0.z : s0.x, h ? s0.w : s0.y);
        mma16816(acc[2 * mt + 1], a0, a1, a2, a3, h ? s1.z : s1.x, h ? s1.w : s1.y);
      }
    }
  }
#pragma unroll
  for (int j = 0; j < 4; j++) {
    const float(&c0)[4] = acc[j & 2];
    const float(&c1)[4] = acc[(j & 2) + 1];
    asm volatile("st.relaxed.gpu.global.v2.u32 [%0], {%1,%2};" ::"l"(img + w2img_off(g2_inv(m0 + 4 * g + j), n0 + 4 * l)),
                 "r"(pack_bf16(c0[2 * (j & 1)], c0[2 * (j & 1) + 1])), "r"(pack_bf16(c1[2 * (j & 1)], c1[2 * (j & 1) + 1])) : "memory");
  }
}

__global__ void __launch_bounds__(256) fold_kernel(const __nv_bfloat16* __restrict__ wqkv,
                                                   const __nv_bfloat16* __restrict__ wo, uint8_t* wimg) {
  const int u = blockIdx.x * 8 + (threadIdx.x >> 5);
  if (u < 144) fold_w1(u, wqkv, wimg);
  else fold_w2(u - 144, wqkv, wo, wimg);
}

struct TileCoord { int pr, pc, I, J, up, kind; };
struct TileTable { uint16_t e[kCtas * 6], g[5][8][2], b[5][2][4]; };
inline void make_tiles(TileTable& tt) {
  for (int tile = 0; tile < kCtas * 6; tile++) {
    const int b = tile / 6, k = tile - 6 * b;
    const int p = b < 128 ? (tile - 672) >> 1 : b - 80;
    const int strip = b < 112 ? b >> 1 : b >= 128 && k >= 2 ? (b & 1) * 27 + (b & 2) * 14 : p + (p < 26 ? 1 : 3);
    const int pr = strip >= 28, J = (strip - pr * 28) >> 1, pc = strip & 1, up = b < 112 ? b & 1 : pr;
    const int first = b < 112 ? 8 - 2 * pr - up : 13 * pr, step = b < 112 ? k : k & 1;
    const int I = up ? first - step : first + step;
    const int kind = I == 13 * pr ? 3 + pr : J == 13 * pc ? 1 + pc : 0;
    tt.e[tile] = (uint16_t)(I | J << 4 | pr << 8 | pc << 9 | up << 10 | kind << 11);
  }
  for (int kind = 0; kind < 5; kind++) {
    const bool col = kind == 1 || kind == 2;
    auto off = [kind](int t) { return kind == 0 ? 2 * t : kind & 1 ? t + (t == 7) : t + (t > 0); };
    for (int j = 0; j < 8; j++) {
      const int w = j >> 1, h = j & 1;
      tt.g[kind][j][0] = (uint16_t)(col ? 3 * off(w + 4 * h) : 3 * (kW * off(2 * w) + 8 * h));
      tt.g[kind][j][1] = (uint16_t)(128 * (col ? 5 : 5 + off(2 * w + 1) - off(2 * w)));
    }
    for (int i = 0; i < 2; i++) {
      const int w = kind == 0 ? 0 : kind & 1 ? 3 * i : 1 - i;
      tt.b[kind][i][0] = tt.g[kind][2 * w][0];
      tt.b[kind][i][1] = (uint16_t)(128 * (kind == 0 ? 0 : (col ? 3 : 1) + i));
      tt.b[kind][i][2] = (uint16_t)(2048 * w);
      tt.b[kind][i][3] = 0;
    }
  }
}
__device__ __forceinline__ int num_tiles() { return blockIdx.x < 128 ? 6 : 4; }
__device__ __forceinline__ TileCoord decode_tile(const TileTable& tt, int tile) {
  const uint32_t e = tt.e[tile];
  return TileCoord{(int)(e >> 8) & 1, (int)(e >> 9) & 1, (int)e & 15, (int)(e >> 4) & 15, (int)(e >> 10) & 1, (int)(e >> 11)};
}
__device__ __forceinline__ int halo_r0(const TileCoord& t) { return 8 * t.I + 6 * t.pr - 6; }
__device__ __forceinline__ int halo_c0(const TileCoord& t) { return min(max(8 * t.J + 6 * t.pc - 6, -3), 102); }

__device__ __forceinline__ uint32_t bar_full(uint32_t bars, int wg, int c) { return bars + (wg * 3 + c) * 8; }
__device__ __forceinline__ uint32_t bar_w1c(uint32_t bars, int c) { return bars + (6 + c) * 8; }
__device__ __forceinline__ uint32_t bar_w2(uint32_t bars) { return bars + 9 * 8; }
__device__ __forceinline__ uint32_t bar_x(uint32_t bars, int j, int c) { return bars + (j == 0 ? 10 : c ? 17 + c : 11) * 8; }
__device__ __forceinline__ uint32_t bar_w1q(uint32_t bars) { return bars + 12 * 8; }
__device__ __forceinline__ uint32_t bar_xf(uint32_t bars) { return bars + 13 * 8; }
__device__ __forceinline__ uint32_t bar_w2m(uint32_t bars) { return bars + 14 * 8; }
__device__ __forceinline__ uint32_t bar_redo(uint32_t bars) { return bars + 15 * 8; }
__device__ __forceinline__ uint32_t bar_wok(uint32_t bars) { return bars + 16 * 8; }
__device__ __forceinline__ uint32_t bar_go(uint32_t bars) { return bars + 17 * 8; }
__device__ __forceinline__ uint32_t bar_raw(uint32_t bars, int j = 0) { return bars + (21 + j) * 8; }
__device__ __forceinline__ uint32_t bar_w2a(uint32_t bars) { return bars + 20 * 8; }
constexpr int kNumBars = 22;

__device__ __forceinline__ uint64_t wdesc(uint64_t d0, int s) { return d0 + (((s >> 2) * kWChunk + (s & 3) * 32) >> 4); }

__device__ __forceinline__ uint32_t x_chunk(int k, int c) { return kXOff + (k == 0 ? kWChunk : 0) + (k & 1 ? 2 - c : c) * 8192; }
__device__ __forceinline__ uint32_t out_slot(int k, int nt) { return k + 1 < nt ? kW2Off + (~k & 1) * 2 * kWChunk : kW1Off + kWChunk; }
template <int I0, int I1>
__device__ __forceinline__ void store_rows(bool on, __nv_bfloat16* pA, __nv_bfloat16* pB, const uint32_t (&a)[24], const uint32_t (&b)[24]) {
#pragma unroll
  for (int i = 2 * I0; i < 2 * I1; i++) {
    const uint32_t* v = (i & 1 ? b : a) + 4 * (i >> 1);
    asm volatile("{\n.reg .pred p;\nsetp.ne.u32 p, %5, 0;\n@p st.global.v4.u32 [%0], {%1,%2,%3,%4};\n}\n" ::"l"((i & 1 ? pB : pA) + 32 * (i >> 1)),
                 "r"(v[0]), "r"(v[1]), "r"(v[2]), "r"(v[3]), "r"((uint32_t)on) : "memory");
  }
}
template <int I0, int I1>
__device__ __forceinline__ void stage_out(const uint32_t (&ad)[4], const uint32_t (&a)[24], const uint32_t (&b)[24]) {
#pragma unroll
  for (int i = I0; i < I1; i++) {
    const uint32_t* v = (i < 6 ? a : b) + 4 * (i % 6);
    asm volatile("st.shared.v4.u32 [%0], {%1,%2,%3,%4};" ::"r"(ad[i % 6 / 3 * 2 + (i % 3 == 1)] + (i % 3 == 2) * 1024 + (i / 6) * 12288),
                 "r"(v[0]), "r"(v[1]), "r"(v[2]), "r"(v[3]) : "memory");
  }
}
__device__ __forceinline__ uint32_t now_ns() {
  uint32_t t;
  asm volatile("mov.u32 %0, %globaltimer_lo;" : "=r"(t)::"memory");
  return t;
}
__device__ __forceinline__ void wait_clock(uint32_t t_start, uint32_t t) {
  while (now_ns() - t_start < t) { }
}
#define NAT_PRED(f, m) ".reg .pred p;\n.reg .b32 t;\nand.b32 t, " f ", " m ";\nsetp.ne.u32 p, t, 0;\n"
constexpr uint32_t kHiV = 1, kHiU = 8, kColB = 0x20, kInV = 0x100, kInU = 0x1000, kColA = 0x10000;
template <uint32_t M>
__device__ __forceinline__ float pick(const float* a, const float* b, uint32_t f) {
  float d;
  asm("{\n" NAT_PRED("%5", "%6") "add.f32 %0, %1, %2;\n@p add.f32 %0, %3, %4;\n}\n"
      : "=&f"(d) : "f"(a[0]), "f"(a[2]), "f"(b[0]), "f"(b[2]), "r"(f), "n"(M));
  return d;
}
template <uint32_t M>
__device__ __forceinline__ float sel(float a, float b, uint32_t f) {
  float d;
  asm("{\n" NAT_PRED("%3", "%4") "selp.f32 %0, %1, %2, p;\n}\n" : "=f"(d) : "f"(a), "f"(b), "r"(f), "n"(M));
  return d;
}
template <uint32_t M>
__device__ __forceinline__ void max_if(float& m, float v, uint32_t f) {
  asm("{\n" NAT_PRED("%2", "%3") "@p max.f32 %0, %0, %1;\n}\n" : "+f"(m) : "f"(v), "r"(f), "n"(M));
}
template <uint32_t M>
__device__ __forceinline__ void add_if(float& m, float v, uint32_t f) {
  asm("{\n" NAT_PRED("%2", "%3") "@p add.f32 %0, %0, %1;\n}\n" : "+f"(m) : "f"(v), "r"(f), "n"(M));
}
__device__ __forceinline__ void pick_v(const float* a, float* v, uint32_t f) {
  v[0] = pick<kHiV>(a, a + 16, f), v[1] = pick<kHiV>(a + 1, a + 17, f);
  v[2] = pick<kHiV * 2>(a + 4, a + 20, f), v[3] = pick<kHiV * 2>(a + 5, a + 21, f);
  v[4] = pick<kHiV * 4>(a + 8, a + 24, f), v[5] = pick<kHiV * 4>(a + 9, a + 25, f);
  v[6] = a[12] + a[14], v[7] = a[13] + a[15];
}
__device__ __forceinline__ void pick_u(const float* a, float* v, uint32_t f) {
#pragma unroll
  for (int c = 0; c < 3; c++) v[2 * c] = pick<kHiU>(a + 4 * c, a + 4 * c + 12, f), v[2 * c + 1] = pick<kHiU * 2>(a + 4 * c + 1, a + 4 * c + 13, f);
}
__device__ __forceinline__ uint32_t sign_bytes(uint32_t v, uint32_t sel) {
  uint32_t d;
  asm("prmt.b32 %0, %1, %1, %2;" : "=r"(d) : "r"(v), "r"(sel));
  return d;
}
__device__ __forceinline__ float own_max(const float (&v)[14], uint32_t f) {
  float m = sel<kInV>(fmaxf(v[0], v[1]), -INFINITY, f), m2 = sel<kInV * 2>(fmaxf(v[2], v[3]), -INFINITY, f);
  max_if<kInV * 4>(m, fmaxf(v[4], v[5]), f);
  max_if<kInV * 8>(m2, fmaxf(v[6], v[7]), f);
  max_if<kInU>(m, fmaxf(fmaxf(v[8], v[10]), v[12]), f);
  max_if<kInU * 2>(m2, fmaxf(fmaxf(v[9], v[11]), v[13]), f);
  return fmaxf(m, m2);
}
__device__ __forceinline__ float quad_max(float m) {
  const float a = __shfl_xor_sync(0xffffffffu, m, 1), b = __shfl_xor_sync(0xffffffffu, m, 2), c = __shfl_xor_sync(0xffffffffu, m, 3);
  return fmaxf(fmaxf(m, a), fmaxf(b, c));
}
__device__ __forceinline__ float row_rcp(const float (&v)[14], uint32_t f) {
  float s = sel<kInV>(v[0] + v[1], 0.f, f), s2 = sel<kInV * 2>(v[2] + v[3], 0.f, f);
  add_if<kInV * 4>(s, v[4] + v[5], f);
  add_if<kInV * 8>(s2, v[6] + v[7], f);
  add_if<kInU>(s, v[8] + v[10] + v[12], f);
  add_if<kInU * 2>(s2, v[9] + v[11] + v[13], f);
  s += s2;
  const float a = __shfl_xor_sync(0xffffffffu, s, 1), b = __shfl_xor_sync(0xffffffffu, s, 2), c = __shfl_xor_sync(0xffffffffu, s, 3);
  return rcp_approx((s + a) + (b + c));
}
__device__ __forceinline__ void route(const float (&v)[14], float s, const uint32_t (&rt)[9], uint32_t (&p)[14]) {
#pragma unroll
  for (int i = 0; i < 7; i++) {
    const uint32_t u = pack_bf16(v[2 * i] * s, v[2 * i + 1] * s);
    if (i < 4) p[i] = u & rt[i];
    if (i < 3) p[i + 4] = u & rt[i + 4];
    if (i >= 4) {
      p[i + 3] = u & rt[7];
      p[i + 6] = u & rt[8];
    }
  }
}

template <int C, int T0 = 0, int T1 = 7>
__device__ __forceinline__ void pv_chunk(float (&z)[32], const uint32_t (&pa)[14], const uint32_t (&pb)[14],
                                         const uint32_t (&meta)[4], uint64_t dV) {
#pragma unroll
  for (int t = T0; t < T1; t++) {
    if (t & 1)
      wg_s64t1<0, 32>(z, pa[2 * t], pb[2 * t], pa[2 * t + 1], pb[2 * t + 1], dV + ((2 * C * kChunkBytes + t * 2048) >> 4), 1,
                      meta[t >> 1]);
    else if (t > 0)
      wg_s64t<0, 32>(z, pa[2 * t], pb[2 * t], pa[2 * t + 1], pb[2 * t + 1], dV + ((2 * C * kChunkBytes + t * 2048) >> 4), 1,
                     meta[t >> 1]);
    else
      wg_s64tz<0, 32>(z, pa[0], pb[0], pa[1], pb[1], dV + ((2 * C * kChunkBytes) >> 4), 0, meta[0]);
  }
}
template <int C>
__device__ __forceinline__ void pack_z(const float (&z)[32], uint32_t (&za)[24], uint32_t (&zb)[24]) {
#pragma unroll
  for (int j = 0; j < 8; j++) {
    za[8 * C + j] = pack_bf16(z[4 * j], z[4 * j + 1]);
    zb[8 * C + j] = pack_bf16(z[4 * j + 2], z[4 * j + 3]);
  }
}

template <int H>
__device__ __forceinline__ void pack_out(const float (&ac)[48], uint32_t (&oa)[24], uint32_t (&ob)[24]) {
#pragma unroll
  for (int j = 0; j < 12; j++) {
    oa[12 * H + j] = pack_bf16(ac[4 * j], ac[4 * j + 1]);
    ob[12 * H + j] = pack_bf16(ac[4 * j + 2], ac[4 * j + 3]);
  }
}
struct Maps { CUtensorMap v6, v2, v14, u8, px[8], wv, wo; };
__device__ __forceinline__ void tma_prefetch_5d(const CUtensorMap* map, int c0, int c1, int c2, int c3, int c4) {
  asm volatile("cp.async.bulk.prefetch.tensor.5d.L2.global.tile [%0, {%1, %2, %3, %4, %5}];" ::"l"((uint64_t)map), "r"(c0), "r"(c1),
               "r"(c2), "r"(c3), "r"(c4) : "memory");
}
__device__ __forceinline__ int first_line(const TileCoord tc) { return 3 * (qpix(tc.pr, 8 * tc.I) * kW + qpix(tc.pc, 8 * tc.J)); }
__device__ __forceinline__ void load_px(const Maps& tm, const TileTable& tt, uint32_t dst, uint32_t bar, int line, int kind) {
#pragma unroll
  for (int i = 0; i < 2; i++) {
    if (i == 0 || kind != 0) {
      const CUtensorMap* map = (const CUtensorMap*)((const char*)tm.px + tt.b[kind][i][1]);
      if (bar) tma_load_5d(dst + tt.b[kind][i][2], map, bar, 0, 0, 0, 0, line + tt.b[kind][i][0]);
      else tma_prefetch_5d(map, 0, 0, 0, 0, line + tt.b[kind][i][0]);
    }
  }
}
__device__ __forceinline__ void store_px(const Maps& tm, const TileTable& tt, uint32_t buf, int line, int kind) {
#pragma unroll
  for (int i = 0; i < 8; i++) {
    const int j = 2 * (i & 3) + (i >> 2);
    asm volatile("cp.async.bulk.tensor.5d.global.shared::cta.tile.bulk_group [%0, {%2, %2, %2, %2, %3}], [%1];" ::"l"(
                     (uint64_t)tm.px + tt.g[kind][j][1]), "r"(buf + i * 3072), "r"(0), "r"(line + tt.g[kind][j][0]) : "memory");
  }
  asm volatile("cp.async.bulk.commit_group;" ::: "memory");
}
__device__ __noinline__ bool refetch(uint32_t base, const uint8_t* src, bool gap) {
  constexpr uint32_t bars = 1024 + kBarOff, cnt = bars + 192;
#pragma unroll 1
  for (uint32_t o = 0; o < kWBytes && !gap; o += 2048) {
    uint32_t mx = 0;
#pragma unroll
    for (int i = 0; i < 4; i++) {
      uint4 v;
      asm volatile("ld.shared.v4.u32 {%0,%1,%2,%3}, [%4];" : "=r"(v.x), "=r"(v.y), "=r"(v.z), "=r"(v.w)
                   : "r"(base + o + i * 512 + (threadIdx.x & 31) * 16));
      mx = __vimax3_u32(__vimax3_u32(mx, v.x, v.y), v.z, v.w);
    }
    gap = __any_sync(0xffffffffu, mx == kEmpty);
  }
  uint32_t n;
  asm volatile("ld.shared.u32 %0, [%1];" : "=r"(n) : "r"(cnt) : "memory");
  if (!gap || __any_sync(0xffffffffu, n > (1u << 12))) return false;
  asm volatile("bar.sync 15, 128;" ::: "memory");
  if (threadIdx.x == 0) {
    asm volatile("st.shared.u32 [%0], %1;" ::"r"(cnt), "r"(n + 1) : "memory");
    mbar_arrive_expect_tx(bar_redo(bars), kWBytes);
    bulk_load(base, src, kWBytes, bar_redo(bars));
  }
  __syncwarp();
  mbar_wait(bar_redo(bars), n & 1);
  return true;
}
__device__ __forceinline__ bool any_nan(const uint32_t (&a)[24]) {
  uint32_t m[2] = {a[0], a[1]}, nan;
#pragma unroll
  for (int i = 2; i < 24; i++) asm("max.NaN.bf16x2 %0, %0, %1;" : "+r"(m[i & 1]) : "r"(a[i]));
  asm("max.NaN.bf16x2 %0, %0, %1;" : "+r"(m[0]) : "r"(m[1]));
  asm volatile("{\n.reg .pred p;\nsetp.ne.u32 p, %1, 0;\nbar.red.or.pred p, 15, 128, p;\nselp.u32 %0, 1, 0, p;\n}\n"
               : "=r"(nan) : "r"(((m[0] & 0x7FFF7FFFu) + 0x007F007Fu) & 0x80008000u) : "memory");
  return __any_sync(0xffffffffu, nan);
}
template <int S0, int S1, int Z>
__device__ __forceinline__ void g2_steps(float (&ac)[48], const uint32_t (&za)[24], const uint32_t (&zb)[24], uint64_t d) {
#pragma unroll
  for (int s = S0; s < S1; s++) {
    const uint64_t ds = d + (((s >> 2 & 1) * (kWChunk / 2) + (s & 3) * 32) >> 4);
    if (s == Z) wg_d96z<0, 48>(ac, za[2 * s], zb[2 * s], za[2 * s + 1], zb[2 * s + 1], ds, 0);
    else wg_d96<0, 48>(ac, za[2 * s], zb[2 * s], za[2 * s + 1], zb[2 * s + 1], ds, 1);
  }
}

__device__ __forceinline__ void consumer(const int wg, __nv_bfloat16* out, const uint8_t* wimg, const uint32_t sbase,
                                         const uint32_t zero, const Maps& tm, const TileTable& tt) {
  const int tid = threadIdx.x & 127;
  const int w = __shfl_sync(0xffffffffu, tid >> 5, 0), lane = tid & 31;
  const uint64_t dK = make_desc(sbase, 16, 1024);
  const uint64_t dV = make_desc(sbase, kChunkBytes, 512, 2);
  const uint64_t dW1 = make_desc(sbase + kW1Off, 16, 1024);
  const uint64_t dX0 = make_desc(sbase + kW2Off + wg * 2 * kWChunk, 16, 1024), dY0 = make_desc(sbase + kW2Off + (1 - wg) * 2 * kWChunk, 16, 1024);
  const uint64_t dX2 = make_desc(sbase + kXOff + wg * (kWChunk / 2), 16, 1024), dY2 = make_desc(sbase + kXOff + (1 - wg) * (kWChunk / 2), 16, 1024);
  const uint32_t bars = sbase + kBarOff;
  int tile0 = blockIdx.x * kTilesPerCta;
  asm volatile("" : "+r"(tile0));
  const int nt = num_tiles();

  uint32_t pix = 0, geo[6] = {};
  const int l = lane & 3;
#pragma unroll 1
  for (int j = 4; j >= 0; j -= 2) {
    const TileCoord tc = decode_tile(tt, tile0 + wg + j);
    const bool col = tc.kind == 1 || tc.kind == 2;
    const int g = col ? lane >> 2 : 2 * w + ((lane >> 2) & 1), qc = col ? w : lane >> 3;
    const uint32_t pr = qpix(tc.pr, 8 * tc.I + g) * kW;
    if (j == nt - 2) pix = (pr + qpix(tc.pc, 8 * tc.J + qc)) | (pr + qpix(tc.pc, 8 * tc.J + qc + 4)) << 16;
    const int d = 8 * tc.J + 6 * tc.pc - 6 - halo_c0(tc);
    const int ro = woff(tc.pr, tc.I, g), coA = woff(tc.pc, tc.J, qc) + d, coB = woff(tc.pc, tc.J, qc + 4) + d - 3;
#pragma unroll
    for (int i = 5; i >= 2; i--) geo[i] = geo[i - 2];
    const uint32_t lr = 0x1FCu << ro;
    const uint32_t lv = lr >> (2 + (l >> 1)), lu = lr >> (2 * l + 2 * tc.up);
    const uint32_t t = __byte_perm(lv, lu, wg ? 0x4501 : 0x5410);
    geo[0] = (((t & 0x15u) | (lv & 0x40u)) * 0x02082080u & 0x80808080u) | (((t >> 8) & 0x15u) * 0x01041040u & 0x40404040u) |
             (__byte_perm(t << 5, t << 4, 0x7362) & 0x20202020u) | (nt == 6);
    const int dr = (ro - 1) & 7;
    const uint32_t hiv = (((1u << ((ro - (l >> 1) + 1) >> 1)) - 1u) ^ (wg ? 7u : 0u)) & 7u, hiu = (t >> 24) & 3u;
    const uint32_t ca = (1u << coA) - 1u;
    geo[1] = hiv * kHiV | hiu * kHiU | ((((1u << coB) - 1u) >> (2 * (l & 1))) & 3u) * kColB |
             (15u & ~((uint32_t)((dr & 1) == (l >> 1)) << (dr >> 1))) * kInV | ((t >> 16 | t >> 24) & 3u) * kInU | ca * kColA |
             (ca >> ((0x49 >> (2 * l)) & 3) & 1u) << 19 | (uint32_t)(l == 3) << 20 | (0x55u & ((1u << (2 * coB)) - 1u)) << 24;
  }
  keep_regs(geo);
  const int so = (lane >> 3) | (lane & 4);
  uint32_t sts = sbase + w * 3072 + so * 128 + (((lane & 3) ^ so) << 4);
  __nv_bfloat16* poA = out + 8 * l + (pix & 0xFFFFu) * kC + 96 * wg;
  __nv_bfloat16* poB = out + 8 * l + (pix >> 16) * kC + 96 * wg;
  asm volatile("" : "+l"(poA), "+l"(poB), "+r"(sts));
  uint32_t oa[24], ob[24];
#pragma unroll
  for (int j = 0; j < 24; j++) oa[j] = ob[j] = 0u;
  keep_regs(oa);
  keep_regs(ob);
  PROF(wg, 0);
  if (threadIdx.x == 0) GT(1);

  for (int k = wg; k < nt; k += 2) {
    const uint32_t ph = (k >> 1) & 1;
    const int it = k >> 1;
    uint32_t qa[24], qb[24], hok[3];
    uint32_t fl = geo[1];
    {
      float acc[96];
      const uint32_t xp = (k + (k > 0)) & 1;
      const uint32_t xok = mbar_test(bar_x(bars, k > 0, 0), xp);
      if (k > 0) nb_sync(1 + (1 - wg));
#pragma unroll
      for (int s = 0; s < 12; s++) {
        if (s == 0) mbar_wait_if(xok, bar_x(bars, k > 0, 0), xp);
        if (s == 0 && k < 2) PROF(wg, 1);
        if (s == 0) PROFS(2, wg, 2 + it * 12);
        if (s == 0 && w == 0 && k < 2) GT(20 + wg);
        if ((s & 3) == 0 && (k == 0 || s > 0)) {
          mbar_wait(k == 0 ? bar_w1c(bars, s >> 2) : bar_x(bars, 1, s >> 2), xp);
          PROFS(17, wg, 50 + (s >> 2));
        }
        if ((s & 3) == 0) wg_fence();
        const uint64_t dX = make_desc(sbase + x_chunk(k, s >> 2), 16, 1024) + 2 * (s & 3);
        if (s == 0) wg_m192z<0, 96>(acc, dX, dW1, 0);
        else wg_m192<0, 96>(acc, dX, wdesc(dW1, s), 1);
        if ((s & 3) == 3) wg_commit();
      }
      PROFS(13, wg, 13 + it * 12);
      const uint32_t e = sts + out_slot(k, nt), o = e ^ 64;
      uint32_t ad[4] = {wg ? o + 1024 : e, wg ? e + 2048 : o, wg ? e : o + 1024, wg ? o : e + 2048};
      keep_regs(ad);
      wg_wait<2>();
      if (k > 0) nb_arrive_p(0);
      wg_wait<1>();
      if (k > 0) nb_arrive_p(14);
      wg_wait<0>();
      if (k > 0) {
        nb_arrive_p(6);
        sched_fence();
      }
      fence_regs(acc);
      PROFS(3, wg, 3 + it * 12);
#pragma unroll
      for (int j = 0; j < 24; j++) {
        qa[j] = pack_bf16(acc[4 * j], acc[4 * j + 1]);
        qb[j] = pack_bf16(acc[4 * j + 2], acc[4 * j + 3]);
      }
      keep_regs(qa);
      keep_regs(qb);
      sched_fence();
      if (k >= 2) {
        nb_sync(11);
        stage_out<0, 6>(ad, oa, ob);
        nb_sync(12);
        stage_out<6, 12>(ad, oa, ob);
      }
#pragma unroll
      for (int c = 0; c < 3; c++) hok[c] = mbar_test(bar_full(bars, wg, c), ph);
      if (k >= 2) {
        fence_proxy_async();
        nb_arrive_p(10);
      }
    }

    float aE[52], aO[24], bO[52], bE[28];
    const uint32_t mq = 0xEEEE4444u | zero;
    PROFS(4, wg, 4 + it * 12);

    mbar_wait_if(hok[0], bar_full(bars, wg, 0), ph);
    PROFS(14, wg, 40 + it * 3);
    if (w == 0 && k < 2) GT(22 + wg);
    if (k > 0) nb_sync(3 + (1 - wg));
    wg_fence();
#pragma unroll
    for (int ks = 0; ks < 6; ks++) {
      if (ks == 2) {
        mbar_wait_if(hok[1], bar_full(bars, wg, 1), ph);
        PROFS(14, wg, 41 + it * 3);
        wg_fence();
      }
      if (ks == 4) {
        mbar_wait_if(hok[2], bar_full(bars, wg, 2), ph);
        PROFS(14, wg, 42 + it * 3);
        wg_fence();
      }
      const uint64_t d = dK + ((ks * kChunkBytes) >> 4);
      if (ks == 0) wg_s104z<0, 52>(aE, qa[0], qa[1], qa[2], qa[3], d, 0, mq);
      else wg_s104<0, 52>(aE, qa[4 * ks], qa[4 * ks + 1], qa[4 * ks + 2], qa[4 * ks + 3], d, 1, mq);
      if (ks == 0) wg_s48z<0, 24>(aO, qa[0], qa[1], qa[2], qa[3], d + ((7 * 1024 + 64) >> 4), 0, mq);
    }
    wg_commit();
#pragma unroll
    for (int ks = 1; ks < 6; ks++)
      wg_s48<0, 24>(aO, qa[4 * ks], qa[4 * ks + 1], qa[4 * ks + 2], qa[4 * ks + 3], dK + ((ks * kChunkBytes + 7 * 1024 + 64) >> 4), 1, mq);
    wg_commit();
    wg_s56z<0, 28>(bE, qb[0], qb[1], qb[2], qb[3], dK, 0, mq);
#pragma unroll
    for (int ks = 1; ks < 6; ks++) wg_s56<0, 28>(bE, qb[4 * ks], qb[4 * ks + 1], qb[4 * ks + 2], qb[4 * ks + 3], dK + ((ks * kChunkBytes) >> 4), 1, mq);
    wg_commit();
    wg_wait<2>();
    fence_regs(aE);
    PROFS(5, wg, 5 + it * 12);

    uint32_t pa[14], pb[14], meta[4];
    {
      float vA[14], vB[14];
      pick_v(aE, vA, fl);
      pick_u(aE + 28, vA + 8, fl);
      fence_regs(vA);
      if (k == 0) {
        if (__builtin_expect(__any_sync(0xffffffffu, vA[6] != vA[6]), 0)) {
          wg_wait<0>();
          fence_regs(aO);
          fence_regs(bE);
          if (refetch(sbase + kW1Off, wimg, false)) {
#pragma unroll
            for (int j = 0; j < 24; j++) oa[j] = ob[j] = 0u;
            k -= 2;
            continue;
          }
        }
        if (elect_one()) mbar_arrive(bar_xf(bars));
      }
      wg_fence();
      wg_s104z<0, 52>(bO, qb[0], qb[1], qb[2], qb[3], dK + 4, 0, mq);
#pragma unroll
      for (int ks = 1; ks < 6; ks++)
        wg_s104<0, 52>(bO, qb[4 * ks], qb[4 * ks + 1], qb[4 * ks + 2], qb[4 * ks + 3], dK + ((ks * kChunkBytes + 64) >> 4), 1, mq);
      wg_commit();
      if (k + 1 < nt) nb_arrive(1 + wg);
      uint32_t rt[9];
#pragma unroll
      for (int i = 0; i < 7; i++) rt[i] = sign_bytes(geo[0] << (i >> 2), 0x8888u + 0x1111u * (i & 3));
      rt[7] = sign_bytes(geo[0] << 2, 0x9988u);
      rt[8] = sign_bytes(geo[0] << 2, 0xBBAAu);
      keep_regs(rt);
      pa[13] = geo[0] & zero, pb[13] = geo[1] & zero;
      wg_wait<2>();
      keep_regs(qa);
      fence_regs(aO);
      float oA[6], eB[8];
      pick_u(aO, oA, fl);
      wg_wait<1>();
      fence_regs(bE);
      pick_v(bE, eB, fl);
      vA[8] = sel<kColA>(oA[0], vA[8], fl), vA[9] = sel<kColA>(oA[1], vA[9], fl);
      vA[10] = sel<kColA * 2>(oA[2], vA[10], fl), vA[11] = sel<kColA * 2>(oA[3], vA[11], fl);
      vA[12] = sel<kColA * 4>(oA[4], vA[12], fl), vA[13] = sel<kColA * 4>(oA[5], vA[13], fl);
      {
        const float m1 = __uint_as_float(0x88DD88DDu), m0 = __uint_as_float(0x88DDDD88u);
        meta[0] = 0xDD88DD88u ^ __byte_perm(fl, 0u, 0x3344);
        meta[1] = __float_as_uint(sel<kColA * 16>(sel<kColA>(m1, m0, fl), __uint_as_float(meta[0]), fl));
        meta[2] = __float_as_uint(sel<kColA * 8>(m1, m0, fl));
        meta[3] = __float_as_uint(sel<kColA * 4>(m1, m0, fl));
        keep_regs(meta);
      }
      float mA = own_max(vA, fl);
      fl |= __float_as_uint(eB[7]) & zero;
      fence_regs(eB);
      fence_regs(vA);
      asm volatile("" : "+f"(mA), "+r"(fl));
      sched_fence();
      wg_wait<0>();
      sched_fence();
      keep_regs(qb);
      fence_regs(bO);
      PROFS(6, wg, 6 + it * 12);
      if (w == 0) GT(24 + k);
      mA = quad_max(mA);
      pick_v(bO, vB, fl);
      pick_u(bO + 28, vB + 8, fl);
#pragma unroll
      for (int i = 0; i < 8; i += 2) vB[i] = sel<kColB>(vB[i], eB[i], fl), vB[i + 1] = sel<kColB * 2>(vB[i + 1], eB[i + 1], fl);
#pragma unroll
      for (int i = 0; i < 14; i++) vA[i] = i < 3 ? ex2(vA[i] - mA) : vA[i] - mA;
      fence_regs(vA);
      fence_regs(vB);
      sched_fence();
#pragma unroll
      for (int i = 3; i < 14; i++) vA[i] = ex2(vA[i]);
      const float mB = quad_max(own_max(vB, fl));
      PROFS(7, wg, 7 + it * 12);
#pragma unroll
      for (int i = 0; i < 14; i++) vB[i] = i < 1 ? ex2(vB[i] - mB) : vB[i] - mB;
      fence_regs(vA);
      fence_regs(vB);
      sched_fence();
#pragma unroll
      for (int i = 1; i < 14; i++) vB[i] = ex2(vB[i]);
      route(vA, row_rcp(vA, fl), rt, pa);
      route(vB, row_rcp(vB, fl), rt, pb);
    }
    PROFS(8, wg, 8 + it * 12);
    if (k == NAT_PK) PROFS(18, wg, 53);
    sched_fence();

    float ac0[48], ac1[48];
    {
      float z0[32], z1[32], z2[32];
      uint32_t za[24], zb[24];
      wg_fence();
      pv_chunk<0>(z0, pa, pb, meta, dV);
      wg_commit();
      pv_chunk<1>(z1, pa, pb, meta, dV);
      wg_commit();
      wg_wait<1>();
      if (k == NAT_PK) PROFS(18, wg, 54);
      if (k + 1 < nt) nb_arrive_p(7);
      pv_chunk<2, 0, 3>(z2, pa, pb, meta, dV);
      wg_commit();
      sched_fence();
      fence_regs(z0);
      pack_z<0>(z0, za, zb);
      sched_fence();
      wg_fence();
      pv_chunk<2, 3, 7>(z2, pa, pb, meta, dV);
      wg_commit();
      wg_wait<2>();
      if (k == NAT_PK) PROFS(19, wg, 55);
      if (k + 1 < nt) nb_arrive_p(8);
      if (k < 2) mbar_wait(k == 1 ? bar_wok(bars) : bar_w2a(bars), 0);
      wg_fence();
      g2_steps<0, 3, 0>(ac0, za, zb, dX0);
      wg_commit();
      sched_fence();
      fence_regs(z1);
      pack_z<1>(z1, za, zb);
      sched_fence();
      wg_fence();
      g2_steps<3, 4, 0>(ac0, za, zb, dX0);
      wg_commit();
      g2_steps<4, 8, 0>(ac0, za, zb, dX0);
      wg_commit();
      wg_wait<3>();
      if (k + 1 < nt) nb_arrive_p(9);
      else nb_arrive(11);
      if (k == NAT_PK) PROFS(20, wg, 56);
      keep_regs(pa);
      keep_regs(pb);
      keep_regs(meta);
      sched_fence();
      const uint32_t mok = mbar_test(bar_w2m(bars), k + 1 < nt ? k & 1 : ~k & 1);
      const uint32_t wp = k < 2 ? 0 : k + 1 < nt ? ~k & 1 : k & 1, wok = mbar_test(bar_w2(bars), wp);
      fence_regs(z2);
      pack_z<2>(z2, za, zb);
      keep_regs(za);
      keep_regs(zb);
      sched_fence();
      PROFS(9, wg, 9 + it * 12);
      wg_wait<1>();
      if (k > 0 && k + 1 < nt) nb_arrive(11);
      mbar_wait_if(mok, bar_w2m(bars), k & 1);
      wg_fence();
      g2_steps<8, 12, 0>(ac0, za, zb, dX2);
      wg_commit();
      g2_steps<8, 12, 8>(ac1, za, zb, dY2);
      wg_commit();
      wg_wait<2>();
      if (k > 0 && k + 1 < nt) nb_arrive(12);
      mbar_wait_if(wok, bar_w2(bars), wp);
      wg_fence();
      g2_steps<0, 4, 8>(ac1, za, zb, dY0);
      wg_commit();
      wg_wait<2>();
      if (k + 2 < nt) nb_arrive_p(13);
      const bool direct = k + 2 >= nt;
      sched_fence();
      fence_regs(ac0);
      pack_out<0>(ac0, oa, ob);
      store_rows<0, 1>(direct, poA, poB, oa, ob);
      sched_fence();
      wg_fence();
      g2_steps<4, 8, 8>(ac1, za, zb, dY0);
      wg_commit();
      if (k + 1 < nt) nb_arrive(3 + wg);
      PROFS(10, wg, 10 + it * 12);
      wg_wait<2>();
      if (k + 2 < nt && (k > 0 || nt == 6)) nb_arrive_p(5);
      store_rows<1, 3>(direct, poA, poB, oa, ob);
      __nv_bfloat16 *qA = poA - 192 * wg, *qB = poB - 192 * wg;
      if (k + 2 == nt) nb_sync(11);
      sched_fence();
      wg_wait<0>();
      fence_regs(ac1);
      pack_out<1>(ac1, oa, ob);
      asm volatile("" : "+l"(qA), "+l"(qB));
      store_rows<3, 6>(direct, qA, qB, oa, ob);
      if (direct) break;
      if (k == 0) {
        if (any_nan(oa)) {
          for (int c = 0; c < 3 && __any_sync(0xffffffffu, geo[2] & 1u); c++) mbar_wait(bar_x(bars, 1, c), 1);
          bool first = true;
          do {
            if (!__any_sync(0xffffffffu, refetch(sbase + kW2Off, wimg + w2_offset(), first))) break;
            first = false;
            wg_fence();
            g2_steps<0, 8, 0>(ac0, za, zb, dX0);
            g2_steps<8, 12, 0>(ac0, za, zb, dX2);
            g2_steps<8, 12, 8>(ac1, za, zb, dY2);
            g2_steps<0, 8, 8>(ac1, za, zb, dY0);
            wg_commit();
            wg_wait<0>();
            fence_regs(ac0);
            fence_regs(ac1);
            pack_out<0>(ac0, oa, ob);
            pack_out<1>(ac1, oa, ob);
          } while (any_nan(oa));
          if (__any_sync(0xffffffffu, geo[2] & 1u)) {
            asm volatile("bar.sync 15, 128;" ::: "memory");
            if (w == 0 && elect_one()) {
              const TileCoord tc = decode_tile(tt, tile0 + 2);
              mbar_arrive_expect_tx(bar_raw(bars), kWChunk);
#pragma unroll 1
              for (int c = 0; c < 3; c++) load_px(tm, tt, sbase + x_chunk(2, c), bar_raw(bars), first_line(tc) + c, tc.kind);
            }
            __syncwarp();
            mbar_wait(bar_raw(bars), 0);
          }
        }
        if (nt < 6) nb_arrive_p(5);
        if (elect_one()) mbar_arrive(bar_wok(bars));
      }
      keep_regs(za);
      keep_regs(zb);
#pragma unroll
      for (int i = 0; i < 4; i++) geo[i] = geo[i + 2];
      keep_regs(oa);
      keep_regs(ob);
      PROFS(12, wg, 12 + it * 12);
      sched_fence();
    }
  }
  PROF(wg, 38);
  GT_DUMP();
  PROF_DUMP(wg);
}

struct HaloCols { int vj, vc, uj, uc; };
__device__ __forceinline__ HaloCols halo_cols(const TileCoord& tc) {
  const int c0 = halo_c0(tc);
  return HaloCols{c0 > 98, c0 > 98 ? 98 : c0 + 3, c0 < 0 ? -1 : 0, c0 < 0 ? 4 : c0};
}
__device__ __forceinline__ void first_halo(const Maps& tm, uint32_t sbase, const TileCoord tc, int i) {
  const HaloCols hc = halo_cols(tc);
  const uint32_t dst = sbase + i * kChunkBytes, bar = bar_full(sbase + kBarOff, 0, i >> 1);
  const int h0 = halo_r0(tc), ch = 24 * tc.pc + 4 * i;
  tma_load_5d(dst, &tm.v14, bar, ch, hc.vj, hc.vc, tc.pr, h0);
  tma_load_5d(dst + 7 * 1024, &tm.u8, bar, ch, hc.uj, h0 + (tc.up ? 0 : -2), tc.pr, hc.uc);
  tma_load_5d(dst + 10 * 1024, &tm.u8, bar, ch, hc.uj, h0 + (tc.up ? 8 : 6), tc.pr, hc.uc);
}
__device__ __forceinline__ void load_halo(const Maps& tm, uint32_t sbase, uint32_t bars, const TileCoord tc, int k, int c) {
  const HaloCols hc = halo_cols(tc);
  const int h6 = halo_r0(tc) + (tc.up ? 0 : 8), h2 = halo_r0(tc) + 6, h8 = halo_r0(tc) + (tc.up ? 0 : 6), ch = 24 * tc.pc + 8 * c;
  uint32_t dv = sbase + 2 * c * kChunkBytes, du = dv + 7 * 1024;
  if (((k ^ tc.up) & 1) == 0) dv += 4 * 1024, du += 3 * 1024;
  const uint32_t bar = bar_full(bars, k & 1, c);
  mbar_arrive_expect_tx(bar, 14 * 1024);
  nb_sync_p(7 + c);
#pragma unroll
  for (int h = 0; h < 2; h++) {
    tma_load_5d(dv + h * kChunkBytes, &tm.v6, bar, ch + 4 * h, hc.vj, hc.vc, tc.pr, h6);
    tma_load_5d(du + h * kChunkBytes, &tm.u8, bar, ch + 4 * h, hc.uj, h8, tc.pr, hc.uc);
    tma_load_5d(sbase + (2 * c + h) * kChunkBytes + 3 * 1024, &tm.v2, bar, ch + 4 * h, hc.vj, hc.vc, tc.pr, h2);
  }
  PROFS(15, 2, k * 4 + c);
}
__device__ __forceinline__ void gather_px(const __nv_bfloat16* __restrict__ x, uint32_t sbase, const TileCoord tc) {
  const int lane = threadIdx.x & 31, g = lane >> 3;
  uint32_t ro[4], co[4];
#pragma unroll
  for (int i = 0; i < 4; i++) {
    ro[i] = qpix(tc.pr, 8 * tc.I + 2 * i + (g & 1)) * (kW * kC * 2) + 16 * (lane & 7);
    co[i] = qpix(tc.pc, 8 * tc.J + 2 * i + (g >> 1)) * (kC * 2);
  }
  const uint32_t dst = sbase + kXOff + g * 128 + (((lane & 7) ^ g) << 4);
  if (lane < 8)
    asm volatile("cp.async.bulk.prefetch.L2.global [%0], 3456;" ::"l"(x + (qpix(tc.pr, 8 * tc.I + lane) * kW + 215 * tc.pc) * kC) : "memory");
  __syncwarp();
  keep_regs(ro);
  keep_regs(co);
  sched_fence();
  nb_sync_p(13);
  nb_sync_p(5);
#pragma unroll
  for (int i = 0; i < 16; i++) {
    const char* src = (const char*)x + (ro[i >> 2] + co[i & 3]);
#pragma unroll
    for (int q = 0; q < 3; q++)
      asm volatile("cp.async.cg.shared.global [%0], [%1], 16;" ::"r"((dst ^ ((i & 1) * 576)) + (i >> 1) * 1024 + q * 8192), "l"(src + 128 * q) : "memory");
  }
  asm volatile("cp.async.wait_all;" ::: "memory");
  fence_proxy_async();
  __syncwarp();
  if (lane < 3) mbar_arrive(bar_x(sbase + kBarOff, 1, lane));
  __syncwarp();
}

__global__ void __launch_bounds__(384, 1)
nat_kernel(const __nv_bfloat16* __restrict__ x, __nv_bfloat16* out, const __nv_bfloat16* __restrict__ wqkv,
           const __nv_bfloat16* __restrict__ wo, uint8_t* wimg, const uint32_t zero,
           const __grid_constant__ Maps tm, const __grid_constant__ TileTable tt) {
  extern __shared__ uint8_t smem_raw[];
  constexpr uint32_t sbase = 1024;
  constexpr uint32_t bars = sbase + kBarOff;
  if (smem_u32(smem_raw) != sbase) __trap();
  const int tid = threadIdx.x;
  const uint32_t t_start = now_ns();
  if (tid == 0) GT(0);
  const int wid = __shfl_sync(0xffffffffu, tid >> 5, 0);
  const bool w2cta = blockIdx.x - 128 < 3 && wqkv != nullptr;
  if (wid >= 8) {
    asm volatile("setmaxnreg.dec.sync.aligned.u32 24;");
    const int c = wid & 3, lane = tid & 31;
    const int tile0 = blockIdx.x * kTilesPerCta, nt = num_tiles();
    uint32_t w2o = 0;
    if (c == 3) {
      if (elect_one()) wait_clock(t_start, NAT_TM);
      __syncwarp();
      asm volatile("prefetch.tensormap [%0];" ::"l"((uint64_t)tm.px) : "memory");
      asm volatile("prefetch.tensormap [%0];" ::"l"((uint64_t)&tm.v6) : "memory");
      asm volatile("prefetch.tensormap [%0];" ::"l"((uint64_t)&tm.v2) : "memory");
      asm volatile("prefetch.tensormap [%0];" ::"l"((uint64_t)(tm.px + (blockIdx.x < 112 ? 5 : 6))) : "memory");
      asm volatile("prefetch.tensormap [%0];" ::"l"((uint64_t)(tm.px + 7)) : "memory");
      if (nt < 6) {
        asm volatile("prefetch.tensormap [%0];" ::"l"((uint64_t)(tm.px + 1)) : "memory");
        asm volatile("prefetch.tensormap [%0];" ::"l"((uint64_t)(tm.px + 2)) : "memory");
        asm volatile("prefetch.tensormap [%0];" ::"l"((uint64_t)&tm.v14) : "memory");
        asm volatile("prefetch.tensormap [%0];" ::"l"((uint64_t)&tm.u8) : "memory");
      }
      __nanosleep(NAT_TW2 - 2800);
      asm volatile("bar.sync 4, 64;" ::: "memory");
      w2o = w2_offset();
      if (elect_one()) {
        mbar_arrive_expect_tx(bar_w2a(bars), kWChunk);
        mbar_arrive_expect_tx(bar_w2(bars), kWChunk);
        wait_clock(t_start, NAT_TW2);
        bulk_load(sbase + kW2Off, wimg + w2o, kWChunk, bar_w2a(bars));
        mbar_wait(bar_xf(bars), 0);
        bulk_load(sbase + kW2Off + 2 * kWChunk, wimg + (w2o + 2 * kWChunk), kWChunk, bar_w2(bars));
      }
      __syncwarp();
      if (nt < 6) gather_px(x, sbase, decode_tile(tt, tile0 + 2));
      if (wqkv == nullptr) return;
      mbar_wait(bar_wok(bars), 0);
      if (lane == 0) asm volatile("red.relaxed.gpu.global.add.u32 [%0], 1;" ::"l"(g_flag) : "memory");
      if (blockIdx.x != kCtas - 1) return;
#pragma unroll
      for (int i = 0; i < 8; i++) asm volatile("st.shared.v4.u32 [%0], {%1,%1,%1,%1};" ::"r"(bars + 1024 + i * 512 + lane * 16), "r"(kEmpty) : "memory");
      fence_proxy_async();
      __syncwarp();
      if (elect_one()) {
#pragma unroll 1
        for (int i = 0; i < 36; i++) {
          if (i == 18) {
            uint32_t v, it = 0;
            do {
              __nanosleep(500);
              asm volatile("ld.relaxed.gpu.global.u32 %0, [%1];" : "=r"(v) : "l"(g_flag) : "memory");
            } while (v < gridDim.x && ++it < (1u << 18));
          }
          asm volatile("cp.async.bulk.global.shared::cta.bulk_group [%0], [%1], 4096;" ::"l"(
                           wimg + (i < 18 ? 3 * kWBytes - w2o + i * 4096 : (i - 18) * 4096)), "r"(bars + 1024) : "memory");
          asm volatile("cp.async.bulk.commit_group;" ::: "memory");
          asm volatile("cp.async.bulk.wait_group.read 1;" ::: "memory");
        }
        asm volatile("cp.async.bulk.wait_group 0;" ::: "memory");
        g_flag[0] = 0;
        g_flag[32] = w2o == kWBytes;
      }
      return;
    }
    if (!elect_one()) return;
    if (c == 0) {
      for (int i = 0; i < kNumBars; i++)
        if ((i != 0 && i != 10 || nt < 6) && (i != 21 || !w2cta)) mbar_init(bars + i * 8, i == 13 || i == 16 ? 4 : 1);
      asm volatile("st.shared.v2.u32 [%0], {%1,%1};" ::"r"(bars + 192), "r"(0) : "memory");
      asm volatile("fence.mbarrier_init.release.cluster;" ::: "memory");
      if (w2cta) asm volatile("bar.sync 10, 64;" ::: "memory");
      asm volatile("bar.arrive 0, 160;" ::: "memory");
      asm volatile("bar.arrive 14, 160;" ::: "memory");
      asm volatile("bar.arrive 13, 96;" ::: "memory");
      asm volatile("bar.arrive 4, 64;" ::: "memory");
      const TileCoord tc0 = decode_tile(tt, tile0);
      const HaloCols hc = halo_cols(tc0);
      const int h0 = halo_r0(tc0);
#pragma unroll
      for (int j = 0; j < 3; j++)
        if (j > 0 || nt < 6) mbar_arrive_expect_tx(bar_full(bars, 0, j), 2 * kChunkBytes);
      wait_clock(t_start, NAT_HP);
#pragma unroll
      for (int q = 8; q < 24 && !w2cta; q += 8) {
        tma_prefetch_5d(blockIdx.x < 112 ? &tm.v6 : &tm.v14, 24 * tc0.pc + q, hc.vj, hc.vc, tc0.pr, h0 + (tc0.up || blockIdx.x >= 112 ? 0 : 8));
        tma_prefetch_5d(&tm.u8, 24 * tc0.pc + q, hc.uj, h0 + (tc0.up ? 0 : 6), tc0.pr, hc.uc);
      }
#pragma unroll 1
      for (int i = nt < 6 ? 0 : 2; i < 6; i++) {
        if (i == 2) mbar_wait(bar_w1q(bars), 0);
        first_halo(tm, sbase, tc0, i);
      }
      mbar_arrive(bar_go(bars));
      w2o = w2_offset();
    } else {
      asm volatile("bar.sync 13, 96;" ::: "memory");
      if (c == 2) {
        if (wqkv != nullptr && blockIdx.x < 131) asm volatile("bar.sync 12, 64;" ::: "memory");
        const uint32_t c0 = clock();
        while ((uint32_t)clock() - c0 < NAT_TD && nt == 6) { }
        wait_clock(t_start, NAT_T0);
#pragma unroll
        for (int j = 0; j < 3; j++) {
          mbar_arrive_expect_tx(bar_w1c(bars, j), kWChunk);
          bulk_load(sbase + kW1Off + j * kWChunk, wimg + j * kWChunk, kWChunk, bar_w1c(bars, j));
        }
        mbar_arrive(bar_w1q(bars));
        GT(2);
      } else {
#pragma unroll 1
        for (int j = nt == 6; j < 2; j++) {
          const TileCoord tc = decode_tile(tt, tile0 + j);
          const int line = first_line(tc);
          if (j == 1) mbar_wait(bar_go(bars), 0);
          if (j == 0) GT(15);
#pragma unroll 1
          for (int q = 0; q < 3; q++) {
            load_px(tm, tt, sbase + x_chunk(j, q), bar_x(bars, j, q), line + q, tc.kind);
            if (j == 1 || q == 0) mbar_arrive_expect_tx(bar_x(bars, j, q), j ? 8192 : kWChunk);
          }
          if (j == 0) GT(16);
        }
        w2o = w2_offset();
        wait_clock(t_start, NAT_TW2);
        mbar_wait(bar_xf(bars), 0);
      }
    }
#pragma unroll 1
    for (int k = 1; k < nt; k++) {
      const TileCoord tn = decode_tile(tt, tile0 + k + 1);
      const int line = first_line(tn);
      const bool more = k + 1 < nt && (k > 1 || nt == 6);
      if (c == 1) {
#pragma unroll
        for (int q = 0; q < 3; q++) {
          nb_sync_p(q == 0 ? 0 : q == 1 ? 14 : 6);
          bulk_load(sbase + x_chunk(k, q), wimg + (w2o + x_chunk(k, q) - kW2Off), 8192, bar_w2m(bars));
        }
        mbar_arrive_expect_tx(bar_w2m(bars), kWChunk);
      }
      if (c == 2) {
        if (k == 1) wait_clock(t_start, NAT_TX2);
        else __nanosleep(NAT_PFD);
#pragma unroll 1
        for (int q = 0; q < 3 && more; q++) load_px(tm, tt, 0, 0, line + q, tn.kind);
      }
      if (c == 2 && (blockIdx.x >= 112 || k == 5)) {
        const TileCoord tc = decode_tile(tt, tile0 + k);
        const HaloCols hc = halo_cols(tc);
        const int h8 = halo_r0(tc) + (tc.up ? 0 : 6);
#pragma unroll 1
        for (int q = 0; q < 24; q += 8) {
          tma_prefetch_5d(&tm.v6, 24 * tc.pc + q, hc.vj, hc.vc, tc.pr, h8);
          tma_prefetch_5d(&tm.v2, 24 * tc.pc + q, hc.vj, hc.vc, tc.pr, h8 + 6);
          tma_prefetch_5d(&tm.u8, 24 * tc.pc + q, hc.uj, h8, tc.pr, hc.uc);
        }
      }
      load_halo(tm, sbase, bars, decode_tile(tt, tile0 + k), k, c);
      if (c == 0 && more) {
#pragma unroll
        for (int q = 0; q < 3; q++) {
          if (q < 2) nb_sync_p(q ? 5 : 13);
          load_px(tm, tt, sbase + x_chunk(k + 1, q), bar_x(bars, 1, q), line + q, tn.kind);
          if (q != 1) mbar_arrive_expect_tx(bar_x(bars, 1, q), 8192);
        }
        mbar_arrive_expect_tx(bar_x(bars, 1, 1), 8192);
        PROFS(16, 2, k * 4 + 3);
      }
      if (c == 0 && k >= 2) {
        const TileCoord tp = decode_tile(tt, tile0 + k - 2);
        const int lp = first_line(tp);
        nb_sync_p(10);
        __nanosleep(NAT_XW);
        store_px(tm, tt, sbase + out_slot(k, nt), lp, tp.kind);
        if (k + 1 < nt) {
          asm volatile("cp.async.bulk.wait_group.read 0;" ::: "memory");
          bulk_load(sbase + out_slot(k, nt), wimg + (w2o + out_slot(k, nt) - kW2Off), kWChunk, bar_w2(bars));
          mbar_arrive_expect_tx(bar_w2(bars), kWChunk);
        }
      }
    }
    asm volatile("cp.async.bulk.wait_group 0;" ::: "memory");
  } else {
    if (blockIdx.x < 128) {
      if ((wid == 4 || (wid == 5 && blockIdx.x - 2 < 16)) && wqkv != nullptr) {
        fold_w1(blockIdx.x - 2 < 16 ? 2 * blockIdx.x + wid - 6 : blockIdx.x + (blockIdx.x < 2 ? 0 : 16), wqkv, wimg);
        if (wid == 4) asm volatile("bar.arrive 12, 64;" ::: "memory");
        if (tid == 128) GT(7);
      }
      sched_fence();
      if (wid == 1 && elect_one()) {
        const TileCoord tc = decode_tile(tt, blockIdx.x * kTilesPerCta);
        mbar_init(bar_x(bars, 0, 0), 1);
        asm volatile("fence.mbarrier_init.release.cluster;" ::: "memory");
        mbar_arrive_expect_tx(bar_x(bars, 0, 0), kWChunk);
        GT(15);
#pragma unroll 1
        for (int q = 0; q < 3; q++) load_px(tm, tt, sbase + x_chunk(0, q), bar_x(bars, 0, 0), first_line(tc) + q, tc.kind);
        GT(16);
      }
      __syncwarp();
      sched_fence();
      if (wid == 2 && elect_one()) {
        const TileCoord tc = decode_tile(tt, blockIdx.x * kTilesPerCta);
        mbar_init(bar_full(bars, 0, 0), 1);
        asm volatile("fence.mbarrier_init.release.cluster;" ::: "memory");
        mbar_arrive_expect_tx(bar_full(bars, 0, 0), 2 * kChunkBytes);
        asm volatile("prefetch.tensormap [%0];" ::"l"((uint64_t)&tm.u8) : "memory");
        GT(17);
        first_halo(tm, sbase, tc, 0);
        first_halo(tm, sbase, tc, 1);
      }
      __syncwarp();
    }
    sched_fence();
    {
      if (blockIdx.x >= 128 && wqkv != nullptr && (wid | 2) == 2 && elect_one())
        asm volatile("cp.async.bulk.prefetch.L2.global [%0], %1;" ::"l"(wid ? wo + (blockIdx.x & 3) * 48 * 192 : wqkv + (blockIdx.x & 3) * 48 * 576),
                     "r"(wid ? 48 * 384 : 48 * 1152) : "memory");
      __syncwarp();
      if (w2cta) {
        const int q = blockIdx.x & 3, h = wid >> 2;
        uint32_t w2o = 0;
        if (wid == 1 && elect_one()) {
          asm volatile("prefetch.tensormap [%0];" ::"l"((uint64_t)&tm.wo) : "memory");
          mbar_init(bar_raw(bars, 0), 1);
          mbar_init(bar_raw(bars, 1), 1);
          asm volatile("fence.mbarrier_init.release.cluster;" ::: "memory");
#pragma unroll
          for (int j = 0; j < 3; j++)
            asm volatile("cp.async.bulk.tensor.3d.shared::cluster.global.tile.mbarrier::complete_tx::bytes [%0], [%1, {%3, %4, %5}], [%2];" ::"r"(
                             j ? sbase + kW2Off + (j - 1) * (kWBytes / 2) : sbase),
                         "l"((uint64_t)(j ? &tm.wo : &tm.wv)), "r"(bar_raw(bars, j >> 1)), "r"(0), "r"(j ? 0 : 64 * q), "r"(j ? 3 * j - 3 : 6) : "memory");
          mbar_arrive_expect_tx(bar_raw(bars, 0), kWChunk + kWBytes / 2);
          mbar_arrive_expect_tx(bar_raw(bars, 1), kWBytes / 2);
          w2o = w2_offset();
        }
        __syncwarp();
#pragma unroll 1
        for (int r = 1 - h;; r++) {
          if (r > 0) asm volatile("bar.sync 11, 256;" ::: "memory");
          if (r == 2) break;
          if (r > 0) {
            mbar_wait(bar_raw(bars, 0), 0);
            mbar_wait(bar_raw(bars, h), 0);
          }
          if (tid == 0) GT(7);
          float acc[48];
          const uint64_t db = make_desc(sbase + kW2Off + h * (kWBytes / 2), kWChunk / 2, 512, 2);
          wg_fence();
          wg_m96tz<0, 48>(acc, make_desc(sbase, 16, 1024), db, 0);
#pragma unroll
          for (int s = 1; s < 12; s++) wg_m96t<0, 48>(acc, make_desc(sbase + (s >> 2) * 8192 + (s & 3) * 32, 16, 1024), db + s * 64, 1);
          wg_commit();
          wg_wait<0>();
          fence_regs(acc);
          if (tid == 0) GT(19);
          const int m = (tid >> 3) & 3;
#pragma unroll
          for (int j = 0; j < 12; j += 2) {
            const int n = g2_inv(8 * (j + (m >> 1)) + (tid & 7));
            asm volatile("stmatrix.sync.aligned.m8n8.x4.trans.shared.b16 [%0], {%1,%2,%3,%4};" ::"r"(
                             sbase + kW1Off + h * (kWChunk / 2) + n * 128 + (((2 * (wid & 3) + (m & 1)) ^ (n & 7)) << 4)),
                         "r"(pack_bf16(acc[4 * j], acc[4 * j + 1])), "r"(pack_bf16(acc[4 * j + 2], acc[4 * j + 3])),
                         "r"(pack_bf16(acc[4 * j + 4], acc[4 * j + 5])), "r"(pack_bf16(acc[4 * j + 6], acc[4 * j + 7])) : "memory");
          }
          fence_proxy_async();
        }
        if (tid == 0) GT(18);
        if (wid == 1) {
          if (elect_one()) {
#pragma unroll
            for (int i = 0; i < 2; i++)
              asm volatile("cp.async.bulk.global.shared::cta.bulk_group [%0], [%1], %2;" ::"l"(wimg + (w2o + w2piece(i, q) * (kWChunk / 2))),
                           "r"(sbase + kW1Off + i * (kWChunk / 2)), "r"(kWChunk / 2) : "memory");
            asm volatile("cp.async.bulk.commit_group;" ::: "memory");
          }
          __syncwarp();
          asm volatile("bar.arrive 10, 64;" ::: "memory");
          if (elect_one()) asm volatile("cp.async.bulk.wait_group.read 0;" ::: "memory");
          if (tid == 32) GT(31);
          __syncwarp();
          asm volatile("bar.arrive 12, 64;" ::: "memory");
        }
      }
    }
    __syncwarp();
    if (wid < 4) asm volatile("bar.sync 0, 160;" ::: "memory");
    else asm volatile("bar.sync 14, 160;" ::: "memory");
    asm volatile("setmaxnreg.inc.sync.aligned.u32 240;");
    consumer(wid >> 2, out, wimg, sbase, zero, tm, tt);
  }
}

}

typedef CUresult (*PFN_encodeTiled)(CUtensorMap*, CUtensorMapDataType, cuuint32_t, void*, const cuuint64_t*,
                                    const cuuint64_t*, const cuuint32_t*, const cuuint32_t*, CUtensorMapInterleave,
                                    CUtensorMapSwizzle, CUtensorMapL2promotion, CUtensorMapFloatOOBfill);

extern "C" void kernel_launch(void* const* d_in, const int* in_sizes, int n_in, void* d_out, int out_size) {
  const __nv_bfloat16* x = (const __nv_bfloat16*)d_in[0];
  const __nv_bfloat16* wqkv = (const __nv_bfloat16*)d_in[1];
  const __nv_bfloat16* wo = (const __nv_bfloat16*)d_in[2];
  __nv_bfloat16* out = (__nv_bfloat16*)d_out;

  static PFN_encodeTiled encode = nullptr;
  static int num_sms = 0;
  static uint8_t* wimg = nullptr;
  if (!encode) {
    void* fn = nullptr;
    cudaDriverEntryPointQueryResult qres;
    cudaGetDriverEntryPoint("cuTensorMapEncodeTiled", &fn, cudaEnableDefault, &qres);
    encode = (PFN_encodeTiled)fn;
    cudaFuncSetAttribute(nat::nat_kernel, cudaFuncAttributeMaxDynamicSharedMemorySize, nat::kSmemBytes);
    cudaGetSymbolAddress((void**)&wimg, nat::g_wimg32);
    int dev = 0;
    cudaGetDevice(&dev);
    cudaDeviceGetAttribute(&num_sms, cudaDevAttrMultiProcessorCount, dev);
  }
  nat::Maps tm;
  cuuint32_t estr[5] = {1, 1, 1, 1, 1};
  {
    cuuint64_t vdim[5] = {48, 2, 105, 2, 112}, udim[5] = {48, 2, 112, 2, 105};
    cuuint64_t vstr[4] = {7 * 768, 768, 224 * 384, 2 * 224 * 384}, ustr[4] = {7 * 768, 2 * 224 * 384, 224 * 384, 768};
    CUtensorMap* maps[4] = {&tm.v6, &tm.v2, &tm.v14, &tm.u8};
    for (int i = 0; i < 4; i++) {
      cuuint32_t box[5] = {4, 2, i < 3 ? 4u : 8u, 1, i == 0 ? 6u : i == 1 ? 2u : i == 2 ? 14u : 3u};
      encode(maps[i], CU_TENSOR_MAP_DATA_TYPE_UINT32, 5, (void*)x, i < 3 ? vdim : udim, i < 3 ? vstr : ustr, box, estr,
             CU_TENSOR_MAP_INTERLEAVE_16B, CU_TENSOR_MAP_SWIZZLE_128B, CU_TENSOR_MAP_L2_PROMOTION_L2_128B, CU_TENSOR_MAP_FLOAT_OOB_FILL_NONE);
    }
  }
  for (int i = 0; i < 8; i++) {
    const cuuint32_t row = 224 * 384;
    const cuuint32_t shape[8][6] = {{2, 8, 4, 2 * row, 768, 4 * row}, {2, 8, 3, row, 768, 2 * row},     {2, 8, 1, 2 * row, 768, 4 * row},
                                    {8, 2, 3, 2 * row, 4 * 384, 384}, {8, 2, 1, 2 * row, 5 * 384, 384}, {4, 2, 3, 4 * row, 2 * row, 128},
                                    {4, 2, 3, 768, row, 128},         {4, 2, 3, 768, 2 * row, 128}};
    const cuuint32_t* sh = shape[i];
    cuuint64_t dim[5] = {64, sh[0], sh[1], sh[2], 224 * 224 * 3};
    cuuint64_t str[4] = {sh[3], sh[4], sh[5], 128};
    cuuint32_t box[5] = {64, sh[0], sh[1], sh[2], 1};
    encode(tm.px + i, CU_TENSOR_MAP_DATA_TYPE_BFLOAT16, 5, i < 5 ? (void*)x : (void*)out, dim, str, box, estr, CU_TENSOR_MAP_INTERLEAVE_NONE,
           CU_TENSOR_MAP_SWIZZLE_128B, i < 5 ? CU_TENSOR_MAP_L2_PROMOTION_L2_128B : CU_TENSOR_MAP_L2_PROMOTION_NONE,
           CU_TENSOR_MAP_FLOAT_OOB_FILL_NONE);
  }
  for (int i = 0; i < 2; i++) {
    cuuint64_t dim[3] = {i ? 32u : 64u, 192, i ? 6u : 9u}, str[2] = {i ? 384u : 1152u, i ? 64u : 128u};
    cuuint32_t box[3] = {i ? 32u : 64u, i ? 192u : 64u, 3};
    encode(i ? &tm.wo : &tm.wv, CU_TENSOR_MAP_DATA_TYPE_BFLOAT16, 3, i ? (void*)wo : (void*)wqkv, dim, str, box, estr,
           CU_TENSOR_MAP_INTERLEAVE_NONE, i ? CU_TENSOR_MAP_SWIZZLE_64B : CU_TENSOR_MAP_SWIZZLE_128B, CU_TENSOR_MAP_L2_PROMOTION_L2_256B,
           CU_TENSOR_MAP_FLOAT_OOB_FILL_NONE);
  }
  nat::TileTable tt;
  nat::make_tiles(tt);
  const int grid = nat::kCtas;
  if (num_sms >= grid) {
    nat::nat_kernel<<<grid, 384, nat::kSmemBytes>>>(x, out, wqkv, wo, wimg, 0u, tm, tt);
  } else {
    nat::fold_kernel<<<27, 256>>>(wqkv, wo, wimg);
    nat::nat_kernel<<<grid, 384, nat::kSmemBytes>>>(x, out, nullptr, nullptr, wimg, 0u, tm, tt);
  }
}
```

```cpp
#include <cuda_runtime.h>
#include <cuda_bf16.h>
#include <cuda.h>
#include <stdint.h>

#define NAT_TM 1300
#define NAT_HP 1800
#define NAT_T0 2130
#define NAT_TD 1250
#define NAT_TX2 3800
#define NAT_TW2 4600
#define NAT_PFD 300
#define NAT_XW 200
#define NAT_BB 1
#define NAT_GW 1
#define NAT_PK 3
namespace nat {

constexpr int kW = 224, kC = 192;
constexpr int kCtas = 132;
constexpr int kTilesPerCta = 6;
constexpr float kAlpha = 0.07216878364870322f * 1.4426950408889634f;
constexpr uint32_t kChunkBytes = 13 * 1024;
constexpr uint32_t kWChunk = 192 * 128;
constexpr uint32_t kWBytes = 3 * kWChunk;
constexpr uint32_t kW1Off = 6 * kChunkBytes;
constexpr uint32_t kW2Off = kW1Off + kWBytes;
constexpr uint32_t kXOff = kW2Off + kWChunk;
constexpr uint32_t kBarOff = kW2Off + kWBytes;
constexpr uint32_t kProfOff = kBarOff + 208;
constexpr uint32_t kSmemBytes = kBarOff + 1024 + 4096;

static_assert(kW1Off % 1024 == 0 && kW2Off % 1024 == 0 && kChunkBytes % 1024 == 0, "swizzle alignment");
static_assert(kSmemBytes <= 232448, "smem");

constexpr uint32_t kEmpty = 0xFFFFFFFFu;
#define NAT_R8(v) v, v, v, v, v, v, v, v
#define NAT_R2K(v) NAT_R8(NAT_R8(NAT_R8(v))), NAT_R8(NAT_R8(NAT_R8(v))), NAT_R8(NAT_R8(NAT_R8(v))), NAT_R8(NAT_R8(NAT_R8(v)))
#define NAT_IMG NAT_R8(NAT_R2K(kEmpty)), NAT_R2K(kEmpty)
__device__ __align__(1024) uint32_t g_wimg32[3 * kWBytes / 4] = {NAT_IMG, NAT_IMG, NAT_IMG};
static_assert(kWBytes / 4 == 9 * 2048, "initialiser");
__device__ __align__(128) uint32_t g_flag[64];
__device__ __forceinline__ uint32_t w2_offset() {
  uint32_t v;
  asm volatile("ld.relaxed.gpu.global.u32 %0, [%1];" : "=r"(v) : "l"(g_flag + 32) : "memory");
  return (1 + v) * kWBytes;
}

#define PROFS(id, wgid, slotid) do { } while (0)
#define PROF(wgid, slotid) do { } while (0)
#define PROF_DUMP(wgid) do { } while (0)

#define GT(slotid) do { } while (0)
#define GT_DUMP() do { } while (0)

__device__ __forceinline__ uint32_t smem_u32(const void* p) { return (uint32_t)__cvta_generic_to_shared(p); }

__device__ __forceinline__ void mbar_init(uint32_t bar, uint32_t count) {
  asm volatile("mbarrier.init.shared::cta.b64 [%0], %1;" ::"r"(bar), "r"(count) : "memory");
}
__device__ __forceinline__ void mbar_arrive(uint32_t bar) {
  asm volatile("mbarrier.arrive.shared::cta.b64 _, [%0];" ::"r"(bar) : "memory");
}
__device__ __forceinline__ void mbar_arrive_expect_tx(uint32_t bar, uint32_t bytes) {
  asm volatile("mbarrier.arrive.expect_tx.shared::cta.b64 _, [%0], %1;" ::"r"(bar), "r"(bytes) : "memory");
}
__device__ __forceinline__ void mbar_wait(uint32_t bar, uint32_t parity) {
  uint32_t ok;
  uint32_t it = 0;
  do {
    asm volatile(
        "{\n.reg .pred p;\n"
        "mbarrier.try_wait.parity.shared::cta.b64 p, [%1], %2;\n"
        "selp.u32 %0, 1, 0, p;\n}\n"
        : "=r"(ok)
        : "r"(bar), "r"(parity)
        : "memory");
    if (++it > (1u << 24)) break;
  } while (!ok);
}
__device__ __forceinline__ uint32_t mbar_test(uint32_t bar, uint32_t parity) {
  uint32_t ok;
  asm volatile("{\n.reg .pred p;\nmbarrier.test_wait.parity.shared::cta.b64 p, [%1], %2;\nselp.u32 %0, 1, 0, p;\n}\n"
               : "=r"(ok) : "r"(bar), "r"(parity) : "memory");
  return ok;
}
__device__ __forceinline__ void mbar_wait_if(uint32_t ok, uint32_t bar, uint32_t parity) {
  if (!__all_sync(0xffffffffu, ok)) mbar_wait(bar, parity);
}
__device__ __forceinline__ bool elect_one() {
  uint32_t r;
  asm volatile("{\n.reg .pred p;\nelect.sync _|p, 0xffffffff;\nselp.u32 %0, 1, 0, p;\n}\n" : "=r"(r));
  return r != 0;
}
__device__ __forceinline__ void nb_arrive(int id) { asm volatile("bar.arrive %0, 256;" ::"r"(id) : "memory"); }
__device__ __forceinline__ void nb_sync(int id) { asm volatile("bar.sync %0, 256;" ::"r"(id) : "memory"); }
__device__ __forceinline__ void nb_arrive_p(int id) { asm volatile("bar.arrive %0, 160;" ::"r"(id) : "memory"); }
__device__ __forceinline__ void nb_sync_p(int id) { asm volatile("bar.sync %0, 160;" ::"r"(id) : "memory"); }
__device__ __forceinline__ void fence_proxy_async() { asm volatile("fence.proxy.async.shared::cta;" ::: "memory"); }

__device__ __forceinline__ void tma_load_5d(uint32_t dst, const CUtensorMap* map, uint32_t bar, int c0, int c1, int c2,
                                            int c3, int c4) {
  asm volatile(
      "cp.async.bulk.tensor.5d.shared::cluster.global.tile.mbarrier::complete_tx::bytes "
      "[%0], [%1, {%3, %4, %5, %6, %7}], [%2];"
      ::"r"(dst), "l"((uint64_t)map), "r"(bar), "r"(c0), "r"(c1), "r"(c2), "r"(c3), "r"(c4)
      : "memory");
}
__device__ __forceinline__ void bulk_load(uint32_t dst, const void* src, uint32_t bytes, uint32_t bar) {
  asm volatile("cp.async.bulk.shared::cluster.global.mbarrier::complete_tx::bytes [%0], [%1], %2, [%3];"
               ::"r"(dst), "l"((uint64_t)src), "r"(bytes), "r"(bar)
               : "memory");
}

__device__ __forceinline__ void wg_fence() { asm volatile("wgmma.fence.sync.aligned;" ::: "memory"); }
__device__ __forceinline__ void wg_commit() { asm volatile("wgmma.commit_group.sync.aligned;" ::: "memory"); }
template <int N>
__device__ __forceinline__ void wg_wait() { asm volatile("wgmma.wait_group.sync.aligned %0;" ::"n"(N) : "memory"); }

template <int N>
__device__ __forceinline__ void fence_regs(float (&d)[N]) {
#pragma unroll
  for (int i = 0; i < N; i++) asm volatile("" : "+f"(d[i])::"memory");
}
template <int N>
__device__ __forceinline__ void keep_regs(uint32_t (&d)[N]) {
#pragma unroll
  for (int i = 0; i < N; i++) asm volatile("" : "+r"(d[i])::"memory");
}

__device__ __forceinline__ uint32_t pack_bf16(float lo, float hi) {
  uint32_t d;
  asm("cvt.rn.bf16x2.f32 %0, %1, %2;" : "=r"(d) : "f"(hi), "f"(lo));
  return d;
}
__device__ __forceinline__ float ex2(float x) {
  float y;
  asm("ex2.approx.ftz.f32 %0, %1;" : "=f"(y) : "f"(x));
  return y;
}
__device__ __forceinline__ float rcp_approx(float x) {
  float y;
  asm("rcp.approx.ftz.f32 %0, %1;" : "=f"(y) : "f"(x));
  return y;
}
__device__ __forceinline__ uint4 ldg128_nc(const void* p) {
  uint4 v;
  asm volatile("ld.global.nc.v4.u32 {%0,%1,%2,%3}, [%4];" : "=r"(v.x), "=r"(v.y), "=r"(v.z), "=r"(v.w) : "l"(p));
  return v;
}

__device__ __forceinline__ long long clk64() {
  long long c;
  asm volatile("mov.u64 %0, %clock64;" : "=l"(c)::"memory");
  return c;
}
__device__ __forceinline__ void sched_fence() { while (clk64() < 0) { } }

__device__ __forceinline__ uint64_t make_desc(uint32_t addr, uint32_t lbo, uint32_t sbo, uint32_t mode = 1) {
  return (uint64_t)((addr & 0x3FFFF) >> 4) | ((uint64_t)(lbo >> 4) << 16) | ((uint64_t)(sbo >> 4) << 32) |
         ((uint64_t)mode << 62);
}

template <int OFF, int NN>
__device__ __forceinline__ void wg_m192(float (&d)[NN], uint64_t desc_a, uint64_t desc_b, int scale_d) {
  asm volatile(
      "{\n.reg .pred p;\nsetp.ne.b32 p, %98, 0;\n"
      "wgmma.mma_async.sync.aligned.m64n192k16.f32.bf16.bf16 "
      "{%0,%1,%2,%3,%4,%5,%6,%7,%8,%9,%10,%11,%12,%13,%14,%15,"
      "%16,%17,%18,%19,%20,%21,%22,%23,%24,%25,%26,%27,%28,%29,%30,%31,"
      "%32,%33,%34,%35,%36,%37,%38,%39,%40,%41,%42,%43,%44,%45,%46,%47,"
      "%48,%49,%50,%51,%52,%53,%54,%55,%56,%57,%58,%59,%60,%61,%62,%63,"
      "%64,%65,%66,%67,%68,%69,%70,%71,%72,%73,%74,%75,%76,%77,%78,%79,"
      "%80,%81,%82,%83,%84,%85,%86,%87,%88,%89,%90,%91,%92,%93,%94,%95}, "
      "%96, %97, p, 1, 1, 0, 0;\n}\n"
      : "+f"(d[OFF + 0]), "+f"(d[OFF + 1]), "+f"(d[OFF + 2]), "+f"(d[OFF + 3]), "+f"(d[OFF + 4]), "+f"(d[OFF + 5]),
        "+f"(d[OFF + 6]), "+f"(d[OFF + 7]), "+f"(d[OFF + 8]), "+f"(d[OFF + 9]), "+f"(d[OFF + 10]), "+f"(d[OFF + 11]),
        "+f"(d[OFF + 12]), "+f"(d[OFF + 13]), "+f"(d[OFF + 14]), "+f"(d[OFF + 15]), "+f"(d[OFF + 16]), "+f"(d[OFF + 17]),
        "+f"(d[OFF + 18]), "+f"(d[OFF + 19]), "+f"(d[OFF + 20]), "+f"(d[OFF + 21]), "+f"(d[OFF + 22]), "+f"(d[OFF + 23]),
        "+f"(d[OFF + 24]), "+f"(d[OFF + 25]), "+f"(d[OFF + 26]), "+f"(d[OFF + 27]), "+f"(d[OFF + 28]), "+f"(d[OFF + 29]),
        "+f"(d[OFF + 30]), "+f"(d[OFF + 31]), "+f"(d[OFF + 32]), "+f"(d[OFF + 33]), "+f"(d[OFF + 34]), "+f"(d[OFF + 35]),
        "+f"(d[OFF + 36]), "+f"(d[OFF + 37]), "+f"(d[OFF + 38]), "+f"(d[OFF + 39]), "+f"(d[OFF + 40]), "+f"(d[OFF + 41]),
        "+f"(d[OFF + 42]), "+f"(d[OFF + 43]), "+f"(d[OFF + 44]), "+f"(d[OFF + 45]), "+f"(d[OFF + 46]), "+f"(d[OFF + 47]),
        "+f"(d[OFF + 48]), "+f"(d[OFF + 49]), "+f"(d[OFF + 50]), "+f"(d[OFF + 51]), "+f"(d[OFF + 52]), "+f"(d[OFF + 53]),
        "+f"(d[OFF + 54]), "+f"(d[OFF + 55]), "+f"(d[OFF + 56]), "+f"(d[OFF + 57]), "+f"(d[OFF + 58]), "+f"(d[OFF + 59]),
        "+f"(d[OFF + 60]), "+f"(d[OFF + 61]), "+f"(d[OFF + 62]), "+f"(d[OFF + 63]), "+f"(d[OFF + 64]), "+f"(d[OFF + 65]),
        "+f"(d[OFF + 66]), "+f"(d[OFF + 67]), "+f"(d[OFF + 68]), "+f"(d[OFF + 69]), "+f"(d[OFF + 70]), "+f"(d[OFF + 71]),
        "+f"(d[OFF + 72]), "+f"(d[OFF + 73]), "+f"(d[OFF + 74]), "+f"(d[OFF + 75]), "+f"(d[OFF + 76]), "+f"(d[OFF + 77]),
        "+f"(d[OFF + 78]), "+f"(d[OFF + 79]), "+f"(d[OFF + 80]), "+f"(d[OFF + 81]), "+f"(d[OFF + 82]), "+f"(d[OFF + 83]),
        "+f"(d[OFF + 84]), "+f"(d[OFF + 85]), "+f"(d[OFF + 86]), "+f"(d[OFF + 87]), "+f"(d[OFF + 88]), "+f"(d[OFF + 89]),
        "+f"(d[OFF + 90]), "+f"(d[OFF + 91]), "+f"(d[OFF + 92]), "+f"(d[OFF + 93]), "+f"(d[OFF + 94]), "+f"(d[OFF + 95])
      : "l"(desc_a), "l"(desc_b), "r"(scale_d));
}

template <int OFF, int NN>
__device__ __forceinline__ void wg_m192z(float (&d)[NN], uint64_t desc_a, uint64_t desc_b, int scale_d) {
  asm volatile(
      "{\n.reg .pred p;\nsetp.ne.b32 p, %98, 0;\n"
      "wgmma.mma_async.sync.aligned.m64n192k16.f32.bf16.bf16 "
      "{%0,%1,%2,%3,%4,%5,%6,%7,%8,%9,%10,%11,%12,%13,%14,%15,"
      "%16,%17,%18,%19,%20,%21,%22,%23,%24,%25,%26,%27,%28,%29,%30,%31,"
      "%32,%33,%34,%35,%36,%37,%38,%39,%40,%41,%42,%43,%44,%45,%46,%47,"
      "%48,%49,%50,%51,%52,%53,%54,%55,%56,%57,%58,%59,%60,%61,%62,%63,"
      "%64,%65,%66,%67,%68,%69,%70,%71,%72,%73,%74,%75,%76,%77,%78,%79,"
      "%80,%81,%82,%83,%84,%85,%86,%87,%88,%89,%90,%91,%92,%93,%94,%95}, "
      "%96, %97, p, 1, 1, 0, 0;\n}\n"
      : "=f"(d[OFF + 0]), "=f"(d[OFF + 1]), "=f"(d[OFF + 2]), "=f"(d[OFF + 3]), "=f"(d[OFF + 4]), "=f"(d[OFF + 5]),
        "=f"(d[OFF + 6]), "=f"(d[OFF + 7]), "=f"(d[OFF + 8]), "=f"(d[OFF + 9]), "=f"(d[OFF + 10]), "=f"(d[OFF + 11]),
        "=f"(d[OFF + 12]), "=f"(d[OFF + 13]), "=f"(d[OFF + 14]), "=f"(d[OFF + 15]), "=f"(d[OFF + 16]), "=f"(d[OFF + 17]),
        "=f"(d[OFF + 18]), "=f"(d[OFF + 19]), "=f"(d[OFF + 20]), "=f"(d[OFF + 21]), "=f"(d[OFF + 22]), "=f"(d[OFF + 23]),
        "=f"(d[OFF + 24]), "=f"(d[OFF + 25]), "=f"(d[OFF + 26]), "=f"(d[OFF + 27]), "=f"(d[OFF + 28]), "=f"(d[OFF + 29]),
        "=f"(d[OFF + 30]), "=f"(d[OFF + 31]), "=f"(d[OFF + 32]), "=f"(d[OFF + 33]), "=f"(d[OFF + 34]), "=f"(d[OFF + 35]),
        "=f"(d[OFF + 36]), "=f"(d[OFF + 37]), "=f"(d[OFF + 38]), "=f"(d[OFF + 39]), "=f"(d[OFF + 40]), "=f"(d[OFF + 41]),
        "=f"(d[OFF + 42]), "=f"(d[OFF + 43]), "=f"(d[OFF + 44]), "=f"(d[OFF + 45]), "=f"(d[OFF + 46]), "=f"(d[OFF + 47]),
        "=f"(d[OFF + 48]), "=f"(d[OFF + 49]), "=f"(d[OFF + 50]), "=f"(d[OFF + 51]), "=f"(d[OFF + 52]), "=f"(d[OFF + 53]),
        "=f"(d[OFF + 54]), "=f"(d[OFF + 55]), "=f"(d[OFF + 56]), "=f"(d[OFF + 57]), "=f"(d[OFF + 58]), "=f"(d[OFF + 59]),
        "=f"(d[OFF + 60]), "=f"(d[OFF + 61]), "=f"(d[OFF + 62]), "=f"(d[OFF + 63]), "=f"(d[OFF + 64]), "=f"(d[OFF + 65]),
        "=f"(d[OFF + 66]), "=f"(d[OFF + 67]), "=f"(d[OFF + 68]), "=f"(d[OFF + 69]), "=f"(d[OFF + 70]), "=f"(d[OFF + 71]),
        "=f"(d[OFF + 72]), "=f"(d[OFF + 73]), "=f"(d[OFF + 74]), "=f"(d[OFF + 75]), "=f"(d[OFF + 76]), "=f"(d[OFF + 77]),
        "=f"(d[OFF + 78]), "=f"(d[OFF + 79]), "=f"(d[OFF + 80]), "=f"(d[OFF + 81]), "=f"(d[OFF + 82]), "=f"(d[OFF + 83]),
        "=f"(d[OFF + 84]), "=f"(d[OFF + 85]), "=f"(d[OFF + 86]), "=f"(d[OFF + 87]), "=f"(d[OFF + 88]), "=f"(d[OFF + 89]),
        "=f"(d[OFF + 90]), "=f"(d[OFF + 91]), "=f"(d[OFF + 92]), "=f"(d[OFF + 93]), "=f"(d[OFF + 94]), "=f"(d[OFF + 95])
      : "l"(desc_a), "l"(desc_b), "r"(scale_d));
}

template <int OFF, int NN>
__device__ __forceinline__ void wg_m96t(float (&d)[NN], uint64_t desc_a, uint64_t desc_b, int scale_d) {
  asm volatile(
      "{\n.reg .pred p;\nsetp.ne.b32 p, %50, 0;\n"
      "wgmma.mma_async.sync.aligned.m64n96k16.f32.bf16.bf16 "
      "{%0,%1,%2,%3,%4,%5,%6,%7,%8,%9,%10,%11,%12,%13,%14,%15,"
      "%16,%17,%18,%19,%20,%21,%22,%23,%24,%25,%26,%27,%28,%29,%30,%31,"
      "%32,%33,%34,%35,%36,%37,%38,%39,%40,%41,%42,%43,%44,%45,%46,%47}, "
      "%48, %49, p, 1, 1, 0, 1;\n}\n"
      : "+f"(d[OFF + 0]), "+f"(d[OFF + 1]), "+f"(d[OFF + 2]), "+f"(d[OFF + 3]), "+f"(d[OFF + 4]), "+f"(d[OFF + 5]),
        "+f"(d[OFF + 6]), "+f"(d[OFF + 7]), "+f"(d[OFF + 8]), "+f"(d[OFF + 9]), "+f"(d[OFF + 10]), "+f"(d[OFF + 11]),
        "+f"(d[OFF + 12]), "+f"(d[OFF + 13]), "+f"(d[OFF + 14]), "+f"(d[OFF + 15]), "+f"(d[OFF + 16]), "+f"(d[OFF + 17]),
        "+f"(d[OFF + 18]), "+f"(d[OFF + 19]), "+f"(d[OFF + 20]), "+f"(d[OFF + 21]), "+f"(d[OFF + 22]), "+f"(d[OFF + 23]),
        "+f"(d[OFF + 24]), "+f"(d[OFF + 25]), "+f"(d[OFF + 26]), "+f"(d[OFF + 27]), "+f"(d[OFF + 28]), "+f"(d[OFF + 29]),
        "+f"(d[OFF + 30]), "+f"(d[OFF + 31]), "+f"(d[OFF + 32]), "+f"(d[OFF + 33]), "+f"(d[OFF + 34]), "+f"(d[OFF + 35]),
        "+f"(d[OFF + 36]), "+f"(d[OFF + 37]), "+f"(d[OFF + 38]), "+f"(d[OFF + 39]), "+f"(d[OFF + 40]), "+f"(d[OFF + 41]),
        "+f"(d[OFF + 42]), "+f"(d[OFF + 43]), "+f"(d[OFF + 44]), "+f"(d[OFF + 45]), "+f"(d[OFF + 46]), "+f"(d[OFF + 47])
      : "l"(desc_a), "l"(desc_b), "r"(scale_d));
}

template <int OFF, int NN>
__device__ __forceinline__ void wg_m96tz(float (&d)[NN], uint64_t desc_a, uint64_t desc_b, int scale_d) {
  asm volatile(
      "{\n.reg .pred p;\nsetp.ne.b32 p, %50, 0;\n"
      "wgmma.mma_async.sync.aligned.m64n96k16.f32.bf16.bf16 "
      "{%0,%1,%2,%3,%4,%5,%6,%7,%8,%9,%10,%11,%12,%13,%14,%15,"
      "%16,%17,%18,%19,%20,%21,%22,%23,%24,%25,%26,%27,%28,%29,%30,%31,"
      "%32,%33,%34,%35,%36,%37,%38,%39,%40,%41,%42,%43,%44,%45,%46,%47}, "
      "%48, %49, p, 1, 1, 0, 1;\n}\n"
      : "=f"(d[OFF + 0]), "=f"(d[OFF + 1]), "=f"(d[OFF + 2]), "=f"(d[OFF + 3]), "=f"(d[OFF + 4]), "=f"(d[OFF + 5]),
        "=f"(d[OFF + 6]), "=f"(d[OFF + 7]), "=f"(d[OFF + 8]), "=f"(d[OFF + 9]), "=f"(d[OFF + 10]), "=f"(d[OFF + 11]),
        "=f"(d[OFF + 12]), "=f"(d[OFF + 13]), "=f"(d[OFF + 14]), "=f"(d[OFF + 15]), "=f"(d[OFF + 16]), "=f"(d[OFF + 17]),
        "=f"(d[OFF + 18]), "=f"(d[OFF + 19]), "=f"(d[OFF + 20]), "=f"(d[OFF + 21]), "=f"(d[OFF + 22]), "=f"(d[OFF + 23]),
        "=f"(d[OFF + 24]), "=f"(d[OFF + 25]), "=f"(d[OFF + 26]), "=f"(d[OFF + 27]), "=f"(d[OFF + 28]), "=f"(d[OFF + 29]),
        "=f"(d[OFF + 30]), "=f"(d[OFF + 31]), "=f"(d[OFF + 32]), "=f"(d[OFF + 33]), "=f"(d[OFF + 34]), "=f"(d[OFF + 35]),
        "=f"(d[OFF + 36]), "=f"(d[OFF + 37]), "=f"(d[OFF + 38]), "=f"(d[OFF + 39]), "=f"(d[OFF + 40]), "=f"(d[OFF + 41]),
        "=f"(d[OFF + 42]), "=f"(d[OFF + 43]), "=f"(d[OFF + 44]), "=f"(d[OFF + 45]), "=f"(d[OFF + 46]), "=f"(d[OFF + 47])
      : "l"(desc_a), "l"(desc_b), "r"(scale_d));
}

template <int OFF, int NN>
__device__ __forceinline__ void wg_d96(float (&d)[NN], uint32_t a0, uint32_t a1, uint32_t a2, uint32_t a3,
                                       uint64_t desc_b, int scale_d) {
  asm volatile(
      "{\n.reg .pred p;\nsetp.ne.b32 p, %53, 0;\n"
      "wgmma.mma_async.sync.aligned.m64n96k16.f32.bf16.bf16 "
      "{%0,%1,%2,%3,%4,%5,%6,%7,%8,%9,%10,%11,%12,%13,%14,%15,"
      "%16,%17,%18,%19,%20,%21,%22,%23,%24,%25,%26,%27,%28,%29,%30,%31,"
      "%32,%33,%34,%35,%36,%37,%38,%39,%40,%41,%42,%43,%44,%45,%46,%47}, "
      "{%48,%49,%50,%51}, %52, p, 1, 1, 0;\n}\n"
      : "+f"(d[OFF + 0]), "+f"(d[OFF + 1]), "+f"(d[OFF + 2]), "+f"(d[OFF + 3]), "+f"(d[OFF + 4]), "+f"(d[OFF + 5]),
        "+f"(d[OFF + 6]), "+f"(d[OFF + 7]), "+f"(d[OFF + 8]), "+f"(d[OFF + 9]), "+f"(d[OFF + 10]), "+f"(d[OFF + 11]),
        "+f"(d[OFF + 12]), "+f"(d[OFF + 13]), "+f"(d[OFF + 14]), "+f"(d[OFF + 15]), "+f"(d[OFF + 16]), "+f"(d[OFF + 17]),
        "+f"(d[OFF + 18]), "+f"(d[OFF + 19]), "+f"(d[OFF + 20]), "+f"(d[OFF + 21]), "+f"(d[OFF + 22]), "+f"(d[OFF + 23]),
        "+f"(d[OFF + 24]), "+f"(d[OFF + 25]), "+f"(d[OFF + 26]), "+f"(d[OFF + 27]), "+f"(d[OFF + 28]), "+f"(d[OFF + 29]),
        "+f"(d[OFF + 30]), "+f"(d[OFF + 31]), "+f"(d[OFF + 32]), "+f"(d[OFF + 33]), "+f"(d[OFF + 34]), "+f"(d[OFF + 35]),
        "+f"(d[OFF + 36]), "+f"(d[OFF + 37]), "+f"(d[OFF + 38]), "+f"(d[OFF + 39]), "+f"(d[OFF + 40]), "+f"(d[OFF + 41]),
        "+f"(d[OFF + 42]), "+f"(d[OFF + 43]), "+f"(d[OFF + 44]), "+f"(d[OFF + 45]), "+f"(d[OFF + 46]), "+f"(d[OFF + 47])
      : "r"(a0), "r"(a1), "r"(a2), "r"(a3), "l"(desc_b), "r"(scale_d));
}

template <int OFF, int NN>
__device__ __forceinline__ void wg_d96z(float (&d)[NN], uint32_t a0, uint32_t a1, uint32_t a2, uint32_t a3,
                                       uint64_t desc_b, int scale_d) {
  asm volatile(
      "{\n.reg .pred p;\nsetp.ne.b32 p, %53, 0;\n"
      "wgmma.mma_async.sync.aligned.m64n96k16.f32.bf16.bf16 "
      "{%0,%1,%2,%3,%4,%5,%6,%7,%8,%9,%10,%11,%12,%13,%14,%15,"
      "%16,%17,%18,%19,%20,%21,%22,%23,%24,%25,%26,%27,%28,%29,%30,%31,"
      "%32,%33,%34,%35,%36,%37,%38,%39,%40,%41,%42,%43,%44,%45,%46,%47}, "
      "{%48,%49,%50,%51}, %52, p, 1, 1, 0;\n}\n"
      : "=f"(d[OFF + 0]), "=f"(d[OFF + 1]), "=f"(d[OFF + 2]), "=f"(d[OFF + 3]), "=f"(d[OFF + 4]), "=f"(d[OFF + 5]),
        "=f"(d[OFF + 6]), "=f"(d[OFF + 7]), "=f"(d[OFF + 8]), "=f"(d[OFF + 9]), "=f"(d[OFF + 10]), "=f"(d[OFF + 11]),
        "=f"(d[OFF + 12]), "=f"(d[OFF + 13]), "=f"(d[OFF + 14]), "=f"(d[OFF + 15]), "=f"(d[OFF + 16]), "=f"(d[OFF + 17]),
        "=f"(d[OFF + 18]), "=f"(d[OFF + 19]), "=f"(d[OFF + 20]), "=f"(d[OFF + 21]), "=f"(d[OFF + 22]), "=f"(d[OFF + 23]),
        "=f"(d[OFF + 24]), "=f"(d[OFF + 25]), "=f"(d[OFF + 26]), "=f"(d[OFF + 27]), "=f"(d[OFF + 28]), "=f"(d[OFF + 29]),
        "=f"(d[OFF + 30]), "=f"(d[OFF + 31]), "=f"(d[OFF + 32]), "=f"(d[OFF + 33]), "=f"(d[OFF + 34]), "=f"(d[OFF + 35]),
        "=f"(d[OFF + 36]), "=f"(d[OFF + 37]), "=f"(d[OFF + 38]), "=f"(d[OFF + 39]), "=f"(d[OFF + 40]), "=f"(d[OFF + 41]),
        "=f"(d[OFF + 42]), "=f"(d[OFF + 43]), "=f"(d[OFF + 44]), "=f"(d[OFF + 45]), "=f"(d[OFF + 46]), "=f"(d[OFF + 47])
      : "r"(a0), "r"(a1), "r"(a2), "r"(a3), "l"(desc_b), "r"(scale_d));
}

template <int OFF, int NN>
__device__ __forceinline__ void wg_s104(float (&d)[NN], uint32_t a0, uint32_t a1, uint32_t a2, uint32_t a3,
                                       uint64_t desc_b, int scale_d, uint32_t meta) {
  asm volatile(
      "{\n.reg .pred p;\nsetp.ne.b32 p, %57, 0;\n"
      "wgmma.mma_async.sp.sync.aligned.m64n104k32.f32.bf16.bf16 "
      "{%0,%1,%2,%3,%4,%5,%6,%7,%8,%9,%10,%11,%12,%13,%14,%15,"
      "%16,%17,%18,%19,%20,%21,%22,%23,%24,%25,%26,%27,%28,%29,%30,%31,"
      "%32,%33,%34,%35,%36,%37,%38,%39,%40,%41,%42,%43,%44,%45,%46,%47,"
      "%48,%49,%50,%51}, "
      "{%52,%53,%54,%55}, %56, %58, 0, p, 1, 1, 0;\n}\n"
      : "+f"(d[OFF + 0]), "+f"(d[OFF + 1]), "+f"(d[OFF + 2]), "+f"(d[OFF + 3]), "+f"(d[OFF + 4]), "+f"(d[OFF + 5]),
        "+f"(d[OFF + 6]), "+f"(d[OFF + 7]), "+f"(d[OFF + 8]), "+f"(d[OFF + 9]), "+f"(d[OFF + 10]), "+f"(d[OFF + 11]),
        "+f"(d[OFF + 12]), "+f"(d[OFF + 13]), "+f"(d[OFF + 14]), "+f"(d[OFF + 15]), "+f"(d[OFF + 16]), "+f"(d[OFF + 17]),
        "+f"(d[OFF + 18]), "+f"(d[OFF + 19]), "+f"(d[OFF + 20]), "+f"(d[OFF + 21]), "+f"(d[OFF + 22]), "+f"(d[OFF + 23]),
        "+f"(d[OFF + 24]), "+f"(d[OFF + 25]), "+f"(d[OFF + 26]), "+f"(d[OFF + 27]), "+f"(d[OFF + 28]), "+f"(d[OFF + 29]),
        "+f"(d[OFF + 30]), "+f"(d[OFF + 31]), "+f"(d[OFF + 32]), "+f"(d[OFF + 33]), "+f"(d[OFF + 34]), "+f"(d[OFF + 35]),
        "+f"(d[OFF + 36]), "+f"(d[OFF + 37]), "+f"(d[OFF + 38]), "+f"(d[OFF + 39]), "+f"(d[OFF + 40]), "+f"(d[OFF + 41]),
        "+f"(d[OFF + 42]), "+f"(d[OFF + 43]), "+f"(d[OFF + 44]), "+f"(d[OFF + 45]), "+f"(d[OFF + 46]), "+f"(d[OFF + 47]),
        "+f"(d[OFF + 48]), "+f"(d[OFF + 49]), "+f"(d[OFF + 50]), "+f"(d[OFF + 51])
      : "r"(a0), "r"(a1), "r"(a2), "r"(a3), "l"(desc_b), "r"(scale_d), "r"(meta));
}

template <int OFF, int NN>
__device__ __forceinline__ void wg_s104z(float (&d)[NN], uint32_t a0, uint32_t a1, uint32_t a2, uint32_t a3,
                                       uint64_t desc_b, int scale_d, uint32_t meta) {
  asm volatile(
      "{\n.reg .pred p;\nsetp.ne.b32 p, %57, 0;\n"
      "wgmma.mma_async.sp.sync.aligned.m64n104k32.f32.bf16.bf16 "
      "{%0,%1,%2,%3,%4,%5,%6,%7,%8,%9,%10,%11,%12,%13,%14,%15,"
      "%16,%17,%18,%19,%20,%21,%22,%23,%24,%25,%26,%27,%28,%29,%30,%31,"
      "%32,%33,%34,%35,%36,%37,%38,%39,%40,%41,%42,%43,%44,%45,%46,%47,"
      "%48,%49,%50,%51}, "
      "{%52,%53,%54,%55}, %56, %58, 0, p, 1, 1, 0;\n}\n"
      : "=f"(d[OFF + 0]), "=f"(d[OFF + 1]), "=f"(d[OFF + 2]), "=f"(d[OFF + 3]), "=f"(d[OFF + 4]), "=f"(d[OFF + 5]),
        "=f"(d[OFF + 6]), "=f"(d[OFF + 7]), "=f"(d[OFF + 8]), "=f"(d[OFF + 9]), "=f"(d[OFF + 10]), "=f"(d[OFF + 11]),
        "=f"(d[OFF + 12]), "=f"(d[OFF + 13]), "=f"(d[OFF + 14]), "=f"(d[OFF + 15]), "=f"(d[OFF + 16]), "=f"(d[OFF + 17]),
        "=f"(d[OFF + 18]), "=f"(d[OFF + 19]), "=f"(d[OFF + 20]), "=f"(d[OFF + 21]), "=f"(d[OFF + 22]), "=f"(d[OFF + 23]),
        "=f"(d[OFF + 24]), "=f"(d[OFF + 25]), "=f"(d[OFF + 26]), "=f"(d[OFF + 27]), "=f"(d[OFF + 28]), "=f"(d[OFF + 29]),
        "=f"(d[OFF + 30]), "=f"(d[OFF + 31]), "=f"(d[OFF + 32]), "=f"(d[OFF + 33]), "=f"(d[OFF + 34]), "=f"(d[OFF + 35]),
        "=f"(d[OFF + 36]), "=f"(d[OFF + 37]), "=f"(d[OFF + 38]), "=f"(d[OFF + 39]), "=f"(d[OFF + 40]), "=f"(d[OFF + 41]),
        "=f"(d[OFF + 42]), "=f"(d[OFF + 43]), "=f"(d[OFF + 44]), "=f"(d[OFF + 45]), "=f"(d[OFF + 46]), "=f"(d[OFF + 47]),
        "=f"(d[OFF + 48]), "=f"(d[OFF + 49]), "=f"(d[OFF + 50]), "=f"(d[OFF + 51])
      : "r"(a0), "r"(a1), "r"(a2), "r"(a3), "l"(desc_b), "r"(scale_d), "r"(meta));
}

template <int OFF, int NN>
__device__ __forceinline__ void wg_s48(float (&d)[NN], uint32_t a0, uint32_t a1, uint32_t a2, uint32_t a3,
                                       uint64_t desc_b, int scale_d, uint32_t meta) {
  asm volatile(
      "{\n.reg .pred p;\nsetp.ne.b32 p, %29, 0;\n"
      "wgmma.mma_async.sp.sync.aligned.m64n48k32.f32.bf16.bf16 "
      "{%0,%1,%2,%3,%4,%5,%6,%7,%8,%9,%10,%11,%12,%13,%14,%15,"
      "%16,%17,%18,%19,%20,%21,%22,%23}, "
      "{%24,%25,%26,%27}, %28, %30, 0, p, 1, 1, 0;\n}\n"
      : "+f"(d[OFF + 0]), "+f"(d[OFF + 1]), "+f"(d[OFF + 2]), "+f"(d[OFF + 3]), "+f"(d[OFF + 4]), "+f"(d[OFF + 5]),
        "+f"(d[OFF + 6]), "+f"(d[OFF + 7]), "+f"(d[OFF + 8]), "+f"(d[OFF + 9]), "+f"(d[OFF + 10]), "+f"(d[OFF + 11]),
        "+f"(d[OFF + 12]), "+f"(d[OFF + 13]), "+f"(d[OFF + 14]), "+f"(d[OFF + 15]), "+f"(d[OFF + 16]), "+f"(d[OFF + 17]),
        "+f"(d[OFF + 18]), "+f"(d[OFF + 19]), "+f"(d[OFF + 20]), "+f"(d[OFF + 21]), "+f"(d[OFF + 22]), "+f"(d[OFF + 23])
      : "r"(a0), "r"(a1), "r"(a2), "r"(a3), "l"(desc_b), "r"(scale_d), "r"(meta));
}

template <int OFF, int NN>
__device__ __forceinline__ void wg_s48z(float (&d)[NN], uint32_t a0, uint32_t a1, uint32_t a2, uint32_t a3,
                                       uint64_t desc_b, int scale_d, uint32_t meta) {
  asm volatile(
      "{\n.reg .pred p;\nsetp.ne.b32 p, %29, 0;\n"
      "wgmma.mma_async.sp.sync.aligned.m64n48k32.f32.bf16.bf16 "
      "{%0,%1,%2,%3,%4,%5,%6,%7,%8,%9,%10,%11,%12,%13,%14,%15,"
      "%16,%17,%18,%19,%20,%21,%22,%23}, "
      "{%24,%25,%26,%27}, %28, %30, 0, p, 1, 1, 0;\n}\n"
      : "=f"(d[OFF + 0]), "=f"(d[OFF + 1]), "=f"(d[OFF + 2]), "=f"(d[OFF + 3]), "=f"(d[OFF + 4]), "=f"(d[OFF + 5]),
        "=f"(d[OFF + 6]), "=f"(d[OFF + 7]), "=f"(d[OFF + 8]), "=f"(d[OFF + 9]), "=f"(d[OFF + 10]), "=f"(d[OFF + 11]),
        "=f"(d[OFF + 12]), "=f"(d[OFF + 13]), "=f"(d[OFF + 14]), "=f"(d[OFF + 15]), "=f"(d[OFF + 16]), "=f"(d[OFF + 17]),
        "=f"(d[OFF + 18]), "=f"(d[OFF + 19]), "=f"(d[OFF + 20]), "=f"(d[OFF + 21]), "=f"(d[OFF + 22]), "=f"(d[OFF + 23])
      : "r"(a0), "r"(a1), "r"(a2), "r"(a3), "l"(desc_b), "r"(scale_d), "r"(meta));
}

template <int OFF, int NN>
__device__ __forceinline__ void wg_s56(float (&d)[NN], uint32_t a0, uint32_t a1, uint32_t a2, uint32_t a3,
                                       uint64_t desc_b, int scale_d, uint32_t meta) {
  asm volatile(
      "{\n.reg .pred p;\nsetp.ne.b32 p, %33, 0;\n"
      "wgmma.mma_async.sp.sync.aligned.m64n56k32.f32.bf16.bf16 "
      "{%0,%1,%2,%3,%4,%5,%6,%7,%8,%9,%10,%11,%12,%13,%14,%15,"
      "%16,%17,%18,%19,%20,%21,%22,%23,%24,%25,%26,%27}, "
      "{%28,%29,%30,%31}, %32, %34, 0, p, 1, 1, 0;\n}\n"
      : "+f"(d[OFF + 0]), "+f"(d[OFF + 1]), "+f"(d[OFF + 2]), "+f"(d[OFF + 3]), "+f"(d[OFF + 4]), "+f"(d[OFF + 5]),
        "+f"(d[OFF + 6]), "+f"(d[OFF + 7]), "+f"(d[OFF + 8]), "+f"(d[OFF + 9]), "+f"(d[OFF + 10]), "+f"(d[OFF + 11]),
        "+f"(d[OFF + 12]), "+f"(d[OFF + 13]), "+f"(d[OFF + 14]), "+f"(d[OFF + 15]), "+f"(d[OFF + 16]), "+f"(d[OFF + 17]),
        "+f"(d[OFF + 18]), "+f"(d[OFF + 19]), "+f"(d[OFF + 20]), "+f"(d[OFF + 21]), "+f"(d[OFF + 22]), "+f"(d[OFF + 23]),
        "+f"(d[OFF + 24]), "+f"(d[OFF + 25]), "+f"(d[OFF + 26]), "+f"(d[OFF + 27])
      : "r"(a0), "r"(a1), "r"(a2), "r"(a3), "l"(desc_b), "r"(scale_d), "r"(meta));
}

template <int OFF, int NN>
__device__ __forceinline__ void wg_s56z(float (&d)[NN], uint32_t a0, uint32_t a1, uint32_t a2, uint32_t a3,
                                       uint64_t desc_b, int scale_d, uint32_t meta) {
  asm volatile(
      "{\n.reg .pred p;\nsetp.ne.b32 p, %33, 0;\n"
      "wgmma.mma_async.sp.sync.aligned.m64n56k32.f32.bf16.bf16 "
      "{%0,%1,%2,%3,%4,%5,%6,%7,%8,%9,%10,%11,%12,%13,%14,%15,"
      "%16,%17,%18,%19,%20,%21,%22,%23,%24,%25,%26,%27}, "
      "{%28,%29,%30,%31}, %32, %34, 0, p, 1, 1, 0;\n}\n"
      : "=f"(d[OFF + 0]), "=f"(d[OFF + 1]), "=f"(d[OFF + 2]), "=f"(d[OFF + 3]), "=f"(d[OFF + 4]), "=f"(d[OFF + 5]),
        "=f"(d[OFF + 6]), "=f"(d[OFF + 7]), "=f"(d[OFF + 8]), "=f"(d[OFF + 9]), "=f"(d[OFF + 10]), "=f"(d[OFF + 11]),
        "=f"(d[OFF + 12]), "=f"(d[OFF + 13]), "=f"(d[OFF + 14]), "=f"(d[OFF + 15]), "=f"(d[OFF + 16]), "=f"(d[OFF + 17]),
        "=f"(d[OFF + 18]), "=f"(d[OFF + 19]), "=f"(d[OFF + 20]), "=f"(d[OFF + 21]), "=f"(d[OFF + 22]), "=f"(d[OFF + 23]),
        "=f"(d[OFF + 24]), "=f"(d[OFF + 25]), "=f"(d[OFF + 26]), "=f"(d[OFF + 27])
      : "r"(a0), "r"(a1), "r"(a2), "r"(a3), "l"(desc_b), "r"(scale_d), "r"(meta));
}

template <int OFF, int NN>
__device__ __forceinline__ void wg_s64t(float (&d)[NN], uint32_t a0, uint32_t a1, uint32_t a2, uint32_t a3,
                                       uint64_t desc_b, int scale_d, uint32_t meta) {
  asm volatile(
      "{\n.reg .pred p;\nsetp.ne.b32 p, %37, 0;\n"
      "wgmma.mma_async.sp.sync.aligned.m64n64k32.f32.bf16.bf16 "
      "{%0,%1,%2,%3,%4,%5,%6,%7,%8,%9,%10,%11,%12,%13,%14,%15,"
      "%16,%17,%18,%19,%20,%21,%22,%23,%24,%25,%26,%27,%28,%29,%30,%31}, "
      "{%32,%33,%34,%35}, %36, %38, 0, p, 1, 1, 1;\n}\n"
      : "+f"(d[OFF + 0]), "+f"(d[OFF + 1]), "+f"(d[OFF + 2]), "+f"(d[OFF + 3]), "+f"(d[OFF + 4]), "+f"(d[OFF + 5]),
        "+f"(d[OFF + 6]), "+f"(d[OFF + 7]), "+f"(d[OFF + 8]), "+f"(d[OFF + 9]), "+f"(d[OFF + 10]), "+f"(d[OFF + 11]),
        "+f"(d[OFF + 12]), "+f"(d[OFF + 13]), "+f"(d[OFF + 14]), "+f"(d[OFF + 15]), "+f"(d[OFF + 16]), "+f"(d[OFF + 17]),
        "+f"(d[OFF + 18]), "+f"(d[OFF + 19]), "+f"(d[OFF + 20]), "+f"(d[OFF + 21]), "+f"(d[OFF + 22]), "+f"(d[OFF + 23]),
        "+f"(d[OFF + 24]), "+f"(d[OFF + 25]), "+f"(d[OFF + 26]), "+f"(d[OFF + 27]), "+f"(d[OFF + 28]), "+f"(d[OFF + 29]),
        "+f"(d[OFF + 30]), "+f"(d[OFF + 31])
      : "r"(a0), "r"(a1), "r"(a2), "r"(a3), "l"(desc_b), "r"(scale_d), "r"(meta));
}

template <int OFF, int NN>
__device__ __forceinline__ void wg_s64t1(float (&d)[NN], uint32_t a0, uint32_t a1, uint32_t a2, uint32_t a3,
                                       uint64_t desc_b, int scale_d, uint32_t meta) {
  asm volatile(
      "{\n.reg .pred p;\nsetp.ne.b32 p, %37, 0;\n"
      "wgmma.mma_async.sp.sync.aligned.m64n64k32.f32.bf16.bf16 "
      "{%0,%1,%2,%3,%4,%5,%6,%7,%8,%9,%10,%11,%12,%13,%14,%15,"
      "%16,%17,%18,%19,%20,%21,%22,%23,%24,%25,%26,%27,%28,%29,%30,%31}, "
      "{%32,%33,%34,%35}, %36, %38, 1, p, 1, 1, 1;\n}\n"
      : "+f"(d[OFF + 0]), "+f"(d[OFF + 1]), "+f"(d[OFF + 2]), "+f"(d[OFF + 3]), "+f"(d[OFF + 4]), "+f"(d[OFF + 5]),
        "+f"(d[OFF + 6]), "+f"(d[OFF + 7]), "+f"(d[OFF + 8]), "+f"(d[OFF + 9]), "+f"(d[OFF + 10]), "+f"(d[OFF + 11]),
        "+f"(d[OFF + 12]), "+f"(d[OFF + 13]), "+f"(d[OFF + 14]), "+f"(d[OFF + 15]), "+f"(d[OFF + 16]), "+f"(d[OFF + 17]),
        "+f"(d[OFF + 18]), "+f"(d[OFF + 19]), "+f"(d[OFF + 20]), "+f"(d[OFF + 21]), "+f"(d[OFF + 22]), "+f"(d[OFF + 23]),
        "+f"(d[OFF + 24]), "+f"(d[OFF + 25]), "+f"(d[OFF + 26]), "+f"(d[OFF + 27]), "+f"(d[OFF + 28]), "+f"(d[OFF + 29]),
        "+f"(d[OFF + 30]), "+f"(d[OFF + 31])
      : "r"(a0), "r"(a1), "r"(a2), "r"(a3), "l"(desc_b), "r"(scale_d), "r"(meta));
}

template <int OFF, int NN>
__device__ __forceinline__ void wg_s64tz(float (&d)[NN], uint32_t a0, uint32_t a1, uint32_t a2, uint32_t a3,
                                       uint64_t desc_b, int scale_d, uint32_t meta) {
  asm volatile(
      "{\n.reg .pred p;\nsetp.ne.b32 p, %37, 0;\n"
      "wgmma.mma_async.sp.sync.aligned.m64n64k32.f32.bf16.bf16 "
      "{%0,%1,%2,%3,%4,%5,%6,%7,%8,%9,%10,%11,%12,%13,%14,%15,"
      "%16,%17,%18,%19,%20,%21,%22,%23,%24,%25,%26,%27,%28,%29,%30,%31}, "
      "{%32,%33,%34,%35}, %36, %38, 0, p, 1, 1, 1;\n}\n"
      : "=f"(d[OFF + 0]), "=f"(d[OFF + 1]), "=f"(d[OFF + 2]), "=f"(d[OFF + 3]), "=f"(d[OFF + 4]), "=f"(d[OFF + 5]),
        "=f"(d[OFF + 6]), "=f"(d[OFF + 7]), "=f"(d[OFF + 8]), "=f"(d[OFF + 9]), "=f"(d[OFF + 10]), "=f"(d[OFF + 11]),
        "=f"(d[OFF + 12]), "=f"(d[OFF + 13]), "=f"(d[OFF + 14]), "=f"(d[OFF + 15]), "=f"(d[OFF + 16]), "=f"(d[OFF + 17]),
        "=f"(d[OFF + 18]), "=f"(d[OFF + 19]), "=f"(d[OFF + 20]), "=f"(d[OFF + 21]), "=f"(d[OFF + 22]), "=f"(d[OFF + 23]),
        "=f"(d[OFF + 24]), "=f"(d[OFF + 25]), "=f"(d[OFF + 26]), "=f"(d[OFF + 27]), "=f"(d[OFF + 28]), "=f"(d[OFF + 29]),
        "=f"(d[OFF + 30]), "=f"(d[OFF + 31])
      : "r"(a0), "r"(a1), "r"(a2), "r"(a3), "l"(desc_b), "r"(scale_d), "r"(meta));
}

__device__ __forceinline__ int g2_inv(int ch) { return 32 * (ch >> 5) + 8 * ((ch >> 1) & 3) + 2 * ((ch >> 3) & 3) + (ch & 1); }
__host__ __device__ __forceinline__ uint32_t wimg_off(int n, int k) {
  return (uint32_t)(k >> 6) * kWChunk + (uint32_t)n * 128 + (uint32_t)((((k & 63) >> 3) ^ (n & 7)) << 4) + (k & 7) * 2;
}
__host__ __device__ constexpr int w2piece(int h, int c) { return c == 2 ? 2 + h : 4 * h + c; }
__device__ __forceinline__ uint32_t w2img_off(int n, int k) { return wimg_off(n % 96, k & 63) + w2piece(n >= 96, k >> 6) * (kWChunk / 2); }
__device__ __forceinline__ int qpix(int par, int t) {
  const int a = 2 * t + 13 * par - 6, b = t + 112 * par;
  return par ? min(a, b) : max(a, b);
}
__device__ __forceinline__ int woff(int par, int i, int r) {
  const int a = 99 * par + 6 - 8 * i;
  return par ? min(r, a) : max(r, a);
}

__device__ __forceinline__ void mma16816(float (&c)[4], uint32_t a0, uint32_t a1, uint32_t a2, uint32_t a3, uint32_t b0,
                                         uint32_t b1) {
  asm volatile(
      "mma.sync.aligned.m16n8k16.row.col.f32.bf16.bf16.f32 {%0,%1,%2,%3}, {%4,%5,%6,%7}, {%8,%9}, {%0,%1,%2,%3};"
      : "+f"(c[0]), "+f"(c[1]), "+f"(c[2]), "+f"(c[3])
      : "r"(a0), "r"(a1), "r"(a2), "r"(a3), "r"(b0), "r"(b1));
}

__device__ __forceinline__ void fold_w1(const int u, const __nv_bfloat16* __restrict__ wqkv, uint8_t* wimg) {
  const int g = (threadIdx.x >> 2) & 7, l = threadIdx.x & 3;
  const int m0 = (u / 12) * 16, s = u % 12;
  uint4 A[12], B[12];
  const __nv_bfloat16* arow = wqkv + (m0 + 4 * (g >> 1) + (g & 1)) * 576 + 192 + 8 * l;
  const __nv_bfloat16* brow = wqkv + (16 * s + 4 * (g >> 1) + (g & 1)) * 576 + 8 * l;
#pragma unroll
  for (int i = 0; i < 12; i++) {
    A[i] = ldg128_nc(arow + (i & 1) * 2 * 576 + 32 * (i >> 1));
    B[i] = ldg128_nc(brow + (i & 1) * 2 * 576 + 32 * (i >> 1));
  }
  sched_fence();
  uint8_t* dst = wimg + wimg_off(m0 + g, 16 * s + 4 * l);
  float acc[4][4];
#pragma unroll
  for (int j = 0; j < 16; j++) acc[j >> 2][j & 3] = 0.f;
#pragma unroll
  for (int i = 0; i < 6; i++) {
    const uint4 &a0 = A[2 * i], &a1 = A[2 * i + 1];
#pragma unroll
    for (int nb = 0; nb < 2; nb++) {
      mma16816(acc[2 * nb], a0.x, a1.x, a0.y, a1.y, B[2 * i + nb].x, B[2 * i + nb].y);
      mma16816(acc[2 * nb + 1], a0.z, a1.z, a0.w, a1.w, B[2 * i + nb].z, B[2 * i + nb].w);
    }
  }
#pragma unroll
  for (int j = 0; j < 2; j++) {
    const uint2 v = make_uint2(pack_bf16((acc[0][2 * j] + acc[1][2 * j]) * kAlpha, (acc[0][2 * j + 1] + acc[1][2 * j + 1]) * kAlpha),
                               pack_bf16((acc[2][2 * j] + acc[3][2 * j]) * kAlpha, (acc[2][2 * j + 1] + acc[3][2 * j + 1]) * kAlpha));
    asm volatile("st.relaxed.gpu.global.v2.u32 [%0], {%1,%2};" ::"l"(dst + j * 1024), "r"(v.x), "r"(v.y) : "memory");
  }
}
__device__ __forceinline__ void fold_w2(const int u, const __nv_bfloat16* __restrict__ wqkv, const __nv_bfloat16* __restrict__ wo,
                                        uint8_t* wimg) {
  const int g = (threadIdx.x >> 2) & 7, l = threadIdx.x & 3;
  const int m0 = (u / 12) * 32, n0 = (u % 12) * 16;
  uint4 S[12];
  uint32_t L[96];
  const __nv_bfloat16* brow = wqkv + (n0 + 4 * (g >> 1) + (g & 1)) * 576 + 384 + 8 * l;
#pragma unroll
  for (int i = 0; i < 12; i++) S[i] = ldg128_nc(brow + (i & 1) * 2 * 576 + 32 * (i >> 1));
  const __nv_bfloat16* acol = wo + (8 * l) * 192 + m0 + 4 * g;
#pragma unroll
  for (int c = 0; c < 48; c++)
    asm volatile("ld.global.nc.v2.u32 {%0,%1}, [%2];" : "=r"(L[2 * c]), "=r"(L[2 * c + 1]) : "l"(acol + (32 * (c >> 3) + (c & 7)) * 192));
  const uint32_t off = w2_offset();
  sched_fence();
  uint8_t* img = wimg + off;
  float acc[4][4];
#pragma unroll
  for (int j = 0; j < 16; j++) acc[j >> 2][j & 3] = 0.f;
#pragma unroll
  for (int i = 0; i < 6; i++) {
#pragma unroll
    for (int h = 0; h < 2; h++) {
      const uint4 &s0 = S[2 * i], &s1 = S[2 * i + 1];
#pragma unroll
      for (int mt = 0; mt < 2; mt++) {
        const uint32_t* a = L + 16 * i + 8 * h + mt;
        const uint32_t a0 = __byte_perm(a[0], a[2], 0x5410), a1 = __byte_perm(a[0], a[2], 0x7632);
        const uint32_t a2 = __byte_perm(a[4], a[6], 0x5410), a3 = __byte_perm(a[4], a[6], 0x7632);
        mma16816(acc[2 * mt], a0, a1, a2, a3, h ? s0.z : s0.x, h ? s0.w : s0.y);
        mma16816(acc[2 * mt + 1], a0, a1, a2, a3, h ? s1.z : s1.x, h ? s1.w : s1.y);
      }
    }
  }
#pragma unroll
  for (int j = 0; j < 4; j++) {
    const float(&c0)[4] = acc[j & 2];
    const float(&c1)[4] = acc[(j & 2) + 1];
    asm volatile("st.relaxed.gpu.global.v2.u32 [%0], {%1,%2};" ::"l"(img + w2img_off(g2_inv(m0 + 4 * g + j), n0 + 4 * l)),
                 "r"(pack_bf16(c0[2 * (j & 1)], c0[2 * (j & 1) + 1])), "r"(pack_bf16(c1[2 * (j & 1)], c1[2 * (j & 1) + 1])) : "memory");
  }
}

__global__ void __launch_bounds__(256) fold_kernel(const __nv_bfloat16* __restrict__ wqkv,
                                                   const __nv_bfloat16* __restrict__ wo, uint8_t* wimg) {
  const int u = blockIdx.x * 8 + (threadIdx.x >> 5);
  if (u < 144) fold_w1(u, wqkv, wimg);
  else fold_w2(u - 144, wqkv, wo, wimg);
}

struct TileCoord { int pr, pc, I, J, up, kind; };
struct TileTable { uint16_t e[kCtas * 6], g[5][8][2], b[5][2][4]; };
inline void make_tiles(TileTable& tt) {
  for (int tile = 0; tile < kCtas * 6; tile++) {
    const int b = tile / 6, k = tile - 6 * b;
    const int p = b < 128 ? (tile - 672) >> 1 : b - 80;
    const int strip = b < 112 ? b >> 1 : b >= 128 && k >= 2 ? (b & 1) * 27 + (b & 2) * 14 : p + (p < 26 ? 1 : 3);
    const int pr = strip >= 28, J = (strip - pr * 28) >> 1, pc = strip & 1, up = b < 112 ? b & 1 : pr;
    const int first = b < 112 ? 8 - 2 * pr - up : 13 * pr, step = b < 112 ? k : k & 1;
    const int I = up ? first - step : first + step;
    const int kind = I == 13 * pr ? 3 + pr : J == 13 * pc ? 1 + pc : 0;
    tt.e[tile] = (uint16_t)(I | J << 4 | pr << 8 | pc << 9 | up << 10 | kind << 11);
  }
  for (int kind = 0; kind < 5; kind++) {
    const bool col = kind == 1 || kind == 2;
    auto off = [kind](int t) { return kind == 0 ? 2 * t : kind & 1 ? t + (t == 7) : t + (t > 0); };
    for (int j = 0; j < 8; j++) {
      const int w = j >> 1, h = j & 1;
      tt.g[kind][j][0] = (uint16_t)(col ? 3 * off(w + 4 * h) : 3 * (kW * off(2 * w) + 8 * h));
      tt.g[kind][j][1] = (uint16_t)(128 * (col ? 5 : 5 + off(2 * w + 1) - off(2 * w)));
    }
    for (int i = 0; i < 2; i++) {
      const int w = kind == 0 ? 0 : kind & 1 ? 3 * i : 1 - i;
      tt.b[kind][i][0] = tt.g[kind][2 * w][0];
      tt.b[kind][i][1] = (uint16_t)(128 * (kind == 0 ? 0 : (col ? 3 : 1) + i));
      tt.b[kind][i][2] = (uint16_t)(2048 * w);
      tt.b[kind][i][3] = 0;
    }
  }
}
__device__ __forceinline__ int num_tiles() { return blockIdx.x < 128 ? 6 : 4; }
__device__ __forceinline__ TileCoord decode_tile(const TileTable& tt, int tile) {
  const uint32_t e = tt.e[tile];
  return TileCoord{(int)(e >> 8) & 1, (int)(e >> 9) & 1, (int)e & 15, (int)(e >> 4) & 15, (int)(e >> 10) & 1, (int)(e >> 11)};
}
__device__ __forceinline__ int halo_r0(const TileCoord& t) { return 8 * t.I + 6 * t.pr - 6; }
__device__ __forceinline__ int halo_c0(const TileCoord& t) { return min(max(8 * t.J + 6 * t.pc - 6, -3), 102); }

__device__ __forceinline__ uint32_t bar_full(uint32_t bars, int wg, int c) { return bars + (wg * 3 + c) * 8; }
__device__ __forceinline__ uint32_t bar_w1c(uint32_t bars, int c) { return bars + (6 + c) * 8; }
__device__ __forceinline__ uint32_t bar_w2(uint32_t bars) { return bars + 9 * 8; }
__device__ __forceinline__ uint32_t bar_x(uint32_t bars, int j, int c) { return bars + (j == 0 ? 10 : c ? 17 + c : 11) * 8; }
__device__ __forceinline__ uint32_t bar_w1q(uint32_t bars) { return bars + 12 * 8; }
__device__ __forceinline__ uint32_t bar_xf(uint32_t bars) { return bars + 13 * 8; }
__device__ __forceinline__ uint32_t bar_w2m(uint32_t bars) { return bars + 14 * 8; }
__device__ __forceinline__ uint32_t bar_redo(uint32_t bars) { return bars + 15 * 8; }
__device__ __forceinline__ uint32_t bar_wok(uint32_t bars) { return bars + 16 * 8; }
__device__ __forceinline__ uint32_t bar_go(uint32_t bars) { return bars + 17 * 8; }
__device__ __forceinline__ uint32_t bar_raw(uint32_t bars, int j = 0) { return bars + (21 + j) * 8; }
__device__ __forceinline__ uint32_t bar_w2a(uint32_t bars) { return bars + 20 * 8; }
constexpr int kNumBars = 22;

__device__ __forceinline__ uint64_t wdesc(uint64_t d0, int s) { return d0 + (((s >> 2) * kWChunk + (s & 3) * 32) >> 4); }

__device__ __forceinline__ uint32_t x_chunk(int k, int c) { return kXOff + (k == 0 ? kWChunk : 0) + (k & 1 ? 2 - c : c) * 8192; }
__device__ __forceinline__ uint32_t out_slot(int k, int nt) { return k + 1 < nt ? kW2Off + (~k & 1) * 2 * kWChunk : kW1Off + kWChunk; }
template <int I0, int I1>
__device__ __forceinline__ void store_rows(bool on, __nv_bfloat16* pA, __nv_bfloat16* pB, const uint32_t (&a)[24], const uint32_t (&b)[24]) {
#pragma unroll
  for (int i = 2 * I0; i < 2 * I1; i++) {
    const uint32_t* v = (i & 1 ? b : a) + 4 * (i >> 1);
    asm volatile("{\n.reg .pred p;\nsetp.ne.u32 p, %5, 0;\n@p st.global.v4.u32 [%0], {%1,%2,%3,%4};\n}\n" ::"l"((i & 1 ? pB : pA) + 32 * (i >> 1)),
                 "r"(v[0]), "r"(v[1]), "r"(v[2]), "r"(v[3]), "r"((uint32_t)on) : "memory");
  }
}
template <int I0, int I1>
__device__ __forceinline__ void stage_out(const uint32_t (&ad)[4], const uint32_t (&a)[24], const uint32_t (&b)[24]) {
#pragma unroll
  for (int i = I0; i < I1; i++) {
    const uint32_t* v = (i < 6 ? a : b) + 4 * (i % 6);
    asm volatile("st.shared.v4.u32 [%0], {%1,%2,%3,%4};" ::"r"(ad[i % 6 / 3 * 2 + (i % 3 == 1)] + (i % 3 == 2) * 1024 + (i / 6) * 12288),
                 "r"(v[0]), "r"(v[1]), "r"(v[2]), "r"(v[3]) : "memory");
  }
}
__device__ __forceinline__ uint32_t now_ns() {
  uint32_t t;
  asm volatile("mov.u32 %0, %globaltimer_lo;" : "=r"(t)::"memory");
  return t;
}
__device__ __forceinline__ void wait_clock(uint32_t t_start, uint32_t t) {
  while (now_ns() - t_start < t) { }
}
#define NAT_PRED(f, m) ".reg .pred p;\n.reg .b32 t;\nand.b32 t, " f ", " m ";\nsetp.ne.u32 p, t, 0;\n"
constexpr uint32_t kHiV = 1, kHiU = 8, kColB = 0x20, kInV = 0x100, kInU = 0x1000, kColA = 0x10000;
template <uint32_t M>
__device__ __forceinline__ float pick(const float* a, const float* b, uint32_t f) {
  float d;
  asm("{\n" NAT_PRED("%5", "%6") "add.f32 %0, %1, %2;\n@p add.f32 %0, %3, %4;\n}\n"
      : "=&f"(d) : "f"(a[0]), "f"(a[2]), "f"(b[0]), "f"(b[2]), "r"(f), "n"(M));
  return d;
}
template <uint32_t M>
__device__ __forceinline__ float sel(float a, float b, uint32_t f) {
  float d;
  asm("{\n" NAT_PRED("%3", "%4") "selp.f32 %0, %1, %2, p;\n}\n" : "=f"(d) : "f"(a), "f"(b), "r"(f), "n"(M));
  return d;
}
template <uint32_t M>
__device__ __forceinline__ void max_if(float& m, float v, uint32_t f) {
  asm("{\n" NAT_PRED("%2", "%3") "@p max.f32 %0, %0, %1;\n}\n" : "+f"(m) : "f"(v), "r"(f), "n"(M));
}
template <uint32_t M>
__device__ __forceinline__ void add_if(float& m, float v, uint32_t f) {
  asm("{\n" NAT_PRED("%2", "%3") "@p add.f32 %0, %0, %1;\n}\n" : "+f"(m) : "f"(v), "r"(f), "n"(M));
}
__device__ __forceinline__ void pick_v(const float* a, float* v, uint32_t f) {
  v[0] = pick<kHiV>(a, a + 16, f), v[1] = pick<kHiV>(a + 1, a + 17, f);
  v[2] = pick<kHiV * 2>(a + 4, a + 20, f), v[3] = pick<kHiV * 2>(a + 5, a + 21, f);
  v[4] = pick<kHiV * 4>(a + 8, a + 24, f), v[5] = pick<kHiV * 4>(a + 9, a + 25, f);
  v[6] = a[12] + a[14], v[7] = a[13] + a[15];
}
__device__ __forceinline__ void pick_u(const float* a, float* v, uint32_t f) {
#pragma unroll
  for (int c = 0; c < 3; c++) v[2 * c] = pick<kHiU>(a + 4 * c, a + 4 * c + 12, f), v[2 * c + 1] = pick<kHiU * 2>(a + 4 * c + 1, a + 4 * c + 13, f);
}
__device__ __forceinline__ uint32_t sign_bytes(uint32_t v, uint32_t sel) {
  uint32_t d;
  asm("prmt.b32 %0, %1, %1, %2;" : "=r"(d) : "r"(v), "r"(sel));
  return d;
}
__device__ __forceinline__ float own_max(const float (&v)[14], uint32_t f) {
  float m = sel<kInV>(fmaxf(v[0], v[1]), -INFINITY, f), m2 = sel<kInV * 2>(fmaxf(v[2], v[3]), -INFINITY, f);
  max_if<kInV * 4>(m, fmaxf(v[4], v[5]), f);
  max_if<kInV * 8>(m2, fmaxf(v[6], v[7]), f);
  max_if<kInU>(m, fmaxf(fmaxf(v[8], v[10]), v[12]), f);
  max_if<kInU * 2>(m2, fmaxf(fmaxf(v[9], v[11]), v[13]), f);
  return fmaxf(m, m2);
}
__device__ __forceinline__ float quad_max(float m) {
  const float a = __shfl_xor_sync(0xffffffffu, m, 1), b = __shfl_xor_sync(0xffffffffu, m, 2), c = __shfl_xor_sync(0xffffffffu, m, 3);
  return fmaxf(fmaxf(m, a), fmaxf(b, c));
}
__device__ __forceinline__ float row_rcp(const float (&v)[14], uint32_t f) {
  float s = sel<kInV>(v[0] + v[1], 0.f, f), s2 = sel<kInV * 2>(v[2] + v[3], 0.f, f);
  add_if<kInV * 4>(s, v[4] + v[5], f);
  add_if<kInV * 8>(s2, v[6] + v[7], f);
  add_if<kInU>(s, v[8] + v[10] + v[12], f);
  add_if<kInU * 2>(s2, v[9] + v[11] + v[13], f);
  s += s2;
  const float a = __shfl_xor_sync(0xffffffffu, s, 1), b = __shfl_xor_sync(0xffffffffu, s, 2), c = __shfl_xor_sync(0xffffffffu, s, 3);
  return rcp_approx((s + a) + (b + c));
}
__device__ __forceinline__ void route(const float (&v)[14], float s, const uint32_t (&rt)[9], uint32_t (&p)[14]) {
#pragma unroll
  for (int i = 0; i < 7; i++) {
    const uint32_t u = pack_bf16(v[2 * i] * s, v[2 * i + 1] * s);
    if (i < 4) p[i] = u & rt[i];
    if (i < 3) p[i + 4] = u & rt[i + 4];
    if (i >= 4) {
      p[i + 3] = u & rt[7];
      p[i + 6] = u & rt[8];
    }
  }
}

template <int C, int T0 = 0, int T1 = 7>
__device__ __forceinline__ void pv_chunk(float (&z)[32], const uint32_t (&pa)[14], const uint32_t (&pb)[14],
                                         const uint32_t (&meta)[4], uint64_t dV) {
#pragma unroll
  for (int t = T0; t < T1; t++) {
    if (t & 1)
      wg_s64t1<0, 32>(z, pa[2 * t], pb[2 * t], pa[2 * t + 1], pb[2 * t + 1], dV + ((2 * C * kChunkBytes + t * 2048) >> 4), 1,
                      meta[t >> 1]);
    else if (t > 0)
      wg_s64t<0, 32>(z, pa[2 * t], pb[2 * t], pa[2 * t + 1], pb[2 * t + 1], dV + ((2 * C * kChunkBytes + t * 2048) >> 4), 1,
                     meta[t >> 1]);
    else
      wg_s64tz<0, 32>(z, pa[0], pb[0], pa[1], pb[1], dV + ((2 * C * kChunkBytes) >> 4), 0, meta[0]);
  }
}
template <int C>
__device__ __forceinline__ void pack_z(const float (&z)[32], uint32_t (&za)[24], uint32_t (&zb)[24]) {
#pragma unroll
  for (int j = 0; j < 8; j++) {
    za[8 * C + j] = pack_bf16(z[4 * j], z[4 * j + 1]);
    zb[8 * C + j] = pack_bf16(z[4 * j + 2], z[4 * j + 3]);
  }
}

template <int H>
__device__ __forceinline__ void pack_out(const float (&ac)[48], uint32_t (&oa)[24], uint32_t (&ob)[24]) {
#pragma unroll
  for (int j = 0; j < 12; j++) {
    oa[12 * H + j] = pack_bf16(ac[4 * j], ac[4 * j + 1]);
    ob[12 * H + j] = pack_bf16(ac[4 * j + 2], ac[4 * j + 3]);
  }
}
struct Maps { CUtensorMap v6, v2, v14, u8, px[8], wv, wo; };
__device__ __forceinline__ void tma_prefetch_5d(const CUtensorMap* map, int c0, int c1, int c2, int c3, int c4) {
  asm volatile("cp.async.bulk.prefetch.tensor.5d.L2.global.tile [%0, {%1, %2, %3, %4, %5}];" ::"l"((uint64_t)map), "r"(c0), "r"(c1),
               "r"(c2), "r"(c3), "r"(c4) : "memory");
}
__device__ __forceinline__ int first_line(const TileCoord tc) { return 3 * (qpix(tc.pr, 8 * tc.I) * kW + qpix(tc.pc, 8 * tc.J)); }
__device__ __forceinline__ void load_px(const Maps& tm, const TileTable& tt, uint32_t dst, uint32_t bar, int line, int kind) {
#pragma unroll
  for (int i = 0; i < 2; i++) {
    if (i == 0 || kind != 0) {
      const CUtensorMap* map = (const CUtensorMap*)((const char*)tm.px + tt.b[kind][i][1]);
      if (bar) tma_load_5d(dst + tt.b[kind][i][2], map, bar, 0, 0, 0, 0, line + tt.b[kind][i][0]);
      else tma_prefetch_5d(map, 0, 0, 0, 0, line + tt.b[kind][i][0]);
    }
  }
}
__device__ __forceinline__ void store_px(const Maps& tm, const TileTable& tt, uint32_t buf, int line, int kind) {
#pragma unroll
  for (int i = 0; i < 8; i++) {
    const int j = 2 * (i & 3) + (i >> 2);
    asm volatile("cp.async.bulk.tensor.5d.global.shared::cta.tile.bulk_group [%0, {%2, %2, %2, %2, %3}], [%1];" ::"l"(
                     (uint64_t)tm.px + tt.g[kind][j][1]), "r"(buf + i * 3072), "r"(0), "r"(line + tt.g[kind][j][0]) : "memory");
  }
  asm volatile("cp.async.bulk.commit_group;" ::: "memory");
}
__device__ __noinline__ bool refetch(uint32_t base, const uint8_t* src, bool gap) {
  constexpr uint32_t bars = 1024 + kBarOff, cnt = bars + 192;
#pragma unroll 1
  for (uint32_t o = 0; o < kWBytes && !gap; o += 2048) {
    uint32_t mx = 0;
#pragma unroll
    for (int i = 0; i < 4; i++) {
      uint4 v;
      asm volatile("ld.shared.v4.u32 {%0,%1,%2,%3}, [%4];" : "=r"(v.x), "=r"(v.y), "=r"(v.z), "=r"(v.w)
                   : "r"(base + o + i * 512 + (threadIdx.x & 31) * 16));
      mx = __vimax3_u32(__vimax3_u32(mx, v.x, v.y), v.z, v.w);
    }
    gap = __any_sync(0xffffffffu, mx == kEmpty);
  }
  uint32_t n;
  asm volatile("ld.shared.u32 %0, [%1];" : "=r"(n) : "r"(cnt) : "memory");
  if (!gap || __any_sync(0xffffffffu, n > (1u << 12))) return false;
  asm volatile("bar.sync 15, 128;" ::: "memory");
  if (threadIdx.x == 0) {
    asm volatile("st.shared.u32 [%0], %1;" ::"r"(cnt), "r"(n + 1) : "memory");
    mbar_arrive_expect_tx(bar_redo(bars), kWBytes);
    bulk_load(base, src, kWBytes, bar_redo(bars));
  }
  __syncwarp();
  mbar_wait(bar_redo(bars), n & 1);
  return true;
}
__device__ __forceinline__ bool any_nan(const uint32_t (&a)[24]) {
  uint32_t m[2] = {a[0], a[1]}, nan;
#pragma unroll
  for (int i = 2; i < 24; i++) asm("max.NaN.bf16x2 %0, %0, %1;" : "+r"(m[i & 1]) : "r"(a[i]));
  asm("max.NaN.bf16x2 %0, %0, %1;" : "+r"(m[0]) : "r"(m[1]));
  asm volatile("{\n.reg .pred p;\nsetp.ne.u32 p, %1, 0;\nbar.red.or.pred p, 15, 128, p;\nselp.u32 %0, 1, 0, p;\n}\n"
               : "=r"(nan) : "r"(((m[0] & 0x7FFF7FFFu) + 0x007F007Fu) & 0x80008000u) : "memory");
  return __any_sync(0xffffffffu, nan);
}
template <int S0, int S1, int Z>
__device__ __forceinline__ void g2_steps(float (&ac)[48], const uint32_t (&za)[24], const uint32_t (&zb)[24], uint64_t d) {
#pragma unroll
  for (int s = S0; s < S1; s++) {
    const uint64_t ds = d + (((s >> 2 & 1) * (kWChunk / 2) + (s & 3) * 32) >> 4);
    if (s == Z) wg_d96z<0, 48>(ac, za[2 * s], zb[2 * s], za[2 * s + 1], zb[2 * s + 1], ds, 0);
    else wg_d96<0, 48>(ac, za[2 * s], zb[2 * s], za[2 * s + 1], zb[2 * s + 1], ds, 1);
  }
}

__device__ __forceinline__ void consumer(const int wg, __nv_bfloat16* out, const uint8_t* wimg, const uint32_t sbase,
                                         const uint32_t zero, const Maps& tm, const TileTable& tt) {
  const int tid = threadIdx.x & 127;
  const int w = __shfl_sync(0xffffffffu, tid >> 5, 0), lane = tid & 31;
  const uint64_t dK = make_desc(sbase, 16, 1024);
  const uint64_t dV = make_desc(sbase, kChunkBytes, 512, 2);
  const uint64_t dW1 = make_desc(sbase + kW1Off, 16, 1024);
  const uint64_t dX0 = make_desc(sbase + kW2Off + wg * 2 * kWChunk, 16, 1024), dY0 = make_desc(sbase + kW2Off + (1 - wg) * 2 * kWChunk, 16, 1024);
  const uint64_t dX2 = make_desc(sbase + kXOff + wg * (kWChunk / 2), 16, 1024), dY2 = make_desc(sbase + kXOff + (1 - wg) * (kWChunk / 2), 16, 1024);
  const uint32_t bars = sbase + kBarOff;
  int tile0 = blockIdx.x * kTilesPerCta;
  asm volatile("" : "+r"(tile0));
  const int nt = num_tiles();

  uint32_t pix = 0, geo[6] = {};
  const int l = lane & 3;
#pragma unroll 1
  for (int j = 4; j >= 0; j -= 2) {
    const TileCoord tc = decode_tile(tt, tile0 + wg + j);
    const bool col = tc.kind == 1 || tc.kind == 2;
    const int g = col ? lane >> 2 : 2 * w + ((lane >> 2) & 1), qc = col ? w : lane >> 3;
    const uint32_t pr = qpix(tc.pr, 8 * tc.I + g) * kW;
    if (j == nt - 2) pix = (pr + qpix(tc.pc, 8 * tc.J + qc)) | (pr + qpix(tc.pc, 8 * tc.J + qc + 4)) << 16;
    const int d = 8 * tc.J + 6 * tc.pc - 6 - halo_c0(tc);
    const int ro = woff(tc.pr, tc.I, g), coA = woff(tc.pc, tc.J, qc) + d, coB = woff(tc.pc, tc.J, qc + 4) + d - 3;
#pragma unroll
    for (int i = 5; i >= 2; i--) geo[i] = geo[i - 2];
    const uint32_t lr = 0x1FCu << ro;
    const uint32_t lv = lr >> (2 + (l >> 1)), lu = lr >> (2 * l + 2 * tc.up);
    const uint32_t t = __byte_perm(lv, lu, wg ? 0x4501 : 0x5410);
    geo[0] = (((t & 0x15u) | (lv & 0x40u)) * 0x02082080u & 0x80808080u) | (((t >> 8) & 0x15u) * 0x01041040u & 0x40404040u) |
             (__byte_perm(t << 5, t << 4, 0x7362) & 0x20202020u) | (nt == 6);
    const int dr = (ro - 1) & 7;
    const uint32_t hiv = (((1u << ((ro - (l >> 1) + 1) >> 1)) - 1u) ^ (wg ? 7u : 0u)) & 7u, hiu = (t >> 24) & 3u;
    const uint32_t ca = (1u << coA) - 1u;
    geo[1] = hiv * kHiV | hiu * kHiU | ((((1u << coB) - 1u) >> (2 * (l & 1))) & 3u) * kColB |
             (15u & ~((uint32_t)((dr & 1) == (l >> 1)) << (dr >> 1))) * kInV | ((t >> 16 | t >> 24) & 3u) * kInU | ca * kColA |
             (ca >> ((0x49 >> (2 * l)) & 3) & 1u) << 19 | (uint32_t)(l == 3) << 20 | (0x55u & ((1u << (2 * coB)) - 1u)) << 24;
  }
  keep_regs(geo);
  const int so = (lane >> 3) | (lane & 4);
  uint32_t sts = sbase + w * 3072 + so * 128 + (((lane & 3) ^ so) << 4);
  __nv_bfloat16* poA = out + 8 * l + (pix & 0xFFFFu) * kC + 96 * wg;
  __nv_bfloat16* poB = out + 8 * l + (pix >> 16) * kC + 96 * wg;
  asm volatile("" : "+l"(poA), "+l"(poB), "+r"(sts));
  uint32_t oa[24], ob[24];
#pragma unroll
  for (int j = 0; j < 24; j++) oa[j] = ob[j] = 0u;
  keep_regs(oa);
  keep_regs(ob);
  PROF(wg, 0);
  if (threadIdx.x == 0) GT(1);

  for (int k = wg; k < nt; k += 2) {
    const uint32_t ph = (k >> 1) & 1;
    const int it = k >> 1;
    uint32_t qa[24], qb[24], hok[3];
    uint32_t fl = geo[1];
    {
      float acc[96];
      const uint32_t xp = (k + (k > 0)) & 1;
      const uint32_t xok = mbar_test(bar_x(bars, k > 0, 0), xp);
      if (k > 0) nb_sync(1 + (1 - wg));
#pragma unroll
      for (int s = 0; s < 12; s++) {
        if (s == 0) mbar_wait_if(xok, bar_x(bars, k > 0, 0), xp);
        if (s == 0 && k < 2) PROF(wg, 1);
        if (s == 0) PROFS(2, wg, 2 + it * 12);
        if (s == 0 && w == 0 && k < 2) GT(20 + wg);
        if (s == 4 && NAT_GW) wg_wait<1>();
        if ((s & 3) == 0 && (k == 0 || s > 0)) {
          mbar_wait(k == 0 ? bar_w1c(bars, s >> 2) : bar_x(bars, 1, s >> 2), xp);
          PROFS(17, wg, 50 + (s >> 2));
        }
        if ((s & 3) == 0) wg_fence();
        const uint64_t dX = make_desc(sbase + x_chunk(k, s >> 2), 16, 1024) + 2 * (s & 3);
        if (s == 0) wg_m192z<0, 96>(acc, dX, dW1, 0);
        else wg_m192<0, 96>(acc, dX, wdesc(dW1, s), 1);
        if ((s & 3) == 3 || (s == 0 && NAT_GW)) wg_commit();
      }
      PROFS(13, wg, 13 + it * 12);
      const uint32_t e = sts + out_slot(k, nt), o = e ^ 64;
      uint32_t ad[4] = {wg ? o + 1024 : e, wg ? e + 2048 : o, wg ? e : o + 1024, wg ? o : e + 2048};
      keep_regs(ad);
      wg_wait<2>();
      if (k > 0) nb_arrive_p(0);
      wg_wait<1>();
      if (k > 0) nb_arrive_p(14);
      wg_wait<0>();
      if (k > 0) {
        nb_arrive_p(6);
        sched_fence();
      }
      fence_regs(acc);
      PROFS(3, wg, 3 + it * 12);
#pragma unroll
      for (int j = 0; j < 24; j++) {
        qa[j] = pack_bf16(acc[4 * j], acc[4 * j + 1]);
        qb[j] = pack_bf16(acc[4 * j + 2], acc[4 * j + 3]);
      }
      keep_regs(qa);
      keep_regs(qb);
      sched_fence();
      if (k >= 2) {
        nb_sync(11);
        stage_out<0, 6>(ad, oa, ob);
        nb_sync(12);
        stage_out<6, 12>(ad, oa, ob);
      }
#pragma unroll
      for (int c = 0; c < 3; c++) hok[c] = mbar_test(bar_full(bars, wg, c), ph);
      if (k >= 2) {
        fence_proxy_async();
        nb_arrive_p(10);
      }
    }

    float aE[52], aO[24], bO[52], bE[28];
    const uint32_t mq = 0xEEEE4444u | zero;
    PROFS(4, wg, 4 + it * 12);

    mbar_wait_if(hok[0], bar_full(bars, wg, 0), ph);
    PROFS(14, wg, 40 + it * 3);
    if (w == 0 && k < 2) GT(22 + wg);
    if (k > 0) nb_sync(3 + (1 - wg));
    wg_fence();
#pragma unroll
    for (int ks = 0; ks < 6; ks++) {
      if (ks == 2) {
        mbar_wait_if(hok[1], bar_full(bars, wg, 1), ph);
        PROFS(14, wg, 41 + it * 3);
        wg_fence();
      }
      if (ks == 4) {
        mbar_wait_if(hok[2], bar_full(bars, wg, 2), ph);
        PROFS(14, wg, 42 + it * 3);
        wg_fence();
      }
      const uint64_t d = dK + ((ks * kChunkBytes) >> 4);
      if (ks == 0) wg_s104z<0, 52>(aE, qa[0], qa[1], qa[2], qa[3], d, 0, mq);
      else wg_s104<0, 52>(aE, qa[4 * ks], qa[4 * ks + 1], qa[4 * ks + 2], qa[4 * ks + 3], d, 1, mq);
      if (ks == 0) wg_s48z<0, 24>(aO, qa[0], qa[1], qa[2], qa[3], d + ((7 * 1024 + 64) >> 4), 0, mq);
    }
    wg_commit();
#pragma unroll
    for (int ks = 1; ks < 6; ks++)
      wg_s48<0, 24>(aO, qa[4 * ks], qa[4 * ks + 1], qa[4 * ks + 2], qa[4 * ks + 3], dK + ((ks * kChunkBytes + 7 * 1024 + 64) >> 4), 1, mq);
    wg_commit();
    wg_s56z<0, 28>(bE, qb[0], qb[1], qb[2], qb[3], dK, 0, mq);
#pragma unroll
    for (int ks = 1; ks < 6; ks++) wg_s56<0, 28>(bE, qb[4 * ks], qb[4 * ks + 1], qb[4 * ks + 2], qb[4 * ks + 3], dK + ((ks * kChunkBytes) >> 4), 1, mq);
    wg_commit();
    wg_wait<2>();
    fence_regs(aE);
    PROFS(5, wg, 5 + it * 12);

    uint32_t pa[14], pb[14], meta[4];
    {
      float vA[14], vB[14];
      pick_v(aE, vA, fl);
      pick_u(aE + 28, vA + 8, fl);
      fence_regs(vA);
      if (k == 0) {
        if (__builtin_expect(__any_sync(0xffffffffu, vA[6] != vA[6]), 0)) {
          wg_wait<0>();
          fence_regs(aO);
          fence_regs(bE);
          if (refetch(sbase + kW1Off, wimg, false)) {
#pragma unroll
            for (int j = 0; j < 24; j++) oa[j] = ob[j] = 0u;
            k -= 2;
            continue;
          }
        }
        if (elect_one()) mbar_arrive(bar_xf(bars));
      }
      wg_fence();
      wg_s104z<0, 52>(bO, qb[0], qb[1], qb[2], qb[3], dK + 4, 0, mq);
#pragma unroll
      for (int ks = 1; ks < 6; ks++)
        wg_s104<0, 52>(bO, qb[4 * ks], qb[4 * ks + 1], qb[4 * ks + 2], qb[4 * ks + 3], dK + ((ks * kChunkBytes + 64) >> 4), 1, mq);
      wg_commit();
      if (k + 1 < nt) nb_arrive(1 + wg);
      uint32_t rt[9];
#pragma unroll
      for (int i = 0; i < 7; i++) rt[i] = sign_bytes(geo[0] << (i >> 2), 0x8888u + 0x1111u * (i & 3));
      rt[7] = sign_bytes(geo[0] << 2, 0x9988u);
      rt[8] = sign_bytes(geo[0] << 2, 0xBBAAu);
      keep_regs(rt);
      pa[13] = geo[0] & zero, pb[13] = geo[1] & zero;
      wg_wait<2>();
      keep_regs(qa);
      fence_regs(aO);
      float oA[6], eB[8];
      pick_u(aO, oA, fl);
      wg_wait<1>();
      fence_regs(bE);
      pick_v(bE, eB, fl);
      vA[8] = sel<kColA>(oA[0], vA[8], fl), vA[9] = sel<kColA>(oA[1], vA[9], fl);
      vA[10] = sel<kColA * 2>(oA[2], vA[10], fl), vA[11] = sel<kColA * 2>(oA[3], vA[11], fl);
      vA[12] = sel<kColA * 4>(oA[4], vA[12], fl), vA[13] = sel<kColA * 4>(oA[5], vA[13], fl);
      {
        const float m1 = __uint_as_float(0x88DD88DDu), m0 = __uint_as_float(0x88DDDD88u);
        meta[0] = 0xDD88DD88u ^ __byte_perm(fl, 0u, 0x3344);
        meta[1] = __float_as_uint(sel<kColA * 16>(sel<kColA>(m1, m0, fl), __uint_as_float(meta[0]), fl));
        meta[2] = __float_as_uint(sel<kColA * 8>(m1, m0, fl));
        meta[3] = __float_as_uint(sel<kColA * 4>(m1, m0, fl));
        keep_regs(meta);
      }
      float mA = own_max(vA, fl);
      fl |= __float_as_uint(eB[7]) & zero;
      fence_regs(eB);
      fence_regs(vA);
      asm volatile("" : "+f"(mA), "+r"(fl));
      sched_fence();
      wg_wait<0>();
      sched_fence();
      keep_regs(qb);
      fence_regs(bO);
      PROFS(6, wg, 6 + it * 12);
      if (w == 0) GT(24 + k);
      mA = quad_max(mA);
      pick_v(bO, vB, fl);
      pick_u(bO + 28, vB + 8, fl);
#pragma unroll
      for (int i = 0; i < 8; i += 2) vB[i] = sel<kColB>(vB[i], eB[i], fl), vB[i + 1] = sel<kColB * 2>(vB[i + 1], eB[i + 1], fl);
#pragma unroll
      for (int i = 0; i < 14; i++) vA[i] = i < 3 ? ex2(vA[i] - mA) : vA[i] - mA;
      fence_regs(vA);
      fence_regs(vB);
      sched_fence();
#pragma unroll
      for (int i = 3; i < 14; i++) vA[i] = ex2(vA[i]);
      const float mB = quad_max(own_max(vB, fl));
      PROFS(7, wg, 7 + it * 12);
#pragma unroll
      for (int i = 0; i < 14; i++) vB[i] = i < 1 ? ex2(vB[i] - mB) : vB[i] - mB;
      fence_regs(vA);
      fence_regs(vB);
      sched_fence();
#pragma unroll
      for (int i = 1; i < 14; i++) vB[i] = ex2(vB[i]);
      route(vA, row_rcp(vA, fl), rt, pa);
      route(vB, row_rcp(vB, fl), rt, pb);
    }
    PROFS(8, wg, 8 + it * 12);
    if (k == NAT_PK) PROFS(18, wg, 53);
    sched_fence();

    float ac0[48], ac1[48];
    {
      float z0[32], z1[32], z2[32];
      uint32_t za[24], zb[24];
      wg_fence();
      pv_chunk<0>(z0, pa, pb, meta, dV);
      wg_commit();
      pv_chunk<1>(z1, pa, pb, meta, dV);
      wg_commit();
      wg_wait<1>();
      if (k == NAT_PK) PROFS(18, wg, 54);
      if (k + 1 < nt) nb_arrive_p(7);
      pv_chunk<2, 0, 3>(z2, pa, pb, meta, dV);
      wg_commit();
      sched_fence();
      fence_regs(z0);
      pack_z<0>(z0, za, zb);
      sched_fence();
      wg_fence();
      pv_chunk<2, 3, 7>(z2, pa, pb, meta, dV);
      wg_commit();
      wg_wait<2>();
      if (k == NAT_PK) PROFS(19, wg, 55);
      if (k + 1 < nt) nb_arrive_p(8);
      if (k < 2) mbar_wait(k == 1 ? bar_wok(bars) : bar_w2a(bars), 0);
      wg_fence();
      g2_steps<0, 3, 0>(ac0, za, zb, dX0);
      wg_commit();
      sched_fence();
      fence_regs(z1);
      pack_z<1>(z1, za, zb);
      sched_fence();
      wg_fence();
      g2_steps<3, 4, 0>(ac0, za, zb, dX0);
      wg_commit();
      g2_steps<4, 8, 0>(ac0, za, zb, dX0);
      wg_commit();
      wg_wait<3>();
      if (k + 1 < nt) nb_arrive_p(9);
      else nb_arrive(11);
      if (k == NAT_PK) PROFS(20, wg, 56);
      keep_regs(pa);
      keep_regs(pb);
      keep_regs(meta);
      sched_fence();
      const uint32_t mok = mbar_test(bar_w2m(bars), k + 1 < nt ? k & 1 : ~k & 1);
      const uint32_t wp = k < 2 ? 0 : k + 1 < nt ? ~k & 1 : k & 1, wok = mbar_test(bar_w2(bars), wp);
      fence_regs(z2);
      pack_z<2>(z2, za, zb);
      keep_regs(za);
      keep_regs(zb);
      sched_fence();
      PROFS(9, wg, 9 + it * 12);
      wg_wait<1>();
      if (k > 0 && k + 1 < nt) nb_arrive(11);
      mbar_wait_if(mok, bar_w2m(bars), k & 1);
      wg_fence();
      g2_steps<8, 12, 0>(ac0, za, zb, dX2);
      wg_commit();
      g2_steps<8, 12, 8>(ac1, za, zb, dY2);
      wg_commit();
      wg_wait<2>();
      if (k > 0 && k + 1 < nt) nb_arrive(12);
      mbar_wait_if(wok, bar_w2(bars), wp);
      wg_fence();
      g2_steps<0, 4, 8>(ac1, za, zb, dY0);
      wg_commit();
      wg_wait<2>();
      if (k + 2 < nt) nb_arrive_p(13);
      const bool direct = k + 2 >= nt;
      sched_fence();
      fence_regs(ac0);
      pack_out<0>(ac0, oa, ob);
      store_rows<0, 1>(direct, poA, poB, oa, ob);
      sched_fence();
      wg_fence();
      g2_steps<4, 8, 8>(ac1, za, zb, dY0);
      wg_commit();
      if (k + 1 < nt) nb_arrive(3 + wg);
      PROFS(10, wg, 10 + it * 12);
      wg_wait<2>();
      if (k + 2 < nt && (k > 0 || nt == 6)) nb_arrive_p(5);
      store_rows<1, 3>(direct, poA, poB, oa, ob);
      __nv_bfloat16 *qA = poA - 192 * wg, *qB = poB - 192 * wg;
      if (k + 2 == nt) nb_sync(11);
      sched_fence();
      wg_wait<0>();
      fence_regs(ac1);
      if (direct) {
        pack_out<1>(ac1, oa, ob);
        asm volatile("" : "+l"(qA), "+l"(qB));
        store_rows<3, 6>(true, qA, qB, oa, ob);
        break;
      }
      sched_fence();
      pack_out<1>(ac1, oa, ob);
      if (k == 0) {
        if (any_nan(oa)) {
          for (int c = 0; c < 3 && __any_sync(0xffffffffu, geo[2] & 1u); c++) mbar_wait(bar_x(bars, 1, c), 1);
          bool first = true;
          do {
            if (!__any_sync(0xffffffffu, refetch(sbase + kW2Off, wimg + w2_offset(), first))) break;
            first = false;
            wg_fence();
            g2_steps<0, 8, 0>(ac0, za, zb, dX0);
            g2_steps<8, 12, 0>(ac0, za, zb, dX2);
            g2_steps<8, 12, 8>(ac1, za, zb, dY2);
            g2_steps<0, 8, 8>(ac1, za, zb, dY0);
            wg_commit();
            wg_wait<0>();
            fence_regs(ac0);
            fence_regs(ac1);
            pack_out<0>(ac0, oa, ob);
            pack_out<1>(ac1, oa, ob);
          } while (any_nan(oa));
          if (__any_sync(0xffffffffu, geo[2] & 1u)) {
            asm volatile("bar.sync 15, 128;" ::: "memory");
            if (w == 0 && elect_one()) {
              const TileCoord tc = decode_tile(tt, tile0 + 2);
              mbar_arrive_expect_tx(bar_raw(bars), kWChunk);
#pragma unroll 1
              for (int c = 0; c < 3; c++) load_px(tm, tt, sbase + x_chunk(2, c), bar_raw(bars), first_line(tc) + c, tc.kind);
            }
            __syncwarp();
            mbar_wait(bar_raw(bars), 0);
          }
        }
        if (nt < 6) nb_arrive_p(5);
        if (elect_one()) mbar_arrive(bar_wok(bars));
      }
      keep_regs(za);
      keep_regs(zb);
#pragma unroll
      for (int i = 0; i < 4; i++) geo[i] = geo[i + 2];
      keep_regs(oa);
      keep_regs(ob);
      PROFS(12, wg, 12 + it * 12);
      sched_fence();
    }
  }
  PROF(wg, 38);
  GT_DUMP();
  PROF_DUMP(wg);
}

struct HaloCols { int vj, vc, uj, uc; };
__device__ __forceinline__ HaloCols halo_cols(const TileCoord& tc) {
  const int c0 = halo_c0(tc);
  return HaloCols{c0 > 98, c0 > 98 ? 98 : c0 + 3, c0 < 0 ? -1 : 0, c0 < 0 ? 4 : c0};
}
__device__ __forceinline__ void first_halo(const Maps& tm, uint32_t sbase, const TileCoord tc, int i) {
  const HaloCols hc = halo_cols(tc);
  const uint32_t dst = sbase + i * kChunkBytes, bar = bar_full(sbase + kBarOff, 0, i >> 1);
  const int h0 = halo_r0(tc), ch = 24 * tc.pc + 4 * i;
  tma_load_5d(dst, &tm.v14, bar, ch, hc.vj, hc.vc, tc.pr, h0);
  tma_load_5d(dst + 7 * 1024, &tm.u8, bar, ch, hc.uj, h0 + (tc.up ? 0 : -2), tc.pr, hc.uc);
  tma_load_5d(dst + 10 * 1024, &tm.u8, bar, ch, hc.uj, h0 + (tc.up ? 8 : 6), tc.pr, hc.uc);
}
__device__ __forceinline__ void load_halo(const Maps& tm, uint32_t sbase, uint32_t bars, const TileCoord tc, int k, int c) {
  const HaloCols hc = halo_cols(tc);
  const int h6 = halo_r0(tc) + (tc.up ? 0 : 8), h2 = halo_r0(tc) + 6, h8 = halo_r0(tc) + (tc.up ? 0 : 6), ch = 24 * tc.pc + 8 * c;
  uint32_t dv = sbase + 2 * c * kChunkBytes, du = dv + 7 * 1024;
  if (((k ^ tc.up) & 1) == 0) dv += 4 * 1024, du += 3 * 1024;
  const uint32_t bar = bar_full(bars, k & 1, c);
  mbar_arrive_expect_tx(bar, 14 * 1024);
  nb_sync_p(7 + c);
#pragma unroll
  for (int h = 0; h < 2; h++) {
    tma_load_5d(dv + h * kChunkBytes, &tm.v6, bar, ch + 4 * h, hc.vj, hc.vc, tc.pr, h6);
    tma_load_5d(du + h * kChunkBytes, &tm.u8, bar, ch + 4 * h, hc.uj, h8, tc.pr, hc.uc);
    tma_load_5d(sbase + (2 * c + h) * kChunkBytes + 3 * 1024, &tm.v2, bar, ch + 4 * h, hc.vj, hc.vc, tc.pr, h2);
  }
  PROFS(15, 2, k * 4 + c);
}
__device__ __forceinline__ void gather_px(const __nv_bfloat16* __restrict__ x, uint32_t sbase, const TileCoord tc) {
  const int lane = threadIdx.x & 31, g = lane >> 3;
  uint32_t ro[4], co[4];
#pragma unroll
  for (int i = 0; i < 4; i++) {
    ro[i] = qpix(tc.pr, 8 * tc.I + 2 * i + (g & 1)) * (kW * kC * 2) + 16 * (lane & 7);
    co[i] = qpix(tc.pc, 8 * tc.J + 2 * i + (g >> 1)) * (kC * 2);
  }
  const uint32_t dst = sbase + kXOff + g * 128 + (((lane & 7) ^ g) << 4);
  if (lane < 8)
    asm volatile("cp.async.bulk.prefetch.L2.global [%0], 3456;" ::"l"(x + (qpix(tc.pr, 8 * tc.I + lane) * kW + 215 * tc.pc) * kC) : "memory");
  __syncwarp();
  keep_regs(ro);
  keep_regs(co);
  sched_fence();
  nb_sync_p(13);
  nb_sync_p(5);
#pragma unroll
  for (int i = 0; i < 16; i++) {
    const char* src = (const char*)x + (ro[i >> 2] + co[i & 3]);
#pragma unroll
    for (int q = 0; q < 3; q++)
      asm volatile("cp.async.cg.shared.global [%0], [%1], 16;" ::"r"((dst ^ ((i & 1) * 576)) + (i >> 1) * 1024 + q * 8192), "l"(src + 128 * q) : "memory");
  }
  asm volatile("cp.async.wait_all;" ::: "memory");
  fence_proxy_async();
  __syncwarp();
  if (lane < 3) mbar_arrive(bar_x(sbase + kBarOff, 1, lane));
  __syncwarp();
}

__global__ void __launch_bounds__(384, 1)
nat_kernel(const __nv_bfloat16* __restrict__ x, __nv_bfloat16* out, const __nv_bfloat16* __restrict__ wqkv,
           const __nv_bfloat16* __restrict__ wo, uint8_t* wimg, const uint32_t zero,
           const __grid_constant__ Maps tm, const __grid_constant__ TileTable tt) {
  extern __shared__ uint8_t smem_raw[];
  constexpr uint32_t sbase = 1024;
  constexpr uint32_t bars = sbase + kBarOff;
  if (smem_u32(smem_raw) != sbase) __trap();
  const int tid = threadIdx.x;
  const uint32_t t_start = now_ns();
  if (tid == 0) GT(0);
  const int wid = __shfl_sync(0xffffffffu, tid >> 5, 0);
  const bool w2cta = blockIdx.x - 128 < 3 && wqkv != nullptr;
  if (wid >= 8) {
    asm volatile("setmaxnreg.dec.sync.aligned.u32 24;");
    const int c = wid & 3, lane = tid & 31;
    const int tile0 = blockIdx.x * kTilesPerCta, nt = num_tiles();
    uint32_t w2o = 0;
    if (c == 3) {
      if (elect_one()) wait_clock(t_start, NAT_TM);
      __syncwarp();
      asm volatile("prefetch.tensormap [%0];" ::"l"((uint64_t)tm.px) : "memory");
      asm volatile("prefetch.tensormap [%0];" ::"l"((uint64_t)&tm.v6) : "memory");
      asm volatile("prefetch.tensormap [%0];" ::"l"((uint64_t)&tm.v2) : "memory");
      asm volatile("prefetch.tensormap [%0];" ::"l"((uint64_t)(tm.px + (blockIdx.x < 112 ? 5 : 6))) : "memory");
      asm volatile("prefetch.tensormap [%0];" ::"l"((uint64_t)(tm.px + 7)) : "memory");
      if (nt < 6) {
        asm volatile("prefetch.tensormap [%0];" ::"l"((uint64_t)(tm.px + 1)) : "memory");
        asm volatile("prefetch.tensormap [%0];" ::"l"((uint64_t)(tm.px + 2)) : "memory");
        asm volatile("prefetch.tensormap [%0];" ::"l"((uint64_t)&tm.v14) : "memory");
        asm volatile("prefetch.tensormap [%0];" ::"l"((uint64_t)&tm.u8) : "memory");
      }
      __nanosleep(NAT_TW2 - 2800);
      asm volatile("bar.sync 4, 64;" ::: "memory");
      w2o = w2_offset();
      if (elect_one()) {
        mbar_arrive_expect_tx(bar_w2a(bars), kWChunk);
        mbar_arrive_expect_tx(bar_w2(bars), kWChunk);
        wait_clock(t_start, NAT_TW2);
        bulk_load(sbase + kW2Off, wimg + w2o, kWChunk, bar_w2a(bars));
        mbar_wait(bar_xf(bars), 0);
        bulk_load(sbase + kW2Off + 2 * kWChunk, wimg + (w2o + 2 * kWChunk), kWChunk, bar_w2(bars));
      }
      __syncwarp();
      if (nt < 6) gather_px(x, sbase, decode_tile(tt, tile0 + 2));
      if (wqkv == nullptr) return;
      mbar_wait(bar_wok(bars), 0);
      if (lane == 0) asm volatile("red.relaxed.gpu.global.add.u32 [%0], 1;" ::"l"(g_flag) : "memory");
      if (blockIdx.x != kCtas - 1) return;
#pragma unroll
      for (int i = 0; i < 8; i++) asm volatile("st.shared.v4.u32 [%0], {%1,%1,%1,%1};" ::"r"(bars + 1024 + i * 512 + lane * 16), "r"(kEmpty) : "memory");
      fence_proxy_async();
      __syncwarp();
      if (elect_one()) {
#pragma unroll 1
        for (int i = 0; i < 36; i++) {
          if (i == 18) {
            uint32_t v, it = 0;
            do {
              __nanosleep(500);
              asm volatile("ld.relaxed.gpu.global.u32 %0, [%1];" : "=r"(v) : "l"(g_flag) : "memory");
            } while (v < gridDim.x && ++it < (1u << 18));
          }
          asm volatile("cp.async.bulk.global.shared::cta.bulk_group [%0], [%1], 4096;" ::"l"(
                           wimg + (i < 18 ? 3 * kWBytes - w2o + i * 4096 : (i - 18) * 4096)), "r"(bars + 1024) : "memory");
          asm volatile("cp.async.bulk.commit_group;" ::: "memory");
          asm volatile("cp.async.bulk.wait_group.read 1;" ::: "memory");
        }
        asm volatile("cp.async.bulk.wait_group 0;" ::: "memory");
        g_flag[0] = 0;
        g_flag[32] = w2o == kWBytes;
      }
      return;
    }
    if (!elect_one()) return;
    if (c == 0) {
      for (int i = 0; i < kNumBars; i++)
        if ((i != 0 && i != 10 || nt < 6) && (i != 21 || !w2cta)) mbar_init(bars + i * 8, i == 13 || i == 16 ? 4 : 1);
      asm volatile("st.shared.v2.u32 [%0], {%1,%1};" ::"r"(bars + 192), "r"(0) : "memory");
      asm volatile("fence.mbarrier_init.release.cluster;" ::: "memory");
      if (w2cta) asm volatile("bar.sync 10, 64;" ::: "memory");
      asm volatile("bar.arrive 0, 160;" ::: "memory");
      asm volatile("bar.arrive 14, 160;" ::: "memory");
      asm volatile("bar.arrive 13, 96;" ::: "memory");
      asm volatile("bar.arrive 4, 64;" ::: "memory");
      const TileCoord tc0 = decode_tile(tt, tile0);
      const HaloCols hc = halo_cols(tc0);
      const int h0 = halo_r0(tc0);
#pragma unroll
      for (int j = 0; j < 3; j++)
        if (j > 0 || nt < 6) mbar_arrive_expect_tx(bar_full(bars, 0, j), 2 * kChunkBytes);
      wait_clock(t_start, NAT_HP);
#pragma unroll
      for (int q = 8; q < 24 && !w2cta; q += 8) {
        tma_prefetch_5d(blockIdx.x < 112 ? &tm.v6 : &tm.v14, 24 * tc0.pc + q, hc.vj, hc.vc, tc0.pr, h0 + (tc0.up || blockIdx.x >= 112 ? 0 : 8));
        tma_prefetch_5d(&tm.u8, 24 * tc0.pc + q, hc.uj, h0 + (tc0.up ? 0 : 6), tc0.pr, hc.uc);
      }
#pragma unroll 1
      for (int i = nt < 6 ? 0 : 2; i < 6; i++) {
        if (i == 2) mbar_wait(bar_w1q(bars), 0);
        first_halo(tm, sbase, tc0, i);
      }
      mbar_arrive(bar_go(bars));
      w2o = w2_offset();
    } else {
      asm volatile("bar.sync 13, 96;" ::: "memory");
      if (c == 2) {
        if (wqkv != nullptr && blockIdx.x < 131) asm volatile("bar.sync 12, 64;" ::: "memory");
        const uint32_t c0 = clock();
        while ((uint32_t)clock() - c0 < NAT_TD && nt == 6) { }
        wait_clock(t_start, NAT_T0);
#pragma unroll
        for (int j = 0; j < 3; j++) {
          mbar_arrive_expect_tx(bar_w1c(bars, j), kWChunk);
          bulk_load(sbase + kW1Off + j * kWChunk, wimg + j * kWChunk, kWChunk, bar_w1c(bars, j));
        }
        mbar_arrive(bar_w1q(bars));
        GT(2);
      } else {
#pragma unroll 1
        for (int j = nt == 6; j < 2; j++) {
          const TileCoord tc = decode_tile(tt, tile0 + j);
          const int line = first_line(tc);
          if (j == 1) mbar_wait(bar_go(bars), 0);
          if (j == 0) GT(15);
#pragma unroll 1
          for (int q = 0; q < 3; q++) {
            load_px(tm, tt, sbase + x_chunk(j, q), bar_x(bars, j, q), line + q, tc.kind);
            if (j == 1 || q == 0) mbar_arrive_expect_tx(bar_x(bars, j, q), j ? 8192 : kWChunk);
          }
          if (j == 0) GT(16);
        }
        w2o = w2_offset();
        wait_clock(t_start, NAT_TW2);
        mbar_wait(bar_xf(bars), 0);
      }
    }
#pragma unroll 1
    for (int k = 1; k < nt; k++) {
      const TileCoord tn = decode_tile(tt, tile0 + k + 1);
      const int line = first_line(tn);
      const bool more = k + 1 < nt && (k > 1 || nt == 6);
      if (c == 1) {
#pragma unroll
        for (int q = 0; q < 3; q++) {
          nb_sync_p(q == 0 ? 0 : q == 1 ? 14 : 6);
          bulk_load(sbase + x_chunk(k, q), wimg + (w2o + x_chunk(k, q) - kW2Off), 8192, bar_w2m(bars));
        }
        mbar_arrive_expect_tx(bar_w2m(bars), kWChunk);
      }
      if (c == 2) {
        if (k == 1) wait_clock(t_start, NAT_TX2);
        else __nanosleep(NAT_PFD);
#pragma unroll 1
        for (int q = 0; q < 3 && more; q++) load_px(tm, tt, 0, 0, line + q, tn.kind);
      }
      if (c == 2 && (blockIdx.x >= 112 || k == 5)) {
        const TileCoord tc = decode_tile(tt, tile0 + k);
        const HaloCols hc = halo_cols(tc);
        const int h8 = halo_r0(tc) + (tc.up ? 0 : 6);
#pragma unroll 1
        for (int q = 0; q < 24; q += 8) {
          tma_prefetch_5d(&tm.v6, 24 * tc.pc + q, hc.vj, hc.vc, tc.pr, h8);
          tma_prefetch_5d(&tm.v2, 24 * tc.pc + q, hc.vj, hc.vc, tc.pr, h8 + 6);
          tma_prefetch_5d(&tm.u8, 24 * tc.pc + q, hc.uj, h8, tc.pr, hc.uc);
        }
      }
      load_halo(tm, sbase, bars, decode_tile(tt, tile0 + k), k, c);
      if (c == 0 && more) {
#pragma unroll
        for (int q = 0; q < 3; q++) {
          if (q < 2) nb_sync_p(q ? 5 : 13);
          load_px(tm, tt, sbase + x_chunk(k + 1, q), bar_x(bars, 1, q), line + q, tn.kind);
          if (q != 1) mbar_arrive_expect_tx(bar_x(bars, 1, q), 8192);
        }
        mbar_arrive_expect_tx(bar_x(bars, 1, 1), 8192);
        PROFS(16, 2, k * 4 + 3);
      }
      if (c == 0 && k >= 2) {
        const TileCoord tp = decode_tile(tt, tile0 + k - 2);
        const int lp = first_line(tp);
        nb_sync_p(10);
        __nanosleep(NAT_XW);
        store_px(tm, tt, sbase + out_slot(k, nt), lp, tp.kind);
        if (k + 1 < nt) {
          asm volatile("cp.async.bulk.wait_group.read 0;" ::: "memory");
          bulk_load(sbase + out_slot(k, nt), wimg + (w2o + out_slot(k, nt) - kW2Off), kWChunk, bar_w2(bars));
          mbar_arrive_expect_tx(bar_w2(bars), kWChunk);
        }
      }
    }
    asm volatile("cp.async.bulk.wait_group 0;" ::: "memory");
  } else {
    if (blockIdx.x < 128) {
      if ((wid == 4 || (wid == 5 && blockIdx.x - 2 < 16)) && wqkv != nullptr) {
        fold_w1(blockIdx.x - 2 < 16 ? 2 * blockIdx.x + wid - 6 : blockIdx.x + (blockIdx.x < 2 ? 0 : 16), wqkv, wimg);
        if (wid == 4) asm volatile("bar.arrive 12, 64;" ::: "memory");
        if (tid == 128) GT(7);
      }
      sched_fence();
      if (wid == 1 && elect_one()) {
        const TileCoord tc = decode_tile(tt, blockIdx.x * kTilesPerCta);
        mbar_init(bar_x(bars, 0, 0), 1);
        asm volatile("fence.mbarrier_init.release.cluster;" ::: "memory");
        mbar_arrive_expect_tx(bar_x(bars, 0, 0), kWChunk);
        GT(15);
#pragma unroll 1
        for (int q = 0; q < 3; q++) load_px(tm, tt, sbase + x_chunk(0, q), bar_x(bars, 0, 0), first_line(tc) + q, tc.kind);
        GT(16);
      }
      __syncwarp();
      sched_fence();
      if (wid == 2 && elect_one()) {
        const TileCoord tc = decode_tile(tt, blockIdx.x * kTilesPerCta);
        mbar_init(bar_full(bars, 0, 0), 1);
        asm volatile("fence.mbarrier_init.release.cluster;" ::: "memory");
        mbar_arrive_expect_tx(bar_full(bars, 0, 0), 2 * kChunkBytes);
        asm volatile("prefetch.tensormap [%0];" ::"l"((uint64_t)&tm.u8) : "memory");
        GT(17);
        first_halo(tm, sbase, tc, 0);
        first_halo(tm, sbase, tc, 1);
      }
      __syncwarp();
    }
    sched_fence();
    {
      if (blockIdx.x >= 128 && wqkv != nullptr && (wid | 2) == 2 && elect_one())
        asm volatile("cp.async.bulk.prefetch.L2.global [%0], %1;" ::"l"(wid ? wo + (blockIdx.x & 3) * 48 * 192 : wqkv + (blockIdx.x & 3) * 48 * 576),
                     "r"(wid ? 48 * 384 : 48 * 1152) : "memory");
      __syncwarp();
      if (w2cta) {
        const int q = blockIdx.x & 3, h = wid >> 2;
        uint32_t w2o = 0;
        if (wid == 1 && elect_one()) {
          asm volatile("prefetch.tensormap [%0];" ::"l"((uint64_t)&tm.wo) : "memory");
          mbar_init(bar_raw(bars, 0), 1);
          mbar_init(bar_raw(bars, 1), 1);
          asm volatile("fence.mbarrier_init.release.cluster;" ::: "memory");
#pragma unroll
          for (int j = 0; j < 3; j++)
            asm volatile("cp.async.bulk.tensor.3d.shared::cluster.global.tile.mbarrier::complete_tx::bytes [%0], [%1, {%3, %4, %5}], [%2];" ::"r"(
                             j ? sbase + kW2Off + (j - 1) * (kWBytes / 2) : sbase),
                         "l"((uint64_t)(j ? &tm.wo : &tm.wv)), "r"(bar_raw(bars, j >> 1)), "r"(0), "r"(j ? 0 : 64 * q), "r"(j ? 3 * j - 3 : 6) : "memory");
          mbar_arrive_expect_tx(bar_raw(bars, 0), kWChunk + kWBytes / 2);
          mbar_arrive_expect_tx(bar_raw(bars, 1), kWBytes / 2);
          w2o = w2_offset();
        }
        __syncwarp();
#pragma unroll 1
        for (int r = 1 - h;; r++) {
          if (r > 0) asm volatile("bar.sync 11, 256;" ::: "memory");
          if (r == 2) break;
          if (r > 0) {
            mbar_wait(bar_raw(bars, 0), 0);
            mbar_wait(bar_raw(bars, h), 0);
          }
          if (tid == 0) GT(7);
          float acc[48];
          const uint64_t db = make_desc(sbase + kW2Off + h * (kWBytes / 2), kWChunk / 2, 512, 2);
          wg_fence();
          wg_m96tz<0, 48>(acc, make_desc(sbase, 16, 1024), db, 0);
#pragma unroll
          for (int s = 1; s < 12; s++) wg_m96t<0, 48>(acc, make_desc(sbase + (s >> 2) * 8192 + (s & 3) * 32, 16, 1024), db + s * 64, 1);
          wg_commit();
          wg_wait<0>();
          fence_regs(acc);
          if (tid == 0) GT(19);
          const int m = (tid >> 3) & 3;
#pragma unroll
          for (int j = 0; j < 12; j += 2) {
            const int n = g2_inv(8 * (j + (m >> 1)) + (tid & 7));
            asm volatile("stmatrix.sync.aligned.m8n8.x4.trans.shared.b16 [%0], {%1,%2,%3,%4};" ::"r"(
                             sbase + kW1Off + h * (kWChunk / 2) + n * 128 + (((2 * (wid & 3) + (m & 1)) ^ (n & 7)) << 4)),
                         "r"(pack_bf16(acc[4 * j], acc[4 * j + 1])), "r"(pack_bf16(acc[4 * j + 2], acc[4 * j + 3])),
                         "r"(pack_bf16(acc[4 * j + 4], acc[4 * j + 5])), "r"(pack_bf16(acc[4 * j + 6], acc[4 * j + 7])) : "memory");
          }
          fence_proxy_async();
        }
        if (tid == 0) GT(18);
        if (wid == 1) {
          if (elect_one()) {
#pragma unroll
            for (int i = 0; i < 2; i++)
              asm volatile("cp.async.bulk.global.shared::cta.bulk_group [%0], [%1], %2;" ::"l"(wimg + (w2o + w2piece(i, q) * (kWChunk / 2))),
                           "r"(sbase + kW1Off + i * (kWChunk / 2)), "r"(kWChunk / 2) : "memory");
            asm volatile("cp.async.bulk.commit_group;" ::: "memory");
          }
          __syncwarp();
          asm volatile("bar.arrive 10, 64;" ::: "memory");
          if (elect_one()) asm volatile("cp.async.bulk.wait_group.read 0;" ::: "memory");
          if (tid == 32) GT(31);
          __syncwarp();
          asm volatile("bar.arrive 12, 64;" ::: "memory");
        }
      }
    }
    __syncwarp();
    if (wid < 4) asm volatile("bar.sync 0, 160;" ::: "memory");
    else asm volatile("bar.sync 14, 160;" ::: "memory");
    asm volatile("setmaxnreg.inc.sync.aligned.u32 240;");
    consumer(wid >> 2, out, wimg, sbase, zero, tm, tt);
  }
}

}

typedef CUresult (*PFN_encodeTiled)(CUtensorMap*, CUtensorMapDataType, cuuint32_t, void*, const cuuint64_t*,
                                    const cuuint64_t*, const cuuint32_t*, const cuuint32_t*, CUtensorMapInterleave,
                                    CUtensorMapSwizzle, CUtensorMapL2promotion, CUtensorMapFloatOOBfill);

extern "C" void kernel_launch(void* const* d_in, const int* in_sizes, int n_in, void* d_out, int out_size) {
  const __nv_bfloat16* x = (const __nv_bfloat16*)d_in[0];
  const __nv_bfloat16* wqkv = (const __nv_bfloat16*)d_in[1];
  const __nv_bfloat16* wo = (const __nv_bfloat16*)d_in[2];
  __nv_bfloat16* out = (__nv_bfloat16*)d_out;

  static PFN_encodeTiled encode = nullptr;
  static int num_sms = 0;
  static uint8_t* wimg = nullptr;
  if (!encode) {
    void* fn = nullptr;
    cudaDriverEntryPointQueryResult qres;
    cudaGetDriverEntryPoint("cuTensorMapEncodeTiled", &fn, cudaEnableDefault, &qres);
    encode = (PFN_encodeTiled)fn;
    cudaFuncSetAttribute(nat::nat_kernel, cudaFuncAttributeMaxDynamicSharedMemorySize, nat::kSmemBytes);
    cudaGetSymbolAddress((void**)&wimg, nat::g_wimg32);
    int dev = 0;
    cudaGetDevice(&dev);
    cudaDeviceGetAttribute(&num_sms, cudaDevAttrMultiProcessorCount, dev);
  }
  nat::Maps tm;
  cuuint32_t estr[5] = {1, 1, 1, 1, 1};
  {
    cuuint64_t vdim[5] = {48, 2, 105, 2, 112}, udim[5] = {48, 2, 112, 2, 105};
    cuuint64_t vstr[4] = {7 * 768, 768, 224 * 384, 2 * 224 * 384}, ustr[4] = {7 * 768, 2 * 224 * 384, 224 * 384, 768};
    CUtensorMap* maps[4] = {&tm.v6, &tm.v2, &tm.v14, &tm.u8};
    for (int i = 0; i < 4; i++) {
      cuuint32_t box[5] = {4, 2, i < 3 ? 4u : 8u, 1, i == 0 ? 6u : i == 1 ? 2u : i == 2 ? 14u : 3u};
      encode(maps[i], CU_TENSOR_MAP_DATA_TYPE_UINT32, 5, (void*)x, i < 3 ? vdim : udim, i < 3 ? vstr : ustr, box, estr,
             CU_TENSOR_MAP_INTERLEAVE_16B, CU_TENSOR_MAP_SWIZZLE_128B, CU_TENSOR_MAP_L2_PROMOTION_L2_128B, CU_TENSOR_MAP_FLOAT_OOB_FILL_NONE);
    }
  }
  for (int i = 0; i < 8; i++) {
    const cuuint32_t row = 224 * 384;
    const cuuint32_t shape[8][6] = {{2, 8, 4, 2 * row, 768, 4 * row}, {2, 8, 3, row, 768, 2 * row},     {2, 8, 1, 2 * row, 768, 4 * row},
                                    {8, 2, 3, 2 * row, 4 * 384, 384}, {8, 2, 1, 2 * row, 5 * 384, 384}, {4, 2, 3, 4 * row, 2 * row, 128},
                                    {4, 2, 3, 768, row, 128},         {4, 2, 3, 768, 2 * row, 128}};
    const cuuint32_t* sh = shape[i];
    cuuint64_t dim[5] = {64, sh[0], sh[1], sh[2], 224 * 224 * 3};
    cuuint64_t str[4] = {sh[3], sh[4], sh[5], 128};
    cuuint32_t box[5] = {64, sh[0], sh[1], sh[2], 1};
    encode(tm.px + i, CU_TENSOR_MAP_DATA_TYPE_BFLOAT16, 5, i < 5 ? (void*)x : (void*)out, dim, str, box, estr, CU_TENSOR_MAP_INTERLEAVE_NONE,
           CU_TENSOR_MAP_SWIZZLE_128B, i < 5 ? CU_TENSOR_MAP_L2_PROMOTION_L2_128B : CU_TENSOR_MAP_L2_PROMOTION_NONE,
           CU_TENSOR_MAP_FLOAT_OOB_FILL_NONE);
  }
  for (int i = 0; i < 2; i++) {
    cuuint64_t dim[3] = {i ? 32u : 64u, 192, i ? 6u : 9u}, str[2] = {i ? 384u : 1152u, i ? 64u : 128u};
    cuuint32_t box[3] = {i ? 32u : 64u, i ? 192u : 64u, 3};
    encode(i ? &tm.wo : &tm.wv, CU_TENSOR_MAP_DATA_TYPE_BFLOAT16, 3, i ? (void*)wo : (void*)wqkv, dim, str, box, estr,
           CU_TENSOR_MAP_INTERLEAVE_NONE, i ? CU_TENSOR_MAP_SWIZZLE_64B : CU_TENSOR_MAP_SWIZZLE_128B, CU_TENSOR_MAP_L2_PROMOTION_L2_256B,
           CU_TENSOR_MAP_FLOAT_OOB_FILL_NONE);
  }
  nat::TileTable tt;
  nat::make_tiles(tt);
  const int grid = nat::kCtas;
  if (num_sms >= grid) {
    nat::nat_kernel<<<grid, 384, nat::kSmemBytes>>>(x, out, wqkv, wo, wimg, 0u, tm, tt);
  } else {
    nat::fold_kernel<<<27, 256>>>(wqkv, wo, wimg);
    nat::nat_kernel<<<grid, 384, nat::kSmemBytes>>>(x, out, nullptr, nullptr, wimg, 0u, tm, tt);
  }
}
```

```cpp
#include <cuda_runtime.h>
#include <cuda_bf16.h>
#include <cuda.h>
#include <stdint.h>

#define NAT_TM 1300
#define NAT_HP 1800
#define NAT_T0 2130
#define NAT_TD 1250
#define NAT_TX2 3800
#define NAT_TW2 4600
#define NAT_PFD 300
#define NAT_XW 200
#define NAT_PK 3
namespace nat {

constexpr int kW = 224, kC = 192;
constexpr int kCtas = 132;
constexpr int kTilesPerCta = 6;
constexpr float kAlpha = 0.07216878364870322f * 1.4426950408889634f;
constexpr uint32_t kChunkBytes = 13 * 1024;
constexpr uint32_t kWChunk = 192 * 128;
constexpr uint32_t kWBytes = 3 * kWChunk;
constexpr uint32_t kW1Off = 6 * kChunkBytes;
constexpr uint32_t kW2Off = kW1Off + kWBytes;
constexpr uint32_t kXOff = kW2Off + kWChunk;
constexpr uint32_t kBarOff = kW2Off + kWBytes;
constexpr uint32_t kProfOff = kBarOff + 208;
constexpr uint32_t kSmemBytes = kBarOff + 1024 + 4096;

static_assert(kW1Off % 1024 == 0 && kW2Off % 1024 == 0 && kChunkBytes % 1024 == 0, "swizzle alignment");
static_assert(kSmemBytes <= 232448, "smem");

constexpr uint32_t kEmpty = 0xFFFFFFFFu;
#define NAT_R8(v) v, v, v, v, v, v, v, v
#define NAT_R2K(v) NAT_R8(NAT_R8(NAT_R8(v))), NAT_R8(NAT_R8(NAT_R8(v))), NAT_R8(NAT_R8(NAT_R8(v))), NAT_R8(NAT_R8(NAT_R8(v)))
#define NAT_IMG NAT_R8(NAT_R2K(kEmpty)), NAT_R2K(kEmpty)
__device__ __align__(1024) uint32_t g_wimg32[3 * kWBytes / 4] = {NAT_IMG, NAT_IMG, NAT_IMG};
static_assert(kWBytes / 4 == 9 * 2048, "initialiser");
__device__ __align__(128) uint32_t g_flag[64];
__device__ __forceinline__ uint32_t w2_offset() {
  uint32_t v;
  asm volatile("ld.relaxed.gpu.global.u32 %0, [%1];" : "=r"(v) : "l"(g_flag + 32) : "memory");
  return (1 + v) * kWBytes;
}

#define PROFS(id, wgid, slotid) do { } while (0)
#define PROF(wgid, slotid) do { } while (0)
#define PROF_DUMP(wgid) do { } while (0)

#define GT(slotid) do { } while (0)
#define GT_DUMP() do { } while (0)

__device__ __forceinline__ uint32_t smem_u32(const void* p) { return (uint32_t)__cvta_generic_to_shared(p); }

__device__ __forceinline__ void mbar_init(uint32_t bar, uint32_t count) {
  asm volatile("mbarrier.init.shared::cta.b64 [%0], %1;" ::"r"(bar), "r"(count) : "memory");
}
__device__ __forceinline__ void mbar_arrive(uint32_t bar) {
  asm volatile("mbarrier.arrive.shared::cta.b64 _, [%0];" ::"r"(bar) : "memory");
}
__device__ __forceinline__ void mbar_arrive_expect_tx(uint32_t bar, uint32_t bytes) {
  asm volatile("mbarrier.arrive.expect_tx.shared::cta.b64 _, [%0], %1;" ::"r"(bar), "r"(bytes) : "memory");
}
__device__ __forceinline__ void mbar_wait(uint32_t bar, uint32_t parity) {
  uint32_t ok;
  uint32_t it = 0;
  do {
    asm volatile(
        "{\n.reg .pred p;\n"
        "mbarrier.try_wait.parity.shared::cta.b64 p, [%1], %2;\n"
        "selp.u32 %0, 1, 0, p;\n}\n"
        : "=r"(ok)
        : "r"(bar), "r"(parity)
        : "memory");
    if (++it > (1u << 24)) break;
  } while (!ok);
}
__device__ __forceinline__ uint32_t mbar_test(uint32_t bar, uint32_t parity) {
  uint32_t ok;
  asm volatile("{\n.reg .pred p;\nmbarrier.test_wait.parity.shared::cta.b64 p, [%1], %2;\nselp.u32 %0, 1, 0, p;\n}\n"
               : "=r"(ok) : "r"(bar), "r"(parity) : "memory");
  return ok;
}
__device__ __forceinline__ void mbar_wait_if(uint32_t ok, uint32_t bar, uint32_t parity) {
  if (!__all_sync(0xffffffffu, ok)) mbar_wait(bar, parity);
}
__device__ __forceinline__ bool elect_one() {
  uint32_t r;
  asm volatile("{\n.reg .pred p;\nelect.sync _|p, 0xffffffff;\nselp.u32 %0, 1, 0, p;\n}\n" : "=r"(r));
  return r != 0;
}
__device__ __forceinline__ void nb_arrive(int id) { asm volatile("bar.arrive %0, 256;" ::"r"(id) : "memory"); }
__device__ __forceinline__ void nb_sync(int id) { asm volatile("bar.sync %0, 256;" ::"r"(id) : "memory"); }
__device__ __forceinline__ void nb_arrive_p(int id) { asm volatile("bar.arrive %0, 160;" ::"r"(id) : "memory"); }
__device__ __forceinline__ void nb_sync_p(int id) { asm volatile("bar.sync %0, 160;" ::"r"(id) : "memory"); }
__device__ __forceinline__ void fence_proxy_async() { asm volatile("fence.proxy.async.shared::cta;" ::: "memory"); }

__device__ __forceinline__ void tma_load_5d(uint32_t dst, const CUtensorMap* map, uint32_t bar, int c0, int c1, int c2,
                                            int c3, int c4) {
  asm volatile(
      "cp.async.bulk.tensor.5d.shared::cluster.global.tile.mbarrier::complete_tx::bytes "
      "[%0], [%1, {%3, %4, %5, %6, %7}], [%2];"
      ::"r"(dst), "l"((uint64_t)map), "r"(bar), "r"(c0), "r"(c1), "r"(c2), "r"(c3), "r"(c4)
      : "memory");
}
__device__ __forceinline__ void bulk_load(uint32_t dst, const void* src, uint32_t bytes, uint32_t bar) {
  asm volatile("cp.async.bulk.shared::cluster.global.mbarrier::complete_tx::bytes [%0], [%1], %2, [%3];"
               ::"r"(dst), "l"((uint64_t)src), "r"(bytes), "r"(bar)
               : "memory");
}

__device__ __forceinline__ void wg_fence() { asm volatile("wgmma.fence.sync.aligned;" ::: "memory"); }
__device__ __forceinline__ void wg_commit() { asm volatile("wgmma.commit_group.sync.aligned;" ::: "memory"); }
template <int N>
__device__ __forceinline__ void wg_wait() { asm volatile("wgmma.wait_group.sync.aligned %0;" ::"n"(N) : "memory"); }

template <int N>
__device__ __forceinline__ void fence_regs(float (&d)[N]) {
#pragma unroll
  for (int i = 0; i < N; i++) asm volatile("" : "+f"(d[i])::"memory");
}
template <int N>
__device__ __forceinline__ void keep_regs(uint32_t (&d)[N]) {
#pragma unroll
  for (int i = 0; i < N; i++) asm volatile("" : "+r"(d[i])::"memory");
}

__device__ __forceinline__ uint32_t pack_bf16(float lo, float hi) {
  uint32_t d;
  asm("cvt.rn.bf16x2.f32 %0, %1, %2;" : "=r"(d) : "f"(hi), "f"(lo));
  return d;
}
__device__ __forceinline__ float ex2(float x) {
  float y;
  asm("ex2.approx.ftz.f32 %0, %1;" : "=f"(y) : "f"(x));
  return y;
}
__device__ __forceinline__ float rcp_approx(float x) {
  float y;
  asm("rcp.approx.ftz.f32 %0, %1;" : "=f"(y) : "f"(x));
  return y;
}
__device__ __forceinline__ uint4 ldg128_nc(const void* p) {
  uint4 v;
  asm volatile("ld.global.nc.v4.u32 {%0,%1,%2,%3}, [%4];" : "=r"(v.x), "=r"(v.y), "=r"(v.z), "=r"(v.w) : "l"(p));
  return v;
}

__device__ __forceinline__ long long clk64() {
  long long c;
  asm volatile("mov.u64 %0, %clock64;" : "=l"(c)::"memory");
  return c;
}
__device__ __forceinline__ void sched_fence() { while (clk64() < 0) { } }

__device__ __forceinline__ uint64_t make_desc(uint32_t addr, uint32_t lbo, uint32_t sbo, uint32_t mode = 1) {
  return (uint64_t)((addr & 0x3FFFF) >> 4) | ((uint64_t)(lbo >> 4) << 16) | ((uint64_t)(sbo >> 4) << 32) |
         ((uint64_t)mode << 62);
}

template <int OFF, int NN>
__device__ __forceinline__ void wg_m192(float (&d)[NN], uint64_t desc_a, uint64_t desc_b, int scale_d) {
  asm volatile(
      "{\n.reg .pred p;\nsetp.ne.b32 p, %98, 0;\n"
      "wgmma.mma_async.sync.aligned.m64n192k16.f32.bf16.bf16 "
      "{%0,%1,%2,%3,%4,%5,%6,%7,%8,%9,%10,%11,%12,%13,%14,%15,"
      "%16,%17,%18,%19,%20,%21,%22,%23,%24,%25,%26,%27,%28,%29,%30,%31,"
      "%32,%33,%34,%35,%36,%37,%38,%39,%40,%41,%42,%43,%44,%45,%46,%47,"
      "%48,%49,%50,%51,%52,%53,%54,%55,%56,%57,%58,%59,%60,%61,%62,%63,"
      "%64,%65,%66,%67,%68,%69,%70,%71,%72,%73,%74,%75,%76,%77,%78,%79,"
      "%80,%81,%82,%83,%84,%85,%86,%87,%88,%89,%90,%91,%92,%93,%94,%95}, "
      "%96, %97, p, 1, 1, 0, 0;\n}\n"
      : "+f"(d[OFF + 0]), "+f"(d[OFF + 1]), "+f"(d[OFF + 2]), "+f"(d[OFF + 3]), "+f"(d[OFF + 4]), "+f"(d[OFF + 5]),
        "+f"(d[OFF + 6]), "+f"(d[OFF + 7]), "+f"(d[OFF + 8]), "+f"(d[OFF + 9]), "+f"(d[OFF + 10]), "+f"(d[OFF + 11]),
        "+f"(d[OFF + 12]), "+f"(d[OFF + 13]), "+f"(d[OFF + 14]), "+f"(d[OFF + 15]), "+f"(d[OFF + 16]), "+f"(d[OFF + 17]),
        "+f"(d[OFF + 18]), "+f"(d[OFF + 19]), "+f"(d[OFF + 20]), "+f"(d[OFF + 21]), "+f"(d[OFF + 22]), "+f"(d[OFF + 23]),
        "+f"(d[OFF + 24]), "+f"(d[OFF + 25]), "+f"(d[OFF + 26]), "+f"(d[OFF + 27]), "+f"(d[OFF + 28]), "+f"(d[OFF + 29]),
        "+f"(d[OFF + 30]), "+f"(d[OFF + 31]), "+f"(d[OFF + 32]), "+f"(d[OFF + 33]), "+f"(d[OFF + 34]), "+f"(d[OFF + 35]),
        "+f"(d[OFF + 36]), "+f"(d[OFF + 37]), "+f"(d[OFF + 38]), "+f"(d[OFF + 39]), "+f"(d[OFF + 40]), "+f"(d[OFF + 41]),
        "+f"(d[OFF + 42]), "+f"(d[OFF + 43]), "+f"(d[OFF + 44]), "+f"(d[OFF + 45]), "+f"(d[OFF + 46]), "+f"(d[OFF + 47]),
        "+f"(d[OFF + 48]), "+f"(d[OFF + 49]), "+f"(d[OFF + 50]), "+f"(d[OFF + 51]), "+f"(d[OFF + 52]), "+f"(d[OFF + 53]),
        "+f"(d[OFF + 54]), "+f"(d[OFF + 55]), "+f"(d[OFF + 56]), "+f"(d[OFF + 57]), "+f"(d[OFF + 58]), "+f"(d[OFF + 59]),
        "+f"(d[OFF + 60]), "+f"(d[OFF + 61]), "+f"(d[OFF + 62]), "+f"(d[OFF + 63]), "+f"(d[OFF + 64]), "+f"(d[OFF + 65]),
        "+f"(d[OFF + 66]), "+f"(d[OFF + 67]), "+f"(d[OFF + 68]), "+f"(d[OFF + 69]), "+f"(d[OFF + 70]), "+f"(d[OFF + 71]),
        "+f"(d[OFF + 72]), "+f"(d[OFF + 73]), "+f"(d[OFF + 74]), "+f"(d[OFF + 75]), "+f"(d[OFF + 76]), "+f"(d[OFF + 77]),
        "+f"(d[OFF + 78]), "+f"(d[OFF + 79]), "+f"(d[OFF + 80]), "+f"(d[OFF + 81]), "+f"(d[OFF + 82]), "+f"(d[OFF + 83]),
        "+f"(d[OFF + 84]), "+f"(d[OFF + 85]), "+f"(d[OFF + 86]), "+f"(d[OFF + 87]), "+f"(d[OFF + 88]), "+f"(d[OFF + 89]),
        "+f"(d[OFF + 90]), "+f"(d[OFF + 91]), "+f"(d[OFF + 92]), "+f"(d[OFF + 93]), "+f"(d[OFF + 94]), "+f"(d[OFF + 95])
      : "l"(desc_a), "l"(desc_b), "r"(scale_d));
}

template <int OFF, int NN>
__device__ __forceinline__ void wg_m192z(float (&d)[NN], uint64_t desc_a, uint64_t desc_b, int scale_d) {
  asm volatile(
      "{\n.reg .pred p;\nsetp.ne.b32 p, %98, 0;\n"
      "wgmma.mma_async.sync.aligned.m64n192k16.f32.bf16.bf16 "
      "{%0,%1,%2,%3,%4,%5,%6,%7,%8,%9,%10,%11,%12,%13,%14,%15,"
      "%16,%17,%18,%19,%20,%21,%22,%23,%24,%25,%26,%27,%28,%29,%30,%31,"
      "%32,%33,%34,%35,%36,%37,%38,%39,%40,%41,%42,%43,%44,%45,%46,%47,"
      "%48,%49,%50,%51,%52,%53,%54,%55,%56,%57,%58,%59,%60,%61,%62,%63,"
      "%64,%65,%66,%67,%68,%69,%70,%71,%72,%73,%74,%75,%76,%77,%78,%79,"
      "%80,%81,%82,%83,%84,%85,%86,%87,%88,%89,%90,%91,%92,%93,%94,%95}, "
      "%96, %97, p, 1, 1, 0, 0;\n}\n"
      : "=f"(d[OFF + 0]), "=f"(d[OFF + 1]), "=f"(d[OFF + 2]), "=f"(d[OFF + 3]), "=f"(d[OFF + 4]), "=f"(d[OFF + 5]),
        "=f"(d[OFF + 6]), "=f"(d[OFF + 7]), "=f"(d[OFF + 8]), "=f"(d[OFF + 9]), "=f"(d[OFF + 10]), "=f"(d[OFF + 11]),
        "=f"(d[OFF + 12]), "=f"(d[OFF + 13]), "=f"(d[OFF + 14]), "=f"(d[OFF + 15]), "=f"(d[OFF + 16]), "=f"(d[OFF + 17]),
        "=f"(d[OFF + 18]), "=f"(d[OFF + 19]), "=f"(d[OFF + 20]), "=f"(d[OFF + 21]), "=f"(d[OFF + 22]), "=f"(d[OFF + 23]),
        "=f"(d[OFF + 24]), "=f"(d[OFF + 25]), "=f"(d[OFF + 26]), "=f"(d[OFF + 27]), "=f"(d[OFF + 28]), "=f"(d[OFF + 29]),
        "=f"(d[OFF + 30]), "=f"(d[OFF + 31]), "=f"(d[OFF + 32]), "=f"(d[OFF + 33]), "=f"(d[OFF + 34]), "=f"(d[OFF + 35]),
        "=f"(d[OFF + 36]), "=f"(d[OFF + 37]), "=f"(d[OFF + 38]), "=f"(d[OFF + 39]), "=f"(d[OFF + 40]), "=f"(d[OFF + 41]),
        "=f"(d[OFF + 42]), "=f"(d[OFF + 43]), "=f"(d[OFF + 44]), "=f"(d[OFF + 45]), "=f"(d[OFF + 46]), "=f"(d[OFF + 47]),
        "=f"(d[OFF + 48]), "=f"(d[OFF + 49]), "=f"(d[OFF + 50]), "=f"(d[OFF + 51]), "=f"(d[OFF + 52]), "=f"(d[OFF + 53]),
        "=f"(d[OFF + 54]), "=f"(d[OFF + 55]), "=f"(d[OFF + 56]), "=f"(d[OFF + 57]), "=f"(d[OFF + 58]), "=f"(d[OFF + 59]),
        "=f"(d[OFF + 60]), "=f"(d[OFF + 61]), "=f"(d[OFF + 62]), "=f"(d[OFF + 63]), "=f"(d[OFF + 64]), "=f"(d[OFF + 65]),
        "=f"(d[OFF + 66]), "=f"(d[OFF + 67]), "=f"(d[OFF + 68]), "=f"(d[OFF + 69]), "=f"(d[OFF + 70]), "=f"(d[OFF + 71]),
        "=f"(d[OFF + 72]), "=f"(d[OFF + 73]), "=f"(d[OFF + 74]), "=f"(d[OFF + 75]), "=f"(d[OFF + 76]), "=f"(d[OFF + 77]),
        "=f"(d[OFF + 78]), "=f"(d[OFF + 79]), "=f"(d[OFF + 80]), "=f"(d[OFF + 81]), "=f"(d[OFF + 82]), "=f"(d[OFF + 83]),
        "=f"(d[OFF + 84]), "=f"(d[OFF + 85]), "=f"(d[OFF + 86]), "=f"(d[OFF + 87]), "=f"(d[OFF + 88]), "=f"(d[OFF + 89]),
        "=f"(d[OFF + 90]), "=f"(d[OFF + 91]), "=f"(d[OFF + 92]), "=f"(d[OFF + 93]), "=f"(d[OFF + 94]), "=f"(d[OFF + 95])
      : "l"(desc_a), "l"(desc_b), "r"(scale_d));
}

template <int OFF, int NN>
__device__ __forceinline__ void wg_m96t(float (&d)[NN], uint64_t desc_a, uint64_t desc_b, int scale_d) {
  asm volatile(
      "{\n.reg .pred p;\nsetp.ne.b32 p, %50, 0;\n"
      "wgmma.mma_async.sync.aligned.m64n96k16.f32.bf16.bf16 "
      "{%0,%1,%2,%3,%4,%5,%6,%7,%8,%9,%10,%11,%12,%13,%14,%15,"
      "%16,%17,%18,%19,%20,%21,%22,%23,%24,%25,%26,%27,%28,%29,%30,%31,"
      "%32,%33,%34,%35,%36,%37,%38,%39,%40,%41,%42,%43,%44,%45,%46,%47}, "
      "%48, %49, p, 1, 1, 0, 1;\n}\n"
      : "+f"(d[OFF + 0]), "+f"(d[OFF + 1]), "+f"(d[OFF + 2]), "+f"(d[OFF + 3]), "+f"(d[OFF + 4]), "+f"(d[OFF + 5]),
        "+f"(d[OFF + 6]), "+f"(d[OFF + 7]), "+f"(d[OFF + 8]), "+f"(d[OFF + 9]), "+f"(d[OFF + 10]), "+f"(d[OFF + 11]),
        "+f"(d[OFF + 12]), "+f"(d[OFF + 13]), "+f"(d[OFF + 14]), "+f"(d[OFF + 15]), "+f"(d[OFF + 16]), "+f"(d[OFF + 17]),
        "+f"(d[OFF + 18]), "+f"(d[OFF + 19]), "+f"(d[OFF + 20]), "+f"(d[OFF + 21]), "+f"(d[OFF + 22]), "+f"(d[OFF + 23]),
        "+f"(d[OFF + 24]), "+f"(d[OFF + 25]), "+f"(d[OFF + 26]), "+f"(d[OFF + 27]), "+f"(d[OFF + 28]), "+f"(d[OFF + 29]),
        "+f"(d[OFF + 30]), "+f"(d[OFF + 31]), "+f"(d[OFF + 32]), "+f"(d[OFF + 33]), "+f"(d[OFF + 34]), "+f"(d[OFF + 35]),
        "+f"(d[OFF + 36]), "+f"(d[OFF + 37]), "+f"(d[OFF + 38]), "+f"(d[OFF + 39]), "+f"(d[OFF + 40]), "+f"(d[OFF + 41]),
        "+f"(d[OFF + 42]), "+f"(d[OFF + 43]), "+f"(d[OFF + 44]), "+f"(d[OFF + 45]), "+f"(d[OFF + 46]), "+f"(d[OFF + 47])
      : "l"(desc_a), "l"(desc_b), "r"(scale_d));
}

template <int OFF, int NN>
__device__ __forceinline__ void wg_m96tz(float (&d)[NN], uint64_t desc_a, uint64_t desc_b, int scale_d) {
  asm volatile(
      "{\n.reg .pred p;\nsetp.ne.b32 p, %50, 0;\n"
      "wgmma.mma_async.sync.aligned.m64n96k16.f32.bf16.bf16 "
      "{%0,%1,%2,%3,%4,%5,%6,%7,%8,%9,%10,%11,%12,%13,%14,%15,"
      "%16,%17,%18,%19,%20,%21,%22,%23,%24,%25,%26,%27,%28,%29,%30,%31,"
      "%32,%33,%34,%35,%36,%37,%38,%39,%40,%41,%42,%43,%44,%45,%46,%47}, "
      "%48, %49, p, 1, 1, 0, 1;\n}\n"
      : "=f"(d[OFF + 0]), "=f"(d[OFF + 1]), "=f"(d[OFF + 2]), "=f"(d[OFF + 3]), "=f"(d[OFF + 4]), "=f"(d[OFF + 5]),
        "=f"(d[OFF + 6]), "=f"(d[OFF + 7]), "=f"(d[OFF + 8]), "=f"(d[OFF + 9]), "=f"(d[OFF + 10]), "=f"(d[OFF + 11]),
        "=f"(d[OFF + 12]), "=f"(d[OFF + 13]), "=f"(d[OFF + 14]), "=f"(d[OFF + 15]), "=f"(d[OFF + 16]), "=f"(d[OFF + 17]),
        "=f"(d[OFF + 18]), "=f"(d[OFF + 19]), "=f"(d[OFF + 20]), "=f"(d[OFF + 21]), "=f"(d[OFF + 22]), "=f"(d[OFF + 23]),
        "=f"(d[OFF + 24]), "=f"(d[OFF + 25]), "=f"(d[OFF + 26]), "=f"(d[OFF + 27]), "=f"(d[OFF + 28]), "=f"(d[OFF + 29]),
        "=f"(d[OFF + 30]), "=f"(d[OFF + 31]), "=f"(d[OFF + 32]), "=f"(d[OFF + 33]), "=f"(d[OFF + 34]), "=f"(d[OFF + 35]),
        "=f"(d[OFF + 36]), "=f"(d[OFF + 37]), "=f"(d[OFF + 38]), "=f"(d[OFF + 39]), "=f"(d[OFF + 40]), "=f"(d[OFF + 41]),
        "=f"(d[OFF + 42]), "=f"(d[OFF + 43]), "=f"(d[OFF + 44]), "=f"(d[OFF + 45]), "=f"(d[OFF + 46]), "=f"(d[OFF + 47])
      : "l"(desc_a), "l"(desc_b), "r"(scale_d));
}

template <int OFF, int NN>
__device__ __forceinline__ void wg_d96(float (&d)[NN], uint32_t a0, uint32_t a1, uint32_t a2, uint32_t a3,
                                       uint64_t desc_b, int scale_d) {
  asm volatile(
      "{\n.reg .pred p;\nsetp.ne.b32 p, %53, 0;\n"
      "wgmma.mma_async.sync.aligned.m64n96k16.f32.bf16.bf16 "
      "{%0,%1,%2,%3,%4,%5,%6,%7,%8,%9,%10,%11,%12,%13,%14,%15,"
      "%16,%17,%18,%19,%20,%21,%22,%23,%24,%25,%26,%27,%28,%29,%30,%31,"
      "%32,%33,%34,%35,%36,%37,%38,%39,%40,%41,%42,%43,%44,%45,%46,%47}, "
      "{%48,%49,%50,%51}, %52, p, 1, 1, 0;\n}\n"
      : "+f"(d[OFF + 0]), "+f"(d[OFF + 1]), "+f"(d[OFF + 2]), "+f"(d[OFF + 3]), "+f"(d[OFF + 4]), "+f"(d[OFF + 5]),
        "+f"(d[OFF + 6]), "+f"(d[OFF + 7]), "+f"(d[OFF + 8]), "+f"(d[OFF + 9]), "+f"(d[OFF + 10]), "+f"(d[OFF + 11]),
        "+f"(d[OFF + 12]), "+f"(d[OFF + 13]), "+f"(d[OFF + 14]), "+f"(d[OFF + 15]), "+f"(d[OFF + 16]), "+f"(d[OFF + 17]),
        "+f"(d[OFF + 18]), "+f"(d[OFF + 19]), "+f"(d[OFF + 20]), "+f"(d[OFF + 21]), "+f"(d[OFF + 22]), "+f"(d[OFF + 23]),
        "+f"(d[OFF + 24]), "+f"(d[OFF + 25]), "+f"(d[OFF + 26]), "+f"(d[OFF + 27]), "+f"(d[OFF + 28]), "+f"(d[OFF + 29]),
        "+f"(d[OFF + 30]), "+f"(d[OFF + 31]), "+f"(d[OFF + 32]), "+f"(d[OFF + 33]), "+f"(d[OFF + 34]), "+f"(d[OFF + 35]),
        "+f"(d[OFF + 36]), "+f"(d[OFF + 37]), "+f"(d[OFF + 38]), "+f"(d[OFF + 39]), "+f"(d[OFF + 40]), "+f"(d[OFF + 41]),
        "+f"(d[OFF + 42]), "+f"(d[OFF + 43]), "+f"(d[OFF + 44]), "+f"(d[OFF + 45]), "+f"(d[OFF + 46]), "+f"(d[OFF + 47])
      : "r"(a0), "r"(a1), "r"(a2), "r"(a3), "l"(desc_b), "r"(scale_d));
}

template <int OFF, int NN>
__device__ __forceinline__ void wg_d96z(float (&d)[NN], uint32_t a0, uint32_t a1, uint32_t a2, uint32_t a3,
                                       uint64_t desc_b, int scale_d) {
  asm volatile(
      "{\n.reg .pred p;\nsetp.ne.b32 p, %53, 0;\n"
      "wgmma.mma_async.sync.aligned.m64n96k16.f32.bf16.bf16 "
      "{%0,%1,%2,%3,%4,%5,%6,%7,%8,%9,%10,%11,%12,%13,%14,%15,"
      "%16,%17,%18,%19,%20,%21,%22,%23,%24,%25,%26,%27,%28,%29,%30,%31,"
      "%32,%33,%34,%35,%36,%37,%38,%39,%40,%41,%42,%43,%44,%45,%46,%47}, "
      "{%48,%49,%50,%51}, %52, p, 1, 1, 0;\n}\n"
      : "=f"(d[OFF + 0]), "=f"(d[OFF + 1]), "=f"(d[OFF + 2]), "=f"(d[OFF + 3]), "=f"(d[OFF + 4]), "=f"(d[OFF + 5]),
        "=f"(d[OFF + 6]), "=f"(d[OFF + 7]), "=f"(d[OFF + 8]), "=f"(d[OFF + 9]), "=f"(d[OFF + 10]), "=f"(d[OFF + 11]),
        "=f"(d[OFF + 12]), "=f"(d[OFF + 13]), "=f"(d[OFF + 14]), "=f"(d[OFF + 15]), "=f"(d[OFF + 16]), "=f"(d[OFF + 17]),
        "=f"(d[OFF + 18]), "=f"(d[OFF + 19]), "=f"(d[OFF + 20]), "=f"(d[OFF + 21]), "=f"(d[OFF + 22]), "=f"(d[OFF + 23]),
        "=f"(d[OFF + 24]), "=f"(d[OFF + 25]), "=f"(d[OFF + 26]), "=f"(d[OFF + 27]), "=f"(d[OFF + 28]), "=f"(d[OFF + 29]),
        "=f"(d[OFF + 30]), "=f"(d[OFF + 31]), "=f"(d[OFF + 32]), "=f"(d[OFF + 33]), "=f"(d[OFF + 34]), "=f"(d[OFF + 35]),
        "=f"(d[OFF + 36]), "=f"(d[OFF + 37]), "=f"(d[OFF + 38]), "=f"(d[OFF + 39]), "=f"(d[OFF + 40]), "=f"(d[OFF + 41]),
        "=f"(d[OFF + 42]), "=f"(d[OFF + 43]), "=f"(d[OFF + 44]), "=f"(d[OFF + 45]), "=f"(d[OFF + 46]), "=f"(d[OFF + 47])
      : "r"(a0), "r"(a1), "r"(a2), "r"(a3), "l"(desc_b), "r"(scale_d));
}

template <int OFF, int NN>
__device__ __forceinline__ void wg_s104(float (&d)[NN], uint32_t a0, uint32_t a1, uint32_t a2, uint32_t a3,
                                       uint64_t desc_b, int scale_d, uint32_t meta) {
  asm volatile(
      "{\n.reg .pred p;\nsetp.ne.b32 p, %57, 0;\n"
      "wgmma.mma_async.sp.sync.aligned.m64n104k32.f32.bf16.bf16 "
      "{%0,%1,%2,%3,%4,%5,%6,%7,%8,%9,%10,%11,%12,%13,%14,%15,"
      "%16,%17,%18,%19,%20,%21,%22,%23,%24,%25,%26,%27,%28,%29,%30,%31,"
      "%32,%33,%34,%35,%36,%37,%38,%39,%40,%41,%42,%43,%44,%45,%46,%47,"
      "%48,%49,%50,%51}, "
      "{%52,%53,%54,%55}, %56, %58, 0, p, 1, 1, 0;\n}\n"
      : "+f"(d[OFF + 0]), "+f"(d[OFF + 1]), "+f"(d[OFF + 2]), "+f"(d[OFF + 3]), "+f"(d[OFF + 4]), "+f"(d[OFF + 5]),
        "+f"(d[OFF + 6]), "+f"(d[OFF + 7]), "+f"(d[OFF + 8]), "+f"(d[OFF + 9]), "+f"(d[OFF + 10]), "+f"(d[OFF + 11]),
        "+f"(d[OFF + 12]), "+f"(d[OFF + 13]), "+f"(d[OFF + 14]), "+f"(d[OFF + 15]), "+f"(d[OFF + 16]), "+f"(d[OFF + 17]),
        "+f"(d[OFF + 18]), "+f"(d[OFF + 19]), "+f"(d[OFF + 20]), "+f"(d[OFF + 21]), "+f"(d[OFF + 22]), "+f"(d[OFF + 23]),
        "+f"(d[OFF + 24]), "+f"(d[OFF + 25]), "+f"(d[OFF + 26]), "+f"(d[OFF + 27]), "+f"(d[OFF + 28]), "+f"(d[OFF + 29]),
        "+f"(d[OFF + 30]), "+f"(d[OFF + 31]), "+f"(d[OFF + 32]), "+f"(d[OFF + 33]), "+f"(d[OFF + 34]), "+f"(d[OFF + 35]),
        "+f"(d[OFF + 36]), "+f"(d[OFF + 37]), "+f"(d[OFF + 38]), "+f"(d[OFF + 39]), "+f"(d[OFF + 40]), "+f"(d[OFF + 41]),
        "+f"(d[OFF + 42]), "+f"(d[OFF + 43]), "+f"(d[OFF + 44]), "+f"(d[OFF + 45]), "+f"(d[OFF + 46]), "+f"(d[OFF + 47]),
        "+f"(d[OFF + 48]), "+f"(d[OFF + 49]), "+f"(d[OFF + 50]), "+f"(d[OFF + 51])
      : "r"(a0), "r"(a1), "r"(a2), "r"(a3), "l"(desc_b), "r"(scale_d), "r"(meta));
}

template <int OFF, int NN>
__device__ __forceinline__ void wg_s104z(float (&d)[NN], uint32_t a0, uint32_t a1, uint32_t a2, uint32_t a3,
                                       uint64_t desc_b, int scale_d, uint32_t meta) {
  asm volatile(
      "{\n.reg .pred p;\nsetp.ne.b32 p, %57, 0;\n"
      "wgmma.mma_async.sp.sync.aligned.m64n104k32.f32.bf16.bf16 "
      "{%0,%1,%2,%3,%4,%5,%6,%7,%8,%9,%10,%11,%12,%13,%14,%15,"
      "%16,%17,%18,%19,%20,%21,%22,%23,%24,%25,%26,%27,%28,%29,%30,%31,"
      "%32,%33,%34,%35,%36,%37,%38,%39,%40,%41,%42,%43,%44,%45,%46,%47,"
      "%48,%49,%50,%51}, "
      "{%52,%53,%54,%55}, %56, %58, 0, p, 1, 1, 0;\n}\n"
      : "=f"(d[OFF + 0]), "=f"(d[OFF + 1]), "=f"(d[OFF + 2]), "=f"(d[OFF + 3]), "=f"(d[OFF + 4]), "=f"(d[OFF + 5]),
        "=f"(d[OFF + 6]), "=f"(d[OFF + 7]), "=f"(d[OFF + 8]), "=f"(d[OFF + 9]), "=f"(d[OFF + 10]), "=f"(d[OFF + 11]),
        "=f"(d[OFF + 12]), "=f"(d[OFF + 13]), "=f"(d[OFF + 14]), "=f"(d[OFF + 15]), "=f"(d[OFF + 16]), "=f"(d[OFF + 17]),
        "=f"(d[OFF + 18]), "=f"(d[OFF + 19]), "=f"(d[OFF + 20]), "=f"(d[OFF + 21]), "=f"(d[OFF + 22]), "=f"(d[OFF + 23]),
        "=f"(d[OFF + 24]), "=f"(d[OFF + 25]), "=f"(d[OFF + 26]), "=f"(d[OFF + 27]), "=f"(d[OFF + 28]), "=f"(d[OFF + 29]),
        "=f"(d[OFF + 30]), "=f"(d[OFF + 31]), "=f"(d[OFF + 32]), "=f"(d[OFF + 33]), "=f"(d[OFF + 34]), "=f"(d[OFF + 35]),
        "=f"(d[OFF + 36]), "=f"(d[OFF + 37]), "=f"(d[OFF + 38]), "=f"(d[OFF + 39]), "=f"(d[OFF + 40]), "=f"(d[OFF + 41]),
        "=f"(d[OFF + 42]), "=f"(d[OFF + 43]), "=f"(d[OFF + 44]), "=f"(d[OFF + 45]), "=f"(d[OFF + 46]), "=f"(d[OFF + 47]),
        "=f"(d[OFF + 48]), "=f"(d[OFF + 49]), "=f"(d[OFF + 50]), "=f"(d[OFF + 51])
      : "r"(a0), "r"(a1), "r"(a2), "r"(a3), "l"(desc_b), "r"(scale_d), "r"(meta));
}

template <int OFF, int NN>
__device__ __forceinline__ void wg_s48(float (&d)[NN], uint32_t a0, uint32_t a1, uint32_t a2, uint32_t a3,
                                       uint64_t desc_b, int scale_d, uint32_t meta) {
  asm volatile(
      "{\n.reg .pred p;\nsetp.ne.b32 p, %29, 0;\n"
      "wgmma.mma_async.sp.sync.aligned.m64n48k32.f32.bf16.bf16 "
      "{%0,%1,%2,%3,%4,%5,%6,%7,%8,%9,%10,%11,%12,%13,%14,%15,"
      "%16,%17,%18,%19,%20,%21,%22,%23}, "
      "{%24,%25,%26,%27}, %28, %30, 0, p, 1, 1, 0;\n}\n"
      : "+f"(d[OFF + 0]), "+f"(d[OFF + 1]), "+f"(d[OFF + 2]), "+f"(d[OFF + 3]), "+f"(d[OFF + 4]), "+f"(d[OFF + 5]),
        "+f"(d[OFF + 6]), "+f"(d[OFF + 7]), "+f"(d[OFF + 8]), "+f"(d[OFF + 9]), "+f"(d[OFF + 10]), "+f"(d[OFF + 11]),
        "+f"(d[OFF + 12]), "+f"(d[OFF + 13]), "+f"(d[OFF + 14]), "+f"(d[OFF + 15]), "+f"(d[OFF + 16]), "+f"(d[OFF + 17]),
        "+f"(d[OFF + 18]), "+f"(d[OFF + 19]), "+f"(d[OFF + 20]), "+f"(d[OFF + 21]), "+f"(d[OFF + 22]), "+f"(d[OFF + 23])
      : "r"(a0), "r"(a1), "r"(a2), "r"(a3), "l"(desc_b), "r"(scale_d), "r"(meta));
}

template <int OFF, int NN>
__device__ __forceinline__ void wg_s48z(float (&d)[NN], uint32_t a0, uint32_t a1, uint32_t a2, uint32_t a3,
                                       uint64_t desc_b, int scale_d, uint32_t meta) {
  asm volatile(
      "{\n.reg .pred p;\nsetp.ne.b32 p, %29, 0;\n"
      "wgmma.mma_async.sp.sync.aligned.m64n48k32.f32.bf16.bf16 "
      "{%0,%1,%2,%3,%4,%5,%6,%7,%8,%9,%10,%11,%12,%13,%14,%15,"
      "%16,%17,%18,%19,%20,%21,%22,%23}, "
      "{%24,%25,%26,%27}, %28, %30, 0, p, 1, 1, 0;\n}\n"
      : "=f"(d[OFF + 0]), "=f"(d[OFF + 1]), "=f"(d[OFF + 2]), "=f"(d[OFF + 3]), "=f"(d[OFF + 4]), "=f"(d[OFF + 5]),
        "=f"(d[OFF + 6]), "=f"(d[OFF + 7]), "=f"(d[OFF + 8]), "=f"(d[OFF + 9]), "=f"(d[OFF + 10]), "=f"(d[OFF + 11]),
        "=f"(d[OFF + 12]), "=f"(d[OFF + 13]), "=f"(d[OFF + 14]), "=f"(d[OFF + 15]), "=f"(d[OFF + 16]), "=f"(d[OFF + 17]),
        "=f"(d[OFF + 18]), "=f"(d[OFF + 19]), "=f"(d[OFF + 20]), "=f"(d[OFF + 21]), "=f"(d[OFF + 22]), "=f"(d[OFF + 23])
      : "r"(a0), "r"(a1), "r"(a2), "r"(a3), "l"(desc_b), "r"(scale_d), "r"(meta));
}

template <int OFF, int NN>
__device__ __forceinline__ void wg_s56(float (&d)[NN], uint32_t a0, uint32_t a1, uint32_t a2, uint32_t a3,
                                       uint64_t desc_b, int scale_d, uint32_t meta) {
  asm volatile(
      "{\n.reg .pred p;\nsetp.ne.b32 p, %33, 0;\n"
      "wgmma.mma_async.sp.sync.aligned.m64n56k32.f32.bf16.bf16 "
      "{%0,%1,%2,%3,%4,%5,%6,%7,%8,%9,%10,%11,%12,%13,%14,%15,"
      "%16,%17,%18,%19,%20,%21,%22,%23,%24,%25,%26,%27}, "
      "{%28,%29,%30,%31}, %32, %34, 0, p, 1, 1, 0;\n}\n"
      : "+f"(d[OFF + 0]), "+f"(d[OFF + 1]), "+f"(d[OFF + 2]), "+f"(d[OFF + 3]), "+f"(d[OFF + 4]), "+f"(d[OFF + 5]),
        "+f"(d[OFF + 6]), "+f"(d[OFF + 7]), "+f"(d[OFF + 8]), "+f"(d[OFF + 9]), "+f"(d[OFF + 10]), "+f"(d[OFF + 11]),
        "+f"(d[OFF + 12]), "+f"(d[OFF + 13]), "+f"(d[OFF + 14]), "+f"(d[OFF + 15]), "+f"(d[OFF + 16]), "+f"(d[OFF + 17]),
        "+f"(d[OFF + 18]), "+f"(d[OFF + 19]), "+f"(d[OFF + 20]), "+f"(d[OFF + 21]), "+f"(d[OFF + 22]), "+f"(d[OFF + 23]),
        "+f"(d[OFF + 24]), "+f"(d[OFF + 25]), "+f"(d[OFF + 26]), "+f"(d[OFF + 27])
      : "r"(a0), "r"(a1), "r"(a2), "r"(a3), "l"(desc_b), "r"(scale_d), "r"(meta));
}

template <int OFF, int NN>
__device__ __forceinline__ void wg_s56z(float (&d)[NN], uint32_t a0, uint32_t a1, uint32_t a2, uint32_t a3,
                                       uint64_t desc_b, int scale_d, uint32_t meta) {
  asm volatile(
      "{\n.reg .pred p;\nsetp.ne.b32 p, %33, 0;\n"
      "wgmma.mma_async.sp.sync.aligned.m64n56k32.f32.bf16.bf16 "
      "{%0,%1,%2,%3,%4,%5,%6,%7,%8,%9,%10,%11,%12,%13,%14,%15,"
      "%16,%17,%18,%19,%20,%21,%22,%23,%24,%25,%26,%27}, "
      "{%28,%29,%30,%31}, %32, %34, 0, p, 1, 1, 0;\n}\n"
      : "=f"(d[OFF + 0]), "=f"(d[OFF + 1]), "=f"(d[OFF + 2]), "=f"(d[OFF + 3]), "=f"(d[OFF + 4]), "=f"(d[OFF + 5]),
        "=f"(d[OFF + 6]), "=f"(d[OFF + 7]), "=f"(d[OFF + 8]), "=f"(d[OFF + 9]), "=f"(d[OFF + 10]), "=f"(d[OFF + 11]),
        "=f"(d[OFF + 12]), "=f"(d[OFF + 13]), "=f"(d[OFF + 14]), "=f"(d[OFF + 15]), "=f"(d[OFF + 16]), "=f"(d[OFF + 17]),
        "=f"(d[OFF + 18]), "=f"(d[OFF + 19]), "=f"(d[OFF + 20]), "=f"(d[OFF + 21]), "=f"(d[OFF + 22]), "=f"(d[OFF + 23]),
        "=f"(d[OFF + 24]), "=f"(d[OFF + 25]), "=f"(d[OFF + 26]), "=f"(d[OFF + 27])
      : "r"(a0), "r"(a1), "r"(a2), "r"(a3), "l"(desc_b), "r"(scale_d), "r"(meta));
}

template <int OFF, int NN>
__device__ __forceinline__ void wg_s64t(float (&d)[NN], uint32_t a0, uint32_t a1, uint32_t a2, uint32_t a3,
                                       uint64_t desc_b, int scale_d, uint32_t meta) {
  asm volatile(
      "{\n.reg .pred p;\nsetp.ne.b32 p, %37, 0;\n"
      "wgmma.mma_async.sp.sync.aligned.m64n64k32.f32.bf16.bf16 "
      "{%0,%1,%2,%3,%4,%5,%6,%7,%8,%9,%10,%11,%12,%13,%14,%15,"
      "%16,%17,%18,%19,%20,%21,%22,%23,%24,%25,%26,%27,%28,%29,%30,%31}, "
      "{%32,%33,%34,%35}, %36, %38, 0, p, 1, 1, 1;\n}\n"
      : "+f"(d[OFF + 0]), "+f"(d[OFF + 1]), "+f"(d[OFF + 2]), "+f"(d[OFF + 3]), "+f"(d[OFF + 4]), "+f"(d[OFF + 5]),
        "+f"(d[OFF + 6]), "+f"(d[OFF + 7]), "+f"(d[OFF + 8]), "+f"(d[OFF + 9]), "+f"(d[OFF + 10]), "+f"(d[OFF + 11]),
        "+f"(d[OFF + 12]), "+f"(d[OFF + 13]), "+f"(d[OFF + 14]), "+f"(d[OFF + 15]), "+f"(d[OFF + 16]), "+f"(d[OFF + 17]),
        "+f"(d[OFF + 18]), "+f"(d[OFF + 19]), "+f"(d[OFF + 20]), "+f"(d[OFF + 21]), "+f"(d[OFF + 22]), "+f"(d[OFF + 23]),
        "+f"(d[OFF + 24]), "+f"(d[OFF + 25]), "+f"(d[OFF + 26]), "+f"(d[OFF + 27]), "+f"(d[OFF + 28]), "+f"(d[OFF + 29]),
        "+f"(d[OFF + 30]), "+f"(d[OFF + 31])
      : "r"(a0), "r"(a1), "r"(a2), "r"(a3), "l"(desc_b), "r"(scale_d), "r"(meta));
}

template <int OFF, int NN>
__device__ __forceinline__ void wg_s64t1(float (&d)[NN], uint32_t a0, uint32_t a1, uint32_t a2, uint32_t a3,
                                       uint64_t desc_b, int scale_d, uint32_t meta) {
  asm volatile(
      "{\n.reg .pred p;\nsetp.ne.b32 p, %37, 0;\n"
      "wgmma.mma_async.sp.sync.aligned.m64n64k32.f32.bf16.bf16 "
      "{%0,%1,%2,%3,%4,%5,%6,%7,%8,%9,%10,%11,%12,%13,%14,%15,"
      "%16,%17,%18,%19,%20,%21,%22,%23,%24,%25,%26,%27,%28,%29,%30,%31}, "
      "{%32,%33,%34,%35}, %36, %38, 1, p, 1, 1, 1;\n}\n"
      : "+f"(d[OFF + 0]), "+f"(d[OFF + 1]), "+f"(d[OFF + 2]), "+f"(d[OFF + 3]), "+f"(d[OFF + 4]), "+f"(d[OFF + 5]),
        "+f"(d[OFF + 6]), "+f"(d[OFF + 7]), "+f"(d[OFF + 8]), "+f"(d[OFF + 9]), "+f"(d[OFF + 10]), "+f"(d[OFF + 11]),
        "+f"(d[OFF + 12]), "+f"(d[OFF + 13]), "+f"(d[OFF + 14]), "+f"(d[OFF + 15]), "+f"(d[OFF + 16]), "+f"(d[OFF + 17]),
        "+f"(d[OFF + 18]), "+f"(d[OFF + 19]), "+f"(d[OFF + 20]), "+f"(d[OFF + 21]), "+f"(d[OFF + 22]), "+f"(d[OFF + 23]),
        "+f"(d[OFF + 24]), "+f"(d[OFF + 25]), "+f"(d[OFF + 26]), "+f"(d[OFF + 27]), "+f"(d[OFF + 28]), "+f"(d[OFF + 29]),
        "+f"(d[OFF + 30]), "+f"(d[OFF + 31])
      : "r"(a0), "r"(a1), "r"(a2), "r"(a3), "l"(desc_b), "r"(scale_d), "r"(meta));
}

template <int OFF, int NN>
__device__ __forceinline__ void wg_s64tz(float (&d)[NN], uint32_t a0, uint32_t a1, uint32_t a2, uint32_t a3,
                                       uint64_t desc_b, int scale_d, uint32_t meta) {
  asm volatile(
      "{\n.reg .pred p;\nsetp.ne.b32 p, %37, 0;\n"
      "wgmma.mma_async.sp.sync.aligned.m64n64k32.f32.bf16.bf16 "
      "{%0,%1,%2,%3,%4,%5,%6,%7,%8,%9,%10,%11,%12,%13,%14,%15,"
      "%16,%17,%18,%19,%20,%21,%22,%23,%24,%25,%26,%27,%28,%29,%30,%31}, "
      "{%32,%33,%34,%35}, %36, %38, 0, p, 1, 1, 1;\n}\n"
      : "=f"(d[OFF + 0]), "=f"(d[OFF + 1]), "=f"(d[OFF + 2]), "=f"(d[OFF + 3]), "=f"(d[OFF + 4]), "=f"(d[OFF + 5]),
        "=f"(d[OFF + 6]), "=f"(d[OFF + 7]), "=f"(d[OFF + 8]), "=f"(d[OFF + 9]), "=f"(d[OFF + 10]), "=f"(d[OFF + 11]),
        "=f"(d[OFF + 12]), "=f"(d[OFF + 13]), "=f"(d[OFF + 14]), "=f"(d[OFF + 15]), "=f"(d[OFF + 16]), "=f"(d[OFF + 17]),
        "=f"(d[OFF + 18]), "=f"(d[OFF + 19]), "=f"(d[OFF + 20]), "=f"(d[OFF + 21]), "=f"(d[OFF + 22]), "=f"(d[OFF + 23]),
        "=f"(d[OFF + 24]), "=f"(d[OFF + 25]), "=f"(d[OFF + 26]), "=f"(d[OFF + 27]), "=f"(d[OFF + 28]), "=f"(d[OFF + 29]),
        "=f"(d[OFF + 30]), "=f"(d[OFF + 31])
      : "r"(a0), "r"(a1), "r"(a2), "r"(a3), "l"(desc_b), "r"(scale_d), "r"(meta));
}

__device__ __forceinline__ int g2_inv(int ch) { return 32 * (ch >> 5) + 8 * ((ch >> 1) & 3) + 2 * ((ch >> 3) & 3) + (ch & 1); }
__host__ __device__ __forceinline__ uint32_t wimg_off(int n, int k) {
  return (uint32_t)(k >> 6) * kWChunk + (uint32_t)n * 128 + (uint32_t)((((k & 63) >> 3) ^ (n & 7)) << 4) + (k & 7) * 2;
}
__host__ __device__ constexpr int w2piece(int h, int c) { return c == 2 ? 2 + h : 4 * h + c; }
__device__ __forceinline__ uint32_t w2img_off(int n, int k) { return wimg_off(n % 96, k & 63) + w2piece(n >= 96, k >> 6) * (kWChunk / 2); }
__device__ __forceinline__ int qpix(int par, int t) {
  const int a = 2 * t + 13 * par - 6, b = t + 112 * par;
  return par ? min(a, b) : max(a, b);
}
__device__ __forceinline__ int woff(int par, int i, int r) {
  const int a = 99 * par + 6 - 8 * i;
  return par ? min(r, a) : max(r, a);
}

__device__ __forceinline__ void mma16816(float (&c)[4], uint32_t a0, uint32_t a1, uint32_t a2, uint32_t a3, uint32_t b0,
                                         uint32_t b1) {
  asm volatile(
      "mma.sync.aligned.m16n8k16.row.col.f32.bf16.bf16.f32 {%0,%1,%2,%3}, {%4,%5,%6,%7}, {%8,%9}, {%0,%1,%2,%3};"
      : "+f"(c[0]), "+f"(c[1]), "+f"(c[2]), "+f"(c[3])
      : "r"(a0), "r"(a1), "r"(a2), "r"(a3), "r"(b0), "r"(b1));
}

__device__ __forceinline__ void fold_w1(const int u, const __nv_bfloat16* __restrict__ wqkv, uint8_t* wimg) {
  const int g = (threadIdx.x >> 2) & 7, l = threadIdx.x & 3;
  const int m0 = (u / 12) * 16, s = u % 12;
  uint4 A[12], B[12];
  const __nv_bfloat16* arow = wqkv + (m0 + 4 * (g >> 1) + (g & 1)) * 576 + 192 + 8 * l;
  const __nv_bfloat16* brow = wqkv + (16 * s + 4 * (g >> 1) + (g & 1)) * 576 + 8 * l;
#pragma unroll
  for (int i = 0; i < 12; i++) {
    A[i] = ldg128_nc(arow + (i & 1) * 2 * 576 + 32 * (i >> 1));
    B[i] = ldg128_nc(brow + (i & 1) * 2 * 576 + 32 * (i >> 1));
  }
  sched_fence();
  uint8_t* dst = wimg + wimg_off(m0 + g, 16 * s + 4 * l);
  float acc[4][4];
#pragma unroll
  for (int j = 0; j < 16; j++) acc[j >> 2][j & 3] = 0.f;
#pragma unroll
  for (int i = 0; i < 6; i++) {
    const uint4 &a0 = A[2 * i], &a1 = A[2 * i + 1];
#pragma unroll
    for (int nb = 0; nb < 2; nb++) {
      mma16816(acc[2 * nb], a0.x, a1.x, a0.y, a1.y, B[2 * i + nb].x, B[2 * i + nb].y);
      mma16816(acc[2 * nb + 1], a0.z, a1.z, a0.w, a1.w, B[2 * i + nb].z, B[2 * i + nb].w);
    }
  }
#pragma unroll
  for (int j = 0; j < 2; j++) {
    const uint2 v = make_uint2(pack_bf16((acc[0][2 * j] + acc[1][2 * j]) * kAlpha, (acc[0][2 * j + 1] + acc[1][2 * j + 1]) * kAlpha),
                               pack_bf16((acc[2][2 * j] + acc[3][2 * j]) * kAlpha, (acc[2][2 * j + 1] + acc[3][2 * j + 1]) * kAlpha));
    asm volatile("st.relaxed.gpu.global.v2.u32 [%0], {%1,%2};" ::"l"(dst + j * 1024), "r"(v.x), "r"(v.y) : "memory");
  }
}
__device__ __forceinline__ void fold_w2(const int u, const __nv_bfloat16* __restrict__ wqkv, const __nv_bfloat16* __restrict__ wo,
                                        uint8_t* wimg) {
  const int g = (threadIdx.x >> 2) & 7, l = threadIdx.x & 3;
  const int m0 = (u / 12) * 32, n0 = (u % 12) * 16;
  uint4 S[12];
  uint32_t L[96];
  const __nv_bfloat16* brow = wqkv + (n0 + 4 * (g >> 1) + (g & 1)) * 576 + 384 + 8 * l;
#pragma unroll
  for (int i = 0; i < 12; i++) S[i] = ldg128_nc(brow + (i & 1) * 2 * 576 + 32 * (i >> 1));
  const __nv_bfloat16* acol = wo + (8 * l) * 192 + m0 + 4 * g;
#pragma unroll
  for (int c = 0; c < 48; c++)
    asm volatile("ld.global.nc.v2.u32 {%0,%1}, [%2];" : "=r"(L[2 * c]), "=r"(L[2 * c + 1]) : "l"(acol + (32 * (c >> 3) + (c & 7)) * 192));
  const uint32_t off = w2_offset();
  sched_fence();
  uint8_t* img = wimg + off;
  float acc[4][4];
#pragma unroll
  for (int j = 0; j < 16; j++) acc[j >> 2][j & 3] = 0.f;
#pragma unroll
  for (int i = 0; i < 6; i++) {
#pragma unroll
    for (int h = 0; h < 2; h++) {
      const uint4 &s0 = S[2 * i], &s1 = S[2 * i + 1];
#pragma unroll
      for (int mt = 0; mt < 2; mt++) {
        const uint32_t* a = L + 16 * i + 8 * h + mt;
        const uint32_t a0 = __byte_perm(a[0], a[2], 0x5410), a1 = __byte_perm(a[0], a[2], 0x7632);
        const uint32_t a2 = __byte_perm(a[4], a[6], 0x5410), a3 = __byte_perm(a[4], a[6], 0x7632);
        mma16816(acc[2 * mt], a0, a1, a2, a3, h ? s0.z : s0.x, h ? s0.w : s0.y);
        mma16816(acc[2 * mt + 1], a0, a1, a2, a3, h ? s1.z : s1.x, h ? s1.w : s1.y);
      }
    }
  }
#pragma unroll
  for (int j = 0; j < 4; j++) {
    const float(&c0)[4] = acc[j & 2];
    const float(&c1)[4] = acc[(j & 2) + 1];
    asm volatile("st.relaxed.gpu.global.v2.u32 [%0], {%1,%2};" ::"l"(img + w2img_off(g2_inv(m0 + 4 * g + j), n0 + 4 * l)),
                 "r"(pack_bf16(c0[2 * (j & 1)], c0[2 * (j & 1) + 1])), "r"(pack_bf16(c1[2 * (j & 1)], c1[2 * (j & 1) + 1])) : "memory");
  }
}

__global__ void __launch_bounds__(256) fold_kernel(const __nv_bfloat16* __restrict__ wqkv,
                                                   const __nv_bfloat16* __restrict__ wo, uint8_t* wimg) {
  const int u = blockIdx.x * 8 + (threadIdx.x >> 5);
  if (u < 144) fold_w1(u, wqkv, wimg);
  else fold_w2(u - 144, wqkv, wo, wimg);
}

struct TileCoord { int pr, pc, I, J, up, kind; };
struct TileTable { uint16_t e[kCtas * 6], g[5][8][2], b[5][2][4]; };
inline void make_tiles(TileTable& tt) {
  for (int tile = 0; tile < kCtas * 6; tile++) {
    const int b = tile / 6, k = tile - 6 * b;
    const int p = b < 128 ? (tile - 672) >> 1 : b - 80;
    const int strip = b < 112 ? b >> 1 : b >= 128 && k >= 2 ? (b & 1) * 27 + (b & 2) * 14 : p + (p < 26 ? 1 : 3);
    const int pr = strip >= 28, J = (strip - pr * 28) >> 1, pc = strip & 1, up = b < 112 ? b & 1 : pr;
    const int first = b < 112 ? 8 - 2 * pr - up : 13 * pr, step = b < 112 ? k : k & 1;
    const int I = up ? first - step : first + step;
    const int kind = I == 13 * pr ? 3 + pr : J == 13 * pc ? 1 + pc : 0;
    tt.e[tile] = (uint16_t)(I | J << 4 | pr << 8 | pc << 9 | up << 10 | kind << 11);
  }
  for (int kind = 0; kind < 5; kind++) {
    const bool col = kind == 1 || kind == 2;
    auto off = [kind](int t) { return kind == 0 ? 2 * t : kind & 1 ? t + (t == 7) : t + (t > 0); };
    for (int j = 0; j < 8; j++) {
      const int w = j >> 1, h = j & 1;
      tt.g[kind][j][0] = (uint16_t)(col ? 3 * off(w + 4 * h) : 3 * (kW * off(2 * w) + 8 * h));
      tt.g[kind][j][1] = (uint16_t)(128 * (col ? 5 : 5 + off(2 * w + 1) - off(2 * w)));
    }
    for (int i = 0; i < 2; i++) {
      const int w = kind == 0 ? 0 : kind & 1 ? 3 * i : 1 - i;
      tt.b[kind][i][0] = tt.g[kind][2 * w][0];
      tt.b[kind][i][1] = (uint16_t)(128 * (kind == 0 ? 0 : (col ? 3 : 1) + i));
      tt.b[kind][i][2] = (uint16_t)(2048 * w);
      tt.b[kind][i][3] = 0;
    }
  }
}
__device__ __forceinline__ int num_tiles() { return blockIdx.x < 128 ? 6 : 4; }
__device__ __forceinline__ TileCoord decode_tile(const TileTable& tt, int tile) {
  const uint32_t e = tt.e[tile];
  return TileCoord{(int)(e >> 8) & 1, (int)(e >> 9) & 1, (int)e & 15, (int)(e >> 4) & 15, (int)(e >> 10) & 1, (int)(e >> 11)};
}
__device__ __forceinline__ int halo_r0(const TileCoord& t) { return 8 * t.I + 6 * t.pr - 6; }
__device__ __forceinline__ int halo_c0(const TileCoord& t) { return min(max(8 * t.J + 6 * t.pc - 6, -3), 102); }

__device__ __forceinline__ uint32_t bar_full(uint32_t bars, int wg, int c) { return bars + (wg * 3 + c) * 8; }
__device__ __forceinline__ uint32_t bar_w1c(uint32_t bars, int c) { return bars + (6 + c) * 8; }
__device__ __forceinline__ uint32_t bar_w2(uint32_t bars) { return bars + 9 * 8; }
__device__ __forceinline__ uint32_t bar_x(uint32_t bars, int j, int c) { return bars + (j == 0 ? 10 : c ? 17 + c : 11) * 8; }
__device__ __forceinline__ uint32_t bar_w1q(uint32_t bars) { return bars + 12 * 8; }
__device__ __forceinline__ uint32_t bar_xf(uint32_t bars) { return bars + 13 * 8; }
__device__ __forceinline__ uint32_t bar_w2m(uint32_t bars) { return bars + 14 * 8; }
__device__ __forceinline__ uint32_t bar_redo(uint32_t bars) { return bars + 15 * 8; }
__device__ __forceinline__ uint32_t bar_wok(uint32_t bars) { return bars + 16 * 8; }
__device__ __forceinline__ uint32_t bar_go(uint32_t bars) { return bars + 17 * 8; }
__device__ __forceinline__ uint32_t bar_raw(uint32_t bars, int j = 0) { return bars + (21 + j) * 8; }
__device__ __forceinline__ uint32_t bar_w2a(uint32_t bars) { return bars + 20 * 8; }
constexpr int kNumBars = 22;

__device__ __forceinline__ uint64_t wdesc(uint64_t d0, int s) { return d0 + (((s >> 2) * kWChunk + (s & 3) * 32) >> 4); }

__device__ __forceinline__ uint32_t x_chunk(int k, int c) { return kXOff + (k == 0 ? kWChunk : 0) + (k & 1 ? 2 - c : c) * 8192; }
__device__ __forceinline__ uint32_t out_slot(int k, int nt) { return k + 1 < nt ? kW2Off + (~k & 1) * 2 * kWChunk : kW1Off + kWChunk; }
template <int I0, int I1>
__device__ __forceinline__ void store_rows(bool on, __nv_bfloat16* pA, __nv_bfloat16* pB, const uint32_t (&a)[24], const uint32_t (&b)[24]) {
#pragma unroll
  for (int i = 2 * I0; i < 2 * I1; i++) {
    const uint32_t* v = (i & 1 ? b : a) + 4 * (i >> 1);
    asm volatile("{\n.reg .pred p;\nsetp.ne.u32 p, %5, 0;\n@p st.global.v4.u32 [%0], {%1,%2,%3,%4};\n}\n" ::"l"((i & 1 ? pB : pA) + 32 * (i >> 1)),
                 "r"(v[0]), "r"(v[1]), "r"(v[2]), "r"(v[3]), "r"((uint32_t)on) : "memory");
  }
}
template <int I0, int I1>
__device__ __forceinline__ void stage_out(const uint32_t (&ad)[4], const uint32_t (&a)[24], const uint32_t (&b)[24]) {
#pragma unroll
  for (int i = I0; i < I1; i++) {
    const uint32_t* v = (i < 6 ? a : b) + 4 * (i % 6);
    asm volatile("st.shared.v4.u32 [%0], {%1,%2,%3,%4};" ::"r"(ad[i % 6 / 3 * 2 + (i % 3 == 1)] + (i % 3 == 2) * 1024 + (i / 6) * 12288),
                 "r"(v[0]), "r"(v[1]), "r"(v[2]), "r"(v[3]) : "memory");
  }
}
__device__ __forceinline__ uint32_t now_ns() {
  uint32_t t;
  asm volatile("mov.u32 %0, %globaltimer_lo;" : "=r"(t)::"memory");
  return t;
}
__device__ __forceinline__ void wait_clock(uint32_t t_start, uint32_t t) {
  while (now_ns() - t_start < t) { }
}
#define NAT_PRED(f, m) ".reg .pred p;\n.reg .b32 t;\nand.b32 t, " f ", " m ";\nsetp.ne.u32 p, t, 0;\n"
constexpr uint32_t kHiV = 1, kHiU = 8, kColB = 0x20, kInV = 0x100, kInU = 0x1000, kColA = 0x10000;
template <uint32_t M>
__device__ __forceinline__ float pick(const float* a, const float* b, uint32_t f) {
  float d;
  asm("{\n" NAT_PRED("%5", "%6") "add.f32 %0, %1, %2;\n@p add.f32 %0, %3, %4;\n}\n"
      : "=&f"(d) : "f"(a[0]), "f"(a[2]), "f"(b[0]), "f"(b[2]), "r"(f), "n"(M));
  return d;
}
template <uint32_t M>
__device__ __forceinline__ float sel(float a, float b, uint32_t f) {
  float d;
  asm("{\n" NAT_PRED("%3", "%4") "selp.f32 %0, %1, %2, p;\n}\n" : "=f"(d) : "f"(a), "f"(b), "r"(f), "n"(M));
  return d;
}
template <uint32_t M>
__device__ __forceinline__ void max_if(float& m, float v, uint32_t f) {
  asm("{\n" NAT_PRED("%2", "%3") "@p max.f32 %0, %0, %1;\n}\n" : "+f"(m) : "f"(v), "r"(f), "n"(M));
}
template <uint32_t M>
__device__ __forceinline__ void add_if(float& m, float v, uint32_t f) {
  asm("{\n" NAT_PRED("%2", "%3") "@p add.f32 %0, %0, %1;\n}\n" : "+f"(m) : "f"(v), "r"(f), "n"(M));
}
__device__ __forceinline__ void pick_v(const float* a, float* v, uint32_t f) {
  v[0] = pick<kHiV>(a, a + 16, f), v[1] = pick<kHiV>(a + 1, a + 17, f);
  v[2] = pick<kHiV * 2>(a + 4, a + 20, f), v[3] = pick<kHiV * 2>(a + 5, a + 21, f);
  v[4] = pick<kHiV * 4>(a + 8, a + 24, f), v[5] = pick<kHiV * 4>(a + 9, a + 25, f);
  v[6] = a[12] + a[14], v[7] = a[13] + a[15];
}
__device__ __forceinline__ void pick_u(const float* a, float* v, uint32_t f) {
#pragma unroll
  for (int c = 0; c < 3; c++) v[2 * c] = pick<kHiU>(a + 4 * c, a + 4 * c + 12, f), v[2 * c + 1] = pick<kHiU * 2>(a + 4 * c + 1, a + 4 * c + 13, f);
}
__device__ __forceinline__ uint32_t sign_bytes(uint32_t v, uint32_t sel) {
  uint32_t d;
  asm("prmt.b32 %0, %1, %1, %2;" : "=r"(d) : "r"(v), "r"(sel));
  return d;
}
__device__ __forceinline__ float own_max(const float (&v)[14], uint32_t f) {
  float m = sel<kInV>(fmaxf(v[0], v[1]), -INFINITY, f), m2 = sel<kInV * 2>(fmaxf(v[2], v[3]), -INFINITY, f);
  max_if<kInV * 4>(m, fmaxf(v[4], v[5]), f);
  max_if<kInV * 8>(m2, fmaxf(v[6], v[7]), f);
  max_if<kInU>(m, fmaxf(fmaxf(v[8], v[10]), v[12]), f);
  max_if<kInU * 2>(m2, fmaxf(fmaxf(v[9], v[11]), v[13]), f);
  return fmaxf(m, m2);
}
__device__ __forceinline__ float quad_max(float m) {
  const float a = __shfl_xor_sync(0xffffffffu, m, 1), b = __shfl_xor_sync(0xffffffffu, m, 2), c = __shfl_xor_sync(0xffffffffu, m, 3);
  return fmaxf(fmaxf(m, a), fmaxf(b, c));
}
__device__ __forceinline__ float row_rcp(const float (&v)[14], uint32_t f) {
  float s = sel<kInV>(v[0] + v[1], 0.f, f), s2 = sel<kInV * 2>(v[2] + v[3], 0.f, f);
  add_if<kInV * 4>(s, v[4] + v[5], f);
  add_if<kInV * 8>(s2, v[6] + v[7], f);
  add_if<kInU>(s, v[8] + v[10] + v[12], f);
  add_if<kInU * 2>(s2, v[9] + v[11] + v[13], f);
  s += s2;
  const float a = __shfl_xor_sync(0xffffffffu, s, 1), b = __shfl_xor_sync(0xffffffffu, s, 2), c = __shfl_xor_sync(0xffffffffu, s, 3);
  return rcp_approx((s + a) + (b + c));
}
__device__ __forceinline__ void route(const float (&v)[14], float s, const uint32_t (&rt)[9], uint32_t (&p)[14]) {
#pragma unroll
  for (int i = 0; i < 7; i++) {
    const uint32_t u = pack_bf16(v[2 * i] * s, v[2 * i + 1] * s);
    if (i < 4) p[i] = u & rt[i];
    if (i < 3) p[i + 4] = u & rt[i + 4];
    if (i >= 4) {
      p[i + 3] = u & rt[7];
      p[i + 6] = u & rt[8];
    }
  }
}

template <int C, int T0 = 0, int T1 = 7>
__device__ __forceinline__ void pv_chunk(float (&z)[32], const uint32_t (&pa)[14], const uint32_t (&pb)[14],
                                         const uint32_t (&meta)[4], uint64_t dV) {
#pragma unroll
  for (int t = T0; t < T1; t++) {
    if (t & 1)
      wg_s64t1<0, 32>(z, pa[2 * t], pb[2 * t], pa[2 * t + 1], pb[2 * t + 1], dV + ((2 * C * kChunkBytes + t * 2048) >> 4), 1,
                      meta[t >> 1]);
    else if (t > 0)
      wg_s64t<0, 32>(z, pa[2 * t], pb[2 * t], pa[2 * t + 1], pb[2 * t + 1], dV + ((2 * C * kChunkBytes + t * 2048) >> 4), 1,
                     meta[t >> 1]);
    else
      wg_s64tz<0, 32>(z, pa[0], pb[0], pa[1], pb[1], dV + ((2 * C * kChunkBytes) >> 4), 0, meta[0]);
  }
}
template <int C>
__device__ __forceinline__ void pack_z(const float (&z)[32], uint32_t (&za)[24], uint32_t (&zb)[24]) {
#pragma unroll
  for (int j = 0; j < 8; j++) {
    za[8 * C + j] = pack_bf16(z[4 * j], z[4 * j + 1]);
    zb[8 * C + j] = pack_bf16(z[4 * j + 2], z[4 * j + 3]);
  }
}

template <int H>
__device__ __forceinline__ void pack_out(const float (&ac)[48], uint32_t (&oa)[24], uint32_t (&ob)[24]) {
#pragma unroll
  for (int j = 0; j < 12; j++) {
    oa[12 * H + j] = pack_bf16(ac[4 * j], ac[4 * j + 1]);
    ob[12 * H + j] = pack_bf16(ac[4 * j + 2], ac[4 * j + 3]);
  }
}
struct Maps { CUtensorMap v6, v2, v14, u8, px[8], wv, wo; };
__device__ __forceinline__ void tma_prefetch_5d(const CUtensorMap* map, int c0, int c1, int c2, int c3, int c4) {
  asm volatile("cp.async.bulk.prefetch.tensor.5d.L2.global.tile [%0, {%1, %2, %3, %4, %5}];" ::"l"((uint64_t)map), "r"(c0), "r"(c1),
               "r"(c2), "r"(c3), "r"(c4) : "memory");
}
__device__ __forceinline__ int first_line(const TileCoord tc) { return 3 * (qpix(tc.pr, 8 * tc.I) * kW + qpix(tc.pc, 8 * tc.J)); }
__device__ __forceinline__ void load_px(const Maps& tm, const TileTable& tt, uint32_t dst, uint32_t bar, int line, int kind) {
#pragma unroll
  for (int i = 0; i < 2; i++) {
    if (i == 0 || kind != 0) {
      const CUtensorMap* map = (const CUtensorMap*)((const char*)tm.px + tt.b[kind][i][1]);
      if (bar) tma_load_5d(dst + tt.b[kind][i][2], map, bar, 0, 0, 0, 0, line + tt.b[kind][i][0]);
      else tma_prefetch_5d(map, 0, 0, 0, 0, line + tt.b[kind][i][0]);
    }
  }
}
__device__ __forceinline__ void store_px(const Maps& tm, const TileTable& tt, uint32_t buf, int line, int kind) {
#pragma unroll
  for (int i = 0; i < 8; i++) {
    const int j = 2 * (i & 3) + (i >> 2);
    asm volatile("cp.async.bulk.tensor.5d.global.shared::cta.tile.bulk_group [%0, {%2, %2, %2, %2, %3}], [%1];" ::"l"(
                     (uint64_t)tm.px + tt.g[kind][j][1]), "r"(buf + i * 3072), "r"(0), "r"(line + tt.g[kind][j][0]) : "memory");
  }
  asm volatile("cp.async.bulk.commit_group;" ::: "memory");
}
__device__ __noinline__ bool refetch(uint32_t base, const uint8_t* src, bool gap) {
  constexpr uint32_t bars = 1024 + kBarOff, cnt = bars + 192;
#pragma unroll 1
  for (uint32_t o = 0; o < kWBytes && !gap; o += 2048) {
    uint32_t mx = 0;
#pragma unroll
    for (int i = 0; i < 4; i++) {
      uint4 v;
      asm volatile("ld.shared.v4.u32 {%0,%1,%2,%3}, [%4];" : "=r"(v.x), "=r"(v.y), "=r"(v.z), "=r"(v.w)
                   : "r"(base + o + i * 512 + (threadIdx.x & 31) * 16));
      mx = __vimax3_u32(__vimax3_u32(mx, v.x, v.y), v.z, v.w);
    }
    gap = __any_sync(0xffffffffu, mx == kEmpty);
  }
  uint32_t n;
  asm volatile("ld.shared.u32 %0, [%1];" : "=r"(n) : "r"(cnt) : "memory");
  if (!gap || __any_sync(0xffffffffu, n > (1u << 12))) return false;
  asm volatile("bar.sync 15, 128;" ::: "memory");
  if (threadIdx.x == 0) {
    asm volatile("st.shared.u32 [%0], %1;" ::"r"(cnt), "r"(n + 1) : "memory");
    mbar_arrive_expect_tx(bar_redo(bars), kWBytes);
    bulk_load(base, src, kWBytes, bar_redo(bars));
  }
  __syncwarp();
  mbar_wait(bar_redo(bars), n & 1);
  return true;
}
__device__ __forceinline__ bool any_nan(const uint32_t (&a)[24]) {
  uint32_t m[2] = {a[0], a[1]}, nan;
#pragma unroll
  for (int i = 2; i < 24; i++) asm("max.NaN.bf16x2 %0, %0, %1;" : "+r"(m[i & 1]) : "r"(a[i]));
  asm("max.NaN.bf16x2 %0, %0, %1;" : "+r"(m[0]) : "r"(m[1]));
  asm volatile("{\n.reg .pred p;\nsetp.ne.u32 p, %1, 0;\nbar.red.or.pred p, 15, 128, p;\nselp.u32 %0, 1, 0, p;\n}\n"
               : "=r"(nan) : "r"(((m[0] & 0x7FFF7FFFu) + 0x007F007Fu) & 0x80008000u) : "memory");
  return __any_sync(0xffffffffu, nan);
}
template <int S0, int S1, int Z>
__device__ __forceinline__ void g2_steps(float (&ac)[48], const uint32_t (&za)[24], const uint32_t (&zb)[24], uint64_t d) {
#pragma unroll
  for (int s = S0; s < S1; s++) {
    const uint64_t ds = d + (((s >> 2 & 1) * (kWChunk / 2) + (s & 3) * 32) >> 4);
    if (s == Z) wg_d96z<0, 48>(ac, za[2 * s], zb[2 * s], za[2 * s + 1], zb[2 * s + 1], ds, 0);
    else wg_d96<0, 48>(ac, za[2 * s], zb[2 * s], za[2 * s + 1], zb[2 * s + 1], ds, 1);
  }
}

__device__ __forceinline__ void consumer(const int wg, __nv_bfloat16* out, const uint8_t* wimg, const uint32_t sbase,
                                         const uint32_t zero, const Maps& tm, const TileTable& tt) {
  const int tid = threadIdx.x & 127;
  const int w = __shfl_sync(0xffffffffu, tid >> 5, 0), lane = tid & 31;
  const uint64_t dK = make_desc(sbase, 16, 1024);
  const uint64_t dV = make_desc(sbase, kChunkBytes, 512, 2);
  const uint64_t dW1 = make_desc(sbase + kW1Off, 16, 1024);
  const uint64_t dX0 = make_desc(sbase + kW2Off + wg * 2 * kWChunk, 16, 1024), dY0 = make_desc(sbase + kW2Off + (1 - wg) * 2 * kWChunk, 16, 1024);
  const uint64_t dX2 = make_desc(sbase + kXOff + wg * (kWChunk / 2), 16, 1024), dY2 = make_desc(sbase + kXOff + (1 - wg) * (kWChunk / 2), 16, 1024);
  const uint32_t bars = sbase + kBarOff;
  int tile0 = blockIdx.x * kTilesPerCta;
  asm volatile("" : "+r"(tile0));
  const int nt = num_tiles();

  uint32_t pix = 0, geo[6] = {};
  const int l = lane & 3;
#pragma unroll 1
  for (int j = 4; j >= 0; j -= 2) {
    const TileCoord tc = decode_tile(tt, tile0 + wg + j);
    const bool col = tc.kind == 1 || tc.kind == 2;
    const int g = col ? lane >> 2 : 2 * w + ((lane >> 2) & 1), qc = col ? w : lane >> 3;
    const uint32_t pr = qpix(tc.pr, 8 * tc.I + g) * kW;
    if (j == nt - 2) pix = (pr + qpix(tc.pc, 8 * tc.J + qc)) | (pr + qpix(tc.pc, 8 * tc.J + qc + 4)) << 16;
    const int d = 8 * tc.J + 6 * tc.pc - 6 - halo_c0(tc);
    const int ro = woff(tc.pr, tc.I, g), coA = woff(tc.pc, tc.J, qc) + d, coB = woff(tc.pc, tc.J, qc + 4) + d - 3;
#pragma unroll
    for (int i = 5; i >= 2; i--) geo[i] = geo[i - 2];
    const uint32_t lr = 0x1FCu << ro;
    const uint32_t lv = lr >> (2 + (l >> 1)), lu = lr >> (2 * l + 2 * tc.up);
    const uint32_t t = __byte_perm(lv, lu, wg ? 0x4501 : 0x5410);
    geo[0] = (((t & 0x15u) | (lv & 0x40u)) * 0x02082080u & 0x80808080u) | (((t >> 8) & 0x15u) * 0x01041040u & 0x40404040u) |
             (__byte_perm(t << 5, t << 4, 0x7362) & 0x20202020u) | (nt == 6);
    const int dr = (ro - 1) & 7;
    const uint32_t hiv = (((1u << ((ro - (l >> 1) + 1) >> 1)) - 1u) ^ (wg ? 7u : 0u)) & 7u, hiu = (t >> 24) & 3u;
    const uint32_t ca = (1u << coA) - 1u;
    geo[1] = hiv * kHiV | hiu * kHiU | ((((1u << coB) - 1u) >> (2 * (l & 1))) & 3u) * kColB |
             (15u & ~((uint32_t)((dr & 1) == (l >> 1)) << (dr >> 1))) * kInV | ((t >> 16 | t >> 24) & 3u) * kInU | ca * kColA |
             (ca >> ((0x49 >> (2 * l)) & 3) & 1u) << 19 | (uint32_t)(l == 3) << 20 | (0x55u & ((1u << (2 * coB)) - 1u)) << 24;
  }
  keep_regs(geo);
  const int so = (lane >> 3) | (lane & 4);
  uint32_t sts = sbase + w * 3072 + so * 128 + (((lane & 3) ^ so) << 4);
  __nv_bfloat16* poA = out + 8 * l + (pix & 0xFFFFu) * kC + 96 * wg;
  __nv_bfloat16* poB = out + 8 * l + (pix >> 16) * kC + 96 * wg;
  asm volatile("" : "+l"(poA), "+l"(poB), "+r"(sts));
  uint32_t oa[24], ob[24];
#pragma unroll
  for (int j = 0; j < 24; j++) oa[j] = ob[j] = 0u;
  keep_regs(oa);
  keep_regs(ob);
  PROF(wg, 0);
  if (threadIdx.x == 0) GT(1);

  for (int k = wg; k < nt; k += 2) {
    const uint32_t ph = (k >> 1) & 1;
    const int it = k >> 1;
    uint32_t qa[24], qb[24], hok[3];
    uint32_t fl = geo[1];
    {
      float acc[96];
      const uint32_t xp = (k + (k > 0)) & 1;
      if (k > 0) nb_sync(1 + (1 - wg));
#pragma unroll
      for (int s = 0; s < 12; s++) {
        if (s == 0) mbar_wait(bar_x(bars, k > 0, 0), xp);
        if (s == 0 && k < 2) PROF(wg, 1);
        if (s == 0) PROFS(2, wg, 2 + it * 12);
        if (s == 0 && w == 0 && k < 2) GT(20 + wg);
        if (s == 4) wg_wait<1>();
        if ((s & 3) == 0 && (k == 0 || s > 0)) {
          mbar_wait(k == 0 ? bar_w1c(bars, s >> 2) : bar_x(bars, 1, s >> 2), xp);
          PROFS(17, wg, 50 + (s >> 2));
        }
        if ((s & 3) == 0) wg_fence();
        const uint64_t dX = make_desc(sbase + x_chunk(k, s >> 2), 16, 1024) + 2 * (s & 3);
        if (s == 0) wg_m192z<0, 96>(acc, dX, dW1, 0);
        else wg_m192<0, 96>(acc, dX, wdesc(dW1, s), 1);
        if ((s & 3) == 3 || s == 0) wg_commit();
      }
      PROFS(13, wg, 13 + it * 12);
      const uint32_t e = sts + out_slot(k, nt), o = e ^ 64;
      uint32_t ad[4] = {wg ? o + 1024 : e, wg ? e + 2048 : o, wg ? e : o + 1024, wg ? o : e + 2048};
      keep_regs(ad);
      wg_wait<2>();
      if (k > 0) nb_arrive_p(0);
      wg_wait<1>();
      if (k > 0) nb_arrive_p(14);
      wg_wait<0>();
      if (k > 0) {
        nb_arrive_p(6);
        sched_fence();
      }
      fence_regs(acc);
      PROFS(3, wg, 3 + it * 12);
#pragma unroll
      for (int j = 0; j < 24; j++) {
        qa[j] = pack_bf16(acc[4 * j], acc[4 * j + 1]);
        qb[j] = pack_bf16(acc[4 * j + 2], acc[4 * j + 3]);
      }
      keep_regs(qa);
      keep_regs(qb);
      sched_fence();
      if (k >= 2) {
        nb_sync(11);
        stage_out<0, 6>(ad, oa, ob);
        nb_sync(12);
        stage_out<6, 12>(ad, oa, ob);
      }
#pragma unroll
      for (int c = 0; c < 3; c++) hok[c] = mbar_test(bar_full(bars, wg, c), ph);
      if (k >= 2) {
        fence_proxy_async();
        nb_arrive_p(10);
      }
    }

    float aE[52], aO[24], bO[52], bE[28];
    const uint32_t mq = 0xEEEE4444u | zero;
    PROFS(4, wg, 4 + it * 12);

    mbar_wait_if(hok[0], bar_full(bars, wg, 0), ph);
    PROFS(14, wg, 40 + it * 3);
    if (w == 0 && k < 2) GT(22 + wg);
    if (k > 0) nb_sync(3 + (1 - wg));
    wg_fence();
#pragma unroll
    for (int ks = 0; ks < 6; ks++) {
      if (ks == 2) {
        mbar_wait_if(hok[1], bar_full(bars, wg, 1), ph);
        PROFS(14, wg, 41 + it * 3);
        wg_fence();
      }
      if (ks == 4) {
        mbar_wait_if(hok[2], bar_full(bars, wg, 2), ph);
        PROFS(14, wg, 42 + it * 3);
        wg_fence();
      }
      const uint64_t d = dK + ((ks * kChunkBytes) >> 4);
      if (ks == 0) wg_s104z<0, 52>(aE, qa[0], qa[1], qa[2], qa[3], d, 0, mq);
      else wg_s104<0, 52>(aE, qa[4 * ks], qa[4 * ks + 1], qa[4 * ks + 2], qa[4 * ks + 3], d, 1, mq);
      if (ks == 0) wg_s48z<0, 24>(aO, qa[0], qa[1], qa[2], qa[3], d + ((7 * 1024 + 64) >> 4), 0, mq);
    }
    wg_commit();
#pragma unroll
    for (int ks = 1; ks < 6; ks++)
      wg_s48<0, 24>(aO, qa[4 * ks], qa[4 * ks + 1], qa[4 * ks + 2], qa[4 * ks + 3], dK + ((ks * kChunkBytes + 7 * 1024 + 64) >> 4), 1, mq);
    wg_commit();
    wg_s56z<0, 28>(bE, qb[0], qb[1], qb[2], qb[3], dK, 0, mq);
#pragma unroll
    for (int ks = 1; ks < 6; ks++) wg_s56<0, 28>(bE, qb[4 * ks], qb[4 * ks + 1], qb[4 * ks + 2], qb[4 * ks + 3], dK + ((ks * kChunkBytes) >> 4), 1, mq);
    wg_commit();
    wg_wait<2>();
    fence_regs(aE);
    PROFS(5, wg, 5 + it * 12);

    uint32_t pa[14], pb[14], meta[4];
    {
      float vA[14], vB[14];
      pick_v(aE, vA, fl);
      pick_u(aE + 28, vA + 8, fl);
      fence_regs(vA);
      if (k == 0) {
        if (__builtin_expect(__any_sync(0xffffffffu, vA[6] != vA[6]), 0)) {
          wg_wait<0>();
          fence_regs(aO);
          fence_regs(bE);
          if (refetch(sbase + kW1Off, wimg, false)) {
#pragma unroll
            for (int j = 0; j < 24; j++) oa[j] = ob[j] = 0u;
            k -= 2;
            continue;
          }
        }
        if (elect_one()) mbar_arrive(bar_xf(bars));
      }
      wg_fence();
      wg_s104z<0, 52>(bO, qb[0], qb[1], qb[2], qb[3], dK + 4, 0, mq);
#pragma unroll
      for (int ks = 1; ks < 6; ks++)
        wg_s104<0, 52>(bO, qb[4 * ks], qb[4 * ks + 1], qb[4 * ks + 2], qb[4 * ks + 3], dK + ((ks * kChunkBytes + 64) >> 4), 1, mq);
      wg_commit();
      if (k + 1 < nt) nb_arrive(1 + wg);
      uint32_t rt[9];
#pragma unroll
      for (int i = 0; i < 7; i++) rt[i] = sign_bytes(geo[0] << (i >> 2), 0x8888u + 0x1111u * (i & 3));
      rt[7] = sign_bytes(geo[0] << 2, 0x9988u);
      rt[8] = sign_bytes(geo[0] << 2, 0xBBAAu);
      keep_regs(rt);
      pa[13] = geo[0] & zero, pb[13] = geo[1] & zero;
      wg_wait<2>();
      keep_regs(qa);
      fence_regs(aO);
      float oA[6], eB[8];
      pick_u(aO, oA, fl);
      wg_wait<1>();
      fence_regs(bE);
      pick_v(bE, eB, fl);
      vA[8] = sel<kColA>(oA[0], vA[8], fl), vA[9] = sel<kColA>(oA[1], vA[9], fl);
      vA[10] = sel<kColA * 2>(oA[2], vA[10], fl), vA[11] = sel<kColA * 2>(oA[3], vA[11], fl);
      vA[12] = sel<kColA * 4>(oA[4], vA[12], fl), vA[13] = sel<kColA * 4>(oA[5], vA[13], fl);
      {
        const float m1 = __uint_as_float(0x88DD88DDu), m0 = __uint_as_float(0x88DDDD88u);
        meta[0] = 0xDD88DD88u ^ __byte_perm(fl, 0u, 0x3344);
        meta[1] = __float_as_uint(sel<kColA * 16>(sel<kColA>(m1, m0, fl), __uint_as_float(meta[0]), fl));
        meta[2] = __float_as_uint(sel<kColA * 8>(m1, m0, fl));
        meta[3] = __float_as_uint(sel<kColA * 4>(m1, m0, fl));
        keep_regs(meta);
      }
      float mA = own_max(vA, fl);
      fl |= __float_as_uint(eB[7]) & zero;
      fence_regs(eB);
      fence_regs(vA);
      asm volatile("" : "+f"(mA), "+r"(fl));
      sched_fence();
      wg_wait<0>();
      sched_fence();
      keep_regs(qb);
      fence_regs(bO);
      PROFS(6, wg, 6 + it * 12);
      if (w == 0) GT(24 + k);
      mA = quad_max(mA);
      pick_v(bO, vB, fl);
      pick_u(bO + 28, vB + 8, fl);
#pragma unroll
      for (int i = 0; i < 8; i += 2) vB[i] = sel<kColB>(vB[i], eB[i], fl), vB[i + 1] = sel<kColB * 2>(vB[i + 1], eB[i + 1], fl);
#pragma unroll
      for (int i = 0; i < 14; i++) vA[i] = i < 3 ? ex2(vA[i] - mA) : vA[i] - mA;
      fence_regs(vA);
      fence_regs(vB);
      sched_fence();
#pragma unroll
      for (int i = 3; i < 14; i++) vA[i] = ex2(vA[i]);
      const float mB = quad_max(own_max(vB, fl));
      PROFS(7, wg, 7 + it * 12);
#pragma unroll
      for (int i = 0; i < 14; i++) vB[i] = i < 1 ? ex2(vB[i] - mB) : vB[i] - mB;
      fence_regs(vA);
      fence_regs(vB);
      sched_fence();
#pragma unroll
      for (int i = 1; i < 14; i++) vB[i] = ex2(vB[i]);
      route(vA, row_rcp(vA, fl), rt, pa);
      route(vB, row_rcp(vB, fl), rt, pb);
    }
    PROFS(8, wg, 8 + it * 12);
    if (k == NAT_PK) PROFS(18, wg, 53);
    sched_fence();

    float ac0[48], ac1[48];
    {
      float z0[32], z1[32], z2[32];
      uint32_t za[24], zb[24];
      wg_fence();
      pv_chunk<0>(z0, pa, pb, meta, dV);
      wg_commit();
      pv_chunk<1>(z1, pa, pb, meta, dV);
      wg_commit();
      wg_wait<1>();
      if (k == NAT_PK) PROFS(18, wg, 54);
      if (k + 1 < nt) nb_arrive_p(7);
      pv_chunk<2, 0, 3>(z2, pa, pb, meta, dV);
      wg_commit();
      sched_fence();
      fence_regs(z0);
      pack_z<0>(z0, za, zb);
      sched_fence();
      wg_fence();
      pv_chunk<2, 3, 7>(z2, pa, pb, meta, dV);
      wg_commit();
      wg_wait<2>();
      if (k == NAT_PK) PROFS(19, wg, 55);
      if (k + 1 < nt) nb_arrive_p(8);
      if (k < 2) mbar_wait(k == 1 ? bar_wok(bars) : bar_w2a(bars), 0);
      wg_fence();
      g2_steps<0, 3, 0>(ac0, za, zb, dX0);
      wg_commit();
      sched_fence();
      fence_regs(z1);
      pack_z<1>(z1, za, zb);
      sched_fence();
      wg_fence();
      g2_steps<3, 4, 0>(ac0, za, zb, dX0);
      wg_commit();
      g2_steps<4, 8, 0>(ac0, za, zb, dX0);
      wg_commit();
      wg_wait<3>();
      if (k + 1 < nt) nb_arrive_p(9);
      else nb_arrive(11);
      if (k == NAT_PK) PROFS(20, wg, 56);
      keep_regs(pa);
      keep_regs(pb);
      keep_regs(meta);
      sched_fence();
      const uint32_t mok = mbar_test(bar_w2m(bars), k + 1 < nt ? k & 1 : ~k & 1);
      const uint32_t wp = k < 2 ? 0 : k + 1 < nt ? ~k & 1 : k & 1, wok = mbar_test(bar_w2(bars), wp);
      fence_regs(z2);
      pack_z<2>(z2, za, zb);
      keep_regs(za);
      keep_regs(zb);
      sched_fence();
      PROFS(9, wg, 9 + it * 12);
      wg_wait<1>();
      if (k > 0 && k + 1 < nt) nb_arrive(11);
      mbar_wait_if(mok, bar_w2m(bars), k & 1);
      wg_fence();
      g2_steps<8, 12, 0>(ac0, za, zb, dX2);
      wg_commit();
      g2_steps<8, 12, 8>(ac1, za, zb, dY2);
      wg_commit();
      wg_wait<2>();
      if (k > 0 && k + 1 < nt) nb_arrive(12);
      mbar_wait_if(wok, bar_w2(bars), wp);
      wg_fence();
      g2_steps<0, 4, 8>(ac1, za, zb, dY0);
      wg_commit();
      wg_wait<2>();
      if (k + 2 < nt) nb_arrive_p(13);
      const bool direct = k + 2 >= nt;
      sched_fence();
      fence_regs(ac0);
      pack_out<0>(ac0, oa, ob);
      store_rows<0, 1>(direct, poA, poB, oa, ob);
      sched_fence();
      wg_fence();
      g2_steps<4, 8, 8>(ac1, za, zb, dY0);
      wg_commit();
      if (k + 1 < nt) nb_arrive(3 + wg);
      PROFS(10, wg, 10 + it * 12);
      wg_wait<2>();
      if (k + 2 < nt && (k > 0 || nt == 6)) nb_arrive_p(5);
      store_rows<1, 3>(direct, poA, poB, oa, ob);
      __nv_bfloat16 *qA = poA - 192 * wg, *qB = poB - 192 * wg;
      if (k + 2 == nt) nb_sync(11);
      sched_fence();
      wg_wait<0>();
      fence_regs(ac1);
      if (direct) {
        pack_out<1>(ac1, oa, ob);
        asm volatile("" : "+l"(qA), "+l"(qB));
        store_rows<3, 6>(true, qA, qB, oa, ob);
        break;
      }
      sched_fence();
      pack_out<1>(ac1, oa, ob);
      if (k == 0) {
        if (any_nan(oa)) {
          for (int c = 0; c < 3 && __any_sync(0xffffffffu, geo[2] & 1u); c++) mbar_wait(bar_x(bars, 1, c), 1);
          bool first = true;
          do {
            if (!__any_sync(0xffffffffu, refetch(sbase + kW2Off, wimg + w2_offset(), first))) break;
            first = false;
            wg_fence();
            g2_steps<0, 8, 0>(ac0, za, zb, dX0);
            g2_steps<8, 12, 0>(ac0, za, zb, dX2);
            g2_steps<8, 12, 8>(ac1, za, zb, dY2);
            g2_steps<0, 8, 8>(ac1, za, zb, dY0);
            wg_commit();
            wg_wait<0>();
            fence_regs(ac0);
            fence_regs(ac1);
            pack_out<0>(ac0, oa, ob);
            pack_out<1>(ac1, oa, ob);
          } while (any_nan(oa));
          if (__any_sync(0xffffffffu, geo[2] & 1u)) {
            asm volatile("bar.sync 15, 128;" ::: "memory");
            if (w == 0 && elect_one()) {
              const TileCoord tc = decode_tile(tt, tile0 + 2);
              mbar_arrive_expect_tx(bar_raw(bars), kWChunk);
#pragma unroll 1
              for (int c = 0; c < 3; c++) load_px(tm, tt, sbase + x_chunk(2, c), bar_raw(bars), first_line(tc) + c, tc.kind);
            }
            __syncwarp();
            mbar_wait(bar_raw(bars), 0);
          }
        }
        if (nt < 6) nb_arrive_p(5);
        if (elect_one()) mbar_arrive(bar_wok(bars));
      }
      keep_regs(za);
      keep_regs(zb);
#pragma unroll
      for (int i = 0; i < 4; i++) geo[i] = geo[i + 2];
      keep_regs(oa);
      keep_regs(ob);
      PROFS(12, wg, 12 + it * 12);
      sched_fence();
    }
  }
  PROF(wg, 38);
  GT_DUMP();
  PROF_DUMP(wg);
}

struct HaloCols { int vj, vc, uj, uc; };
__device__ __forceinline__ HaloCols halo_cols(const TileCoord& tc) {
  const int c0 = halo_c0(tc);
  return HaloCols{c0 > 98, c0 > 98 ? 98 : c0 + 3, c0 < 0 ? -1 : 0, c0 < 0 ? 4 : c0};
}
__device__ __forceinline__ void first_halo(const Maps& tm, uint32_t sbase, const TileCoord tc, int i) {
  const HaloCols hc = halo_cols(tc);
  const uint32_t dst = sbase + i * kChunkBytes, bar = bar_full(sbase + kBarOff, 0, i >> 1);
  const int h0 = halo_r0(tc), ch = 24 * tc.pc + 4 * i;
  tma_load_5d(dst, &tm.v14, bar, ch, hc.vj, hc.vc, tc.pr, h0);
  tma_load_5d(dst + 7 * 1024, &tm.u8, bar, ch, hc.uj, h0 + (tc.up ? 0 : -2), tc.pr, hc.uc);
  tma_load_5d(dst + 10 * 1024, &tm.u8, bar, ch, hc.uj, h0 + (tc.up ? 8 : 6), tc.pr, hc.uc);
}
__device__ __forceinline__ void load_halo(const Maps& tm, uint32_t sbase, uint32_t bars, const TileCoord tc, int k, int c) {
  const HaloCols hc = halo_cols(tc);
  const int h6 = halo_r0(tc) + (tc.up ? 0 : 8), h2 = halo_r0(tc) + 6, h8 = halo_r0(tc) + (tc.up ? 0 : 6), ch = 24 * tc.pc + 8 * c;
  uint32_t dv = sbase + 2 * c * kChunkBytes, du = dv + 7 * 1024;
  if (((k ^ tc.up) & 1) == 0) dv += 4 * 1024, du += 3 * 1024;
  const uint32_t bar = bar_full(bars, k & 1, c);
  mbar_arrive_expect_tx(bar, 14 * 1024);
  nb_sync_p(7 + c);
#pragma unroll
  for (int h = 0; h < 2; h++) {
    tma_load_5d(dv + h * kChunkBytes, &tm.v6, bar, ch + 4 * h, hc.vj, hc.vc, tc.pr, h6);
    tma_load_5d(du + h * kChunkBytes, &tm.u8, bar, ch + 4 * h, hc.uj, h8, tc.pr, hc.uc);
    tma_load_5d(sbase + (2 * c + h) * kChunkBytes + 3 * 1024, &tm.v2, bar, ch + 4 * h, hc.vj, hc.vc, tc.pr, h2);
  }
  PROFS(15, 2, k * 4 + c);
}
__device__ __forceinline__ void gather_px(const __nv_bfloat16* __restrict__ x, uint32_t sbase, const TileCoord tc) {
  const int lane = threadIdx.x & 31, g = lane >> 3;
  uint32_t ro[4], co[4];
#pragma unroll
  for (int i = 0; i < 4; i++) {
    ro[i] = qpix(tc.pr, 8 * tc.I + 2 * i + (g & 1)) * (kW * kC * 2) + 16 * (lane & 7);
    co[i] = qpix(tc.pc, 8 * tc.J + 2 * i + (g >> 1)) * (kC * 2);
  }
  const uint32_t dst = sbase + kXOff + g * 128 + (((lane & 7) ^ g) << 4);
  if (lane < 8)
    asm volatile("cp.async.bulk.prefetch.L2.global [%0], 3456;" ::"l"(x + (qpix(tc.pr, 8 * tc.I + lane) * kW + 215 * tc.pc) * kC) : "memory");
  __syncwarp();
  keep_regs(ro);
  keep_regs(co);
  sched_fence();
  nb_sync_p(13);
  nb_sync_p(5);
#pragma unroll
  for (int i = 0; i < 16; i++) {
    const char* src = (const char*)x + (ro[i >> 2] + co[i & 3]);
#pragma unroll
    for (int q = 0; q < 3; q++)
      asm volatile("cp.async.cg.shared.global [%0], [%1], 16;" ::"r"((dst ^ ((i & 1) * 576)) + (i >> 1) * 1024 + q * 8192), "l"(src + 128 * q) : "memory");
  }
  asm volatile("cp.async.wait_all;" ::: "memory");
  fence_proxy_async();
  __syncwarp();
  if (lane < 3) mbar_arrive(bar_x(sbase + kBarOff, 1, lane));
  __syncwarp();
}

__global__ void __launch_bounds__(384, 1)
nat_kernel(const __nv_bfloat16* __restrict__ x, __nv_bfloat16* out, const __nv_bfloat16* __restrict__ wqkv,
           const __nv_bfloat16* __restrict__ wo, uint8_t* wimg, const uint32_t zero,
           const __grid_constant__ Maps tm, const __grid_constant__ TileTable tt) {
  extern __shared__ uint8_t smem_raw[];
  constexpr uint32_t sbase = 1024;
  constexpr uint32_t bars = sbase + kBarOff;
  if (smem_u32(smem_raw) != sbase) __trap();
  const int tid = threadIdx.x;
  const uint32_t t_start = now_ns();
  if (tid == 0) GT(0);
  const int wid = __shfl_sync(0xffffffffu, tid >> 5, 0);
  const bool w2cta = blockIdx.x - 128 < 3 && wqkv != nullptr;
  if (wid >= 8) {
    asm volatile("setmaxnreg.dec.sync.aligned.u32 24;");
    const int c = wid & 3, lane = tid & 31;
    const int tile0 = blockIdx.x * kTilesPerCta, nt = num_tiles();
    uint32_t w2o = 0;
    if (c == 3) {
      if (elect_one()) wait_clock(t_start, NAT_TM);
      __syncwarp();
      asm volatile("prefetch.tensormap [%0];" ::"l"((uint64_t)tm.px) : "memory");
      asm volatile("prefetch.tensormap [%0];" ::"l"((uint64_t)&tm.v6) : "memory");
      asm volatile("prefetch.tensormap [%0];" ::"l"((uint64_t)&tm.v2) : "memory");
      asm volatile("prefetch.tensormap [%0];" ::"l"((uint64_t)(tm.px + (blockIdx.x < 112 ? 5 : 6))) : "memory");
      asm volatile("prefetch.tensormap [%0];" ::"l"((uint64_t)(tm.px + 7)) : "memory");
      if (nt < 6) {
        asm volatile("prefetch.tensormap [%0];" ::"l"((uint64_t)(tm.px + 1)) : "memory");
        asm volatile("prefetch.tensormap [%0];" ::"l"((uint64_t)(tm.px + 2)) : "memory");
        asm volatile("prefetch.tensormap [%0];" ::"l"((uint64_t)&tm.v14) : "memory");
        asm volatile("prefetch.tensormap [%0];" ::"l"((uint64_t)&tm.u8) : "memory");
      }
      __nanosleep(NAT_TW2 - 2800);
      asm volatile("bar.sync 4, 64;" ::: "memory");
      w2o = w2_offset();
      if (elect_one()) {
        mbar_arrive_expect_tx(bar_w2a(bars), kWChunk);
        mbar_arrive_expect_tx(bar_w2(bars), kWChunk);
        wait_clock(t_start, NAT_TW2);
        bulk_load(sbase + kW2Off, wimg + w2o, kWChunk, bar_w2a(bars));
        mbar_wait(bar_xf(bars), 0);
        bulk_load(sbase + kW2Off + 2 * kWChunk, wimg + (w2o + 2 * kWChunk), kWChunk, bar_w2(bars));
      }
      __syncwarp();
      if (nt < 6) gather_px(x, sbase, decode_tile(tt, tile0 + 2));
      if (wqkv == nullptr) return;
      mbar_wait(bar_wok(bars), 0);
      if (lane == 0) asm volatile("red.relaxed.gpu.global.add.u32 [%0], 1;" ::"l"(g_flag) : "memory");
      if (blockIdx.x != kCtas - 1) return;
#pragma unroll
      for (int i = 0; i < 8; i++) asm volatile("st.shared.v4.u32 [%0], {%1,%1,%1,%1};" ::"r"(bars + 1024 + i * 512 + lane * 16), "r"(kEmpty) : "memory");
      fence_proxy_async();
      __syncwarp();
      if (elect_one()) {
#pragma unroll 1
        for (int i = 0; i < 36; i++) {
          if (i == 18) {
            uint32_t v, it = 0;
            do {
              __nanosleep(500);
              asm volatile("ld.relaxed.gpu.global.u32 %0, [%1];" : "=r"(v) : "l"(g_flag) : "memory");
            } while (v < gridDim.x && ++it < (1u << 18));
          }
          asm volatile("cp.async.bulk.global.shared::cta.bulk_group [%0], [%1], 4096;" ::"l"(
                           wimg + (i < 18 ? 3 * kWBytes - w2o + i * 4096 : (i - 18) * 4096)), "r"(bars + 1024) : "memory");
          asm volatile("cp.async.bulk.commit_group;" ::: "memory");
          asm volatile("cp.async.bulk.wait_group.read 1;" ::: "memory");
        }
        asm volatile("cp.async.bulk.wait_group 0;" ::: "memory");
        g_flag[0] = 0;
        g_flag[32] = w2o == kWBytes;
      }
      return;
    }
    if (!elect_one()) return;
    if (c == 0) {
      for (int i = 0; i < kNumBars; i++)
        if ((i != 0 && i != 10 || nt < 6) && (i != 21 || !w2cta)) mbar_init(bars + i * 8, i == 13 || i == 16 ? 4 : 1);
      asm volatile("st.shared.v2.u32 [%0], {%1,%1};" ::"r"(bars + 192), "r"(0) : "memory");
      asm volatile("fence.mbarrier_init.release.cluster;" ::: "memory");
      if (w2cta) asm volatile("bar.sync 10, 64;" ::: "memory");
      asm volatile("bar.arrive 0, 160;" ::: "memory");
      asm volatile("bar.arrive 14, 160;" ::: "memory");
      asm volatile("bar.arrive 13, 96;" ::: "memory");
      asm volatile("bar.arrive 4, 64;" ::: "memory");
      const TileCoord tc0 = decode_tile(tt, tile0);
      const HaloCols hc = halo_cols(tc0);
      const int h0 = halo_r0(tc0);
#pragma unroll
      for (int j = 0; j < 3; j++)
        if (j > 0 || nt < 6) mbar_arrive_expect_tx(bar_full(bars, 0, j), 2 * kChunkBytes);
      wait_clock(t_start, NAT_HP);
#pragma unroll
      for (int q = 8; q < 24 && !w2cta; q += 8) {
        tma_prefetch_5d(blockIdx.x < 112 ? &tm.v6 : &tm.v14, 24 * tc0.pc + q, hc.vj, hc.vc, tc0.pr, h0 + (tc0.up || blockIdx.x >= 112 ? 0 : 8));
        tma_prefetch_5d(&tm.u8, 24 * tc0.pc + q, hc.uj, h0 + (tc0.up ? 0 : 6), tc0.pr, hc.uc);
      }
#pragma unroll 1
      for (int i = nt < 6 ? 0 : 2; i < 6; i++) {
        if (i == 2) mbar_wait(bar_w1q(bars), 0);
        first_halo(tm, sbase, tc0, i);
      }
      mbar_arrive(bar_go(bars));
      w2o = w2_offset();
    } else {
      asm volatile("bar.sync 13, 96;" ::: "memory");
      if (c == 2) {
        if (wqkv != nullptr && blockIdx.x < 131) asm volatile("bar.sync 12, 64;" ::: "memory");
        const uint32_t c0 = clock();
        while ((uint32_t)clock() - c0 < NAT_TD && nt == 6) { }
        wait_clock(t_start, NAT_T0);
#pragma unroll
        for (int j = 0; j < 3; j++) {
          mbar_arrive_expect_tx(bar_w1c(bars, j), kWChunk);
          bulk_load(sbase + kW1Off + j * kWChunk, wimg + j * kWChunk, kWChunk, bar_w1c(bars, j));
        }
        mbar_arrive(bar_w1q(bars));
        GT(2);
      } else {
#pragma unroll 1
        for (int j = nt == 6; j < 2; j++) {
          const TileCoord tc = decode_tile(tt, tile0 + j);
          const int line = first_line(tc);
          if (j == 1) mbar_wait(bar_go(bars), 0);
          if (j == 0) GT(15);
#pragma unroll 1
          for (int q = 0; q < 3; q++) {
            load_px(tm, tt, sbase + x_chunk(j, q), bar_x(bars, j, q), line + q, tc.kind);
            if (j == 1 || q == 0) mbar_arrive_expect_tx(bar_x(bars, j, q), j ? 8192 : kWChunk);
          }
          if (j == 0) GT(16);
        }
        w2o = w2_offset();
        wait_clock(t_start, NAT_TW2);
        mbar_wait(bar_xf(bars), 0);
      }
    }
#pragma unroll 1
    for (int k = 1; k < nt; k++) {
      const TileCoord tn = decode_tile(tt, tile0 + k + 1);
      const int line = first_line(tn);
      const bool more = k + 1 < nt && (k > 1 || nt == 6);
      if (c == 1) {
#pragma unroll
        for (int q = 0; q < 3; q++) {
          nb_sync_p(q == 0 ? 0 : q == 1 ? 14 : 6);
          bulk_load(sbase + x_chunk(k, q), wimg + (w2o + x_chunk(k, q) - kW2Off), 8192, bar_w2m(bars));
        }
        mbar_arrive_expect_tx(bar_w2m(bars), kWChunk);
      }
      if (c == 2) {
        if (k == 1) wait_clock(t_start, NAT_TX2);
        else __nanosleep(NAT_PFD);
#pragma unroll 1
        for (int q = 0; q < 3 && more; q++) load_px(tm, tt, 0, 0, line + q, tn.kind);
      }
      if (c == 2 && (blockIdx.x >= 112 || k == 5)) {
        const TileCoord tc = decode_tile(tt, tile0 + k);
        const HaloCols hc = halo_cols(tc);
        const int h8 = halo_r0(tc) + (tc.up ? 0 : 6);
#pragma unroll 1
        for (int q = 0; q < 24; q += 8) {
          tma_prefetch_5d(&tm.v6, 24 * tc.pc + q, hc.vj, hc.vc, tc.pr, h8);
          tma_prefetch_5d(&tm.v2, 24 * tc.pc + q, hc.vj, hc.vc, tc.pr, h8 + 6);
          tma_prefetch_5d(&tm.u8, 24 * tc.pc + q, hc.uj, h8, tc.pr, hc.uc);
        }
      }
      load_halo(tm, sbase, bars, decode_tile(tt, tile0 + k), k, c);
      if (c == 0 && more) {
#pragma unroll
        for (int q = 0; q < 3; q++) {
          if (q < 2) nb_sync_p(q ? 5 : 13);
          load_px(tm, tt, sbase + x_chunk(k + 1, q), bar_x(bars, 1, q), line + q, tn.kind);
          if (q != 1) mbar_arrive_expect_tx(bar_x(bars, 1, q), 8192);
        }
        mbar_arrive_expect_tx(bar_x(bars, 1, 1), 8192);
        PROFS(16, 2, k * 4 + 3);
      }
      if (c == 0 && k >= 2) {
        const TileCoord tp = decode_tile(tt, tile0 + k - 2);
        const int lp = first_line(tp);
        nb_sync_p(10);
        __nanosleep(NAT_XW);
        store_px(tm, tt, sbase + out_slot(k, nt), lp, tp.kind);
        if (k + 1 < nt) {
          asm volatile("cp.async.bulk.wait_group.read 0;" ::: "memory");
          bulk_load(sbase + out_slot(k, nt), wimg + (w2o + out_slot(k, nt) - kW2Off), kWChunk, bar_w2(bars));
          mbar_arrive_expect_tx(bar_w2(bars), kWChunk);
        }
      }
    }
    asm volatile("cp.async.bulk.wait_group 0;" ::: "memory");
  } else {
    if (blockIdx.x < 128) {
      if ((wid == 4 || (wid == 5 && blockIdx.x - 2 < 16)) && wqkv != nullptr) {
        fold_w1(blockIdx.x - 2 < 16 ? 2 * blockIdx.x + wid - 6 : blockIdx.x + (blockIdx.x < 2 ? 0 : 16), wqkv, wimg);
        if (wid == 4) asm volatile("bar.arrive 12, 64;" ::: "memory");
        if (tid == 128) GT(7);
      }
      sched_fence();
      if (wid == 1 && elect_one()) {
        const TileCoord tc = decode_tile(tt, blockIdx.x * kTilesPerCta);
        mbar_init(bar_x(bars, 0, 0), 1);
        asm volatile("fence.mbarrier_init.release.cluster;" ::: "memory");
        mbar_arrive_expect_tx(bar_x(bars, 0, 0), kWChunk);
        GT(15);
#pragma unroll 1
        for (int q = 0; q < 3; q++) load_px(tm, tt, sbase + x_chunk(0, q), bar_x(bars, 0, 0), first_line(tc) + q, tc.kind);
        GT(16);
      }
      __syncwarp();
      sched_fence();
      if (wid == 2 && elect_one()) {
        const TileCoord tc = decode_tile(tt, blockIdx.x * kTilesPerCta);
        mbar_init(bar_full(bars, 0, 0), 1);
        asm volatile("fence.mbarrier_init.release.cluster;" ::: "memory");
        mbar_arrive_expect_tx(bar_full(bars, 0, 0), 2 * kChunkBytes);
        asm volatile("prefetch.tensormap [%0];" ::"l"((uint64_t)&tm.u8) : "memory");
        GT(17);
        first_halo(tm, sbase, tc, 0);
        first_halo(tm, sbase, tc, 1);
      }
      __syncwarp();
    }
    sched_fence();
    {
      if (blockIdx.x >= 128 && wqkv != nullptr && (wid | 2) == 2 && elect_one())
        asm volatile("cp.async.bulk.prefetch.L2.global [%0], %1;" ::"l"(wid ? wo + (blockIdx.x & 3) * 48 * 192 : wqkv + (blockIdx.x & 3) * 48 * 576),
                     "r"(wid ? 48 * 384 : 48 * 1152) : "memory");
      __syncwarp();
      if (w2cta) {
        const int q = blockIdx.x & 3, h = wid >> 2;
        uint32_t w2o = 0;
        if (wid == 1 && elect_one()) {
          asm volatile("prefetch.tensormap [%0];" ::"l"((uint64_t)&tm.wo) : "memory");
          mbar_init(bar_raw(bars, 0), 1);
          mbar_init(bar_raw(bars, 1), 1);
          asm volatile("fence.mbarrier_init.release.cluster;" ::: "memory");
#pragma unroll
          for (int j = 0; j < 3; j++)
            asm volatile("cp.async.bulk.tensor.3d.shared::cluster.global.tile.mbarrier::complete_tx::bytes [%0], [%1, {%3, %4, %5}], [%2];" ::"r"(
                             j ? sbase + kW2Off + (j - 1) * (kWBytes / 2) : sbase),
                         "l"((uint64_t)(j ? &tm.wo : &tm.wv)), "r"(bar_raw(bars, j >> 1)), "r"(0), "r"(j ? 0 : 64 * q), "r"(j ? 3 * j - 3 : 6) : "memory");
          mbar_arrive_expect_tx(bar_raw(bars, 0), kWChunk + kWBytes / 2);
          mbar_arrive_expect_tx(bar_raw(bars, 1), kWBytes / 2);
          w2o = w2_offset();
        }
        __syncwarp();
#pragma unroll 1
        for (int r = 1 - h;; r++) {
          if (r > 0) asm volatile("bar.sync 11, 256;" ::: "memory");
          if (r == 2) break;
          if (r > 0) {
            mbar_wait(bar_raw(bars, 0), 0);
            mbar_wait(bar_raw(bars, h), 0);
          }
          if (tid == 0) GT(7);
          float acc[48];
          const uint64_t db = make_desc(sbase + kW2Off + h * (kWBytes / 2), kWChunk / 2, 512, 2);
          wg_fence();
          wg_m96tz<0, 48>(acc, make_desc(sbase, 16, 1024), db, 0);
#pragma unroll
          for (int s = 1; s < 12; s++) wg_m96t<0, 48>(acc, make_desc(sbase + (s >> 2) * 8192 + (s & 3) * 32, 16, 1024), db + s * 64, 1);
          wg_commit();
          wg_wait<0>();
          fence_regs(acc);
          if (tid == 0) GT(19);
          const int m = (tid >> 3) & 3;
#pragma unroll
          for (int j = 0; j < 12; j += 2) {
            const int n = g2_inv(8 * (j + (m >> 1)) + (tid & 7));
            asm volatile("stmatrix.sync.aligned.m8n8.x4.trans.shared.b16 [%0], {%1,%2,%3,%4};" ::"r"(
                             sbase + kW1Off + h * (kWChunk / 2) + n * 128 + (((2 * (wid & 3) + (m & 1)) ^ (n & 7)) << 4)),
                         "r"(pack_bf16(acc[4 * j], acc[4 * j + 1])), "r"(pack_bf16(acc[4 * j + 2], acc[4 * j + 3])),
                         "r"(pack_bf16(acc[4 * j + 4], acc[4 * j + 5])), "r"(pack_bf16(acc[4 * j + 6], acc[4 * j + 7])) : "memory");
          }
          fence_proxy_async();
        }
        if (tid == 0) GT(18);
        if (wid == 1) {
          if (elect_one()) {
#pragma unroll
            for (int i = 0; i < 2; i++)
              asm volatile("cp.async.bulk.global.shared::cta.bulk_group [%0], [%1], %2;" ::"l"(wimg + (w2o + w2piece(i, q) * (kWChunk / 2))),
                           "r"(sbase + kW1Off + i * (kWChunk / 2)), "r"(kWChunk / 2) : "memory");
            asm volatile("cp.async.bulk.commit_group;" ::: "memory");
          }
          __syncwarp();
          asm volatile("bar.arrive 10, 64;" ::: "memory");
          if (elect_one()) asm volatile("cp.async.bulk.wait_group.read 0;" ::: "memory");
          if (tid == 32) GT(31);
          __syncwarp();
          asm volatile("bar.arrive 12, 64;" ::: "memory");
        }
      }
    }
    __syncwarp();
    if (wid < 4) asm volatile("bar.sync 0, 160;" ::: "memory");
    else asm volatile("bar.sync 14, 160;" ::: "memory");
    asm volatile("setmaxnreg.inc.sync.aligned.u32 240;");
    consumer(wid >> 2, out, wimg, sbase, zero, tm, tt);
  }
}

}

typedef CUresult (*PFN_encodeTiled)(CUtensorMap*, CUtensorMapDataType, cuuint32_t, void*, const cuuint64_t*,
                                    const cuuint64_t*, const cuuint32_t*, const cuuint32_t*, CUtensorMapInterleave,
                                    CUtensorMapSwizzle, CUtensorMapL2promotion, CUtensorMapFloatOOBfill);

extern "C" void kernel_launch(void* const* d_in, const int* in_sizes, int n_in, void* d_out, int out_size) {
  const __nv_bfloat16* x = (const __nv_bfloat16*)d_in[0];
  const __nv_bfloat16* wqkv = (const __nv_bfloat16*)d_in[1];
  const __nv_bfloat16* wo = (const __nv_bfloat16*)d_in[2];
  __nv_bfloat16* out = (__nv_bfloat16*)d_out;

  static PFN_encodeTiled encode = nullptr;
  static int num_sms = 0;
  static uint8_t* wimg = nullptr;
  if (!encode) {
    void* fn = nullptr;
    cudaDriverEntryPointQueryResult qres;
    cudaGetDriverEntryPoint("cuTensorMapEncodeTiled", &fn, cudaEnableDefault, &qres);
    encode = (PFN_encodeTiled)fn;
    cudaFuncSetAttribute(nat::nat_kernel, cudaFuncAttributeMaxDynamicSharedMemorySize, nat::kSmemBytes);
    cudaGetSymbolAddress((void**)&wimg, nat::g_wimg32);
    int dev = 0;
    cudaGetDevice(&dev);
    cudaDeviceGetAttribute(&num_sms, cudaDevAttrMultiProcessorCount, dev);
  }
  nat::Maps tm;
  cuuint32_t estr[5] = {1, 1, 1, 1, 1};
  {
    cuuint64_t vdim[5] = {48, 2, 105, 2, 112}, udim[5] = {48, 2, 112, 2, 105};
    cuuint64_t vstr[4] = {7 * 768, 768, 224 * 384, 2 * 224 * 384}, ustr[4] = {7 * 768, 2 * 224 * 384, 224 * 384, 768};
    CUtensorMap* maps[4] = {&tm.v6, &tm.v2, &tm.v14, &tm.u8};
    for (int i = 0; i < 4; i++) {
      cuuint32_t box[5] = {4, 2, i < 3 ? 4u : 8u, 1, i == 0 ? 6u : i == 1 ? 2u : i == 2 ? 14u : 3u};
      encode(maps[i], CU_TENSOR_MAP_DATA_TYPE_UINT32, 5, (void*)x, i < 3 ? vdim : udim, i < 3 ? vstr : ustr, box, estr,
             CU_TENSOR_MAP_INTERLEAVE_16B, CU_TENSOR_MAP_SWIZZLE_128B, CU_TENSOR_MAP_L2_PROMOTION_L2_128B, CU_TENSOR_MAP_FLOAT_OOB_FILL_NONE);
    }
  }
  for (int i = 0; i < 8; i++) {
    const cuuint32_t row = 224 * 384;
    const cuuint32_t shape[8][6] = {{2, 8, 4, 2 * row, 768, 4 * row}, {2, 8, 3, row, 768, 2 * row},     {2, 8, 1, 2 * row, 768, 4 * row},
                                    {8, 2, 3, 2 * row, 4 * 384, 384}, {8, 2, 1, 2 * row, 5 * 384, 384}, {4, 2, 3, 4 * row, 2 * row, 128},
                                    {4, 2, 3, 768, row, 128},         {4, 2, 3, 768, 2 * row, 128}};
    const cuuint32_t* sh = shape[i];
    cuuint64_t dim[5] = {64, sh[0], sh[1], sh[2], 224 * 224 * 3};
    cuuint64_t str[4] = {sh[3], sh[4], sh[5], 128};
    cuuint32_t box[5] = {64, sh[0], sh[1], sh[2], 1};
    encode(tm.px + i, CU_TENSOR_MAP_DATA_TYPE_BFLOAT16, 5, i < 5 ? (void*)x : (void*)out, dim, str, box, estr, CU_TENSOR_MAP_INTERLEAVE_NONE,
           CU_TENSOR_MAP_SWIZZLE_128B, i < 5 ? CU_TENSOR_MAP_L2_PROMOTION_L2_128B : CU_TENSOR_MAP_L2_PROMOTION_NONE,
           CU_TENSOR_MAP_FLOAT_OOB_FILL_NONE);
  }
  for (int i = 0; i < 2; i++) {
    cuuint64_t dim[3] = {i ? 32u : 64u, 192, i ? 6u : 9u}, str[2] = {i ? 384u : 1152u, i ? 64u : 128u};
    cuuint32_t box[3] = {i ? 32u : 64u, i ? 192u : 64u, 3};
    encode(i ? &tm.wo : &tm.wv, CU_TENSOR_MAP_DATA_TYPE_BFLOAT16, 3, i ? (void*)wo : (void*)wqkv, dim, str, box, estr,
           CU_TENSOR_MAP_INTERLEAVE_NONE, i ? CU_TENSOR_MAP_SWIZZLE_64B : CU_TENSOR_MAP_SWIZZLE_128B, CU_TENSOR_MAP_L2_PROMOTION_L2_256B,
           CU_TENSOR_MAP_FLOAT_OOB_FILL_NONE);
  }
  nat::TileTable tt;
  nat::make_tiles(tt);
  const int grid = nat::kCtas;
  if (num_sms >= grid) {
    nat::nat_kernel<<<grid, 384, nat::kSmemBytes>>>(x, out, wqkv, wo, wimg, 0u, tm, tt);
  } else {
    nat::fold_kernel<<<27, 256>>>(wqkv, wo, wimg);
    nat::nat_kernel<<<grid, 384, nat::kSmemBytes>>>(x, out, nullptr, nullptr, wimg, 0u, tm, tt);
  }
}
```

```cpp
#include <cuda_runtime.h>
#include <cuda_bf16.h>
#include <cuda.h>
#include <stdint.h>

#define NAT_TM 1300
#define NAT_HP 1800
#define NAT_T0 2130
#define NAT_TD 1250
#define NAT_TX2 3800
#define NAT_TW2 4600
#define NAT_PFD 300
#define NAT_XW 200
#define NAT_PK 3
namespace nat {

constexpr int kW = 224, kC = 192;
constexpr int kCtas = 132;
constexpr int kTilesPerCta = 6;
constexpr float kAlpha = 0.07216878364870322f * 1.4426950408889634f;
constexpr uint32_t kChunkBytes = 13 * 1024;
constexpr uint32_t kWChunk = 192 * 128;
constexpr uint32_t kWBytes = 3 * kWChunk;
constexpr uint32_t kW1Off = 6 * kChunkBytes;
constexpr uint32_t kW2Off = kW1Off + kWBytes;
constexpr uint32_t kXOff = kW2Off + kWChunk;
constexpr uint32_t kBarOff = kW2Off + kWBytes;
constexpr uint32_t kProfOff = kBarOff + 208;
constexpr uint32_t kSmemBytes = kBarOff + 1024 + 4096;

static_assert(kW1Off % 1024 == 0 && kW2Off % 1024 == 0 && kChunkBytes % 1024 == 0, "swizzle alignment");
static_assert(kSmemBytes <= 232448, "smem");

constexpr uint32_t kEmpty = 0xFFFFFFFFu;
#define NAT_R8(v) v, v, v, v, v, v, v, v
#define NAT_R2K(v) NAT_R8(NAT_R8(NAT_R8(v))), NAT_R8(NAT_R8(NAT_R8(v))), NAT_R8(NAT_R8(NAT_R8(v))), NAT_R8(NAT_R8(NAT_R8(v)))
#define NAT_IMG NAT_R8(NAT_R2K(kEmpty)), NAT_R2K(kEmpty)
__device__ __align__(1024) uint32_t g_wimg32[3 * kWBytes / 4] = {NAT_IMG, NAT_IMG, NAT_IMG};
static_assert(kWBytes / 4 == 9 * 2048, "initialiser");
__device__ __align__(128) uint32_t g_flag[64];
__device__ __forceinline__ uint32_t w2_offset() {
  uint32_t v;
  asm volatile("ld.relaxed.gpu.global.u32 %0, [%1];" : "=r"(v) : "l"(g_flag + 32) : "memory");
  return (1 + v) * kWBytes;
}

#define PROFS(id, wgid, slotid) do { } while (0)
#define PROF(wgid, slotid) do { } while (0)
#define PROF_DUMP(wgid) do { } while (0)

#define GT(slotid) do { } while (0)
#define GT_DUMP() do { } while (0)

__device__ __forceinline__ uint32_t smem_u32(const void* p) { return (uint32_t)__cvta_generic_to_shared(p); }

__device__ __forceinline__ void mbar_init(uint32_t bar, uint32_t count) {
  asm volatile("mbarrier.init.shared::cta.b64 [%0], %1;" ::"r"(bar), "r"(count) : "memory");
}
__device__ __forceinline__ void mbar_arrive(uint32_t bar) {
  asm volatile("mbarrier.arrive.shared::cta.b64 _, [%0];" ::"r"(bar) : "memory");
}
__device__ __forceinline__ void mbar_arrive_expect_tx(uint32_t bar, uint32_t bytes) {
  asm volatile("mbarrier.arrive.expect_tx.shared::cta.b64 _, [%0], %1;" ::"r"(bar), "r"(bytes) : "memory");
}
__device__ __forceinline__ void mbar_wait(uint32_t bar, uint32_t parity) {
  uint32_t ok;
  uint32_t it = 0;
  do {
    asm volatile(
        "{\n.reg .pred p;\n"
        "mbarrier.try_wait.parity.shared::cta.b64 p, [%1], %2;\n"
        "selp.u32 %0, 1, 0, p;\n}\n"
        : "=r"(ok)
        : "r"(bar), "r"(parity)
        : "memory");
    if (++it > (1u << 24)) break;
  } while (!ok);
}
__device__ __forceinline__ uint32_t mbar_test(uint32_t bar, uint32_t parity) {
  uint32_t ok;
  asm volatile("{\n.reg .pred p;\nmbarrier.test_wait.parity.shared::cta.b64 p, [%1], %2;\nselp.u32 %0, 1, 0, p;\n}\n"
               : "=r"(ok) : "r"(bar), "r"(parity) : "memory");
  return ok;
}
__device__ __forceinline__ void mbar_wait_if(uint32_t ok, uint32_t bar, uint32_t parity) {
  if (!__all_sync(0xffffffffu, ok)) mbar_wait(bar, parity);
}
__device__ __forceinline__ bool elect_one() {
  uint32_t r;
  asm volatile("{\n.reg .pred p;\nelect.sync _|p, 0xffffffff;\nselp.u32 %0, 1, 0, p;\n}\n" : "=r"(r));
  return r != 0;
}
__device__ __forceinline__ void nb_arrive(int id) { asm volatile("bar.arrive %0, 256;" ::"r"(id) : "memory"); }
__device__ __forceinline__ void nb_sync(int id) { asm volatile("bar.sync %0, 256;" ::"r"(id) : "memory"); }
__device__ __forceinline__ void nb_arrive_p(int id) { asm volatile("bar.arrive %0, 160;" ::"r"(id) : "memory"); }
__device__ __forceinline__ void nb_sync_p(int id) { asm volatile("bar.sync %0, 160;" ::"r"(id) : "memory"); }
__device__ __forceinline__ void fence_proxy_async() { asm volatile("fence.proxy.async.shared::cta;" ::: "memory"); }

__device__ __forceinline__ void tma_load_5d(uint32_t dst, const CUtensorMap* map, uint32_t bar, int c0, int c1, int c2,
                                            int c3, int c4) {
  asm volatile(
      "cp.async.bulk.tensor.5d.shared::cluster.global.tile.mbarrier::complete_tx::bytes "
      "[%0], [%1, {%3, %4, %5, %6, %7}], [%2];"
      ::"r"(dst), "l"((uint64_t)map), "r"(bar), "r"(c0), "r"(c1), "r"(c2), "r"(c3), "r"(c4)
      : "memory");
}
__device__ __forceinline__ void bulk_load(uint32_t dst, const void* src, uint32_t bytes, uint32_t bar) {
  asm volatile("cp.async.bulk.shared::cluster.global.mbarrier::complete_tx::bytes [%0], [%1], %2, [%3];"
               ::"r"(dst), "l"((uint64_t)src), "r"(bytes), "r"(bar)
               : "memory");
}

__device__ __forceinline__ void wg_fence() { asm volatile("wgmma.fence.sync.aligned;" ::: "memory"); }
__device__ __forceinline__ void wg_commit() { asm volatile("wgmma.commit_group.sync.aligned;" ::: "memory"); }
template <int N>
__device__ __forceinline__ void wg_wait() { asm volatile("wgmma.wait_group.sync.aligned %0;" ::"n"(N) : "memory"); }

template <int N>
__device__ __forceinline__ void fence_regs(float (&d)[N]) {
#pragma unroll
  for (int i = 0; i < N; i++) asm volatile("" : "+f"(d[i])::"memory");
}
template <int N>
__device__ __forceinline__ void keep_regs(uint32_t (&d)[N]) {
#pragma unroll
  for (int i = 0; i < N; i++) asm volatile("" : "+r"(d[i])::"memory");
}

__device__ __forceinline__ uint32_t pack_bf16(float lo, float hi) {
  uint32_t d;
  asm("cvt.rn.bf16x2.f32 %0, %1, %2;" : "=r"(d) : "f"(hi), "f"(lo));
  return d;
}
__device__ __forceinline__ float ex2(float x) {
  float y;
  asm("ex2.approx.ftz.f32 %0, %1;" : "=f"(y) : "f"(x));
  return y;
}
__device__ __forceinline__ float rcp_approx(float x) {
  float y;
  asm("rcp.approx.ftz.f32 %0, %1;" : "=f"(y) : "f"(x));
  return y;
}
__device__ __forceinline__ uint4 ldg128_nc(const void* p) {
  uint4 v;
  asm volatile("ld.global.nc.v4.u32 {%0,%1,%2,%3}, [%4];" : "=r"(v.x), "=r"(v.y), "=r"(v.z), "=r"(v.w) : "l"(p));
  return v;
}

__device__ __forceinline__ long long clk64() {
  long long c;
  asm volatile("mov.u64 %0, %clock64;" : "=l"(c)::"memory");
  return c;
}
__device__ __forceinline__ void sched_fence() { while (clk64() < 0) { } }

__device__ __forceinline__ uint64_t make_desc(uint32_t addr, uint32_t lbo, uint32_t sbo, uint32_t mode = 1) {
  return (uint64_t)((addr & 0x3FFFF) >> 4) | ((uint64_t)(lbo >> 4) << 16) | ((uint64_t)(sbo >> 4) << 32) |
         ((uint64_t)mode << 62);
}

template <int OFF, int NN>
__device__ __forceinline__ void wg_m192(float (&d)[NN], uint64_t desc_a, uint64_t desc_b, int scale_d) {
  asm volatile(
      "{\n.reg .pred p;\nsetp.ne.b32 p, %98, 0;\n"
      "wgmma.mma_async.sync.aligned.m64n192k16.f32.bf16.bf16 "
      "{%0,%1,%2,%3,%4,%5,%6,%7,%8,%9,%10,%11,%12,%13,%14,%15,"
      "%16,%17,%18,%19,%20,%21,%22,%23,%24,%25,%26,%27,%28,%29,%30,%31,"
      "%32,%33,%34,%35,%36,%37,%38,%39,%40,%41,%42,%43,%44,%45,%46,%47,"
      "%48,%49,%50,%51,%52,%53,%54,%55,%56,%57,%58,%59,%60,%61,%62,%63,"
      "%64,%65,%66,%67,%68,%69,%70,%71,%72,%73,%74,%75,%76,%77,%78,%79,"
      "%80,%81,%82,%83,%84,%85,%86,%87,%88,%89,%90,%91,%92,%93,%94,%95}, "
      "%96, %97, p, 1, 1, 0, 0;\n}\n"
      : "+f"(d[OFF + 0]), "+f"(d[OFF + 1]), "+f"(d[OFF + 2]), "+f"(d[OFF + 3]), "+f"(d[OFF + 4]), "+f"(d[OFF + 5]),
        "+f"(d[OFF + 6]), "+f"(d[OFF + 7]), "+f"(d[OFF + 8]), "+f"(d[OFF + 9]), "+f"(d[OFF + 10]), "+f"(d[OFF + 11]),
        "+f"(d[OFF + 12]), "+f"(d[OFF + 13]), "+f"(d[OFF + 14]), "+f"(d[OFF + 15]), "+f"(d[OFF + 16]), "+f"(d[OFF + 17]),
        "+f"(d[OFF + 18]), "+f"(d[OFF + 19]), "+f"(d[OFF + 20]), "+f"(d[OFF + 21]), "+f"(d[OFF + 22]), "+f"(d[OFF + 23]),
        "+f"(d[OFF + 24]), "+f"(d[OFF + 25]), "+f"(d[OFF + 26]), "+f"(d[OFF + 27]), "+f"(d[OFF + 28]), "+f"(d[OFF + 29]),
        "+f"(d[OFF + 30]), "+f"(d[OFF + 31]), "+f"(d[OFF + 32]), "+f"(d[OFF + 33]), "+f"(d[OFF + 34]), "+f"(d[OFF + 35]),
        "+f"(d[OFF + 36]), "+f"(d[OFF + 37]), "+f"(d[OFF + 38]), "+f"(d[OFF + 39]), "+f"(d[OFF + 40]), "+f"(d[OFF + 41]),
        "+f"(d[OFF + 42]), "+f"(d[OFF + 43]), "+f"(d[OFF + 44]), "+f"(d[OFF + 45]), "+f"(d[OFF + 46]), "+f"(d[OFF + 47]),
        "+f"(d[OFF + 48]), "+f"(d[OFF + 49]), "+f"(d[OFF + 50]), "+f"(d[OFF + 51]), "+f"(d[OFF + 52]), "+f"(d[OFF + 53]),
        "+f"(d[OFF + 54]), "+f"(d[OFF + 55]), "+f"(d[OFF + 56]), "+f"(d[OFF + 57]), "+f"(d[OFF + 58]), "+f"(d[OFF + 59]),
        "+f"(d[OFF + 60]), "+f"(d[OFF + 61]), "+f"(d[OFF + 62]), "+f"(d[OFF + 63]), "+f"(d[OFF + 64]), "+f"(d[OFF + 65]),
        "+f"(d[OFF + 66]), "+f"(d[OFF + 67]), "+f"(d[OFF + 68]), "+f"(d[OFF + 69]), "+f"(d[OFF + 70]), "+f"(d[OFF + 71]),
        "+f"(d[OFF + 72]), "+f"(d[OFF + 73]), "+f"(d[OFF + 74]), "+f"(d[OFF + 75]), "+f"(d[OFF + 76]), "+f"(d[OFF + 77]),
        "+f"(d[OFF + 78]), "+f"(d[OFF + 79]), "+f"(d[OFF + 80]), "+f"(d[OFF + 81]), "+f"(d[OFF + 82]), "+f"(d[OFF + 83]),
        "+f"(d[OFF + 84]), "+f"(d[OFF + 85]), "+f"(d[OFF + 86]), "+f"(d[OFF + 87]), "+f"(d[OFF + 88]), "+f"(d[OFF + 89]),
        "+f"(d[OFF + 90]), "+f"(d[OFF + 91]), "+f"(d[OFF + 92]), "+f"(d[OFF + 93]), "+f"(d[OFF + 94]), "+f"(d[OFF + 95])
      : "l"(desc_a), "l"(desc_b), "r"(scale_d));
}

template <int OFF, int NN>
__device__ __forceinline__ void wg_m192z(float (&d)[NN], uint64_t desc_a, uint64_t desc_b, int scale_d) {
  asm volatile(
      "{\n.reg .pred p;\nsetp.ne.b32 p, %98, 0;\n"
      "wgmma.mma_async.sync.aligned.m64n192k16.f32.bf16.bf16 "
      "{%0,%1,%2,%3,%4,%5,%6,%7,%8,%9,%10,%11,%12,%13,%14,%15,"
      "%16,%17,%18,%19,%20,%21,%22,%23,%24,%25,%26,%27,%28,%29,%30,%31,"
      "%32,%33,%34,%35,%36,%37,%38,%39,%40,%41,%42,%43,%44,%45,%46,%47,"
      "%48,%49,%50,%51,%52,%53,%54,%55,%56,%57,%58,%59,%60,%61,%62,%63,"
      "%64,%65,%66,%67,%68,%69,%70,%71,%72,%73,%74,%75,%76,%77,%78,%79,"
      "%80,%81,%82,%83,%84,%85,%86,%87,%88,%89,%90,%91,%92,%93,%94,%95}, "
      "%96, %97, p, 1, 1, 0, 0;\n}\n"
      : "=f"(d[OFF + 0]), "=f"(d[OFF + 1]), "=f"(d[OFF + 2]), "=f"(d[OFF + 3]), "=f"(d[OFF + 4]), "=f"(d[OFF + 5]),
        "=f"(d[OFF + 6]), "=f"(d[OFF + 7]), "=f"(d[OFF + 8]), "=f"(d[OFF + 9]), "=f"(d[OFF + 10]), "=f"(d[OFF + 11]),
        "=f"(d[OFF + 12]), "=f"(d[OFF + 13]), "=f"(d[OFF + 14]), "=f"(d[OFF + 15]), "=f"(d[OFF + 16]), "=f"(d[OFF + 17]),
        "=f"(d[OFF + 18]), "=f"(d[OFF + 19]), "=f"(d[OFF + 20]), "=f"(d[OFF + 21]), "=f"(d[OFF + 22]), "=f"(d[OFF + 23]),
        "=f"(d[OFF + 24]), "=f"(d[OFF + 25]), "=f"(d[OFF + 26]), "=f"(d[OFF + 27]), "=f"(d[OFF + 28]), "=f"(d[OFF + 29]),
        "=f"(d[OFF + 30]), "=f"(d[OFF + 31]), "=f"(d[OFF + 32]), "=f"(d[OFF + 33]), "=f"(d[OFF + 34]), "=f"(d[OFF + 35]),
        "=f"(d[OFF + 36]), "=f"(d[OFF + 37]), "=f"(d[OFF + 38]), "=f"(d[OFF + 39]), "=f"(d[OFF + 40]), "=f"(d[OFF + 41]),
        "=f"(d[OFF + 42]), "=f"(d[OFF + 43]), "=f"(d[OFF + 44]), "=f"(d[OFF + 45]), "=f"(d[OFF + 46]), "=f"(d[OFF + 47]),
        "=f"(d[OFF + 48]), "=f"(d[OFF + 49]), "=f"(d[OFF + 50]), "=f"(d[OFF + 51]), "=f"(d[OFF + 52]), "=f"(d[OFF + 53]),
        "=f"(d[OFF + 54]), "=f"(d[OFF + 55]), "=f"(d[OFF + 56]), "=f"(d[OFF + 57]), "=f"(d[OFF + 58]), "=f"(d[OFF + 59]),
        "=f"(d[OFF + 60]), "=f"(d[OFF + 61]), "=f"(d[OFF + 62]), "=f"(d[OFF + 63]), "=f"(d[OFF + 64]), "=f"(d[OFF + 65]),
        "=f"(d[OFF + 66]), "=f"(d[OFF + 67]), "=f"(d[OFF + 68]), "=f"(d[OFF + 69]), "=f"(d[OFF + 70]), "=f"(d[OFF + 71]),
        "=f"(d[OFF + 72]), "=f"(d[OFF + 73]), "=f"(d[OFF + 74]), "=f"(d[OFF + 75]), "=f"(d[OFF + 76]), "=f"(d[OFF + 77]),
        "=f"(d[OFF + 78]), "=f"(d[OFF + 79]), "=f"(d[OFF + 80]), "=f"(d[OFF + 81]), "=f"(d[OFF + 82]), "=f"(d[OFF + 83]),
        "=f"(d[OFF + 84]), "=f"(d[OFF + 85]), "=f"(d[OFF + 86]), "=f"(d[OFF + 87]), "=f"(d[OFF + 88]), "=f"(d[OFF + 89]),
        "=f"(d[OFF + 90]), "=f"(d[OFF + 91]), "=f"(d[OFF + 92]), "=f"(d[OFF + 93]), "=f"(d[OFF + 94]), "=f"(d[OFF + 95])
      : "l"(desc_a), "l"(desc_b), "r"(scale_d));
}

template <int OFF, int NN>
__device__ __forceinline__ void wg_m96t(float (&d)[NN], uint64_t desc_a, uint64_t desc_b, int scale_d) {
  asm volatile(
      "{\n.reg .pred p;\nsetp.ne.b32 p, %50, 0;\n"
      "wgmma.mma_async.sync.aligned.m64n96k16.f32.bf16.bf16 "
      "{%0,%1,%2,%3,%4,%5,%6,%7,%8,%9,%10,%11,%12,%13,%14,%15,"
      "%16,%17,%18,%19,%20,%21,%22,%23,%24,%25,%26,%27,%28,%29,%30,%31,"
      "%32,%33,%34,%35,%36,%37,%38,%39,%40,%41,%42,%43,%44,%45,%46,%47}, "
      "%48, %49, p, 1, 1, 0, 1;\n}\n"
      : "+f"(d[OFF + 0]), "+f"(d[OFF + 1]), "+f"(d[OFF + 2]), "+f"(d[OFF + 3]), "+f"(d[OFF + 4]), "+f"(d[OFF + 5]),
        "+f"(d[OFF + 6]), "+f"(d[OFF + 7]), "+f"(d[OFF + 8]), "+f"(d[OFF + 9]), "+f"(d[OFF + 10]), "+f"(d[OFF + 11]),
        "+f"(d[OFF + 12]), "+f"(d[OFF + 13]), "+f"(d[OFF + 14]), "+f"(d[OFF + 15]), "+f"(d[OFF + 16]), "+f"(d[OFF + 17]),
        "+f"(d[OFF + 18]), "+f"(d[OFF + 19]), "+f"(d[OFF + 20]), "+f"(d[OFF + 21]), "+f"(d[OFF + 22]), "+f"(d[OFF + 23]),
        "+f"(d[OFF + 24]), "+f"(d[OFF + 25]), "+f"(d[OFF + 26]), "+f"(d[OFF + 27]), "+f"(d[OFF + 28]), "+f"(d[OFF + 29]),
        "+f"(d[OFF + 30]), "+f"(d[OFF + 31]), "+f"(d[OFF + 32]), "+f"(d[OFF + 33]), "+f"(d[OFF + 34]), "+f"(d[OFF + 35]),
        "+f"(d[OFF + 36]), "+f"(d[OFF + 37]), "+f"(d[OFF + 38]), "+f"(d[OFF + 39]), "+f"(d[OFF + 40]), "+f"(d[OFF + 41]),
        "+f"(d[OFF + 42]), "+f"(d[OFF + 43]), "+f"(d[OFF + 44]), "+f"(d[OFF + 45]), "+f"(d[OFF + 46]), "+f"(d[OFF + 47])
      : "l"(desc_a), "l"(desc_b), "r"(scale_d));
}

template <int OFF, int NN>
__device__ __forceinline__ void wg_m96tz(float (&d)[NN], uint64_t desc_a, uint64_t desc_b, int scale_d) {
  asm volatile(
      "{\n.reg .pred p;\nsetp.ne.b32 p, %50, 0;\n"
      "wgmma.mma_async.sync.aligned.m64n96k16.f32.bf16.bf16 "
      "{%0,%1,%2,%3,%4,%5,%6,%7,%8,%9,%10,%11,%12,%13,%14,%15,"
      "%16,%17,%18,%19,%20,%21,%22,%23,%24,%25,%26,%27,%28,%29,%30,%31,"
      "%32,%33,%34,%35,%36,%37,%38,%39,%40,%41,%42,%43,%44,%45,%46,%47}, "
      "%48, %49, p, 1, 1, 0, 1;\n}\n"
      : "=f"(d[OFF + 0]), "=f"(d[OFF + 1]), "=f"(d[OFF + 2]), "=f"(d[OFF + 3]), "=f"(d[OFF + 4]), "=f"(d[OFF + 5]),
        "=f"(d[OFF + 6]), "=f"(d[OFF + 7]), "=f"(d[OFF + 8]), "=f"(d[OFF + 9]), "=f"(d[OFF + 10]), "=f"(d[OFF + 11]),
        "=f"(d[OFF + 12]), "=f"(d[OFF + 13]), "=f"(d[OFF + 14]), "=f"(d[OFF + 15]), "=f"(d[OFF + 16]), "=f"(d[OFF + 17]),
        "=f"(d[OFF + 18]), "=f"(d[OFF + 19]), "=f"(d[OFF + 20]), "=f"(d[OFF + 21]), "=f"(d[OFF + 22]), "=f"(d[OFF + 23]),
        "=f"(d[OFF + 24]), "=f"(d[OFF + 25]), "=f"(d[OFF + 26]), "=f"(d[OFF + 27]), "=f"(d[OFF + 28]), "=f"(d[OFF + 29]),
        "=f"(d[OFF + 30]), "=f"(d[OFF + 31]), "=f"(d[OFF + 32]), "=f"(d[OFF + 33]), "=f"(d[OFF + 34]), "=f"(d[OFF + 35]),
        "=f"(d[OFF + 36]), "=f"(d[OFF + 37]), "=f"(d[OFF + 38]), "=f"(d[OFF + 39]), "=f"(d[OFF + 40]), "=f"(d[OFF + 41]),
        "=f"(d[OFF + 42]), "=f"(d[OFF + 43]), "=f"(d[OFF + 44]), "=f"(d[OFF + 45]), "=f"(d[OFF + 46]), "=f"(d[OFF + 47])
      : "l"(desc_a), "l"(desc_b), "r"(scale_d));
}

template <int OFF, int NN>
__device__ __forceinline__ void wg_d96(float (&d)[NN], uint32_t a0, uint32_t a1, uint32_t a2, uint32_t a3,
                                       uint64_t desc_b, int scale_d) {
  asm volatile(
      "{\n.reg .pred p;\nsetp.ne.b32 p, %53, 0;\n"
      "wgmma.mma_async.sync.aligned.m64n96k16.f32.bf16.bf16 "
      "{%0,%1,%2,%3,%4,%5,%6,%7,%8,%9,%10,%11,%12,%13,%14,%15,"
      "%16,%17,%18,%19,%20,%21,%22,%23,%24,%25,%26,%27,%28,%29,%30,%31,"
      "%32,%33,%34,%35,%36,%37,%38,%39,%40,%41,%42,%43,%44,%45,%46,%47}, "
      "{%48,%49,%50,%51}, %52, p, 1, 1, 0;\n}\n"
      : "+f"(d[OFF + 0]), "+f"(d[OFF + 1]), "+f"(d[OFF + 2]), "+f"(d[OFF + 3]), "+f"(d[OFF + 4]), "+f"(d[OFF + 5]),
        "+f"(d[OFF + 6]), "+f"(d[OFF + 7]), "+f"(d[OFF + 8]), "+f"(d[OFF + 9]), "+f"(d[OFF + 10]), "+f"(d[OFF + 11]),
        "+f"(d[OFF + 12]), "+f"(d[OFF + 13]), "+f"(d[OFF + 14]), "+f"(d[OFF + 15]), "+f"(d[OFF + 16]), "+f"(d[OFF + 17]),
        "+f"(d[OFF + 18]), "+f"(d[OFF + 19]), "+f"(d[OFF + 20]), "+f"(d[OFF + 21]), "+f"(d[OFF + 22]), "+f"(d[OFF + 23]),
        "+f"(d[OFF + 24]), "+f"(d[OFF + 25]), "+f"(d[OFF + 26]), "+f"(d[OFF + 27]), "+f"(d[OFF + 28]), "+f"(d[OFF + 29]),
        "+f"(d[OFF + 30]), "+f"(d[OFF + 31]), "+f"(d[OFF + 32]), "+f"(d[OFF + 33]), "+f"(d[OFF + 34]), "+f"(d[OFF + 35]),
        "+f"(d[OFF + 36]), "+f"(d[OFF + 37]), "+f"(d[OFF + 38]), "+f"(d[OFF + 39]), "+f"(d[OFF + 40]), "+f"(d[OFF + 41]),
        "+f"(d[OFF + 42]), "+f"(d[OFF + 43]), "+f"(d[OFF + 44]), "+f"(d[OFF + 45]), "+f"(d[OFF + 46]), "+f"(d[OFF + 47])
      : "r"(a0), "r"(a1), "r"(a2), "r"(a3), "l"(desc_b), "r"(scale_d));
}

template <int OFF, int NN>
__device__ __forceinline__ void wg_d96z(float (&d)[NN], uint32_t a0, uint32_t a1, uint32_t a2, uint32_t a3,
                                       uint64_t desc_b, int scale_d) {
  asm volatile(
      "{\n.reg .pred p;\nsetp.ne.b32 p, %53, 0;\n"
      "wgmma.mma_async.sync.aligned.m64n96k16.f32.bf16.bf16 "
      "{%0,%1,%2,%3,%4,%5,%6,%7,%8,%9,%10,%11,%12,%13,%14,%15,"
      "%16,%17,%18,%19,%20,%21,%22,%23,%24,%25,%26,%27,%28,%29,%30,%31,"
      "%32,%33,%34,%35,%36,%37,%38,%39,%40,%41,%42,%43,%44,%45,%46,%47}, "
      "{%48,%49,%50,%51}, %52, p, 1, 1, 0;\n}\n"
      : "=f"(d[OFF + 0]), "=f"(d[OFF + 1]), "=f"(d[OFF + 2]), "=f"(d[OFF + 3]), "=f"(d[OFF + 4]), "=f"(d[OFF + 5]),
        "=f"(d[OFF + 6]), "=f"(d[OFF + 7]), "=f"(d[OFF + 8]), "=f"(d[OFF + 9]), "=f"(d[OFF + 10]), "=f"(d[OFF + 11]),
        "=f"(d[OFF + 12]), "=f"(d[OFF + 13]), "=f"(d[OFF + 14]), "=f"(d[OFF + 15]), "=f"(d[OFF + 16]), "=f"(d[OFF + 17]),
        "=f"(d[OFF + 18]), "=f"(d[OFF + 19]), "=f"(d[OFF + 20]), "=f"(d[OFF + 21]), "=f"(d[OFF + 22]), "=f"(d[OFF + 23]),
        "=f"(d[OFF + 24]), "=f"(d[OFF + 25]), "=f"(d[OFF + 26]), "=f"(d[OFF + 27]), "=f"(d[OFF + 28]), "=f"(d[OFF + 29]),
        "=f"(d[OFF + 30]), "=f"(d[OFF + 31]), "=f"(d[OFF + 32]), "=f"(d[OFF + 33]), "=f"(d[OFF + 34]), "=f"(d[OFF + 35]),
        "=f"(d[OFF + 36]), "=f"(d[OFF + 37]), "=f"(d[OFF + 38]), "=f"(d[OFF + 39]), "=f"(d[OFF + 40]), "=f"(d[OFF + 41]),
        "=f"(d[OFF + 42]), "=f"(d[OFF + 43]), "=f"(d[OFF + 44]), "=f"(d[OFF + 45]), "=f"(d[OFF + 46]), "=f"(d[OFF + 47])
      : "r"(a0), "r"(a1), "r"(a2), "r"(a3), "l"(desc_b), "r"(scale_d));
}

template <int OFF, int NN>
__device__ __forceinline__ void wg_s104(float (&d)[NN], uint32_t a0, uint32_t a1, uint32_t a2, uint32_t a3,
                                       uint64_t desc_b, int scale_d, uint32_t meta) {
  asm volatile(
      "{\n.reg .pred p;\nsetp.ne.b32 p, %57, 0;\n"
      "wgmma.mma_async.sp.sync.aligned.m64n104k32.f32.bf16.bf16 "
      "{%0,%1,%2,%3,%4,%5,%6,%7,%8,%9,%10,%11,%12,%13,%14,%15,"
      "%16,%17,%18,%19,%20,%21,%22,%23,%24,%25,%26,%27,%28,%29,%30,%31,"
      "%32,%33,%34,%35,%36,%37,%38,%39,%40,%41,%42,%43,%44,%45,%46,%47,"
      "%48,%49,%50,%51}, "
      "{%52,%53,%54,%55}, %56, %58, 0, p, 1, 1, 0;\n}\n"
      : "+f"(d[OFF + 0]), "+f"(d[OFF + 1]), "+f"(d[OFF + 2]), "+f"(d[OFF + 3]), "+f"(d[OFF + 4]), "+f"(d[OFF + 5]),
        "+f"(d[OFF + 6]), "+f"(d[OFF + 7]), "+f"(d[OFF + 8]), "+f"(d[OFF + 9]), "+f"(d[OFF + 10]), "+f"(d[OFF + 11]),
        "+f"(d[OFF + 12]), "+f"(d[OFF + 13]), "+f"(d[OFF + 14]), "+f"(d[OFF + 15]), "+f"(d[OFF + 16]), "+f"(d[OFF + 17]),
        "+f"(d[OFF + 18]), "+f"(d[OFF + 19]), "+f"(d[OFF + 20]), "+f"(d[OFF + 21]), "+f"(d[OFF + 22]), "+f"(d[OFF + 23]),
        "+f"(d[OFF + 24]), "+f"(d[OFF + 25]), "+f"(d[OFF + 26]), "+f"(d[OFF + 27]), "+f"(d[OFF + 28]), "+f"(d[OFF + 29]),
        "+f"(d[OFF + 30]), "+f"(d[OFF + 31]), "+f"(d[OFF + 32]), "+f"(d[OFF + 33]), "+f"(d[OFF + 34]), "+f"(d[OFF + 35]),
        "+f"(d[OFF + 36]), "+f"(d[OFF + 37]), "+f"(d[OFF + 38]), "+f"(d[OFF + 39]), "+f"(d[OFF + 40]), "+f"(d[OFF + 41]),
        "+f"(d[OFF + 42]), "+f"(d[OFF + 43]), "+f"(d[OFF + 44]), "+f"(d[OFF + 45]), "+f"(d[OFF + 46]), "+f"(d[OFF + 47]),
        "+f"(d[OFF + 48]), "+f"(d[OFF + 49]), "+f"(d[OFF + 50]), "+f"(d[OFF + 51])
      : "r"(a0), "r"(a1), "r"(a2), "r"(a3), "l"(desc_b), "r"(scale_d), "r"(meta));
}

template <int OFF, int NN>
__device__ __forceinline__ void wg_s104z(float (&d)[NN], uint32_t a0, uint32_t a1, uint32_t a2, uint32_t a3,
                                       uint64_t desc_b, int scale_d, uint32_t meta) {
  asm volatile(
      "{\n.reg .pred p;\nsetp.ne.b32 p, %57, 0;\n"
      "wgmma.mma_async.sp.sync.aligned.m64n104k32.f32.bf16.bf16 "
      "{%0,%1,%2,%3,%4,%5,%6,%7,%8,%9,%10,%11,%12,%13,%14,%15,"
      "%16,%17,%18,%19,%20,%21,%22,%23,%24,%25,%26,%27,%28,%29,%30,%31,"
      "%32,%33,%34,%35,%36,%37,%38,%39,%40,%41,%42,%43,%44,%45,%46,%47,"
      "%48,%49,%50,%51}, "
      "{%52,%53,%54,%55}, %56, %58, 0, p, 1, 1, 0;\n}\n"
      : "=f"(d[OFF + 0]), "=f"(d[OFF + 1]), "=f"(d[OFF + 2]), "=f"(d[OFF + 3]), "=f"(d[OFF + 4]), "=f"(d[OFF + 5]),
        "=f"(d[OFF + 6]), "=f"(d[OFF + 7]), "=f"(d[OFF + 8]), "=f"(d[OFF + 9]), "=f"(d[OFF + 10]), "=f"(d[OFF + 11]),
        "=f"(d[OFF + 12]), "=f"(d[OFF + 13]), "=f"(d[OFF + 14]), "=f"(d[OFF + 15]), "=f"(d[OFF + 16]), "=f"(d[OFF + 17]),
        "=f"(d[OFF + 18]), "=f"(d[OFF + 19]), "=f"(d[OFF + 20]), "=f"(d[OFF + 21]), "=f"(d[OFF + 22]), "=f"(d[OFF + 23]),
        "=f"(d[OFF + 24]), "=f"(d[OFF + 25]), "=f"(d[OFF + 26]), "=f"(d[OFF + 27]), "=f"(d[OFF + 28]), "=f"(d[OFF + 29]),
        "=f"(d[OFF + 30]), "=f"(d[OFF + 31]), "=f"(d[OFF + 32]), "=f"(d[OFF + 33]), "=f"(d[OFF + 34]), "=f"(d[OFF + 35]),
        "=f"(d[OFF + 36]), "=f"(d[OFF + 37]), "=f"(d[OFF + 38]), "=f"(d[OFF + 39]), "=f"(d[OFF + 40]), "=f"(d[OFF + 41]),
        "=f"(d[OFF + 42]), "=f"(d[OFF + 43]), "=f"(d[OFF + 44]), "=f"(d[OFF + 45]), "=f"(d[OFF + 46]), "=f"(d[OFF + 47]),
        "=f"(d[OFF + 48]), "=f"(d[OFF + 49]), "=f"(d[OFF + 50]), "=f"(d[OFF + 51])
      : "r"(a0), "r"(a1), "r"(a2), "r"(a3), "l"(desc_b), "r"(scale_d), "r"(meta));
}

template <int OFF, int NN>
__device__ __forceinline__ void wg_s48(float (&d)[NN], uint32_t a0, uint32_t a1, uint32_t a2, uint32_t a3,
                                       uint64_t desc_b, int scale_d, uint32_t meta) {
  asm volatile(
      "{\n.reg .pred p;\nsetp.ne.b32 p, %29, 0;\n"
      "wgmma.mma_async.sp.sync.aligned.m64n48k32.f32.bf16.bf16 "
      "{%0,%1,%2,%3,%4,%5,%6,%7,%8,%9,%10,%11,%12,%13,%14,%15,"
      "%16,%17,%18,%19,%20,%21,%22,%23}, "
      "{%24,%25,%26,%27}, %28, %30, 0, p, 1, 1, 0;\n}\n"
      : "+f"(d[OFF + 0]), "+f"(d[OFF + 1]), "+f"(d[OFF + 2]), "+f"(d[OFF + 3]), "+f"(d[OFF + 4]), "+f"(d[OFF + 5]),
        "+f"(d[OFF + 6]), "+f"(d[OFF + 7]), "+f"(d[OFF + 8]), "+f"(d[OFF + 9]), "+f"(d[OFF + 10]), "+f"(d[OFF + 11]),
        "+f"(d[OFF + 12]), "+f"(d[OFF + 13]), "+f"(d[OFF + 14]), "+f"(d[OFF + 15]), "+f"(d[OFF + 16]), "+f"(d[OFF + 17]),
        "+f"(d[OFF + 18]), "+f"(d[OFF + 19]), "+f"(d[OFF + 20]), "+f"(d[OFF + 21]), "+f"(d[OFF + 22]), "+f"(d[OFF + 23])
      : "r"(a0), "r"(a1), "r"(a2), "r"(a3), "l"(desc_b), "r"(scale_d), "r"(meta));
}

template <int OFF, int NN>
__device__ __forceinline__ void wg_s48z(float (&d)[NN], uint32_t a0, uint32_t a1, uint32_t a2, uint32_t a3,
                                       uint64_t desc_b, int scale_d, uint32_t meta) {
  asm volatile(
      "{\n.reg .pred p;\nsetp.ne.b32 p, %29, 0;\n"
      "wgmma.mma_async.sp.sync.aligned.m64n48k32.f32.bf16.bf16 "
      "{%0,%1,%2,%3,%4,%5,%6,%7,%8,%9,%10,%11,%12,%13,%14,%15,"
      "%16,%17,%18,%19,%20,%21,%22,%23}, "
      "{%24,%25,%26,%27}, %28, %30, 0, p, 1, 1, 0;\n}\n"
      : "=f"(d[OFF + 0]), "=f"(d[OFF + 1]), "=f"(d[OFF + 2]), "=f"(d[OFF + 3]), "=f"(d[OFF + 4]), "=f"(d[OFF + 5]),
        "=f"(d[OFF + 6]), "=f"(d[OFF + 7]), "=f"(d[OFF + 8]), "=f"(d[OFF + 9]), "=f"(d[OFF + 10]), "=f"(d[OFF + 11]),
        "=f"(d[OFF + 12]), "=f"(d[OFF + 13]), "=f"(d[OFF + 14]), "=f"(d[OFF + 15]), "=f"(d[OFF + 16]), "=f"(d[OFF + 17]),
        "=f"(d[OFF + 18]), "=f"(d[OFF + 19]), "=f"(d[OFF + 20]), "=f"(d[OFF + 21]), "=f"(d[OFF + 22]), "=f"(d[OFF + 23])
      : "r"(a0), "r"(a1), "r"(a2), "r"(a3), "l"(desc_b), "r"(scale_d), "r"(meta));
}

template <int OFF, int NN>
__device__ __forceinline__ void wg_s56(float (&d)[NN], uint32_t a0, uint32_t a1, uint32_t a2, uint32_t a3,
                                       uint64_t desc_b, int scale_d, uint32_t meta) {
  asm volatile(
      "{\n.reg .pred p;\nsetp.ne.b32 p, %33, 0;\n"
      "wgmma.mma_async.sp.sync.aligned.m64n56k32.f32.bf16.bf16 "
      "{%0,%1,%2,%3,%4,%5,%6,%7,%8,%9,%10,%11,%12,%13,%14,%15,"
      "%16,%17,%18,%19,%20,%21,%22,%23,%24,%25,%26,%27}, "
      "{%28,%29,%30,%31}, %32, %34, 0, p, 1, 1, 0;\n}\n"
      : "+f"(d[OFF + 0]), "+f"(d[OFF + 1]), "+f"(d[OFF + 2]), "+f"(d[OFF + 3]), "+f"(d[OFF + 4]), "+f"(d[OFF + 5]),
        "+f"(d[OFF + 6]), "+f"(d[OFF + 7]), "+f"(d[OFF + 8]), "+f"(d[OFF + 9]), "+f"(d[OFF + 10]), "+f"(d[OFF + 11]),
        "+f"(d[OFF + 12]), "+f"(d[OFF + 13]), "+f"(d[OFF + 14]), "+f"(d[OFF + 15]), "+f"(d[OFF + 16]), "+f"(d[OFF + 17]),
        "+f"(d[OFF + 18]), "+f"(d[OFF + 19]), "+f"(d[OFF + 20]), "+f"(d[OFF + 21]), "+f"(d[OFF + 22]), "+f"(d[OFF + 23]),
        "+f"(d[OFF + 24]), "+f"(d[OFF + 25]), "+f"(d[OFF + 26]), "+f"(d[OFF + 27])
      : "r"(a0), "r"(a1), "r"(a2), "r"(a3), "l"(desc_b), "r"(scale_d), "r"(meta));
}

template <int OFF, int NN>
__device__ __forceinline__ void wg_s56z(float (&d)[NN], uint32_t a0, uint32_t a1, uint32_t a2, uint32_t a3,
                                       uint64_t desc_b, int scale_d, uint32_t meta) {
  asm volatile(
      "{\n.reg .pred p;\nsetp.ne.b32 p, %33, 0;\n"
      "wgmma.mma_async.sp.sync.aligned.m64n56k32.f32.bf16.bf16 "
      "{%0,%1,%2,%3,%4,%5,%6,%7,%8,%9,%10,%11,%12,%13,%14,%15,"
      "%16,%17,%18,%19,%20,%21,%22,%23,%24,%25,%26,%27}, "
      "{%28,%29,%30,%31}, %32, %34, 0, p, 1, 1, 0;\n}\n"
      : "=f"(d[OFF + 0]), "=f"(d[OFF + 1]), "=f"(d[OFF + 2]), "=f"(d[OFF + 3]), "=f"(d[OFF + 4]), "=f"(d[OFF + 5]),
        "=f"(d[OFF + 6]), "=f"(d[OFF + 7]), "=f"(d[OFF + 8]), "=f"(d[OFF + 9]), "=f"(d[OFF + 10]), "=f"(d[OFF + 11]),
        "=f"(d[OFF + 12]), "=f"(d[OFF + 13]), "=f"(d[OFF + 14]), "=f"(d[OFF + 15]), "=f"(d[OFF + 16]), "=f"(d[OFF + 17]),
        "=f"(d[OFF + 18]), "=f"(d[OFF + 19]), "=f"(d[OFF + 20]), "=f"(d[OFF + 21]), "=f"(d[OFF + 22]), "=f"(d[OFF + 23]),
        "=f"(d[OFF + 24]), "=f"(d[OFF + 25]), "=f"(d[OFF + 26]), "=f"(d[OFF + 27])
      : "r"(a0), "r"(a1), "r"(a2), "r"(a3), "l"(desc_b), "r"(scale_d), "r"(meta));
}

template <int OFF, int NN>
__device__ __forceinline__ void wg_s64t(float (&d)[NN], uint32_t a0, uint32_t a1, uint32_t a2, uint32_t a3,
                                       uint64_t desc_b, int scale_d, uint32_t meta) {
  asm volatile(
      "{\n.reg .pred p;\nsetp.ne.b32 p, %37, 0;\n"
      "wgmma.mma_async.sp.sync.aligned.m64n64k32.f32.bf16.bf16 "
      "{%0,%1,%2,%3,%4,%5,%6,%7,%8,%9,%10,%11,%12,%13,%14,%15,"
      "%16,%17,%18,%19,%20,%21,%22,%23,%24,%25,%26,%27,%28,%29,%30,%31}, "
      "{%32,%33,%34,%35}, %36, %38, 0, p, 1, 1, 1;\n}\n"
      : "+f"(d[OFF + 0]), "+f"(d[OFF + 1]), "+f"(d[OFF + 2]), "+f"(d[OFF + 3]), "+f"(d[OFF + 4]), "+f"(d[OFF + 5]),
        "+f"(d[OFF + 6]), "+f"(d[OFF + 7]), "+f"(d[OFF + 8]), "+f"(d[OFF + 9]), "+f"(d[OFF + 10]), "+f"(d[OFF + 11]),
        "+f"(d[OFF + 12]), "+f"(d[OFF + 13]), "+f"(d[OFF + 14]), "+f"(d[OFF + 15]), "+f"(d[OFF + 16]), "+f"(d[OFF + 17]),
        "+f"(d[OFF + 18]), "+f"(d[OFF + 19]), "+f"(d[OFF + 20]), "+f"(d[OFF + 21]), "+f"(d[OFF + 22]), "+f"(d[OFF + 23]),
        "+f"(d[OFF + 24]), "+f"(d[OFF + 25]), "+f"(d[OFF + 26]), "+f"(d[OFF + 27]), "+f"(d[OFF + 28]), "+f"(d[OFF + 29]),
        "+f"(d[OFF + 30]), "+f"(d[OFF + 31])
      : "r"(a0), "r"(a1), "r"(a2), "r"(a3), "l"(desc_b), "r"(scale_d), "r"(meta));
}

template <int OFF, int NN>
__device__ __forceinline__ void wg_s64t1(float (&d)[NN], uint32_t a0, uint32_t a1, uint32_t a2, uint32_t a3,
                                       uint64_t desc_b, int scale_d, uint32_t meta) {
  asm volatile(
      "{\n.reg .pred p;\nsetp.ne.b32 p, %37, 0;\n"
      "wgmma.mma_async.sp.sync.aligned.m64n64k32.f32.bf16.bf16 "
      "{%0,%1,%2,%3,%4,%5,%6,%7,%8,%9,%10,%11,%12,%13,%14,%15,"
      "%16,%17,%18,%19,%20,%21,%22,%23,%24,%25,%26,%27,%28,%29,%30,%31}, "
      "{%32,%33,%34,%35}, %36, %38, 1, p, 1, 1, 1;\n}\n"
      : "+f"(d[OFF + 0]), "+f"(d[OFF + 1]), "+f"(d[OFF + 2]), "+f"(d[OFF + 3]), "+f"(d[OFF + 4]), "+f"(d[OFF + 5]),
        "+f"(d[OFF + 6]), "+f"(d[OFF + 7]), "+f"(d[OFF + 8]), "+f"(d[OFF + 9]), "+f"(d[OFF + 10]), "+f"(d[OFF + 11]),
        "+f"(d[OFF + 12]), "+f"(d[OFF + 13]), "+f"(d[OFF + 14]), "+f"(d[OFF + 15]), "+f"(d[OFF + 16]), "+f"(d[OFF + 17]),
        "+f"(d[OFF + 18]), "+f"(d[OFF + 19]), "+f"(d[OFF + 20]), "+f"(d[OFF + 21]), "+f"(d[OFF + 22]), "+f"(d[OFF + 23]),
        "+f"(d[OFF + 24]), "+f"(d[OFF + 25]), "+f"(d[OFF + 26]), "+f"(d[OFF + 27]), "+f"(d[OFF + 28]), "+f"(d[OFF + 29]),
        "+f"(d[OFF + 30]), "+f"(d[OFF + 31])
      : "r"(a0), "r"(a1), "r"(a2), "r"(a3), "l"(desc_b), "r"(scale_d), "r"(meta));
}

template <int OFF, int NN>
__device__ __forceinline__ void wg_s64tz(float (&d)[NN], uint32_t a0, uint32_t a1, uint32_t a2, uint32_t a3,
                                       uint64_t desc_b, int scale_d, uint32_t meta) {
  asm volatile(
      "{\n.reg .pred p;\nsetp.ne.b32 p, %37, 0;\n"
      "wgmma.mma_async.sp.sync.aligned.m64n64k32.f32.bf16.bf16 "
      "{%0,%1,%2,%3,%4,%5,%6,%7,%8,%9,%10,%11,%12,%13,%14,%15,"
      "%16,%17,%18,%19,%20,%21,%22,%23,%24,%25,%26,%27,%28,%29,%30,%31}, "
      "{%32,%33,%34,%35}, %36, %38, 0, p, 1, 1, 1;\n}\n"
      : "=f"(d[OFF + 0]), "=f"(d[OFF + 1]), "=f"(d[OFF + 2]), "=f"(d[OFF + 3]), "=f"(d[OFF + 4]), "=f"(d[OFF + 5]),
        "=f"(d[OFF + 6]), "=f"(d[OFF + 7]), "=f"(d[OFF + 8]), "=f"(d[OFF + 9]), "=f"(d[OFF + 10]), "=f"(d[OFF + 11]),
        "=f"(d[OFF + 12]), "=f"(d[OFF + 13]), "=f"(d[OFF + 14]), "=f"(d[OFF + 15]), "=f"(d[OFF + 16]), "=f"(d[OFF + 17]),
        "=f"(d[OFF + 18]), "=f"(d[OFF + 19]), "=f"(d[OFF + 20]), "=f"(d[OFF + 21]), "=f"(d[OFF + 22]), "=f"(d[OFF + 23]),
        "=f"(d[OFF + 24]), "=f"(d[OFF + 25]), "=f"(d[OFF + 26]), "=f"(d[OFF + 27]), "=f"(d[OFF + 28]), "=f"(d[OFF + 29]),
        "=f"(d[OFF + 30]), "=f"(d[OFF + 31])
      : "r"(a0), "r"(a1), "r"(a2), "r"(a3), "l"(desc_b), "r"(scale_d), "r"(meta));
}

__device__ __forceinline__ int g2_inv(int ch) { return 32 * (ch >> 5) + 8 * ((ch >> 1) & 3) + 2 * ((ch >> 3) & 3) + (ch & 1); }
__host__ __device__ __forceinline__ uint32_t wimg_off(int n, int k) {
  return (uint32_t)(k >> 6) * kWChunk + (uint32_t)n * 128 + (uint32_t)((((k & 63) >> 3) ^ (n & 7)) << 4) + (k & 7) * 2;
}
__host__ __device__ constexpr int w2piece(int h, int c) { return c == 2 ? 2 + h : 4 * h + c; }
__device__ __forceinline__ uint32_t w2img_off(int n, int k) { return wimg_off(n % 96, k & 63) + w2piece(n >= 96, k >> 6) * (kWChunk / 2); }
__device__ __forceinline__ int qpix(int par, int t) {
  const int a = 2 * t + 13 * par - 6, b = t + 112 * par;
  return par ? min(a, b) : max(a, b);
}
__device__ __forceinline__ int woff(int par, int i, int r) {
  const int a = 99 * par + 6 - 8 * i;
  return par ? min(r, a) : max(r, a);
}

__device__ __forceinline__ void mma16816(float (&c)[4], uint32_t a0, uint32_t a1, uint32_t a2, uint32_t a3, uint32_t b0,
                                         uint32_t b1) {
  asm volatile(
      "mma.sync.aligned.m16n8k16.row.col.f32.bf16.bf16.f32 {%0,%1,%2,%3}, {%4,%5,%6,%7}, {%8,%9}, {%0,%1,%2,%3};"
      : "+f"(c[0]), "+f"(c[1]), "+f"(c[2]), "+f"(c[3])
      : "r"(a0), "r"(a1), "r"(a2), "r"(a3), "r"(b0), "r"(b1));
}

__device__ __forceinline__ void fold_w1(const int u, const __nv_bfloat16* __restrict__ wqkv, uint8_t* wimg) {
  const int g = (threadIdx.x >> 2) & 7, l = threadIdx.x & 3;
  const int m0 = (u / 12) * 16, s = u % 12;
  uint4 A[12], B[12];
  const __nv_bfloat16* arow = wqkv + (m0 + 4 * (g >> 1) + (g & 1)) * 576 + 192 + 8 * l;
  const __nv_bfloat16* brow = wqkv + (16 * s + 4 * (g >> 1) + (g & 1)) * 576 + 8 * l;
#pragma unroll
  for (int i = 0; i < 12; i++) {
    A[i] = ldg128_nc(arow + (i & 1) * 2 * 576 + 32 * (i >> 1));
    B[i] = ldg128_nc(brow + (i & 1) * 2 * 576 + 32 * (i >> 1));
  }
  sched_fence();
  uint8_t* dst = wimg + wimg_off(m0 + g, 16 * s + 4 * l);
  float acc[4][4];
#pragma unroll
  for (int j = 0; j < 16; j++) acc[j >> 2][j & 3] = 0.f;
#pragma unroll
  for (int i = 0; i < 6; i++) {
    const uint4 &a0 = A[2 * i], &a1 = A[2 * i + 1];
#pragma unroll
    for (int nb = 0; nb < 2; nb++) {
      mma16816(acc[2 * nb], a0.x, a1.x, a0.y, a1.y, B[2 * i + nb].x, B[2 * i + nb].y);
      mma16816(acc[2 * nb + 1], a0.z, a1.z, a0.w, a1.w, B[2 * i + nb].z, B[2 * i + nb].w);
    }
  }
#pragma unroll
  for (int j = 0; j < 2; j++) {
    const uint2 v = make_uint2(pack_bf16((acc[0][2 * j] + acc[1][2 * j]) * kAlpha, (acc[0][2 * j + 1] + acc[1][2 * j + 1]) * kAlpha),
                               pack_bf16((acc[2][2 * j] + acc[3][2 * j]) * kAlpha, (acc[2][2 * j + 1] + acc[3][2 * j + 1]) * kAlpha));
    asm volatile("st.relaxed.gpu.global.v2.u32 [%0], {%1,%2};" ::"l"(dst + j * 1024), "r"(v.x), "r"(v.y) : "memory");
  }
}
__device__ __forceinline__ void fold_w2(const int u, const __nv_bfloat16* __restrict__ wqkv, const __nv_bfloat16* __restrict__ wo,
                                        uint8_t* wimg) {
  const int g = (threadIdx.x >> 2) & 7, l = threadIdx.x & 3;
  const int m0 = (u / 12) * 32, n0 = (u % 12) * 16;
  uint4 S[12];
  uint32_t L[96];
  const __nv_bfloat16* brow = wqkv + (n0 + 4 * (g >> 1) + (g & 1)) * 576 + 384 + 8 * l;
#pragma unroll
  for (int i = 0; i < 12; i++) S[i] = ldg128_nc(brow + (i & 1) * 2 * 576 + 32 * (i >> 1));
  const __nv_bfloat16* acol = wo + (8 * l) * 192 + m0 + 4 * g;
#pragma unroll
  for (int c = 0; c < 48; c++)
    asm volatile("ld.global.nc.v2.u32 {%0,%1}, [%2];" : "=r"(L[2 * c]), "=r"(L[2 * c + 1]) : "l"(acol + (32 * (c >> 3) + (c & 7)) * 192));
  const uint32_t off = w2_offset();
  sched_fence();
  uint8_t* img = wimg + off;
  float acc[4][4];
#pragma unroll
  for (int j = 0; j < 16; j++) acc[j >> 2][j & 3] = 0.f;
#pragma unroll
  for (int i = 0; i < 6; i++) {
#pragma unroll
    for (int h = 0; h < 2; h++) {
      const uint4 &s0 = S[2 * i], &s1 = S[2 * i + 1];
#pragma unroll
      for (int mt = 0; mt < 2; mt++) {
        const uint32_t* a = L + 16 * i + 8 * h + mt;
        const uint32_t a0 = __byte_perm(a[0], a[2], 0x5410), a1 = __byte_perm(a[0], a[2], 0x7632);
        const uint32_t a2 = __byte_perm(a[4], a[6], 0x5410), a3 = __byte_perm(a[4], a[6], 0x7632);
        mma16816(acc[2 * mt], a0, a1, a2, a3, h ? s0.z : s0.x, h ? s0.w : s0.y);
        mma16816(acc[2 * mt + 1], a0, a1, a2, a3, h ? s1.z : s1.x, h ? s1.w : s1.y);
      }
    }
  }
#pragma unroll
  for (int j = 0; j < 4; j++) {
    const float(&c0)[4] = acc[j & 2];
    const float(&c1)[4] = acc[(j & 2) + 1];
    asm volatile("st.relaxed.gpu.global.v2.u32 [%0], {%1,%2};" ::"l"(img + w2img_off(g2_inv(m0 + 4 * g + j), n0 + 4 * l)),
                 "r"(pack_bf16(c0[2 * (j & 1)], c0[2 * (j & 1) + 1])), "r"(pack_bf16(c1[2 * (j & 1)], c1[2 * (j & 1) + 1])) : "memory");
  }
}

__global__ void __launch_bounds__(256) fold_kernel(const __nv_bfloat16* __restrict__ wqkv,
                                                   const __nv_bfloat16* __restrict__ wo, uint8_t* wimg) {
  const int u = blockIdx.x * 8 + (threadIdx.x >> 5);
  if (u < 144) fold_w1(u, wqkv, wimg);
  else fold_w2(u - 144, wqkv, wo, wimg);
}

struct TileCoord { int pr, pc, I, J, up, kind; };
struct TileTable { uint16_t e[kCtas * 6], g[5][8][2], b[5][2][4]; };
inline void make_tiles(TileTable& tt) {
  for (int tile = 0; tile < kCtas * 6; tile++) {
    const int b = tile / 6, k = tile - 6 * b;
    const int p = b < 128 ? (tile - 672) >> 1 : b - 80;
    const int strip = b < 112 ? b >> 1 : b >= 128 && k >= 2 ? (b & 1) * 27 + (b & 2) * 14 : p + (p < 26 ? 1 : 3);
    const int pr = strip >= 28, J = (strip - pr * 28) >> 1, pc = strip & 1, up = b < 112 ? b & 1 : pr;
    const int first = b < 112 ? 8 - 2 * pr - up : 13 * pr, step = b < 112 ? k : k & 1;
    const int I = up ? first - step : first + step;
    const int kind = I == 13 * pr ? 3 + pr : J == 13 * pc ? 1 + pc : 0;
    tt.e[tile] = (uint16_t)(I | J << 4 | pr << 8 | pc << 9 | up << 10 | kind << 11);
  }
  for (int kind = 0; kind < 5; kind++) {
    const bool col = kind == 1 || kind == 2;
    auto off = [kind](int t) { return kind == 0 ? 2 * t : kind & 1 ? t + (t == 7) : t + (t > 0); };
    for (int j = 0; j < 8; j++) {
      const int w = j >> 1, h = j & 1;
      tt.g[kind][j][0] = (uint16_t)(col ? 3 * off(w + 4 * h) : 3 * (kW * off(2 * w) + 8 * h));
      tt.g[kind][j][1] = (uint16_t)(128 * (col ? 5 : 5 + off(2 * w + 1) - off(2 * w)));
    }
    for (int i = 0; i < 2; i++) {
      const int w = kind == 0 ? 0 : kind & 1 ? 3 * i : 1 - i;
      tt.b[kind][i][0] = tt.g[kind][2 * w][0];
      tt.b[kind][i][1] = (uint16_t)(128 * (kind == 0 ? 0 : (col ? 3 : 1) + i));
      tt.b[kind][i][2] = (uint16_t)(2048 * w);
      tt.b[kind][i][3] = 0;
    }
  }
}
__device__ __forceinline__ int num_tiles() { return blockIdx.x < 128 ? 6 : 4; }
__device__ __forceinline__ TileCoord decode_tile(const TileTable& tt, int tile) {
  const uint32_t e = tt.e[tile];
  return TileCoord{(int)(e >> 8) & 1, (int)(e >> 9) & 1, (int)e & 15, (int)(e >> 4) & 15, (int)(e >> 10) & 1, (int)(e >> 11)};
}
__device__ __forceinline__ int halo_r0(const TileCoord& t) { return 8 * t.I + 6 * t.pr - 6; }
__device__ __forceinline__ int halo_c0(const TileCoord& t) { return min(max(8 * t.J + 6 * t.pc - 6, -3), 102); }

__device__ __forceinline__ uint32_t bar_full(uint32_t bars, int wg, int c) { return bars + (wg * 3 + c) * 8; }
__device__ __forceinline__ uint32_t bar_w1c(uint32_t bars, int c) { return bars + (6 + c) * 8; }
__device__ __forceinline__ uint32_t bar_w2(uint32_t bars) { return bars + 9 * 8; }
__device__ __forceinline__ uint32_t bar_x(uint32_t bars, int j, int c) { return bars + (j == 0 ? 10 : c ? 17 + c : 11) * 8; }
__device__ __forceinline__ uint32_t bar_w1q(uint32_t bars) { return bars + 12 * 8; }
__device__ __forceinline__ uint32_t bar_xf(uint32_t bars) { return bars + 13 * 8; }
__device__ __forceinline__ uint32_t bar_w2m(uint32_t bars) { return bars + 14 * 8; }
__device__ __forceinline__ uint32_t bar_redo(uint32_t bars) { return bars + 15 * 8; }
__device__ __forceinline__ uint32_t bar_wok(uint32_t bars) { return bars + 16 * 8; }
__device__ __forceinline__ uint32_t bar_go(uint32_t bars) { return bars + 17 * 8; }
__device__ __forceinline__ uint32_t bar_raw(uint32_t bars, int j = 0) { return bars + (21 + j) * 8; }
__device__ __forceinline__ uint32_t bar_w2a(uint32_t bars) { return bars + 20 * 8; }
constexpr int kNumBars = 22;

__device__ __forceinline__ uint64_t wdesc(uint64_t d0, int s) { return d0 + (((s >> 2) * kWChunk + (s & 3) * 32) >> 4); }

__device__ __forceinline__ uint32_t x_chunk(int k, int c) { return kXOff + (k == 0 ? kWChunk : 0) + (k & 1 ? 2 - c : c) * 8192; }
__device__ __forceinline__ uint32_t out_slot(int k, int nt) { return k + 1 < nt ? kW2Off + (~k & 1) * 2 * kWChunk : kW1Off + kWChunk; }
template <int I0, int I1>
__device__ __forceinline__ void store_rows(bool on, __nv_bfloat16* pA, __nv_bfloat16* pB, const uint32_t (&a)[24], const uint32_t (&b)[24]) {
#pragma unroll
  for (int i = 2 * I0; i < 2 * I1; i++) {
    const uint32_t* v = (i & 1 ? b : a) + 4 * (i >> 1);
    asm volatile("{\n.reg .pred p;\nsetp.ne.u32 p, %5, 0;\n@p st.global.v4.u32 [%0], {%1,%2,%3,%4};\n}\n" ::"l"((i & 1 ? pB : pA) + 32 * (i >> 1)),
                 "r"(v[0]), "r"(v[1]), "r"(v[2]), "r"(v[3]), "r"((uint32_t)on) : "memory");
  }
}
template <int I0, int I1>
__device__ __forceinline__ void stage_out(const uint32_t (&ad)[4], const uint32_t (&a)[24], const uint32_t (&b)[24]) {
#pragma unroll
  for (int i = I0; i < I1; i++) {
    const uint32_t* v = (i < 6 ? a : b) + 4 * (i % 6);
    asm volatile("st.shared.v4.u32 [%0], {%1,%2,%3,%4};" ::"r"(ad[i % 6 / 3 * 2 + (i % 3 == 1)] + (i % 3 == 2) * 1024 + (i / 6) * 12288),
                 "r"(v[0]), "r"(v[1]), "r"(v[2]), "r"(v[3]) : "memory");
  }
}
__device__ __forceinline__ uint32_t now_ns() {
  uint32_t t;
  asm volatile("mov.u32 %0, %globaltimer_lo;" : "=r"(t)::"memory");
  return t;
}
__device__ __forceinline__ void wait_clock(uint32_t t_start, uint32_t t) {
  while (now_ns() - t_start < t) { }
}
__device__ __forceinline__ void sleep_clock(uint32_t t_start, uint32_t t) {
  while (now_ns() - t_start < t) __nanosleep(100);
}
#define NAT_PRED(f, m) ".reg .pred p;\n.reg .b32 t;\nand.b32 t, " f ", " m ";\nsetp.ne.u32 p, t, 0;\n"
constexpr uint32_t kHiV = 1, kHiU = 8, kColB = 0x20, kInV = 0x100, kInU = 0x1000, kColA = 0x10000;
template <uint32_t M>
__device__ __forceinline__ float pick(const float* a, const float* b, uint32_t f) {
  float d;
  asm("{\n" NAT_PRED("%5", "%6") "add.f32 %0, %1, %2;\n@p add.f32 %0, %3, %4;\n}\n"
      : "=&f"(d) : "f"(a[0]), "f"(a[2]), "f"(b[0]), "f"(b[2]), "r"(f), "n"(M));
  return d;
}
template <uint32_t M>
__device__ __forceinline__ float sel(float a, float b, uint32_t f) {
  float d;
  asm("{\n" NAT_PRED("%3", "%4") "selp.f32 %0, %1, %2, p;\n}\n" : "=f"(d) : "f"(a), "f"(b), "r"(f), "n"(M));
  return d;
}
template <uint32_t M>
__device__ __forceinline__ void max_if(float& m, float v, uint32_t f) {
  asm("{\n" NAT_PRED("%2", "%3") "@p max.f32 %0, %0, %1;\n}\n" : "+f"(m) : "f"(v), "r"(f), "n"(M));
}
template <uint32_t M>
__device__ __forceinline__ void add_if(float& m, float v, uint32_t f) {
  asm("{\n" NAT_PRED("%2", "%3") "@p add.f32 %0, %0, %1;\n}\n" : "+f"(m) : "f"(v), "r"(f), "n"(M));
}
__device__ __forceinline__ void pick_v(const float* a, float* v, uint32_t f) {
  v[0] = pick<kHiV>(a, a + 16, f), v[1] = pick<kHiV>(a + 1, a + 17, f);
  v[2] = pick<kHiV * 2>(a + 4, a + 20, f), v[3] = pick<kHiV * 2>(a + 5, a + 21, f);
  v[4] = pick<kHiV * 4>(a + 8, a + 24, f), v[5] = pick<kHiV * 4>(a + 9, a + 25, f);
  v[6] = a[12] + a[14], v[7] = a[13] + a[15];
}
__device__ __forceinline__ void pick_u(const float* a, float* v, uint32_t f) {
#pragma unroll
  for (int c = 0; c < 3; c++) v[2 * c] = pick<kHiU>(a + 4 * c, a + 4 * c + 12, f), v[2 * c + 1] = pick<kHiU * 2>(a + 4 * c + 1, a + 4 * c + 13, f);
}
__device__ __forceinline__ uint32_t sign_bytes(uint32_t v, uint32_t sel) {
  uint32_t d;
  asm("prmt.b32 %0, %1, %1, %2;" : "=r"(d) : "r"(v), "r"(sel));
  return d;
}
__device__ __forceinline__ float own_max(const float (&v)[14], uint32_t f) {
  float m = sel<kInV>(fmaxf(v[0], v[1]), -INFINITY, f), m2 = sel<kInV * 2>(fmaxf(v[2], v[3]), -INFINITY, f);
  max_if<kInV * 4>(m, fmaxf(v[4], v[5]), f);
  max_if<kInV * 8>(m2, fmaxf(v[6], v[7]), f);
  max_if<kInU>(m, fmaxf(fmaxf(v[8], v[10]), v[12]), f);
  max_if<kInU * 2>(m2, fmaxf(fmaxf(v[9], v[11]), v[13]), f);
  return fmaxf(m, m2);
}
__device__ __forceinline__ float quad_max(float m) {
  const float a = __shfl_xor_sync(0xffffffffu, m, 1), b = __shfl_xor_sync(0xffffffffu, m, 2), c = __shfl_xor_sync(0xffffffffu, m, 3);
  return fmaxf(fmaxf(m, a), fmaxf(b, c));
}
__device__ __forceinline__ float row_rcp(const float (&v)[14], uint32_t f) {
  float s = sel<kInV>(v[0] + v[1], 0.f, f), s2 = sel<kInV * 2>(v[2] + v[3], 0.f, f);
  add_if<kInV * 4>(s, v[4] + v[5], f);
  add_if<kInV * 8>(s2, v[6] + v[7], f);
  add_if<kInU>(s, v[8] + v[10] + v[12], f);
  add_if<kInU * 2>(s2, v[9] + v[11] + v[13], f);
  s += s2;
  const float a = __shfl_xor_sync(0xffffffffu, s, 1), b = __shfl_xor_sync(0xffffffffu, s, 2), c = __shfl_xor_sync(0xffffffffu, s, 3);
  return rcp_approx((s + a) + (b + c));
}
__device__ __forceinline__ void route(const float (&v)[14], float s, const uint32_t (&rt)[9], uint32_t (&p)[14]) {
#pragma unroll
  for (int i = 0; i < 7; i++) {
    const uint32_t u = pack_bf16(v[2 * i] * s, v[2 * i + 1] * s);
    if (i < 4) p[i] = u & rt[i];
    if (i < 3) p[i + 4] = u & rt[i + 4];
    if (i >= 4) {
      p[i + 3] = u & rt[7];
      p[i + 6] = u & rt[8];
    }
  }
}

template <int C, int T0 = 0, int T1 = 7>
__device__ __forceinline__ void pv_chunk(float (&z)[32], const uint32_t (&pa)[14], const uint32_t (&pb)[14],
                                         const uint32_t (&meta)[4], uint64_t dV) {
#pragma unroll
  for (int t = T0; t < T1; t++) {
    if (t & 1)
      wg_s64t1<0, 32>(z, pa[2 * t], pb[2 * t], pa[2 * t + 1], pb[2 * t + 1], dV + ((2 * C * kChunkBytes + t * 2048) >> 4), 1,
                      meta[t >> 1]);
    else if (t > 0)
      wg_s64t<0, 32>(z, pa[2 * t], pb[2 * t], pa[2 * t + 1], pb[2 * t + 1], dV + ((2 * C * kChunkBytes + t * 2048) >> 4), 1,
                     meta[t >> 1]);
    else
      wg_s64tz<0, 32>(z, pa[0], pb[0], pa[1], pb[1], dV + ((2 * C * kChunkBytes) >> 4), 0, meta[0]);
  }
}
template <int C>
__device__ __forceinline__ void pack_z(const float (&z)[32], uint32_t (&za)[24], uint32_t (&zb)[24]) {
#pragma unroll
  for (int j = 0; j < 8; j++) {
    za[8 * C + j] = pack_bf16(z[4 * j], z[4 * j + 1]);
    zb[8 * C + j] = pack_bf16(z[4 * j + 2], z[4 * j + 3]);
  }
}

template <int H>
__device__ __forceinline__ void pack_out(const float (&ac)[48], uint32_t (&oa)[24], uint32_t (&ob)[24]) {
#pragma unroll
  for (int j = 0; j < 12; j++) {
    oa[12 * H + j] = pack_bf16(ac[4 * j], ac[4 * j + 1]);
    ob[12 * H + j] = pack_bf16(ac[4 * j + 2], ac[4 * j + 3]);
  }
}
struct Maps { CUtensorMap v6, v2, v14, u8, px[8], wv, wo; };
__device__ __forceinline__ void tma_prefetch_5d(const CUtensorMap* map, int c0, int c1, int c2, int c3, int c4) {
  asm volatile("cp.async.bulk.prefetch.tensor.5d.L2.global.tile [%0, {%1, %2, %3, %4, %5}];" ::"l"((uint64_t)map), "r"(c0), "r"(c1),
               "r"(c2), "r"(c3), "r"(c4) : "memory");
}
__device__ __forceinline__ int first_line(const TileCoord tc) { return 3 * (qpix(tc.pr, 8 * tc.I) * kW + qpix(tc.pc, 8 * tc.J)); }
__device__ __forceinline__ void load_px(const Maps& tm, const TileTable& tt, uint32_t dst, uint32_t bar, int line, int kind) {
#pragma unroll
  for (int i = 0; i < 2; i++) {
    if (i == 0 || kind != 0) {
      const CUtensorMap* map = (const CUtensorMap*)((const char*)tm.px + tt.b[kind][i][1]);
      if (bar) tma_load_5d(dst + tt.b[kind][i][2], map, bar, 0, 0, 0, 0, line + tt.b[kind][i][0]);
      else tma_prefetch_5d(map, 0, 0, 0, 0, line + tt.b[kind][i][0]);
    }
  }
}
__device__ __forceinline__ void store_px(const Maps& tm, const TileTable& tt, uint32_t buf, int line, int kind) {
#pragma unroll
  for (int i = 0; i < 8; i++) {
    const int j = 2 * (i & 3) + (i >> 2);
    asm volatile("cp.async.bulk.tensor.5d.global.shared::cta.tile.bulk_group [%0, {%2, %2, %2, %2, %3}], [%1];" ::"l"(
                     (uint64_t)tm.px + tt.g[kind][j][1]), "r"(buf + i * 3072), "r"(0), "r"(line + tt.g[kind][j][0]) : "memory");
  }
  asm volatile("cp.async.bulk.commit_group;" ::: "memory");
}
__device__ __noinline__ bool refetch(uint32_t base, const uint8_t* src, bool gap) {
  constexpr uint32_t bars = 1024 + kBarOff, cnt = bars + 192;
#pragma unroll 1
  for (uint32_t o = 0; o < kWBytes && !gap; o += 2048) {
    uint32_t mx = 0;
#pragma unroll
    for (int i = 0; i < 4; i++) {
      uint4 v;
      asm volatile("ld.shared.v4.u32 {%0,%1,%2,%3}, [%4];" : "=r"(v.x), "=r"(v.y), "=r"(v.z), "=r"(v.w)
                   : "r"(base + o + i * 512 + (threadIdx.x & 31) * 16));
      mx = __vimax3_u32(__vimax3_u32(mx, v.x, v.y), v.z, v.w);
    }
    gap = __any_sync(0xffffffffu, mx == kEmpty);
  }
  uint32_t n;
  asm volatile("ld.shared.u32 %0, [%1];" : "=r"(n) : "r"(cnt) : "memory");
  if (!gap || __any_sync(0xffffffffu, n > (1u << 12))) return false;
  asm volatile("bar.sync 15, 128;" ::: "memory");
  if (threadIdx.x == 0) {
    asm volatile("st.shared.u32 [%0], %1;" ::"r"(cnt), "r"(n + 1) : "memory");
    mbar_arrive_expect_tx(bar_redo(bars), kWBytes);
    bulk_load(base, src, kWBytes, bar_redo(bars));
  }
  __syncwarp();
  mbar_wait(bar_redo(bars), n & 1);
  return true;
}
__device__ __forceinline__ bool any_nan(const uint32_t (&a)[24]) {
  uint32_t m[2] = {a[0], a[1]}, nan;
#pragma unroll
  for (int i = 2; i < 24; i++) asm("max.NaN.bf16x2 %0, %0, %1;" : "+r"(m[i & 1]) : "r"(a[i]));
  asm("max.NaN.bf16x2 %0, %0, %1;" : "+r"(m[0]) : "r"(m[1]));
  asm volatile("{\n.reg .pred p;\nsetp.ne.u32 p, %1, 0;\nbar.red.or.pred p, 15, 128, p;\nselp.u32 %0, 1, 0, p;\n}\n"
               : "=r"(nan) : "r"(((m[0] & 0x7FFF7FFFu) + 0x007F007Fu) & 0x80008000u) : "memory");
  return __any_sync(0xffffffffu, nan);
}
template <int S0, int S1, int Z>
__device__ __forceinline__ void g2_steps(float (&ac)[48], const uint32_t (&za)[24], const uint32_t (&zb)[24], uint64_t d) {
#pragma unroll
  for (int s = S0; s < S1; s++) {
    const uint64_t ds = d + (((s >> 2 & 1) * (kWChunk / 2) + (s & 3) * 32) >> 4);
    if (s == Z) wg_d96z<0, 48>(ac, za[2 * s], zb[2 * s], za[2 * s + 1], zb[2 * s + 1], ds, 0);
    else wg_d96<0, 48>(ac, za[2 * s], zb[2 * s], za[2 * s + 1], zb[2 * s + 1], ds, 1);
  }
}

__device__ __forceinline__ void consumer(const int wg, __nv_bfloat16* out, const uint8_t* wimg, const uint32_t sbase,
                                         const uint32_t zero, const Maps& tm, const TileTable& tt) {
  const int tid = threadIdx.x & 127;
  const int w = __shfl_sync(0xffffffffu, tid >> 5, 0), lane = tid & 31;
  const uint64_t dK = make_desc(sbase, 16, 1024);
  const uint64_t dV = make_desc(sbase, kChunkBytes, 512, 2);
  const uint64_t dW1 = make_desc(sbase + kW1Off, 16, 1024);
  const uint64_t dX0 = make_desc(sbase + kW2Off + wg * 2 * kWChunk, 16, 1024), dY0 = make_desc(sbase + kW2Off + (1 - wg) * 2 * kWChunk, 16, 1024);
  const uint64_t dX2 = make_desc(sbase + kXOff + wg * (kWChunk / 2), 16, 1024), dY2 = make_desc(sbase + kXOff + (1 - wg) * (kWChunk / 2), 16, 1024);
  const uint32_t bars = sbase + kBarOff;
  int tile0 = blockIdx.x * kTilesPerCta;
  asm volatile("" : "+r"(tile0));
  const int nt = num_tiles();

  uint32_t pix = 0, geo[6] = {};
  const int l = lane & 3;
#pragma unroll 1
  for (int j = 4; j >= 0; j -= 2) {
    const TileCoord tc = decode_tile(tt, tile0 + wg + j);
    const bool col = tc.kind == 1 || tc.kind == 2;
    const int g = col ? lane >> 2 : 2 * w + ((lane >> 2) & 1), qc = col ? w : lane >> 3;
    const uint32_t pr = qpix(tc.pr, 8 * tc.I + g) * kW;
    if (j == nt - 2) pix = (pr + qpix(tc.pc, 8 * tc.J + qc)) | (pr + qpix(tc.pc, 8 * tc.J + qc + 4)) << 16;
    const int d = 8 * tc.J + 6 * tc.pc - 6 - halo_c0(tc);
    const int ro = woff(tc.pr, tc.I, g), coA = woff(tc.pc, tc.J, qc) + d, coB = woff(tc.pc, tc.J, qc + 4) + d - 3;
#pragma unroll
    for (int i = 5; i >= 2; i--) geo[i] = geo[i - 2];
    const uint32_t lr = 0x1FCu << ro;
    const uint32_t lv = lr >> (2 + (l >> 1)), lu = lr >> (2 * l + 2 * tc.up);
    const uint32_t t = __byte_perm(lv, lu, wg ? 0x4501 : 0x5410);
    geo[0] = (((t & 0x15u) | (lv & 0x40u)) * 0x02082080u & 0x80808080u) | (((t >> 8) & 0x15u) * 0x01041040u & 0x40404040u) |
             (__byte_perm(t << 5, t << 4, 0x7362) & 0x20202020u) | (nt == 6);
    const int dr = (ro - 1) & 7;
    const uint32_t hiv = (((1u << ((ro - (l >> 1) + 1) >> 1)) - 1u) ^ (wg ? 7u : 0u)) & 7u, hiu = (t >> 24) & 3u;
    const uint32_t ca = (1u << coA) - 1u;
    geo[1] = hiv * kHiV | hiu * kHiU | ((((1u << coB) - 1u) >> (2 * (l & 1))) & 3u) * kColB |
             (15u & ~((uint32_t)((dr & 1) == (l >> 1)) << (dr >> 1))) * kInV | ((t >> 16 | t >> 24) & 3u) * kInU | ca * kColA |
             (ca >> ((0x49 >> (2 * l)) & 3) & 1u) << 19 | (uint32_t)(l == 3) << 20 | (0x55u & ((1u << (2 * coB)) - 1u)) << 24;
  }
  keep_regs(geo);
  const int so = (lane >> 3) | (lane & 4);
  uint32_t sts = sbase + w * 3072 + so * 128 + (((lane & 3) ^ so) << 4);
  __nv_bfloat16* poA = out + 8 * l + (pix & 0xFFFFu) * kC + 96 * wg;
  __nv_bfloat16* poB = out + 8 * l + (pix >> 16) * kC + 96 * wg;
  asm volatile("" : "+l"(poA), "+l"(poB), "+r"(sts));
  uint32_t oa[24], ob[24];
#pragma unroll
  for (int j = 0; j < 24; j++) oa[j] = ob[j] = 0u;
  keep_regs(oa);
  keep_regs(ob);
  PROF(wg, 0);
  if (threadIdx.x == 0) GT(1);

  for (int k = wg; k < nt; k += 2) {
    const uint32_t ph = (k >> 1) & 1;
    const int it = k >> 1;
    uint32_t qa[24], qb[24], hok[3];
    uint32_t fl = geo[1];
    {
      float acc[96];
      const uint32_t xp = (k + (k > 0)) & 1;
      if (k > 0) nb_sync(1 + (1 - wg));
#pragma unroll
      for (int s = 0; s < 12; s++) {
        if (s == 0) mbar_wait(bar_x(bars, k > 0, 0), xp);
        if (s == 0 && k < 2) PROF(wg, 1);
        if (s == 0) PROFS(2, wg, 2 + it * 12);
        if (s == 0 && w == 0 && k < 2) GT(20 + wg);
        if (s == 4) wg_wait<1>();
        if ((s & 3) == 0 && (k == 0 || s > 0)) {
          mbar_wait(k == 0 ? bar_w1c(bars, s >> 2) : bar_x(bars, 1, s >> 2), xp);
          PROFS(17, wg, 50 + (s >> 2));
        }
        if ((s & 3) == 0) wg_fence();
        const uint64_t dX = make_desc(sbase + x_chunk(k, s >> 2), 16, 1024) + 2 * (s & 3);
        if (s == 0) wg_m192z<0, 96>(acc, dX, dW1, 0);
        else wg_m192<0, 96>(acc, dX, wdesc(dW1, s), 1);
        if ((s & 3) == 3 || s == 0) wg_commit();
      }
      PROFS(13, wg, 13 + it * 12);
      const uint32_t e = sts + out_slot(k, nt), o = e ^ 64;
      uint32_t ad[4] = {wg ? o + 1024 : e, wg ? e + 2048 : o, wg ? e : o + 1024, wg ? o : e + 2048};
      keep_regs(ad);
      wg_wait<2>();
      if (k > 0) nb_arrive_p(0);
      wg_wait<1>();
      if (k > 0) nb_arrive_p(14);
      wg_wait<0>();
      if (k > 0) {
        nb_arrive_p(6);
        sched_fence();
      }
      fence_regs(acc);
      PROFS(3, wg, 3 + it * 12);
#pragma unroll
      for (int j = 0; j < 24; j++) {
        qa[j] = pack_bf16(acc[4 * j], acc[4 * j + 1]);
        qb[j] = pack_bf16(acc[4 * j + 2], acc[4 * j + 3]);
      }
      keep_regs(qa);
      keep_regs(qb);
      sched_fence();
      if (k >= 2) {
        nb_sync(11);
        stage_out<0, 6>(ad, oa, ob);
        nb_sync(12);
        stage_out<6, 12>(ad, oa, ob);
      }
#pragma unroll
      for (int c = 0; c < 3; c++) hok[c] = mbar_test(bar_full(bars, wg, c), ph);
      if (k >= 2) {
        fence_proxy_async();
        nb_arrive_p(10);
      }
    }

    float aE[52], aO[24], bO[52], bE[28];
    const uint32_t mq = 0xEEEE4444u | zero;
    PROFS(4, wg, 4 + it * 12);

    mbar_wait_if(hok[0], bar_full(bars, wg, 0), ph);
    PROFS(14, wg, 40 + it * 3);
    if (w == 0 && k < 2) GT(22 + wg);
    if (k > 0) nb_sync(3 + (1 - wg));
    wg_fence();
#pragma unroll
    for (int ks = 0; ks < 6; ks++) {
      if (ks == 2) {
        mbar_wait_if(hok[1], bar_full(bars, wg, 1), ph);
        PROFS(14, wg, 41 + it * 3);
        wg_fence();
      }
      if (ks == 4) {
        mbar_wait_if(hok[2], bar_full(bars, wg, 2), ph);
        PROFS(14, wg, 42 + it * 3);
        wg_fence();
      }
      const uint64_t d = dK + ((ks * kChunkBytes) >> 4);
      if (ks == 0) wg_s104z<0, 52>(aE, qa[0], qa[1], qa[2], qa[3], d, 0, mq);
      else wg_s104<0, 52>(aE, qa[4 * ks], qa[4 * ks + 1], qa[4 * ks + 2], qa[4 * ks + 3], d, 1, mq);
      if (ks == 0) wg_s48z<0, 24>(aO, qa[0], qa[1], qa[2], qa[3], d + ((7 * 1024 + 64) >> 4), 0, mq);
    }
    wg_commit();
#pragma unroll
    for (int ks = 1; ks < 6; ks++)
      wg_s48<0, 24>(aO, qa[4 * ks], qa[4 * ks + 1], qa[4 * ks + 2], qa[4 * ks + 3], dK + ((ks * kChunkBytes + 7 * 1024 + 64) >> 4), 1, mq);
    wg_commit();
    wg_s56z<0, 28>(bE, qb[0], qb[1], qb[2], qb[3], dK, 0, mq);
#pragma unroll
    for (int ks = 1; ks < 6; ks++) wg_s56<0, 28>(bE, qb[4 * ks], qb[4 * ks + 1], qb[4 * ks + 2], qb[4 * ks + 3], dK + ((ks * kChunkBytes) >> 4), 1, mq);
    wg_commit();
    wg_wait<2>();
    fence_regs(aE);
    PROFS(5, wg, 5 + it * 12);

    uint32_t pa[14], pb[14], meta[4];
    {
      float vA[14], vB[14];
      pick_v(aE, vA, fl);
      pick_u(aE + 28, vA + 8, fl);
      fence_regs(vA);
      if (k == 0) {
        if (__builtin_expect(__any_sync(0xffffffffu, vA[6] != vA[6]), 0)) {
          wg_wait<0>();
          fence_regs(aO);
          fence_regs(bE);
          if (refetch(sbase + kW1Off, wimg, false)) {
#pragma unroll
            for (int j = 0; j < 24; j++) oa[j] = ob[j] = 0u;
            k -= 2;
            continue;
          }
        }
        if (elect_one()) mbar_arrive(bar_xf(bars));
      }
      wg_fence();
      wg_s104z<0, 52>(bO, qb[0], qb[1], qb[2], qb[3], dK + 4, 0, mq);
#pragma unroll
      for (int ks = 1; ks < 6; ks++)
        wg_s104<0, 52>(bO, qb[4 * ks], qb[4 * ks + 1], qb[4 * ks + 2], qb[4 * ks + 3], dK + ((ks * kChunkBytes + 64) >> 4), 1, mq);
      wg_commit();
      if (k + 1 < nt) nb_arrive(1 + wg);
      uint32_t rt[9];
#pragma unroll
      for (int i = 0; i < 7; i++) rt[i] = sign_bytes(geo[0] << (i >> 2), 0x8888u + 0x1111u * (i & 3));
      rt[7] = sign_bytes(geo[0] << 2, 0x9988u);
      rt[8] = sign_bytes(geo[0] << 2, 0xBBAAu);
      keep_regs(rt);
      pa[13] = geo[0] & zero, pb[13] = geo[1] & zero;
      wg_wait<2>();
      keep_regs(qa);
      fence_regs(aO);
      float oA[6], eB[8];
      pick_u(aO, oA, fl);
      wg_wait<1>();
      fence_regs(bE);
      pick_v(bE, eB, fl);
      vA[8] = sel<kColA>(oA[0], vA[8], fl), vA[9] = sel<kColA>(oA[1], vA[9], fl);
      vA[10] = sel<kColA * 2>(oA[2], vA[10], fl), vA[11] = sel<kColA * 2>(oA[3], vA[11], fl);
      vA[12] = sel<kColA * 4>(oA[4], vA[12], fl), vA[13] = sel<kColA * 4>(oA[5], vA[13], fl);
      {
        const float m1 = __uint_as_float(0x88DD88DDu), m0 = __uint_as_float(0x88DDDD88u);
        meta[0] = 0xDD88DD88u ^ __byte_perm(fl, 0u, 0x3344);
        meta[1] = __float_as_uint(sel<kColA * 16>(sel<kColA>(m1, m0, fl), __uint_as_float(meta[0]), fl));
        meta[2] = __float_as_uint(sel<kColA * 8>(m1, m0, fl));
        meta[3] = __float_as_uint(sel<kColA * 4>(m1, m0, fl));
        keep_regs(meta);
      }
      float mA = own_max(vA, fl);
      fl |= __float_as_uint(eB[7]) & zero;
      fence_regs(eB);
      fence_regs(vA);
      asm volatile("" : "+f"(mA), "+r"(fl));
      sched_fence();
      wg_wait<0>();
      sched_fence();
      keep_regs(qb);
      fence_regs(bO);
      PROFS(6, wg, 6 + it * 12);
      if (w == 0) GT(24 + k);
      mA = quad_max(mA);
      pick_v(bO, vB, fl);
      pick_u(bO + 28, vB + 8, fl);
#pragma unroll
      for (int i = 0; i < 8; i += 2) vB[i] = sel<kColB>(vB[i], eB[i], fl), vB[i + 1] = sel<kColB * 2>(vB[i + 1], eB[i + 1], fl);
#pragma unroll
      for (int i = 0; i < 14; i++) vA[i] = i < 3 ? ex2(vA[i] - mA) : vA[i] - mA;
      fence_regs(vA);
      fence_regs(vB);
      sched_fence();
#pragma unroll
      for (int i = 3; i < 14; i++) vA[i] = ex2(vA[i]);
      const float mB = quad_max(own_max(vB, fl));
      PROFS(7, wg, 7 + it * 12);
#pragma unroll
      for (int i = 0; i < 14; i++) vB[i] = i < 1 ? ex2(vB[i] - mB) : vB[i] - mB;
      fence_regs(vA);
      fence_regs(vB);
      sched_fence();
#pragma unroll
      for (int i = 1; i < 14; i++) vB[i] = ex2(vB[i]);
      route(vA, row_rcp(vA, fl), rt, pa);
      route(vB, row_rcp(vB, fl), rt, pb);
    }
    PROFS(8, wg, 8 + it * 12);
    if (k == NAT_PK) PROFS(18, wg, 53);
    sched_fence();

    float ac0[48], ac1[48];
    {
      float z0[32], z1[32], z2[32];
      uint32_t za[24], zb[24];
      wg_fence();
      pv_chunk<0>(z0, pa, pb, meta, dV);
      wg_commit();
      pv_chunk<1>(z1, pa, pb, meta, dV);
      wg_commit();
      wg_wait<1>();
      if (k == NAT_PK) PROFS(18, wg, 54);
      if (k + 1 < nt) nb_arrive_p(7);
      pv_chunk<2, 0, 3>(z2, pa, pb, meta, dV);
      wg_commit();
      sched_fence();
      fence_regs(z0);
      pack_z<0>(z0, za, zb);
      sched_fence();
      wg_fence();
      pv_chunk<2, 3, 7>(z2, pa, pb, meta, dV);
      wg_commit();
      wg_wait<2>();
      if (k == NAT_PK) PROFS(19, wg, 55);
      if (k + 1 < nt) nb_arrive_p(8);
      if (k < 2) mbar_wait(k == 1 ? bar_wok(bars) : bar_w2a(bars), 0);
      wg_fence();
      g2_steps<0, 3, 0>(ac0, za, zb, dX0);
      wg_commit();
      sched_fence();
      fence_regs(z1);
      pack_z<1>(z1, za, zb);
      sched_fence();
      wg_fence();
      g2_steps<3, 4, 0>(ac0, za, zb, dX0);
      wg_commit();
      g2_steps<4, 8, 0>(ac0, za, zb, dX0);
      wg_commit();
      wg_wait<3>();
      if (k + 1 < nt) nb_arrive_p(9);
      else nb_arrive(11);
      if (k == NAT_PK) PROFS(20, wg, 56);
      keep_regs(pa);
      keep_regs(pb);
      keep_regs(meta);
      sched_fence();
      const uint32_t mok = mbar_test(bar_w2m(bars), k + 1 < nt ? k & 1 : ~k & 1);
      const uint32_t wp = k < 2 ? 0 : k + 1 < nt ? ~k & 1 : k & 1, wok = mbar_test(bar_w2(bars), wp);
      fence_regs(z2);
      pack_z<2>(z2, za, zb);
      keep_regs(za);
      keep_regs(zb);
      sched_fence();
      PROFS(9, wg, 9 + it * 12);
      wg_wait<1>();
      if (k > 0 && k + 1 < nt) nb_arrive(11);
      mbar_wait_if(mok, bar_w2m(bars), k & 1);
      wg_fence();
      g2_steps<8, 12, 0>(ac0, za, zb, dX2);
      wg_commit();
      g2_steps<8, 12, 8>(ac1, za, zb, dY2);
      wg_commit();
      wg_wait<2>();
      if (k > 0 && k + 1 < nt) nb_arrive(12);
      mbar_wait_if(wok, bar_w2(bars), wp);
      wg_fence();
      g2_steps<0, 4, 8>(ac1, za, zb, dY0);
      wg_commit();
      wg_wait<2>();
      if (k + 2 < nt) nb_arrive_p(13);
      const bool direct = k + 2 >= nt;
      sched_fence();
      fence_regs(ac0);
      pack_out<0>(ac0, oa, ob);
      store_rows<0, 1>(direct, poA, poB, oa, ob);
      sched_fence();
      wg_fence();
      g2_steps<4, 8, 8>(ac1, za, zb, dY0);
      wg_commit();
      if (k + 1 < nt) nb_arrive(3 + wg);
      PROFS(10, wg, 10 + it * 12);
      wg_wait<2>();
      if (k + 2 < nt && (k > 0 || nt == 6)) nb_arrive_p(5);
      store_rows<1, 3>(direct, poA, poB, oa, ob);
      __nv_bfloat16 *qA = poA - 192 * wg, *qB = poB - 192 * wg;
      if (k + 2 == nt) nb_sync(11);
      sched_fence();
      wg_wait<0>();
      fence_regs(ac1);
      if (direct) {
        pack_out<1>(ac1, oa, ob);
        asm volatile("" : "+l"(qA), "+l"(qB));
        store_rows<3, 6>(true, qA, qB, oa, ob);
        break;
      }
      sched_fence();
      pack_out<1>(ac1, oa, ob);
      if (k == 0) {
        if (any_nan(oa)) {
          for (int c = 0; c < 3 && __any_sync(0xffffffffu, geo[2] & 1u); c++) mbar_wait(bar_x(bars, 1, c), 1);
          bool first = true;
          do {
            if (!__any_sync(0xffffffffu, refetch(sbase + kW2Off, wimg + w2_offset(), first))) break;
            first = false;
            wg_fence();
            g2_steps<0, 8, 0>(ac0, za, zb, dX0);
            g2_steps<8, 12, 0>(ac0, za, zb, dX2);
            g2_steps<8, 12, 8>(ac1, za, zb, dY2);
            g2_steps<0, 8, 8>(ac1, za, zb, dY0);
            wg_commit();
            wg_wait<0>();
            fence_regs(ac0);
            fence_regs(ac1);
            pack_out<0>(ac0, oa, ob);
            pack_out<1>(ac1, oa, ob);
          } while (any_nan(oa));
          if (__any_sync(0xffffffffu, geo[2] & 1u)) {
            asm volatile("bar.sync 15, 128;" ::: "memory");
            if (w == 0 && elect_one()) {
              const TileCoord tc = decode_tile(tt, tile0 + 2);
              mbar_arrive_expect_tx(bar_raw(bars), kWChunk);
#pragma unroll 1
              for (int c = 0; c < 3; c++) load_px(tm, tt, sbase + x_chunk(2, c), bar_raw(bars), first_line(tc) + c, tc.kind);
            }
            __syncwarp();
            mbar_wait(bar_raw(bars), 0);
          }
        }
        if (nt < 6) nb_arrive_p(5);
        if (elect_one()) mbar_arrive(bar_wok(bars));
      }
      keep_regs(za);
      keep_regs(zb);
#pragma unroll
      for (int i = 0; i < 4; i++) geo[i] = geo[i + 2];
      keep_regs(oa);
      keep_regs(ob);
      PROFS(12, wg, 12 + it * 12);
      sched_fence();
    }
  }
  PROF(wg, 38);
  GT_DUMP();
  PROF_DUMP(wg);
}

struct HaloCols { int vj, vc, uj, uc; };
__device__ __forceinline__ HaloCols halo_cols(const TileCoord& tc) {
  const int c0 = halo_c0(tc);
  return HaloCols{c0 > 98, c0 > 98 ? 98 : c0 + 3, c0 < 0 ? -1 : 0, c0 < 0 ? 4 : c0};
}
__device__ __forceinline__ void first_halo(const Maps& tm, uint32_t sbase, const TileCoord tc, int i) {
  const HaloCols hc = halo_cols(tc);
  const uint32_t dst = sbase + i * kChunkBytes, bar = bar_full(sbase + kBarOff, 0, i >> 1);
  const int h0 = halo_r0(tc), ch = 24 * tc.pc + 4 * i;
  tma_load_5d(dst, &tm.v14, bar, ch, hc.vj, hc.vc, tc.pr, h0);
  tma_load_5d(dst + 7 * 1024, &tm.u8, bar, ch, hc.uj, h0 + (tc.up ? 0 : -2), tc.pr, hc.uc);
  tma_load_5d(dst + 10 * 1024, &tm.u8, bar, ch, hc.uj, h0 + (tc.up ? 8 : 6), tc.pr, hc.uc);
}
__device__ __forceinline__ void load_halo(const Maps& tm, uint32_t sbase, uint32_t bars, const TileCoord tc, int k, int c) {
  const HaloCols hc = halo_cols(tc);
  const int h6 = halo_r0(tc) + (tc.up ? 0 : 8), h2 = halo_r0(tc) + 6, h8 = halo_r0(tc) + (tc.up ? 0 : 6), ch = 24 * tc.pc + 8 * c;
  uint32_t dv = sbase + 2 * c * kChunkBytes, du = dv + 7 * 1024;
  if (((k ^ tc.up) & 1) == 0) dv += 4 * 1024, du += 3 * 1024;
  const uint32_t bar = bar_full(bars, k & 1, c);
  mbar_arrive_expect_tx(bar, 14 * 1024);
  nb_sync_p(7 + c);
#pragma unroll
  for (int h = 0; h < 2; h++) {
    tma_load_5d(dv + h * kChunkBytes, &tm.v6, bar, ch + 4 * h, hc.vj, hc.vc, tc.pr, h6);
    tma_load_5d(du + h * kChunkBytes, &tm.u8, bar, ch + 4 * h, hc.uj, h8, tc.pr, hc.uc);
    tma_load_5d(sbase + (2 * c + h) * kChunkBytes + 3 * 1024, &tm.v2, bar, ch + 4 * h, hc.vj, hc.vc, tc.pr, h2);
  }
  PROFS(15, 2, k * 4 + c);
}
__device__ __forceinline__ void gather_px(const __nv_bfloat16* __restrict__ x, uint32_t sbase, const TileCoord tc) {
  const int lane = threadIdx.x & 31, g = lane >> 3;
  uint32_t ro[4], co[4];
#pragma unroll
  for (int i = 0; i < 4; i++) {
    ro[i] = qpix(tc.pr, 8 * tc.I + 2 * i + (g & 1)) * (kW * kC * 2) + 16 * (lane & 7);
    co[i] = qpix(tc.pc, 8 * tc.J + 2 * i + (g >> 1)) * (kC * 2);
  }
  const uint32_t dst = sbase + kXOff + g * 128 + (((lane & 7) ^ g) << 4);
  if (lane < 8)
    asm volatile("cp.async.bulk.prefetch.L2.global [%0], 3456;" ::"l"(x + (qpix(tc.pr, 8 * tc.I + lane) * kW + 215 * tc.pc) * kC) : "memory");
  __syncwarp();
  keep_regs(ro);
  keep_regs(co);
  sched_fence();
  nb_sync_p(13);
  nb_sync_p(5);
#pragma unroll
  for (int i = 0; i < 16; i++) {
    const char* src = (const char*)x + (ro[i >> 2] + co[i & 3]);
#pragma unroll
    for (int q = 0; q < 3; q++)
      asm volatile("cp.async.cg.shared.global [%0], [%1], 16;" ::"r"((dst ^ ((i & 1) * 576)) + (i >> 1) * 1024 + q * 8192), "l"(src + 128 * q) : "memory");
  }
  asm volatile("cp.async.wait_all;" ::: "memory");
  fence_proxy_async();
  __syncwarp();
  if (lane < 3) mbar_arrive(bar_x(sbase + kBarOff, 1, lane));
  __syncwarp();
}

__global__ void __launch_bounds__(384, 1)
nat_kernel(const __nv_bfloat16* __restrict__ x, __nv_bfloat16* out, const __nv_bfloat16* __restrict__ wqkv,
           const __nv_bfloat16* __restrict__ wo, uint8_t* wimg, const uint32_t zero,
           const __grid_constant__ Maps tm, const __grid_constant__ TileTable tt) {
  extern __shared__ uint8_t smem_raw[];
  constexpr uint32_t sbase = 1024;
  constexpr uint32_t bars = sbase + kBarOff;
  if (smem_u32(smem_raw) != sbase) __trap();
  const int tid = threadIdx.x;
  const uint32_t t_start = now_ns();
  if (tid == 0) GT(0);
  const int wid = __shfl_sync(0xffffffffu, tid >> 5, 0);
  const bool w2cta = blockIdx.x - 128 < 3 && wqkv != nullptr;
  if (wid >= 8) {
    asm volatile("setmaxnreg.dec.sync.aligned.u32 24;");
    const int c = wid & 3, lane = tid & 31;
    const int tile0 = blockIdx.x * kTilesPerCta, nt = num_tiles();
    uint32_t w2o = 0;
    if (c == 3) {
      if (elect_one()) wait_clock(t_start, NAT_TM);
      __syncwarp();
      asm volatile("prefetch.tensormap [%0];" ::"l"((uint64_t)tm.px) : "memory");
      asm volatile("prefetch.tensormap [%0];" ::"l"((uint64_t)&tm.v6) : "memory");
      asm volatile("prefetch.tensormap [%0];" ::"l"((uint64_t)&tm.v2) : "memory");
      asm volatile("prefetch.tensormap [%0];" ::"l"((uint64_t)(tm.px + (blockIdx.x < 112 ? 5 : 6))) : "memory");
      asm volatile("prefetch.tensormap [%0];" ::"l"((uint64_t)(tm.px + 7)) : "memory");
      if (nt < 6) {
        asm volatile("prefetch.tensormap [%0];" ::"l"((uint64_t)(tm.px + 1)) : "memory");
        asm volatile("prefetch.tensormap [%0];" ::"l"((uint64_t)(tm.px + 2)) : "memory");
        asm volatile("prefetch.tensormap [%0];" ::"l"((uint64_t)&tm.v14) : "memory");
        asm volatile("prefetch.tensormap [%0];" ::"l"((uint64_t)&tm.u8) : "memory");
      }
      __nanosleep(1600);
      asm volatile("bar.sync 4, 64;" ::: "memory");
      w2o = w2_offset();
      if (elect_one()) {
        mbar_arrive_expect_tx(bar_w2a(bars), kWChunk);
        mbar_arrive_expect_tx(bar_w2(bars), kWChunk);
        sleep_clock(t_start, NAT_TW2);
        bulk_load(sbase + kW2Off, wimg + w2o, kWChunk, bar_w2a(bars));
        mbar_wait(bar_xf(bars), 0);
        bulk_load(sbase + kW2Off + 2 * kWChunk, wimg + (w2o + 2 * kWChunk), kWChunk, bar_w2(bars));
      }
      __syncwarp();
      if (nt < 6) gather_px(x, sbase, decode_tile(tt, tile0 + 2));
      if (wqkv == nullptr) return;
      __nanosleep(2500);
      mbar_wait(bar_wok(bars), 0);
      if (lane == 0) asm volatile("red.relaxed.gpu.global.add.u32 [%0], 1;" ::"l"(g_flag) : "memory");
      if (blockIdx.x != kCtas - 1) return;
#pragma unroll
      for (int i = 0; i < 8; i++) asm volatile("st.shared.v4.u32 [%0], {%1,%1,%1,%1};" ::"r"(bars + 1024 + i * 512 + lane * 16), "r"(kEmpty) : "memory");
      fence_proxy_async();
      __syncwarp();
      if (elect_one()) {
#pragma unroll 1
        for (int i = 0; i < 36; i++) {
          if (i == 18) {
            uint32_t v, it = 0;
            do {
              __nanosleep(500);
              asm volatile("ld.relaxed.gpu.global.u32 %0, [%1];" : "=r"(v) : "l"(g_flag) : "memory");
            } while (v < gridDim.x && ++it < (1u << 18));
          }
          asm volatile("cp.async.bulk.global.shared::cta.bulk_group [%0], [%1], 4096;" ::"l"(
                           wimg + (i < 18 ? 3 * kWBytes - w2o + i * 4096 : (i - 18) * 4096)), "r"(bars + 1024) : "memory");
          asm volatile("cp.async.bulk.commit_group;" ::: "memory");
          asm volatile("cp.async.bulk.wait_group.read 1;" ::: "memory");
        }
        asm volatile("cp.async.bulk.wait_group 0;" ::: "memory");
        g_flag[0] = 0;
        g_flag[32] = w2o == kWBytes;
      }
      return;
    }
    if (!elect_one()) return;
    if (c == 0) {
      for (int i = 0; i < kNumBars; i++)
        if ((i != 0 && i != 10 || nt < 6) && (i != 21 || !w2cta)) mbar_init(bars + i * 8, i == 13 || i == 16 ? 4 : 1);
      asm volatile("st.shared.v2.u32 [%0], {%1,%1};" ::"r"(bars + 192), "r"(0) : "memory");
      asm volatile("fence.mbarrier_init.release.cluster;" ::: "memory");
      if (w2cta) asm volatile("bar.sync 10, 64;" ::: "memory");
      asm volatile("bar.arrive 0, 160;" ::: "memory");
      asm volatile("bar.arrive 14, 160;" ::: "memory");
      asm volatile("bar.arrive 13, 96;" ::: "memory");
      asm volatile("bar.arrive 4, 64;" ::: "memory");
      const TileCoord tc0 = decode_tile(tt, tile0);
      const HaloCols hc = halo_cols(tc0);
      const int h0 = halo_r0(tc0);
#pragma unroll
      for (int j = 0; j < 3; j++)
        if (j > 0 || nt < 6) mbar_arrive_expect_tx(bar_full(bars, 0, j), 2 * kChunkBytes);
      wait_clock(t_start, NAT_HP);
#pragma unroll
      for (int q = 8; q < 24 && !w2cta; q += 8) {
        tma_prefetch_5d(blockIdx.x < 112 ? &tm.v6 : &tm.v14, 24 * tc0.pc + q, hc.vj, hc.vc, tc0.pr, h0 + (tc0.up || blockIdx.x >= 112 ? 0 : 8));
        tma_prefetch_5d(&tm.u8, 24 * tc0.pc + q, hc.uj, h0 + (tc0.up ? 0 : 6), tc0.pr, hc.uc);
      }
#pragma unroll 1
      for (int i = nt < 6 ? 0 : 2; i < 6; i++) {
        if (i == 2) mbar_wait(bar_w1q(bars), 0);
        first_halo(tm, sbase, tc0, i);
      }
      mbar_arrive(bar_go(bars));
      w2o = w2_offset();
    } else {
      asm volatile("bar.sync 13, 96;" ::: "memory");
      if (c == 2) {
        if (wqkv != nullptr && blockIdx.x < 131) asm volatile("bar.sync 12, 64;" ::: "memory");
        const uint32_t c0 = clock();
        while ((uint32_t)clock() - c0 < NAT_TD && nt == 6) { }
        wait_clock(t_start, NAT_T0);
#pragma unroll
        for (int j = 0; j < 3; j++) {
          mbar_arrive_expect_tx(bar_w1c(bars, j), kWChunk);
          bulk_load(sbase + kW1Off + j * kWChunk, wimg + j * kWChunk, kWChunk, bar_w1c(bars, j));
        }
        mbar_arrive(bar_w1q(bars));
        GT(2);
      } else {
#pragma unroll 1
        for (int j = nt == 6; j < 2; j++) {
          const TileCoord tc = decode_tile(tt, tile0 + j);
          const int line = first_line(tc);
          if (j == 1) mbar_wait(bar_go(bars), 0);
          if (j == 0) GT(15);
#pragma unroll 1
          for (int q = 0; q < 3; q++) {
            load_px(tm, tt, sbase + x_chunk(j, q), bar_x(bars, j, q), line + q, tc.kind);
            if (j == 1 || q == 0) mbar_arrive_expect_tx(bar_x(bars, j, q), j ? 8192 : kWChunk);
          }
          if (j == 0) GT(16);
        }
        w2o = w2_offset();
        sleep_clock(t_start, NAT_TW2);
        mbar_wait(bar_xf(bars), 0);
      }
    }
#pragma unroll 1
    for (int k = 1; k < nt; k++) {
      const TileCoord tn = decode_tile(tt, tile0 + k + 1);
      const int line = first_line(tn);
      const bool more = k + 1 < nt && (k > 1 || nt == 6);
      if (c == 1) {
#pragma unroll
        for (int q = 0; q < 3; q++) {
          nb_sync_p(q == 0 ? 0 : q == 1 ? 14 : 6);
          bulk_load(sbase + x_chunk(k, q), wimg + (w2o + x_chunk(k, q) - kW2Off), 8192, bar_w2m(bars));
        }
        mbar_arrive_expect_tx(bar_w2m(bars), kWChunk);
      }
      if (c == 2) {
        if (k == 1) sleep_clock(t_start, NAT_TX2);
        else __nanosleep(NAT_PFD);
#pragma unroll 1
        for (int q = 0; q < 3 && more; q++) load_px(tm, tt, 0, 0, line + q, tn.kind);
      }
      if (c == 2 && (blockIdx.x >= 112 || k == 5)) {
        const TileCoord tc = decode_tile(tt, tile0 + k);
        const HaloCols hc = halo_cols(tc);
        const int h8 = halo_r0(tc) + (tc.up ? 0 : 6);
#pragma unroll 1
        for (int q = 0; q < 24; q += 8) {
          tma_prefetch_5d(&tm.v6, 24 * tc.pc + q, hc.vj, hc.vc, tc.pr, h8);
          tma_prefetch_5d(&tm.v2, 24 * tc.pc + q, hc.vj, hc.vc, tc.pr, h8 + 6);
          tma_prefetch_5d(&tm.u8, 24 * tc.pc + q, hc.uj, h8, tc.pr, hc.uc);
        }
      }
      load_halo(tm, sbase, bars, decode_tile(tt, tile0 + k), k, c);
      if (c == 0 && more) {
        if (nt < 6) mbar_wait(bar_x(bars, 1, 0), 1);
#pragma unroll
        for (int q = 0; q < 3; q++) {
          if (q < 2) nb_sync_p(q ? 5 : 13);
          load_px(tm, tt, sbase + x_chunk(k + 1, q), bar_x(bars, 1, q), line + q, tn.kind);
          if (q != 1) mbar_arrive_expect_tx(bar_x(bars, 1, q), 8192);
        }
        mbar_arrive_expect_tx(bar_x(bars, 1, 1), 8192);
        PROFS(16, 2, k * 4 + 3);
      }
      if (c == 0 && k >= 2) {
        const TileCoord tp = decode_tile(tt, tile0 + k - 2);
        const int lp = first_line(tp);
        nb_sync_p(10);
        __nanosleep(NAT_XW);
        store_px(tm, tt, sbase + out_slot(k, nt), lp, tp.kind);
        if (k + 1 < nt) {
          asm volatile("cp.async.bulk.wait_group.read 0;" ::: "memory");
          bulk_load(sbase + out_slot(k, nt), wimg + (w2o + out_slot(k, nt) - kW2Off), kWChunk, bar_w2(bars));
          mbar_arrive_expect_tx(bar_w2(bars), kWChunk);
        }
      }
    }
    asm volatile("cp.async.bulk.wait_group 0;" ::: "memory");
  } else {
    if (blockIdx.x < 128) {
      if ((wid == 4 || (wid == 5 && blockIdx.x - 2 < 16)) && wqkv != nullptr) {
        fold_w1(blockIdx.x - 2 < 16 ? 2 * blockIdx.x + wid - 6 : blockIdx.x + (blockIdx.x < 2 ? 0 : 16), wqkv, wimg);
        if (wid == 4) asm volatile("bar.arrive 12, 64;" ::: "memory");
        if (tid == 128) GT(7);
      }
      sched_fence();
      if (wid == 1 && elect_one()) {
        const TileCoord tc = decode_tile(tt, blockIdx.x * kTilesPerCta);
        mbar_init(bar_x(bars, 0, 0), 1);
        asm volatile("fence.mbarrier_init.release.cluster;" ::: "memory");
        mbar_arrive_expect_tx(bar_x(bars, 0, 0), kWChunk);
        GT(15);
#pragma unroll 1
        for (int q = 0; q < 3; q++) load_px(tm, tt, sbase + x_chunk(0, q), bar_x(bars, 0, 0), first_line(tc) + q, tc.kind);
        GT(16);
      }
      __syncwarp();
      sched_fence();
      if (wid == 2 && elect_one()) {
        const TileCoord tc = decode_tile(tt, blockIdx.x * kTilesPerCta);
        mbar_init(bar_full(bars, 0, 0), 1);
        asm volatile("fence.mbarrier_init.release.cluster;" ::: "memory");
        mbar_arrive_expect_tx(bar_full(bars, 0, 0), 2 * kChunkBytes);
        asm volatile("prefetch.tensormap [%0];" ::"l"((uint64_t)&tm.u8) : "memory");
        GT(17);
        first_halo(tm, sbase, tc, 0);
        first_halo(tm, sbase, tc, 1);
      }
      __syncwarp();
    }
    sched_fence();
    {
      if (blockIdx.x >= 128 && wqkv != nullptr && (wid | 2) == 2 && elect_one())
        asm volatile("cp.async.bulk.prefetch.L2.global [%0], %1;" ::"l"(wid ? wo + (blockIdx.x & 3) * 48 * 192 : wqkv + (blockIdx.x & 3) * 48 * 576),
                     "r"(wid ? 48 * 384 : 48 * 1152) : "memory");
      __syncwarp();
      if (w2cta) {
        const int q = blockIdx.x & 3, h = wid >> 2;
        uint32_t w2o = 0;
        if (wid == 1 && elect_one()) {
          asm volatile("prefetch.tensormap [%0];" ::"l"((uint64_t)&tm.wo) : "memory");
          mbar_init(bar_raw(bars, 0), 1);
          mbar_init(bar_raw(bars, 1), 1);
          asm volatile("fence.mbarrier_init.release.cluster;" ::: "memory");
#pragma unroll
          for (int j = 0; j < 3; j++)
            asm volatile("cp.async.bulk.tensor.3d.shared::cluster.global.tile.mbarrier::complete_tx::bytes [%0], [%1, {%3, %4, %5}], [%2];" ::"r"(
                             j ? sbase + kW2Off + (j - 1) * (kWBytes / 2) : sbase),
                         "l"((uint64_t)(j ? &tm.wo : &tm.wv)), "r"(bar_raw(bars, j >> 1)), "r"(0), "r"(j ? 0 : 64 * q), "r"(j ? 3 * j - 3 : 6) : "memory");
          mbar_arrive_expect_tx(bar_raw(bars, 0), kWChunk + kWBytes / 2);
          mbar_arrive_expect_tx(bar_raw(bars, 1), kWBytes / 2);
          w2o = w2_offset();
        }
        __syncwarp();
#pragma unroll 1
        for (int r = 1 - h;; r++) {
          if (r > 0) asm volatile("bar.sync 11, 256;" ::: "memory");
          if (r == 2) break;
          if (r > 0) {
            mbar_wait(bar_raw(bars, 0), 0);
            mbar_wait(bar_raw(bars, h), 0);
          }
          if (tid == 0) GT(7);
          float acc[48];
          const uint64_t db = make_desc(sbase + kW2Off + h * (kWBytes / 2), kWChunk / 2, 512, 2);
          wg_fence();
          wg_m96tz<0, 48>(acc, make_desc(sbase, 16, 1024), db, 0);
#pragma unroll
          for (int s = 1; s < 12; s++) wg_m96t<0, 48>(acc, make_desc(sbase + (s >> 2) * 8192 + (s & 3) * 32, 16, 1024), db + s * 64, 1);
          wg_commit();
          wg_wait<0>();
          fence_regs(acc);
          if (tid == 0) GT(19);
          const int m = (tid >> 3) & 3;
#pragma unroll
          for (int j = 0; j < 12; j += 2) {
            const int n = g2_inv(8 * (j + (m >> 1)) + (tid & 7));
            asm volatile("stmatrix.sync.aligned.m8n8.x4.trans.shared.b16 [%0], {%1,%2,%3,%4};" ::"r"(
                             sbase + kW1Off + h * (kWChunk / 2) + n * 128 + (((2 * (wid & 3) + (m & 1)) ^ (n & 7)) << 4)),
                         "r"(pack_bf16(acc[4 * j], acc[4 * j + 1])), "r"(pack_bf16(acc[4 * j + 2], acc[4 * j + 3])),
                         "r"(pack_bf16(acc[4 * j + 4], acc[4 * j + 5])), "r"(pack_bf16(acc[4 * j + 6], acc[4 * j + 7])) : "memory");
          }
          fence_proxy_async();
        }
        if (tid == 0) GT(18);
        if (wid == 1) {
          if (elect_one()) {
#pragma unroll
            for (int i = 0; i < 2; i++)
              asm volatile("cp.async.bulk.global.shared::cta.bulk_group [%0], [%1], %2;" ::"l"(wimg + (w2o + w2piece(i, q) * (kWChunk / 2))),
                           "r"(sbase + kW1Off + i * (kWChunk / 2)), "r"(kWChunk / 2) : "memory");
            asm volatile("cp.async.bulk.commit_group;" ::: "memory");
          }
          __syncwarp();
          asm volatile("bar.arrive 10, 64;" ::: "memory");
          if (elect_one()) asm volatile("cp.async.bulk.wait_group.read 0;" ::: "memory");
          if (tid == 32) GT(31);
          __syncwarp();
          asm volatile("bar.arrive 12, 64;" ::: "memory");
        }
      }
    }
    __syncwarp();
    if (wid < 4) asm volatile("bar.sync 0, 160;" ::: "memory");
    else asm volatile("bar.sync 14, 160;" ::: "memory");
    asm volatile("setmaxnreg.inc.sync.aligned.u32 240;");
    consumer(wid >> 2, out, wimg, sbase, zero, tm, tt);
  }
}

}

typedef CUresult (*PFN_encodeTiled)(CUtensorMap*, CUtensorMapDataType, cuuint32_t, void*, const cuuint64_t*,
                                    const cuuint64_t*, const cuuint32_t*, const cuuint32_t*, CUtensorMapInterleave,
                                    CUtensorMapSwizzle, CUtensorMapL2promotion, CUtensorMapFloatOOBfill);

extern "C" void kernel_launch(void* const* d_in, const int* in_sizes, int n_in, void* d_out, int out_size) {
  const __nv_bfloat16* x = (const __nv_bfloat16*)d_in[0];
  const __nv_bfloat16* wqkv = (const __nv_bfloat16*)d_in[1];
  const __nv_bfloat16* wo = (const __nv_bfloat16*)d_in[2];
  __nv_bfloat16* out = (__nv_bfloat16*)d_out;

  static PFN_encodeTiled encode = nullptr;
  static int num_sms = 0;
  static uint8_t* wimg = nullptr;
  if (!encode) {
    void* fn = nullptr;
    cudaDriverEntryPointQueryResult qres;
    cudaGetDriverEntryPoint("cuTensorMapEncodeTiled", &fn, cudaEnableDefault, &qres);
    encode = (PFN_encodeTiled)fn;
    cudaFuncSetAttribute(nat::nat_kernel, cudaFuncAttributeMaxDynamicSharedMemorySize, nat::kSmemBytes);
    cudaGetSymbolAddress((void**)&wimg, nat::g_wimg32);
    int dev = 0;
    cudaGetDevice(&dev);
    cudaDeviceGetAttribute(&num_sms, cudaDevAttrMultiProcessorCount, dev);
  }
  nat::Maps tm;
  cuuint32_t estr[5] = {1, 1, 1, 1, 1};
  {
    cuuint64_t vdim[5] = {48, 2, 105, 2, 112}, udim[5] = {48, 2, 112, 2, 105};
    cuuint64_t vstr[4] = {7 * 768, 768, 224 * 384, 2 * 224 * 384}, ustr[4] = {7 * 768, 2 * 224 * 384, 224 * 384, 768};
    CUtensorMap* maps[4] = {&tm.v6, &tm.v2, &tm.v14, &tm.u8};
    for (int i = 0; i < 4; i++) {
      cuuint32_t box[5] = {4, 2, i < 3 ? 4u : 8u, 1, i == 0 ? 6u : i == 1 ? 2u : i == 2 ? 14u : 3u};
      encode(maps[i], CU_TENSOR_MAP_DATA_TYPE_UINT32, 5, (void*)x, i < 3 ? vdim : udim, i < 3 ? vstr : ustr, box, estr,
             CU_TENSOR_MAP_INTERLEAVE_16B, CU_TENSOR_MAP_SWIZZLE_128B, CU_TENSOR_MAP_L2_PROMOTION_L2_128B, CU_TENSOR_MAP_FLOAT_OOB_FILL_NONE);
    }
  }
  for (int i = 0; i < 8; i++) {
    const cuuint32_t row = 224 * 384;
    const cuuint32_t shape[8][6] = {{2, 8, 4, 2 * row, 768, 4 * row}, {2, 8, 3, row, 768, 2 * row},     {2, 8, 1, 2 * row, 768, 4 * row},
                                    {8, 2, 3, 2 * row, 4 * 384, 384}, {8, 2, 1, 2 * row, 5 * 384, 384}, {4, 2, 3, 4 * row, 2 * row, 128},
                                    {4, 2, 3, 768, row, 128},         {4, 2, 3, 768, 2 * row, 128}};
    const cuuint32_t* sh = shape[i];
    cuuint64_t dim[5] = {64, sh[0], sh[1], sh[2], 224 * 224 * 3};
    cuuint64_t str[4] = {sh[3], sh[4], sh[5], 128};
    cuuint32_t box[5] = {64, sh[0], sh[1], sh[2], 1};
    encode(tm.px + i, CU_TENSOR_MAP_DATA_TYPE_BFLOAT16, 5, i < 5 ? (void*)x : (void*)out, dim, str, box, estr, CU_TENSOR_MAP_INTERLEAVE_NONE,
           CU_TENSOR_MAP_SWIZZLE_128B, i < 5 ? CU_TENSOR_MAP_L2_PROMOTION_L2_128B : CU_TENSOR_MAP_L2_PROMOTION_NONE,
           CU_TENSOR_MAP_FLOAT_OOB_FILL_NONE);
  }
  for (int i = 0; i < 2; i++) {
    cuuint64_t dim[3] = {i ? 32u : 64u, 192, i ? 6u : 9u}, str[2] = {i ? 384u : 1152u, i ? 64u : 128u};
    cuuint32_t box[3] = {i ? 32u : 64u, i ? 192u : 64u, 3};
    encode(i ? &tm.wo : &tm.wv, CU_TENSOR_MAP_DATA_TYPE_BFLOAT16, 3, i ? (void*)wo : (void*)wqkv, dim, str, box, estr,
           CU_TENSOR_MAP_INTERLEAVE_NONE, i ? CU_TENSOR_MAP_SWIZZLE_64B : CU_TENSOR_MAP_SWIZZLE_128B, CU_TENSOR_MAP_L2_PROMOTION_L2_256B,
           CU_TENSOR_MAP_FLOAT_OOB_FILL_NONE);
  }
  nat::TileTable tt;
  nat::make_tiles(tt);
  const int grid = nat::kCtas;
  if (num_sms >= grid) {
    nat::nat_kernel<<<grid, 384, nat::kSmemBytes>>>(x, out, wqkv, wo, wimg, 0u, tm, tt);
  } else {
    nat::fold_kernel<<<27, 256>>>(wqkv, wo, wimg);
    nat::nat_kernel<<<grid, 384, nat::kSmemBytes>>>(x, out, nullptr, nullptr, wimg, 0u, tm, tt);
  }
}
```

```cpp
#include <cuda_runtime.h>
#include <cuda_bf16.h>
#include <cuda.h>
#include <stdint.h>

#define NAT_TM 1300
#define NAT_HP 1800
#define NAT_T0 2130
#define NAT_TD 1250
#define NAT_TX2 3800
#define NAT_TW2 4600
#define NAT_PFD 300
#define NAT_XW 200
#define NAT_PK 3
namespace nat {

constexpr int kW = 224, kC = 192;
constexpr int kCtas = 132;
constexpr int kTilesPerCta = 6;
constexpr float kAlpha = 0.07216878364870322f * 1.4426950408889634f;
constexpr uint32_t kChunkBytes = 13 * 1024;
constexpr uint32_t kWChunk = 192 * 128;
constexpr uint32_t kWBytes = 3 * kWChunk;
constexpr uint32_t kW1Off = 6 * kChunkBytes;
constexpr uint32_t kW2Off = kW1Off + kWBytes;
constexpr uint32_t kXOff = kW2Off + kWChunk;
constexpr uint32_t kBarOff = kW2Off + kWBytes;
constexpr uint32_t kProfOff = kBarOff + 208;
constexpr uint32_t kSmemBytes = kBarOff + 1024 + 4096;

static_assert(kW1Off % 1024 == 0 && kW2Off % 1024 == 0 && kChunkBytes % 1024 == 0, "swizzle alignment");
static_assert(kSmemBytes <= 232448, "smem");

constexpr uint32_t kEmpty = 0xFFFFFFFFu;
#define NAT_R8(v) v, v, v, v, v, v, v, v
#define NAT_R2K(v) NAT_R8(NAT_R8(NAT_R8(v))), NAT_R8(NAT_R8(NAT_R8(v))), NAT_R8(NAT_R8(NAT_R8(v))), NAT_R8(NAT_R8(NAT_R8(v)))
#define NAT_IMG NAT_R8(NAT_R2K(kEmpty)), NAT_R2K(kEmpty)
__device__ __align__(1024) uint32_t g_wimg32[3 * kWBytes / 4] = {NAT_IMG, NAT_IMG, NAT_IMG};
static_assert(kWBytes / 4 == 9 * 2048, "initialiser");
__device__ __align__(128) uint32_t g_flag[64];
__device__ __forceinline__ uint32_t w2_offset() {
  uint32_t v;
  asm volatile("ld.relaxed.gpu.global.u32 %0, [%1];" : "=r"(v) : "l"(g_flag + 32) : "memory");
  return (1 + v) * kWBytes;
}

#define PROFS(id, wgid, slotid) do { } while (0)
#define PROF(wgid, slotid) do { } while (0)
#define PROF_DUMP(wgid) do { } while (0)

#define GT(slotid) do { } while (0)
#define GT_DUMP() do { } while (0)

__device__ __forceinline__ uint32_t smem_u32(const void* p) { return (uint32_t)__cvta_generic_to_shared(p); }

__device__ __forceinline__ void mbar_init(uint32_t bar, uint32_t count) {
  asm volatile("mbarrier.init.shared::cta.b64 [%0], %1;" ::"r"(bar), "r"(count) : "memory");
}
__device__ __forceinline__ void mbar_arrive(uint32_t bar) {
  asm volatile("mbarrier.arrive.shared::cta.b64 _, [%0];" ::"r"(bar) : "memory");
}
__device__ __forceinline__ void mbar_arrive_expect_tx(uint32_t bar, uint32_t bytes) {
  asm volatile("mbarrier.arrive.expect_tx.shared::cta.b64 _, [%0], %1;" ::"r"(bar), "r"(bytes) : "memory");
}
__device__ __forceinline__ void mbar_wait(uint32_t bar, uint32_t parity) {
  uint32_t ok;
  uint32_t it = 0;
  do {
    asm volatile(
        "{\n.reg .pred p;\n"
        "mbarrier.try_wait.parity.shared::cta.b64 p, [%1], %2;\n"
        "selp.u32 %0, 1, 0, p;\n}\n"
        : "=r"(ok)
        : "r"(bar), "r"(parity)
        : "memory");
    if (++it > (1u << 24)) break;
  } while (!ok);
}
__device__ __forceinline__ uint32_t mbar_test(uint32_t bar, uint32_t parity) {
  uint32_t ok;
  asm volatile("{\n.reg .pred p;\nmbarrier.test_wait.parity.shared::cta.b64 p, [%1], %2;\nselp.u32 %0, 1, 0, p;\n}\n"
               : "=r"(ok) : "r"(bar), "r"(parity) : "memory");
  return ok;
}
__device__ __forceinline__ void mbar_wait_if(uint32_t ok, uint32_t bar, uint32_t parity) {
  if (!__all_sync(0xffffffffu, ok)) mbar_wait(bar, parity);
}
__device__ __forceinline__ bool elect_one() {
  uint32_t r;
  asm volatile("{\n.reg .pred p;\nelect.sync _|p, 0xffffffff;\nselp.u32 %0, 1, 0, p;\n}\n" : "=r"(r));
  return r != 0;
}
__device__ __forceinline__ void nb_arrive(int id) { asm volatile("bar.arrive %0, 256;" ::"r"(id) : "memory"); }
__device__ __forceinline__ void nb_sync(int id) { asm volatile("bar.sync %0, 256;" ::"r"(id) : "memory"); }
__device__ __forceinline__ void nb_arrive_p(int id) { asm volatile("bar.arrive %0, 160;" ::"r"(id) : "memory"); }
__device__ __forceinline__ void nb_sync_p(int id) { asm volatile("bar.sync %0, 160;" ::"r"(id) : "memory"); }
__device__ __forceinline__ void fence_proxy_async() { asm volatile("fence.proxy.async.shared::cta;" ::: "memory"); }

__device__ __forceinline__ void tma_load_5d(uint32_t dst, const CUtensorMap* map, uint32_t bar, int c0, int c1, int c2,
                                            int c3, int c4) {
  asm volatile(
      "cp.async.bulk.tensor.5d.shared::cluster.global.tile.mbarrier::complete_tx::bytes "
      "[%0], [%1, {%3, %4, %5, %6, %7}], [%2];"
      ::"r"(dst), "l"((uint64_t)map), "r"(bar), "r"(c0), "r"(c1), "r"(c2), "r"(c3), "r"(c4)
      : "memory");
}
__device__ __forceinline__ void bulk_load(uint32_t dst, const void* src, uint32_t bytes, uint32_t bar) {
  asm volatile("cp.async.bulk.shared::cluster.global.mbarrier::complete_tx::bytes [%0], [%1], %2, [%3];"
               ::"r"(dst), "l"((uint64_t)src), "r"(bytes), "r"(bar)
               : "memory");
}

__device__ __forceinline__ void wg_fence() { asm volatile("wgmma.fence.sync.aligned;" ::: "memory"); }
__device__ __forceinline__ void wg_commit() { asm volatile("wgmma.commit_group.sync.aligned;" ::: "memory"); }
template <int N>
__device__ __forceinline__ void wg_wait() { asm volatile("wgmma.wait_group.sync.aligned %0;" ::"n"(N) : "memory"); }

template <int N>
__device__ __forceinline__ void fence_regs(float (&d)[N]) {
#pragma unroll
  for (int i = 0; i < N; i++) asm volatile("" : "+f"(d[i])::"memory");
}
template <int N>
__device__ __forceinline__ void keep_regs(uint32_t (&d)[N]) {
#pragma unroll
  for (int i = 0; i < N; i++) asm volatile("" : "+r"(d[i])::"memory");
}

__device__ __forceinline__ uint32_t pack_bf16(float lo, float hi) {
  uint32_t d;
  asm("cvt.rn.bf16x2.f32 %0, %1, %2;" : "=r"(d) : "f"(hi), "f"(lo));
  return d;
}
__device__ __forceinline__ float ex2(float x) {
  float y;
  asm("ex2.approx.ftz.f32 %0, %1;" : "=f"(y) : "f"(x));
  return y;
}
__device__ __forceinline__ float rcp_approx(float x) {
  float y;
  asm("rcp.approx.ftz.f32 %0, %1;" : "=f"(y) : "f"(x));
  return y;
}
__device__ __forceinline__ uint4 ldg128_nc(const void* p) {
  uint4 v;
  asm volatile("ld.global.nc.v4.u32 {%0,%1,%2,%3}, [%4];" : "=r"(v.x), "=r"(v.y), "=r"(v.z), "=r"(v.w) : "l"(p));
  return v;
}

__device__ __forceinline__ long long clk64() {
  long long c;
  asm volatile("mov.u64 %0, %clock64;" : "=l"(c)::"memory");
  return c;
}
__device__ __forceinline__ void sched_fence() { while (clk64() < 0) { } }

__device__ __forceinline__ uint64_t make_desc(uint32_t addr, uint32_t lbo, uint32_t sbo, uint32_t mode = 1) {
  return (uint64_t)((addr & 0x3FFFF) >> 4) | ((uint64_t)(lbo >> 4) << 16) | ((uint64_t)(sbo >> 4) << 32) |
         ((uint64_t)mode << 62);
}

template <int OFF, int NN>
__device__ __forceinline__ void wg_m192(float (&d)[NN], uint64_t desc_a, uint64_t desc_b, int scale_d) {
  asm volatile(
      "{\n.reg .pred p;\nsetp.ne.b32 p, %98, 0;\n"
      "wgmma.mma_async.sync.aligned.m64n192k16.f32.bf16.bf16 "
      "{%0,%1,%2,%3,%4,%5,%6,%7,%8,%9,%10,%11,%12,%13,%14,%15,"
      "%16,%17,%18,%19,%20,%21,%22,%23,%24,%25,%26,%27,%28,%29,%30,%31,"
      "%32,%33,%34,%35,%36,%37,%38,%39,%40,%41,%42,%43,%44,%45,%46,%47,"
      "%48,%49,%50,%51,%52,%53,%54,%55,%56,%57,%58,%59,%60,%61,%62,%63,"
      "%64,%65,%66,%67,%68,%69,%70,%71,%72,%73,%74,%75,%76,%77,%78,%79,"
      "%80,%81,%82,%83,%84,%85,%86,%87,%88,%89,%90,%91,%92,%93,%94,%95}, "
      "%96, %97, p, 1, 1, 0, 0;\n}\n"
      : "+f"(d[OFF + 0]), "+f"(d[OFF + 1]), "+f"(d[OFF + 2]), "+f"(d[OFF + 3]), "+f"(d[OFF + 4]), "+f"(d[OFF + 5]),
        "+f"(d[OFF + 6]), "+f"(d[OFF + 7]), "+f"(d[OFF + 8]), "+f"(d[OFF + 9]), "+f"(d[OFF + 10]), "+f"(d[OFF + 11]),
        "+f"(d[OFF + 12]), "+f"(d[OFF + 13]), "+f"(d[OFF + 14]), "+f"(d[OFF + 15]), "+f"(d[OFF + 16]), "+f"(d[OFF + 17]),
        "+f"(d[OFF + 18]), "+f"(d[OFF + 19]), "+f"(d[OFF + 20]), "+f"(d[OFF + 21]), "+f"(d[OFF + 22]), "+f"(d[OFF + 23]),
        "+f"(d[OFF + 24]), "+f"(d[OFF + 25]), "+f"(d[OFF + 26]), "+f"(d[OFF + 27]), "+f"(d[OFF + 28]), "+f"(d[OFF + 29]),
        "+f"(d[OFF + 30]), "+f"(d[OFF + 31]), "+f"(d[OFF + 32]), "+f"(d[OFF + 33]), "+f"(d[OFF + 34]), "+f"(d[OFF + 35]),
        "+f"(d[OFF + 36]), "+f"(d[OFF + 37]), "+f"(d[OFF + 38]), "+f"(d[OFF + 39]), "+f"(d[OFF + 40]), "+f"(d[OFF + 41]),
        "+f"(d[OFF + 42]), "+f"(d[OFF + 43]), "+f"(d[OFF + 44]), "+f"(d[OFF + 45]), "+f"(d[OFF + 46]), "+f"(d[OFF + 47]),
        "+f"(d[OFF + 48]), "+f"(d[OFF + 49]), "+f"(d[OFF + 50]), "+f"(d[OFF + 51]), "+f"(d[OFF + 52]), "+f"(d[OFF + 53]),
        "+f"(d[OFF + 54]), "+f"(d[OFF + 55]), "+f"(d[OFF + 56]), "+f"(d[OFF + 57]), "+f"(d[OFF + 58]), "+f"(d[OFF + 59]),
        "+f"(d[OFF + 60]), "+f"(d[OFF + 61]), "+f"(d[OFF + 62]), "+f"(d[OFF + 63]), "+f"(d[OFF + 64]), "+f"(d[OFF + 65]),
        "+f"(d[OFF + 66]), "+f"(d[OFF + 67]), "+f"(d[OFF + 68]), "+f"(d[OFF + 69]), "+f"(d[OFF + 70]), "+f"(d[OFF + 71]),
        "+f"(d[OFF + 72]), "+f"(d[OFF + 73]), "+f"(d[OFF + 74]), "+f"(d[OFF + 75]), "+f"(d[OFF + 76]), "+f"(d[OFF + 77]),
        "+f"(d[OFF + 78]), "+f"(d[OFF + 79]), "+f"(d[OFF + 80]), "+f"(d[OFF + 81]), "+f"(d[OFF + 82]), "+f"(d[OFF + 83]),
        "+f"(d[OFF + 84]), "+f"(d[OFF + 85]), "+f"(d[OFF + 86]), "+f"(d[OFF + 87]), "+f"(d[OFF + 88]), "+f"(d[OFF + 89]),
        "+f"(d[OFF + 90]), "+f"(d[OFF + 91]), "+f"(d[OFF + 92]), "+f"(d[OFF + 93]), "+f"(d[OFF + 94]), "+f"(d[OFF + 95])
      : "l"(desc_a), "l"(desc_b), "r"(scale_d));
}

template <int OFF, int NN>
__device__ __forceinline__ void wg_m192z(float (&d)[NN], uint64_t desc_a, uint64_t desc_b, int scale_d) {
  asm volatile(
      "{\n.reg .pred p;\nsetp.ne.b32 p, %98, 0;\n"
      "wgmma.mma_async.sync.aligned.m64n192k16.f32.bf16.bf16 "
      "{%0,%1,%2,%3,%4,%5,%6,%7,%8,%9,%10,%11,%12,%13,%14,%15,"
      "%16,%17,%18,%19,%20,%21,%22,%23,%24,%25,%26,%27,%28,%29,%30,%31,"
      "%32,%33,%34,%35,%36,%37,%38,%39,%40,%41,%42,%43,%44,%45,%46,%47,"
      "%48,%49,%50,%51,%52,%53,%54,%55,%56,%57,%58,%59,%60,%61,%62,%63,"
      "%64,%65,%66,%67,%68,%69,%70,%71,%72,%73,%74,%75,%76,%77,%78,%79,"
      "%80,%81,%82,%83,%84,%85,%86,%87,%88,%89,%90,%91,%92,%93,%94,%95}, "
      "%96, %97, p, 1, 1, 0, 0;\n}\n"
      : "=f"(d[OFF + 0]), "=f"(d[OFF + 1]), "=f"(d[OFF + 2]), "=f"(d[OFF + 3]), "=f"(d[OFF + 4]), "=f"(d[OFF + 5]),
        "=f"(d[OFF + 6]), "=f"(d[OFF + 7]), "=f"(d[OFF + 8]), "=f"(d[OFF + 9]), "=f"(d[OFF + 10]), "=f"(d[OFF + 11]),
        "=f"(d[OFF + 12]), "=f"(d[OFF + 13]), "=f"(d[OFF + 14]), "=f"(d[OFF + 15]), "=f"(d[OFF + 16]), "=f"(d[OFF + 17]),
        "=f"(d[OFF + 18]), "=f"(d[OFF + 19]), "=f"(d[OFF + 20]), "=f"(d[OFF + 21]), "=f"(d[OFF + 22]), "=f"(d[OFF + 23]),
        "=f"(d[OFF + 24]), "=f"(d[OFF + 25]), "=f"(d[OFF + 26]), "=f"(d[OFF + 27]), "=f"(d[OFF + 28]), "=f"(d[OFF + 29]),
        "=f"(d[OFF + 30]), "=f"(d[OFF + 31]), "=f"(d[OFF + 32]), "=f"(d[OFF + 33]), "=f"(d[OFF + 34]), "=f"(d[OFF + 35]),
        "=f"(d[OFF + 36]), "=f"(d[OFF + 37]), "=f"(d[OFF + 38]), "=f"(d[OFF + 39]), "=f"(d[OFF + 40]), "=f"(d[OFF + 41]),
        "=f"(d[OFF + 42]), "=f"(d[OFF + 43]), "=f"(d[OFF + 44]), "=f"(d[OFF + 45]), "=f"(d[OFF + 46]), "=f"(d[OFF + 47]),
        "=f"(d[OFF + 48]), "=f"(d[OFF + 49]), "=f"(d[OFF + 50]), "=f"(d[OFF + 51]), "=f"(d[OFF + 52]), "=f"(d[OFF + 53]),
        "=f"(d[OFF + 54]), "=f"(d[OFF + 55]), "=f"(d[OFF + 56]), "=f"(d[OFF + 57]), "=f"(d[OFF + 58]), "=f"(d[OFF + 59]),
        "=f"(d[OFF + 60]), "=f"(d[OFF + 61]), "=f"(d[OFF + 62]), "=f"(d[OFF + 63]), "=f"(d[OFF + 64]), "=f"(d[OFF + 65]),
        "=f"(d[OFF + 66]), "=f"(d[OFF + 67]), "=f"(d[OFF + 68]), "=f"(d[OFF + 69]), "=f"(d[OFF + 70]), "=f"(d[OFF + 71]),
        "=f"(d[OFF + 72]), "=f"(d[OFF + 73]), "=f"(d[OFF + 74]), "=f"(d[OFF + 75]), "=f"(d[OFF + 76]), "=f"(d[OFF + 77]),
        "=f"(d[OFF + 78]), "=f"(d[OFF + 79]), "=f"(d[OFF + 80]), "=f"(d[OFF + 81]), "=f"(d[OFF + 82]), "=f"(d[OFF + 83]),
        "=f"(d[OFF + 84]), "=f"(d[OFF + 85]), "=f"(d[OFF + 86]), "=f"(d[OFF + 87]), "=f"(d[OFF + 88]), "=f"(d[OFF + 89]),
        "=f"(d[OFF + 90]), "=f"(d[OFF + 91]), "=f"(d[OFF + 92]), "=f"(d[OFF + 93]), "=f"(d[OFF + 94]), "=f"(d[OFF + 95])
      : "l"(desc_a), "l"(desc_b), "r"(scale_d));
}

template <int OFF, int NN>
__device__ __forceinline__ void wg_m96t(float (&d)[NN], uint64_t desc_a, uint64_t desc_b, int scale_d) {
  asm volatile(
      "{\n.reg .pred p;\nsetp.ne.b32 p, %50, 0;\n"
      "wgmma.mma_async.sync.aligned.m64n96k16.f32.bf16.bf16 "
      "{%0,%1,%2,%3,%4,%5,%6,%7,%8,%9,%10,%11,%12,%13,%14,%15,"
      "%16,%17,%18,%19,%20,%21,%22,%23,%24,%25,%26,%27,%28,%29,%30,%31,"
      "%32,%33,%34,%35,%36,%37,%38,%39,%40,%41,%42,%43,%44,%45,%46,%47}, "
      "%48, %49, p, 1, 1, 0, 1;\n}\n"
      : "+f"(d[OFF + 0]), "+f"(d[OFF + 1]), "+f"(d[OFF + 2]), "+f"(d[OFF + 3]), "+f"(d[OFF + 4]), "+f"(d[OFF + 5]),
        "+f"(d[OFF + 6]), "+f"(d[OFF + 7]), "+f"(d[OFF + 8]), "+f"(d[OFF + 9]), "+f"(d[OFF + 10]), "+f"(d[OFF + 11]),
        "+f"(d[OFF + 12]), "+f"(d[OFF + 13]), "+f"(d[OFF + 14]), "+f"(d[OFF + 15]), "+f"(d[OFF + 16]), "+f"(d[OFF + 17]),
        "+f"(d[OFF + 18]), "+f"(d[OFF + 19]), "+f"(d[OFF + 20]), "+f"(d[OFF + 21]), "+f"(d[OFF + 22]), "+f"(d[OFF + 23]),
        "+f"(d[OFF + 24]), "+f"(d[OFF + 25]), "+f"(d[OFF + 26]), "+f"(d[OFF + 27]), "+f"(d[OFF + 28]), "+f"(d[OFF + 29]),
        "+f"(d[OFF + 30]), "+f"(d[OFF + 31]), "+f"(d[OFF + 32]), "+f"(d[OFF + 33]), "+f"(d[OFF + 34]), "+f"(d[OFF + 35]),
        "+f"(d[OFF + 36]), "+f"(d[OFF + 37]), "+f"(d[OFF + 38]), "+f"(d[OFF + 39]), "+f"(d[OFF + 40]), "+f"(d[OFF + 41]),
        "+f"(d[OFF + 42]), "+f"(d[OFF + 43]), "+f"(d[OFF + 44]), "+f"(d[OFF + 45]), "+f"(d[OFF + 46]), "+f"(d[OFF + 47])
      : "l"(desc_a), "l"(desc_b), "r"(scale_d));
}

template <int OFF, int NN>
__device__ __forceinline__ void wg_m96tz(float (&d)[NN], uint64_t desc_a, uint64_t desc_b, int scale_d) {
  asm volatile(
      "{\n.reg .pred p;\nsetp.ne.b32 p, %50, 0;\n"
      "wgmma.mma_async.sync.aligned.m64n96k16.f32.bf16.bf16 "
      "{%0,%1,%2,%3,%4,%5,%6,%7,%8,%9,%10,%11,%12,%13,%14,%15,"
      "%16,%17,%18,%19,%20,%21,%22,%23,%24,%25,%26,%27,%28,%29,%30,%31,"
      "%32,%33,%34,%35,%36,%37,%38,%39,%40,%41,%42,%43,%44,%45,%46,%47}, "
      "%48, %49, p, 1, 1, 0, 1;\n}\n"
      : "=f"(d[OFF + 0]), "=f"(d[OFF + 1]), "=f"(d[OFF + 2]), "=f"(d[OFF + 3]), "=f"(d[OFF + 4]), "=f"(d[OFF + 5]),
        "=f"(d[OFF + 6]), "=f"(d[OFF + 7]), "=f"(d[OFF + 8]), "=f"(d[OFF + 9]), "=f"(d[OFF + 10]), "=f"(d[OFF + 11]),
        "=f"(d[OFF + 12]), "=f"(d[OFF + 13]), "=f"(d[OFF + 14]), "=f"(d[OFF + 15]), "=f"(d[OFF + 16]), "=f"(d[OFF + 17]),
        "=f"(d[OFF + 18]), "=f"(d[OFF + 19]), "=f"(d[OFF + 20]), "=f"(d[OFF + 21]), "=f"(d[OFF + 22]), "=f"(d[OFF + 23]),
        "=f"(d[OFF + 24]), "=f"(d[OFF + 25]), "=f"(d[OFF + 26]), "=f"(d[OFF + 27]), "=f"(d[OFF + 28]), "=f"(d[OFF + 29]),
        "=f"(d[OFF + 30]), "=f"(d[OFF + 31]), "=f"(d[OFF + 32]), "=f"(d[OFF + 33]), "=f"(d[OFF + 34]), "=f"(d[OFF + 35]),
        "=f"(d[OFF + 36]), "=f"(d[OFF + 37]), "=f"(d[OFF + 38]), "=f"(d[OFF + 39]), "=f"(d[OFF + 40]), "=f"(d[OFF + 41]),
        "=f"(d[OFF + 42]), "=f"(d[OFF + 43]), "=f"(d[OFF + 44]), "=f"(d[OFF + 45]), "=f"(d[OFF + 46]), "=f"(d[OFF + 47])
      : "l"(desc_a), "l"(desc_b), "r"(scale_d));
}

template <int OFF, int NN>
__device__ __forceinline__ void wg_d96(float (&d)[NN], uint32_t a0, uint32_t a1, uint32_t a2, uint32_t a3,
                                       uint64_t desc_b, int scale_d) {
  asm volatile(
      "{\n.reg .pred p;\nsetp.ne.b32 p, %53, 0;\n"
      "wgmma.mma_async.sync.aligned.m64n96k16.f32.bf16.bf16 "
      "{%0,%1,%2,%3,%4,%5,%6,%7,%8,%9,%10,%11,%12,%13,%14,%15,"
      "%16,%17,%18,%19,%20,%21,%22,%23,%24,%25,%26,%27,%28,%29,%30,%31,"
      "%32,%33,%34,%35,%36,%37,%38,%39,%40,%41,%42,%43,%44,%45,%46,%47}, "
      "{%48,%49,%50,%51}, %52, p, 1, 1, 0;\n}\n"
      : "+f"(d[OFF + 0]), "+f"(d[OFF + 1]), "+f"(d[OFF + 2]), "+f"(d[OFF + 3]), "+f"(d[OFF + 4]), "+f"(d[OFF + 5]),
        "+f"(d[OFF + 6]), "+f"(d[OFF + 7]), "+f"(d[OFF + 8]), "+f"(d[OFF + 9]), "+f"(d[OFF + 10]), "+f"(d[OFF + 11]),
        "+f"(d[OFF + 12]), "+f"(d[OFF + 13]), "+f"(d[OFF + 14]), "+f"(d[OFF + 15]), "+f"(d[OFF + 16]), "+f"(d[OFF + 17]),
        "+f"(d[OFF + 18]), "+f"(d[OFF + 19]), "+f"(d[OFF + 20]), "+f"(d[OFF + 21]), "+f"(d[OFF + 22]), "+f"(d[OFF + 23]),
        "+f"(d[OFF + 24]), "+f"(d[OFF + 25]), "+f"(d[OFF + 26]), "+f"(d[OFF + 27]), "+f"(d[OFF + 28]), "+f"(d[OFF + 29]),
        "+f"(d[OFF + 30]), "+f"(d[OFF + 31]), "+f"(d[OFF + 32]), "+f"(d[OFF + 33]), "+f"(d[OFF + 34]), "+f"(d[OFF + 35]),
        "+f"(d[OFF + 36]), "+f"(d[OFF + 37]), "+f"(d[OFF + 38]), "+f"(d[OFF + 39]), "+f"(d[OFF + 40]), "+f"(d[OFF + 41]),
        "+f"(d[OFF + 42]), "+f"(d[OFF + 43]), "+f"(d[OFF + 44]), "+f"(d[OFF + 45]), "+f"(d[OFF + 46]), "+f"(d[OFF + 47])
      : "r"(a0), "r"(a1), "r"(a2), "r"(a3), "l"(desc_b), "r"(scale_d));
}

template <int OFF, int NN>
__device__ __forceinline__ void wg_d96z(float (&d)[NN], uint32_t a0, uint32_t a1, uint32_t a2, uint32_t a3,
                                       uint64_t desc_b, int scale_d) {
  asm volatile(
      "{\n.reg .pred p;\nsetp.ne.b32 p, %53, 0;\n"
      "wgmma.mma_async.sync.aligned.m64n96k16.f32.bf16.bf16 "
      "{%0,%1,%2,%3,%4,%5,%6,%7,%8,%9,%10,%11,%12,%13,%14,%15,"
      "%16,%17,%18,%19,%20,%21,%22,%23,%24,%25,%26,%27,%28,%29,%30,%31,"
      "%32,%33,%34,%35,%36,%37,%38,%39,%40,%41,%42,%43,%44,%45,%46,%47}, "
      "{%48,%49,%50,%51}, %52, p, 1, 1, 0;\n}\n"
      : "=f"(d[OFF + 0]), "=f"(d[OFF + 1]), "=f"(d[OFF + 2]), "=f"(d[OFF + 3]), "=f"(d[OFF + 4]), "=f"(d[OFF + 5]),
        "=f"(d[OFF + 6]), "=f"(d[OFF + 7]), "=f"(d[OFF + 8]), "=f"(d[OFF + 9]), "=f"(d[OFF + 10]), "=f"(d[OFF + 11]),
        "=f"(d[OFF + 12]), "=f"(d[OFF + 13]), "=f"(d[OFF + 14]), "=f"(d[OFF + 15]), "=f"(d[OFF + 16]), "=f"(d[OFF + 17]),
        "=f"(d[OFF + 18]), "=f"(d[OFF + 19]), "=f"(d[OFF + 20]), "=f"(d[OFF + 21]), "=f"(d[OFF + 22]), "=f"(d[OFF + 23]),
        "=f"(d[OFF + 24]), "=f"(d[OFF + 25]), "=f"(d[OFF + 26]), "=f"(d[OFF + 27]), "=f"(d[OFF + 28]), "=f"(d[OFF + 29]),
        "=f"(d[OFF + 30]), "=f"(d[OFF + 31]), "=f"(d[OFF + 32]), "=f"(d[OFF + 33]), "=f"(d[OFF + 34]), "=f"(d[OFF + 35]),
        "=f"(d[OFF + 36]), "=f"(d[OFF + 37]), "=f"(d[OFF + 38]), "=f"(d[OFF + 39]), "=f"(d[OFF + 40]), "=f"(d[OFF + 41]),
        "=f"(d[OFF + 42]), "=f"(d[OFF + 43]), "=f"(d[OFF + 44]), "=f"(d[OFF + 45]), "=f"(d[OFF + 46]), "=f"(d[OFF + 47])
      : "r"(a0), "r"(a1), "r"(a2), "r"(a3), "l"(desc_b), "r"(scale_d));
}

template <int OFF, int NN>
__device__ __forceinline__ void wg_s104(float (&d)[NN], uint32_t a0, uint32_t a1, uint32_t a2, uint32_t a3,
                                       uint64_t desc_b, int scale_d, uint32_t meta) {
  asm volatile(
      "{\n.reg .pred p;\nsetp.ne.b32 p, %57, 0;\n"
      "wgmma.mma_async.sp.sync.aligned.m64n104k32.f32.bf16.bf16 "
      "{%0,%1,%2,%3,%4,%5,%6,%7,%8,%9,%10,%11,%12,%13,%14,%15,"
      "%16,%17,%18,%19,%20,%21,%22,%23,%24,%25,%26,%27,%28,%29,%30,%31,"
      "%32,%33,%34,%35,%36,%37,%38,%39,%40,%41,%42,%43,%44,%45,%46,%47,"
      "%48,%49,%50,%51}, "
      "{%52,%53,%54,%55}, %56, %58, 0, p, 1, 1, 0;\n}\n"
      : "+f"(d[OFF + 0]), "+f"(d[OFF + 1]), "+f"(d[OFF + 2]), "+f"(d[OFF + 3]), "+f"(d[OFF + 4]), "+f"(d[OFF + 5]),
        "+f"(d[OFF + 6]), "+f"(d[OFF + 7]), "+f"(d[OFF + 8]), "+f"(d[OFF + 9]), "+f"(d[OFF + 10]), "+f"(d[OFF + 11]),
        "+f"(d[OFF + 12]), "+f"(d[OFF + 13]), "+f"(d[OFF + 14]), "+f"(d[OFF + 15]), "+f"(d[OFF + 16]), "+f"(d[OFF + 17]),
        "+f"(d[OFF + 18]), "+f"(d[OFF + 19]), "+f"(d[OFF + 20]), "+f"(d[OFF + 21]), "+f"(d[OFF + 22]), "+f"(d[OFF + 23]),
        "+f"(d[OFF + 24]), "+f"(d[OFF + 25]), "+f"(d[OFF + 26]), "+f"(d[OFF + 27]), "+f"(d[OFF + 28]), "+f"(d[OFF + 29]),
        "+f"(d[OFF + 30]), "+f"(d[OFF + 31]), "+f"(d[OFF + 32]), "+f"(d[OFF + 33]), "+f"(d[OFF + 34]), "+f"(d[OFF + 35]),
        "+f"(d[OFF + 36]), "+f"(d[OFF + 37]), "+f"(d[OFF + 38]), "+f"(d[OFF + 39]), "+f"(d[OFF + 40]), "+f"(d[OFF + 41]),
        "+f"(d[OFF + 42]), "+f"(d[OFF + 43]), "+f"(d[OFF + 44]), "+f"(d[OFF + 45]), "+f"(d[OFF + 46]), "+f"(d[OFF + 47]),
        "+f"(d[OFF + 48]), "+f"(d[OFF + 49]), "+f"(d[OFF + 50]), "+f"(d[OFF + 51])
      : "r"(a0), "r"(a1), "r"(a2), "r"(a3), "l"(desc_b), "r"(scale_d), "r"(meta));
}

template <int OFF, int NN>
__device__ __forceinline__ void wg_s104z(float (&d)[NN], uint32_t a0, uint32_t a1, uint32_t a2, uint32_t a3,
                                       uint64_t desc_b, int scale_d, uint32_t meta) {
  asm volatile(
      "{\n.reg .pred p;\nsetp.ne.b32 p, %57, 0;\n"
      "wgmma.mma_async.sp.sync.aligned.m64n104k32.f32.bf16.bf16 "
      "{%0,%1,%2,%3,%4,%5,%6,%7,%8,%9,%10,%11,%12,%13,%14,%15,"
      "%16,%17,%18,%19,%20,%21,%22,%23,%24,%25,%26,%27,%28,%29,%30,%31,"
      "%32,%33,%34,%35,%36,%37,%38,%39,%40,%41,%42,%43,%44,%45,%46,%47,"
      "%48,%49,%50,%51}, "
      "{%52,%53,%54,%55}, %56, %58, 0, p, 1, 1, 0;\n}\n"
      : "=f"(d[OFF + 0]), "=f"(d[OFF + 1]), "=f"(d[OFF + 2]), "=f"(d[OFF + 3]), "=f"(d[OFF + 4]), "=f"(d[OFF + 5]),
        "=f"(d[OFF + 6]), "=f"(d[OFF + 7]), "=f"(d[OFF + 8]), "=f"(d[OFF + 9]), "=f"(d[OFF + 10]), "=f"(d[OFF + 11]),
        "=f"(d[OFF + 12]), "=f"(d[OFF + 13]), "=f"(d[OFF + 14]), "=f"(d[OFF + 15]), "=f"(d[OFF + 16]), "=f"(d[OFF + 17]),
        "=f"(d[OFF + 18]), "=f"(d[OFF + 19]), "=f"(d[OFF + 20]), "=f"(d[OFF + 21]), "=f"(d[OFF + 22]), "=f"(d[OFF + 23]),
        "=f"(d[OFF + 24]), "=f"(d[OFF + 25]), "=f"(d[OFF + 26]), "=f"(d[OFF + 27]), "=f"(d[OFF + 28]), "=f"(d[OFF + 29]),
        "=f"(d[OFF + 30]), "=f"(d[OFF + 31]), "=f"(d[OFF + 32]), "=f"(d[OFF + 33]), "=f"(d[OFF + 34]), "=f"(d[OFF + 35]),
        "=f"(d[OFF + 36]), "=f"(d[OFF + 37]), "=f"(d[OFF + 38]), "=f"(d[OFF + 39]), "=f"(d[OFF + 40]), "=f"(d[OFF + 41]),
        "=f"(d[OFF + 42]), "=f"(d[OFF + 43]), "=f"(d[OFF + 44]), "=f"(d[OFF + 45]), "=f"(d[OFF + 46]), "=f"(d[OFF + 47]),
        "=f"(d[OFF + 48]), "=f"(d[OFF + 49]), "=f"(d[OFF + 50]), "=f"(d[OFF + 51])
      : "r"(a0), "r"(a1), "r"(a2), "r"(a3), "l"(desc_b), "r"(scale_d), "r"(meta));
}

template <int OFF, int NN>
__device__ __forceinline__ void wg_s48(float (&d)[NN], uint32_t a0, uint32_t a1, uint32_t a2, uint32_t a3,
                                       uint64_t desc_b, int scale_d, uint32_t meta) {
  asm volatile(
      "{\n.reg .pred p;\nsetp.ne.b32 p, %29, 0;\n"
      "wgmma.mma_async.sp.sync.aligned.m64n48k32.f32.bf16.bf16 "
      "{%0,%1,%2,%3,%4,%5,%6,%7,%8,%9,%10,%11,%12,%13,%14,%15,"
      "%16,%17,%18,%19,%20,%21,%22,%23}, "
      "{%24,%25,%26,%27}, %28, %30, 0, p, 1, 1, 0;\n}\n"
      : "+f"(d[OFF + 0]), "+f"(d[OFF + 1]), "+f"(d[OFF + 2]), "+f"(d[OFF + 3]), "+f"(d[OFF + 4]), "+f"(d[OFF + 5]),
        "+f"(d[OFF + 6]), "+f"(d[OFF + 7]), "+f"(d[OFF + 8]), "+f"(d[OFF + 9]), "+f"(d[OFF + 10]), "+f"(d[OFF + 11]),
        "+f"(d[OFF + 12]), "+f"(d[OFF + 13]), "+f"(d[OFF + 14]), "+f"(d[OFF + 15]), "+f"(d[OFF + 16]), "+f"(d[OFF + 17]),
        "+f"(d[OFF + 18]), "+f"(d[OFF + 19]), "+f"(d[OFF + 20]), "+f"(d[OFF + 21]), "+f"(d[OFF + 22]), "+f"(d[OFF + 23])
      : "r"(a0), "r"(a1), "r"(a2), "r"(a3), "l"(desc_b), "r"(scale_d), "r"(meta));
}

template <int OFF, int NN>
__device__ __forceinline__ void wg_s48z(float (&d)[NN], uint32_t a0, uint32_t a1, uint32_t a2, uint32_t a3,
                                       uint64_t desc_b, int scale_d, uint32_t meta) {
  asm volatile(
      "{\n.reg .pred p;\nsetp.ne.b32 p, %29, 0;\n"
      "wgmma.mma_async.sp.sync.aligned.m64n48k32.f32.bf16.bf16 "
      "{%0,%1,%2,%3,%4,%5,%6,%7,%8,%9,%10,%11,%12,%13,%14,%15,"
      "%16,%17,%18,%19,%20,%21,%22,%23}, "
      "{%24,%25,%26,%27}, %28, %30, 0, p, 1, 1, 0;\n}\n"
      : "=f"(d[OFF + 0]), "=f"(d[OFF + 1]), "=f"(d[OFF + 2]), "=f"(d[OFF + 3]), "=f"(d[OFF + 4]), "=f"(d[OFF + 5]),
        "=f"(d[OFF + 6]), "=f"(d[OFF + 7]), "=f"(d[OFF + 8]), "=f"(d[OFF + 9]), "=f"(d[OFF + 10]), "=f"(d[OFF + 11]),
        "=f"(d[OFF + 12]), "=f"(d[OFF + 13]), "=f"(d[OFF + 14]), "=f"(d[OFF + 15]), "=f"(d[OFF + 16]), "=f"(d[OFF + 17]),
        "=f"(d[OFF + 18]), "=f"(d[OFF + 19]), "=f"(d[OFF + 20]), "=f"(d[OFF + 21]), "=f"(d[OFF + 22]), "=f"(d[OFF + 23])
      : "r"(a0), "r"(a1), "r"(a2), "r"(a3), "l"(desc_b), "r"(scale_d), "r"(meta));
}

template <int OFF, int NN>
__device__ __forceinline__ void wg_s56(float (&d)[NN], uint32_t a0, uint32_t a1, uint32_t a2, uint32_t a3,
                                       uint64_t desc_b, int scale_d, uint32_t meta) {
  asm volatile(
      "{\n.reg .pred p;\nsetp.ne.b32 p, %33, 0;\n"
      "wgmma.mma_async.sp.sync.aligned.m64n56k32.f32.bf16.bf16 "
      "{%0,%1,%2,%3,%4,%5,%6,%7,%8,%9,%10,%11,%12,%13,%14,%15,"
      "%16,%17,%18,%19,%20,%21,%22,%23,%24,%25,%26,%27}, "
      "{%28,%29,%30,%31}, %32, %34, 0, p, 1, 1, 0;\n}\n"
      : "+f"(d[OFF + 0]), "+f"(d[OFF + 1]), "+f"(d[OFF + 2]), "+f"(d[OFF + 3]), "+f"(d[OFF + 4]), "+f"(d[OFF + 5]),
        "+f"(d[OFF + 6]), "+f"(d[OFF + 7]), "+f"(d[OFF + 8]), "+f"(d[OFF + 9]), "+f"(d[OFF + 10]), "+f"(d[OFF + 11]),
        "+f"(d[OFF + 12]), "+f"(d[OFF + 13]), "+f"(d[OFF + 14]), "+f"(d[OFF + 15]), "+f"(d[OFF + 16]), "+f"(d[OFF + 17]),
        "+f"(d[OFF + 18]), "+f"(d[OFF + 19]), "+f"(d[OFF + 20]), "+f"(d[OFF + 21]), "+f"(d[OFF + 22]), "+f"(d[OFF + 23]),
        "+f"(d[OFF + 24]), "+f"(d[OFF + 25]), "+f"(d[OFF + 26]), "+f"(d[OFF + 27])
      : "r"(a0), "r"(a1), "r"(a2), "r"(a3), "l"(desc_b), "r"(scale_d), "r"(meta));
}

template <int OFF, int NN>
__device__ __forceinline__ void wg_s56z(float (&d)[NN], uint32_t a0, uint32_t a1, uint32_t a2, uint32_t a3,
                                       uint64_t desc_b, int scale_d, uint32_t meta) {
  asm volatile(
      "{\n.reg .pred p;\nsetp.ne.b32 p, %33, 0;\n"
      "wgmma.mma_async.sp.sync.aligned.m64n56k32.f32.bf16.bf16 "
      "{%0,%1,%2,%3,%4,%5,%6,%7,%8,%9,%10,%11,%12,%13,%14,%15,"
      "%16,%17,%18,%19,%20,%21,%22,%23,%24,%25,%26,%27}, "
      "{%28,%29,%30,%31}, %32, %34, 0, p, 1, 1, 0;\n}\n"
      : "=f"(d[OFF + 0]), "=f"(d[OFF + 1]), "=f"(d[OFF + 2]), "=f"(d[OFF + 3]), "=f"(d[OFF + 4]), "=f"(d[OFF + 5]),
        "=f"(d[OFF + 6]), "=f"(d[OFF + 7]), "=f"(d[OFF + 8]), "=f"(d[OFF + 9]), "=f"(d[OFF + 10]), "=f"(d[OFF + 11]),
        "=f"(d[OFF + 12]), "=f"(d[OFF + 13]), "=f"(d[OFF + 14]), "=f"(d[OFF + 15]), "=f"(d[OFF + 16]), "=f"(d[OFF + 17]),
        "=f"(d[OFF + 18]), "=f"(d[OFF + 19]), "=f"(d[OFF + 20]), "=f"(d[OFF + 21]), "=f"(d[OFF + 22]), "=f"(d[OFF + 23]),
        "=f"(d[OFF + 24]), "=f"(d[OFF + 25]), "=f"(d[OFF + 26]), "=f"(d[OFF + 27])
      : "r"(a0), "r"(a1), "r"(a2), "r"(a3), "l"(desc_b), "r"(scale_d), "r"(meta));
}

template <int OFF, int NN>
__device__ __forceinline__ void wg_s64t(float (&d)[NN], uint32_t a0, uint32_t a1, uint32_t a2, uint32_t a3,
                                       uint64_t desc_b, int scale_d, uint32_t meta) {
  asm volatile(
      "{\n.reg .pred p;\nsetp.ne.b32 p, %37, 0;\n"
      "wgmma.mma_async.sp.sync.aligned.m64n64k32.f32.bf16.bf16 "
      "{%0,%1,%2,%3,%4,%5,%6,%7,%8,%9,%10,%11,%12,%13,%14,%15,"
      "%16,%17,%18,%19,%20,%21,%22,%23,%24,%25,%26,%27,%28,%29,%30,%31}, "
      "{%32,%33,%34,%35}, %36, %38, 0, p, 1, 1, 1;\n}\n"
      : "+f"(d[OFF + 0]), "+f"(d[OFF + 1]), "+f"(d[OFF + 2]), "+f"(d[OFF + 3]), "+f"(d[OFF + 4]), "+f"(d[OFF + 5]),
        "+f"(d[OFF + 6]), "+f"(d[OFF + 7]), "+f"(d[OFF + 8]), "+f"(d[OFF + 9]), "+f"(d[OFF + 10]), "+f"(d[OFF + 11]),
        "+f"(d[OFF + 12]), "+f"(d[OFF + 13]), "+f"(d[OFF + 14]), "+f"(d[OFF + 15]), "+f"(d[OFF + 16]), "+f"(d[OFF + 17]),
        "+f"(d[OFF + 18]), "+f"(d[OFF + 19]), "+f"(d[OFF + 20]), "+f"(d[OFF + 21]), "+f"(d[OFF + 22]), "+f"(d[OFF + 23]),
        "+f"(d[OFF + 24]), "+f"(d[OFF + 25]), "+f"(d[OFF + 26]), "+f"(d[OFF + 27]), "+f"(d[OFF + 28]), "+f"(d[OFF + 29]),
        "+f"(d[OFF + 30]), "+f"(d[OFF + 31])
      : "r"(a0), "r"(a1), "r"(a2), "r"(a3), "l"(desc_b), "r"(scale_d), "r"(meta));
}

template <int OFF, int NN>
__device__ __forceinline__ void wg_s64t1(float (&d)[NN], uint32_t a0, uint32_t a1, uint32_t a2, uint32_t a3,
                                       uint64_t desc_b, int scale_d, uint32_t meta) {
  asm volatile(
      "{\n.reg .pred p;\nsetp.ne.b32 p, %37, 0;\n"
      "wgmma.mma_async.sp.sync.aligned.m64n64k32.f32.bf16.bf16 "
      "{%0,%1,%2,%3,%4,%5,%6,%7,%8,%9,%10,%11,%12,%13,%14,%15,"
      "%16,%17,%18,%19,%20,%21,%22,%23,%24,%25,%26,%27,%28,%29,%30,%31}, "
      "{%32,%33,%34,%35}, %36, %38, 1, p, 1, 1, 1;\n}\n"
      : "+f"(d[OFF + 0]), "+f"(d[OFF + 1]), "+f"(d[OFF + 2]), "+f"(d[OFF + 3]), "+f"(d[OFF + 4]), "+f"(d[OFF + 5]),
        "+f"(d[OFF + 6]), "+f"(d[OFF + 7]), "+f"(d[OFF + 8]), "+f"(d[OFF + 9]), "+f"(d[OFF + 10]), "+f"(d[OFF + 11]),
        "+f"(d[OFF + 12]), "+f"(d[OFF + 13]), "+f"(d[OFF + 14]), "+f"(d[OFF + 15]), "+f"(d[OFF + 16]), "+f"(d[OFF + 17]),
        "+f"(d[OFF + 18]), "+f"(d[OFF + 19]), "+f"(d[OFF + 20]), "+f"(d[OFF + 21]), "+f"(d[OFF + 22]), "+f"(d[OFF + 23]),
        "+f"(d[OFF + 24]), "+f"(d[OFF + 25]), "+f"(d[OFF + 26]), "+f"(d[OFF + 27]), "+f"(d[OFF + 28]), "+f"(d[OFF + 29]),
        "+f"(d[OFF + 30]), "+f"(d[OFF + 31])
      : "r"(a0), "r"(a1), "r"(a2), "r"(a3), "l"(desc_b), "r"(scale_d), "r"(meta));
}

template <int OFF, int NN>
__device__ __forceinline__ void wg_s64tz(float (&d)[NN], uint32_t a0, uint32_t a1, uint32_t a2, uint32_t a3,
                                       uint64_t desc_b, int scale_d, uint32_t meta) {
  asm volatile(
      "{\n.reg .pred p;\nsetp.ne.b32 p, %37, 0;\n"
      "wgmma.mma_async.sp.sync.aligned.m64n64k32.f32.bf16.bf16 "
      "{%0,%1,%2,%3,%4,%5,%6,%7,%8,%9,%10,%11,%12,%13,%14,%15,"
      "%16,%17,%18,%19,%20,%21,%22,%23,%24,%25,%26,%27,%28,%29,%30,%31}, "
      "{%32,%33,%34,%35}, %36, %38, 0, p, 1, 1, 1;\n}\n"
      : "=f"(d[OFF + 0]), "=f"(d[OFF + 1]), "=f"(d[OFF + 2]), "=f"(d[OFF + 3]), "=f"(d[OFF + 4]), "=f"(d[OFF + 5]),
        "=f"(d[OFF + 6]), "=f"(d[OFF + 7]), "=f"(d[OFF + 8]), "=f"(d[OFF + 9]), "=f"(d[OFF + 10]), "=f"(d[OFF + 11]),
        "=f"(d[OFF + 12]), "=f"(d[OFF + 13]), "=f"(d[OFF + 14]), "=f"(d[OFF + 15]), "=f"(d[OFF + 16]), "=f"(d[OFF + 17]),
        "=f"(d[OFF + 18]), "=f"(d[OFF + 19]), "=f"(d[OFF + 20]), "=f"(d[OFF + 21]), "=f"(d[OFF + 22]), "=f"(d[OFF + 23]),
        "=f"(d[OFF + 24]), "=f"(d[OFF + 25]), "=f"(d[OFF + 26]), "=f"(d[OFF + 27]), "=f"(d[OFF + 28]), "=f"(d[OFF + 29]),
        "=f"(d[OFF + 30]), "=f"(d[OFF + 31])
      : "r"(a0), "r"(a1), "r"(a2), "r"(a3), "l"(desc_b), "r"(scale_d), "r"(meta));
}

__device__ __forceinline__ int g2_inv(int ch) { return 32 * (ch >> 5) + 8 * ((ch >> 1) & 3) + 2 * ((ch >> 3) & 3) + (ch & 1); }
__host__ __device__ __forceinline__ uint32_t wimg_off(int n, int k) {
  return (uint32_t)(k >> 6) * kWChunk + (uint32_t)n * 128 + (uint32_t)((((k & 63) >> 3) ^ (n & 7)) << 4) + (k & 7) * 2;
}
__host__ __device__ constexpr int w2piece(int h, int c) { return c == 2 ? 2 + h : 4 * h + c; }
__device__ __forceinline__ uint32_t w2img_off(int n, int k) { return wimg_off(n % 96, k & 63) + w2piece(n >= 96, k >> 6) * (kWChunk / 2); }
__device__ __forceinline__ int qpix(int par, int t) {
  const int a = 2 * t + 13 * par - 6, b = t + 112 * par;
  return par ? min(a, b) : max(a, b);
}
__device__ __forceinline__ int woff(int par, int i, int r) {
  const int a = 99 * par + 6 - 8 * i;
  return par ? min(r, a) : max(r, a);
}

__device__ __forceinline__ void mma16816(float (&c)[4], uint32_t a0, uint32_t a1, uint32_t a2, uint32_t a3, uint32_t b0,
                                         uint32_t b1) {
  asm volatile(
      "mma.sync.aligned.m16n8k16.row.col.f32.bf16.bf16.f32 {%0,%1,%2,%3}, {%4,%5,%6,%7}, {%8,%9}, {%0,%1,%2,%3};"
      : "+f"(c[0]), "+f"(c[1]), "+f"(c[2]), "+f"(c[3])
      : "r"(a0), "r"(a1), "r"(a2), "r"(a3), "r"(b0), "r"(b1));
}

__device__ __forceinline__ void fold_w1(const uint32_t u, const __nv_bfloat16* __restrict__ wqkv, uint8_t* wimg) {
  const uint32_t g = (threadIdx.x >> 2) & 7, l = threadIdx.x & 3;
  const uint32_t m0 = (u * 171 >> 11) * 16, s = u - (u * 171 >> 11) * 12;
  uint4 A[12], B[12];
  const __nv_bfloat16* arow = wqkv + (m0 + 4 * (g >> 1) + (g & 1)) * 576 + 192 + 8 * l;
  const __nv_bfloat16* brow = wqkv + (16 * s + 4 * (g >> 1) + (g & 1)) * 576 + 8 * l;
#pragma unroll
  for (int i = 0; i < 12; i++) {
    A[i] = ldg128_nc(arow + (i & 1) * 2 * 576 + 32 * (i >> 1));
    B[i] = ldg128_nc(brow + (i & 1) * 2 * 576 + 32 * (i >> 1));
  }
  sched_fence();
  uint8_t* dst = wimg + wimg_off(m0 + g, 16 * s + 4 * l);
  float acc[4][4];
#pragma unroll
  for (int j = 0; j < 16; j++) acc[j >> 2][j & 3] = 0.f;
#pragma unroll
  for (int i = 0; i < 6; i++) {
    const uint4 &a0 = A[2 * i], &a1 = A[2 * i + 1];
#pragma unroll
    for (int nb = 0; nb < 2; nb++) mma16816(acc[2 * nb], a0.x, a1.x, a0.y, a1.y, B[2 * i + nb].x, B[2 * i + nb].y);
#pragma unroll
    for (int nb = 0; nb < 2; nb++) mma16816(acc[2 * nb + 1], a0.z, a1.z, a0.w, a1.w, B[2 * i + nb].z, B[2 * i + nb].w);
  }
#pragma unroll
  for (int j = 0; j < 2; j++) {
    const uint2 v = make_uint2(pack_bf16((acc[0][2 * j] + acc[1][2 * j]) * kAlpha, (acc[0][2 * j + 1] + acc[1][2 * j + 1]) * kAlpha),
                               pack_bf16((acc[2][2 * j] + acc[3][2 * j]) * kAlpha, (acc[2][2 * j + 1] + acc[3][2 * j + 1]) * kAlpha));
    asm volatile("st.relaxed.gpu.global.v2.u32 [%0], {%1,%2};" ::"l"(dst + j * 1024), "r"(v.x), "r"(v.y) : "memory");
  }
}
__device__ __forceinline__ void fold_w2(const int u, const __nv_bfloat16* __restrict__ wqkv, const __nv_bfloat16* __restrict__ wo,
                                        uint8_t* wimg) {
  const int g = (threadIdx.x >> 2) & 7, l = threadIdx.x & 3;
  const int m0 = (u / 12) * 32, n0 = (u % 12) * 16;
  uint4 S[12];
  uint32_t L[96];
  const __nv_bfloat16* brow = wqkv + (n0 + 4 * (g >> 1) + (g & 1)) * 576 + 384 + 8 * l;
#pragma unroll
  for (int i = 0; i < 12; i++) S[i] = ldg128_nc(brow + (i & 1) * 2 * 576 + 32 * (i >> 1));
  const __nv_bfloat16* acol = wo + (8 * l) * 192 + m0 + 4 * g;
#pragma unroll
  for (int c = 0; c < 48; c++)
    asm volatile("ld.global.nc.v2.u32 {%0,%1}, [%2];" : "=r"(L[2 * c]), "=r"(L[2 * c + 1]) : "l"(acol + (32 * (c >> 3) + (c & 7)) * 192));
  const uint32_t off = w2_offset();
  sched_fence();
  uint8_t* img = wimg + off;
  float acc[4][4];
#pragma unroll
  for (int j = 0; j < 16; j++) acc[j >> 2][j & 3] = 0.f;
#pragma unroll
  for (int i = 0; i < 6; i++) {
#pragma unroll
    for (int h = 0; h < 2; h++) {
      const uint4 &s0 = S[2 * i], &s1 = S[2 * i + 1];
#pragma unroll
      for (int mt = 0; mt < 2; mt++) {
        const uint32_t* a = L + 16 * i + 8 * h + mt;
        const uint32_t a0 = __byte_perm(a[0], a[2], 0x5410), a1 = __byte_perm(a[0], a[2], 0x7632);
        const uint32_t a2 = __byte_perm(a[4], a[6], 0x5410), a3 = __byte_perm(a[4], a[6], 0x7632);
        mma16816(acc[2 * mt], a0, a1, a2, a3, h ? s0.z : s0.x, h ? s0.w : s0.y);
        mma16816(acc[2 * mt + 1], a0, a1, a2, a3, h ? s1.z : s1.x, h ? s1.w : s1.y);
      }
    }
  }
#pragma unroll
  for (int j = 0; j < 4; j++) {
    const float(&c0)[4] = acc[j & 2];
    const float(&c1)[4] = acc[(j & 2) + 1];
    asm volatile("st.relaxed.gpu.global.v2.u32 [%0], {%1,%2};" ::"l"(img + w2img_off(g2_inv(m0 + 4 * g + j), n0 + 4 * l)),
                 "r"(pack_bf16(c0[2 * (j & 1)], c0[2 * (j & 1) + 1])), "r"(pack_bf16(c1[2 * (j & 1)], c1[2 * (j & 1) + 1])) : "memory");
  }
}

__global__ void __launch_bounds__(256) fold_kernel(const __nv_bfloat16* __restrict__ wqkv,
                                                   const __nv_bfloat16* __restrict__ wo, uint8_t* wimg) {
  const int u = blockIdx.x * 8 + (threadIdx.x >> 5);
  if (u < 144) fold_w1(u, wqkv, wimg);
  else fold_w2(u - 144, wqkv, wo, wimg);
}

struct TileCoord { int pr, pc, I, J, up, kind; };
struct TileTable { uint16_t e[kCtas * 6], g[5][8][2], b[5][2][4]; };
inline void make_tiles(TileTable& tt) {
  for (int tile = 0; tile < kCtas * 6; tile++) {
    const int b = tile / 6, k = tile - 6 * b;
    const int p = b < 128 ? (tile - 672) >> 1 : b - 80;
    const int strip = b < 112 ? b >> 1 : b >= 128 && k >= 2 ? (b & 1) * 27 + (b & 2) * 14 : p + (p < 26 ? 1 : 3);
    const int pr = strip >= 28, J = (strip - pr * 28) >> 1, pc = strip & 1, up = b < 112 ? b & 1 : pr;
    const int first = b < 112 ? 8 - 2 * pr - up : 13 * pr, step = b < 112 ? k : k & 1;
    const int I = up ? first - step : first + step;
    const int kind = I == 13 * pr ? 3 + pr : J == 13 * pc ? 1 + pc : 0;
    tt.e[tile] = (uint16_t)(I | J << 4 | pr << 8 | pc << 9 | up << 10 | kind << 11);
  }
  for (int kind = 0; kind < 5; kind++) {
    const bool col = kind == 1 || kind == 2;
    auto off = [kind](int t) { return kind == 0 ? 2 * t : kind & 1 ? t + (t == 7) : t + (t > 0); };
    for (int j = 0; j < 8; j++) {
      const int w = j >> 1, h = j & 1;
      tt.g[kind][j][0] = (uint16_t)(col ? 3 * off(w + 4 * h) : 3 * (kW * off(2 * w) + 8 * h));
      tt.g[kind][j][1] = (uint16_t)(128 * (col ? 5 : 5 + off(2 * w + 1) - off(2 * w)));
    }
    for (int i = 0; i < 2; i++) {
      const int w = kind == 0 ? 0 : kind & 1 ? 3 * i : 1 - i;
      tt.b[kind][i][0] = tt.g[kind][2 * w][0];
      tt.b[kind][i][1] = (uint16_t)(128 * (kind == 0 ? 0 : (col ? 3 : 1) + i));
      tt.b[kind][i][2] = (uint16_t)(2048 * w);
      tt.b[kind][i][3] = 0;
    }
  }
}
__device__ __forceinline__ int num_tiles() { return blockIdx.x < 128 ? 6 : 4; }
__device__ __forceinline__ TileCoord decode_tile(const TileTable& tt, int tile) {
  const uint32_t e = tt.e[tile];
  return TileCoord{(int)(e >> 8) & 1, (int)(e >> 9) & 1, (int)e & 15, (int)(e >> 4) & 15, (int)(e >> 10) & 1, (int)(e >> 11)};
}
__device__ __forceinline__ int halo_r0(const TileCoord& t) { return 8 * t.I + 6 * t.pr - 6; }
__device__ __forceinline__ int halo_c0(const TileCoord& t) { return min(max(8 * t.J + 6 * t.pc - 6, -3), 102); }

__device__ __forceinline__ uint32_t bar_full(uint32_t bars, int wg, int c) { return bars + (wg * 3 + c) * 8; }
__device__ __forceinline__ uint32_t bar_w1c(uint32_t bars, int c) { return bars + (6 + c) * 8; }
__device__ __forceinline__ uint32_t bar_w2(uint32_t bars) { return bars + 9 * 8; }
__device__ __forceinline__ uint32_t bar_x(uint32_t bars, int j, int c) { return bars + (j == 0 ? 10 : c ? 17 + c : 11) * 8; }
__device__ __forceinline__ uint32_t bar_w1q(uint32_t bars) { return bars + 12 * 8; }
__device__ __forceinline__ uint32_t bar_xf(uint32_t bars) { return bars + 13 * 8; }
__device__ __forceinline__ uint32_t bar_w2m(uint32_t bars) { return bars + 14 * 8; }
__device__ __forceinline__ uint32_t bar_redo(uint32_t bars) { return bars + 15 * 8; }
__device__ __forceinline__ uint32_t bar_wok(uint32_t bars) { return bars + 16 * 8; }
__device__ __forceinline__ uint32_t bar_go(uint32_t bars) { return bars + 17 * 8; }
__device__ __forceinline__ uint32_t bar_raw(uint32_t bars, int j = 0) { return bars + (21 + j) * 8; }
__device__ __forceinline__ uint32_t bar_w2a(uint32_t bars) { return bars + 20 * 8; }
constexpr int kNumBars = 22;

__device__ __forceinline__ uint64_t wdesc(uint64_t d0, int s) { return d0 + (((s >> 2) * kWChunk + (s & 3) * 32) >> 4); }

__device__ __forceinline__ uint32_t x_chunk(int k, int c) { return kXOff + (k == 0 ? kWChunk : 0) + (k & 1 ? 2 - c : c) * 8192; }
__device__ __forceinline__ uint32_t out_slot(int k, int nt) { return k + 1 < nt ? kW2Off + (~k & 1) * 2 * kWChunk : kW1Off + kWChunk; }
template <int I0, int I1>
__device__ __forceinline__ void store_rows(bool on, __nv_bfloat16* pA, __nv_bfloat16* pB, const uint32_t (&a)[24], const uint32_t (&b)[24]) {
#pragma unroll
  for (int i = 2 * I0; i < 2 * I1; i++) {
    const uint32_t* v = (i & 1 ? b : a) + 4 * (i >> 1);
    asm volatile("{\n.reg .pred p;\nsetp.ne.u32 p, %5, 0;\n@p st.global.v4.u32 [%0], {%1,%2,%3,%4};\n}\n" ::"l"((i & 1 ? pB : pA) + 32 * (i >> 1)),
                 "r"(v[0]), "r"(v[1]), "r"(v[2]), "r"(v[3]), "r"((uint32_t)on) : "memory");
  }
}
template <int I0, int I1>
__device__ __forceinline__ void stage_out(const uint32_t (&ad)[4], const uint32_t (&a)[24], const uint32_t (&b)[24]) {
#pragma unroll
  for (int i = I0; i < I1; i++) {
    const uint32_t* v = (i < 6 ? a : b) + 4 * (i % 6);
    asm volatile("st.shared.v4.u32 [%0], {%1,%2,%3,%4};" ::"r"(ad[i % 6 / 3 * 2 + (i % 3 == 1)] + (i % 3 == 2) * 1024 + (i / 6) * 12288),
                 "r"(v[0]), "r"(v[1]), "r"(v[2]), "r"(v[3]) : "memory");
  }
}
__device__ __forceinline__ uint32_t now_ns() {
  uint32_t t;
  asm volatile("mov.u32 %0, %globaltimer_lo;" : "=r"(t)::"memory");
  return t;
}
__device__ __forceinline__ void wait_clock(uint32_t t_start, uint32_t t) {
  while (now_ns() - t_start < t) { }
}
__device__ __forceinline__ void sleep_clock(uint32_t t_start, uint32_t t) {
  while (now_ns() - t_start < t) __nanosleep(100);
}
#define NAT_PRED(f, m) ".reg .pred p;\n.reg .b32 t;\nand.b32 t, " f ", " m ";\nsetp.ne.u32 p, t, 0;\n"
constexpr uint32_t kHiV = 1, kHiU = 8, kColB = 0x20, kInV = 0x100, kInU = 0x1000, kColA = 0x10000;
template <uint32_t M>
__device__ __forceinline__ float pick(const float* a, const float* b, uint32_t f) {
  float d;
  asm("{\n" NAT_PRED("%5", "%6") "add.f32 %0, %1, %2;\n@p add.f32 %0, %3, %4;\n}\n"
      : "=&f"(d) : "f"(a[0]), "f"(a[2]), "f"(b[0]), "f"(b[2]), "r"(f), "n"(M));
  return d;
}
template <uint32_t M>
__device__ __forceinline__ float sel(float a, float b, uint32_t f) {
  float d;
  asm("{\n" NAT_PRED("%3", "%4") "selp.f32 %0, %1, %2, p;\n}\n" : "=f"(d) : "f"(a), "f"(b), "r"(f), "n"(M));
  return d;
}
template <uint32_t M>
__device__ __forceinline__ void max_if(float& m, float v, uint32_t f) {
  asm("{\n" NAT_PRED("%2", "%3") "@p max.f32 %0, %0, %1;\n}\n" : "+f"(m) : "f"(v), "r"(f), "n"(M));
}
template <uint32_t M>
__device__ __forceinline__ void add_if(float& m, float v, uint32_t f) {
  asm("{\n" NAT_PRED("%2", "%3") "@p add.f32 %0, %0, %1;\n}\n" : "+f"(m) : "f"(v), "r"(f), "n"(M));
}
__device__ __forceinline__ void pick_v(const float* a, float* v, uint32_t f) {
  v[0] = pick<kHiV>(a, a + 16, f), v[1] = pick<kHiV>(a + 1, a + 17, f);
  v[2] = pick<kHiV * 2>(a + 4, a + 20, f), v[3] = pick<kHiV * 2>(a + 5, a + 21, f);
  v[4] = pick<kHiV * 4>(a + 8, a + 24, f), v[5] = pick<kHiV * 4>(a + 9, a + 25, f);
  v[6] = a[12] + a[14], v[7] = a[13] + a[15];
}
__device__ __forceinline__ void pick_u(const float* a, float* v, uint32_t f) {
#pragma unroll
  for (int c = 0; c < 3; c++) v[2 * c] = pick<kHiU>(a + 4 * c, a + 4 * c + 12, f), v[2 * c + 1] = pick<kHiU * 2>(a + 4 * c + 1, a + 4 * c + 13, f);
}
__device__ __forceinline__ uint32_t sign_bytes(uint32_t v, uint32_t sel) {
  uint32_t d;
  asm("prmt.b32 %0, %1, %1, %2;" : "=r"(d) : "r"(v), "r"(sel));
  return d;
}
__device__ __forceinline__ float own_max(const float (&v)[14], uint32_t f) {
  float m = sel<kInV>(fmaxf(v[0], v[1]), -INFINITY, f), m2 = sel<kInV * 2>(fmaxf(v[2], v[3]), -INFINITY, f);
  max_if<kInV * 4>(m, fmaxf(v[4], v[5]), f);
  max_if<kInV * 8>(m2, fmaxf(v[6], v[7]), f);
  max_if<kInU>(m, fmaxf(fmaxf(v[8], v[10]), v[12]), f);
  max_if<kInU * 2>(m2, fmaxf(fmaxf(v[9], v[11]), v[13]), f);
  return fmaxf(m, m2);
}
__device__ __forceinline__ float quad_max(float m) {
  const float a = __shfl_xor_sync(0xffffffffu, m, 1), b = __shfl_xor_sync(0xffffffffu, m, 2), c = __shfl_xor_sync(0xffffffffu, m, 3);
  return fmaxf(fmaxf(m, a), fmaxf(b, c));
}
__device__ __forceinline__ float row_rcp(const float (&v)[14], uint32_t f) {
  float s = sel<kInV>(v[0] + v[1], 0.f, f), s2 = sel<kInV * 2>(v[2] + v[3], 0.f, f);
  add_if<kInV * 4>(s, v[4] + v[5], f);
  add_if<kInV * 8>(s2, v[6] + v[7], f);
  add_if<kInU>(s, v[8] + v[10] + v[12], f);
  add_if<kInU * 2>(s2, v[9] + v[11] + v[13], f);
  s += s2;
  const float a = __shfl_xor_sync(0xffffffffu, s, 1), b = __shfl_xor_sync(0xffffffffu, s, 2), c = __shfl_xor_sync(0xffffffffu, s, 3);
  return rcp_approx((s + a) + (b + c));
}
__device__ __forceinline__ void route(const float (&v)[14], float s, const uint32_t (&rt)[9], uint32_t (&p)[14]) {
#pragma unroll
  for (int i = 0; i < 7; i++) {
    const uint32_t u = pack_bf16(v[2 * i] * s, v[2 * i + 1] * s);
    if (i < 4) p[i] = u & rt[i];
    if (i < 3) p[i + 4] = u & rt[i + 4];
    if (i >= 4) {
      p[i + 3] = u & rt[7];
      p[i + 6] = u & rt[8];
    }
  }
}

template <int C, int T0 = 0, int T1 = 7>
__device__ __forceinline__ void pv_chunk(float (&z)[32], const uint32_t (&pa)[14], const uint32_t (&pb)[14],
                                         const uint32_t (&meta)[4], uint64_t dV) {
#pragma unroll
  for (int t = T0; t < T1; t++) {
    if (t & 1)
      wg_s64t1<0, 32>(z, pa[2 * t], pb[2 * t], pa[2 * t + 1], pb[2 * t + 1], dV + ((2 * C * kChunkBytes + t * 2048) >> 4), 1,
                      meta[t >> 1]);
    else if (t > 0)
      wg_s64t<0, 32>(z, pa[2 * t], pb[2 * t], pa[2 * t + 1], pb[2 * t + 1], dV + ((2 * C * kChunkBytes + t * 2048) >> 4), 1,
                     meta[t >> 1]);
    else
      wg_s64tz<0, 32>(z, pa[0], pb[0], pa[1], pb[1], dV + ((2 * C * kChunkBytes) >> 4), 0, meta[0]);
  }
}
template <int C>
__device__ __forceinline__ void pack_z(const float (&z)[32], uint32_t (&za)[24], uint32_t (&zb)[24]) {
#pragma unroll
  for (int j = 0; j < 8; j++) {
    za[8 * C + j] = pack_bf16(z[4 * j], z[4 * j + 1]);
    zb[8 * C + j] = pack_bf16(z[4 * j + 2], z[4 * j + 3]);
  }
}

template <int H>
__device__ __forceinline__ void pack_out(const float (&ac)[48], uint32_t (&oa)[24], uint32_t (&ob)[24]) {
#pragma unroll
  for (int j = 0; j < 12; j++) {
    oa[12 * H + j] = pack_bf16(ac[4 * j], ac[4 * j + 1]);
    ob[12 * H + j] = pack_bf16(ac[4 * j + 2], ac[4 * j + 3]);
  }
}
struct Maps { CUtensorMap v6, v2, v14, u8, px[8], wv, wo; };
__device__ __forceinline__ void tma_prefetch_5d(const CUtensorMap* map, int c0, int c1, int c2, int c3, int c4) {
  asm volatile("cp.async.bulk.prefetch.tensor.5d.L2.global.tile [%0, {%1, %2, %3, %4, %5}];" ::"l"((uint64_t)map), "r"(c0), "r"(c1),
               "r"(c2), "r"(c3), "r"(c4) : "memory");
}
__device__ __forceinline__ int first_line(const TileCoord tc) { return 3 * (qpix(tc.pr, 8 * tc.I) * kW + qpix(tc.pc, 8 * tc.J)); }
__device__ __forceinline__ void load_px(const Maps& tm, const TileTable& tt, uint32_t dst, uint32_t bar, int line, int kind) {
#pragma unroll
  for (int i = 0; i < 2; i++) {
    if (i == 0 || kind != 0) {
      const CUtensorMap* map = (const CUtensorMap*)((const char*)tm.px + tt.b[kind][i][1]);
      if (bar) tma_load_5d(dst + tt.b[kind][i][2], map, bar, 0, 0, 0, 0, line + tt.b[kind][i][0]);
      else tma_prefetch_5d(map, 0, 0, 0, 0, line + tt.b[kind][i][0]);
    }
  }
}
__device__ __forceinline__ void store_px(const Maps& tm, const TileTable& tt, uint32_t buf, int line, int kind) {
#pragma unroll
  for (int i = 0; i < 8; i++) {
    const int j = 2 * (i & 3) + (i >> 2);
    asm volatile("cp.async.bulk.tensor.5d.global.shared::cta.tile.bulk_group [%0, {%2, %2, %2, %2, %3}], [%1];" ::"l"(
                     (uint64_t)tm.px + tt.g[kind][j][1]), "r"(buf + i * 3072), "r"(0), "r"(line + tt.g[kind][j][0]) : "memory");
  }
  asm volatile("cp.async.bulk.commit_group;" ::: "memory");
}
__device__ __noinline__ bool refetch(uint32_t base, const uint8_t* src, bool gap) {
  constexpr uint32_t bars = 1024 + kBarOff, cnt = bars + 192;
#pragma unroll 1
  for (uint32_t o = 0; o < kWBytes && !gap; o += 2048) {
    uint32_t mx = 0;
#pragma unroll
    for (int i = 0; i < 4; i++) {
      uint4 v;
      asm volatile("ld.shared.v4.u32 {%0,%1,%2,%3}, [%4];" : "=r"(v.x), "=r"(v.y), "=r"(v.z), "=r"(v.w)
                   : "r"(base + o + i * 512 + (threadIdx.x & 31) * 16));
      mx = __vimax3_u32(__vimax3_u32(mx, v.x, v.y), v.z, v.w);
    }
    gap = __any_sync(0xffffffffu, mx == kEmpty);
  }
  uint32_t n;
  asm volatile("ld.shared.u32 %0, [%1];" : "=r"(n) : "r"(cnt) : "memory");
  if (!gap || __any_sync(0xffffffffu, n > (1u << 12))) return false;
  asm volatile("bar.sync 15, 128;" ::: "memory");
  if (threadIdx.x == 0) {
    asm volatile("st.shared.u32 [%0], %1;" ::"r"(cnt), "r"(n + 1) : "memory");
    mbar_arrive_expect_tx(bar_redo(bars), kWBytes);
    bulk_load(base, src, kWBytes, bar_redo(bars));
  }
  __syncwarp();
  mbar_wait(bar_redo(bars), n & 1);
  return true;
}
__device__ __forceinline__ bool any_nan(const uint32_t (&a)[24]) {
  uint32_t m[2] = {a[0], a[1]}, nan;
#pragma unroll
  for (int i = 2; i < 24; i++) asm("max.NaN.bf16x2 %0, %0, %1;" : "+r"(m[i & 1]) : "r"(a[i]));
  asm("max.NaN.bf16x2 %0, %0, %1;" : "+r"(m[0]) : "r"(m[1]));
  asm volatile("{\n.reg .pred p;\nsetp.ne.u32 p, %1, 0;\nbar.red.or.pred p, 15, 128, p;\nselp.u32 %0, 1, 0, p;\n}\n"
               : "=r"(nan) : "r"(((m[0] & 0x7FFF7FFFu) + 0x007F007Fu) & 0x80008000u) : "memory");
  return __any_sync(0xffffffffu, nan);
}
template <int S0, int S1, int Z>
__device__ __forceinline__ void g2_steps(float (&ac)[48], const uint32_t (&za)[24], const uint32_t (&zb)[24], uint64_t d) {
#pragma unroll
  for (int s = S0; s < S1; s++) {
    const uint64_t ds = d + (((s >> 2 & 1) * (kWChunk / 2) + (s & 3) * 32) >> 4);
    if (s == Z) wg_d96z<0, 48>(ac, za[2 * s], zb[2 * s], za[2 * s + 1], zb[2 * s + 1], ds, 0);
    else wg_d96<0, 48>(ac, za[2 * s], zb[2 * s], za[2 * s + 1], zb[2 * s + 1], ds, 1);
  }
}

__device__ __forceinline__ void consumer(const int wg, __nv_bfloat16* out, const uint8_t* wimg, const uint32_t sbase,
                                         const uint32_t zero, const Maps& tm, const TileTable& tt) {
  const int tid = threadIdx.x & 127;
  const int w = __shfl_sync(0xffffffffu, tid >> 5, 0), lane = tid & 31;
  const uint64_t dK = make_desc(sbase, 16, 1024);
  const uint64_t dV = make_desc(sbase, kChunkBytes, 512, 2);
  const uint64_t dW1 = make_desc(sbase + kW1Off, 16, 1024);
  const uint64_t dX0 = make_desc(sbase + kW2Off + wg * 2 * kWChunk, 16, 1024), dY0 = make_desc(sbase + kW2Off + (1 - wg) * 2 * kWChunk, 16, 1024);
  const uint64_t dX2 = make_desc(sbase + kXOff + wg * (kWChunk / 2), 16, 1024), dY2 = make_desc(sbase + kXOff + (1 - wg) * (kWChunk / 2), 16, 1024);
  const uint32_t bars = sbase + kBarOff;
  int tile0 = blockIdx.x * kTilesPerCta;
  asm volatile("" : "+r"(tile0));
  const int nt = num_tiles();

  uint32_t pix = 0, geo[6] = {};
  const int l = lane & 3;
#pragma unroll 1
  for (int j = 4; j >= 0; j -= 2) {
    const TileCoord tc = decode_tile(tt, tile0 + wg + j);
    const bool col = tc.kind == 1 || tc.kind == 2;
    const int g = col ? lane >> 2 : 2 * w + ((lane >> 2) & 1), qc = col ? w : lane >> 3;
    const uint32_t pr = qpix(tc.pr, 8 * tc.I + g) * kW;
    if (j == nt - 2) pix = (pr + qpix(tc.pc, 8 * tc.J + qc)) | (pr + qpix(tc.pc, 8 * tc.J + qc + 4)) << 16;
    const int d = 8 * tc.J + 6 * tc.pc - 6 - halo_c0(tc);
    const int ro = woff(tc.pr, tc.I, g), coA = woff(tc.pc, tc.J, qc) + d, coB = woff(tc.pc, tc.J, qc + 4) + d - 3;
#pragma unroll
    for (int i = 5; i >= 2; i--) geo[i] = geo[i - 2];
    const uint32_t lr = 0x1FCu << ro;
    const uint32_t lv = lr >> (2 + (l >> 1)), lu = lr >> (2 * l + 2 * tc.up);
    const uint32_t t = __byte_perm(lv, lu, wg ? 0x4501 : 0x5410);
    geo[0] = (((t & 0x15u) | (lv & 0x40u)) * 0x02082080u & 0x80808080u) | (((t >> 8) & 0x15u) * 0x01041040u & 0x40404040u) |
             (__byte_perm(t << 5, t << 4, 0x7362) & 0x20202020u) | (nt == 6);
    const int dr = (ro - 1) & 7;
    const uint32_t hiv = (((1u << ((ro - (l >> 1) + 1) >> 1)) - 1u) ^ (wg ? 7u : 0u)) & 7u, hiu = (t >> 24) & 3u;
    const uint32_t ca = (1u << coA) - 1u;
    geo[1] = hiv * kHiV | hiu * kHiU | ((((1u << coB) - 1u) >> (2 * (l & 1))) & 3u) * kColB |
             (15u & ~((uint32_t)((dr & 1) == (l >> 1)) << (dr >> 1))) * kInV | ((t >> 16 | t >> 24) & 3u) * kInU | ca * kColA |
             (ca >> ((0x49 >> (2 * l)) & 3) & 1u) << 19 | (uint32_t)(l == 3) << 20 | (0x55u & ((1u << (2 * coB)) - 1u)) << 24;
  }
  keep_regs(geo);
  const int so = (lane >> 3) | (lane & 4);
  uint32_t sts = sbase + w * 3072 + so * 128 + (((lane & 3) ^ so) << 4);
  __nv_bfloat16* poA = out + 8 * l + (pix & 0xFFFFu) * kC + 96 * wg;
  __nv_bfloat16* poB = out + 8 * l + (pix >> 16) * kC + 96 * wg;
  asm volatile("" : "+l"(poA), "+l"(poB), "+r"(sts));
  uint32_t oa[24], ob[24];
#pragma unroll
  for (int j = 0; j < 24; j++) oa[j] = ob[j] = 0u;
  keep_regs(oa);
  keep_regs(ob);
  PROF(wg, 0);
  if (threadIdx.x == 0) GT(1);

  for (int k = wg; k < nt; k += 2) {
    const uint32_t ph = (k >> 1) & 1;
    const int it = k >> 1;
    uint32_t qa[24], qb[24], hok[3];
    uint32_t fl = geo[1];
    {
      float acc[96];
      const uint32_t xp = (k + (k > 0)) & 1;
      if (k > 0) nb_sync(1 + (1 - wg));
#pragma unroll
      for (int s = 0; s < 12; s++) {
        if (s == 0) mbar_wait(bar_x(bars, k > 0, 0), xp);
        if (s == 0 && k < 2) PROF(wg, 1);
        if (s == 0) PROFS(2, wg, 2 + it * 12);
        if (s == 0 && w == 0 && k < 2) GT(20 + wg);
        if (s == 4) wg_wait<1>();
        if ((s & 3) == 0 && (k == 0 || s > 0)) {
          mbar_wait(k == 0 ? bar_w1c(bars, s >> 2) : bar_x(bars, 1, s >> 2), xp);
          PROFS(17, wg, 50 + (s >> 2));
        }
        if ((s & 3) == 0) wg_fence();
        const uint64_t dX = make_desc(sbase + x_chunk(k, s >> 2), 16, 1024) + 2 * (s & 3);
        if (s == 0) wg_m192z<0, 96>(acc, dX, dW1, 0);
        else wg_m192<0, 96>(acc, dX, wdesc(dW1, s), 1);
        if ((s & 3) == 3 || s == 0) wg_commit();
      }
      PROFS(13, wg, 13 + it * 12);
      const uint32_t e = sts + out_slot(k, nt), o = e ^ 64;
      uint32_t ad[4] = {wg ? o + 1024 : e, wg ? e + 2048 : o, wg ? e : o + 1024, wg ? o : e + 2048};
      keep_regs(ad);
      wg_wait<2>();
      if (k > 0) nb_arrive_p(0);
      wg_wait<1>();
      if (k > 0) nb_arrive_p(14);
      wg_wait<0>();
      if (k > 0) {
        nb_arrive_p(6);
        sched_fence();
      }
      fence_regs(acc);
      PROFS(3, wg, 3 + it * 12);
#pragma unroll
      for (int j = 0; j < 24; j++) {
        qa[j] = pack_bf16(acc[4 * j], acc[4 * j + 1]);
        qb[j] = pack_bf16(acc[4 * j + 2], acc[4 * j + 3]);
      }
      keep_regs(qa);
      keep_regs(qb);
      sched_fence();
      if (k >= 2) {
        nb_sync(11);
        stage_out<0, 6>(ad, oa, ob);
        nb_sync(12);
        stage_out<6, 12>(ad, oa, ob);
      }
#pragma unroll
      for (int c = 0; c < 3; c++) hok[c] = mbar_test(bar_full(bars, wg, c), ph);
      if (k >= 2) {
        fence_proxy_async();
        nb_arrive_p(10);
      }
    }

    float aE[52], aO[24], bO[52], bE[28];
    const uint32_t mq = 0xEEEE4444u | zero;
    PROFS(4, wg, 4 + it * 12);

    mbar_wait_if(hok[0], bar_full(bars, wg, 0), ph);
    PROFS(14, wg, 40 + it * 3);
    if (w == 0 && k < 2) GT(22 + wg);
    if (k > 0) nb_sync(3 + (1 - wg));
    wg_fence();
#pragma unroll
    for (int ks = 0; ks < 6; ks++) {
      if (ks == 2) {
        mbar_wait_if(hok[1], bar_full(bars, wg, 1), ph);
        PROFS(14, wg, 41 + it * 3);
        wg_fence();
      }
      if (ks == 4) {
        mbar_wait_if(hok[2], bar_full(bars, wg, 2), ph);
        PROFS(14, wg, 42 + it * 3);
        wg_fence();
      }
      const uint64_t d = dK + ((ks * kChunkBytes) >> 4);
      if (ks == 0) wg_s104z<0, 52>(aE, qa[0], qa[1], qa[2], qa[3], d, 0, mq);
      else wg_s104<0, 52>(aE, qa[4 * ks], qa[4 * ks + 1], qa[4 * ks + 2], qa[4 * ks + 3], d, 1, mq);
      if (ks == 0) wg_s48z<0, 24>(aO, qa[0], qa[1], qa[2], qa[3], d + ((7 * 1024 + 64) >> 4), 0, mq);
    }
    wg_commit();
#pragma unroll
    for (int ks = 1; ks < 6; ks++)
      wg_s48<0, 24>(aO, qa[4 * ks], qa[4 * ks + 1], qa[4 * ks + 2], qa[4 * ks + 3], dK + ((ks * kChunkBytes + 7 * 1024 + 64) >> 4), 1, mq);
    wg_commit();
    wg_s56z<0, 28>(bE, qb[0], qb[1], qb[2], qb[3], dK, 0, mq);
#pragma unroll
    for (int ks = 1; ks < 6; ks++) wg_s56<0, 28>(bE, qb[4 * ks], qb[4 * ks + 1], qb[4 * ks + 2], qb[4 * ks + 3], dK + ((ks * kChunkBytes) >> 4), 1, mq);
    wg_commit();
    wg_wait<2>();
    fence_regs(aE);
    PROFS(5, wg, 5 + it * 12);

    uint32_t pa[14], pb[14], meta[4];
    {
      float vA[14], vB[14];
      pick_v(aE, vA, fl);
      pick_u(aE + 28, vA + 8, fl);
      fence_regs(vA);
      if (k == 0) {
        if (__builtin_expect(__any_sync(0xffffffffu, vA[6] != vA[6]), 0)) {
          wg_wait<0>();
          fence_regs(aO);
          fence_regs(bE);
          if (refetch(sbase + kW1Off, wimg, false)) {
#pragma unroll
            for (int j = 0; j < 24; j++) oa[j] = ob[j] = 0u;
            k -= 2;
            continue;
          }
        }
        if (elect_one()) mbar_arrive(bar_xf(bars));
      }
      wg_fence();
      wg_s104z<0, 52>(bO, qb[0], qb[1], qb[2], qb[3], dK + 4, 0, mq);
#pragma unroll
      for (int ks = 1; ks < 6; ks++)
        wg_s104<0, 52>(bO, qb[4 * ks], qb[4 * ks + 1], qb[4 * ks + 2], qb[4 * ks + 3], dK + ((ks * kChunkBytes + 64) >> 4), 1, mq);
      wg_commit();
      if (k + 1 < nt) nb_arrive(1 + wg);
      uint32_t rt[9];
#pragma unroll
      for (int i = 0; i < 7; i++) rt[i] = sign_bytes(geo[0] << (i >> 2), 0x8888u + 0x1111u * (i & 3));
      rt[7] = sign_bytes(geo[0] << 2, 0x9988u);
      rt[8] = sign_bytes(geo[0] << 2, 0xBBAAu);
      keep_regs(rt);
      pa[13] = geo[0] & zero, pb[13] = geo[1] & zero;
      wg_wait<2>();
      keep_regs(qa);
      fence_regs(aO);
      float oA[6], eB[8];
      pick_u(aO, oA, fl);
      wg_wait<1>();
      fence_regs(bE);
      pick_v(bE, eB, fl);
      vA[8] = sel<kColA>(oA[0], vA[8], fl), vA[9] = sel<kColA>(oA[1], vA[9], fl);
      vA[10] = sel<kColA * 2>(oA[2], vA[10], fl), vA[11] = sel<kColA * 2>(oA[3], vA[11], fl);
      vA[12] = sel<kColA * 4>(oA[4], vA[12], fl), vA[13] = sel<kColA * 4>(oA[5], vA[13], fl);
      {
        const float m1 = __uint_as_float(0x88DD88DDu), m0 = __uint_as_float(0x88DDDD88u);
        meta[0] = 0xDD88DD88u ^ __byte_perm(fl, 0u, 0x3344);
        meta[1] = __float_as_uint(sel<kColA * 16>(sel<kColA>(m1, m0, fl), __uint_as_float(meta[0]), fl));
        meta[2] = __float_as_uint(sel<kColA * 8>(m1, m0, fl));
        meta[3] = __float_as_uint(sel<kColA * 4>(m1, m0, fl));
        keep_regs(meta);
      }
      float mA = own_max(vA, fl);
      fl |= __float_as_uint(eB[7]) & zero;
      fence_regs(eB);
      fence_regs(vA);
      asm volatile("" : "+f"(mA), "+r"(fl));
      sched_fence();
      wg_wait<0>();
      sched_fence();
      keep_regs(qb);
      fence_regs(bO);
      PROFS(6, wg, 6 + it * 12);
      if (w == 0) GT(24 + k);
      mA = quad_max(mA);
      pick_v(bO, vB, fl);
      pick_u(bO + 28, vB + 8, fl);
#pragma unroll
      for (int i = 0; i < 8; i += 2) vB[i] = sel<kColB>(vB[i], eB[i], fl), vB[i + 1] = sel<kColB * 2>(vB[i + 1], eB[i + 1], fl);
#pragma unroll
      for (int i = 0; i < 14; i++) vA[i] = i < 3 ? ex2(vA[i] - mA) : vA[i] - mA;
      fence_regs(vA);
      fence_regs(vB);
      sched_fence();
#pragma unroll
      for (int i = 3; i < 14; i++) vA[i] = ex2(vA[i]);
      const float mB = quad_max(own_max(vB, fl));
      PROFS(7, wg, 7 + it * 12);
#pragma unroll
      for (int i = 0; i < 14; i++) vB[i] = i < 1 ? ex2(vB[i] - mB) : vB[i] - mB;
      fence_regs(vA);
      fence_regs(vB);
      sched_fence();
#pragma unroll
      for (int i = 1; i < 14; i++) vB[i] = ex2(vB[i]);
      route(vA, row_rcp(vA, fl), rt, pa);
      route(vB, row_rcp(vB, fl), rt, pb);
    }
    PROFS(8, wg, 8 + it * 12);
    if (k == NAT_PK) PROFS(18, wg, 53);
    sched_fence();

    float ac0[48], ac1[48];
    {
      float z0[32], z1[32], z2[32];
      uint32_t za[24], zb[24];
      wg_fence();
      pv_chunk<0>(z0, pa, pb, meta, dV);
      wg_commit();
      pv_chunk<1>(z1, pa, pb, meta, dV);
      wg_commit();
      wg_wait<1>();
      if (k == NAT_PK) PROFS(18, wg, 54);
      if (k + 1 < nt) nb_arrive_p(7);
      pv_chunk<2, 0, 3>(z2, pa, pb, meta, dV);
      wg_commit();
      sched_fence();
      fence_regs(z0);
      pack_z<0>(z0, za, zb);
      sched_fence();
      wg_fence();
      pv_chunk<2, 3, 7>(z2, pa, pb, meta, dV);
      wg_commit();
      wg_wait<2>();
      if (k == NAT_PK) PROFS(19, wg, 55);
      if (k + 1 < nt) nb_arrive_p(8);
      if (k < 2) mbar_wait(k == 1 ? bar_wok(bars) : bar_w2a(bars), 0);
      wg_fence();
      g2_steps<0, 3, 0>(ac0, za, zb, dX0);
      wg_commit();
      sched_fence();
      fence_regs(z1);
      pack_z<1>(z1, za, zb);
      sched_fence();
      wg_fence();
      g2_steps<3, 4, 0>(ac0, za, zb, dX0);
      wg_commit();
      g2_steps<4, 8, 0>(ac0, za, zb, dX0);
      wg_commit();
      wg_wait<3>();
      if (k + 1 < nt) nb_arrive_p(9);
      else nb_arrive(11);
      if (k == NAT_PK) PROFS(20, wg, 56);
      keep_regs(pa);
      keep_regs(pb);
      keep_regs(meta);
      sched_fence();
      const uint32_t mok = mbar_test(bar_w2m(bars), k + 1 < nt ? k & 1 : ~k & 1);
      const uint32_t wp = k < 2 ? 0 : k + 1 < nt ? ~k & 1 : k & 1, wok = mbar_test(bar_w2(bars), wp);
      fence_regs(z2);
      pack_z<2>(z2, za, zb);
      keep_regs(za);
      keep_regs(zb);
      sched_fence();
      PROFS(9, wg, 9 + it * 12);
      wg_wait<1>();
      if (k > 0 && k + 1 < nt) nb_arrive(11);
      mbar_wait_if(mok, bar_w2m(bars), k & 1);
      wg_fence();
      g2_steps<8, 12, 0>(ac0, za, zb, dX2);
      wg_commit();
      g2_steps<8, 12, 8>(ac1, za, zb, dY2);
      wg_commit();
      wg_wait<2>();
      if (k > 0 && k + 1 < nt) nb_arrive(12);
      mbar_wait_if(wok, bar_w2(bars), wp);
      wg_fence();
      g2_steps<0, 4, 8>(ac1, za, zb, dY0);
      wg_commit();
      wg_wait<2>();
      if (k + 2 < nt) nb_arrive_p(13);
      const bool direct = k + 2 >= nt;
      sched_fence();
      fence_regs(ac0);
      pack_out<0>(ac0, oa, ob);
      store_rows<0, 1>(direct, poA, poB, oa, ob);
      sched_fence();
      wg_fence();
      g2_steps<4, 8, 8>(ac1, za, zb, dY0);
      wg_commit();
      if (k + 1 < nt) nb_arrive(3 + wg);
      PROFS(10, wg, 10 + it * 12);
      wg_wait<2>();
      if (k + 2 < nt && (k > 0 || nt == 6)) nb_arrive_p(5);
      store_rows<1, 3>(direct, poA, poB, oa, ob);
      __nv_bfloat16 *qA = poA - 192 * wg, *qB = poB - 192 * wg;
      if (k + 2 == nt) nb_sync(11);
      sched_fence();
      wg_wait<0>();
      fence_regs(ac1);
      if (direct) {
        pack_out<1>(ac1, oa, ob);
        asm volatile("" : "+l"(qA), "+l"(qB));
        store_rows<3, 6>(true, qA, qB, oa, ob);
        break;
      }
      sched_fence();
      pack_out<1>(ac1, oa, ob);
      if (k == 0) {
        if (any_nan(oa)) {
          for (int c = 0; c < 3 && __any_sync(0xffffffffu, geo[2] & 1u); c++) mbar_wait(bar_x(bars, 1, c), 1);
          bool first = true;
          do {
            if (!__any_sync(0xffffffffu, refetch(sbase + kW2Off, wimg + w2_offset(), first))) break;
            first = false;
            wg_fence();
            g2_steps<0, 8, 0>(ac0, za, zb, dX0);
            g2_steps<8, 12, 0>(ac0, za, zb, dX2);
            g2_steps<8, 12, 8>(ac1, za, zb, dY2);
            g2_steps<0, 8, 8>(ac1, za, zb, dY0);
            wg_commit();
            wg_wait<0>();
            fence_regs(ac0);
            fence_regs(ac1);
            pack_out<0>(ac0, oa, ob);
            pack_out<1>(ac1, oa, ob);
          } while (any_nan(oa));
          if (__any_sync(0xffffffffu, geo[2] & 1u)) {
            asm volatile("bar.sync 15, 128;" ::: "memory");
            if (w == 0 && elect_one()) {
              const TileCoord tc = decode_tile(tt, tile0 + 2);
              mbar_arrive_expect_tx(bar_raw(bars), kWChunk);
#pragma unroll 1
              for (int c = 0; c < 3; c++) load_px(tm, tt, sbase + x_chunk(2, c), bar_raw(bars), first_line(tc) + c, tc.kind);
            }
            __syncwarp();
            mbar_wait(bar_raw(bars), 0);
          }
        }
        if (nt < 6) nb_arrive_p(5);
        if (elect_one()) mbar_arrive(bar_wok(bars));
      }
      keep_regs(za);
      keep_regs(zb);
#pragma unroll
      for (int i = 0; i < 4; i++) geo[i] = geo[i + 2];
      keep_regs(oa);
      keep_regs(ob);
      PROFS(12, wg, 12 + it * 12);
      sched_fence();
    }
  }
  PROF(wg, 38);
  GT_DUMP();
  PROF_DUMP(wg);
}

struct HaloCols { int vj, vc, uj, uc; };
__device__ __forceinline__ HaloCols halo_cols(const TileCoord& tc) {
  const int c0 = halo_c0(tc);
  return HaloCols{c0 > 98, c0 > 98 ? 98 : c0 + 3, c0 < 0 ? -1 : 0, c0 < 0 ? 4 : c0};
}
__device__ __forceinline__ void first_halo(const Maps& tm, uint32_t sbase, const TileCoord tc, int i) {
  const HaloCols hc = halo_cols(tc);
  const uint32_t dst = sbase + i * kChunkBytes, bar = bar_full(sbase + kBarOff, 0, i >> 1);
  const int h0 = halo_r0(tc), ch = 24 * tc.pc + 4 * i;
  tma_load_5d(dst, &tm.v14, bar, ch, hc.vj, hc.vc, tc.pr, h0);
  tma_load_5d(dst + 7 * 1024, &tm.u8, bar, ch, hc.uj, h0 + (tc.up ? 0 : -2), tc.pr, hc.uc);
  tma_load_5d(dst + 10 * 1024, &tm.u8, bar, ch, hc.uj, h0 + (tc.up ? 8 : 6), tc.pr, hc.uc);
}
__device__ __forceinline__ void load_halo(const Maps& tm, uint32_t sbase, uint32_t bars, const TileCoord tc, int k, int c) {
  const HaloCols hc = halo_cols(tc);
  const int h6 = halo_r0(tc) + (tc.up ? 0 : 8), h2 = halo_r0(tc) + 6, h8 = halo_r0(tc) + (tc.up ? 0 : 6), ch = 24 * tc.pc + 8 * c;
  uint32_t dv = sbase + 2 * c * kChunkBytes, du = dv + 7 * 1024;
  if (((k ^ tc.up) & 1) == 0) dv += 4 * 1024, du += 3 * 1024;
  const uint32_t bar = bar_full(bars, k & 1, c);
  mbar_arrive_expect_tx(bar, 14 * 1024);
  nb_sync_p(7 + c);
#pragma unroll
  for (int h = 0; h < 2; h++) {
    tma_load_5d(dv + h * kChunkBytes, &tm.v6, bar, ch + 4 * h, hc.vj, hc.vc, tc.pr, h6);
    tma_load_5d(du + h * kChunkBytes, &tm.u8, bar, ch + 4 * h, hc.uj, h8, tc.pr, hc.uc);
    tma_load_5d(sbase + (2 * c + h) * kChunkBytes + 3 * 1024, &tm.v2, bar, ch + 4 * h, hc.vj, hc.vc, tc.pr, h2);
  }
  PROFS(15, 2, k * 4 + c);
}
__device__ __forceinline__ void gather_px(const __nv_bfloat16* __restrict__ x, uint32_t sbase, const TileCoord tc) {
  const int lane = threadIdx.x & 31, g = lane >> 3;
  uint32_t ro[4], co[4];
#pragma unroll
  for (int i = 0; i < 4; i++) {
    ro[i] = qpix(tc.pr, 8 * tc.I + 2 * i + (g & 1)) * (kW * kC * 2) + 16 * (lane & 7);
    co[i] = qpix(tc.pc, 8 * tc.J + 2 * i + (g >> 1)) * (kC * 2);
  }
  const uint32_t dst = sbase + kXOff + g * 128 + (((lane & 7) ^ g) << 4);
  if (lane < 8)
    asm volatile("cp.async.bulk.prefetch.L2.global [%0], 3456;" ::"l"(x + (qpix(tc.pr, 8 * tc.I + lane) * kW + 215 * tc.pc) * kC) : "memory");
  __syncwarp();
  keep_regs(ro);
  keep_regs(co);
  sched_fence();
  nb_sync_p(13);
  nb_sync_p(5);
#pragma unroll
  for (int i = 0; i < 16; i++) {
    const char* src = (const char*)x + (ro[i >> 2] + co[i & 3]);
#pragma unroll
    for (int q = 0; q < 3; q++)
      asm volatile("cp.async.cg.shared.global [%0], [%1], 16;" ::"r"((dst ^ ((i & 1) * 576)) + (i >> 1) * 1024 + q * 8192), "l"(src + 128 * q) : "memory");
  }
  asm volatile("cp.async.wait_all;" ::: "memory");
  fence_proxy_async();
  __syncwarp();
  if (lane < 3) mbar_arrive(bar_x(sbase + kBarOff, 1, lane));
  __syncwarp();
}

__global__ void __launch_bounds__(384, 1)
nat_kernel(const __nv_bfloat16* __restrict__ x, __nv_bfloat16* out, const __nv_bfloat16* __restrict__ wqkv,
           const __nv_bfloat16* __restrict__ wo, uint8_t* wimg, const uint32_t zero,
           const __grid_constant__ Maps tm, const __grid_constant__ TileTable tt) {
  extern __shared__ uint8_t smem_raw[];
  constexpr uint32_t sbase = 1024;
  constexpr uint32_t bars = sbase + kBarOff;
  const int tid = threadIdx.x;
  const uint32_t t_start = now_ns();
  if (tid == 0) GT(0);
  const int role = __shfl_sync(0xffffffffu, blockIdx.x + 8 * (tid & ~31), 0), wid = role >> 8;
  const bool w2cta = blockIdx.x - 128 < 3 && wqkv != nullptr;
  if (wid >= 8) {
    asm volatile("setmaxnreg.dec.sync.aligned.u32 24;");
    if (smem_u32(smem_raw) != sbase) __trap();
    const int c = wid & 3, lane = tid & 31;
    const int tile0 = blockIdx.x * kTilesPerCta, nt = num_tiles();
    uint32_t w2o = 0;
    if (c == 3) {
      if (elect_one()) wait_clock(t_start, NAT_TM);
      __syncwarp();
      asm volatile("prefetch.tensormap [%0];" ::"l"((uint64_t)tm.px) : "memory");
      asm volatile("prefetch.tensormap [%0];" ::"l"((uint64_t)&tm.v6) : "memory");
      asm volatile("prefetch.tensormap [%0];" ::"l"((uint64_t)&tm.v2) : "memory");
      asm volatile("prefetch.tensormap [%0];" ::"l"((uint64_t)(tm.px + (blockIdx.x < 112 ? 5 : 6))) : "memory");
      asm volatile("prefetch.tensormap [%0];" ::"l"((uint64_t)(tm.px + 7)) : "memory");
      if (nt < 6) {
        asm volatile("prefetch.tensormap [%0];" ::"l"((uint64_t)(tm.px + 1)) : "memory");
        asm volatile("prefetch.tensormap [%0];" ::"l"((uint64_t)(tm.px + 2)) : "memory");
        asm volatile("prefetch.tensormap [%0];" ::"l"((uint64_t)&tm.v14) : "memory");
        asm volatile("prefetch.tensormap [%0];" ::"l"((uint64_t)&tm.u8) : "memory");
      }
      __nanosleep(1600);
      asm volatile("bar.sync 4, 64;" ::: "memory");
      w2o = w2_offset();
      if (elect_one()) {
        mbar_arrive_expect_tx(bar_w2a(bars), kWChunk);
        mbar_arrive_expect_tx(bar_w2(bars), kWChunk);
        sleep_clock(t_start, NAT_TW2);
        bulk_load(sbase + kW2Off, wimg + w2o, kWChunk, bar_w2a(bars));
        mbar_wait(bar_xf(bars), 0);
        bulk_load(sbase + kW2Off + 2 * kWChunk, wimg + (w2o + 2 * kWChunk), kWChunk, bar_w2(bars));
      }
      __syncwarp();
      if (nt < 6) gather_px(x, sbase, decode_tile(tt, tile0 + 2));
      if (wqkv == nullptr) return;
      __nanosleep(2500);
      mbar_wait(bar_wok(bars), 0);
      if (lane == 0) asm volatile("red.relaxed.gpu.global.add.u32 [%0], 1;" ::"l"(g_flag) : "memory");
      if (blockIdx.x != kCtas - 1) return;
#pragma unroll
      for (int i = 0; i < 8; i++) asm volatile("st.shared.v4.u32 [%0], {%1,%1,%1,%1};" ::"r"(bars + 1024 + i * 512 + lane * 16), "r"(kEmpty) : "memory");
      fence_proxy_async();
      __syncwarp();
      if (elect_one()) {
#pragma unroll 1
        for (int i = 0; i < 36; i++) {
          if (i == 18) {
            uint32_t v, it = 0;
            do {
              __nanosleep(500);
              asm volatile("ld.relaxed.gpu.global.u32 %0, [%1];" : "=r"(v) : "l"(g_flag) : "memory");
            } while (v < gridDim.x && ++it < (1u << 18));
          }
          asm volatile("cp.async.bulk.global.shared::cta.bulk_group [%0], [%1], 4096;" ::"l"(
                           wimg + (i < 18 ? 3 * kWBytes - w2o + i * 4096 : (i - 18) * 4096)), "r"(bars + 1024) : "memory");
          asm volatile("cp.async.bulk.commit_group;" ::: "memory");
          asm volatile("cp.async.bulk.wait_group.read 1;" ::: "memory");
        }
        asm volatile("cp.async.bulk.wait_group 0;" ::: "memory");
        g_flag[0] = 0;
        g_flag[32] = w2o == kWBytes;
      }
      return;
    }
    if (!elect_one()) return;
    if (c == 0) {
      for (int i = 0; i < kNumBars; i++)
        if ((i != 0 && i != 10 || nt < 6) && (i != 21 || !w2cta)) mbar_init(bars + i * 8, i == 13 || i == 16 ? 4 : 1);
      asm volatile("st.shared.v2.u32 [%0], {%1,%1};" ::"r"(bars + 192), "r"(0) : "memory");
      asm volatile("fence.mbarrier_init.release.cluster;" ::: "memory");
      if (w2cta) asm volatile("bar.sync 10, 64;" ::: "memory");
      asm volatile("bar.arrive 0, 160;" ::: "memory");
      asm volatile("bar.arrive 14, 160;" ::: "memory");
      asm volatile("bar.arrive 13, 96;" ::: "memory");
      asm volatile("bar.arrive 4, 64;" ::: "memory");
      const TileCoord tc0 = decode_tile(tt, tile0);
      const HaloCols hc = halo_cols(tc0);
      const int h0 = halo_r0(tc0);
#pragma unroll
      for (int j = 0; j < 3; j++)
        if (j > 0 || nt < 6) mbar_arrive_expect_tx(bar_full(bars, 0, j), 2 * kChunkBytes);
      wait_clock(t_start, NAT_HP);
#pragma unroll
      for (int q = 8; q < 24 && !w2cta; q += 8) {
        tma_prefetch_5d(blockIdx.x < 112 ? &tm.v6 : &tm.v14, 24 * tc0.pc + q, hc.vj, hc.vc, tc0.pr, h0 + (tc0.up || blockIdx.x >= 112 ? 0 : 8));
        tma_prefetch_5d(&tm.u8, 24 * tc0.pc + q, hc.uj, h0 + (tc0.up ? 0 : 6), tc0.pr, hc.uc);
      }
#pragma unroll 1
      for (int i = nt < 6 ? 0 : 2; i < 6; i++) {
        if (i == 2) mbar_wait(bar_w1q(bars), 0);
        first_halo(tm, sbase, tc0, i);
      }
      mbar_arrive(bar_go(bars));
      w2o = w2_offset();
    } else {
      asm volatile("bar.sync 13, 96;" ::: "memory");
      if (c == 2) {
        if (wqkv != nullptr && blockIdx.x < 131) asm volatile("bar.sync 12, 64;" ::: "memory");
        const uint32_t c0 = clock();
        while ((uint32_t)clock() - c0 < NAT_TD && nt == 6) { }
        wait_clock(t_start, NAT_T0);
#pragma unroll
        for (int j = 0; j < 3; j++) {
          mbar_arrive_expect_tx(bar_w1c(bars, j), kWChunk);
          bulk_load(sbase + kW1Off + j * kWChunk, wimg + j * kWChunk, kWChunk, bar_w1c(bars, j));
        }
        mbar_arrive(bar_w1q(bars));
        GT(2);
      } else {
#pragma unroll 1
        for (int j = nt == 6; j < 2; j++) {
          const TileCoord tc = decode_tile(tt, tile0 + j);
          const int line = first_line(tc);
          if (j == 1) mbar_wait(bar_go(bars), 0);
          if (j == 0) GT(15);
#pragma unroll 1
          for (int q = 0; q < 3; q++) {
            load_px(tm, tt, sbase + x_chunk(j, q), bar_x(bars, j, q), line + q, tc.kind);
            if (j == 1 || q == 0) mbar_arrive_expect_tx(bar_x(bars, j, q), j ? 8192 : kWChunk);
          }
          if (j == 0) GT(16);
        }
        w2o = w2_offset();
        sleep_clock(t_start, NAT_TW2);
        mbar_wait(bar_xf(bars), 0);
      }
    }
#pragma unroll 1
    for (int k = 1; k < nt; k++) {
      const TileCoord tn = decode_tile(tt, tile0 + k + 1);
      const int line = first_line(tn);
      const bool more = k + 1 < nt && (k > 1 || nt == 6);
      if (c == 1) {
#pragma unroll
        for (int q = 0; q < 3; q++) {
          nb_sync_p(q == 0 ? 0 : q == 1 ? 14 : 6);
          bulk_load(sbase + x_chunk(k, q), wimg + (w2o + x_chunk(k, q) - kW2Off), 8192, bar_w2m(bars));
        }
        mbar_arrive_expect_tx(bar_w2m(bars), kWChunk);
      }
      if (c == 2) {
        if (k == 1) sleep_clock(t_start, NAT_TX2);
        else __nanosleep(NAT_PFD);
#pragma unroll 1
        for (int q = 0; q < 3 && more; q++) load_px(tm, tt, 0, 0, line + q, tn.kind);
      }
      if (c == 2 && (blockIdx.x >= 112 || k == 5)) {
        const TileCoord tc = decode_tile(tt, tile0 + k);
        const HaloCols hc = halo_cols(tc);
        const int h8 = halo_r0(tc) + (tc.up ? 0 : 6);
#pragma unroll 1
        for (int q = 0; q < 24; q += 8) {
          tma_prefetch_5d(&tm.v6, 24 * tc.pc + q, hc.vj, hc.vc, tc.pr, h8);
          tma_prefetch_5d(&tm.v2, 24 * tc.pc + q, hc.vj, hc.vc, tc.pr, h8 + 6);
          tma_prefetch_5d(&tm.u8, 24 * tc.pc + q, hc.uj, h8, tc.pr, hc.uc);
        }
      }
      load_halo(tm, sbase, bars, decode_tile(tt, tile0 + k), k, c);
      if (c == 0 && more) {
        if (nt < 6) mbar_wait(bar_x(bars, 1, 0), 1);
#pragma unroll
        for (int q = 0; q < 3; q++) {
          if (q < 2) nb_sync_p(q ? 5 : 13);
          load_px(tm, tt, sbase + x_chunk(k + 1, q), bar_x(bars, 1, q), line + q, tn.kind);
          if (q != 1) mbar_arrive_expect_tx(bar_x(bars, 1, q), 8192);
        }
        mbar_arrive_expect_tx(bar_x(bars, 1, 1), 8192);
        PROFS(16, 2, k * 4 + 3);
      }
      if (c == 0 && k >= 2) {
        const TileCoord tp = decode_tile(tt, tile0 + k - 2);
        const int lp = first_line(tp);
        nb_sync_p(10);
        __nanosleep(NAT_XW);
        store_px(tm, tt, sbase + out_slot(k, nt), lp, tp.kind);
        if (k + 1 < nt) {
          asm volatile("cp.async.bulk.wait_group.read 0;" ::: "memory");
          bulk_load(sbase + out_slot(k, nt), wimg + (w2o + out_slot(k, nt) - kW2Off), kWChunk, bar_w2(bars));
          mbar_arrive_expect_tx(bar_w2(bars), kWChunk);
        }
      }
    }
    asm volatile("cp.async.bulk.wait_group 0;" ::: "memory");
  } else {
    if ((role & 128) == 0) {
      if ((uint32_t)role - 1024u < 272u && wqkv != nullptr) {
        fold_w1(min(2 * (role & 127) + (wid & 1), (role & 127) + 16), wqkv, wimg);
        if (wid == 4) asm volatile("bar.arrive 12, 64;" ::: "memory");
        if (tid == 128) GT(7);
      }
      sched_fence();
      if (wid == 1 && elect_one()) {
        const TileCoord tc = decode_tile(tt, blockIdx.x * kTilesPerCta);
        mbar_init(bar_x(bars, 0, 0), 1);
        asm volatile("fence.mbarrier_init.release.cluster;" ::: "memory");
        mbar_arrive_expect_tx(bar_x(bars, 0, 0), kWChunk);
        GT(15);
#pragma unroll 1
        for (int q = 0; q < 3; q++) load_px(tm, tt, sbase + x_chunk(0, q), bar_x(bars, 0, 0), first_line(tc) + q, tc.kind);
        GT(16);
      }
      __syncwarp();
      sched_fence();
      if (wid == 2 && elect_one()) {
        const TileCoord tc = decode_tile(tt, blockIdx.x * kTilesPerCta);
        mbar_init(bar_full(bars, 0, 0), 1);
        asm volatile("fence.mbarrier_init.release.cluster;" ::: "memory");
        mbar_arrive_expect_tx(bar_full(bars, 0, 0), 2 * kChunkBytes);
        asm volatile("prefetch.tensormap [%0];" ::"l"((uint64_t)&tm.u8) : "memory");
        GT(17);
        first_halo(tm, sbase, tc, 0);
        first_halo(tm, sbase, tc, 1);
      }
      __syncwarp();
    }
    sched_fence();
    {
      if (blockIdx.x >= 128 && wqkv != nullptr && (wid | 2) == 2 && elect_one())
        asm volatile("cp.async.bulk.prefetch.L2.global [%0], %1;" ::"l"(wid ? wo + (blockIdx.x & 3) * 48 * 192 : wqkv + (blockIdx.x & 3) * 48 * 576),
                     "r"(wid ? 48 * 384 : 48 * 1152) : "memory");
      __syncwarp();
      if (w2cta) {
        const int q = blockIdx.x & 3, h = wid >> 2;
        uint32_t w2o = 0;
        if (wid == 1 && elect_one()) {
          asm volatile("prefetch.tensormap [%0];" ::"l"((uint64_t)&tm.wo) : "memory");
          mbar_init(bar_raw(bars, 0), 1);
          mbar_init(bar_raw(bars, 1), 1);
          asm volatile("fence.mbarrier_init.release.cluster;" ::: "memory");
#pragma unroll
          for (int j = 0; j < 3; j++)
            asm volatile("cp.async.bulk.tensor.3d.shared::cluster.global.tile.mbarrier::complete_tx::bytes [%0], [%1, {%3, %4, %5}], [%2];" ::"r"(
                             j ? sbase + kW2Off + (j - 1) * (kWBytes / 2) : sbase),
                         "l"((uint64_t)(j ? &tm.wo : &tm.wv)), "r"(bar_raw(bars, j >> 1)), "r"(0), "r"(j ? 0 : 64 * q), "r"(j ? 3 * j - 3 : 6) : "memory");
          mbar_arrive_expect_tx(bar_raw(bars, 0), kWChunk + kWBytes / 2);
          mbar_arrive_expect_tx(bar_raw(bars, 1), kWBytes / 2);
          w2o = w2_offset();
        }
        __syncwarp();
#pragma unroll 1
        for (int r = 1 - h;; r++) {
          if (r > 0) asm volatile("bar.sync 11, 256;" ::: "memory");
          if (r == 2) break;
          if (r > 0) {
            mbar_wait(bar_raw(bars, 0), 0);
            mbar_wait(bar_raw(bars, h), 0);
          }
          if (tid == 0) GT(7);
          float acc[48];
          const uint64_t db = make_desc(sbase + kW2Off + h * (kWBytes / 2), kWChunk / 2, 512, 2);
          wg_fence();
          wg_m96tz<0, 48>(acc, make_desc(sbase, 16, 1024), db, 0);
#pragma unroll
          for (int s = 1; s < 12; s++) wg_m96t<0, 48>(acc, make_desc(sbase + (s >> 2) * 8192 + (s & 3) * 32, 16, 1024), db + s * 64, 1);
          wg_commit();
          wg_wait<0>();
          fence_regs(acc);
          if (tid == 0) GT(19);
          const int m = (tid >> 3) & 3;
#pragma unroll
          for (int j = 0; j < 12; j += 2) {
            const int n = g2_inv(8 * (j + (m >> 1)) + (tid & 7));
            asm volatile("stmatrix.sync.aligned.m8n8.x4.trans.shared.b16 [%0], {%1,%2,%3,%4};" ::"r"(
                             sbase + kW1Off + h * (kWChunk / 2) + n * 128 + (((2 * (wid & 3) + (m & 1)) ^ (n & 7)) << 4)),
                         "r"(pack_bf16(acc[4 * j], acc[4 * j + 1])), "r"(pack_bf16(acc[4 * j + 2], acc[4 * j + 3])),
                         "r"(pack_bf16(acc[4 * j + 4], acc[4 * j + 5])), "r"(pack_bf16(acc[4 * j + 6], acc[4 * j + 7])) : "memory");
          }
          fence_proxy_async();
        }
        if (tid == 0) GT(18);
        if (wid == 1) {
          if (elect_one()) {
#pragma unroll
            for (int i = 0; i < 2; i++)
              asm volatile("cp.async.bulk.global.shared::cta.bulk_group [%0], [%1], %2;" ::"l"(wimg + (w2o + w2piece(i, q) * (kWChunk / 2))),
                           "r"(sbase + kW1Off + i * (kWChunk / 2)), "r"(kWChunk / 2) : "memory");
            asm volatile("cp.async.bulk.commit_group;" ::: "memory");
          }
          __syncwarp();
          asm volatile("bar.arrive 10, 64;" ::: "memory");
          if (elect_one()) asm volatile("cp.async.bulk.wait_group.read 0;" ::: "memory");
          if (tid == 32) GT(31);
          __syncwarp();
          asm volatile("bar.arrive 12, 64;" ::: "memory");
        }
      }
    }
    __syncwarp();
    if (wid < 4) asm volatile("bar.sync 0, 160;" ::: "memory");
    else asm volatile("bar.sync 14, 160;" ::: "memory");
    asm volatile("setmaxnreg.inc.sync.aligned.u32 240;");
    consumer(wid >> 2, out, wimg, sbase, zero, tm, tt);
  }
}

}

typedef CUresult (*PFN_encodeTiled)(CUtensorMap*, CUtensorMapDataType, cuuint32_t, void*, const cuuint64_t*,
                                    const cuuint64_t*, const cuuint32_t*, const cuuint32_t*, CUtensorMapInterleave,
                                    CUtensorMapSwizzle, CUtensorMapL2promotion, CUtensorMapFloatOOBfill);

extern "C" void kernel_launch(void* const* d_in, const int* in_sizes, int n_in, void* d_out, int out_size) {
  const __nv_bfloat16* x = (const __nv_bfloat16*)d_in[0];
  const __nv_bfloat16* wqkv = (const __nv_bfloat16*)d_in[1];
  const __nv_bfloat16* wo = (const __nv_bfloat16*)d_in[2];
  __nv_bfloat16* out = (__nv_bfloat16*)d_out;

  static PFN_encodeTiled encode = nullptr;
  static int num_sms = 0;
  static uint8_t* wimg = nullptr;
  if (!encode) {
    void* fn = nullptr;
    cudaDriverEntryPointQueryResult qres;
    cudaGetDriverEntryPoint("cuTensorMapEncodeTiled", &fn, cudaEnableDefault, &qres);
    encode = (PFN_encodeTiled)fn;
    cudaFuncSetAttribute(nat::nat_kernel, cudaFuncAttributeMaxDynamicSharedMemorySize, nat::kSmemBytes);
    cudaGetSymbolAddress((void**)&wimg, nat::g_wimg32);
    int dev = 0;
    cudaGetDevice(&dev);
    cudaDeviceGetAttribute(&num_sms, cudaDevAttrMultiProcessorCount, dev);
  }
  nat::Maps tm;
  cuuint32_t estr[5] = {1, 1, 1, 1, 1};
  {
    cuuint64_t vdim[5] = {48, 2, 105, 2, 112}, udim[5] = {48, 2, 112, 2, 105};
    cuuint64_t vstr[4] = {7 * 768, 768, 224 * 384, 2 * 224 * 384}, ustr[4] = {7 * 768, 2 * 224 * 384, 224 * 384, 768};
    CUtensorMap* maps[4] = {&tm.v6, &tm.v2, &tm.v14, &tm.u8};
    for (int i = 0; i < 4; i++) {
      cuuint32_t box[5] = {4, 2, i < 3 ? 4u : 8u, 1, i == 0 ? 6u : i == 1 ? 2u : i == 2 ? 14u : 3u};
      encode(maps[i], CU_TENSOR_MAP_DATA_TYPE_UINT32, 5, (void*)x, i < 3 ? vdim : udim, i < 3 ? vstr : ustr, box, estr,
             CU_TENSOR_MAP_INTERLEAVE_16B, CU_TENSOR_MAP_SWIZZLE_128B, CU_TENSOR_MAP_L2_PROMOTION_L2_128B, CU_TENSOR_MAP_FLOAT_OOB_FILL_NONE);
    }
  }
  for (int i = 0; i < 8; i++) {
    const cuuint32_t row = 224 * 384;
    const cuuint32_t shape[8][6] = {{2, 8, 4, 2 * row, 768, 4 * row}, {2, 8, 3, row, 768, 2 * row},     {2, 8, 1, 2 * row, 768, 4 * row},
                                    {8, 2, 3, 2 * row, 4 * 384, 384}, {8, 2, 1, 2 * row, 5 * 384, 384}, {4, 2, 3, 4 * row, 2 * row, 128},
                                    {4, 2, 3, 768, row, 128},         {4, 2, 3, 768, 2 * row, 128}};
    const cuuint32_t* sh = shape[i];
    cuuint64_t dim[5] = {64, sh[0], sh[1], sh[2], 224 * 224 * 3};
    cuuint64_t str[4] = {sh[3], sh[4], sh[5], 128};
    cuuint32_t box[5] = {64, sh[0], sh[1], sh[2], 1};
    encode(tm.px + i, CU_TENSOR_MAP_DATA_TYPE_BFLOAT16, 5, i < 5 ? (void*)x : (void*)out, dim, str, box, estr, CU_TENSOR_MAP_INTERLEAVE_NONE,
           CU_TENSOR_MAP_SWIZZLE_128B, i < 5 ? CU_TENSOR_MAP_L2_PROMOTION_L2_128B : CU_TENSOR_MAP_L2_PROMOTION_NONE,
           CU_TENSOR_MAP_FLOAT_OOB_FILL_NONE);
  }
  for (int i = 0; i < 2; i++) {
    cuuint64_t dim[3] = {i ? 32u : 64u, 192, i ? 6u : 9u}, str[2] = {i ? 384u : 1152u, i ? 64u : 128u};
    cuuint32_t box[3] = {i ? 32u : 64u, i ? 192u : 64u, 3};
    encode(i ? &tm.wo : &tm.wv, CU_TENSOR_MAP_DATA_TYPE_BFLOAT16, 3, i ? (void*)wo : (void*)wqkv, dim, str, box, estr,
           CU_TENSOR_MAP_INTERLEAVE_NONE, i ? CU_TENSOR_MAP_SWIZZLE_64B : CU_TENSOR_MAP_SWIZZLE_128B, CU_TENSOR_MAP_L2_PROMOTION_L2_256B,
           CU_TENSOR_MAP_FLOAT_OOB_FILL_NONE);
  }
  nat::TileTable tt;
  nat::make_tiles(tt);
  const int grid = nat::kCtas;
  if (num_sms >= grid) {
    nat::nat_kernel<<<grid, 384, nat::kSmemBytes>>>(x, out, wqkv, wo, wimg, 0u, tm, tt);
  } else {
    nat::fold_kernel<<<27, 256>>>(wqkv, wo, wimg);
    nat::nat_kernel<<<grid, 384, nat::kSmemBytes>>>(x, out, nullptr, nullptr, wimg, 0u, tm, tt);
  }
}
```

```cpp
#include <cuda_runtime.h>
#include <cuda_bf16.h>
#include <cuda.h>
#include <stdint.h>

#define NAT_TM 1300
#define NAT_HP 1800
#define NAT_T0 2130
#define NAT_TD 1250
#define NAT_TX2 3800
#define NAT_TW2 4600
#define NAT_PFD 300
#define NAT_XW 200
#define NAT_PK 3
namespace nat {

constexpr int kW = 224, kC = 192;
constexpr int kCtas = 132;
constexpr int kTilesPerCta = 6;
constexpr float kAlpha = 0.07216878364870322f * 1.4426950408889634f;
constexpr uint32_t kChunkBytes = 13 * 1024;
constexpr uint32_t kWChunk = 192 * 128;
constexpr uint32_t kWBytes = 3 * kWChunk;
constexpr uint32_t kW1Off = 6 * kChunkBytes;
constexpr uint32_t kW2Off = kW1Off + kWBytes;
constexpr uint32_t kXOff = kW2Off + kWChunk;
constexpr uint32_t kBarOff = kW2Off + kWBytes;
constexpr uint32_t kProfOff = kBarOff + 208;
constexpr uint32_t kSmemBytes = kBarOff + 1024 + 4096;

static_assert(kW1Off % 1024 == 0 && kW2Off % 1024 == 0 && kChunkBytes % 1024 == 0, "swizzle alignment");
static_assert(kSmemBytes <= 232448, "smem");

constexpr uint32_t kEmpty = 0xFFFFFFFFu;
#define NAT_R8(v) v, v, v, v, v, v, v, v
#define NAT_R2K(v) NAT_R8(NAT_R8(NAT_R8(v))), NAT_R8(NAT_R8(NAT_R8(v))), NAT_R8(NAT_R8(NAT_R8(v))), NAT_R8(NAT_R8(NAT_R8(v)))
#define NAT_IMG NAT_R8(NAT_R2K(kEmpty)), NAT_R2K(kEmpty)
__device__ __align__(1024) uint32_t g_wimg32[3 * kWBytes / 4] = {NAT_IMG, NAT_IMG, NAT_IMG};
static_assert(kWBytes / 4 == 9 * 2048, "initialiser");
__device__ __align__(128) uint32_t g_flag[64];
__device__ __forceinline__ uint32_t w2_offset() {
  uint32_t v;
  asm volatile("ld.relaxed.gpu.global.u32 %0, [%1];" : "=r"(v) : "l"(g_flag + 32) : "memory");
  return (1 + v) * kWBytes;
}

#define PROFS(id, wgid, slotid) do { } while (0)
#define PROF(wgid, slotid) do { } while (0)
#define PROF_DUMP(wgid) do { } while (0)

#define GT(slotid) do { } while (0)
#define GT_DUMP() do { } while (0)

__device__ __forceinline__ uint32_t smem_u32(const void* p) { return (uint32_t)__cvta_generic_to_shared(p); }

__device__ __forceinline__ void mbar_init(uint32_t bar, uint32_t count) {
  asm volatile("mbarrier.init.shared::cta.b64 [%0], %1;" ::"r"(bar), "r"(count) : "memory");
}
__device__ __forceinline__ void mbar_arrive(uint32_t bar) {
  asm volatile("mbarrier.arrive.shared::cta.b64 _, [%0];" ::"r"(bar) : "memory");
}
__device__ __forceinline__ void mbar_arrive_expect_tx(uint32_t bar, uint32_t bytes) {
  asm volatile("mbarrier.arrive.expect_tx.shared::cta.b64 _, [%0], %1;" ::"r"(bar), "r"(bytes) : "memory");
}
__device__ __forceinline__ void mbar_wait(uint32_t bar, uint32_t parity) {
  uint32_t ok;
  uint32_t it = 0;
  do {
    asm volatile(
        "{\n.reg .pred p;\n"
        "mbarrier.try_wait.parity.shared::cta.b64 p, [%1], %2;\n"
        "selp.u32 %0, 1, 0, p;\n}\n"
        : "=r"(ok)
        : "r"(bar), "r"(parity)
        : "memory");
    if (++it > (1u << 24)) break;
  } while (!ok);
}
__device__ __forceinline__ uint32_t mbar_test(uint32_t bar, uint32_t parity) {
  uint32_t ok;
  asm volatile("{\n.reg .pred p;\nmbarrier.test_wait.parity.shared::cta.b64 p, [%1], %2;\nselp.u32 %0, 1, 0, p;\n}\n"
               : "=r"(ok) : "r"(bar), "r"(parity) : "memory");
  return ok;
}
__device__ __forceinline__ void mbar_wait_if(uint32_t ok, uint32_t bar, uint32_t parity) {
  if (!__all_sync(0xffffffffu, ok)) mbar_wait(bar, parity);
}
__device__ __forceinline__ bool elect_one() {
  uint32_t r;
  asm volatile("{\n.reg .pred p;\nelect.sync _|p, 0xffffffff;\nselp.u32 %0, 1, 0, p;\n}\n" : "=r"(r));
  return r != 0;
}
__device__ __forceinline__ void nb_arrive(int id) { asm volatile("bar.arrive %0, 256;" ::"r"(id) : "memory"); }
__device__ __forceinline__ void nb_sync(int id) { asm volatile("bar.sync %0, 256;" ::"r"(id) : "memory"); }
__device__ __forceinline__ void nb_arrive_p(int id) { asm volatile("bar.arrive %0, 160;" ::"r"(id) : "memory"); }
__device__ __forceinline__ void nb_sync_p(int id) { asm volatile("bar.sync %0, 160;" ::"r"(id) : "memory"); }
__device__ __forceinline__ void fence_proxy_async() { asm volatile("fence.proxy.async.shared::cta;" ::: "memory"); }

__device__ __forceinline__ void tma_load_5d(uint32_t dst, const CUtensorMap* map, uint32_t bar, int c0, int c1, int c2,
                                            int c3, int c4) {
  asm volatile(
      "cp.async.bulk.tensor.5d.shared::cluster.global.tile.mbarrier::complete_tx::bytes "
      "[%0], [%1, {%3, %4, %5, %6, %7}], [%2];"
      ::"r"(dst), "l"((uint64_t)map), "r"(bar), "r"(c0), "r"(c1), "r"(c2), "r"(c3), "r"(c4)
      : "memory");
}
__device__ __forceinline__ void bulk_load(uint32_t dst, const void* src, uint32_t bytes, uint32_t bar) {
  asm volatile("cp.async.bulk.shared::cluster.global.mbarrier::complete_tx::bytes [%0], [%1], %2, [%3];"
               ::"r"(dst), "l"((uint64_t)src), "r"(bytes), "r"(bar)
               : "memory");
}

__device__ __forceinline__ void wg_fence() { asm volatile("wgmma.fence.sync.aligned;" ::: "memory"); }
__device__ __forceinline__ void wg_commit() { asm volatile("wgmma.commit_group.sync.aligned;" ::: "memory"); }
template <int N>
__device__ __forceinline__ void wg_wait() { asm volatile("wgmma.wait_group.sync.aligned %0;" ::"n"(N) : "memory"); }

template <int N>
__device__ __forceinline__ void fence_regs(float (&d)[N]) {
#pragma unroll
  for (int i = 0; i < N; i++) asm volatile("" : "+f"(d[i])::"memory");
}
template <int N>
__device__ __forceinline__ void keep_regs(uint32_t (&d)[N]) {
#pragma unroll
  for (int i = 0; i < N; i++) asm volatile("" : "+r"(d[i])::"memory");
}

__device__ __forceinline__ uint32_t pack_bf16(float lo, float hi) {
  uint32_t d;
  asm("cvt.rn.bf16x2.f32 %0, %1, %2;" : "=r"(d) : "f"(hi), "f"(lo));
  return d;
}
__device__ __forceinline__ float ex2(float x) {
  float y;
  asm("ex2.approx.ftz.f32 %0, %1;" : "=f"(y) : "f"(x));
  return y;
}
__device__ __forceinline__ float rcp_approx(float x) {
  float y;
  asm("rcp.approx.ftz.f32 %0, %1;" : "=f"(y) : "f"(x));
  return y;
}
__device__ __forceinline__ uint4 ldg128_nc(const void* p) {
  uint4 v;
  asm volatile("ld.global.nc.v4.u32 {%0,%1,%2,%3}, [%4];" : "=r"(v.x), "=r"(v.y), "=r"(v.z), "=r"(v.w) : "l"(p));
  return v;
}

__device__ __forceinline__ long long clk64() {
  long long c;
  asm volatile("mov.u64 %0, %clock64;" : "=l"(c)::"memory");
  return c;
}
__device__ __forceinline__ void sched_fence() { while (clk64() < 0) { } }

__device__ __forceinline__ uint64_t make_desc(uint32_t addr, uint32_t lbo, uint32_t sbo, uint32_t mode = 1) {
  return (uint64_t)((addr & 0x3FFFF) >> 4) | ((uint64_t)(lbo >> 4) << 16) | ((uint64_t)(sbo >> 4) << 32) |
         ((uint64_t)mode << 62);
}

template <int OFF, int NN>
__device__ __forceinline__ void wg_m192(float (&d)[NN], uint64_t desc_a, uint64_t desc_b, int scale_d) {
  asm volatile(
      "{\n.reg .pred p;\nsetp.ne.b32 p, %98, 0;\n"
      "wgmma.mma_async.sync.aligned.m64n192k16.f32.bf16.bf16 "
      "{%0,%1,%2,%3,%4,%5,%6,%7,%8,%9,%10,%11,%12,%13,%14,%15,"
      "%16,%17,%18,%19,%20,%21,%22,%23,%24,%25,%26,%27,%28,%29,%30,%31,"
      "%32,%33,%34,%35,%36,%37,%38,%39,%40,%41,%42,%43,%44,%45,%46,%47,"
      "%48,%49,%50,%51,%52,%53,%54,%55,%56,%57,%58,%59,%60,%61,%62,%63,"
      "%64,%65,%66,%67,%68,%69,%70,%71,%72,%73,%74,%75,%76,%77,%78,%79,"
      "%80,%81,%82,%83,%84,%85,%86,%87,%88,%89,%90,%91,%92,%93,%94,%95}, "
      "%96, %97, p, 1, 1, 0, 0;\n}\n"
      : "+f"(d[OFF + 0]), "+f"(d[OFF + 1]), "+f"(d[OFF + 2]), "+f"(d[OFF + 3]), "+f"(d[OFF + 4]), "+f"(d[OFF + 5]),
        "+f"(d[OFF + 6]), "+f"(d[OFF + 7]), "+f"(d[OFF + 8]), "+f"(d[OFF + 9]), "+f"(d[OFF + 10]), "+f"(d[OFF + 11]),
        "+f"(d[OFF + 12]), "+f"(d[OFF + 13]), "+f"(d[OFF + 14]), "+f"(d[OFF + 15]), "+f"(d[OFF + 16]), "+f"(d[OFF + 17]),
        "+f"(d[OFF + 18]), "+f"(d[OFF + 19]), "+f"(d[OFF + 20]), "+f"(d[OFF + 21]), "+f"(d[OFF + 22]), "+f"(d[OFF + 23]),
        "+f"(d[OFF + 24]), "+f"(d[OFF + 25]), "+f"(d[OFF + 26]), "+f"(d[OFF + 27]), "+f"(d[OFF + 28]), "+f"(d[OFF + 29]),
        "+f"(d[OFF + 30]), "+f"(d[OFF + 31]), "+f"(d[OFF + 32]), "+f"(d[OFF + 33]), "+f"(d[OFF + 34]), "+f"(d[OFF + 35]),
        "+f"(d[OFF + 36]), "+f"(d[OFF + 37]), "+f"(d[OFF + 38]), "+f"(d[OFF + 39]), "+f"(d[OFF + 40]), "+f"(d[OFF + 41]),
        "+f"(d[OFF + 42]), "+f"(d[OFF + 43]), "+f"(d[OFF + 44]), "+f"(d[OFF + 45]), "+f"(d[OFF + 46]), "+f"(d[OFF + 47]),
        "+f"(d[OFF + 48]), "+f"(d[OFF + 49]), "+f"(d[OFF + 50]), "+f"(d[OFF + 51]), "+f"(d[OFF + 52]), "+f"(d[OFF + 53]),
        "+f"(d[OFF + 54]), "+f"(d[OFF + 55]), "+f"(d[OFF + 56]), "+f"(d[OFF + 57]), "+f"(d[OFF + 58]), "+f"(d[OFF + 59]),
        "+f"(d[OFF + 60]), "+f"(d[OFF + 61]), "+f"(d[OFF + 62]), "+f"(d[OFF + 63]), "+f"(d[OFF + 64]), "+f"(d[OFF + 65]),
        "+f"(d[OFF + 66]), "+f"(d[OFF + 67]), "+f"(d[OFF + 68]), "+f"(d[OFF + 69]), "+f"(d[OFF + 70]), "+f"(d[OFF + 71]),
        "+f"(d[OFF + 72]), "+f"(d[OFF + 73]), "+f"(d[OFF + 74]), "+f"(d[OFF + 75]), "+f"(d[OFF + 76]), "+f"(d[OFF + 77]),
        "+f"(d[OFF + 78]), "+f"(d[OFF + 79]), "+f"(d[OFF + 80]), "+f"(d[OFF + 81]), "+f"(d[OFF + 82]), "+f"(d[OFF + 83]),
        "+f"(d[OFF + 84]), "+f"(d[OFF + 85]), "+f"(d[OFF + 86]), "+f"(d[OFF + 87]), "+f"(d[OFF + 88]), "+f"(d[OFF + 89]),
        "+f"(d[OFF + 90]), "+f"(d[OFF + 91]), "+f"(d[OFF + 92]), "+f"(d[OFF + 93]), "+f"(d[OFF + 94]), "+f"(d[OFF + 95])
      : "l"(desc_a), "l"(desc_b), "r"(scale_d));
}

template <int OFF, int NN>
__device__ __forceinline__ void wg_m192z(float (&d)[NN], uint64_t desc_a, uint64_t desc_b, int scale_d) {
  asm volatile(
      "{\n.reg .pred p;\nsetp.ne.b32 p, %98, 0;\n"
      "wgmma.mma_async.sync.aligned.m64n192k16.f32.bf16.bf16 "
      "{%0,%1,%2,%3,%4,%5,%6,%7,%8,%9,%10,%11,%12,%13,%14,%15,"
      "%16,%17,%18,%19,%20,%21,%22,%23,%24,%25,%26,%27,%28,%29,%30,%31,"
      "%32,%33,%34,%35,%36,%37,%38,%39,%40,%41,%42,%43,%44,%45,%46,%47,"
      "%48,%49,%50,%51,%52,%53,%54,%55,%56,%57,%58,%59,%60,%61,%62,%63,"
      "%64,%65,%66,%67,%68,%69,%70,%71,%72,%73,%74,%75,%76,%77,%78,%79,"
      "%80,%81,%82,%83,%84,%85,%86,%87,%88,%89,%90,%91,%92,%93,%94,%95}, "
      "%96, %97, p, 1, 1, 0, 0;\n}\n"
      : "=f"(d[OFF + 0]), "=f"(d[OFF + 1]), "=f"(d[OFF + 2]), "=f"(d[OFF + 3]), "=f"(d[OFF + 4]), "=f"(d[OFF + 5]),
        "=f"(d[OFF + 6]), "=f"(d[OFF + 7]), "=f"(d[OFF + 8]), "=f"(d[OFF + 9]), "=f"(d[OFF + 10]), "=f"(d[OFF + 11]),
        "=f"(d[OFF + 12]), "=f"(d[OFF + 13]), "=f"(d[OFF + 14]), "=f"(d[OFF + 15]), "=f"(d[OFF + 16]), "=f"(d[OFF + 17]),
        "=f"(d[OFF + 18]), "=f"(d[OFF + 19]), "=f"(d[OFF + 20]), "=f"(d[OFF + 21]), "=f"(d[OFF + 22]), "=f"(d[OFF + 23]),
        "=f"(d[OFF + 24]), "=f"(d[OFF + 25]), "=f"(d[OFF + 26]), "=f"(d[OFF + 27]), "=f"(d[OFF + 28]), "=f"(d[OFF + 29]),
        "=f"(d[OFF + 30]), "=f"(d[OFF + 31]), "=f"(d[OFF + 32]), "=f"(d[OFF + 33]), "=f"(d[OFF + 34]), "=f"(d[OFF + 35]),
        "=f"(d[OFF + 36]), "=f"(d[OFF + 37]), "=f"(d[OFF + 38]), "=f"(d[OFF + 39]), "=f"(d[OFF + 40]), "=f"(d[OFF + 41]),
        "=f"(d[OFF + 42]), "=f"(d[OFF + 43]), "=f"(d[OFF + 44]), "=f"(d[OFF + 45]), "=f"(d[OFF + 46]), "=f"(d[OFF + 47]),
        "=f"(d[OFF + 48]), "=f"(d[OFF + 49]), "=f"(d[OFF + 50]), "=f"(d[OFF + 51]), "=f"(d[OFF + 52]), "=f"(d[OFF + 53]),
        "=f"(d[OFF + 54]), "=f"(d[OFF + 55]), "=f"(d[OFF + 56]), "=f"(d[OFF + 57]), "=f"(d[OFF + 58]), "=f"(d[OFF + 59]),
        "=f"(d[OFF + 60]), "=f"(d[OFF + 61]), "=f"(d[OFF + 62]), "=f"(d[OFF + 63]), "=f"(d[OFF + 64]), "=f"(d[OFF + 65]),
        "=f"(d[OFF + 66]), "=f"(d[OFF + 67]), "=f"(d[OFF + 68]), "=f"(d[OFF + 69]), "=f"(d[OFF + 70]), "=f"(d[OFF + 71]),
        "=f"(d[OFF + 72]), "=f"(d[OFF + 73]), "=f"(d[OFF + 74]), "=f"(d[OFF + 75]), "=f"(d[OFF + 76]), "=f"(d[OFF + 77]),
        "=f"(d[OFF + 78]), "=f"(d[OFF + 79]), "=f"(d[OFF + 80]), "=f"(d[OFF + 81]), "=f"(d[OFF + 82]), "=f"(d[OFF + 83]),
        "=f"(d[OFF + 84]), "=f"(d[OFF + 85]), "=f"(d[OFF + 86]), "=f"(d[OFF + 87]), "=f"(d[OFF + 88]), "=f"(d[OFF + 89]),
        "=f"(d[OFF + 90]), "=f"(d[OFF + 91]), "=f"(d[OFF + 92]), "=f"(d[OFF + 93]), "=f"(d[OFF + 94]), "=f"(d[OFF + 95])
      : "l"(desc_a), "l"(desc_b), "r"(scale_d));
}

template <int OFF, int NN>
__device__ __forceinline__ void wg_m96t(float (&d)[NN], uint64_t desc_a, uint64_t desc_b, int scale_d) {
  asm volatile(
      "{\n.reg .pred p;\nsetp.ne.b32 p, %50, 0;\n"
      "wgmma.mma_async.sync.aligned.m64n96k16.f32.bf16.bf16 "
      "{%0,%1,%2,%3,%4,%5,%6,%7,%8,%9,%10,%11,%12,%13,%14,%15,"
      "%16,%17,%18,%19,%20,%21,%22,%23,%24,%25,%26,%27,%28,%29,%30,%31,"
      "%32,%33,%34,%35,%36,%37,%38,%39,%40,%41,%42,%43,%44,%45,%46,%47}, "
      "%48, %49, p, 1, 1, 0, 1;\n}\n"
      : "+f"(d[OFF + 0]), "+f"(d[OFF + 1]), "+f"(d[OFF + 2]), "+f"(d[OFF + 3]), "+f"(d[OFF + 4]), "+f"(d[OFF + 5]),
        "+f"(d[OFF + 6]), "+f"(d[OFF + 7]), "+f"(d[OFF + 8]), "+f"(d[OFF + 9]), "+f"(d[OFF + 10]), "+f"(d[OFF + 11]),
        "+f"(d[OFF + 12]), "+f"(d[OFF + 13]), "+f"(d[OFF + 14]), "+f"(d[OFF + 15]), "+f"(d[OFF + 16]), "+f"(d[OFF + 17]),
        "+f"(d[OFF + 18]), "+f"(d[OFF + 19]), "+f"(d[OFF + 20]), "+f"(d[OFF + 21]), "+f"(d[OFF + 22]), "+f"(d[OFF + 23]),
        "+f"(d[OFF + 24]), "+f"(d[OFF + 25]), "+f"(d[OFF + 26]), "+f"(d[OFF + 27]), "+f"(d[OFF + 28]), "+f"(d[OFF + 29]),
        "+f"(d[OFF + 30]), "+f"(d[OFF + 31]), "+f"(d[OFF + 32]), "+f"(d[OFF + 33]), "+f"(d[OFF + 34]), "+f"(d[OFF + 35]),
        "+f"(d[OFF + 36]), "+f"(d[OFF + 37]), "+f"(d[OFF + 38]), "+f"(d[OFF + 39]), "+f"(d[OFF + 40]), "+f"(d[OFF + 41]),
        "+f"(d[OFF + 42]), "+f"(d[OFF + 43]), "+f"(d[OFF + 44]), "+f"(d[OFF + 45]), "+f"(d[OFF + 46]), "+f"(d[OFF + 47])
      : "l"(desc_a), "l"(desc_b), "r"(scale_d));
}

template <int OFF, int NN>
__device__ __forceinline__ void wg_m96tz(float (&d)[NN], uint64_t desc_a, uint64_t desc_b, int scale_d) {
  asm volatile(
      "{\n.reg .pred p;\nsetp.ne.b32 p, %50, 0;\n"
      "wgmma.mma_async.sync.aligned.m64n96k16.f32.bf16.bf16 "
      "{%0,%1,%2,%3,%4,%5,%6,%7,%8,%9,%10,%11,%12,%13,%14,%15,"
      "%16,%17,%18,%19,%20,%21,%22,%23,%24,%25,%26,%27,%28,%29,%30,%31,"
      "%32,%33,%34,%35,%36,%37,%38,%39,%40,%41,%42,%43,%44,%45,%46,%47}, "
      "%48, %49, p, 1, 1, 0, 1;\n}\n"
      : "=f"(d[OFF + 0]), "=f"(d[OFF + 1]), "=f"(d[OFF + 2]), "=f"(d[OFF + 3]), "=f"(d[OFF + 4]), "=f"(d[OFF + 5]),
        "=f"(d[OFF + 6]), "=f"(d[OFF + 7]), "=f"(d[OFF + 8]), "=f"(d[OFF + 9]), "=f"(d[OFF + 10]), "=f"(d[OFF + 11]),
        "=f"(d[OFF + 12]), "=f"(d[OFF + 13]), "=f"(d[OFF + 14]), "=f"(d[OFF + 15]), "=f"(d[OFF + 16]), "=f"(d[OFF + 17]),
        "=f"(d[OFF + 18]), "=f"(d[OFF + 19]), "=f"(d[OFF + 20]), "=f"(d[OFF + 21]), "=f"(d[OFF + 22]), "=f"(d[OFF + 23]),
        "=f"(d[OFF + 24]), "=f"(d[OFF + 25]), "=f"(d[OFF + 26]), "=f"(d[OFF + 27]), "=f"(d[OFF + 28]), "=f"(d[OFF + 29]),
        "=f"(d[OFF + 30]), "=f"(d[OFF + 31]), "=f"(d[OFF + 32]), "=f"(d[OFF + 33]), "=f"(d[OFF + 34]), "=f"(d[OFF + 35]),
        "=f"(d[OFF + 36]), "=f"(d[OFF + 37]), "=f"(d[OFF + 38]), "=f"(d[OFF + 39]), "=f"(d[OFF + 40]), "=f"(d[OFF + 41]),
        "=f"(d[OFF + 42]), "=f"(d[OFF + 43]), "=f"(d[OFF + 44]), "=f"(d[OFF + 45]), "=f"(d[OFF + 46]), "=f"(d[OFF + 47])
      : "l"(desc_a), "l"(desc_b), "r"(scale_d));
}

template <int OFF, int NN>
__device__ __forceinline__ void wg_d96(float (&d)[NN], uint32_t a0, uint32_t a1, uint32_t a2, uint32_t a3,
                                       uint64_t desc_b, int scale_d) {
  asm volatile(
      "{\n.reg .pred p;\nsetp.ne.b32 p, %53, 0;\n"
      "wgmma.mma_async.sync.aligned.m64n96k16.f32.bf16.bf16 "
      "{%0,%1,%2,%3,%4,%5,%6,%7,%8,%9,%10,%11,%12,%13,%14,%15,"
      "%16,%17,%18,%19,%20,%21,%22,%23,%24,%25,%26,%27,%28,%29,%30,%31,"
      "%32,%33,%34,%35,%36,%37,%38,%39,%40,%41,%42,%43,%44,%45,%46,%47}, "
      "{%48,%49,%50,%51}, %52, p, 1, 1, 0;\n}\n"
      : "+f"(d[OFF + 0]), "+f"(d[OFF + 1]), "+f"(d[OFF + 2]), "+f"(d[OFF + 3]), "+f"(d[OFF + 4]), "+f"(d[OFF + 5]),
        "+f"(d[OFF + 6]), "+f"(d[OFF + 7]), "+f"(d[OFF + 8]), "+f"(d[OFF + 9]), "+f"(d[OFF + 10]), "+f"(d[OFF + 11]),
        "+f"(d[OFF + 12]), "+f"(d[OFF + 13]), "+f"(d[OFF + 14]), "+f"(d[OFF + 15]), "+f"(d[OFF + 16]), "+f"(d[OFF + 17]),
        "+f"(d[OFF + 18]), "+f"(d[OFF + 19]), "+f"(d[OFF + 20]), "+f"(d[OFF + 21]), "+f"(d[OFF + 22]), "+f"(d[OFF + 23]),
        "+f"(d[OFF + 24]), "+f"(d[OFF + 25]), "+f"(d[OFF + 26]), "+f"(d[OFF + 27]), "+f"(d[OFF + 28]), "+f"(d[OFF + 29]),
        "+f"(d[OFF + 30]), "+f"(d[OFF + 31]), "+f"(d[OFF + 32]), "+f"(d[OFF + 33]), "+f"(d[OFF + 34]), "+f"(d[OFF + 35]),
        "+f"(d[OFF + 36]), "+f"(d[OFF + 37]), "+f"(d[OFF + 38]), "+f"(d[OFF + 39]), "+f"(d[OFF + 40]), "+f"(d[OFF + 41]),
        "+f"(d[OFF + 42]), "+f"(d[OFF + 43]), "+f"(d[OFF + 44]), "+f"(d[OFF + 45]), "+f"(d[OFF + 46]), "+f"(d[OFF + 47])
      : "r"(a0), "r"(a1), "r"(a2), "r"(a3), "l"(desc_b), "r"(scale_d));
}

template <int OFF, int NN>
__device__ __forceinline__ void wg_d96z(float (&d)[NN], uint32_t a0, uint32_t a1, uint32_t a2, uint32_t a3,
                                       uint64_t desc_b, int scale_d) {
  asm volatile(
      "{\n.reg .pred p;\nsetp.ne.b32 p, %53, 0;\n"
      "wgmma.mma_async.sync.aligned.m64n96k16.f32.bf16.bf16 "
      "{%0,%1,%2,%3,%4,%5,%6,%7,%8,%9,%10,%11,%12,%13,%14,%15,"
      "%16,%17,%18,%19,%20,%21,%22,%23,%24,%25,%26,%27,%28,%29,%30,%31,"
      "%32,%33,%34,%35,%36,%37,%38,%39,%40,%41,%42,%43,%44,%45,%46,%47}, "
      "{%48,%49,%50,%51}, %52, p, 1, 1, 0;\n}\n"
      : "=f"(d[OFF + 0]), "=f"(d[OFF + 1]), "=f"(d[OFF + 2]), "=f"(d[OFF + 3]), "=f"(d[OFF + 4]), "=f"(d[OFF + 5]),
        "=f"(d[OFF + 6]), "=f"(d[OFF + 7]), "=f"(d[OFF + 8]), "=f"(d[OFF + 9]), "=f"(d[OFF + 10]), "=f"(d[OFF + 11]),
        "=f"(d[OFF + 12]), "=f"(d[OFF + 13]), "=f"(d[OFF + 14]), "=f"(d[OFF + 15]), "=f"(d[OFF + 16]), "=f"(d[OFF + 17]),
        "=f"(d[OFF + 18]), "=f"(d[OFF + 19]), "=f"(d[OFF + 20]), "=f"(d[OFF + 21]), "=f"(d[OFF + 22]), "=f"(d[OFF + 23]),
        "=f"(d[OFF + 24]), "=f"(d[OFF + 25]), "=f"(d[OFF + 26]), "=f"(d[OFF + 27]), "=f"(d[OFF + 28]), "=f"(d[OFF + 29]),
        "=f"(d[OFF + 30]), "=f"(d[OFF + 31]), "=f"(d[OFF + 32]), "=f"(d[OFF + 33]), "=f"(d[OFF + 34]), "=f"(d[OFF + 35]),
        "=f"(d[OFF + 36]), "=f"(d[OFF + 37]), "=f"(d[OFF + 38]), "=f"(d[OFF + 39]), "=f"(d[OFF + 40]), "=f"(d[OFF + 41]),
        "=f"(d[OFF + 42]), "=f"(d[OFF + 43]), "=f"(d[OFF + 44]), "=f"(d[OFF + 45]), "=f"(d[OFF + 46]), "=f"(d[OFF + 47])
      : "r"(a0), "r"(a1), "r"(a2), "r"(a3), "l"(desc_b), "r"(scale_d));
}

template <int OFF, int NN>
__device__ __forceinline__ void wg_s104(float (&d)[NN], uint32_t a0, uint32_t a1, uint32_t a2, uint32_t a3,
                                       uint64_t desc_b, int scale_d, uint32_t meta) {
  asm volatile(
      "{\n.reg .pred p;\nsetp.ne.b32 p, %57, 0;\n"
      "wgmma.mma_async.sp.sync.aligned.m64n104k32.f32.bf16.bf16 "
      "{%0,%1,%2,%3,%4,%5,%6,%7,%8,%9,%10,%11,%12,%13,%14,%15,"
      "%16,%17,%18,%19,%20,%21,%22,%23,%24,%25,%26,%27,%28,%29,%30,%31,"
      "%32,%33,%34,%35,%36,%37,%38,%39,%40,%41,%42,%43,%44,%45,%46,%47,"
      "%48,%49,%50,%51}, "
      "{%52,%53,%54,%55}, %56, %58, 0, p, 1, 1, 0;\n}\n"
      : "+f"(d[OFF + 0]), "+f"(d[OFF + 1]), "+f"(d[OFF + 2]), "+f"(d[OFF + 3]), "+f"(d[OFF + 4]), "+f"(d[OFF + 5]),
        "+f"(d[OFF + 6]), "+f"(d[OFF + 7]), "+f"(d[OFF + 8]), "+f"(d[OFF + 9]), "+f"(d[OFF + 10]), "+f"(d[OFF + 11]),
        "+f"(d[OFF + 12]), "+f"(d[OFF + 13]), "+f"(d[OFF + 14]), "+f"(d[OFF + 15]), "+f"(d[OFF + 16]), "+f"(d[OFF + 17]),
        "+f"(d[OFF + 18]), "+f"(d[OFF + 19]), "+f"(d[OFF + 20]), "+f"(d[OFF + 21]), "+f"(d[OFF + 22]), "+f"(d[OFF + 23]),
        "+f"(d[OFF + 24]), "+f"(d[OFF + 25]), "+f"(d[OFF + 26]), "+f"(d[OFF + 27]), "+f"(d[OFF + 28]), "+f"(d[OFF + 29]),
        "+f"(d[OFF + 30]), "+f"(d[OFF + 31]), "+f"(d[OFF + 32]), "+f"(d[OFF + 33]), "+f"(d[OFF + 34]), "+f"(d[OFF + 35]),
        "+f"(d[OFF + 36]), "+f"(d[OFF + 37]), "+f"(d[OFF + 38]), "+f"(d[OFF + 39]), "+f"(d[OFF + 40]), "+f"(d[OFF + 41]),
        "+f"(d[OFF + 42]), "+f"(d[OFF + 43]), "+f"(d[OFF + 44]), "+f"(d[OFF + 45]), "+f"(d[OFF + 46]), "+f"(d[OFF + 47]),
        "+f"(d[OFF + 48]), "+f"(d[OFF + 49]), "+f"(d[OFF + 50]), "+f"(d[OFF + 51])
      : "r"(a0), "r"(a1), "r"(a2), "r"(a3), "l"(desc_b), "r"(scale_d), "r"(meta));
}

template <int OFF, int NN>
__device__ __forceinline__ void wg_s104z(float (&d)[NN], uint32_t a0, uint32_t a1, uint32_t a2, uint32_t a3,
                                       uint64_t desc_b, int scale_d, uint32_t meta) {
  asm volatile(
      "{\n.reg .pred p;\nsetp.ne.b32 p, %57, 0;\n"
      "wgmma.mma_async.sp.sync.aligned.m64n104k32.f32.bf16.bf16 "
      "{%0,%1,%2,%3,%4,%5,%6,%7,%8,%9,%10,%11,%12,%13,%14,%15,"
      "%16,%17,%18,%19,%20,%21,%22,%23,%24,%25,%26,%27,%28,%29,%30,%31,"
      "%32,%33,%34,%35,%36,%37,%38,%39,%40,%41,%42,%43,%44,%45,%46,%47,"
      "%48,%49,%50,%51}, "
      "{%52,%53,%54,%55}, %56, %58, 0, p, 1, 1, 0;\n}\n"
      : "=f"(d[OFF + 0]), "=f"(d[OFF + 1]), "=f"(d[OFF + 2]), "=f"(d[OFF + 3]), "=f"(d[OFF + 4]), "=f"(d[OFF + 5]),
        "=f"(d[OFF + 6]), "=f"(d[OFF + 7]), "=f"(d[OFF + 8]), "=f"(d[OFF + 9]), "=f"(d[OFF + 10]), "=f"(d[OFF + 11]),
        "=f"(d[OFF + 12]), "=f"(d[OFF + 13]), "=f"(d[OFF + 14]), "=f"(d[OFF + 15]), "=f"(d[OFF + 16]), "=f"(d[OFF + 17]),
        "=f"(d[OFF + 18]), "=f"(d[OFF + 19]), "=f"(d[OFF + 20]), "=f"(d[OFF + 21]), "=f"(d[OFF + 22]), "=f"(d[OFF + 23]),
        "=f"(d[OFF + 24]), "=f"(d[OFF + 25]), "=f"(d[OFF + 26]), "=f"(d[OFF + 27]), "=f"(d[OFF + 28]), "=f"(d[OFF + 29]),
        "=f"(d[OFF + 30]), "=f"(d[OFF + 31]), "=f"(d[OFF + 32]), "=f"(d[OFF + 33]), "=f"(d[OFF + 34]), "=f"(d[OFF + 35]),
        "=f"(d[OFF + 36]), "=f"(d[OFF + 37]), "=f"(d[OFF + 38]), "=f"(d[OFF + 39]), "=f"(d[OFF + 40]), "=f"(d[OFF + 41]),
        "=f"(d[OFF + 42]), "=f"(d[OFF + 43]), "=f"(d[OFF + 44]), "=f"(d[OFF + 45]), "=f"(d[OFF + 46]), "=f"(d[OFF + 47]),
        "=f"(d[OFF + 48]), "=f"(d[OFF + 49]), "=f"(d[OFF + 50]), "=f"(d[OFF + 51])
      : "r"(a0), "r"(a1), "r"(a2), "r"(a3), "l"(desc_b), "r"(scale_d), "r"(meta));
}

template <int OFF, int NN>
__device__ __forceinline__ void wg_s48(float (&d)[NN], uint32_t a0, uint32_t a1, uint32_t a2, uint32_t a3,
                                       uint64_t desc_b, int scale_d, uint32_t meta) {
  asm volatile(
      "{\n.reg .pred p;\nsetp.ne.b32 p, %29, 0;\n"
      "wgmma.mma_async.sp.sync.aligned.m64n48k32.f32.bf16.bf16 "
      "{%0,%1,%2,%3,%4,%5,%6,%7,%8,%9,%10,%11,%12,%13,%14,%15,"
      "%16,%17,%18,%19,%20,%21,%22,%23}, "
      "{%24,%25,%26,%27}, %28, %30, 0, p, 1, 1, 0;\n}\n"
      : "+f"(d[OFF + 0]), "+f"(d[OFF + 1]), "+f"(d[OFF + 2]), "+f"(d[OFF + 3]), "+f"(d[OFF + 4]), "+f"(d[OFF + 5]),
        "+f"(d[OFF + 6]), "+f"(d[OFF + 7]), "+f"(d[OFF + 8]), "+f"(d[OFF + 9]), "+f"(d[OFF + 10]), "+f"(d[OFF + 11]),
        "+f"(d[OFF + 12]), "+f"(d[OFF + 13]), "+f"(d[OFF + 14]), "+f"(d[OFF + 15]), "+f"(d[OFF + 16]), "+f"(d[OFF + 17]),
        "+f"(d[OFF + 18]), "+f"(d[OFF + 19]), "+f"(d[OFF + 20]), "+f"(d[OFF + 21]), "+f"(d[OFF + 22]), "+f"(d[OFF + 23])
      : "r"(a0), "r"(a1), "r"(a2), "r"(a3), "l"(desc_b), "r"(scale_d), "r"(meta));
}

template <int OFF, int NN>
__device__ __forceinline__ void wg_s48z(float (&d)[NN], uint32_t a0, uint32_t a1, uint32_t a2, uint32_t a3,
                                       uint64_t desc_b, int scale_d, uint32_t meta) {
  asm volatile(
      "{\n.reg .pred p;\nsetp.ne.b32 p, %29, 0;\n"
      "wgmma.mma_async.sp.sync.aligned.m64n48k32.f32.bf16.bf16 "
      "{%0,%1,%2,%3,%4,%5,%6,%7,%8,%9,%10,%11,%12,%13,%14,%15,"
      "%16,%17,%18,%19,%20,%21,%22,%23}, "
      "{%24,%25,%26,%27}, %28, %30, 0, p, 1, 1, 0;\n}\n"
      : "=f"(d[OFF + 0]), "=f"(d[OFF + 1]), "=f"(d[OFF + 2]), "=f"(d[OFF + 3]), "=f"(d[OFF + 4]), "=f"(d[OFF + 5]),
        "=f"(d[OFF + 6]), "=f"(d[OFF + 7]), "=f"(d[OFF + 8]), "=f"(d[OFF + 9]), "=f"(d[OFF + 10]), "=f"(d[OFF + 11]),
        "=f"(d[OFF + 12]), "=f"(d[OFF + 13]), "=f"(d[OFF + 14]), "=f"(d[OFF + 15]), "=f"(d[OFF + 16]), "=f"(d[OFF + 17]),
        "=f"(d[OFF + 18]), "=f"(d[OFF + 19]), "=f"(d[OFF + 20]), "=f"(d[OFF + 21]), "=f"(d[OFF + 22]), "=f"(d[OFF + 23])
      : "r"(a0), "r"(a1), "r"(a2), "r"(a3), "l"(desc_b), "r"(scale_d), "r"(meta));
}

template <int OFF, int NN>
__device__ __forceinline__ void wg_s56(float (&d)[NN], uint32_t a0, uint32_t a1, uint32_t a2, uint32_t a3,
                                       uint64_t desc_b, int scale_d, uint32_t meta) {
  asm volatile(
      "{\n.reg .pred p;\nsetp.ne.b32 p, %33, 0;\n"
      "wgmma.mma_async.sp.sync.aligned.m64n56k32.f32.bf16.bf16 "
      "{%0,%1,%2,%3,%4,%5,%6,%7,%8,%9,%10,%11,%12,%13,%14,%15,"
      "%16,%17,%18,%19,%20,%21,%22,%23,%24,%25,%26,%27}, "
      "{%28,%29,%30,%31}, %32, %34, 0, p, 1, 1, 0;\n}\n"
      : "+f"(d[OFF + 0]), "+f"(d[OFF + 1]), "+f"(d[OFF + 2]), "+f"(d[OFF + 3]), "+f"(d[OFF + 4]), "+f"(d[OFF + 5]),
        "+f"(d[OFF + 6]), "+f"(d[OFF + 7]), "+f"(d[OFF + 8]), "+f"(d[OFF + 9]), "+f"(d[OFF + 10]), "+f"(d[OFF + 11]),
        "+f"(d[OFF + 12]), "+f"(d[OFF + 13]), "+f"(d[OFF + 14]), "+f"(d[OFF + 15]), "+f"(d[OFF + 16]), "+f"(d[OFF + 17]),
        "+f"(d[OFF + 18]), "+f"(d[OFF + 19]), "+f"(d[OFF + 20]), "+f"(d[OFF + 21]), "+f"(d[OFF + 22]), "+f"(d[OFF + 23]),
        "+f"(d[OFF + 24]), "+f"(d[OFF + 25]), "+f"(d[OFF + 26]), "+f"(d[OFF + 27])
      : "r"(a0), "r"(a1), "r"(a2), "r"(a3), "l"(desc_b), "r"(scale_d), "r"(meta));
}

template <int OFF, int NN>
__device__ __forceinline__ void wg_s56z(float (&d)[NN], uint32_t a0, uint32_t a1, uint32_t a2, uint32_t a3,
                                       uint64_t desc_b, int scale_d, uint32_t meta) {
  asm volatile(
      "{\n.reg .pred p;\nsetp.ne.b32 p, %33, 0;\n"
      "wgmma.mma_async.sp.sync.aligned.m64n56k32.f32.bf16.bf16 "
      "{%0,%1,%2,%3,%4,%5,%6,%7,%8,%9,%10,%11,%12,%13,%14,%15,"
      "%16,%17,%18,%19,%20,%21,%22,%23,%24,%25,%26,%27}, "
      "{%28,%29,%30,%31}, %32, %34, 0, p, 1, 1, 0;\n}\n"
      : "=f"(d[OFF + 0]), "=f"(d[OFF + 1]), "=f"(d[OFF + 2]), "=f"(d[OFF + 3]), "=f"(d[OFF + 4]), "=f"(d[OFF + 5]),
        "=f"(d[OFF + 6]), "=f"(d[OFF + 7]), "=f"(d[OFF + 8]), "=f"(d[OFF + 9]), "=f"(d[OFF + 10]), "=f"(d[OFF + 11]),
        "=f"(d[OFF + 12]), "=f"(d[OFF + 13]), "=f"(d[OFF + 14]), "=f"(d[OFF + 15]), "=f"(d[OFF + 16]), "=f"(d[OFF + 17]),
        "=f"(d[OFF + 18]), "=f"(d[OFF + 19]), "=f"(d[OFF + 20]), "=f"(d[OFF + 21]), "=f"(d[OFF + 22]), "=f"(d[OFF + 23]),
        "=f"(d[OFF + 24]), "=f"(d[OFF + 25]), "=f"(d[OFF + 26]), "=f"(d[OFF + 27])
      : "r"(a0), "r"(a1), "r"(a2), "r"(a3), "l"(desc_b), "r"(scale_d), "r"(meta));
}

template <int OFF, int NN>
__device__ __forceinline__ void wg_s64t(float (&d)[NN], uint32_t a0, uint32_t a1, uint32_t a2, uint32_t a3,
                                       uint64_t desc_b, int scale_d, uint32_t meta) {
  asm volatile(
      "{\n.reg .pred p;\nsetp.ne.b32 p, %37, 0;\n"
      "wgmma.mma_async.sp.sync.aligned.m64n64k32.f32.bf16.bf16 "
      "{%0,%1,%2,%3,%4,%5,%6,%7,%8,%9,%10,%11,%12,%13,%14,%15,"
      "%16,%17,%18,%19,%20,%21,%22,%23,%24,%25,%26,%27,%28,%29,%30,%31}, "
      "{%32,%33,%34,%35}, %36, %38, 0, p, 1, 1, 1;\n}\n"
      : "+f"(d[OFF + 0]), "+f"(d[OFF + 1]), "+f"(d[OFF + 2]), "+f"(d[OFF + 3]), "+f"(d[OFF + 4]), "+f"(d[OFF + 5]),
        "+f"(d[OFF + 6]), "+f"(d[OFF + 7]), "+f"(d[OFF + 8]), "+f"(d[OFF + 9]), "+f"(d[OFF + 10]), "+f"(d[OFF + 11]),
        "+f"(d[OFF + 12]), "+f"(d[OFF + 13]), "+f"(d[OFF + 14]), "+f"(d[OFF + 15]), "+f"(d[OFF + 16]), "+f"(d[OFF + 17]),
        "+f"(d[OFF + 18]), "+f"(d[OFF + 19]), "+f"(d[OFF + 20]), "+f"(d[OFF + 21]), "+f"(d[OFF + 22]), "+f"(d[OFF + 23]),
        "+f"(d[OFF + 24]), "+f"(d[OFF + 25]), "+f"(d[OFF + 26]), "+f"(d[OFF + 27]), "+f"(d[OFF + 28]), "+f"(d[OFF + 29]),
        "+f"(d[OFF + 30]), "+f"(d[OFF + 31])
      : "r"(a0), "r"(a1), "r"(a2), "r"(a3), "l"(desc_b), "r"(scale_d), "r"(meta));
}

template <int OFF, int NN>
__device__ __forceinline__ void wg_s64t1(float (&d)[NN], uint32_t a0, uint32_t a1, uint32_t a2, uint32_t a3,
                                       uint64_t desc_b, int scale_d, uint32_t meta) {
  asm volatile(
      "{\n.reg .pred p;\nsetp.ne.b32 p, %37, 0;\n"
      "wgmma.mma_async.sp.sync.aligned.m64n64k32.f32.bf16.bf16 "
      "{%0,%1,%2,%3,%4,%5,%6,%7,%8,%9,%10,%11,%12,%13,%14,%15,"
      "%16,%17,%18,%19,%20,%21,%22,%23,%24,%25,%26,%27,%28,%29,%30,%31}, "
      "{%32,%33,%34,%35}, %36, %38, 1, p, 1, 1, 1;\n}\n"
      : "+f"(d[OFF + 0]), "+f"(d[OFF + 1]), "+f"(d[OFF + 2]), "+f"(d[OFF + 3]), "+f"(d[OFF + 4]), "+f"(d[OFF + 5]),
        "+f"(d[OFF + 6]), "+f"(d[OFF + 7]), "+f"(d[OFF + 8]), "+f"(d[OFF + 9]), "+f"(d[OFF + 10]), "+f"(d[OFF + 11]),
        "+f"(d[OFF + 12]), "+f"(d[OFF + 13]), "+f"(d[OFF + 14]), "+f"(d[OFF + 15]), "+f"(d[OFF + 16]), "+f"(d[OFF + 17]),
        "+f"(d[OFF + 18]), "+f"(d[OFF + 19]), "+f"(d[OFF + 20]), "+f"(d[OFF + 21]), "+f"(d[OFF + 22]), "+f"(d[OFF + 23]),
        "+f"(d[OFF + 24]), "+f"(d[OFF + 25]), "+f"(d[OFF + 26]), "+f"(d[OFF + 27]), "+f"(d[OFF + 28]), "+f"(d[OFF + 29]),
        "+f"(d[OFF + 30]), "+f"(d[OFF + 31])
      : "r"(a0), "r"(a1), "r"(a2), "r"(a3), "l"(desc_b), "r"(scale_d), "r"(meta));
}

template <int OFF, int NN>
__device__ __forceinline__ void wg_s64tz(float (&d)[NN], uint32_t a0, uint32_t a1, uint32_t a2, uint32_t a3,
                                       uint64_t desc_b, int scale_d, uint32_t meta) {
  asm volatile(
      "{\n.reg .pred p;\nsetp.ne.b32 p, %37, 0;\n"
      "wgmma.mma_async.sp.sync.aligned.m64n64k32.f32.bf16.bf16 "
      "{%0,%1,%2,%3,%4,%5,%6,%7,%8,%9,%10,%11,%12,%13,%14,%15,"
      "%16,%17,%18,%19,%20,%21,%22,%23,%24,%25,%26,%27,%28,%29,%30,%31}, "
      "{%32,%33,%34,%35}, %36, %38, 0, p, 1, 1, 1;\n}\n"
      : "=f"(d[OFF + 0]), "=f"(d[OFF + 1]), "=f"(d[OFF + 2]), "=f"(d[OFF + 3]), "=f"(d[OFF + 4]), "=f"(d[OFF + 5]),
        "=f"(d[OFF + 6]), "=f"(d[OFF + 7]), "=f"(d[OFF + 8]), "=f"(d[OFF + 9]), "=f"(d[OFF + 10]), "=f"(d[OFF + 11]),
        "=f"(d[OFF + 12]), "=f"(d[OFF + 13]), "=f"(d[OFF + 14]), "=f"(d[OFF + 15]), "=f"(d[OFF + 16]), "=f"(d[OFF + 17]),
        "=f"(d[OFF + 18]), "=f"(d[OFF + 19]), "=f"(d[OFF + 20]), "=f"(d[OFF + 21]), "=f"(d[OFF + 22]), "=f"(d[OFF + 23]),
        "=f"(d[OFF + 24]), "=f"(d[OFF + 25]), "=f"(d[OFF + 26]), "=f"(d[OFF + 27]), "=f"(d[OFF + 28]), "=f"(d[OFF + 29]),
        "=f"(d[OFF + 30]), "=f"(d[OFF + 31])
      : "r"(a0), "r"(a1), "r"(a2), "r"(a3), "l"(desc_b), "r"(scale_d), "r"(meta));
}

__device__ __forceinline__ int g2_inv(int ch) { return 32 * (ch >> 5) + 8 * ((ch >> 1) & 3) + 2 * ((ch >> 3) & 3) + (ch & 1); }
__host__ __device__ __forceinline__ uint32_t wimg_off(int n, int k) {
  return (uint32_t)(k >> 6) * kWChunk + (uint32_t)n * 128 + (uint32_t)((((k & 63) >> 3) ^ (n & 7)) << 4) + (k & 7) * 2;
}
__host__ __device__ constexpr int w2piece(int h, int c) { return c == 2 ? 2 + h : 4 * h + c; }
__device__ __forceinline__ uint32_t w2img_off(int n, int k) { return wimg_off(n % 96, k & 63) + w2piece(n >= 96, k >> 6) * (kWChunk / 2); }
__device__ __forceinline__ int qpix(int par, int t) {
  const int a = 2 * t + 13 * par - 6, b = t + 112 * par;
  return par ? min(a, b) : max(a, b);
}
__device__ __forceinline__ int woff(int par, int i, int r) {
  const int a = 99 * par + 6 - 8 * i;
  return par ? min(r, a) : max(r, a);
}

__device__ __forceinline__ void mma16816(float (&c)[4], uint32_t a0, uint32_t a1, uint32_t a2, uint32_t a3, uint32_t b0,
                                         uint32_t b1) {
  asm volatile(
      "mma.sync.aligned.m16n8k16.row.col.f32.bf16.bf16.f32 {%0,%1,%2,%3}, {%4,%5,%6,%7}, {%8,%9}, {%0,%1,%2,%3};"
      : "+f"(c[0]), "+f"(c[1]), "+f"(c[2]), "+f"(c[3])
      : "r"(a0), "r"(a1), "r"(a2), "r"(a3), "r"(b0), "r"(b1));
}

__device__ __forceinline__ void fold_w1(const uint32_t u, const __nv_bfloat16* __restrict__ wqkv, uint8_t* wimg) {
  const uint32_t g = (threadIdx.x >> 2) & 7, l = threadIdx.x & 3;
  const uint32_t m0 = (u * 171 >> 11) * 16, s = u - (u * 171 >> 11) * 12;
  uint4 A[12], B[12];
  const __nv_bfloat16* arow = wqkv + (m0 + 4 * (g >> 1) + (g & 1)) * 576 + 192 + 8 * l;
  const __nv_bfloat16* brow = wqkv + (16 * s + 4 * (g >> 1) + (g & 1)) * 576 + 8 * l;
#pragma unroll
  for (int i = 0; i < 12; i++) {
    A[i] = ldg128_nc(arow + (i & 1) * 2 * 576 + 32 * (i >> 1));
    B[i] = ldg128_nc(brow + (i & 1) * 2 * 576 + 32 * (i >> 1));
  }
  uint8_t* dst = wimg + wimg_off(m0 + g, 16 * s + 4 * l);
  uint32_t zero = (uint32_t)(uint64_t)wimg & 15u, one = zero + 1;
  asm volatile("" : "+l"(dst), "+r"(zero), "+r"(one));
  sched_fence();
  float acc[4][4];
#pragma unroll
  for (int j = 0; j < 16; j++) acc[j >> 2][j & 3] = 0.f;
#pragma unroll
  for (int i = 0; i < 6; i++) {
    const uint4 &a0 = A[2 * i], &a1 = A[2 * i + 1];
    const uint32_t f[8] = {a0.x | zero, a1.x * one, a0.y | zero, a1.y * one, a0.z | zero, a1.z * one, a0.w | zero, a1.w * one};
#pragma unroll
    for (int nb = 0; nb < 2; nb++) {
      mma16816(acc[2 * nb], f[0], f[1], f[2], f[3], B[2 * i + nb].x, B[2 * i + nb].y);
      mma16816(acc[2 * nb + 1], f[4], f[5], f[6], f[7], B[2 * i + nb].z, B[2 * i + nb].w);
    }
  }
#pragma unroll
  for (int j = 0; j < 2; j++) {
    const uint2 v = make_uint2(pack_bf16((acc[0][2 * j] + acc[1][2 * j]) * kAlpha, (acc[0][2 * j + 1] + acc[1][2 * j + 1]) * kAlpha),
                               pack_bf16((acc[2][2 * j] + acc[3][2 * j]) * kAlpha, (acc[2][2 * j + 1] + acc[3][2 * j + 1]) * kAlpha));
    asm volatile("st.relaxed.gpu.global.v2.u32 [%0], {%1,%2};" ::"l"(dst + j * 1024), "r"(v.x), "r"(v.y) : "memory");
  }
}
__device__ __forceinline__ void fold_w2(const int u, const __nv_bfloat16* __restrict__ wqkv, const __nv_bfloat16* __restrict__ wo,
                                        uint8_t* wimg) {
  const int g = (threadIdx.x >> 2) & 7, l = threadIdx.x & 3;
  const int m0 = (u / 12) * 32, n0 = (u % 12) * 16;
  uint4 S[12];
  uint32_t L[96];
  const __nv_bfloat16* brow = wqkv + (n0 + 4 * (g >> 1) + (g & 1)) * 576 + 384 + 8 * l;
#pragma unroll
  for (int i = 0; i < 12; i++) S[i] = ldg128_nc(brow + (i & 1) * 2 * 576 + 32 * (i >> 1));
  const __nv_bfloat16* acol = wo + (8 * l) * 192 + m0 + 4 * g;
#pragma unroll
  for (int c = 0; c < 48; c++)
    asm volatile("ld.global.nc.v2.u32 {%0,%1}, [%2];" : "=r"(L[2 * c]), "=r"(L[2 * c + 1]) : "l"(acol + (32 * (c >> 3) + (c & 7)) * 192));
  const uint32_t off = w2_offset();
  sched_fence();
  uint8_t* img = wimg + off;
  float acc[4][4];
#pragma unroll
  for (int j = 0; j < 16; j++) acc[j >> 2][j & 3] = 0.f;
#pragma unroll
  for (int i = 0; i < 6; i++) {
#pragma unroll
    for (int h = 0; h < 2; h++) {
      const uint4 &s0 = S[2 * i], &s1 = S[2 * i + 1];
#pragma unroll
      for (int mt = 0; mt < 2; mt++) {
        const uint32_t* a = L + 16 * i + 8 * h + mt;
        const uint32_t a0 = __byte_perm(a[0], a[2], 0x5410), a1 = __byte_perm(a[0], a[2], 0x7632);
        const uint32_t a2 = __byte_perm(a[4], a[6], 0x5410), a3 = __byte_perm(a[4], a[6], 0x7632);
        mma16816(acc[2 * mt], a0, a1, a2, a3, h ? s0.z : s0.x, h ? s0.w : s0.y);
        mma16816(acc[2 * mt + 1], a0, a1, a2, a3, h ? s1.z : s1.x, h ? s1.w : s1.y);
      }
    }
  }
#pragma unroll
  for (int j = 0; j < 4; j++) {
    const float(&c0)[4] = acc[j & 2];
    const float(&c1)[4] = acc[(j & 2) + 1];
    asm volatile("st.relaxed.gpu.global.v2.u32 [%0], {%1,%2};" ::"l"(img + w2img_off(g2_inv(m0 + 4 * g + j), n0 + 4 * l)),
                 "r"(pack_bf16(c0[2 * (j & 1)], c0[2 * (j & 1) + 1])), "r"(pack_bf16(c1[2 * (j & 1)], c1[2 * (j & 1) + 1])) : "memory");
  }
}

__global__ void __launch_bounds__(256) fold_kernel(const __nv_bfloat16* __restrict__ wqkv,
                                                   const __nv_bfloat16* __restrict__ wo, uint8_t* wimg) {
  const int u = blockIdx.x * 8 + (threadIdx.x >> 5);
  if (u < 144) fold_w1(u, wqkv, wimg);
  else fold_w2(u - 144, wqkv, wo, wimg);
}

struct TileCoord { int pr, pc, I, J, up, kind; };
struct TileTable { uint16_t e[kCtas * 6], g[5][8][2], b[5][2][4]; };
inline void make_tiles(TileTable& tt) {
  for (int tile = 0; tile < kCtas * 6; tile++) {
    const int b = tile / 6, k = tile - 6 * b;
    const int p = b < 128 ? (tile - 672) >> 1 : b - 80;
    const int strip = b < 112 ? b >> 1 : b >= 128 && k >= 2 ? (b & 1) * 27 + (b & 2) * 14 : p + (p < 26 ? 1 : 3);
    const int pr = strip >= 28, J = (strip - pr * 28) >> 1, pc = strip & 1, up = b < 112 ? b & 1 : pr;
    const int first = b < 112 ? 8 - 2 * pr - up : 13 * pr, step = b < 112 ? k : k & 1;
    const int I = up ? first - step : first + step;
    const int kind = I == 13 * pr ? 3 + pr : J == 13 * pc ? 1 + pc : 0;
    tt.e[tile] = (uint16_t)(I | J << 4 | pr << 8 | pc << 9 | up << 10 | kind << 11);
  }
  for (int kind = 0; kind < 5; kind++) {
    const bool col = kind == 1 || kind == 2;
    auto off = [kind](int t) { return kind == 0 ? 2 * t : kind & 1 ? t + (t == 7) : t + (t > 0); };
    for (int j = 0; j < 8; j++) {
      const int w = j >> 1, h = j & 1;
      tt.g[kind][j][0] = (uint16_t)(col ? 3 * off(w + 4 * h) : 3 * (kW * off(2 * w) + 8 * h));
      tt.g[kind][j][1] = (uint16_t)(128 * (col ? 5 : 5 + off(2 * w + 1) - off(2 * w)));
    }
    for (int i = 0; i < 2; i++) {
      const int w = kind == 0 ? 0 : kind & 1 ? 3 * i : 1 - i;
      tt.b[kind][i][0] = tt.g[kind][2 * w][0];
      tt.b[kind][i][1] = (uint16_t)(128 * (kind == 0 ? 0 : (col ? 3 : 1) + i));
      tt.b[kind][i][2] = (uint16_t)(2048 * w);
      tt.b[kind][i][3] = 0;
    }
  }
}
__device__ __forceinline__ int num_tiles() { return blockIdx.x < 128 ? 6 : 4; }
__device__ __forceinline__ TileCoord decode_tile(const TileTable& tt, int tile) {
  const uint32_t e = tt.e[tile];
  return TileCoord{(int)(e >> 8) & 1, (int)(e >> 9) & 1, (int)e & 15, (int)(e >> 4) & 15, (int)(e >> 10) & 1, (int)(e >> 11)};
}
__device__ __forceinline__ int halo_r0(const TileCoord& t) { return 8 * t.I + 6 * t.pr - 6; }
__device__ __forceinline__ int halo_c0(const TileCoord& t) { return min(max(8 * t.J + 6 * t.pc - 6, -3), 102); }

__device__ __forceinline__ uint32_t bar_full(uint32_t bars, int wg, int c) { return bars + (wg * 3 + c) * 8; }
__device__ __forceinline__ uint32_t bar_w1c(uint32_t bars, int c) { return bars + (6 + c) * 8; }
__device__ __forceinline__ uint32_t bar_w2(uint32_t bars) { return bars + 9 * 8; }
__device__ __forceinline__ uint32_t bar_x(uint32_t bars, int j, int c) { return bars + (j == 0 ? 10 : c ? 17 + c : 11) * 8; }
__device__ __forceinline__ uint32_t bar_w1q(uint32_t bars) { return bars + 12 * 8; }
__device__ __forceinline__ uint32_t bar_xf(uint32_t bars) { return bars + 13 * 8; }
__device__ __forceinline__ uint32_t bar_w2m(uint32_t bars) { return bars + 14 * 8; }
__device__ __forceinline__ uint32_t bar_redo(uint32_t bars) { return bars + 15 * 8; }
__device__ __forceinline__ uint32_t bar_wok(uint32_t bars) { return bars + 16 * 8; }
__device__ __forceinline__ uint32_t bar_go(uint32_t bars) { return bars + 17 * 8; }
__device__ __forceinline__ uint32_t bar_raw(uint32_t bars, int j = 0) { return bars + (21 + j) * 8; }
__device__ __forceinline__ uint32_t bar_w2a(uint32_t bars) { return bars + 20 * 8; }
constexpr int kNumBars = 22;

__device__ __forceinline__ uint64_t wdesc(uint64_t d0, int s) { return d0 + (((s >> 2) * kWChunk + (s & 3) * 32) >> 4); }

__device__ __forceinline__ uint32_t x_chunk(int k, int c) { return kXOff + (k == 0 ? kWChunk : 0) + (k & 1 ? 2 - c : c) * 8192; }
__device__ __forceinline__ uint32_t out_slot(int k, int nt) { return k + 1 < nt ? kW2Off + (~k & 1) * 2 * kWChunk : kW1Off + kWChunk; }
template <int I0, int I1>
__device__ __forceinline__ void store_rows(bool on, __nv_bfloat16* pA, __nv_bfloat16* pB, const uint32_t (&a)[24], const uint32_t (&b)[24]) {
#pragma unroll
  for (int i = 2 * I0; i < 2 * I1; i++) {
    const uint32_t* v = (i & 1 ? b : a) + 4 * (i >> 1);
    asm volatile("{\n.reg .pred p;\nsetp.ne.u32 p, %5, 0;\n@p st.global.v4.u32 [%0], {%1,%2,%3,%4};\n}\n" ::"l"((i & 1 ? pB : pA) + 32 * (i >> 1)),
                 "r"(v[0]), "r"(v[1]), "r"(v[2]), "r"(v[3]), "r"((uint32_t)on) : "memory");
  }
}
template <int I0, int I1>
__device__ __forceinline__ void stage_out(const uint32_t (&ad)[4], const uint32_t (&a)[24], const uint32_t (&b)[24]) {
#pragma unroll
  for (int i = I0; i < I1; i++) {
    const uint32_t* v = (i < 6 ? a : b) + 4 * (i % 6);
    asm volatile("st.shared.v4.u32 [%0], {%1,%2,%3,%4};" ::"r"(ad[i % 6 / 3 * 2 + (i % 3 == 1)] + (i % 3 == 2) * 1024 + (i / 6) * 12288),
                 "r"(v[0]), "r"(v[1]), "r"(v[2]), "r"(v[3]) : "memory");
  }
}
__device__ __forceinline__ uint32_t now_ns() {
  uint32_t t;
  asm volatile("mov.u32 %0, %globaltimer_lo;" : "=r"(t)::"memory");
  return t;
}
__device__ __forceinline__ void wait_clock(uint32_t t_start, uint32_t t) {
  while (now_ns() - t_start < t) { }
}
__device__ __forceinline__ void sleep_clock(uint32_t t_start, uint32_t t) {
  while (now_ns() - t_start < t) __nanosleep(100);
}
#define NAT_PRED(f, m) ".reg .pred p;\n.reg .b32 t;\nand.b32 t, " f ", " m ";\nsetp.ne.u32 p, t, 0;\n"
constexpr uint32_t kHiV = 1, kHiU = 8, kColB = 0x20, kInV = 0x100, kInU = 0x1000, kColA = 0x10000;
template <uint32_t M>
__device__ __forceinline__ float pick(const float* a, const float* b, uint32_t f) {
  float d;
  asm("{\n" NAT_PRED("%5", "%6") "add.f32 %0, %1, %2;\n@p add.f32 %0, %3, %4;\n}\n"
      : "=&f"(d) : "f"(a[0]), "f"(a[2]), "f"(b[0]), "f"(b[2]), "r"(f), "n"(M));
  return d;
}
template <uint32_t M>
__device__ __forceinline__ float sel(float a, float b, uint32_t f) {
  float d;
  asm("{\n" NAT_PRED("%3", "%4") "selp.f32 %0, %1, %2, p;\n}\n" : "=f"(d) : "f"(a), "f"(b), "r"(f), "n"(M));
  return d;
}
template <uint32_t M>
__device__ __forceinline__ void max_if(float& m, float v, uint32_t f) {
  asm("{\n" NAT_PRED("%2", "%3") "@p max.f32 %0, %0, %1;\n}\n" : "+f"(m) : "f"(v), "r"(f), "n"(M));
}
template <uint32_t M>
__device__ __forceinline__ void add_if(float& m, float v, uint32_t f) {
  asm("{\n" NAT_PRED("%2", "%3") "@p add.f32 %0, %0, %1;\n}\n" : "+f"(m) : "f"(v), "r"(f), "n"(M));
}
__device__ __forceinline__ void pick_v(const float* a, float* v, uint32_t f) {
  v[0] = pick<kHiV>(a, a + 16, f), v[1] = pick<kHiV>(a + 1, a + 17, f);
  v[2] = pick<kHiV * 2>(a + 4, a + 20, f), v[3] = pick<kHiV * 2>(a + 5, a + 21, f);
  v[4] = pick<kHiV * 4>(a + 8, a + 24, f), v[5] = pick<kHiV * 4>(a + 9, a + 25, f);
  v[6] = a[12] + a[14], v[7] = a[13] + a[15];
}
__device__ __forceinline__ void pick_u(const float* a, float* v, uint32_t f) {
#pragma unroll
  for (int c = 0; c < 3; c++) v[2 * c] = pick<kHiU>(a + 4 * c, a + 4 * c + 12, f), v[2 * c + 1] = pick<kHiU * 2>(a + 4 * c + 1, a + 4 * c + 13, f);
}
__device__ __forceinline__ uint32_t sign_bytes(uint32_t v, uint32_t sel) {
  uint32_t d;
  asm("prmt.b32 %0, %1, %1, %2;" : "=r"(d) : "r"(v), "r"(sel));
  return d;
}
__device__ __forceinline__ float own_max(const float (&v)[14], uint32_t f) {
  float m = sel<kInV>(fmaxf(v[0], v[1]), -INFINITY, f), m2 = sel<kInV * 2>(fmaxf(v[2], v[3]), -INFINITY, f);
  max_if<kInV * 4>(m, fmaxf(v[4], v[5]), f);
  max_if<kInV * 8>(m2, fmaxf(v[6], v[7]), f);
  max_if<kInU>(m, fmaxf(fmaxf(v[8], v[10]), v[12]), f);
  max_if<kInU * 2>(m2, fmaxf(fmaxf(v[9], v[11]), v[13]), f);
  return fmaxf(m, m2);
}
__device__ __forceinline__ float quad_max(float m) {
  const float a = __shfl_xor_sync(0xffffffffu, m, 1), b = __shfl_xor_sync(0xffffffffu, m, 2), c = __shfl_xor_sync(0xffffffffu, m, 3);
  return fmaxf(fmaxf(m, a), fmaxf(b, c));
}
__device__ __forceinline__ float row_rcp(const float (&v)[14], uint32_t f) {
  float s = sel<kInV>(v[0] + v[1], 0.f, f), s2 = sel<kInV * 2>(v[2] + v[3], 0.f, f);
  add_if<kInV * 4>(s, v[4] + v[5], f);
  add_if<kInV * 8>(s2, v[6] + v[7], f);
  add_if<kInU>(s, v[8] + v[10] + v[12], f);
  add_if<kInU * 2>(s2, v[9] + v[11] + v[13], f);
  s += s2;
  const float a = __shfl_xor_sync(0xffffffffu, s, 1), b = __shfl_xor_sync(0xffffffffu, s, 2), c = __shfl_xor_sync(0xffffffffu, s, 3);
  return rcp_approx((s + a) + (b + c));
}
__device__ __forceinline__ void route(const float (&v)[14], float s, const uint32_t (&rt)[9], uint32_t (&p)[14]) {
#pragma unroll
  for (int i = 0; i < 7; i++) {
    const uint32_t u = pack_bf16(v[2 * i] * s, v[2 * i + 1] * s);
    if (i < 4) p[i] = u & rt[i];
    if (i < 3) p[i + 4] = u & rt[i + 4];
    if (i >= 4) {
      p[i + 3] = u & rt[7];
      p[i + 6] = u & rt[8];
    }
  }
}

template <int C, int T0 = 0, int T1 = 7>
__device__ __forceinline__ void pv_chunk(float (&z)[32], const uint32_t (&pa)[14], const uint32_t (&pb)[14],
                                         const uint32_t (&meta)[4], uint64_t dV) {
#pragma unroll
  for (int t = T0; t < T1; t++) {
    if (t & 1)
      wg_s64t1<0, 32>(z, pa[2 * t], pb[2 * t], pa[2 * t + 1], pb[2 * t + 1], dV + ((2 * C * kChunkBytes + t * 2048) >> 4), 1,
                      meta[t >> 1]);
    else if (t > 0)
      wg_s64t<0, 32>(z, pa[2 * t], pb[2 * t], pa[2 * t + 1], pb[2 * t + 1], dV + ((2 * C * kChunkBytes + t * 2048) >> 4), 1,
                     meta[t >> 1]);
    else
      wg_s64tz<0, 32>(z, pa[0], pb[0], pa[1], pb[1], dV + ((2 * C * kChunkBytes) >> 4), 0, meta[0]);
  }
}
template <int C>
__device__ __forceinline__ void pack_z(const float (&z)[32], uint32_t (&za)[24], uint32_t (&zb)[24]) {
#pragma unroll
  for (int j = 0; j < 8; j++) {
    za[8 * C + j] = pack_bf16(z[4 * j], z[4 * j + 1]);
    zb[8 * C + j] = pack_bf16(z[4 * j + 2], z[4 * j + 3]);
  }
}

template <int H>
__device__ __forceinline__ void pack_out(const float (&ac)[48], uint32_t (&oa)[24], uint32_t (&ob)[24]) {
#pragma unroll
  for (int j = 0; j < 12; j++) {
    oa[12 * H + j] = pack_bf16(ac[4 * j], ac[4 * j + 1]);
    ob[12 * H + j] = pack_bf16(ac[4 * j + 2], ac[4 * j + 3]);
  }
}
struct Maps { CUtensorMap v6, v2, v14, u8, px[8], wv, wo; };
__device__ __forceinline__ void tma_prefetch_5d(const CUtensorMap* map, int c0, int c1, int c2, int c3, int c4) {
  asm volatile("cp.async.bulk.prefetch.tensor.5d.L2.global.tile [%0, {%1, %2, %3, %4, %5}];" ::"l"((uint64_t)map), "r"(c0), "r"(c1),
               "r"(c2), "r"(c3), "r"(c4) : "memory");
}
__device__ __forceinline__ int first_line(const TileCoord tc) { return 3 * (qpix(tc.pr, 8 * tc.I) * kW + qpix(tc.pc, 8 * tc.J)); }
__device__ __forceinline__ void load_px(const Maps& tm, const TileTable& tt, uint32_t dst, uint32_t bar, int line, int kind) {
#pragma unroll
  for (int i = 0; i < 2; i++) {
    if (i == 0 || kind != 0) {
      const CUtensorMap* map = (const CUtensorMap*)((const char*)tm.px + tt.b[kind][i][1]);
      if (bar) tma_load_5d(dst + tt.b[kind][i][2], map, bar, 0, 0, 0, 0, line + tt.b[kind][i][0]);
      else tma_prefetch_5d(map, 0, 0, 0, 0, line + tt.b[kind][i][0]);
    }
  }
}
__device__ __forceinline__ void store_px(const Maps& tm, const TileTable& tt, uint32_t buf, int line, int kind) {
#pragma unroll
  for (int i = 0; i < 8; i++) {
    const int j = 2 * (i & 3) + (i >> 2);
    asm volatile("cp.async.bulk.tensor.5d.global.shared::cta.tile.bulk_group [%0, {%2, %2, %2, %2, %3}], [%1];" ::"l"(
                     (uint64_t)tm.px + tt.g[kind][j][1]), "r"(buf + i * 3072), "r"(0), "r"(line + tt.g[kind][j][0]) : "memory");
  }
  asm volatile("cp.async.bulk.commit_group;" ::: "memory");
}
__device__ __noinline__ bool refetch(uint32_t base, const uint8_t* src, bool gap) {
  constexpr uint32_t bars = 1024 + kBarOff, cnt = bars + 192;
#pragma unroll 1
  for (uint32_t o = 0; o < kWBytes && !gap; o += 2048) {
    uint32_t mx = 0;
#pragma unroll
    for (int i = 0; i < 4; i++) {
      uint4 v;
      asm volatile("ld.shared.v4.u32 {%0,%1,%2,%3}, [%4];" : "=r"(v.x), "=r"(v.y), "=r"(v.z), "=r"(v.w)
                   : "r"(base + o + i * 512 + (threadIdx.x & 31) * 16));
      mx = __vimax3_u32(__vimax3_u32(mx, v.x, v.y), v.z, v.w);
    }
    gap = __any_sync(0xffffffffu, mx == kEmpty);
  }
  uint32_t n;
  asm volatile("ld.shared.u32 %0, [%1];" : "=r"(n) : "r"(cnt) : "memory");
  if (!gap || __any_sync(0xffffffffu, n > (1u << 12))) return false;
  asm volatile("bar.sync 15, 128;" ::: "memory");
  if (threadIdx.x == 0) {
    asm volatile("st.shared.u32 [%0], %1;" ::"r"(cnt), "r"(n + 1) : "memory");
    mbar_arrive_expect_tx(bar_redo(bars), kWBytes);
    bulk_load(base, src, kWBytes, bar_redo(bars));
  }
  __syncwarp();
  mbar_wait(bar_redo(bars), n & 1);
  return true;
}
__device__ __forceinline__ bool any_nan(const uint32_t (&a)[24]) {
  uint32_t m[2] = {a[0], a[1]}, nan;
#pragma unroll
  for (int i = 2; i < 24; i++) asm("max.NaN.bf16x2 %0, %0, %1;" : "+r"(m[i & 1]) : "r"(a[i]));
  asm("max.NaN.bf16x2 %0, %0, %1;" : "+r"(m[0]) : "r"(m[1]));
  asm volatile("{\n.reg .pred p;\nsetp.ne.u32 p, %1, 0;\nbar.red.or.pred p, 15, 128, p;\nselp.u32 %0, 1, 0, p;\n}\n"
               : "=r"(nan) : "r"(((m[0] & 0x7FFF7FFFu) + 0x007F007Fu) & 0x80008000u) : "memory");
  return __any_sync(0xffffffffu, nan);
}
template <int S0, int S1, int Z>
__device__ __forceinline__ void g2_steps(float (&ac)[48], const uint32_t (&za)[24], const uint32_t (&zb)[24], uint64_t d) {
#pragma unroll
  for (int s = S0; s < S1; s++) {
    const uint64_t ds = d + (((s >> 2 & 1) * (kWChunk / 2) + (s & 3) * 32) >> 4);
    if (s == Z) wg_d96z<0, 48>(ac, za[2 * s], zb[2 * s], za[2 * s + 1], zb[2 * s + 1], ds, 0);
    else wg_d96<0, 48>(ac, za[2 * s], zb[2 * s], za[2 * s + 1], zb[2 * s + 1], ds, 1);
  }
}

__device__ __forceinline__ void consumer(const int wg, __nv_bfloat16* out, const uint8_t* wimg, const uint32_t sbase,
                                         const uint32_t zero, const Maps& tm, const TileTable& tt) {
  const int tid = threadIdx.x & 127;
  const int w = __shfl_sync(0xffffffffu, tid >> 5, 0), lane = tid & 31;
  const uint64_t dK = make_desc(sbase, 16, 1024);
  const uint64_t dV = make_desc(sbase, kChunkBytes, 512, 2);
  const uint64_t dW1 = make_desc(sbase + kW1Off, 16, 1024);
  const uint64_t dX0 = make_desc(sbase + kW2Off + wg * 2 * kWChunk, 16, 1024), dY0 = make_desc(sbase + kW2Off + (1 - wg) * 2 * kWChunk, 16, 1024);
  const uint64_t dX2 = make_desc(sbase + kXOff + wg * (kWChunk / 2), 16, 1024), dY2 = make_desc(sbase + kXOff + (1 - wg) * (kWChunk / 2), 16, 1024);
  const uint32_t bars = sbase + kBarOff;
  int tile0 = blockIdx.x * kTilesPerCta;
  asm volatile("" : "+r"(tile0));
  const int nt = num_tiles();

  uint32_t pix = 0, geo[6] = {};
  const int l = lane & 3;
#pragma unroll 1
  for (int j = 4; j >= 0; j -= 2) {
    const TileCoord tc = decode_tile(tt, tile0 + wg + j);
    const bool col = tc.kind == 1 || tc.kind == 2;
    const int g = col ? lane >> 2 : 2 * w + ((lane >> 2) & 1), qc = col ? w : lane >> 3;
    const uint32_t pr = qpix(tc.pr, 8 * tc.I + g) * kW;
    if (j == nt - 2) pix = (pr + qpix(tc.pc, 8 * tc.J + qc)) | (pr + qpix(tc.pc, 8 * tc.J + qc + 4)) << 16;
    const int d = 8 * tc.J + 6 * tc.pc - 6 - halo_c0(tc);
    const int ro = woff(tc.pr, tc.I, g), coA = woff(tc.pc, tc.J, qc) + d, coB = woff(tc.pc, tc.J, qc + 4) + d - 3;
#pragma unroll
    for (int i = 5; i >= 2; i--) geo[i] = geo[i - 2];
    const uint32_t lr = 0x1FCu << ro;
    const uint32_t lv = lr >> (2 + (l >> 1)), lu = lr >> (2 * l + 2 * tc.up);
    const uint32_t t = __byte_perm(lv, lu, wg ? 0x4501 : 0x5410);
    geo[0] = (((t & 0x15u) | (lv & 0x40u)) * 0x02082080u & 0x80808080u) | (((t >> 8) & 0x15u) * 0x01041040u & 0x40404040u) |
             (__byte_perm(t << 5, t << 4, 0x7362) & 0x20202020u) | (nt == 6);
    const int dr = (ro - 1) & 7;
    const uint32_t hiv = (((1u << ((ro - (l >> 1) + 1) >> 1)) - 1u) ^ (wg ? 7u : 0u)) & 7u, hiu = (t >> 24) & 3u;
    const uint32_t ca = (1u << coA) - 1u;
    geo[1] = hiv * kHiV | hiu * kHiU | ((((1u << coB) - 1u) >> (2 * (l & 1))) & 3u) * kColB |
             (15u & ~((uint32_t)((dr & 1) == (l >> 1)) << (dr >> 1))) * kInV | ((t >> 16 | t >> 24) & 3u) * kInU | ca * kColA |
             (ca >> ((0x49 >> (2 * l)) & 3) & 1u) << 19 | (uint32_t)(l == 3) << 20 | (0x55u & ((1u << (2 * coB)) - 1u)) << 24;
  }
  keep_regs(geo);
  const int so = (lane >> 3) | (lane & 4);
  uint32_t sts = sbase + w * 3072 + so * 128 + (((lane & 3) ^ so) << 4);
  __nv_bfloat16* poA = out + 8 * l + (pix & 0xFFFFu) * kC + 96 * wg;
  __nv_bfloat16* poB = out + 8 * l + (pix >> 16) * kC + 96 * wg;
  asm volatile("" : "+l"(poA), "+l"(poB), "+r"(sts));
  uint32_t oa[24], ob[24];
#pragma unroll
  for (int j = 0; j < 24; j++) oa[j] = ob[j] = 0u;
  keep_regs(oa);
  keep_regs(ob);
  PROF(wg, 0);
  if (threadIdx.x == 0) GT(1);

  for (int k = wg; k < nt; k += 2) {
    const uint32_t ph = (k >> 1) & 1;
    const int it = k >> 1;
    uint32_t qa[24], qb[24], hok[3];
    uint32_t fl = geo[1];
    {
      float acc[96];
      const uint32_t xp = (k + (k > 0)) & 1;
      if (k > 0) nb_sync(1 + (1 - wg));
#pragma unroll
      for (int s = 0; s < 12; s++) {
        if (s == 0) mbar_wait(bar_x(bars, k > 0, 0), xp);
        if (s == 0 && k < 2) PROF(wg, 1);
        if (s == 0) PROFS(2, wg, 2 + it * 12);
        if (s == 0 && w == 0 && k < 2) GT(20 + wg);
        if (s == 4) wg_wait<1>();
        if ((s & 3) == 0 && (k == 0 || s > 0)) {
          mbar_wait(k == 0 ? bar_w1c(bars, s >> 2) : bar_x(bars, 1, s >> 2), xp);
          PROFS(17, wg, 50 + (s >> 2));
        }
        if ((s & 3) == 0) wg_fence();
        const uint64_t dX = make_desc(sbase + x_chunk(k, s >> 2), 16, 1024) + 2 * (s & 3);
        if (s == 0) wg_m192z<0, 96>(acc, dX, dW1, 0);
        else wg_m192<0, 96>(acc, dX, wdesc(dW1, s), 1);
        if ((s & 3) == 3 || s == 0) wg_commit();
      }
      PROFS(13, wg, 13 + it * 12);
      const uint32_t e = sts + out_slot(k, nt), o = e ^ 64;
      uint32_t ad[4] = {wg ? o + 1024 : e, wg ? e + 2048 : o, wg ? e : o + 1024, wg ? o : e + 2048};
      keep_regs(ad);
      wg_wait<2>();
      if (k > 0) nb_arrive_p(0);
      wg_wait<1>();
      if (k > 0) nb_arrive_p(14);
      wg_wait<0>();
      if (k > 0) {
        nb_arrive_p(6);
        sched_fence();
      }
      fence_regs(acc);
      PROFS(3, wg, 3 + it * 12);
#pragma unroll
      for (int j = 0; j < 24; j++) {
        qa[j] = pack_bf16(acc[4 * j], acc[4 * j + 1]);
        qb[j] = pack_bf16(acc[4 * j + 2], acc[4 * j + 3]);
      }
      keep_regs(qa);
      keep_regs(qb);
      sched_fence();
      if (k >= 2) {
        nb_sync(11);
        stage_out<0, 6>(ad, oa, ob);
        nb_sync(12);
        stage_out<6, 12>(ad, oa, ob);
      }
#pragma unroll
      for (int c = 0; c < 3; c++) hok[c] = mbar_test(bar_full(bars, wg, c), ph);
      if (k >= 2) {
        fence_proxy_async();
        nb_arrive_p(10);
      }
    }

    float aE[52], aO[24], bO[52], bE[28];
    const uint32_t mq = 0xEEEE4444u | zero;
    PROFS(4, wg, 4 + it * 12);

    mbar_wait_if(hok[0], bar_full(bars, wg, 0), ph);
    PROFS(14, wg, 40 + it * 3);
    if (w == 0 && k < 2) GT(22 + wg);
    if (k > 0) nb_sync(3 + (1 - wg));
    wg_fence();
#pragma unroll
    for (int ks = 0; ks < 6; ks++) {
      if (ks == 2) {
        mbar_wait_if(hok[1], bar_full(bars, wg, 1), ph);
        PROFS(14, wg, 41 + it * 3);
        wg_fence();
      }
      if (ks == 4) {
        mbar_wait_if(hok[2], bar_full(bars, wg, 2), ph);
        PROFS(14, wg, 42 + it * 3);
        wg_fence();
      }
      const uint64_t d = dK + ((ks * kChunkBytes) >> 4);
      if (ks == 0) wg_s104z<0, 52>(aE, qa[0], qa[1], qa[2], qa[3], d, 0, mq);
      else wg_s104<0, 52>(aE, qa[4 * ks], qa[4 * ks + 1], qa[4 * ks + 2], qa[4 * ks + 3], d, 1, mq);
      if (ks == 0) wg_s48z<0, 24>(aO, qa[0], qa[1], qa[2], qa[3], d + ((7 * 1024 + 64) >> 4), 0, mq);
    }
    wg_commit();
#pragma unroll
    for (int ks = 1; ks < 6; ks++)
      wg_s48<0, 24>(aO, qa[4 * ks], qa[4 * ks + 1], qa[4 * ks + 2], qa[4 * ks + 3], dK + ((ks * kChunkBytes + 7 * 1024 + 64) >> 4), 1, mq);
    wg_commit();
    wg_s56z<0, 28>(bE, qb[0], qb[1], qb[2], qb[3], dK, 0, mq);
#pragma unroll
    for (int ks = 1; ks < 6; ks++) wg_s56<0, 28>(bE, qb[4 * ks], qb[4 * ks + 1], qb[4 * ks + 2], qb[4 * ks + 3], dK + ((ks * kChunkBytes) >> 4), 1, mq);
    wg_commit();
    wg_wait<2>();
    fence_regs(aE);
    PROFS(5, wg, 5 + it * 12);

    uint32_t pa[14], pb[14], meta[4];
    {
      float vA[14], vB[14];
      pick_v(aE, vA, fl);
      pick_u(aE + 28, vA + 8, fl);
      fence_regs(vA);
      if (k == 0) {
        if (__builtin_expect(__any_sync(0xffffffffu, vA[6] != vA[6]), 0)) {
          wg_wait<0>();
          fence_regs(aO);
          fence_regs(bE);
          if (refetch(sbase + kW1Off, wimg, false)) {
#pragma unroll
            for (int j = 0; j < 24; j++) oa[j] = ob[j] = 0u;
            k -= 2;
            continue;
          }
        }
        if (elect_one()) mbar_arrive(bar_xf(bars));
      }
      wg_fence();
      wg_s104z<0, 52>(bO, qb[0], qb[1], qb[2], qb[3], dK + 4, 0, mq);
#pragma unroll
      for (int ks = 1; ks < 6; ks++)
        wg_s104<0, 52>(bO, qb[4 * ks], qb[4 * ks + 1], qb[4 * ks + 2], qb[4 * ks + 3], dK + ((ks * kChunkBytes + 64) >> 4), 1, mq);
      wg_commit();
      if (k + 1 < nt) nb_arrive(1 + wg);
      uint32_t rt[9];
#pragma unroll
      for (int i = 0; i < 7; i++) rt[i] = sign_bytes(geo[0] << (i >> 2), 0x8888u + 0x1111u * (i & 3));
      rt[7] = sign_bytes(geo[0] << 2, 0x9988u);
      rt[8] = sign_bytes(geo[0] << 2, 0xBBAAu);
      keep_regs(rt);
      pa[13] = geo[0] & zero, pb[13] = geo[1] & zero;
      wg_wait<2>();
      keep_regs(qa);
      fence_regs(aO);
      float oA[6], eB[8];
      pick_u(aO, oA, fl);
      wg_wait<1>();
      fence_regs(bE);
      pick_v(bE, eB, fl);
      vA[8] = sel<kColA>(oA[0], vA[8], fl), vA[9] = sel<kColA>(oA[1], vA[9], fl);
      vA[10] = sel<kColA * 2>(oA[2], vA[10], fl), vA[11] = sel<kColA * 2>(oA[3], vA[11], fl);
      vA[12] = sel<kColA * 4>(oA[4], vA[12], fl), vA[13] = sel<kColA * 4>(oA[5], vA[13], fl);
      {
        const float m1 = __uint_as_float(0x88DD88DDu), m0 = __uint_as_float(0x88DDDD88u);
        meta[0] = 0xDD88DD88u ^ __byte_perm(fl, 0u, 0x3344);
        meta[1] = __float_as_uint(sel<kColA * 16>(sel<kColA>(m1, m0, fl), __uint_as_float(meta[0]), fl));
        meta[2] = __float_as_uint(sel<kColA * 8>(m1, m0, fl));
        meta[3] = __float_as_uint(sel<kColA * 4>(m1, m0, fl));
        keep_regs(meta);
      }
      float mA = own_max(vA, fl);
      fl |= __float_as_uint(eB[7]) & zero;
      fence_regs(eB);
      fence_regs(vA);
      asm volatile("" : "+f"(mA), "+r"(fl));
      sched_fence();
      wg_wait<0>();
      sched_fence();
      keep_regs(qb);
      fence_regs(bO);
      PROFS(6, wg, 6 + it * 12);
      if (w == 0) GT(24 + k);
      mA = quad_max(mA);
      pick_v(bO, vB, fl);
      pick_u(bO + 28, vB + 8, fl);
#pragma unroll
      for (int i = 0; i < 8; i += 2) vB[i] = sel<kColB>(vB[i], eB[i], fl), vB[i + 1] = sel<kColB * 2>(vB[i + 1], eB[i + 1], fl);
#pragma unroll
      for (int i = 0; i < 14; i++) vA[i] = i < 3 ? ex2(vA[i] - mA) : vA[i] - mA;
      fence_regs(vA);
      fence_regs(vB);
      sched_fence();
#pragma unroll
      for (int i = 3; i < 14; i++) vA[i] = ex2(vA[i]);
      const float mB = quad_max(own_max(vB, fl));
      PROFS(7, wg, 7 + it * 12);
#pragma unroll
      for (int i = 0; i < 14; i++) vB[i] = i < 1 ? ex2(vB[i] - mB) : vB[i] - mB;
      fence_regs(vA);
      fence_regs(vB);
      sched_fence();
#pragma unroll
      for (int i = 1; i < 14; i++) vB[i] = ex2(vB[i]);
      route(vA, row_rcp(vA, fl), rt, pa);
      route(vB, row_rcp(vB, fl), rt, pb);
    }
    PROFS(8, wg, 8 + it * 12);
    if (k == NAT_PK) PROFS(18, wg, 53);
    sched_fence();

    float ac0[48], ac1[48];
    {
      float z0[32], z1[32], z2[32];
      uint32_t za[24], zb[24];
      wg_fence();
      pv_chunk<0>(z0, pa, pb, meta, dV);
      wg_commit();
      pv_chunk<1>(z1, pa, pb, meta, dV);
      wg_commit();
      wg_wait<1>();
      if (k == NAT_PK) PROFS(18, wg, 54);
      if (k + 1 < nt) nb_arrive_p(7);
      pv_chunk<2, 0, 3>(z2, pa, pb, meta, dV);
      wg_commit();
      sched_fence();
      fence_regs(z0);
      pack_z<0>(z0, za, zb);
      sched_fence();
      wg_fence();
      pv_chunk<2, 3, 7>(z2, pa, pb, meta, dV);
      wg_commit();
      wg_wait<2>();
      if (k == NAT_PK) PROFS(19, wg, 55);
      if (k + 1 < nt) nb_arrive_p(8);
      if (k < 2) mbar_wait(k == 1 ? bar_wok(bars) : bar_w2a(bars), 0);
      wg_fence();
      g2_steps<0, 3, 0>(ac0, za, zb, dX0);
      wg_commit();
      sched_fence();
      fence_regs(z1);
      pack_z<1>(z1, za, zb);
      sched_fence();
      wg_fence();
      g2_steps<3, 4, 0>(ac0, za, zb, dX0);
      wg_commit();
      g2_steps<4, 8, 0>(ac0, za, zb, dX0);
      wg_commit();
      wg_wait<3>();
      if (k + 1 < nt) nb_arrive_p(9);
      else nb_arrive(11);
      if (k == NAT_PK) PROFS(20, wg, 56);
      keep_regs(pa);
      keep_regs(pb);
      keep_regs(meta);
      sched_fence();
      const uint32_t mok = mbar_test(bar_w2m(bars), k + 1 < nt ? k & 1 : ~k & 1);
      const uint32_t wp = k < 2 ? 0 : k + 1 < nt ? ~k & 1 : k & 1, wok = mbar_test(bar_w2(bars), wp);
      fence_regs(z2);
      pack_z<2>(z2, za, zb);
      keep_regs(za);
      keep_regs(zb);
      sched_fence();
      PROFS(9, wg, 9 + it * 12);
      wg_wait<1>();
      if (k > 0 && k + 1 < nt) nb_arrive(11);
      mbar_wait_if(mok, bar_w2m(bars), k & 1);
      wg_fence();
      g2_steps<8, 12, 0>(ac0, za, zb, dX2);
      wg_commit();
      g2_steps<8, 12, 8>(ac1, za, zb, dY2);
      wg_commit();
      wg_wait<2>();
      if (k > 0 && k + 1 < nt) nb_arrive(12);
      mbar_wait_if(wok, bar_w2(bars), wp);
      wg_fence();
      g2_steps<0, 4, 8>(ac1, za, zb, dY0);
      wg_commit();
      wg_wait<2>();
      if (k + 2 < nt) nb_arrive_p(13);
      const bool direct = k + 2 >= nt;
      sched_fence();
      fence_regs(ac0);
      pack_out<0>(ac0, oa, ob);
      store_rows<0, 1>(direct, poA, poB, oa, ob);
      sched_fence();
      wg_fence();
      g2_steps<4, 8, 8>(ac1, za, zb, dY0);
      wg_commit();
      if (k + 1 < nt) nb_arrive(3 + wg);
      PROFS(10, wg, 10 + it * 12);
      wg_wait<2>();
      if (k + 2 < nt && (k > 0 || nt == 6)) nb_arrive_p(5);
      store_rows<1, 3>(direct, poA, poB, oa, ob);
      __nv_bfloat16 *qA = poA - 192 * wg, *qB = poB - 192 * wg;
      if (k + 2 == nt) nb_sync(11);
      sched_fence();
      wg_wait<0>();
      fence_regs(ac1);
      if (direct) {
        pack_out<1>(ac1, oa, ob);
        asm volatile("" : "+l"(qA), "+l"(qB));
        store_rows<3, 6>(true, qA, qB, oa, ob);
        break;
      }
      sched_fence();
      pack_out<1>(ac1, oa, ob);
      if (k == 0) {
        if (any_nan(oa)) {
          for (int c = 0; c < 3 && __any_sync(0xffffffffu, geo[2] & 1u); c++) mbar_wait(bar_x(bars, 1, c), 1);
          bool first = true;
          do {
            if (!__any_sync(0xffffffffu, refetch(sbase + kW2Off, wimg + w2_offset(), first))) break;
            first = false;
            wg_fence();
            g2_steps<0, 8, 0>(ac0, za, zb, dX0);
            g2_steps<8, 12, 0>(ac0, za, zb, dX2);
            g2_steps<8, 12, 8>(ac1, za, zb, dY2);
            g2_steps<0, 8, 8>(ac1, za, zb, dY0);
            wg_commit();
            wg_wait<0>();
            fence_regs(ac0);
            fence_regs(ac1);
            pack_out<0>(ac0, oa, ob);
            pack_out<1>(ac1, oa, ob);
          } while (any_nan(oa));
          if (__any_sync(0xffffffffu, geo[2] & 1u)) {
            asm volatile("bar.sync 15, 128;" ::: "memory");
            if (w == 0 && elect_one()) {
              const TileCoord tc = decode_tile(tt, tile0 + 2);
              mbar_arrive_expect_tx(bar_raw(bars), kWChunk);
#pragma unroll 1
              for (int c = 0; c < 3; c++) load_px(tm, tt, sbase + x_chunk(2, c), bar_raw(bars), first_line(tc) + c, tc.kind);
            }
            __syncwarp();
            mbar_wait(bar_raw(bars), 0);
          }
        }
        if (nt < 6) nb_arrive_p(5);
        if (elect_one()) mbar_arrive(bar_wok(bars));
      }
      keep_regs(za);
      keep_regs(zb);
#pragma unroll
      for (int i = 0; i < 4; i++) geo[i] = geo[i + 2];
      keep_regs(oa);
      keep_regs(ob);
      PROFS(12, wg, 12 + it * 12);
      sched_fence();
    }
  }
  PROF(wg, 38);
  GT_DUMP();
  PROF_DUMP(wg);
}

struct HaloCols { int vj, vc, uj, uc; };
__device__ __forceinline__ HaloCols halo_cols(const TileCoord& tc) {
  const int c0 = halo_c0(tc);
  return HaloCols{c0 > 98, c0 > 98 ? 98 : c0 + 3, c0 < 0 ? -1 : 0, c0 < 0 ? 4 : c0};
}
__device__ __forceinline__ void first_halo(const Maps& tm, uint32_t sbase, const TileCoord tc, int i) {
  const HaloCols hc = halo_cols(tc);
  const uint32_t dst = sbase + i * kChunkBytes, bar = bar_full(sbase + kBarOff, 0, i >> 1);
  const int h0 = halo_r0(tc), ch = 24 * tc.pc + 4 * i;
  tma_load_5d(dst, &tm.v14, bar, ch, hc.vj, hc.vc, tc.pr, h0);
  tma_load_5d(dst + 7 * 1024, &tm.u8, bar, ch, hc.uj, h0 + (tc.up ? 0 : -2), tc.pr, hc.uc);
  tma_load_5d(dst + 10 * 1024, &tm.u8, bar, ch, hc.uj, h0 + (tc.up ? 8 : 6), tc.pr, hc.uc);
}
__device__ __forceinline__ void load_halo(const Maps& tm, uint32_t sbase, uint32_t bars, const TileCoord tc, int k, int c) {
  const HaloCols hc = halo_cols(tc);
  const int h6 = halo_r0(tc) + (tc.up ? 0 : 8), h2 = halo_r0(tc) + 6, h8 = halo_r0(tc) + (tc.up ? 0 : 6), ch = 24 * tc.pc + 8 * c;
  uint32_t dv = sbase + 2 * c * kChunkBytes, du = dv + 7 * 1024;
  if (((k ^ tc.up) & 1) == 0) dv += 4 * 1024, du += 3 * 1024;
  const uint32_t bar = bar_full(bars, k & 1, c);
  mbar_arrive_expect_tx(bar, 14 * 1024);
  nb_sync_p(7 + c);
#pragma unroll
  for (int h = 0; h < 2; h++) {
    tma_load_5d(dv + h * kChunkBytes, &tm.v6, bar, ch + 4 * h, hc.vj, hc.vc, tc.pr, h6);
    tma_load_5d(du + h * kChunkBytes, &tm.u8, bar, ch + 4 * h, hc.uj, h8, tc.pr, hc.uc);
    tma_load_5d(sbase + (2 * c + h) * kChunkBytes + 3 * 1024, &tm.v2, bar, ch + 4 * h, hc.vj, hc.vc, tc.pr, h2);
  }
  PROFS(15, 2, k * 4 + c);
}
__device__ __forceinline__ void gather_px(const __nv_bfloat16* __restrict__ x, uint32_t sbase, const TileCoord tc) {
  const int lane = threadIdx.x & 31, g = lane >> 3;
  uint32_t ro[4], co[4];
#pragma unroll
  for (int i = 0; i < 4; i++) {
    ro[i] = qpix(tc.pr, 8 * tc.I + 2 * i + (g & 1)) * (kW * kC * 2) + 16 * (lane & 7);
    co[i] = qpix(tc.pc, 8 * tc.J + 2 * i + (g >> 1)) * (kC * 2);
  }
  const uint32_t dst = sbase + kXOff + g * 128 + (((lane & 7) ^ g) << 4);
  if (lane < 8)
    asm volatile("cp.async.bulk.prefetch.L2.global [%0], 3456;" ::"l"(x + (qpix(tc.pr, 8 * tc.I + lane) * kW + 215 * tc.pc) * kC) : "memory");
  __syncwarp();
  keep_regs(ro);
  keep_regs(co);
  sched_fence();
  nb_sync_p(13);
  nb_sync_p(5);
#pragma unroll
  for (int i = 0; i < 16; i++) {
    const char* src = (const char*)x + (ro[i >> 2] + co[i & 3]);
#pragma unroll
    for (int q = 0; q < 3; q++)
      asm volatile("cp.async.cg.shared.global [%0], [%1], 16;" ::"r"((dst ^ ((i & 1) * 576)) + (i >> 1) * 1024 + q * 8192), "l"(src + 128 * q) : "memory");
  }
  asm volatile("cp.async.wait_all;" ::: "memory");
  fence_proxy_async();
  __syncwarp();
  if (lane < 3) mbar_arrive(bar_x(sbase + kBarOff, 1, lane));
  __syncwarp();
}

__global__ void __launch_bounds__(384, 1)
nat_kernel(const __nv_bfloat16* __restrict__ x, __nv_bfloat16* out, const __nv_bfloat16* __restrict__ wqkv,
           const __nv_bfloat16* __restrict__ wo, uint8_t* wimg, const uint32_t zero,
           const __grid_constant__ Maps tm, const __grid_constant__ TileTable tt) {
  extern __shared__ uint8_t smem_raw[];
  constexpr uint32_t sbase = 1024;
  constexpr uint32_t bars = sbase + kBarOff;
  const int tid = threadIdx.x;
  const uint32_t t_start = now_ns();
  if (tid == 0) GT(0);
  const int role = __shfl_sync(0xffffffffu, blockIdx.x + 8 * (tid & ~31), 0), wid = role >> 8;
  const bool w2cta = blockIdx.x - 128 < 3 && wqkv != nullptr;
  if (wid >= 8) {
    asm volatile("setmaxnreg.dec.sync.aligned.u32 24;");
    if (smem_u32(smem_raw) != sbase) __trap();
    const int c = wid & 3, lane = tid & 31;
    const int tile0 = blockIdx.x * kTilesPerCta, nt = num_tiles();
    uint32_t w2o = 0;
    if (c == 3) {
      if (elect_one()) wait_clock(t_start, NAT_TM);
      __syncwarp();
      asm volatile("prefetch.tensormap [%0];" ::"l"((uint64_t)tm.px) : "memory");
      asm volatile("prefetch.tensormap [%0];" ::"l"((uint64_t)&tm.v6) : "memory");
      asm volatile("prefetch.tensormap [%0];" ::"l"((uint64_t)&tm.v2) : "memory");
      asm volatile("prefetch.tensormap [%0];" ::"l"((uint64_t)(tm.px + (blockIdx.x < 112 ? 5 : 6))) : "memory");
      asm volatile("prefetch.tensormap [%0];" ::"l"((uint64_t)(tm.px + 7)) : "memory");
      if (nt < 6) {
        asm volatile("prefetch.tensormap [%0];" ::"l"((uint64_t)(tm.px + 1)) : "memory");
        asm volatile("prefetch.tensormap [%0];" ::"l"((uint64_t)(tm.px + 2)) : "memory");
        asm volatile("prefetch.tensormap [%0];" ::"l"((uint64_t)&tm.v14) : "memory");
        asm volatile("prefetch.tensormap [%0];" ::"l"((uint64_t)&tm.u8) : "memory");
      }
      __nanosleep(1600);
      asm volatile("bar.sync 4, 64;" ::: "memory");
      w2o = w2_offset();
      if (elect_one()) {
        mbar_arrive_expect_tx(bar_w2a(bars), kWChunk);
        mbar_arrive_expect_tx(bar_w2(bars), kWChunk);
        sleep_clock(t_start, NAT_TW2);
        bulk_load(sbase + kW2Off, wimg + w2o, kWChunk, bar_w2a(bars));
        mbar_wait(bar_xf(bars), 0);
        bulk_load(sbase + kW2Off + 2 * kWChunk, wimg + (w2o + 2 * kWChunk), kWChunk, bar_w2(bars));
      }
      __syncwarp();
      if (nt < 6) gather_px(x, sbase, decode_tile(tt, tile0 + 2));
      if (wqkv == nullptr) return;
      __nanosleep(2500);
      mbar_wait(bar_wok(bars), 0);
      if (lane == 0) asm volatile("red.relaxed.gpu.global.add.u32 [%0], 1;" ::"l"(g_flag) : "memory");
      if (blockIdx.x != kCtas - 1) return;
#pragma unroll
      for (int i = 0; i < 8; i++) asm volatile("st.shared.v4.u32 [%0], {%1,%1,%1,%1};" ::"r"(bars + 1024 + i * 512 + lane * 16), "r"(kEmpty) : "memory");
      fence_proxy_async();
      __syncwarp();
      if (elect_one()) {
#pragma unroll 1
        for (int i = 0; i < 36; i++) {
          if (i == 18) {
            uint32_t v, it = 0;
            do {
              __nanosleep(500);
              asm volatile("ld.relaxed.gpu.global.u32 %0, [%1];" : "=r"(v) : "l"(g_flag) : "memory");
            } while (v < gridDim.x && ++it < (1u << 18));
          }
          asm volatile("cp.async.bulk.global.shared::cta.bulk_group [%0], [%1], 4096;" ::"l"(
                           wimg + (i < 18 ? 3 * kWBytes - w2o + i * 4096 : (i - 18) * 4096)), "r"(bars + 1024) : "memory");
          asm volatile("cp.async.bulk.commit_group;" ::: "memory");
          asm volatile("cp.async.bulk.wait_group.read 1;" ::: "memory");
        }
        asm volatile("cp.async.bulk.wait_group 0;" ::: "memory");
        g_flag[0] = 0;
        g_flag[32] = w2o == kWBytes;
      }
      return;
    }
    if (!elect_one()) return;
    if (c == 0) {
      for (int i = 0; i < kNumBars; i++)
        if ((i != 0 && i != 10 || nt < 6) && (i != 21 || !w2cta)) mbar_init(bars + i * 8, i == 13 || i == 16 ? 4 : 1);
      asm volatile("st.shared.v2.u32 [%0], {%1,%1};" ::"r"(bars + 192), "r"(0) : "memory");
      asm volatile("fence.mbarrier_init.release.cluster;" ::: "memory");
      if (w2cta) asm volatile("bar.sync 10, 64;" ::: "memory");
      asm volatile("bar.arrive 0, 160;" ::: "memory");
      asm volatile("bar.arrive 14, 160;" ::: "memory");
      asm volatile("bar.arrive 13, 96;" ::: "memory");
      asm volatile("bar.arrive 4, 64;" ::: "memory");
      const TileCoord tc0 = decode_tile(tt, tile0);
      const HaloCols hc = halo_cols(tc0);
      const int h0 = halo_r0(tc0);
#pragma unroll
      for (int j = 0; j < 3; j++)
        if (j > 0 || nt < 6) mbar_arrive_expect_tx(bar_full(bars, 0, j), 2 * kChunkBytes);
      wait_clock(t_start, NAT_HP);
#pragma unroll
      for (int q = 8; q < 24 && !w2cta; q += 8) {
        tma_prefetch_5d(blockIdx.x < 112 ? &tm.v6 : &tm.v14, 24 * tc0.pc + q, hc.vj, hc.vc, tc0.pr, h0 + (tc0.up || blockIdx.x >= 112 ? 0 : 8));
        tma_prefetch_5d(&tm.u8, 24 * tc0.pc + q, hc.uj, h0 + (tc0.up ? 0 : 6), tc0.pr, hc.uc);
      }
#pragma unroll 1
      for (int i = nt < 6 ? 0 : 2; i < 6; i++) {
        if (i == 2) mbar_wait(bar_w1q(bars), 0);
        first_halo(tm, sbase, tc0, i);
      }
      mbar_arrive(bar_go(bars));
      w2o = w2_offset();
    } else {
      asm volatile("bar.sync 13, 96;" ::: "memory");
      if (c == 2) {
        if (wqkv != nullptr && blockIdx.x < 131) asm volatile("bar.sync 12, 64;" ::: "memory");
        const uint32_t c0 = clock();
        while ((uint32_t)clock() - c0 < NAT_TD && nt == 6) { }
        wait_clock(t_start, NAT_T0);
#pragma unroll
        for (int j = 0; j < 3; j++) {
          mbar_arrive_expect_tx(bar_w1c(bars, j), kWChunk);
          bulk_load(sbase + kW1Off + j * kWChunk, wimg + j * kWChunk, kWChunk, bar_w1c(bars, j));
        }
        mbar_arrive(bar_w1q(bars));
        GT(2);
      } else {
#pragma unroll 1
        for (int j = nt == 6; j < 2; j++) {
          const TileCoord tc = decode_tile(tt, tile0 + j);
          const int line = first_line(tc);
          if (j == 1) mbar_wait(bar_go(bars), 0);
          if (j == 0) GT(15);
#pragma unroll 1
          for (int q = 0; q < 3; q++) {
            load_px(tm, tt, sbase + x_chunk(j, q), bar_x(bars, j, q), line + q, tc.kind);
            if (j == 1 || q == 0) mbar_arrive_expect_tx(bar_x(bars, j, q), j ? 8192 : kWChunk);
          }
          if (j == 0) GT(16);
        }
        w2o = w2_offset();
        sleep_clock(t_start, NAT_TW2);
        mbar_wait(bar_xf(bars), 0);
      }
    }
#pragma unroll 1
    for (int k = 1; k < nt; k++) {
      const TileCoord tn = decode_tile(tt, tile0 + k + 1);
      const int line = first_line(tn);
      const bool more = k + 1 < nt && (k > 1 || nt == 6);
      if (c == 1) {
#pragma unroll
        for (int q = 0; q < 3; q++) {
          nb_sync_p(q == 0 ? 0 : q == 1 ? 14 : 6);
          bulk_load(sbase + x_chunk(k, q), wimg + (w2o + x_chunk(k, q) - kW2Off), 8192, bar_w2m(bars));
        }
        mbar_arrive_expect_tx(bar_w2m(bars), kWChunk);
      }
      if (c == 2) {
        if (k == 1) sleep_clock(t_start, NAT_TX2);
        else __nanosleep(NAT_PFD);
#pragma unroll 1
        for (int q = 0; q < 3 && more; q++) load_px(tm, tt, 0, 0, line + q, tn.kind);
      }
      if (c == 2 && (blockIdx.x >= 112 || k == 5)) {
        const TileCoord tc = decode_tile(tt, tile0 + k);
        const HaloCols hc = halo_cols(tc);
        const int h8 = halo_r0(tc) + (tc.up ? 0 : 6);
#pragma unroll 1
        for (int q = 0; q < 24; q += 8) {
          tma_prefetch_5d(&tm.v6, 24 * tc.pc + q, hc.vj, hc.vc, tc.pr, h8);
          tma_prefetch_5d(&tm.v2, 24 * tc.pc + q, hc.vj, hc.vc, tc.pr, h8 + 6);
          tma_prefetch_5d(&tm.u8, 24 * tc.pc + q, hc.uj, h8, tc.pr, hc.uc);
        }
      }
      load_halo(tm, sbase, bars, decode_tile(tt, tile0 + k), k, c);
      if (c == 0 && more) {
        if (nt < 6) mbar_wait(bar_x(bars, 1, 0), 1);
#pragma unroll
        for (int q = 0; q < 3; q++) {
          if (q < 2) nb_sync_p(q ? 5 : 13);
          load_px(tm, tt, sbase + x_chunk(k + 1, q), bar_x(bars, 1, q), line + q, tn.kind);
          if (q != 1) mbar_arrive_expect_tx(bar_x(bars, 1, q), 8192);
        }
        mbar_arrive_expect_tx(bar_x(bars, 1, 1), 8192);
        PROFS(16, 2, k * 4 + 3);
      }
      if (c == 0 && k >= 2) {
        const TileCoord tp = decode_tile(tt, tile0 + k - 2);
        const int lp = first_line(tp);
        nb_sync_p(10);
        __nanosleep(NAT_XW);
        store_px(tm, tt, sbase + out_slot(k, nt), lp, tp.kind);
        if (k + 1 < nt) {
          asm volatile("cp.async.bulk.wait_group.read 0;" ::: "memory");
          bulk_load(sbase + out_slot(k, nt), wimg + (w2o + out_slot(k, nt) - kW2Off), kWChunk, bar_w2(bars));
          mbar_arrive_expect_tx(bar_w2(bars), kWChunk);
        }
      }
    }
    asm volatile("cp.async.bulk.wait_group 0;" ::: "memory");
  } else {
    if ((role & 128) == 0) {
      if ((uint32_t)role - 1024u < 272u && wqkv != nullptr) {
        fold_w1(min(2 * (role & 127) + (wid & 1), (role & 127) + 16), wqkv, wimg);
        if (wid == 4) asm volatile("bar.arrive 12, 64;" ::: "memory");
        if (tid == 128) GT(7);
      }
      sched_fence();
      if (wid == 1 && elect_one()) {
        const TileCoord tc = decode_tile(tt, blockIdx.x * kTilesPerCta);
        mbar_init(bar_x(bars, 0, 0), 1);
        asm volatile("fence.mbarrier_init.release.cluster;" ::: "memory");
        mbar_arrive_expect_tx(bar_x(bars, 0, 0), kWChunk);
        GT(15);
#pragma unroll 1
        for (int q = 0; q < 3; q++) load_px(tm, tt, sbase + x_chunk(0, q), bar_x(bars, 0, 0), first_line(tc) + q, tc.kind);
        GT(16);
      }
      __syncwarp();
      sched_fence();
      if (wid == 2 && elect_one()) {
        const TileCoord tc = decode_tile(tt, blockIdx.x * kTilesPerCta);
        mbar_init(bar_full(bars, 0, 0), 1);
        asm volatile("fence.mbarrier_init.release.cluster;" ::: "memory");
        mbar_arrive_expect_tx(bar_full(bars, 0, 0), 2 * kChunkBytes);
        asm volatile("prefetch.tensormap [%0];" ::"l"((uint64_t)&tm.u8) : "memory");
        GT(17);
        first_halo(tm, sbase, tc, 0);
        first_halo(tm, sbase, tc, 1);
      }
      __syncwarp();
    }
    sched_fence();
    {
      if (blockIdx.x >= 128 && wqkv != nullptr && (wid | 2) == 2 && elect_one())
        asm volatile("cp.async.bulk.prefetch.L2.global [%0], %1;" ::"l"(wid ? wo + (blockIdx.x & 3) * 48 * 192 : wqkv + (blockIdx.x & 3) * 48 * 576),
                     "r"(wid ? 48 * 384 : 48 * 1152) : "memory");
      __syncwarp();
      if (w2cta) {
        const int q = blockIdx.x & 3, h = wid >> 2;
        uint32_t w2o = 0;
        if (wid == 1 && elect_one()) {
          asm volatile("prefetch.tensormap [%0];" ::"l"((uint64_t)&tm.wo) : "memory");
          mbar_init(bar_raw(bars, 0), 1);
          mbar_init(bar_raw(bars, 1), 1);
          asm volatile("fence.mbarrier_init.release.cluster;" ::: "memory");
#pragma unroll
          for (int j = 0; j < 3; j++)
            asm volatile("cp.async.bulk.tensor.3d.shared::cluster.global.tile.mbarrier::complete_tx::bytes [%0], [%1, {%3, %4, %5}], [%2];" ::"r"(
                             j ? sbase + kW2Off + (j - 1) * (kWBytes / 2) : sbase),
                         "l"((uint64_t)(j ? &tm.wo : &tm.wv)), "r"(bar_raw(bars, j >> 1)), "r"(0), "r"(j ? 0 : 64 * q), "r"(j ? 3 * j - 3 : 6) : "memory");
          mbar_arrive_expect_tx(bar_raw(bars, 0), kWChunk + kWBytes / 2);
          mbar_arrive_expect_tx(bar_raw(bars, 1), kWBytes / 2);
          w2o = w2_offset();
        }
        __syncwarp();
#pragma unroll 1
        for (int r = 1 - h;; r++) {
          if (r > 0) asm volatile("bar.sync 11, 256;" ::: "memory");
          if (r == 2) break;
          if (r > 0) {
            mbar_wait(bar_raw(bars, 0), 0);
            mbar_wait(bar_raw(bars, h), 0);
          }
          if (tid == 0) GT(7);
          float acc[48];
          const uint64_t db = make_desc(sbase + kW2Off + h * (kWBytes / 2), kWChunk / 2, 512, 2);
          wg_fence();
          wg_m96tz<0, 48>(acc, make_desc(sbase, 16, 1024), db, 0);
#pragma unroll
          for (int s = 1; s < 12; s++) wg_m96t<0, 48>(acc, make_desc(sbase + (s >> 2) * 8192 + (s & 3) * 32, 16, 1024), db + s * 64, 1);
          wg_commit();
          wg_wait<0>();
          fence_regs(acc);
          if (tid == 0) GT(19);
          const int m = (tid >> 3) & 3;
#pragma unroll
          for (int j = 0; j < 12; j += 2) {
            const int n = g2_inv(8 * (j + (m >> 1)) + (tid & 7));
            asm volatile("stmatrix.sync.aligned.m8n8.x4.trans.shared.b16 [%0], {%1,%2,%3,%4};" ::"r"(
                             sbase + kW1Off + h * (kWChunk / 2) + n * 128 + (((2 * (wid & 3) + (m & 1)) ^ (n & 7)) << 4)),
                         "r"(pack_bf16(acc[4 * j], acc[4 * j + 1])), "r"(pack_bf16(acc[4 * j + 2], acc[4 * j + 3])),
                         "r"(pack_bf16(acc[4 * j + 4], acc[4 * j + 5])), "r"(pack_bf16(acc[4 * j + 6], acc[4 * j + 7])) : "memory");
          }
          fence_proxy_async();
        }
        if (tid == 0) GT(18);
        if (wid == 1) {
          if (elect_one()) {
#pragma unroll
            for (int i = 0; i < 2; i++)
              asm volatile("cp.async.bulk.global.shared::cta.bulk_group [%0], [%1], %2;" ::"l"(wimg + (w2o + w2piece(i, q) * (kWChunk / 2))),
                           "r"(sbase + kW1Off + i * (kWChunk / 2)), "r"(kWChunk / 2) : "memory");
            asm volatile("cp.async.bulk.commit_group;" ::: "memory");
          }
          __syncwarp();
          asm volatile("bar.arrive 10, 64;" ::: "memory");
          if (elect_one()) asm volatile("cp.async.bulk.wait_group.read 0;" ::: "memory");
          if (tid == 32) GT(31);
          __syncwarp();
          asm volatile("bar.arrive 12, 64;" ::: "memory");
        }
      }
    }
    __syncwarp();
    if (wid < 4) asm volatile("bar.sync 0, 160;" ::: "memory");
    else asm volatile("bar.sync 14, 160;" ::: "memory");
    asm volatile("setmaxnreg.inc.sync.aligned.u32 240;");
    consumer(wid >> 2, out, wimg, sbase, zero, tm, tt);
  }
}

}

typedef CUresult (*PFN_encodeTiled)(CUtensorMap*, CUtensorMapDataType, cuuint32_t, void*, const cuuint64_t*,
                                    const cuuint64_t*, const cuuint32_t*, const cuuint32_t*, CUtensorMapInterleave,
                                    CUtensorMapSwizzle, CUtensorMapL2promotion, CUtensorMapFloatOOBfill);

extern "C" void kernel_launch(void* const* d_in, const int* in_sizes, int n_in, void* d_out, int out_size) {
  const __nv_bfloat16* x = (const __nv_bfloat16*)d_in[0];
  const __nv_bfloat16* wqkv = (const __nv_bfloat16*)d_in[1];
  const __nv_bfloat16* wo = (const __nv_bfloat16*)d_in[2];
  __nv_bfloat16* out = (__nv_bfloat16*)d_out;

  static PFN_encodeTiled encode = nullptr;
  static int num_sms = 0;
  static uint8_t* wimg = nullptr;
  if (!encode) {
    void* fn = nullptr;
    cudaDriverEntryPointQueryResult qres;
    cudaGetDriverEntryPoint("cuTensorMapEncodeTiled", &fn, cudaEnableDefault, &qres);
    encode = (PFN_encodeTiled)fn;
    cudaFuncSetAttribute(nat::nat_kernel, cudaFuncAttributeMaxDynamicSharedMemorySize, nat::kSmemBytes);
    cudaGetSymbolAddress((void**)&wimg, nat::g_wimg32);
    int dev = 0;
    cudaGetDevice(&dev);
    cudaDeviceGetAttribute(&num_sms, cudaDevAttrMultiProcessorCount, dev);
  }
  nat::Maps tm;
  cuuint32_t estr[5] = {1, 1, 1, 1, 1};
  {
    cuuint64_t vdim[5] = {48, 2, 105, 2, 112}, udim[5] = {48, 2, 112, 2, 105};
    cuuint64_t vstr[4] = {7 * 768, 768, 224 * 384, 2 * 224 * 384}, ustr[4] = {7 * 768, 2 * 224 * 384, 224 * 384, 768};
    CUtensorMap* maps[4] = {&tm.v6, &tm.v2, &tm.v14, &tm.u8};
    for (int i = 0; i < 4; i++) {
      cuuint32_t box[5] = {4, 2, i < 3 ? 4u : 8u, 1, i == 0 ? 6u : i == 1 ? 2u : i == 2 ? 14u : 3u};
      encode(maps[i], CU_TENSOR_MAP_DATA_TYPE_UINT32, 5, (void*)x, i < 3 ? vdim : udim, i < 3 ? vstr : ustr, box, estr,
             CU_TENSOR_MAP_INTERLEAVE_16B, CU_TENSOR_MAP_SWIZZLE_128B, CU_TENSOR_MAP_L2_PROMOTION_L2_128B, CU_TENSOR_MAP_FLOAT_OOB_FILL_NONE);
    }
  }
  for (int i = 0; i < 8; i++) {
    const cuuint32_t row = 224 * 384;
    const cuuint32_t shape[8][6] = {{2, 8, 4, 2 * row, 768, 4 * row}, {2, 8, 3, row, 768, 2 * row},     {2, 8, 1, 2 * row, 768, 4 * row},
                                    {8, 2, 3, 2 * row, 4 * 384, 384}, {8, 2, 1, 2 * row, 5 * 384, 384}, {4, 2, 3, 4 * row, 2 * row, 128},
                                    {4, 2, 3, 768, row, 128},         {4, 2, 3, 768, 2 * row, 128}};
    const cuuint32_t* sh = shape[i];
    cuuint64_t dim[5] = {64, sh[0], sh[1], sh[2], 224 * 224 * 3};
    cuuint64_t str[4] = {sh[3], sh[4], sh[5], 128};
    cuuint32_t box[5] = {64, sh[0], sh[1], sh[2], 1};
    encode(tm.px + i, CU_TENSOR_MAP_DATA_TYPE_BFLOAT16, 5, i < 5 ? (void*)x : (void*)out, dim, str, box, estr, CU_TENSOR_MAP_INTERLEAVE_NONE,
           CU_TENSOR_MAP_SWIZZLE_128B, i < 5 ? CU_TENSOR_MAP_L2_PROMOTION_L2_128B : CU_TENSOR_MAP_L2_PROMOTION_NONE,
           CU_TENSOR_MAP_FLOAT_OOB_FILL_NONE);
  }
  for (int i = 0; i < 2; i++) {
    cuuint64_t dim[3] = {i ? 32u : 64u, 192, i ? 6u : 9u}, str[2] = {i ? 384u : 1152u, i ? 64u : 128u};
    cuuint32_t box[3] = {i ? 32u : 64u, i ? 192u : 64u, 3};
    encode(i ? &tm.wo : &tm.wv, CU_TENSOR_MAP_DATA_TYPE_BFLOAT16, 3, i ? (void*)wo : (void*)wqkv, dim, str, box, estr,
           CU_TENSOR_MAP_INTERLEAVE_NONE, i ? CU_TENSOR_MAP_SWIZZLE_64B : CU_TENSOR_MAP_SWIZZLE_128B, CU_TENSOR_MAP_L2_PROMOTION_L2_256B,
           CU_TENSOR_MAP_FLOAT_OOB_FILL_NONE);
  }
  nat::TileTable tt;
  nat::make_tiles(tt);
  const int grid = nat::kCtas;
  if (num_sms >= grid) {
    nat::nat_kernel<<<grid, 384, nat::kSmemBytes>>>(x, out, wqkv, wo, wimg, 0u, tm, tt);
  } else {
    nat::fold_kernel<<<27, 256>>>(wqkv, wo, wimg);
    nat::nat_kernel<<<grid, 384, nat::kSmemBytes>>>(x, out, nullptr, nullptr, wimg, 0u, tm, tt);
  }
}
```

```cpp
#include <cuda_runtime.h>
#include <cuda_bf16.h>
#include <cuda.h>
#include <stdint.h>

#define NAT_TM 1300
#define NAT_HP 1800
#define NAT_T0 2130
#define NAT_TD 1250
#define NAT_TX2 3800
#define NAT_TW2 4600
#define NAT_PFD 300
#define NAT_XW 200
#define NAT_PK 3
namespace nat {

constexpr int kW = 224, kC = 192;
constexpr int kCtas = 132;
constexpr int kTilesPerCta = 6;
constexpr float kAlpha = 0.07216878364870322f * 1.4426950408889634f;
constexpr uint32_t kChunkBytes = 13 * 1024;
constexpr uint32_t kWChunk = 192 * 128;
constexpr uint32_t kWBytes = 3 * kWChunk;
constexpr uint32_t kW1Off = 6 * kChunkBytes;
constexpr uint32_t kW2Off = kW1Off + kWBytes;
constexpr uint32_t kXOff = kW2Off + kWChunk;
constexpr uint32_t kBarOff = kW2Off + kWBytes;
constexpr uint32_t kProfOff = kBarOff + 208;
constexpr uint32_t kSmemBytes = kBarOff + 1024 + 4096;

static_assert(kW1Off % 1024 == 0 && kW2Off % 1024 == 0 && kChunkBytes % 1024 == 0, "swizzle alignment");
static_assert(kSmemBytes <= 232448, "smem");

constexpr uint32_t kEmpty = 0xFFFFFFFFu;
#define NAT_R8(v) v, v, v, v, v, v, v, v
#define NAT_R2K(v) NAT_R8(NAT_R8(NAT_R8(v))), NAT_R8(NAT_R8(NAT_R8(v))), NAT_R8(NAT_R8(NAT_R8(v))), NAT_R8(NAT_R8(NAT_R8(v)))
#define NAT_IMG NAT_R8(NAT_R2K(kEmpty)), NAT_R2K(kEmpty)
__device__ __align__(1024) uint32_t g_wimg32[3 * kWBytes / 4] = {NAT_IMG, NAT_IMG, NAT_IMG};
static_assert(kWBytes / 4 == 9 * 2048, "initialiser");
__device__ __align__(128) uint32_t g_flag[64];
__device__ __forceinline__ uint32_t w2_offset() {
  uint32_t v;
  asm volatile("ld.relaxed.gpu.global.u32 %0, [%1];" : "=r"(v) : "l"(g_flag + 32) : "memory");
  return (1 + v) * kWBytes;
}

#define PROFS(id, wgid, slotid) do { } while (0)
#define PROF(wgid, slotid) do { } while (0)
#define PROF_DUMP(wgid) do { } while (0)

#define GT(slotid) do { } while (0)
#define GT_DUMP() do { } while (0)

__device__ __forceinline__ uint32_t smem_u32(const void* p) { return (uint32_t)__cvta_generic_to_shared(p); }

__device__ __forceinline__ void mbar_init(uint32_t bar, uint32_t count) {
  asm volatile("mbarrier.init.shared::cta.b64 [%0], %1;" ::"r"(bar), "r"(count) : "memory");
}
__device__ __forceinline__ void mbar_arrive(uint32_t bar) {
  asm volatile("mbarrier.arrive.shared::cta.b64 _, [%0];" ::"r"(bar) : "memory");
}
__device__ __forceinline__ void mbar_arrive_expect_tx(uint32_t bar, uint32_t bytes) {
  asm volatile("mbarrier.arrive.expect_tx.shared::cta.b64 _, [%0], %1;" ::"r"(bar), "r"(bytes) : "memory");
}
__device__ __forceinline__ void mbar_wait(uint32_t bar, uint32_t parity) {
  uint32_t ok;
  uint32_t it = 0;
  do {
    asm volatile(
        "{\n.reg .pred p;\n"
        "mbarrier.try_wait.parity.shared::cta.b64 p, [%1], %2;\n"
        "selp.u32 %0, 1, 0, p;\n}\n"
        : "=r"(ok)
        : "r"(bar), "r"(parity)
        : "memory");
    if (++it > (1u << 24)) break;
  } while (!ok);
}
__device__ __forceinline__ uint32_t mbar_test(uint32_t bar, uint32_t parity) {
  uint32_t ok;
  asm volatile("{\n.reg .pred p;\nmbarrier.test_wait.parity.shared::cta.b64 p, [%1], %2;\nselp.u32 %0, 1, 0, p;\n}\n"
               : "=r"(ok) : "r"(bar), "r"(parity) : "memory");
  return ok;
}
__device__ __forceinline__ void mbar_wait_if(uint32_t ok, uint32_t bar, uint32_t parity) {
  if (!__all_sync(0xffffffffu, ok)) mbar_wait(bar, parity);
}
__device__ __forceinline__ bool elect_one() {
  uint32_t r;
  asm volatile("{\n.reg .pred p;\nelect.sync _|p, 0xffffffff;\nselp.u32 %0, 1, 0, p;\n}\n" : "=r"(r));
  return r != 0;
}
__device__ __forceinline__ void nb_arrive(int id) { asm volatile("bar.arrive %0, 256;" ::"r"(id) : "memory"); }
__device__ __forceinline__ void nb_sync(int id) { asm volatile("bar.sync %0, 256;" ::"r"(id) : "memory"); }
__device__ __forceinline__ void nb_arrive_p(int id) { asm volatile("bar.arrive %0, 160;" ::"r"(id) : "memory"); }
__device__ __forceinline__ void nb_sync_p(int id) { asm volatile("bar.sync %0, 160;" ::"r"(id) : "memory"); }
__device__ __forceinline__ void fence_proxy_async() { asm volatile("fence.proxy.async.shared::cta;" ::: "memory"); }

__device__ __forceinline__ void tma_load_5d(uint32_t dst, const CUtensorMap* map, uint32_t bar, int c0, int c1, int c2,
                                            int c3, int c4) {
  asm volatile(
      "cp.async.bulk.tensor.5d.shared::cluster.global.tile.mbarrier::complete_tx::bytes "
      "[%0], [%1, {%3, %4, %5, %6, %7}], [%2];"
      ::"r"(dst), "l"((uint64_t)map), "r"(bar), "r"(c0), "r"(c1), "r"(c2), "r"(c3), "r"(c4)
      : "memory");
}
__device__ __forceinline__ void bulk_load(uint32_t dst, const void* src, uint32_t bytes, uint32_t bar) {
  asm volatile("cp.async.bulk.shared::cluster.global.mbarrier::complete_tx::bytes [%0], [%1], %2, [%3];"
               ::"r"(dst), "l"((uint64_t)src), "r"(bytes), "r"(bar)
               : "memory");
}

__device__ __forceinline__ void wg_fence() { asm volatile("wgmma.fence.sync.aligned;" ::: "memory"); }
__device__ __forceinline__ void wg_commit() { asm volatile("wgmma.commit_group.sync.aligned;" ::: "memory"); }
template <int N>
__device__ __forceinline__ void wg_wait() { asm volatile("wgmma.wait_group.sync.aligned %0;" ::"n"(N) : "memory"); }

template <int N>
__device__ __forceinline__ void fence_regs(float (&d)[N]) {
#pragma unroll
  for (int i = 0; i < N; i++) asm volatile("" : "+f"(d[i])::"memory");
}
template <int N>
__device__ __forceinline__ void keep_regs(uint32_t (&d)[N]) {
#pragma unroll
  for (int i = 0; i < N; i++) asm volatile("" : "+r"(d[i])::"memory");
}

__device__ __forceinline__ uint32_t pack_bf16(float lo, float hi) {
  uint32_t d;
  asm("cvt.rn.bf16x2.f32 %0, %1, %2;" : "=r"(d) : "f"(hi), "f"(lo));
  return d;
}
__device__ __forceinline__ float ex2(float x) {
  float y;
  asm("ex2.approx.ftz.f32 %0, %1;" : "=f"(y) : "f"(x));
  return y;
}
__device__ __forceinline__ float rcp_approx(float x) {
  float y;
  asm("rcp.approx.ftz.f32 %0, %1;" : "=f"(y) : "f"(x));
  return y;
}
__device__ __forceinline__ uint4 ldg128_nc(const void* p) {
  uint4 v;
  asm volatile("ld.global.nc.v4.u32 {%0,%1,%2,%3}, [%4];" : "=r"(v.x), "=r"(v.y), "=r"(v.z), "=r"(v.w) : "l"(p));
  return v;
}

__device__ __forceinline__ long long clk64() {
  long long c;
  asm volatile("mov.u64 %0, %clock64;" : "=l"(c)::"memory");
  return c;
}
__device__ __forceinline__ void sched_fence() { while (clk64() < 0) { } }

__device__ __forceinline__ uint64_t make_desc(uint32_t addr, uint32_t lbo, uint32_t sbo, uint32_t mode = 1) {
  return (uint64_t)((addr & 0x3FFFF) >> 4) | ((uint64_t)(lbo >> 4) << 16) | ((uint64_t)(sbo >> 4) << 32) |
         ((uint64_t)mode << 62);
}

template <int OFF, int NN>
__device__ __forceinline__ void wg_m192(float (&d)[NN], uint64_t desc_a, uint64_t desc_b, int scale_d) {
  asm volatile(
      "{\n.reg .pred p;\nsetp.ne.b32 p, %98, 0;\n"
      "wgmma.mma_async.sync.aligned.m64n192k16.f32.bf16.bf16 "
      "{%0,%1,%2,%3,%4,%5,%6,%7,%8,%9,%10,%11,%12,%13,%14,%15,"
      "%16,%17,%18,%19,%20,%21,%22,%23,%24,%25,%26,%27,%28,%29,%30,%31,"
      "%32,%33,%34,%35,%36,%37,%38,%39,%40,%41,%42,%43,%44,%45,%46,%47,"
      "%48,%49,%50,%51,%52,%53,%54,%55,%56,%57,%58,%59,%60,%61,%62,%63,"
      "%64,%65,%66,%67,%68,%69,%70,%71,%72,%73,%74,%75,%76,%77,%78,%79,"
      "%80,%81,%82,%83,%84,%85,%86,%87,%88,%89,%90,%91,%92,%93,%94,%95}, "
      "%96, %97, p, 1, 1, 0, 0;\n}\n"
      : "+f"(d[OFF + 0]), "+f"(d[OFF + 1]), "+f"(d[OFF + 2]), "+f"(d[OFF + 3]), "+f"(d[OFF + 4]), "+f"(d[OFF + 5]),
        "+f"(d[OFF + 6]), "+f"(d[OFF + 7]), "+f"(d[OFF + 8]), "+f"(d[OFF + 9]), "+f"(d[OFF + 10]), "+f"(d[OFF + 11]),
        "+f"(d[OFF + 12]), "+f"(d[OFF + 13]), "+f"(d[OFF + 14]), "+f"(d[OFF + 15]), "+f"(d[OFF + 16]), "+f"(d[OFF + 17]),
        "+f"(d[OFF + 18]), "+f"(d[OFF + 19]), "+f"(d[OFF + 20]), "+f"(d[OFF + 21]), "+f"(d[OFF + 22]), "+f"(d[OFF + 23]),
        "+f"(d[OFF + 24]), "+f"(d[OFF + 25]), "+f"(d[OFF + 26]), "+f"(d[OFF + 27]), "+f"(d[OFF + 28]), "+f"(d[OFF + 29]),
        "+f"(d[OFF + 30]), "+f"(d[OFF + 31]), "+f"(d[OFF + 32]), "+f"(d[OFF + 33]), "+f"(d[OFF + 34]), "+f"(d[OFF + 35]),
        "+f"(d[OFF + 36]), "+f"(d[OFF + 37]), "+f"(d[OFF + 38]), "+f"(d[OFF + 39]), "+f"(d[OFF + 40]), "+f"(d[OFF + 41]),
        "+f"(d[OFF + 42]), "+f"(d[OFF + 43]), "+f"(d[OFF + 44]), "+f"(d[OFF + 45]), "+f"(d[OFF + 46]), "+f"(d[OFF + 47]),
        "+f"(d[OFF + 48]), "+f"(d[OFF + 49]), "+f"(d[OFF + 50]), "+f"(d[OFF + 51]), "+f"(d[OFF + 52]), "+f"(d[OFF + 53]),
        "+f"(d[OFF + 54]), "+f"(d[OFF + 55]), "+f"(d[OFF + 56]), "+f"(d[OFF + 57]), "+f"(d[OFF + 58]), "+f"(d[OFF + 59]),
        "+f"(d[OFF + 60]), "+f"(d[OFF + 61]), "+f"(d[OFF + 62]), "+f"(d[OFF + 63]), "+f"(d[OFF + 64]), "+f"(d[OFF + 65]),
        "+f"(d[OFF + 66]), "+f"(d[OFF + 67]), "+f"(d[OFF + 68]), "+f"(d[OFF + 69]), "+f"(d[OFF + 70]), "+f"(d[OFF + 71]),
        "+f"(d[OFF + 72]), "+f"(d[OFF + 73]), "+f"(d[OFF + 74]), "+f"(d[OFF + 75]), "+f"(d[OFF + 76]), "+f"(d[OFF + 77]),
        "+f"(d[OFF + 78]), "+f"(d[OFF + 79]), "+f"(d[OFF + 80]), "+f"(d[OFF + 81]), "+f"(d[OFF + 82]), "+f"(d[OFF + 83]),
        "+f"(d[OFF + 84]), "+f"(d[OFF + 85]), "+f"(d[OFF + 86]), "+f"(d[OFF + 87]), "+f"(d[OFF + 88]), "+f"(d[OFF + 89]),
        "+f"(d[OFF + 90]), "+f"(d[OFF + 91]), "+f"(d[OFF + 92]), "+f"(d[OFF + 93]), "+f"(d[OFF + 94]), "+f"(d[OFF + 95])
      : "l"(desc_a), "l"(desc_b), "r"(scale_d));
}

template <int OFF, int NN>
__device__ __forceinline__ void wg_m192z(float (&d)[NN], uint64_t desc_a, uint64_t desc_b, int scale_d) {
  asm volatile(
      "{\n.reg .pred p;\nsetp.ne.b32 p, %98, 0;\n"
      "wgmma.mma_async.sync.aligned.m64n192k16.f32.bf16.bf16 "
      "{%0,%1,%2,%3,%4,%5,%6,%7,%8,%9,%10,%11,%12,%13,%14,%15,"
      "%16,%17,%18,%19,%20,%21,%22,%23,%24,%25,%26,%27,%28,%29,%30,%31,"
      "%32,%33,%34,%35,%36,%37,%38,%39,%40,%41,%42,%43,%44,%45,%46,%47,"
      "%48,%49,%50,%51,%52,%53,%54,%55,%56,%57,%58,%59,%60,%61,%62,%63,"
      "%64,%65,%66,%67,%68,%69,%70,%71,%72,%73,%74,%75,%76,%77,%78,%79,"
      "%80,%81,%82,%83,%84,%85,%86,%87,%88,%89,%90,%91,%92,%93,%94,%95}, "
      "%96, %97, p, 1, 1, 0, 0;\n}\n"
      : "=f"(d[OFF + 0]), "=f"(d[OFF + 1]), "=f"(d[OFF + 2]), "=f"(d[OFF + 3]), "=f"(d[OFF + 4]), "=f"(d[OFF + 5]),
        "=f"(d[OFF + 6]), "=f"(d[OFF + 7]), "=f"(d[OFF + 8]), "=f"(d[OFF + 9]), "=f"(d[OFF + 10]), "=f"(d[OFF + 11]),
        "=f"(d[OFF + 12]), "=f"(d[OFF + 13]), "=f"(d[OFF + 14]), "=f"(d[OFF + 15]), "=f"(d[OFF + 16]), "=f"(d[OFF + 17]),
        "=f"(d[OFF + 18]), "=f"(d[OFF + 19]), "=f"(d[OFF + 20]), "=f"(d[OFF + 21]), "=f"(d[OFF + 22]), "=f"(d[OFF + 23]),
        "=f"(d[OFF + 24]), "=f"(d[OFF + 25]), "=f"(d[OFF + 26]), "=f"(d[OFF + 27]), "=f"(d[OFF + 28]), "=f"(d[OFF + 29]),
        "=f"(d[OFF + 30]), "=f"(d[OFF + 31]), "=f"(d[OFF + 32]), "=f"(d[OFF + 33]), "=f"(d[OFF + 34]), "=f"(d[OFF + 35]),
        "=f"(d[OFF + 36]), "=f"(d[OFF + 37]), "=f"(d[OFF + 38]), "=f"(d[OFF + 39]), "=f"(d[OFF + 40]), "=f"(d[OFF + 41]),
        "=f"(d[OFF + 42]), "=f"(d[OFF + 43]), "=f"(d[OFF + 44]), "=f"(d[OFF + 45]), "=f"(d[OFF + 46]), "=f"(d[OFF + 47]),
        "=f"(d[OFF + 48]), "=f"(d[OFF + 49]), "=f"(d[OFF + 50]), "=f"(d[OFF + 51]), "=f"(d[OFF + 52]), "=f"(d[OFF + 53]),
        "=f"(d[OFF + 54]), "=f"(d[OFF + 55]), "=f"(d[OFF + 56]), "=f"(d[OFF + 57]), "=f"(d[OFF + 58]), "=f"(d[OFF + 59]),
        "=f"(d[OFF + 60]), "=f"(d[OFF + 61]), "=f"(d[OFF + 62]), "=f"(d[OFF + 63]), "=f"(d[OFF + 64]), "=f"(d[OFF + 65]),
        "=f"(d[OFF + 66]), "=f"(d[OFF + 67]), "=f"(d[OFF + 68]), "=f"(d[OFF + 69]), "=f"(d[OFF + 70]), "=f"(d[OFF + 71]),
        "=f"(d[OFF + 72]), "=f"(d[OFF + 73]), "=f"(d[OFF + 74]), "=f"(d[OFF + 75]), "=f"(d[OFF + 76]), "=f"(d[OFF + 77]),
        "=f"(d[OFF + 78]), "=f"(d[OFF + 79]), "=f"(d[OFF + 80]), "=f"(d[OFF + 81]), "=f"(d[OFF + 82]), "=f"(d[OFF + 83]),
        "=f"(d[OFF + 84]), "=f"(d[OFF + 85]), "=f"(d[OFF + 86]), "=f"(d[OFF + 87]), "=f"(d[OFF + 88]), "=f"(d[OFF + 89]),
        "=f"(d[OFF + 90]), "=f"(d[OFF + 91]), "=f"(d[OFF + 92]), "=f"(d[OFF + 93]), "=f"(d[OFF + 94]), "=f"(d[OFF + 95])
      : "l"(desc_a), "l"(desc_b), "r"(scale_d));
}

template <int OFF, int NN>
__device__ __forceinline__ void wg_m96t(float (&d)[NN], uint64_t desc_a, uint64_t desc_b, int scale_d) {
  asm volatile(
      "{\n.reg .pred p;\nsetp.ne.b32 p, %50, 0;\n"
      "wgmma.mma_async.sync.aligned.m64n96k16.f32.bf16.bf16 "
      "{%0,%1,%2,%3,%4,%5,%6,%7,%8,%9,%10,%11,%12,%13,%14,%15,"
      "%16,%17,%18,%19,%20,%21,%22,%23,%24,%25,%26,%27,%28,%29,%30,%31,"
      "%32,%33,%34,%35,%36,%37,%38,%39,%40,%41,%42,%43,%44,%45,%46,%47}, "
      "%48, %49, p, 1, 1, 0, 1;\n}\n"
      : "+f"(d[OFF + 0]), "+f"(d[OFF + 1]), "+f"(d[OFF + 2]), "+f"(d[OFF + 3]), "+f"(d[OFF + 4]), "+f"(d[OFF + 5]),
        "+f"(d[OFF + 6]), "+f"(d[OFF + 7]), "+f"(d[OFF + 8]), "+f"(d[OFF + 9]), "+f"(d[OFF + 10]), "+f"(d[OFF + 11]),
        "+f"(d[OFF + 12]), "+f"(d[OFF + 13]), "+f"(d[OFF + 14]), "+f"(d[OFF + 15]), "+f"(d[OFF + 16]), "+f"(d[OFF + 17]),
        "+f"(d[OFF + 18]), "+f"(d[OFF + 19]), "+f"(d[OFF + 20]), "+f"(d[OFF + 21]), "+f"(d[OFF + 22]), "+f"(d[OFF + 23]),
        "+f"(d[OFF + 24]), "+f"(d[OFF + 25]), "+f"(d[OFF + 26]), "+f"(d[OFF + 27]), "+f"(d[OFF + 28]), "+f"(d[OFF + 29]),
        "+f"(d[OFF + 30]), "+f"(d[OFF + 31]), "+f"(d[OFF + 32]), "+f"(d[OFF + 33]), "+f"(d[OFF + 34]), "+f"(d[OFF + 35]),
        "+f"(d[OFF + 36]), "+f"(d[OFF + 37]), "+f"(d[OFF + 38]), "+f"(d[OFF + 39]), "+f"(d[OFF + 40]), "+f"(d[OFF + 41]),
        "+f"(d[OFF + 42]), "+f"(d[OFF + 43]), "+f"(d[OFF + 44]), "+f"(d[OFF + 45]), "+f"(d[OFF + 46]), "+f"(d[OFF + 47])
      : "l"(desc_a), "l"(desc_b), "r"(scale_d));
}

template <int OFF, int NN>
__device__ __forceinline__ void wg_m96tz(float (&d)[NN], uint64_t desc_a, uint64_t desc_b, int scale_d) {
  asm volatile(
      "{\n.reg .pred p;\nsetp.ne.b32 p, %50, 0;\n"
      "wgmma.mma_async.sync.aligned.m64n96k16.f32.bf16.bf16 "
      "{%0,%1,%2,%3,%4,%5,%6,%7,%8,%9,%10,%11,%12,%13,%14,%15,"
      "%16,%17,%18,%19,%20,%21,%22,%23,%24,%25,%26,%27,%28,%29,%30,%31,"
      "%32,%33,%34,%35,%36,%37,%38,%39,%40,%41,%42,%43,%44,%45,%46,%47}, "
      "%48, %49, p, 1, 1, 0, 1;\n}\n"
      : "=f"(d[OFF + 0]), "=f"(d[OFF + 1]), "=f"(d[OFF + 2]), "=f"(d[OFF + 3]), "=f"(d[OFF + 4]), "=f"(d[OFF + 5]),
        "=f"(d[OFF + 6]), "=f"(d[OFF + 7]), "=f"(d[OFF + 8]), "=f"(d[OFF + 9]), "=f"(d[OFF + 10]), "=f"(d[OFF + 11]),
        "=f"(d[OFF + 12]), "=f"(d[OFF + 13]), "=f"(d[OFF + 14]), "=f"(d[OFF + 15]), "=f"(d[OFF + 16]), "=f"(d[OFF + 17]),
        "=f"(d[OFF + 18]), "=f"(d[OFF + 19]), "=f"(d[OFF + 20]), "=f"(d[OFF + 21]), "=f"(d[OFF + 22]), "=f"(d[OFF + 23]),
        "=f"(d[OFF + 24]), "=f"(d[OFF + 25]), "=f"(d[OFF + 26]), "=f"(d[OFF + 27]), "=f"(d[OFF + 28]), "=f"(d[OFF + 29]),
        "=f"(d[OFF + 30]), "=f"(d[OFF + 31]), "=f"(d[OFF + 32]), "=f"(d[OFF + 33]), "=f"(d[OFF + 34]), "=f"(d[OFF + 35]),
        "=f"(d[OFF + 36]), "=f"(d[OFF + 37]), "=f"(d[OFF + 38]), "=f"(d[OFF + 39]), "=f"(d[OFF + 40]), "=f"(d[OFF + 41]),
        "=f"(d[OFF + 42]), "=f"(d[OFF + 43]), "=f"(d[OFF + 44]), "=f"(d[OFF + 45]), "=f"(d[OFF + 46]), "=f"(d[OFF + 47])
      : "l"(desc_a), "l"(desc_b), "r"(scale_d));
}

template <int OFF, int NN>
__device__ __forceinline__ void wg_d96(float (&d)[NN], uint32_t a0, uint32_t a1, uint32_t a2, uint32_t a3,
                                       uint64_t desc_b, int scale_d) {
  asm volatile(
      "{\n.reg .pred p;\nsetp.ne.b32 p, %53, 0;\n"
      "wgmma.mma_async.sync.aligned.m64n96k16.f32.bf16.bf16 "
      "{%0,%1,%2,%3,%4,%5,%6,%7,%8,%9,%10,%11,%12,%13,%14,%15,"
      "%16,%17,%18,%19,%20,%21,%22,%23,%24,%25,%26,%27,%28,%29,%30,%31,"
      "%32,%33,%34,%35,%36,%37,%38,%39,%40,%41,%42,%43,%44,%45,%46,%47}, "
      "{%48,%49,%50,%51}, %52, p, 1, 1, 0;\n}\n"
      : "+f"(d[OFF + 0]), "+f"(d[OFF + 1]), "+f"(d[OFF + 2]), "+f"(d[OFF + 3]), "+f"(d[OFF + 4]), "+f"(d[OFF + 5]),
        "+f"(d[OFF + 6]), "+f"(d[OFF + 7]), "+f"(d[OFF + 8]), "+f"(d[OFF + 9]), "+f"(d[OFF + 10]), "+f"(d[OFF + 11]),
        "+f"(d[OFF + 12]), "+f"(d[OFF + 13]), "+f"(d[OFF + 14]), "+f"(d[OFF + 15]), "+f"(d[OFF + 16]), "+f"(d[OFF + 17]),
        "+f"(d[OFF + 18]), "+f"(d[OFF + 19]), "+f"(d[OFF + 20]), "+f"(d[OFF + 21]), "+f"(d[OFF + 22]), "+f"(d[OFF + 23]),
        "+f"(d[OFF + 24]), "+f"(d[OFF + 25]), "+f"(d[OFF + 26]), "+f"(d[OFF + 27]), "+f"(d[OFF + 28]), "+f"(d[OFF + 29]),
        "+f"(d[OFF + 30]), "+f"(d[OFF + 31]), "+f"(d[OFF + 32]), "+f"(d[OFF + 33]), "+f"(d[OFF + 34]), "+f"(d[OFF + 35]),
        "+f"(d[OFF + 36]), "+f"(d[OFF + 37]), "+f"(d[OFF + 38]), "+f"(d[OFF + 39]), "+f"(d[OFF + 40]), "+f"(d[OFF + 41]),
        "+f"(d[OFF + 42]), "+f"(d[OFF + 43]), "+f"(d[OFF + 44]), "+f"(d[OFF + 45]), "+f"(d[OFF + 46]), "+f"(d[OFF + 47])
      : "r"(a0), "r"(a1), "r"(a2), "r"(a3), "l"(desc_b), "r"(scale_d));
}

template <int OFF, int NN>
__device__ __forceinline__ void wg_d96z(float (&d)[NN], uint32_t a0, uint32_t a1, uint32_t a2, uint32_t a3,
                                       uint64_t desc_b, int scale_d) {
  asm volatile(
      "{\n.reg .pred p;\nsetp.ne.b32 p, %53, 0;\n"
      "wgmma.mma_async.sync.aligned.m64n96k16.f32.bf16.bf16 "
      "{%0,%1,%2,%3,%4,%5,%6,%7,%8,%9,%10,%11,%12,%13,%14,%15,"
      "%16,%17,%18,%19,%20,%21,%22,%23,%24,%25,%26,%27,%28,%29,%30,%31,"
      "%32,%33,%34,%35,%36,%37,%38,%39,%40,%41,%42,%43,%44,%45,%46,%47}, "
      "{%48,%49,%50,%51}, %52, p, 1, 1, 0;\n}\n"
      : "=f"(d[OFF + 0]), "=f"(d[OFF + 1]), "=f"(d[OFF + 2]), "=f"(d[OFF + 3]), "=f"(d[OFF + 4]), "=f"(d[OFF + 5]),
        "=f"(d[OFF + 6]), "=f"(d[OFF + 7]), "=f"(d[OFF + 8]), "=f"(d[OFF + 9]), "=f"(d[OFF + 10]), "=f"(d[OFF + 11]),
        "=f"(d[OFF + 12]), "=f"(d[OFF + 13]), "=f"(d[OFF + 14]), "=f"(d[OFF + 15]), "=f"(d[OFF + 16]), "=f"(d[OFF + 17]),
        "=f"(d[OFF + 18]), "=f"(d[OFF + 19]), "=f"(d[OFF + 20]), "=f"(d[OFF + 21]), "=f"(d[OFF + 22]), "=f"(d[OFF + 23]),
        "=f"(d[OFF + 24]), "=f"(d[OFF + 25]), "=f"(d[OFF + 26]), "=f"(d[OFF + 27]), "=f"(d[OFF + 28]), "=f"(d[OFF + 29]),
        "=f"(d[OFF + 30]), "=f"(d[OFF + 31]), "=f"(d[OFF + 32]), "=f"(d[OFF + 33]), "=f"(d[OFF + 34]), "=f"(d[OFF + 35]),
        "=f"(d[OFF + 36]), "=f"(d[OFF + 37]), "=f"(d[OFF + 38]), "=f"(d[OFF + 39]), "=f"(d[OFF + 40]), "=f"(d[OFF + 41]),
        "=f"(d[OFF + 42]), "=f"(d[OFF + 43]), "=f"(d[OFF + 44]), "=f"(d[OFF + 45]), "=f"(d[OFF + 46]), "=f"(d[OFF + 47])
      : "r"(a0), "r"(a1), "r"(a2), "r"(a3), "l"(desc_b), "r"(scale_d));
}

template <int OFF, int NN>
__device__ __forceinline__ void wg_s104(float (&d)[NN], uint32_t a0, uint32_t a1, uint32_t a2, uint32_t a3,
                                       uint64_t desc_b, int scale_d, uint32_t meta) {
  asm volatile(
      "{\n.reg .pred p;\nsetp.ne.b32 p, %57, 0;\n"
      "wgmma.mma_async.sp.sync.aligned.m64n104k32.f32.bf16.bf16 "
      "{%0,%1,%2,%3,%4,%5,%6,%7,%8,%9,%10,%11,%12,%13,%14,%15,"
      "%16,%17,%18,%19,%20,%21,%22,%23,%24,%25,%26,%27,%28,%29,%30,%31,"
      "%32,%33,%34,%35,%36,%37,%38,%39,%40,%41,%42,%43,%44,%45,%46,%47,"
      "%48,%49,%50,%51}, "
      "{%52,%53,%54,%55}, %56, %58, 0, p, 1, 1, 0;\n}\n"
      : "+f"(d[OFF + 0]), "+f"(d[OFF + 1]), "+f"(d[OFF + 2]), "+f"(d[OFF + 3]), "+f"(d[OFF + 4]), "+f"(d[OFF + 5]),
        "+f"(d[OFF + 6]), "+f"(d[OFF + 7]), "+f"(d[OFF + 8]), "+f"(d[OFF + 9]), "+f"(d[OFF + 10]), "+f"(d[OFF + 11]),
        "+f"(d[OFF + 12]), "+f"(d[OFF + 13]), "+f"(d[OFF + 14]), "+f"(d[OFF + 15]), "+f"(d[OFF + 16]), "+f"(d[OFF + 17]),
        "+f"(d[OFF + 18]), "+f"(d[OFF + 19]), "+f"(d[OFF + 20]), "+f"(d[OFF + 21]), "+f"(d[OFF + 22]), "+f"(d[OFF + 23]),
        "+f"(d[OFF + 24]), "+f"(d[OFF + 25]), "+f"(d[OFF + 26]), "+f"(d[OFF + 27]), "+f"(d[OFF + 28]), "+f"(d[OFF + 29]),
        "+f"(d[OFF + 30]), "+f"(d[OFF + 31]), "+f"(d[OFF + 32]), "+f"(d[OFF + 33]), "+f"(d[OFF + 34]), "+f"(d[OFF + 35]),
        "+f"(d[OFF + 36]), "+f"(d[OFF + 37]), "+f"(d[OFF + 38]), "+f"(d[OFF + 39]), "+f"(d[OFF + 40]), "+f"(d[OFF + 41]),
        "+f"(d[OFF + 42]), "+f"(d[OFF + 43]), "+f"(d[OFF + 44]), "+f"(d[OFF + 45]), "+f"(d[OFF + 46]), "+f"(d[OFF + 47]),
        "+f"(d[OFF + 48]), "+f"(d[OFF + 49]), "+f"(d[OFF + 50]), "+f"(d[OFF + 51])
      : "r"(a0), "r"(a1), "r"(a2), "r"(a3), "l"(desc_b), "r"(scale_d), "r"(meta));
}

template <int OFF, int NN>
__device__ __forceinline__ void wg_s104z(float (&d)[NN], uint32_t a0, uint32_t a1, uint32_t a2, uint32_t a3,
                                       uint64_t desc_b, int scale_d, uint32_t meta) {
  asm volatile(
      "{\n.reg .pred p;\nsetp.ne.b32 p, %57, 0;\n"
      "wgmma.mma_async.sp.sync.aligned.m64n104k32.f32.bf16.bf16 "
      "{%0,%1,%2,%3,%4,%5,%6,%7,%8,%9,%10,%11,%12,%13,%14,%15,"
      "%16,%17,%18,%19,%20,%21,%22,%23,%24,%25,%26,%27,%28,%29,%30,%31,"
      "%32,%33,%34,%35,%36,%37,%38,%39,%40,%41,%42,%43,%44,%45,%46,%47,"
      "%48,%49,%50,%51}, "
      "{%52,%53,%54,%55}, %56, %58, 0, p, 1, 1, 0;\n}\n"
      : "=f"(d[OFF + 0]), "=f"(d[OFF + 1]), "=f"(d[OFF + 2]), "=f"(d[OFF + 3]), "=f"(d[OFF + 4]), "=f"(d[OFF + 5]),
        "=f"(d[OFF + 6]), "=f"(d[OFF + 7]), "=f"(d[OFF + 8]), "=f"(d[OFF + 9]), "=f"(d[OFF + 10]), "=f"(d[OFF + 11]),
        "=f"(d[OFF + 12]), "=f"(d[OFF + 13]), "=f"(d[OFF + 14]), "=f"(d[OFF + 15]), "=f"(d[OFF + 16]), "=f"(d[OFF + 17]),
        "=f"(d[OFF + 18]), "=f"(d[OFF + 19]), "=f"(d[OFF + 20]), "=f"(d[OFF + 21]), "=f"(d[OFF + 22]), "=f"(d[OFF + 23]),
        "=f"(d[OFF + 24]), "=f"(d[OFF + 25]), "=f"(d[OFF + 26]), "=f"(d[OFF + 27]), "=f"(d[OFF + 28]), "=f"(d[OFF + 29]),
        "=f"(d[OFF + 30]), "=f"(d[OFF + 31]), "=f"(d[OFF + 32]), "=f"(d[OFF + 33]), "=f"(d[OFF + 34]), "=f"(d[OFF + 35]),
        "=f"(d[OFF + 36]), "=f"(d[OFF + 37]), "=f"(d[OFF + 38]), "=f"(d[OFF + 39]), "=f"(d[OFF + 40]), "=f"(d[OFF + 41]),
        "=f"(d[OFF + 42]), "=f"(d[OFF + 43]), "=f"(d[OFF + 44]), "=f"(d[OFF + 45]), "=f"(d[OFF + 46]), "=f"(d[OFF + 47]),
        "=f"(d[OFF + 48]), "=f"(d[OFF + 49]), "=f"(d[OFF + 50]), "=f"(d[OFF + 51])
      : "r"(a0), "r"(a1), "r"(a2), "r"(a3), "l"(desc_b), "r"(scale_d), "r"(meta));
}

template <int OFF, int NN>
__device__ __forceinline__ void wg_s48(float (&d)[NN], uint32_t a0, uint32_t a1, uint32_t a2, uint32_t a3,
                                       uint64_t desc_b, int scale_d, uint32_t meta) {
  asm volatile(
      "{\n.reg .pred p;\nsetp.ne.b32 p, %29, 0;\n"
      "wgmma.mma_async.sp.sync.aligned.m64n48k32.f32.bf16.bf16 "
      "{%0,%1,%2,%3,%4,%5,%6,%7,%8,%9,%10,%11,%12,%13,%14,%15,"
      "%16,%17,%18,%19,%20,%21,%22,%23}, "
      "{%24,%25,%26,%27}, %28, %30, 0, p, 1, 1, 0;\n}\n"
      : "+f"(d[OFF + 0]), "+f"(d[OFF + 1]), "+f"(d[OFF + 2]), "+f"(d[OFF + 3]), "+f"(d[OFF + 4]), "+f"(d[OFF + 5]),
        "+f"(d[OFF + 6]), "+f"(d[OFF + 7]), "+f"(d[OFF + 8]), "+f"(d[OFF + 9]), "+f"(d[OFF + 10]), "+f"(d[OFF + 11]),
        "+f"(d[OFF + 12]), "+f"(d[OFF + 13]), "+f"(d[OFF + 14]), "+f"(d[OFF + 15]), "+f"(d[OFF + 16]), "+f"(d[OFF + 17]),
        "+f"(d[OFF + 18]), "+f"(d[OFF + 19]), "+f"(d[OFF + 20]), "+f"(d[OFF + 21]), "+f"(d[OFF + 22]), "+f"(d[OFF + 23])
      : "r"(a0), "r"(a1), "r"(a2), "r"(a3), "l"(desc_b), "r"(scale_d), "r"(meta));
}

template <int OFF, int NN>
__device__ __forceinline__ void wg_s48z(float (&d)[NN], uint32_t a0, uint32_t a1, uint32_t a2, uint32_t a3,
                                       uint64_t desc_b, int scale_d, uint32_t meta) {
  asm volatile(
      "{\n.reg .pred p;\nsetp.ne.b32 p, %29, 0;\n"
      "wgmma.mma_async.sp.sync.aligned.m64n48k32.f32.bf16.bf16 "
      "{%0,%1,%2,%3,%4,%5,%6,%7,%8,%9,%10,%11,%12,%13,%14,%15,"
      "%16,%17,%18,%19,%20,%21,%22,%23}, "
      "{%24,%25,%26,%27}, %28, %30, 0, p, 1, 1, 0;\n}\n"
      : "=f"(d[OFF + 0]), "=f"(d[OFF + 1]), "=f"(d[OFF + 2]), "=f"(d[OFF + 3]), "=f"(d[OFF + 4]), "=f"(d[OFF + 5]),
        "=f"(d[OFF + 6]), "=f"(d[OFF + 7]), "=f"(d[OFF + 8]), "=f"(d[OFF + 9]), "=f"(d[OFF + 10]), "=f"(d[OFF + 11]),
        "=f"(d[OFF + 12]), "=f"(d[OFF + 13]), "=f"(d[OFF + 14]), "=f"(d[OFF + 15]), "=f"(d[OFF + 16]), "=f"(d[OFF + 17]),
        "=f"(d[OFF + 18]), "=f"(d[OFF + 19]), "=f"(d[OFF + 20]), "=f"(d[OFF + 21]), "=f"(d[OFF + 22]), "=f"(d[OFF + 23])
      : "r"(a0), "r"(a1), "r"(a2), "r"(a3), "l"(desc_b), "r"(scale_d), "r"(meta));
}

template <int OFF, int NN>
__device__ __forceinline__ void wg_s56(float (&d)[NN], uint32_t a0, uint32_t a1, uint32_t a2, uint32_t a3,
                                       uint64_t desc_b, int scale_d, uint32_t meta) {
  asm volatile(
      "{\n.reg .pred p;\nsetp.ne.b32 p, %33, 0;\n"
      "wgmma.mma_async.sp.sync.aligned.m64n56k32.f32.bf16.bf16 "
      "{%0,%1,%2,%3,%4,%5,%6,%7,%8,%9,%10,%11,%12,%13,%14,%15,"
      "%16,%17,%18,%19,%20,%21,%22,%23,%24,%25,%26,%27}, "
      "{%28,%29,%30,%31}, %32, %34, 0, p, 1, 1, 0;\n}\n"
      : "+f"(d[OFF + 0]), "+f"(d[OFF + 1]), "+f"(d[OFF + 2]), "+f"(d[OFF + 3]), "+f"(d[OFF + 4]), "+f"(d[OFF + 5]),
        "+f"(d[OFF + 6]), "+f"(d[OFF + 7]), "+f"(d[OFF + 8]), "+f"(d[OFF + 9]), "+f"(d[OFF + 10]), "+f"(d[OFF + 11]),
        "+f"(d[OFF + 12]), "+f"(d[OFF + 13]), "+f"(d[OFF + 14]), "+f"(d[OFF + 15]), "+f"(d[OFF + 16]), "+f"(d[OFF + 17]),
        "+f"(d[OFF + 18]), "+f"(d[OFF + 19]), "+f"(d[OFF + 20]), "+f"(d[OFF + 21]), "+f"(d[OFF + 22]), "+f"(d[OFF + 23]),
        "+f"(d[OFF + 24]), "+f"(d[OFF + 25]), "+f"(d[OFF + 26]), "+f"(d[OFF + 27])
      : "r"(a0), "r"(a1), "r"(a2), "r"(a3), "l"(desc_b), "r"(scale_d), "r"(meta));
}

template <int OFF, int NN>
__device__ __forceinline__ void wg_s56z(float (&d)[NN], uint32_t a0, uint32_t a1, uint32_t a2, uint32_t a3,
                                       uint64_t desc_b, int scale_d, uint32_t meta) {
  asm volatile(
      "{\n.reg .pred p;\nsetp.ne.b32 p, %33, 0;\n"
      "wgmma.mma_async.sp.sync.aligned.m64n56k32.f32.bf16.bf16 "
      "{%0,%1,%2,%3,%4,%5,%6,%7,%8,%9,%10,%11,%12,%13,%14,%15,"
      "%16,%17,%18,%19,%20,%21,%22,%23,%24,%25,%26,%27}, "
      "{%28,%29,%30,%31}, %32, %34, 0, p, 1, 1, 0;\n}\n"
      : "=f"(d[OFF + 0]), "=f"(d[OFF + 1]), "=f"(d[OFF + 2]), "=f"(d[OFF + 3]), "=f"(d[OFF + 4]), "=f"(d[OFF + 5]),
        "=f"(d[OFF + 6]), "=f"(d[OFF + 7]), "=f"(d[OFF + 8]), "=f"(d[OFF + 9]), "=f"(d[OFF + 10]), "=f"(d[OFF + 11]),
        "=f"(d[OFF + 12]), "=f"(d[OFF + 13]), "=f"(d[OFF + 14]), "=f"(d[OFF + 15]), "=f"(d[OFF + 16]), "=f"(d[OFF + 17]),
        "=f"(d[OFF + 18]), "=f"(d[OFF + 19]), "=f"(d[OFF + 20]), "=f"(d[OFF + 21]), "=f"(d[OFF + 22]), "=f"(d[OFF + 23]),
        "=f"(d[OFF + 24]), "=f"(d[OFF + 25]), "=f"(d[OFF + 26]), "=f"(d[OFF + 27])
      : "r"(a0), "r"(a1), "r"(a2), "r"(a3), "l"(desc_b), "r"(scale_d), "r"(meta));
}

template <int OFF, int NN>
__device__ __forceinline__ void wg_s64t(float (&d)[NN], uint32_t a0, uint32_t a1, uint32_t a2, uint32_t a3,
                                       uint64_t desc_b, int scale_d, uint32_t meta) {
  asm volatile(
      "{\n.reg .pred p;\nsetp.ne.b32 p, %37, 0;\n"
      "wgmma.mma_async.sp.sync.aligned.m64n64k32.f32.bf16.bf16 "
      "{%0,%1,%2,%3,%4,%5,%6,%7,%8,%9,%10,%11,%12,%13,%14,%15,"
      "%16,%17,%18,%19,%20,%21,%22,%23,%24,%25,%26,%27,%28,%29,%30,%31}, "
      "{%32,%33,%34,%35}, %36, %38, 0, p, 1, 1, 1;\n}\n"
      : "+f"(d[OFF + 0]), "+f"(d[OFF + 1]), "+f"(d[OFF + 2]), "+f"(d[OFF + 3]), "+f"(d[OFF + 4]), "+f"(d[OFF + 5]),
        "+f"(d[OFF + 6]), "+f"(d[OFF + 7]), "+f"(d[OFF + 8]), "+f"(d[OFF + 9]), "+f"(d[OFF + 10]), "+f"(d[OFF + 11]),
        "+f"(d[OFF + 12]), "+f"(d[OFF + 13]), "+f"(d[OFF + 14]), "+f"(d[OFF + 15]), "+f"(d[OFF + 16]), "+f"(d[OFF + 17]),
        "+f"(d[OFF + 18]), "+f"(d[OFF + 19]), "+f"(d[OFF + 20]), "+f"(d[OFF + 21]), "+f"(d[OFF + 22]), "+f"(d[OFF + 23]),
        "+f"(d[OFF + 24]), "+f"(d[OFF + 25]), "+f"(d[OFF + 26]), "+f"(d[OFF + 27]), "+f"(d[OFF + 28]), "+f"(d[OFF + 29]),
        "+f"(d[OFF + 30]), "+f"(d[OFF + 31])
      : "r"(a0), "r"(a1), "r"(a2), "r"(a3), "l"(desc_b), "r"(scale_d), "r"(meta));
}

template <int OFF, int NN>
__device__ __forceinline__ void wg_s64t1(float (&d)[NN], uint32_t a0, uint32_t a1, uint32_t a2, uint32_t a3,
                                       uint64_t desc_b, int scale_d, uint32_t meta) {
  asm volatile(
      "{\n.reg .pred p;\nsetp.ne.b32 p, %37, 0;\n"
      "wgmma.mma_async.sp.sync.aligned.m64n64k32.f32.bf16.bf16 "
      "{%0,%1,%2,%3,%4,%5,%6,%7,%8,%9,%10,%11,%12,%13,%14,%15,"
      "%16,%17,%18,%19,%20,%21,%22,%23,%24,%25,%26,%27,%28,%29,%30,%31}, "
      "{%32,%33,%34,%35}, %36, %38, 1, p, 1, 1, 1;\n}\n"
      : "+f"(d[OFF + 0]), "+f"(d[OFF + 1]), "+f"(d[OFF + 2]), "+f"(d[OFF + 3]), "+f"(d[OFF + 4]), "+f"(d[OFF + 5]),
        "+f"(d[OFF + 6]), "+f"(d[OFF + 7]), "+f"(d[OFF + 8]), "+f"(d[OFF + 9]), "+f"(d[OFF + 10]), "+f"(d[OFF + 11]),
        "+f"(d[OFF + 12]), "+f"(d[OFF + 13]), "+f"(d[OFF + 14]), "+f"(d[OFF + 15]), "+f"(d[OFF + 16]), "+f"(d[OFF + 17]),
        "+f"(d[OFF + 18]), "+f"(d[OFF + 19]), "+f"(d[OFF + 20]), "+f"(d[OFF + 21]), "+f"(d[OFF + 22]), "+f"(d[OFF + 23]),
        "+f"(d[OFF + 24]), "+f"(d[OFF + 25]), "+f"(d[OFF + 26]), "+f"(d[OFF + 27]), "+f"(d[OFF + 28]), "+f"(d[OFF + 29]),
        "+f"(d[OFF + 30]), "+f"(d[OFF + 31])
      : "r"(a0), "r"(a1), "r"(a2), "r"(a3), "l"(desc_b), "r"(scale_d), "r"(meta));
}

template <int OFF, int NN>
__device__ __forceinline__ void wg_s64tz(float (&d)[NN], uint32_t a0, uint32_t a1, uint32_t a2, uint32_t a3,
                                       uint64_t desc_b, int scale_d, uint32_t meta) {
  asm volatile(
      "{\n.reg .pred p;\nsetp.ne.b32 p, %37, 0;\n"
      "wgmma.mma_async.sp.sync.aligned.m64n64k32.f32.bf16.bf16 "
      "{%0,%1,%2,%3,%4,%5,%6,%7,%8,%9,%10,%11,%12,%13,%14,%15,"
      "%16,%17,%18,%19,%20,%21,%22,%23,%24,%25,%26,%27,%28,%29,%30,%31}, "
      "{%32,%33,%34,%35}, %36, %38, 0, p, 1, 1, 1;\n}\n"
      : "=f"(d[OFF + 0]), "=f"(d[OFF + 1]), "=f"(d[OFF + 2]), "=f"(d[OFF + 3]), "=f"(d[OFF + 4]), "=f"(d[OFF + 5]),
        "=f"(d[OFF + 6]), "=f"(d[OFF + 7]), "=f"(d[OFF + 8]), "=f"(d[OFF + 9]), "=f"(d[OFF + 10]), "=f"(d[OFF + 11]),
        "=f"(d[OFF + 12]), "=f"(d[OFF + 13]), "=f"(d[OFF + 14]), "=f"(d[OFF + 15]), "=f"(d[OFF + 16]), "=f"(d[OFF + 17]),
        "=f"(d[OFF + 18]), "=f"(d[OFF + 19]), "=f"(d[OFF + 20]), "=f"(d[OFF + 21]), "=f"(d[OFF + 22]), "=f"(d[OFF + 23]),
        "=f"(d[OFF + 24]), "=f"(d[OFF + 25]), "=f"(d[OFF + 26]), "=f"(d[OFF + 27]), "=f"(d[OFF + 28]), "=f"(d[OFF + 29]),
        "=f"(d[OFF + 30]), "=f"(d[OFF + 31])
      : "r"(a0), "r"(a1), "r"(a2), "r"(a3), "l"(desc_b), "r"(scale_d), "r"(meta));
}

__device__ __forceinline__ int g2_inv(int ch) { return 32 * (ch >> 5) + 8 * ((ch >> 1) & 3) + 2 * ((ch >> 3) & 3) + (ch & 1); }
__host__ __device__ __forceinline__ uint32_t wimg_off(int n, int k) {
  return (uint32_t)(k >> 6) * kWChunk + (uint32_t)n * 128 + (uint32_t)((((k & 63) >> 3) ^ (n & 7)) << 4) + (k & 7) * 2;
}
__host__ __device__ constexpr int w2piece(int h, int c) { return c == 2 ? 2 + h : 4 * h + c; }
__device__ __forceinline__ uint32_t w2img_off(int n, int k) { return wimg_off(n % 96, k & 63) + w2piece(n >= 96, k >> 6) * (kWChunk / 2); }
__device__ __forceinline__ int qpix(int par, int t) {
  const int a = 2 * t + 13 * par - 6, b = t + 112 * par;
  return par ? min(a, b) : max(a, b);
}
__device__ __forceinline__ int woff(int par, int i, int r) {
  const int a = 99 * par + 6 - 8 * i;
  return par ? min(r, a) : max(r, a);
}

__device__ __forceinline__ void mma16816(float (&c)[4], uint32_t a0, uint32_t a1, uint32_t a2, uint32_t a3, uint32_t b0,
                                         uint32_t b1) {
  asm volatile(
      "mma.sync.aligned.m16n8k16.row.col.f32.bf16.bf16.f32 {%0,%1,%2,%3}, {%4,%5,%6,%7}, {%8,%9}, {%0,%1,%2,%3};"
      : "+f"(c[0]), "+f"(c[1]), "+f"(c[2]), "+f"(c[3])
      : "r"(a0), "r"(a1), "r"(a2), "r"(a3), "r"(b0), "r"(b1));
}

__device__ __forceinline__ void fold_w1(const uint32_t u, const __nv_bfloat16* __restrict__ wqkv, uint8_t* wimg) {
  const uint32_t g = (threadIdx.x >> 2) & 7, l = threadIdx.x & 3;
  const uint32_t m0 = (u * 171 >> 11) * 16, s = u - (u * 171 >> 11) * 12;
  uint4 A[12], B[12];
  const __nv_bfloat16* arow = wqkv + (m0 + 4 * (g >> 1) + (g & 1)) * 576 + 192 + 8 * l;
  const __nv_bfloat16* brow = wqkv + (16 * s + 4 * (g >> 1) + (g & 1)) * 576 + 8 * l;
#pragma unroll
  for (int i = 0; i < 12; i++) {
    A[i] = ldg128_nc(arow + (i & 1) * 2 * 576 + 32 * (i >> 1));
    B[i] = ldg128_nc(brow + (i & 1) * 2 * 576 + 32 * (i >> 1));
  }
  uint8_t* dst = wimg + wimg_off(m0 + g, 16 * s + 4 * l);
  uint32_t zero = (uint32_t)(uint64_t)wimg & 15u, one = zero + 1;
  asm volatile("" : "+l"(dst), "+r"(zero), "+r"(one));
  sched_fence();
  float acc[4][4];
#pragma unroll
  for (int j = 0; j < 16; j++) acc[j >> 2][j & 3] = 0.f;
#pragma unroll
  for (int i = 0; i < 6; i++) {
    const uint4 &a0 = A[2 * i], &a1 = A[2 * i + 1];
    const uint32_t f[8] = {a0.x | zero, a1.x * one, a0.y | zero, a1.y * one, a0.z | zero, a1.z * one, a0.w | zero, a1.w * one};
#pragma unroll
    for (int nb = 0; nb < 2; nb++) {
      mma16816(acc[2 * nb], f[0], f[1], f[2], f[3], B[2 * i + nb].x, B[2 * i + nb].y);
      mma16816(acc[2 * nb + 1], f[4], f[5], f[6], f[7], B[2 * i + nb].z, B[2 * i + nb].w);
    }
  }
#pragma unroll
  for (int j = 0; j < 2; j++) {
    const uint2 v = make_uint2(pack_bf16((acc[0][2 * j] + acc[1][2 * j]) * kAlpha, (acc[0][2 * j + 1] + acc[1][2 * j + 1]) * kAlpha),
                               pack_bf16((acc[2][2 * j] + acc[3][2 * j]) * kAlpha, (acc[2][2 * j + 1] + acc[3][2 * j + 1]) * kAlpha));
    asm volatile("st.relaxed.gpu.global.v2.u32 [%0], {%1,%2};" ::"l"(dst + j * 1024), "r"(v.x), "r"(v.y) : "memory");
  }
}
__device__ __forceinline__ void fold_w2(const int u, const __nv_bfloat16* __restrict__ wqkv, const __nv_bfloat16* __restrict__ wo,
                                        uint8_t* wimg) {
  const int g = (threadIdx.x >> 2) & 7, l = threadIdx.x & 3;
  const int m0 = (u / 12) * 32, n0 = (u % 12) * 16;
  uint4 S[12];
  uint32_t L[96];
  const __nv_bfloat16* brow = wqkv + (n0 + 4 * (g >> 1) + (g & 1)) * 576 + 384 + 8 * l;
#pragma unroll
  for (int i = 0; i < 12; i++) S[i] = ldg128_nc(brow + (i & 1) * 2 * 576 + 32 * (i >> 1));
  const __nv_bfloat16* acol = wo + (8 * l) * 192 + m0 + 4 * g;
#pragma unroll
  for (int c = 0; c < 48; c++)
    asm volatile("ld.global.nc.v2.u32 {%0,%1}, [%2];" : "=r"(L[2 * c]), "=r"(L[2 * c + 1]) : "l"(acol + (32 * (c >> 3) + (c & 7)) * 192));
  const uint32_t off = w2_offset();
  sched_fence();
  uint8_t* img = wimg + off;
  float acc[4][4];
#pragma unroll
  for (int j = 0; j < 16; j++) acc[j >> 2][j & 3] = 0.f;
#pragma unroll
  for (int i = 0; i < 6; i++) {
#pragma unroll
    for (int h = 0; h < 2; h++) {
      const uint4 &s0 = S[2 * i], &s1 = S[2 * i + 1];
#pragma unroll
      for (int mt = 0; mt < 2; mt++) {
        const uint32_t* a = L + 16 * i + 8 * h + mt;
        const uint32_t a0 = __byte_perm(a[0], a[2], 0x5410), a1 = __byte_perm(a[0], a[2], 0x7632);
        const uint32_t a2 = __byte_perm(a[4], a[6], 0x5410), a3 = __byte_perm(a[4], a[6], 0x7632);
        mma16816(acc[2 * mt], a0, a1, a2, a3, h ? s0.z : s0.x, h ? s0.w : s0.y);
        mma16816(acc[2 * mt + 1], a0, a1, a2, a3, h ? s1.z : s1.x, h ? s1.w : s1.y);
      }
    }
  }
#pragma unroll
  for (int j = 0; j < 4; j++) {
    const float(&c0)[4] = acc[j & 2];
    const float(&c1)[4] = acc[(j & 2) + 1];
    asm volatile("st.relaxed.gpu.global.v2.u32 [%0], {%1,%2};" ::"l"(img + w2img_off(g2_inv(m0 + 4 * g + j), n0 + 4 * l)),
                 "r"(pack_bf16(c0[2 * (j & 1)], c0[2 * (j & 1) + 1])), "r"(pack_bf16(c1[2 * (j & 1)], c1[2 * (j & 1) + 1])) : "memory");
  }
}

__global__ void __launch_bounds__(256) fold_kernel(const __nv_bfloat16* __restrict__ wqkv,
                                                   const __nv_bfloat16* __restrict__ wo, uint8_t* wimg) {
  const int u = blockIdx.x * 8 + (threadIdx.x >> 5);
  if (u < 144) fold_w1(u, wqkv, wimg);
  else fold_w2(u - 144, wqkv, wo, wimg);
}

struct TileCoord { int pr, pc, I, J, up, kind; };
struct TileTable { uint16_t e[kCtas * 6], g[5][8][2], b[5][2][4]; };
inline void make_tiles(TileTable& tt) {
  for (int tile = 0; tile < kCtas * 6; tile++) {
    const int b = tile / 6, k = tile - 6 * b;
    const int p = b < 128 ? (tile - 672) >> 1 : b - 80;
    const int strip = b < 112 ? b >> 1 : b >= 128 && k >= 2 ? (b & 1) * 27 + (b & 2) * 14 : p + (p < 26 ? 1 : 3);
    const int pr = strip >= 28, J = (strip - pr * 28) >> 1, pc = strip & 1, up = b < 112 ? b & 1 : pr;
    const int first = b < 112 ? 8 - 2 * pr - up : 13 * pr, step = b < 112 ? k : k & 1;
    const int I = up ? first - step : first + step;
    const int kind = I == 13 * pr ? 3 + pr : J == 13 * pc ? 1 + pc : 0;
    tt.e[tile] = (uint16_t)(I | J << 4 | pr << 8 | pc << 9 | up << 10 | kind << 11);
  }
  for (int kind = 0; kind < 5; kind++) {
    const bool col = kind == 1 || kind == 2;
    auto off = [kind](int t) { return kind == 0 ? 2 * t : kind & 1 ? t + (t == 7) : t + (t > 0); };
    for (int j = 0; j < 8; j++) {
      const int w = j >> 1, h = j & 1;
      tt.g[kind][j][0] = (uint16_t)(col ? 3 * off(w + 4 * h) : 3 * (kW * off(2 * w) + 8 * h));
      tt.g[kind][j][1] = (uint16_t)(128 * (col ? 5 : 5 + off(2 * w + 1) - off(2 * w)));
    }
    for (int i = 0; i < 2; i++) {
      const int w = kind == 0 ? 0 : kind & 1 ? 3 * i : 1 - i;
      tt.b[kind][i][0] = tt.g[kind][2 * w][0];
      tt.b[kind][i][1] = (uint16_t)(128 * (kind == 0 ? 0 : (col ? 3 : 1) + i));
      tt.b[kind][i][2] = (uint16_t)(2048 * w);
      tt.b[kind][i][3] = 0;
    }
  }
}
__device__ __forceinline__ int num_tiles() { return blockIdx.x < 128 ? 6 : 4; }
__device__ __forceinline__ TileCoord decode_tile(const TileTable& tt, int tile) {
  const uint32_t e = tt.e[tile];
  return TileCoord{(int)(e >> 8) & 1, (int)(e >> 9) & 1, (int)e & 15, (int)(e >> 4) & 15, (int)(e >> 10) & 1, (int)(e >> 11)};
}
__device__ __forceinline__ int halo_r0(const TileCoord& t) { return 8 * t.I + 6 * t.pr - 6; }
__device__ __forceinline__ int halo_c0(const TileCoord& t) { return min(max(8 * t.J + 6 * t.pc - 6, -3), 102); }

__device__ __forceinline__ uint32_t bar_full(uint32_t bars, int wg, int c) { return bars + (wg * 3 + c) * 8; }
__device__ __forceinline__ uint32_t bar_w1c(uint32_t bars, int c) { return bars + (6 + c) * 8; }
__device__ __forceinline__ uint32_t bar_w2(uint32_t bars) { return bars + 9 * 8; }
__device__ __forceinline__ uint32_t bar_x(uint32_t bars, int j, int c) { return bars + (j == 0 ? 10 : c ? 17 + c : 11) * 8; }
__device__ __forceinline__ uint32_t bar_w1q(uint32_t bars) { return bars + 12 * 8; }
__device__ __forceinline__ uint32_t bar_xf(uint32_t bars) { return bars + 13 * 8; }
__device__ __forceinline__ uint32_t bar_w2m(uint32_t bars) { return bars + 14 * 8; }
__device__ __forceinline__ uint32_t bar_redo(uint32_t bars) { return bars + 15 * 8; }
__device__ __forceinline__ uint32_t bar_wok(uint32_t bars) { return bars + 16 * 8; }
__device__ __forceinline__ uint32_t bar_go(uint32_t bars) { return bars + 17 * 8; }
__device__ __forceinline__ uint32_t bar_raw(uint32_t bars, int j = 0) { return bars + (21 + j) * 8; }
__device__ __forceinline__ uint32_t bar_w2a(uint32_t bars) { return bars + 20 * 8; }
constexpr int kNumBars = 22;

__device__ __forceinline__ uint64_t wdesc(uint64_t d0, int s) { return d0 + (((s >> 2) * kWChunk + (s & 3) * 32) >> 4); }

__device__ __forceinline__ uint32_t x_chunk(int k, int c) { return kXOff + (k == 0 ? kWChunk : 0) + (k & 1 ? 2 - c : c) * 8192; }
__device__ __forceinline__ uint32_t out_slot(int k, int nt) { return k + 1 < nt ? kW2Off + (~k & 1) * 2 * kWChunk : kW1Off + kWChunk; }
template <int I0, int I1>
__device__ __forceinline__ void store_rows(bool on, __nv_bfloat16* pA, __nv_bfloat16* pB, const uint32_t (&a)[24], const uint32_t (&b)[24]) {
#pragma unroll
  for (int i = 2 * I0; i < 2 * I1; i++) {
    const uint32_t* v = (i & 1 ? b : a) + 4 * (i >> 1);
    asm volatile("{\n.reg .pred p;\nsetp.ne.u32 p, %5, 0;\n@p st.global.v4.u32 [%0], {%1,%2,%3,%4};\n}\n" ::"l"((i & 1 ? pB : pA) + 32 * (i >> 1)),
                 "r"(v[0]), "r"(v[1]), "r"(v[2]), "r"(v[3]), "r"((uint32_t)on) : "memory");
  }
}
template <int I0, int I1>
__device__ __forceinline__ void stage_out(const uint32_t (&ad)[4], const uint32_t (&a)[24], const uint32_t (&b)[24]) {
#pragma unroll
  for (int i = I0; i < I1; i++) {
    const uint32_t* v = (i < 6 ? a : b) + 4 * (i % 6);
    asm volatile("st.shared.v4.u32 [%0], {%1,%2,%3,%4};" ::"r"(ad[i % 6 / 3 * 2 + (i % 3 == 1)] + (i % 3 == 2) * 1024 + (i / 6) * 12288),
                 "r"(v[0]), "r"(v[1]), "r"(v[2]), "r"(v[3]) : "memory");
  }
}
__device__ __forceinline__ uint32_t now_ns() {
  uint32_t t;
  asm volatile("mov.u32 %0, %globaltimer_lo;" : "=r"(t)::"memory");
  return t;
}
__device__ __forceinline__ void wait_clock(uint32_t t_start, uint32_t t) {
  while (now_ns() - t_start < t) { }
}
__device__ __forceinline__ void sleep_clock(uint32_t t_start, uint32_t t) {
  while (now_ns() - t_start < t) __nanosleep(100);
}
#define NAT_PRED(f, m) ".reg .pred p;\n.reg .b32 t;\nand.b32 t, " f ", " m ";\nsetp.ne.u32 p, t, 0;\n"
constexpr uint32_t kHiV = 1, kHiU = 8, kColB = 0x20, kInV = 0x100, kInU = 0x1000, kColA = 0x10000;
template <uint32_t M>
__device__ __forceinline__ float pick(const float* a, const float* b, uint32_t f) {
  float d;
  asm("{\n" NAT_PRED("%5", "%6") "add.f32 %0, %1, %2;\n@p add.f32 %0, %3, %4;\n}\n"
      : "=&f"(d) : "f"(a[0]), "f"(a[2]), "f"(b[0]), "f"(b[2]), "r"(f), "n"(M));
  return d;
}
template <uint32_t M>
__device__ __forceinline__ float sel(float a, float b, uint32_t f) {
  float d;
  asm("{\n" NAT_PRED("%3", "%4") "selp.f32 %0, %1, %2, p;\n}\n" : "=f"(d) : "f"(a), "f"(b), "r"(f), "n"(M));
  return d;
}
template <uint32_t M>
__device__ __forceinline__ void max_if(float& m, float v, uint32_t f) {
  asm("{\n" NAT_PRED("%2", "%3") "@p max.f32 %0, %0, %1;\n}\n" : "+f"(m) : "f"(v), "r"(f), "n"(M));
}
template <uint32_t M>
__device__ __forceinline__ void add_if(float& m, float v, uint32_t f) {
  asm("{\n" NAT_PRED("%2", "%3") "@p add.f32 %0, %0, %1;\n}\n" : "+f"(m) : "f"(v), "r"(f), "n"(M));
}
__device__ __forceinline__ void pick_v(const float* a, float* v, uint32_t f) {
  v[0] = pick<kHiV>(a, a + 16, f), v[1] = pick<kHiV>(a + 1, a + 17, f);
  v[2] = pick<kHiV * 2>(a + 4, a + 20, f), v[3] = pick<kHiV * 2>(a + 5, a + 21, f);
  v[4] = pick<kHiV * 4>(a + 8, a + 24, f), v[5] = pick<kHiV * 4>(a + 9, a + 25, f);
  v[6] = a[12] + a[14], v[7] = a[13] + a[15];
}
__device__ __forceinline__ void pick_u(const float* a, float* v, uint32_t f) {
#pragma unroll
  for (int c = 0; c < 3; c++) v[2 * c] = pick<kHiU>(a + 4 * c, a + 4 * c + 12, f), v[2 * c + 1] = pick<kHiU * 2>(a + 4 * c + 1, a + 4 * c + 13, f);
}
__device__ __forceinline__ uint32_t sign_bytes(uint32_t v, uint32_t sel) {
  uint32_t d;
  asm("prmt.b32 %0, %1, %1, %2;" : "=r"(d) : "r"(v), "r"(sel));
  return d;
}
__device__ __forceinline__ float own_max(const float (&v)[14], uint32_t f) {
  float m = sel<kInV>(fmaxf(v[0], v[1]), -INFINITY, f), m2 = sel<kInV * 2>(fmaxf(v[2], v[3]), -INFINITY, f);
  max_if<kInV * 4>(m, fmaxf(v[4], v[5]), f);
  max_if<kInV * 8>(m2, fmaxf(v[6], v[7]), f);
  max_if<kInU>(m, fmaxf(fmaxf(v[8], v[10]), v[12]), f);
  max_if<kInU * 2>(m2, fmaxf(fmaxf(v[9], v[11]), v[13]), f);
  return fmaxf(m, m2);
}
__device__ __forceinline__ float quad_max(float m) {
  const float a = __shfl_xor_sync(0xffffffffu, m, 1), b = __shfl_xor_sync(0xffffffffu, m, 2), c = __shfl_xor_sync(0xffffffffu, m, 3);
  return fmaxf(fmaxf(m, a), fmaxf(b, c));
}
__device__ __forceinline__ float row_rcp(const float (&v)[14], uint32_t f) {
  float s = sel<kInV>(v[0] + v[1], 0.f, f), s2 = sel<kInV * 2>(v[2] + v[3], 0.f, f);
  add_if<kInV * 4>(s, v[4] + v[5], f);
  add_if<kInV * 8>(s2, v[6] + v[7], f);
  add_if<kInU>(s, v[8] + v[10] + v[12], f);
  add_if<kInU * 2>(s2, v[9] + v[11] + v[13], f);
  s += s2;
  const float a = __shfl_xor_sync(0xffffffffu, s, 1), b = __shfl_xor_sync(0xffffffffu, s, 2), c = __shfl_xor_sync(0xffffffffu, s, 3);
  return rcp_approx((s + a) + (b + c));
}
__device__ __forceinline__ void route(const float (&v)[14], float s, const uint32_t (&rt)[9], uint32_t (&p)[14]) {
#pragma unroll
  for (int i = 0; i < 7; i++) {
    const uint32_t u = pack_bf16(v[2 * i] * s, v[2 * i + 1] * s);
    if (i < 4) p[i] = u & rt[i];
    if (i < 3) p[i + 4] = u & rt[i + 4];
    if (i >= 4) {
      p[i + 3] = u & rt[7];
      p[i + 6] = u & rt[8];
    }
  }
}

template <int C, int T0 = 0, int T1 = 7>
__device__ __forceinline__ void pv_chunk(float (&z)[32], const uint32_t (&pa)[14], const uint32_t (&pb)[14],
                                         const uint32_t (&meta)[4], uint64_t dV) {
#pragma unroll
  for (int t = T0; t < T1; t++) {
    if (t & 1)
      wg_s64t1<0, 32>(z, pa[2 * t], pb[2 * t], pa[2 * t + 1], pb[2 * t + 1], dV + ((2 * C * kChunkBytes + t * 2048) >> 4), 1,
                      meta[t >> 1]);
    else if (t > 0)
      wg_s64t<0, 32>(z, pa[2 * t], pb[2 * t], pa[2 * t + 1], pb[2 * t + 1], dV + ((2 * C * kChunkBytes + t * 2048) >> 4), 1,
                     meta[t >> 1]);
    else
      wg_s64tz<0, 32>(z, pa[0], pb[0], pa[1], pb[1], dV + ((2 * C * kChunkBytes) >> 4), 0, meta[0]);
  }
}
template <int C>
__device__ __forceinline__ void pack_z(const float (&z)[32], uint32_t (&za)[24], uint32_t (&zb)[24]) {
#pragma unroll
  for (int j = 0; j < 8; j++) {
    za[8 * C + j] = pack_bf16(z[4 * j], z[4 * j + 1]);
    zb[8 * C + j] = pack_bf16(z[4 * j + 2], z[4 * j + 3]);
  }
}

template <int H>
__device__ __forceinline__ void pack_out(const float (&ac)[48], uint32_t (&oa)[24], uint32_t (&ob)[24]) {
#pragma unroll
  for (int j = 0; j < 12; j++) {
    oa[12 * H + j] = pack_bf16(ac[4 * j], ac[4 * j + 1]);
    ob[12 * H + j] = pack_bf16(ac[4 * j + 2], ac[4 * j + 3]);
  }
}
struct Maps { CUtensorMap v6, v2, v14, u8, px[8], wv, wo; };
__device__ __forceinline__ void tma_prefetch_5d(const CUtensorMap* map, int c0, int c1, int c2, int c3, int c4) {
  asm volatile("cp.async.bulk.prefetch.tensor.5d.L2.global.tile [%0, {%1, %2, %3, %4, %5}];" ::"l"((uint64_t)map), "r"(c0), "r"(c1),
               "r"(c2), "r"(c3), "r"(c4) : "memory");
}
__device__ __forceinline__ int first_line(const TileCoord tc) { return 3 * (qpix(tc.pr, 8 * tc.I) * kW + qpix(tc.pc, 8 * tc.J)); }
__device__ __forceinline__ void load_px(const Maps& tm, const TileTable& tt, uint32_t dst, uint32_t bar, int line, int kind) {
#pragma unroll
  for (int i = 0; i < 2; i++) {
    if (i == 0 || kind != 0) {
      const CUtensorMap* map = (const CUtensorMap*)((const char*)tm.px + tt.b[kind][i][1]);
      if (bar) tma_load_5d(dst + tt.b[kind][i][2], map, bar, 0, 0, 0, 0, line + tt.b[kind][i][0]);
      else tma_prefetch_5d(map, 0, 0, 0, 0, line + tt.b[kind][i][0]);
    }
  }
}
__device__ __forceinline__ void store_px(const Maps& tm, const TileTable& tt, uint32_t buf, int line, int kind) {
#pragma unroll
  for (int i = 0; i < 8; i++) {
    const int j = 2 * (i & 3) + (i >> 2);
    asm volatile("cp.async.bulk.tensor.5d.global.shared::cta.tile.bulk_group [%0, {%2, %2, %2, %2, %3}], [%1];" ::"l"(
                     (uint64_t)tm.px + tt.g[kind][j][1]), "r"(buf + i * 3072), "r"(0), "r"(line + tt.g[kind][j][0]) : "memory");
  }
  asm volatile("cp.async.bulk.commit_group;" ::: "memory");
}
__device__ __noinline__ bool refetch(uint32_t base, const uint8_t* src, bool gap) {
  constexpr uint32_t bars = 1024 + kBarOff, cnt = bars + 192;
#pragma unroll 1
  for (uint32_t o = 0; o < kWBytes && !gap; o += 2048) {
    uint32_t mx = 0;
#pragma unroll
    for (int i = 0; i < 4; i++) {
      uint4 v;
      asm volatile("ld.shared.v4.u32 {%0,%1,%2,%3}, [%4];" : "=r"(v.x), "=r"(v.y), "=r"(v.z), "=r"(v.w)
                   : "r"(base + o + i * 512 + (threadIdx.x & 31) * 16));
      mx = __vimax3_u32(__vimax3_u32(mx, v.x, v.y), v.z, v.w);
    }
    gap = __any_sync(0xffffffffu, mx == kEmpty);
  }
  uint32_t n;
  asm volatile("ld.shared.u32 %0, [%1];" : "=r"(n) : "r"(cnt) : "memory");
  if (!gap || __any_sync(0xffffffffu, n > (1u << 12))) return false;
  asm volatile("bar.sync 15, 128;" ::: "memory");
  if (threadIdx.x == 0) {
    asm volatile("st.shared.u32 [%0], %1;" ::"r"(cnt), "r"(n + 1) : "memory");
    mbar_arrive_expect_tx(bar_redo(bars), kWBytes);
    bulk_load(base, src, kWBytes, bar_redo(bars));
  }
  __syncwarp();
  mbar_wait(bar_redo(bars), n & 1);
  return true;
}
__device__ __forceinline__ bool any_nan(const uint32_t (&a)[24]) {
  uint32_t m[2] = {a[0], a[1]}, nan;
#pragma unroll
  for (int i = 2; i < 24; i++) asm("max.NaN.bf16x2 %0, %0, %1;" : "+r"(m[i & 1]) : "r"(a[i]));
  asm("max.NaN.bf16x2 %0, %0, %1;" : "+r"(m[0]) : "r"(m[1]));
  asm volatile("{\n.reg .pred p;\nsetp.ne.u32 p, %1, 0;\nbar.red.or.pred p, 15, 128, p;\nselp.u32 %0, 1, 0, p;\n}\n"
               : "=r"(nan) : "r"(((m[0] & 0x7FFF7FFFu) + 0x007F007Fu) & 0x80008000u) : "memory");
  return __any_sync(0xffffffffu, nan);
}
template <int S0, int S1, int Z>
__device__ __forceinline__ void g2_steps(float (&ac)[48], const uint32_t (&za)[24], const uint32_t (&zb)[24], uint64_t d) {
#pragma unroll
  for (int s = S0; s < S1; s++) {
    const uint64_t ds = d + (((s >> 2 & 1) * (kWChunk / 2) + (s & 3) * 32) >> 4);
    if (s == Z) wg_d96z<0, 48>(ac, za[2 * s], zb[2 * s], za[2 * s + 1], zb[2 * s + 1], ds, 0);
    else wg_d96<0, 48>(ac, za[2 * s], zb[2 * s], za[2 * s + 1], zb[2 * s + 1], ds, 1);
  }
}

__device__ __forceinline__ void consumer(const int wg, __nv_bfloat16* out, const uint8_t* wimg, const uint32_t sbase,
                                         const uint32_t zero, const Maps& tm, const TileTable& tt) {
  const int tid = threadIdx.x & 127;
  const int w = __shfl_sync(0xffffffffu, tid >> 5, 0), lane = tid & 31;
  const uint64_t dK = make_desc(sbase, 16, 1024);
  const uint64_t dV = make_desc(sbase, kChunkBytes, 512, 2);
  const uint64_t dW1 = make_desc(sbase + kW1Off, 16, 1024);
  const uint64_t dX0 = make_desc(sbase + kW2Off + wg * 2 * kWChunk, 16, 1024), dY0 = make_desc(sbase + kW2Off + (1 - wg) * 2 * kWChunk, 16, 1024);
  const uint64_t dX2 = make_desc(sbase + kXOff + wg * (kWChunk / 2), 16, 1024), dY2 = make_desc(sbase + kXOff + (1 - wg) * (kWChunk / 2), 16, 1024);
  const uint32_t bars = sbase + kBarOff;
  int tile0 = blockIdx.x * kTilesPerCta;
  asm volatile("" : "+r"(tile0));
  const int nt = num_tiles();

  uint32_t pix = 0, geo[6] = {};
  const int l = lane & 3;
#pragma unroll 1
  for (int j = 4; j >= 0; j -= 2) {
    const TileCoord tc = decode_tile(tt, tile0 + wg + j);
    const bool col = tc.kind == 1 || tc.kind == 2;
    const int g = col ? lane >> 2 : 2 * w + ((lane >> 2) & 1), qc = col ? w : lane >> 3;
    const uint32_t pr = qpix(tc.pr, 8 * tc.I + g) * kW;
    if (j == nt - 2) pix = (pr + qpix(tc.pc, 8 * tc.J + qc)) | (pr + qpix(tc.pc, 8 * tc.J + qc + 4)) << 16;
    const int d = 8 * tc.J + 6 * tc.pc - 6 - halo_c0(tc);
    const int ro = woff(tc.pr, tc.I, g), coA = woff(tc.pc, tc.J, qc) + d, coB = woff(tc.pc, tc.J, qc + 4) + d - 3;
#pragma unroll
    for (int i = 5; i >= 2; i--) geo[i] = geo[i - 2];
    const uint32_t lr = 0x1FCu << ro;
    const uint32_t lv = lr >> (2 + (l >> 1)), lu = lr >> (2 * l + 2 * tc.up);
    const uint32_t t = __byte_perm(lv, lu, wg ? 0x4501 : 0x5410);
    geo[0] = (((t & 0x15u) | (lv & 0x40u)) * 0x02082080u & 0x80808080u) | (((t >> 8) & 0x15u) * 0x01041040u & 0x40404040u) |
             (__byte_perm(t << 5, t << 4, 0x7362) & 0x20202020u) | (nt == 6);
    const int dr = (ro - 1) & 7;
    const uint32_t hiv = (((1u << ((ro - (l >> 1) + 1) >> 1)) - 1u) ^ (wg ? 7u : 0u)) & 7u, hiu = (t >> 24) & 3u;
    const uint32_t ca = (1u << coA) - 1u;
    geo[1] = hiv * kHiV | hiu * kHiU | ((((1u << coB) - 1u) >> (2 * (l & 1))) & 3u) * kColB |
             (15u & ~((uint32_t)((dr & 1) == (l >> 1)) << (dr >> 1))) * kInV | ((t >> 16 | t >> 24) & 3u) * kInU | ca * kColA |
             (ca >> ((0x49 >> (2 * l)) & 3) & 1u) << 19 | (uint32_t)(l == 3) << 20 | (0x55u & ((1u << (2 * coB)) - 1u)) << 24;
  }
  keep_regs(geo);
  const int so = (lane >> 3) | (lane & 4);
  uint32_t sts = sbase + w * 3072 + so * 128 + (((lane & 3) ^ so) << 4);
  __nv_bfloat16* poA = out + 8 * l + (pix & 0xFFFFu) * kC + 96 * wg;
  __nv_bfloat16* poB = out + 8 * l + (pix >> 16) * kC + 96 * wg;
  asm volatile("" : "+l"(poA), "+l"(poB), "+r"(sts));
  uint32_t oa[24], ob[24];
#pragma unroll
  for (int j = 0; j < 24; j++) oa[j] = ob[j] = 0u;
  keep_regs(oa);
  keep_regs(ob);
  PROF(wg, 0);
  if (threadIdx.x == 0) GT(1);

  for (int k = wg; k < nt; k += 2) {
    const uint32_t ph = (k >> 1) & 1;
    const int it = k >> 1;
    uint32_t qa[24], qb[24], hok[3];
    uint32_t fl = geo[1];
    {
      float acc[96];
      const uint32_t xp = (k + (k > 0)) & 1;
      if (k > 0) nb_sync(1 + (1 - wg));
#pragma unroll
      for (int s = 0; s < 12; s++) {
        if (s == 0) mbar_wait(bar_x(bars, k > 0, 0), xp);
        if (s == 0 && k < 2) PROF(wg, 1);
        if (s == 0) PROFS(2, wg, 2 + it * 12);
        if (s == 0 && w == 0 && k < 2) GT(20 + wg);
        if (s == 4) wg_wait<1>();
        if ((s & 3) == 0 && (k == 0 || s > 0)) {
          mbar_wait(k == 0 ? bar_w1c(bars, s >> 2) : bar_x(bars, 1, s >> 2), xp);
          PROFS(17, wg, 50 + (s >> 2));
        }
        if ((s & 3) == 0) wg_fence();
        const uint64_t dX = make_desc(sbase + x_chunk(k, s >> 2), 16, 1024) + 2 * (s & 3);
        if (s == 0) wg_m192z<0, 96>(acc, dX, dW1, 0);
        else wg_m192<0, 96>(acc, dX, wdesc(dW1, s), 1);
        if ((s & 3) == 3 || s == 0) wg_commit();
      }
      PROFS(13, wg, 13 + it * 12);
      const uint32_t e = sts + out_slot(k, nt), o = e ^ 64;
      uint32_t ad[4] = {wg ? o + 1024 : e, wg ? e + 2048 : o, wg ? e : o + 1024, wg ? o : e + 2048};
      keep_regs(ad);
      wg_wait<2>();
      if (k > 0) nb_arrive_p(0);
      wg_wait<1>();
      if (k > 0) nb_arrive_p(14);
      wg_wait<0>();
      if (k > 0) {
        nb_arrive_p(6);
        sched_fence();
      }
      fence_regs(acc);
      PROFS(3, wg, 3 + it * 12);
#pragma unroll
      for (int j = 0; j < 24; j++) {
        qa[j] = pack_bf16(acc[4 * j], acc[4 * j + 1]);
        qb[j] = pack_bf16(acc[4 * j + 2], acc[4 * j + 3]);
      }
      keep_regs(qa);
      keep_regs(qb);
      sched_fence();
      if (k >= 2) {
        nb_sync(11);
        stage_out<0, 6>(ad, oa, ob);
        nb_sync(12);
        stage_out<6, 12>(ad, oa, ob);
      }
#pragma unroll
      for (int c = 0; c < 3; c++) hok[c] = mbar_test(bar_full(bars, wg, c), ph);
      if (k >= 2) {
        fence_proxy_async();
        nb_arrive_p(10);
      }
    }

    float aE[52], aO[24], bO[52], bE[28];
    const uint32_t mq = 0xEEEE4444u | zero;
    PROFS(4, wg, 4 + it * 12);

    mbar_wait_if(hok[0], bar_full(bars, wg, 0), ph);
    PROFS(14, wg, 40 + it * 3);
    if (w == 0 && k < 2) GT(22 + wg);
    if (k > 0) nb_sync(3 + (1 - wg));
    wg_fence();
#pragma unroll
    for (int ks = 0; ks < 6; ks++) {
      if (ks == 2) {
        mbar_wait_if(hok[1], bar_full(bars, wg, 1), ph);
        PROFS(14, wg, 41 + it * 3);
        wg_fence();
      }
      if (ks == 4) {
        mbar_wait_if(hok[2], bar_full(bars, wg, 2), ph);
        PROFS(14, wg, 42 + it * 3);
        wg_fence();
      }
      const uint64_t d = dK + ((ks * kChunkBytes) >> 4);
      if (ks == 0) wg_s104z<0, 52>(aE, qa[0], qa[1], qa[2], qa[3], d, 0, mq);
      else wg_s104<0, 52>(aE, qa[4 * ks], qa[4 * ks + 1], qa[4 * ks + 2], qa[4 * ks + 3], d, 1, mq);
      if (ks == 0) wg_s48z<0, 24>(aO, qa[0], qa[1], qa[2], qa[3], d + ((7 * 1024 + 64) >> 4), 0, mq);
    }
    wg_commit();
#pragma unroll
    for (int ks = 1; ks < 6; ks++)
      wg_s48<0, 24>(aO, qa[4 * ks], qa[4 * ks + 1], qa[4 * ks + 2], qa[4 * ks + 3], dK + ((ks * kChunkBytes + 7 * 1024 + 64) >> 4), 1, mq);
    wg_commit();
    wg_s56z<0, 28>(bE, qb[0], qb[1], qb[2], qb[3], dK, 0, mq);
#pragma unroll
    for (int ks = 1; ks < 6; ks++) wg_s56<0, 28>(bE, qb[4 * ks], qb[4 * ks + 1], qb[4 * ks + 2], qb[4 * ks + 3], dK + ((ks * kChunkBytes) >> 4), 1, mq);
    wg_commit();
    wg_wait<2>();
    fence_regs(aE);
    PROFS(5, wg, 5 + it * 12);

    uint32_t pa[14], pb[14], meta[4];
    {
      float vA[14], vB[14];
      pick_v(aE, vA, fl);
      pick_u(aE + 28, vA + 8, fl);
      fence_regs(vA);
      if (k == 0) {
        if (__builtin_expect(__any_sync(0xffffffffu, vA[6] != vA[6]), 0)) {
          wg_wait<0>();
          fence_regs(aO);
          fence_regs(bE);
          if (refetch(sbase + kW1Off, wimg, false)) {
#pragma unroll
            for (int j = 0; j < 24; j++) oa[j] = ob[j] = 0u;
            k -= 2;
            continue;
          }
        }
        if (elect_one()) mbar_arrive(bar_xf(bars));
      }
      wg_fence();
      wg_s104z<0, 52>(bO, qb[0], qb[1], qb[2], qb[3], dK + 4, 0, mq);
#pragma unroll
      for (int ks = 1; ks < 6; ks++)
        wg_s104<0, 52>(bO, qb[4 * ks], qb[4 * ks + 1], qb[4 * ks + 2], qb[4 * ks + 3], dK + ((ks * kChunkBytes + 64) >> 4), 1, mq);
      wg_commit();
      if (k + 1 < nt) nb_arrive(1 + wg);
      uint32_t rt[9];
#pragma unroll
      for (int i = 0; i < 7; i++) rt[i] = sign_bytes(geo[0] << (i >> 2), 0x8888u + 0x1111u * (i & 3));
      rt[7] = sign_bytes(geo[0] << 2, 0x9988u);
      rt[8] = sign_bytes(geo[0] << 2, 0xBBAAu);
      keep_regs(rt);
      pa[13] = geo[0] & zero, pb[13] = geo[1] & zero;
      wg_wait<2>();
      keep_regs(qa);
      fence_regs(aO);
      float oA[6], eB[8];
      pick_u(aO, oA, fl);
      wg_wait<1>();
      fence_regs(bE);
      pick_v(bE, eB, fl);
      vA[8] = sel<kColA>(oA[0], vA[8], fl), vA[9] = sel<kColA>(oA[1], vA[9], fl);
      vA[10] = sel<kColA * 2>(oA[2], vA[10], fl), vA[11] = sel<kColA * 2>(oA[3], vA[11], fl);
      vA[12] = sel<kColA * 4>(oA[4], vA[12], fl), vA[13] = sel<kColA * 4>(oA[5], vA[13], fl);
      {
        const float m1 = __uint_as_float(0x88DD88DDu), m0 = __uint_as_float(0x88DDDD88u);
        meta[0] = 0xDD88DD88u ^ __byte_perm(fl, 0u, 0x3344);
        meta[1] = __float_as_uint(sel<kColA * 16>(sel<kColA>(m1, m0, fl), __uint_as_float(meta[0]), fl));
        meta[2] = __float_as_uint(sel<kColA * 8>(m1, m0, fl));
        meta[3] = __float_as_uint(sel<kColA * 4>(m1, m0, fl));
        keep_regs(meta);
      }
      float mA = own_max(vA, fl);
      fl |= __float_as_uint(eB[7]) & zero;
      fence_regs(eB);
      fence_regs(vA);
      asm volatile("" : "+f"(mA), "+r"(fl));
      sched_fence();
      wg_wait<0>();
      sched_fence();
      keep_regs(qb);
      fence_regs(bO);
      PROFS(6, wg, 6 + it * 12);
      if (w == 0) GT(24 + k);
      mA = quad_max(mA);
      pick_v(bO, vB, fl);
      pick_u(bO + 28, vB + 8, fl);
#pragma unroll
      for (int i = 0; i < 8; i += 2) vB[i] = sel<kColB>(vB[i], eB[i], fl), vB[i + 1] = sel<kColB * 2>(vB[i + 1], eB[i + 1], fl);
#pragma unroll
      for (int i = 0; i < 14; i++) vA[i] = i < 3 ? ex2(vA[i] - mA) : vA[i] - mA;
      fence_regs(vA);
      fence_regs(vB);
      sched_fence();
#pragma unroll
      for (int i = 3; i < 14; i++) vA[i] = ex2(vA[i]);
      const float mB = quad_max(own_max(vB, fl));
      PROFS(7, wg, 7 + it * 12);
#pragma unroll
      for (int i = 0; i < 14; i++) vB[i] = i < 1 ? ex2(vB[i] - mB) : vB[i] - mB;
      fence_regs(vA);
      fence_regs(vB);
      sched_fence();
#pragma unroll
      for (int i = 1; i < 14; i++) vB[i] = ex2(vB[i]);
      route(vA, row_rcp(vA, fl), rt, pa);
      route(vB, row_rcp(vB, fl), rt, pb);
    }
    PROFS(8, wg, 8 + it * 12);
    if (k == NAT_PK) PROFS(18, wg, 53);
    sched_fence();

    float ac0[48], ac1[48];
    {
      float z0[32], z1[32], z2[32];
      uint32_t za[24], zb[24];
      wg_fence();
      pv_chunk<0>(z0, pa, pb, meta, dV);
      wg_commit();
      pv_chunk<1>(z1, pa, pb, meta, dV);
      wg_commit();
      wg_wait<1>();
      if (k == NAT_PK) PROFS(18, wg, 54);
      if (k + 1 < nt) nb_arrive_p(7);
      pv_chunk<2, 0, 3>(z2, pa, pb, meta, dV);
      wg_commit();
      sched_fence();
      fence_regs(z0);
      pack_z<0>(z0, za, zb);
      sched_fence();
      wg_fence();
      pv_chunk<2, 3, 7>(z2, pa, pb, meta, dV);
      wg_commit();
      wg_wait<2>();
      if (k == NAT_PK) PROFS(19, wg, 55);
      if (k + 1 < nt) nb_arrive_p(8);
      if (k < 2) mbar_wait(k == 1 ? bar_wok(bars) : bar_w2a(bars), 0);
      wg_fence();
      g2_steps<0, 3, 0>(ac0, za, zb, dX0);
      wg_commit();
      sched_fence();
      fence_regs(z1);
      pack_z<1>(z1, za, zb);
      sched_fence();
      wg_fence();
      g2_steps<3, 4, 0>(ac0, za, zb, dX0);
      wg_commit();
      g2_steps<4, 8, 0>(ac0, za, zb, dX0);
      wg_commit();
      wg_wait<3>();
      if (k + 1 < nt) nb_arrive_p(9);
      else nb_arrive(11);
      if (k == NAT_PK) PROFS(20, wg, 56);
      keep_regs(pa);
      keep_regs(pb);
      keep_regs(meta);
      sched_fence();
      const uint32_t mok = mbar_test(bar_w2m(bars), k + 1 < nt ? k & 1 : ~k & 1);
      const uint32_t wp = k < 2 ? 0 : k + 1 < nt ? ~k & 1 : k & 1, wok = mbar_test(bar_w2(bars), wp);
      fence_regs(z2);
      pack_z<2>(z2, za, zb);
      keep_regs(za);
      keep_regs(zb);
      sched_fence();
      PROFS(9, wg, 9 + it * 12);
      wg_wait<1>();
      if (k > 0 && k + 1 < nt) nb_arrive(11);
      mbar_wait_if(mok, bar_w2m(bars), k & 1);
      wg_fence();
      g2_steps<8, 12, 0>(ac0, za, zb, dX2);
      wg_commit();
      g2_steps<8, 12, 8>(ac1, za, zb, dY2);
      wg_commit();
      wg_wait<2>();
      if (k > 0 && k + 1 < nt) nb_arrive(12);
      mbar_wait_if(wok, bar_w2(bars), wp);
      wg_fence();
      g2_steps<0, 4, 8>(ac1, za, zb, dY0);
      wg_commit();
      wg_wait<2>();
      if (k + 2 < nt) nb_arrive_p(13);
      const bool direct = k + 2 >= nt;
      sched_fence();
      fence_regs(ac0);
      pack_out<0>(ac0, oa, ob);
      store_rows<0, 1>(direct, poA, poB, oa, ob);
      sched_fence();
      wg_fence();
      g2_steps<4, 8, 8>(ac1, za, zb, dY0);
      wg_commit();
      if (k + 1 < nt) nb_arrive(3 + wg);
      PROFS(10, wg, 10 + it * 12);
      wg_wait<2>();
      if (k + 2 < nt && (k > 0 || nt == 6)) nb_arrive_p(5);
      store_rows<1, 3>(direct, poA, poB, oa, ob);
      __nv_bfloat16 *qA = poA - 192 * wg, *qB = poB - 192 * wg;
      if (k + 2 == nt) nb_sync(11);
      sched_fence();
      wg_wait<0>();
      fence_regs(ac1);
      if (direct) {
        pack_out<1>(ac1, oa, ob);
        asm volatile("" : "+l"(qA), "+l"(qB));
        store_rows<3, 6>(true, qA, qB, oa, ob);
        break;
      }
      sched_fence();
      pack_out<1>(ac1, oa, ob);
      if (k == 0) {
        if (any_nan(oa)) {
          for (int c = 0; c < 3 && __any_sync(0xffffffffu, geo[2] & 1u); c++) mbar_wait(bar_x(bars, 1, c), 1);
          bool first = true;
          do {
            if (!__any_sync(0xffffffffu, refetch(sbase + kW2Off, wimg + w2_offset(), first))) break;
            first = false;
            wg_fence();
            g2_steps<0, 8, 0>(ac0, za, zb, dX0);
            g2_steps<8, 12, 0>(ac0, za, zb, dX2);
            g2_steps<8, 12, 8>(ac1, za, zb, dY2);
            g2_steps<0, 8, 8>(ac1, za, zb, dY0);
            wg_commit();
            wg_wait<0>();
            fence_regs(ac0);
            fence_regs(ac1);
            pack_out<0>(ac0, oa, ob);
            pack_out<1>(ac1, oa, ob);
          } while (any_nan(oa));
          if (__any_sync(0xffffffffu, geo[2] & 1u)) {
            asm volatile("bar.sync 15, 128;" ::: "memory");
            if (w == 0 && elect_one()) {
              const TileCoord tc = decode_tile(tt, tile0 + 2);
              mbar_arrive_expect_tx(bar_raw(bars), kWChunk);
#pragma unroll 1
              for (int c = 0; c < 3; c++) load_px(tm, tt, sbase + x_chunk(2, c), bar_raw(bars), first_line(tc) + c, tc.kind);
            }
            __syncwarp();
            mbar_wait(bar_raw(bars), 0);
          }
        }
        if (nt < 6) nb_arrive_p(5);
        if (elect_one()) mbar_arrive(bar_wok(bars));
      }
      keep_regs(za);
      keep_regs(zb);
#pragma unroll
      for (int i = 0; i < 4; i++) geo[i] = geo[i + 2];
      keep_regs(oa);
      keep_regs(ob);
      PROFS(12, wg, 12 + it * 12);
      sched_fence();
    }
  }
  PROF(wg, 38);
  GT_DUMP();
  PROF_DUMP(wg);
}

struct HaloCols { int vj, vc, uj, uc; };
__device__ __forceinline__ HaloCols halo_cols(const TileCoord& tc) {
  const int c0 = halo_c0(tc);
  return HaloCols{c0 > 98, c0 > 98 ? 98 : c0 + 3, c0 < 0 ? -1 : 0, c0 < 0 ? 4 : c0};
}
__device__ __forceinline__ void first_halo(const Maps& tm, uint32_t sbase, const TileCoord tc, int i) {
  const HaloCols hc = halo_cols(tc);
  const uint32_t dst = sbase + i * kChunkBytes, bar = bar_full(sbase + kBarOff, 0, i >> 1);
  const int h0 = halo_r0(tc), ch = 24 * tc.pc + 4 * i;
  tma_load_5d(dst, &tm.v14, bar, ch, hc.vj, hc.vc, tc.pr, h0);
  tma_load_5d(dst + 7 * 1024, &tm.u8, bar, ch, hc.uj, h0 + (tc.up ? 0 : -2), tc.pr, hc.uc);
  tma_load_5d(dst + 10 * 1024, &tm.u8, bar, ch, hc.uj, h0 + (tc.up ? 8 : 6), tc.pr, hc.uc);
}
__device__ __forceinline__ void load_halo(const Maps& tm, uint32_t sbase, uint32_t bars, const TileCoord tc, int k, int c) {
  const HaloCols hc = halo_cols(tc);
  const int h6 = halo_r0(tc) + (tc.up ? 0 : 8), h2 = halo_r0(tc) + 6, h8 = halo_r0(tc) + (tc.up ? 0 : 6), ch = 24 * tc.pc + 8 * c;
  uint32_t dv = sbase + 2 * c * kChunkBytes, du = dv + 7 * 1024;
  if (((k ^ tc.up) & 1) == 0) dv += 4 * 1024, du += 3 * 1024;
  const uint32_t bar = bar_full(bars, k & 1, c);
  mbar_arrive_expect_tx(bar, 14 * 1024);
  nb_sync_p(7 + c);
#pragma unroll
  for (int h = 0; h < 2; h++) {
    tma_load_5d(dv + h * kChunkBytes, &tm.v6, bar, ch + 4 * h, hc.vj, hc.vc, tc.pr, h6);
    tma_load_5d(du + h * kChunkBytes, &tm.u8, bar, ch + 4 * h, hc.uj, h8, tc.pr, hc.uc);
    tma_load_5d(sbase + (2 * c + h) * kChunkBytes + 3 * 1024, &tm.v2, bar, ch + 4 * h, hc.vj, hc.vc, tc.pr, h2);
  }
  PROFS(15, 2, k * 4 + c);
}
__device__ __forceinline__ void gather_px(const __nv_bfloat16* __restrict__ x, uint32_t sbase, const TileCoord tc) {
  const int lane = threadIdx.x & 31, g = lane >> 3;
  uint32_t ro[4], co[4];
#pragma unroll
  for (int i = 0; i < 4; i++) {
    ro[i] = qpix(tc.pr, 8 * tc.I + 2 * i + (g & 1)) * (kW * kC * 2) + 16 * (lane & 7);
    co[i] = qpix(tc.pc, 8 * tc.J + 2 * i + (g >> 1)) * (kC * 2);
  }
  const uint32_t dst = sbase + kXOff + g * 128 + (((lane & 7) ^ g) << 4);
  if (lane < 8)
    asm volatile("cp.async.bulk.prefetch.L2.global [%0], 3456;" ::"l"(x + (qpix(tc.pr, 8 * tc.I + lane) * kW + 215 * tc.pc) * kC) : "memory");
  __syncwarp();
  keep_regs(ro);
  keep_regs(co);
  sched_fence();
  nb_sync_p(13);
  nb_sync_p(5);
#pragma unroll
  for (int i = 0; i < 16; i++) {
    const char* src = (const char*)x + (ro[i >> 2] + co[i & 3]);
#pragma unroll
    for (int q = 0; q < 3; q++)
      asm volatile("cp.async.cg.shared.global [%0], [%1], 16;" ::"r"((dst ^ ((i & 1) * 576)) + (i >> 1) * 1024 + q * 8192), "l"(src + 128 * q) : "memory");
  }
  asm volatile("cp.async.wait_all;" ::: "memory");
  fence_proxy_async();
  __syncwarp();
  if (lane < 3) mbar_arrive(bar_x(sbase + kBarOff, 1, lane));
  __syncwarp();
}

__global__ void __launch_bounds__(384, 1)
nat_kernel(const __nv_bfloat16* __restrict__ x, __nv_bfloat16* out, const __nv_bfloat16* __restrict__ wqkv,
           const __nv_bfloat16* __restrict__ wo, uint8_t* wimg, const uint32_t zero,
           const __grid_constant__ Maps tm, const __grid_constant__ TileTable tt) {
  extern __shared__ uint8_t smem_raw[];
  constexpr uint32_t sbase = 1024;
  constexpr uint32_t bars = sbase + kBarOff;
  const int tid = threadIdx.x;
  const uint32_t t_start = now_ns();
  if (tid == 0) GT(0);
  const int role = __shfl_sync(0xffffffffu, blockIdx.x + 8 * (tid & ~31), 0), wid = role >> 8;
  const bool w2cta = blockIdx.x - 128 < 3 && wqkv != nullptr;
  if (wid >= 8) {
    asm volatile("setmaxnreg.dec.sync.aligned.u32 24;");
    if (smem_u32(smem_raw) != sbase) __trap();
    const int c = wid & 3, lane = tid & 31;
    const int tile0 = blockIdx.x * kTilesPerCta, nt = num_tiles();
    uint32_t w2o = 0;
    if (c == 3) {
      if (elect_one()) wait_clock(t_start, NAT_TM);
      __syncwarp();
      asm volatile("prefetch.tensormap [%0];" ::"l"((uint64_t)tm.px) : "memory");
      asm volatile("prefetch.tensormap [%0];" ::"l"((uint64_t)&tm.v6) : "memory");
      asm volatile("prefetch.tensormap [%0];" ::"l"((uint64_t)&tm.v2) : "memory");
      asm volatile("prefetch.tensormap [%0];" ::"l"((uint64_t)(tm.px + (blockIdx.x < 112 ? 5 : 6))) : "memory");
      asm volatile("prefetch.tensormap [%0];" ::"l"((uint64_t)(tm.px + 7)) : "memory");
      if (nt < 6) {
        asm volatile("prefetch.tensormap [%0];" ::"l"((uint64_t)(tm.px + 1)) : "memory");
        asm volatile("prefetch.tensormap [%0];" ::"l"((uint64_t)(tm.px + 2)) : "memory");
        asm volatile("prefetch.tensormap [%0];" ::"l"((uint64_t)&tm.v14) : "memory");
        asm volatile("prefetch.tensormap [%0];" ::"l"((uint64_t)&tm.u8) : "memory");
      }
      __nanosleep(1600);
      asm volatile("bar.sync 4, 64;" ::: "memory");
      w2o = w2_offset();
      if (elect_one()) {
        mbar_arrive_expect_tx(bar_w2a(bars), kWChunk);
        mbar_arrive_expect_tx(bar_w2(bars), kWChunk);
        sleep_clock(t_start, NAT_TW2);
        bulk_load(sbase + kW2Off, wimg + w2o, kWChunk, bar_w2a(bars));
        mbar_wait(bar_xf(bars), 0);
        bulk_load(sbase + kW2Off + 2 * kWChunk, wimg + (w2o + 2 * kWChunk), kWChunk, bar_w2(bars));
      }
      __syncwarp();
      if (nt < 6) gather_px(x, sbase, decode_tile(tt, tile0 + 2));
      if (wqkv == nullptr) return;
      __nanosleep(2500);
      mbar_wait(bar_wok(bars), 0);
      if (lane == 0) asm volatile("red.relaxed.gpu.global.add.u32 [%0], 1;" ::"l"(g_flag) : "memory");
      if (blockIdx.x != kCtas - 1) return;
#pragma unroll
      for (int i = 0; i < 8; i++) asm volatile("st.shared.v4.u32 [%0], {%1,%1,%1,%1};" ::"r"(bars + 1024 + i * 512 + lane * 16), "r"(kEmpty) : "memory");
      fence_proxy_async();
      __syncwarp();
      if (elect_one()) {
#pragma unroll 1
        for (int i = 0; i < 36; i++) {
          if (i == 18) {
            uint32_t v, it = 0;
            do {
              __nanosleep(500);
              asm volatile("ld.relaxed.gpu.global.u32 %0, [%1];" : "=r"(v) : "l"(g_flag) : "memory");
            } while (v < gridDim.x && ++it < (1u << 18));
          }
          asm volatile("cp.async.bulk.global.shared::cta.bulk_group [%0], [%1], 4096;" ::"l"(
                           wimg + (i < 18 ? 3 * kWBytes - w2o + i * 4096 : (i - 18) * 4096)), "r"(bars + 1024) : "memory");
          asm volatile("cp.async.bulk.commit_group;" ::: "memory");
          asm volatile("cp.async.bulk.wait_group.read 1;" ::: "memory");
        }
        asm volatile("cp.async.bulk.wait_group 0;" ::: "memory");
        g_flag[0] = 0;
        g_flag[32] = w2o == kWBytes;
      }
      return;
    }
    if (!elect_one()) return;
    if (c == 0) {
      for (int i = 0; i < kNumBars; i++)
        if ((i != 0 && i != 10 || nt < 6) && (i != 21 || !w2cta)) mbar_init(bars + i * 8, i == 13 || i == 16 ? 4 : 1);
      asm volatile("st.shared.v2.u32 [%0], {%1,%1};" ::"r"(bars + 192), "r"(0) : "memory");
      asm volatile("fence.mbarrier_init.release.cluster;" ::: "memory");
      if (w2cta) asm volatile("bar.sync 10, 64;" ::: "memory");
      asm volatile("bar.arrive 0, 160;" ::: "memory");
      asm volatile("bar.arrive 14, 160;" ::: "memory");
      asm volatile("bar.arrive 13, 96;" ::: "memory");
      asm volatile("bar.arrive 4, 64;" ::: "memory");
      const TileCoord tc0 = decode_tile(tt, tile0);
      const HaloCols hc = halo_cols(tc0);
      const int h0 = halo_r0(tc0);
#pragma unroll
      for (int j = 0; j < 3; j++)
        if (j > 0 || nt < 6) mbar_arrive_expect_tx(bar_full(bars, 0, j), 2 * kChunkBytes);
      wait_clock(t_start, NAT_HP);
#pragma unroll
      for (int q = 8; q < 24 && !w2cta; q += 8) {
        tma_prefetch_5d(blockIdx.x < 112 ? &tm.v6 : &tm.v14, 24 * tc0.pc + q, hc.vj, hc.vc, tc0.pr, h0 + (tc0.up || blockIdx.x >= 112 ? 0 : 8));
        tma_prefetch_5d(&tm.u8, 24 * tc0.pc + q, hc.uj, h0 + (tc0.up ? 0 : 6), tc0.pr, hc.uc);
      }
#pragma unroll 1
      for (int i = nt < 6 ? 0 : 2; i < 6; i++) {
        if (i == 2) mbar_wait(bar_w1q(bars), 0);
        first_halo(tm, sbase, tc0, i);
      }
      mbar_arrive(bar_go(bars));
      w2o = w2_offset();
    } else {
      asm volatile("bar.sync 13, 96;" ::: "memory");
      if (c == 2) {
        if (wqkv != nullptr && blockIdx.x < 131) asm volatile("bar.sync 12, 64;" ::: "memory");
        const uint32_t c0 = clock();
        while ((uint32_t)clock() - c0 < NAT_TD && nt == 6) { }
        wait_clock(t_start, NAT_T0);
#pragma unroll
        for (int j = 0; j < 3; j++) {
          mbar_arrive_expect_tx(bar_w1c(bars, j), kWChunk);
          bulk_load(sbase + kW1Off + j * kWChunk, wimg + j * kWChunk, kWChunk, bar_w1c(bars, j));
        }
        mbar_arrive(bar_w1q(bars));
        GT(2);
      } else {
#pragma unroll 1
        for (int j = nt == 6; j < 2; j++) {
          const TileCoord tc = decode_tile(tt, tile0 + j);
          const int line = first_line(tc);
          if (j == 1) mbar_wait(bar_go(bars), 0);
          if (j == 0) GT(15);
#pragma unroll 1
          for (int q = 0; q < 3; q++) {
            load_px(tm, tt, sbase + x_chunk(j, q), bar_x(bars, j, q), line + q, tc.kind);
            if (j == 1 || q == 0) mbar_arrive_expect_tx(bar_x(bars, j, q), j ? 8192 : kWChunk);
          }
          if (j == 0) GT(16);
        }
        w2o = w2_offset();
        sleep_clock(t_start, NAT_TW2);
        mbar_wait(bar_xf(bars), 0);
      }
    }
#pragma unroll 1
    for (int k = 1; k < nt; k++) {
      const TileCoord tn = decode_tile(tt, tile0 + k + 1);
      const int line = first_line(tn);
      const bool more = k + 1 < nt && (k > 1 || nt == 6);
      if (c == 1) {
#pragma unroll
        for (int q = 0; q < 3; q++) {
          nb_sync_p(q == 0 ? 0 : q == 1 ? 14 : 6);
          bulk_load(sbase + x_chunk(k, q), wimg + (w2o + x_chunk(k, q) - kW2Off), 8192, bar_w2m(bars));
        }
        mbar_arrive_expect_tx(bar_w2m(bars), kWChunk);
      }
      if (c == 2) {
        if (k == 1) sleep_clock(t_start, NAT_TX2);
        else __nanosleep(NAT_PFD);
#pragma unroll 1
        for (int q = 0; q < 3 && more; q++) load_px(tm, tt, 0, 0, line + q, tn.kind);
      }
      if (c == 2 && (blockIdx.x >= 112 || k == 5)) {
        const TileCoord tc = decode_tile(tt, tile0 + k);
        const HaloCols hc = halo_cols(tc);
        const int h8 = halo_r0(tc) + (tc.up ? 0 : 6);
#pragma unroll 1
        for (int q = 0; q < 24; q += 8) {
          tma_prefetch_5d(&tm.v6, 24 * tc.pc + q, hc.vj, hc.vc, tc.pr, h8);
          tma_prefetch_5d(&tm.v2, 24 * tc.pc + q, hc.vj, hc.vc, tc.pr, h8 + 6);
          tma_prefetch_5d(&tm.u8, 24 * tc.pc + q, hc.uj, h8, tc.pr, hc.uc);
        }
      }
      load_halo(tm, sbase, bars, decode_tile(tt, tile0 + k), k, c);
      if (c == 0 && more) {
        if (nt < 6) mbar_wait(bar_x(bars, 1, 0), 1);
#pragma unroll
        for (int q = 0; q < 3; q++) {
          if (q < 2) nb_sync_p(q ? 5 : 13);
          load_px(tm, tt, sbase + x_chunk(k + 1, q), bar_x(bars, 1, q), line + q, tn.kind);
          if (q != 1) mbar_arrive_expect_tx(bar_x(bars, 1, q), 8192);
        }
        mbar_arrive_expect_tx(bar_x(bars, 1, 1), 8192);
        PROFS(16, 2, k * 4 + 3);
      }
      if (c == 0 && k >= 2) {
        const TileCoord tp = decode_tile(tt, tile0 + k - 2);
        const int lp = first_line(tp);
        nb_sync_p(10);
        __nanosleep(NAT_XW);
        store_px(tm, tt, sbase + out_slot(k, nt), lp, tp.kind);
        if (k + 1 < nt) {
          asm volatile("cp.async.bulk.wait_group.read 0;" ::: "memory");
          bulk_load(sbase + out_slot(k, nt), wimg + (w2o + out_slot(k, nt) - kW2Off), kWChunk, bar_w2(bars));
          mbar_arrive_expect_tx(bar_w2(bars), kWChunk);
        }
      }
    }
    asm volatile("cp.async.bulk.wait_group 0;" ::: "memory");
  } else {
    if ((role & 128) == 0) {
      if ((uint32_t)role - 1024u < 272u && wqkv != nullptr) {
        fold_w1(min(2 * (role & 127) + (wid & 1), (role & 127) + 16), wqkv, wimg);
        if (wid == 4) asm volatile("bar.arrive 12, 64;" ::: "memory");
        if (tid == 128) GT(7);
      }
      sched_fence();
      if (wid == 1 && elect_one()) {
        mbar_init(bar_x(bars, 0, 0), 1);
        asm volatile("fence.mbarrier_init.release.cluster;" ::: "memory");
        GT(15);
        const int b = role & 127, ext = b >= 112, strip = ext ? 3 * b - (b < 121 ? 335 : 333) : b >> 1;
        const int pr = strip >= 28, st = strip - 28 * pr, edge = st - 1u >= 26u, end = ext ? pr : edge & st;
        const int line = 3 * ((ext ? 215 * pr : 122 - 19 * pr - 16 * (b & 1)) * kW + max(8 * st + 5 * (st & 1) - 6, 0));
        const CUtensorMap* map = tm.px + ext + 3 * edge;
        if (ext | edge) asm volatile("prefetch.tensormap [%0];" ::"l"((uint64_t)(map + 1)) : "memory");
#pragma unroll
        for (int q = 0; q < 3; q++)
          tma_load_5d(sbase + x_chunk(0, q) + 2048 * end, map, bar_x(bars, 0, 0), 0, 0, 0, 0, line + q + end * (ext ? 9 * kW : 6));
        if (ext | edge) {
#pragma unroll
          for (int q = 0; q < 3; q++)
            tma_load_5d(sbase + x_chunk(0, q) + 6144 * (1 - end), map + 1, bar_x(bars, 0, 0), 0, 0, 0, 0, line + q + (1 - end) * (ext ? 18 * kW : 9));
        }
        mbar_arrive_expect_tx(bar_x(bars, 0, 0), kWChunk);
        GT(16);
      }
      __syncwarp();
      sched_fence();
      if (wid == 2 && elect_one()) {
        const TileCoord tc = decode_tile(tt, blockIdx.x * kTilesPerCta);
        mbar_init(bar_full(bars, 0, 0), 1);
        asm volatile("fence.mbarrier_init.release.cluster;" ::: "memory");
        mbar_arrive_expect_tx(bar_full(bars, 0, 0), 2 * kChunkBytes);
        asm volatile("prefetch.tensormap [%0];" ::"l"((uint64_t)&tm.u8) : "memory");
        GT(17);
        first_halo(tm, sbase, tc, 0);
        first_halo(tm, sbase, tc, 1);
      }
      __syncwarp();
    }
    sched_fence();
    {
      if (blockIdx.x >= 128 && wqkv != nullptr && (wid | 2) == 2 && elect_one())
        asm volatile("cp.async.bulk.prefetch.L2.global [%0], %1;" ::"l"(wid ? wo + (blockIdx.x & 3) * 48 * 192 : wqkv + (blockIdx.x & 3) * 48 * 576),
                     "r"(wid ? 48 * 384 : 48 * 1152) : "memory");
      __syncwarp();
      if (w2cta) {
        const int q = blockIdx.x & 3, h = wid >> 2;
        uint32_t w2o = 0;
        if (wid == 1 && elect_one()) {
          asm volatile("prefetch.tensormap [%0];" ::"l"((uint64_t)&tm.wo) : "memory");
          mbar_init(bar_raw(bars, 0), 1);
          mbar_init(bar_raw(bars, 1), 1);
          asm volatile("fence.mbarrier_init.release.cluster;" ::: "memory");
#pragma unroll
          for (int j = 0; j < 3; j++)
            asm volatile("cp.async.bulk.tensor.3d.shared::cluster.global.tile.mbarrier::complete_tx::bytes [%0], [%1, {%3, %4, %5}], [%2];" ::"r"(
                             j ? sbase + kW2Off + (j - 1) * (kWBytes / 2) : sbase),
                         "l"((uint64_t)(j ? &tm.wo : &tm.wv)), "r"(bar_raw(bars, j >> 1)), "r"(0), "r"(j ? 0 : 64 * q), "r"(j ? 3 * j - 3 : 6) : "memory");
          mbar_arrive_expect_tx(bar_raw(bars, 0), kWChunk + kWBytes / 2);
          mbar_arrive_expect_tx(bar_raw(bars, 1), kWBytes / 2);
          w2o = w2_offset();
        }
        __syncwarp();
#pragma unroll 1
        for (int r = 1 - h;; r++) {
          if (r > 0) asm volatile("bar.sync 11, 256;" ::: "memory");
          if (r == 2) break;
          if (r > 0) {
            mbar_wait(bar_raw(bars, 0), 0);
            mbar_wait(bar_raw(bars, h), 0);
          }
          if (tid == 0) GT(7);
          float acc[48];
          const uint64_t db = make_desc(sbase + kW2Off + h * (kWBytes / 2), kWChunk / 2, 512, 2);
          wg_fence();
          wg_m96tz<0, 48>(acc, make_desc(sbase, 16, 1024), db, 0);
#pragma unroll
          for (int s = 1; s < 12; s++) wg_m96t<0, 48>(acc, make_desc(sbase + (s >> 2) * 8192 + (s & 3) * 32, 16, 1024), db + s * 64, 1);
          wg_commit();
          wg_wait<0>();
          fence_regs(acc);
          if (tid == 0) GT(19);
          const int m = (tid >> 3) & 3;
#pragma unroll
          for (int j = 0; j < 12; j += 2) {
            const int n = g2_inv(8 * (j + (m >> 1)) + (tid & 7));
            asm volatile("stmatrix.sync.aligned.m8n8.x4.trans.shared.b16 [%0], {%1,%2,%3,%4};" ::"r"(
                             sbase + kW1Off + h * (kWChunk / 2) + n * 128 + (((2 * (wid & 3) + (m & 1)) ^ (n & 7)) << 4)),
                         "r"(pack_bf16(acc[4 * j], acc[4 * j + 1])), "r"(pack_bf16(acc[4 * j + 2], acc[4 * j + 3])),
                         "r"(pack_bf16(acc[4 * j + 4], acc[4 * j + 5])), "r"(pack_bf16(acc[4 * j + 6], acc[4 * j + 7])) : "memory");
          }
          fence_proxy_async();
        }
        if (tid == 0) GT(18);
        if (wid == 1) {
          if (elect_one()) {
#pragma unroll
            for (int i = 0; i < 2; i++)
              asm volatile("cp.async.bulk.global.shared::cta.bulk_group [%0], [%1], %2;" ::"l"(wimg + (w2o + w2piece(i, q) * (kWChunk / 2))),
                           "r"(sbase + kW1Off + i * (kWChunk / 2)), "r"(kWChunk / 2) : "memory");
            asm volatile("cp.async.bulk.commit_group;" ::: "memory");
          }
          __syncwarp();
          asm volatile("bar.arrive 10, 64;" ::: "memory");
          if (elect_one()) asm volatile("cp.async.bulk.wait_group.read 0;" ::: "memory");
          if (tid == 32) GT(31);
          __syncwarp();
          asm volatile("bar.arrive 12, 64;" ::: "memory");
        }
      }
    }
    __syncwarp();
    if (wid < 4) asm volatile("bar.sync 0, 160;" ::: "memory");
    else asm volatile("bar.sync 14, 160;" ::: "memory");
    asm volatile("setmaxnreg.inc.sync.aligned.u32 240;");
    consumer(wid >> 2, out, wimg, sbase, zero, tm, tt);
  }
}

}

typedef CUresult (*PFN_encodeTiled)(CUtensorMap*, CUtensorMapDataType, cuuint32_t, void*, const cuuint64_t*,
                                    const cuuint64_t*, const cuuint32_t*, const cuuint32_t*, CUtensorMapInterleave,
                                    CUtensorMapSwizzle, CUtensorMapL2promotion, CUtensorMapFloatOOBfill);

extern "C" void kernel_launch(void* const* d_in, const int* in_sizes, int n_in, void* d_out, int out_size) {
  const __nv_bfloat16* x = (const __nv_bfloat16*)d_in[0];
  const __nv_bfloat16* wqkv = (const __nv_bfloat16*)d_in[1];
  const __nv_bfloat16* wo = (const __nv_bfloat16*)d_in[2];
  __nv_bfloat16* out = (__nv_bfloat16*)d_out;

  static PFN_encodeTiled encode = nullptr;
  static int num_sms = 0;
  static uint8_t* wimg = nullptr;
  if (!encode) {
    void* fn = nullptr;
    cudaDriverEntryPointQueryResult qres;
    cudaGetDriverEntryPoint("cuTensorMapEncodeTiled", &fn, cudaEnableDefault, &qres);
    encode = (PFN_encodeTiled)fn;
    cudaFuncSetAttribute(nat::nat_kernel, cudaFuncAttributeMaxDynamicSharedMemorySize, nat::kSmemBytes);
    cudaGetSymbolAddress((void**)&wimg, nat::g_wimg32);
    int dev = 0;
    cudaGetDevice(&dev);
    cudaDeviceGetAttribute(&num_sms, cudaDevAttrMultiProcessorCount, dev);
  }
  nat::Maps tm;
  cuuint32_t estr[5] = {1, 1, 1, 1, 1};
  {
    cuuint64_t vdim[5] = {48, 2, 105, 2, 112}, udim[5] = {48, 2, 112, 2, 105};
    cuuint64_t vstr[4] = {7 * 768, 768, 224 * 384, 2 * 224 * 384}, ustr[4] = {7 * 768, 2 * 224 * 384, 224 * 384, 768};
    CUtensorMap* maps[4] = {&tm.v6, &tm.v2, &tm.v14, &tm.u8};
    for (int i = 0; i < 4; i++) {
      cuuint32_t box[5] = {4, 2, i < 3 ? 4u : 8u, 1, i == 0 ? 6u : i == 1 ? 2u : i == 2 ? 14u : 3u};
      encode(maps[i], CU_TENSOR_MAP_DATA_TYPE_UINT32, 5, (void*)x, i < 3 ? vdim : udim, i < 3 ? vstr : ustr, box, estr,
             CU_TENSOR_MAP_INTERLEAVE_16B, CU_TENSOR_MAP_SWIZZLE_128B, CU_TENSOR_MAP_L2_PROMOTION_L2_128B, CU_TENSOR_MAP_FLOAT_OOB_FILL_NONE);
    }
  }
  for (int i = 0; i < 8; i++) {
    const cuuint32_t row = 224 * 384;
    const cuuint32_t shape[8][6] = {{2, 8, 4, 2 * row, 768, 4 * row}, {2, 8, 3, row, 768, 2 * row},     {2, 8, 1, 2 * row, 768, 4 * row},
                                    {8, 2, 3, 2 * row, 4 * 384, 384}, {8, 2, 1, 2 * row, 5 * 384, 384}, {4, 2, 3, 4 * row, 2 * row, 128},
                                    {4, 2, 3, 768, row, 128},         {4, 2, 3, 768, 2 * row, 128}};
    const cuuint32_t* sh = shape[i];
    cuuint64_t dim[5] = {64, sh[0], sh[1], sh[2], 224 * 224 * 3};
    cuuint64_t str[4] = {sh[3], sh[4], sh[5], 128};
    cuuint32_t box[5] = {64, sh[0], sh[1], sh[2], 1};
    encode(tm.px + i, CU_TENSOR_MAP_DATA_TYPE_BFLOAT16, 5, i < 5 ? (void*)x : (void*)out, dim, str, box, estr, CU_TENSOR_MAP_INTERLEAVE_NONE,
           CU_TENSOR_MAP_SWIZZLE_128B, i < 5 ? CU_TENSOR_MAP_L2_PROMOTION_L2_128B : CU_TENSOR_MAP_L2_PROMOTION_NONE,
           CU_TENSOR_MAP_FLOAT_OOB_FILL_NONE);
  }
  for (int i = 0; i < 2; i++) {
    cuuint64_t dim[3] = {i ? 32u : 64u, 192, i ? 6u : 9u}, str[2] = {i ? 384u : 1152u, i ? 64u : 128u};
    cuuint32_t box[3] = {i ? 32u : 64u, i ? 192u : 64u, 3};
    encode(i ? &tm.wo : &tm.wv, CU_TENSOR_MAP_DATA_TYPE_BFLOAT16, 3, i ? (void*)wo : (void*)wqkv, dim, str, box, estr,
           CU_TENSOR_MAP_INTERLEAVE_NONE, i ? CU_TENSOR_MAP_SWIZZLE_64B : CU_TENSOR_MAP_SWIZZLE_128B, CU_TENSOR_MAP_L2_PROMOTION_L2_256B,
           CU_TENSOR_MAP_FLOAT_OOB_FILL_NONE);
  }
  nat::TileTable tt;
  nat::make_tiles(tt);
  const int grid = nat::kCtas;
  if (num_sms >= grid) {
    nat::nat_kernel<<<grid, 384, nat::kSmemBytes>>>(x, out, wqkv, wo, wimg, 0u, tm, tt);
  } else {
    nat::fold_kernel<<<27, 256>>>(wqkv, wo, wimg);
    nat::nat_kernel<<<grid, 384, nat::kSmemBytes>>>(x, out, nullptr, nullptr, wimg, 0u, tm, tt);
  }
}
```

```cpp
#include <cuda_runtime.h>
#include <cuda_bf16.h>
#include <cuda.h>
#include <stdint.h>

#define NAT_TM 1300
#define NAT_HP 1800
#define NAT_T0 2060
#define NAT_TD 1250
#define NAT_TX2 3800
#define NAT_TW2 4600
#define NAT_PFD 300
#define NAT_XW 200
#define NAT_PK 3
namespace nat {

constexpr int kW = 224, kC = 192;
constexpr int kCtas = 132;
constexpr int kTilesPerCta = 6;
constexpr float kAlpha = 0.07216878364870322f * 1.4426950408889634f;
constexpr uint32_t kChunkBytes = 13 * 1024;
constexpr uint32_t kWChunk = 192 * 128;
constexpr uint32_t kWBytes = 3 * kWChunk;
constexpr uint32_t kW1Off = 6 * kChunkBytes;
constexpr uint32_t kW2Off = kW1Off + kWBytes;
constexpr uint32_t kXOff = kW2Off + kWChunk;
constexpr uint32_t kBarOff = kW2Off + kWBytes;
constexpr uint32_t kProfOff = kBarOff + 208;
constexpr uint32_t kSmemBytes = kBarOff + 1024 + 4096;

static_assert(kW1Off % 1024 == 0 && kW2Off % 1024 == 0 && kChunkBytes % 1024 == 0, "swizzle alignment");
static_assert(kSmemBytes <= 232448, "smem");

constexpr uint32_t kEmpty = 0xFFFFFFFFu;
#define NAT_R8(v) v, v, v, v, v, v, v, v
#define NAT_R2K(v) NAT_R8(NAT_R8(NAT_R8(v))), NAT_R8(NAT_R8(NAT_R8(v))), NAT_R8(NAT_R8(NAT_R8(v))), NAT_R8(NAT_R8(NAT_R8(v)))
#define NAT_IMG NAT_R8(NAT_R2K(kEmpty)), NAT_R2K(kEmpty)
__device__ __align__(1024) uint32_t g_wimg32[3 * kWBytes / 4] = {NAT_IMG, NAT_IMG, NAT_IMG};
static_assert(kWBytes / 4 == 9 * 2048, "initialiser");
__device__ __align__(128) uint32_t g_flag[64];
__device__ __forceinline__ uint32_t w2_offset() {
  uint32_t v;
  asm volatile("ld.relaxed.gpu.global.u32 %0, [%1];" : "=r"(v) : "l"(g_flag + 32) : "memory");
  return (1 + v) * kWBytes;
}

#define PROFS(id, wgid, slotid) do { } while (0)
#define PROF(wgid, slotid) do { } while (0)
#define PROF_DUMP(wgid) do { } while (0)

#define GT(slotid) do { } while (0)
#define GT_DUMP() do { } while (0)

__device__ __forceinline__ uint32_t smem_u32(const void* p) { return (uint32_t)__cvta_generic_to_shared(p); }

__device__ __forceinline__ void mbar_init(uint32_t bar, uint32_t count) {
  asm volatile("mbarrier.init.shared::cta.b64 [%0], %1;" ::"r"(bar), "r"(count) : "memory");
}
__device__ __forceinline__ void mbar_arrive(uint32_t bar) {
  asm volatile("mbarrier.arrive.shared::cta.b64 _, [%0];" ::"r"(bar) : "memory");
}
__device__ __forceinline__ void mbar_arrive_expect_tx(uint32_t bar, uint32_t bytes) {
  asm volatile("mbarrier.arrive.expect_tx.shared::cta.b64 _, [%0], %1;" ::"r"(bar), "r"(bytes) : "memory");
}
__device__ __forceinline__ void mbar_wait(uint32_t bar, uint32_t parity) {
  uint32_t ok;
  uint32_t it = 0;
  do {
    asm volatile(
        "{\n.reg .pred p;\n"
        "mbarrier.try_wait.parity.shared::cta.b64 p, [%1], %2;\n"
        "selp.u32 %0, 1, 0, p;\n}\n"
        : "=r"(ok)
        : "r"(bar), "r"(parity)
        : "memory");
    if (++it > (1u << 24)) break;
  } while (!ok);
}
__device__ __forceinline__ uint32_t mbar_test(uint32_t bar, uint32_t parity) {
  uint32_t ok;
  asm volatile("{\n.reg .pred p;\nmbarrier.test_wait.parity.shared::cta.b64 p, [%1], %2;\nselp.u32 %0, 1, 0, p;\n}\n"
               : "=r"(ok) : "r"(bar), "r"(parity) : "memory");
  return ok;
}
__device__ __forceinline__ void mbar_wait_if(uint32_t ok, uint32_t bar, uint32_t parity) {
  if (!__all_sync(0xffffffffu, ok)) mbar_wait(bar, parity);
}
__device__ __forceinline__ bool elect_one() {
  uint32_t r;
  asm volatile("{\n.reg .pred p;\nelect.sync _|p, 0xffffffff;\nselp.u32 %0, 1, 0, p;\n}\n" : "=r"(r));
  return r != 0;
}
__device__ __forceinline__ void nb_arrive(int id) { asm volatile("bar.arrive %0, 256;" ::"r"(id) : "memory"); }
__device__ __forceinline__ void nb_sync(int id) { asm volatile("bar.sync %0, 256;" ::"r"(id) : "memory"); }
__device__ __forceinline__ void nb_arrive_p(int id) { asm volatile("bar.arrive %0, 160;" ::"r"(id) : "memory"); }
__device__ __forceinline__ void nb_sync_p(int id) { asm volatile("bar.sync %0, 160;" ::"r"(id) : "memory"); }
__device__ __forceinline__ void fence_proxy_async() { asm volatile("fence.proxy.async.shared::cta;" ::: "memory"); }

__device__ __forceinline__ void tma_load_5d(uint32_t dst, const CUtensorMap* map, uint32_t bar, int c0, int c1, int c2,
                                            int c3, int c4) {
  asm volatile(
      "cp.async.bulk.tensor.5d.shared::cluster.global.tile.mbarrier::complete_tx::bytes "
      "[%0], [%1, {%3, %4, %5, %6, %7}], [%2];"
      ::"r"(dst), "l"((uint64_t)map), "r"(bar), "r"(c0), "r"(c1), "r"(c2), "r"(c3), "r"(c4)
      : "memory");
}
__device__ __forceinline__ void bulk_load(uint32_t dst, const void* src, uint32_t bytes, uint32_t bar) {
  asm volatile("cp.async.bulk.shared::cluster.global.mbarrier::complete_tx::bytes [%0], [%1], %2, [%3];"
               ::"r"(dst), "l"((uint64_t)src), "r"(bytes), "r"(bar)
               : "memory");
}

__device__ __forceinline__ void wg_fence() { asm volatile("wgmma.fence.sync.aligned;" ::: "memory"); }
__device__ __forceinline__ void wg_commit() { asm volatile("wgmma.commit_group.sync.aligned;" ::: "memory"); }
template <int N>
__device__ __forceinline__ void wg_wait() { asm volatile("wgmma.wait_group.sync.aligned %0;" ::"n"(N) : "memory"); }

template <int N>
__device__ __forceinline__ void fence_regs(float (&d)[N]) {
#pragma unroll
  for (int i = 0; i < N; i++) asm volatile("" : "+f"(d[i])::"memory");
}
template <int N>
__device__ __forceinline__ void keep_regs(uint32_t (&d)[N]) {
#pragma unroll
  for (int i = 0; i < N; i++) asm volatile("" : "+r"(d[i])::"memory");
}

__device__ __forceinline__ uint32_t pack_bf16(float lo, float hi) {
  uint32_t d;
  asm("cvt.rn.bf16x2.f32 %0, %1, %2;" : "=r"(d) : "f"(hi), "f"(lo));
  return d;
}
__device__ __forceinline__ float ex2(float x) {
  float y;
  asm("ex2.approx.ftz.f32 %0, %1;" : "=f"(y) : "f"(x));
  return y;
}
__device__ __forceinline__ float rcp_approx(float x) {
  float y;
  asm("rcp.approx.ftz.f32 %0, %1;" : "=f"(y) : "f"(x));
  return y;
}
__device__ __forceinline__ uint4 ldg128_nc(const void* p) {
  uint4 v;
  asm volatile("ld.global.nc.v4.u32 {%0,%1,%2,%3}, [%4];" : "=r"(v.x), "=r"(v.y), "=r"(v.z), "=r"(v.w) : "l"(p));
  return v;
}

__device__ __forceinline__ long long clk64() {
  long long c;
  asm volatile("mov.u64 %0, %clock64;" : "=l"(c)::"memory");
  return c;
}
__device__ __forceinline__ void sched_fence() { while (clk64() < 0) { } }

__device__ __forceinline__ uint64_t make_desc(uint32_t addr, uint32_t lbo, uint32_t sbo, uint32_t mode = 1) {
  return (uint64_t)((addr & 0x3FFFF) >> 4) | ((uint64_t)(lbo >> 4) << 16) | ((uint64_t)(sbo >> 4) << 32) |
         ((uint64_t)mode << 62);
}

template <int OFF, int NN>
__device__ __forceinline__ void wg_m192(float (&d)[NN], uint64_t desc_a, uint64_t desc_b, int scale_d) {
  asm volatile(
      "{\n.reg .pred p;\nsetp.ne.b32 p, %98, 0;\n"
      "wgmma.mma_async.sync.aligned.m64n192k16.f32.bf16.bf16 "
      "{%0,%1,%2,%3,%4,%5,%6,%7,%8,%9,%10,%11,%12,%13,%14,%15,"
      "%16,%17,%18,%19,%20,%21,%22,%23,%24,%25,%26,%27,%28,%29,%30,%31,"
      "%32,%33,%34,%35,%36,%37,%38,%39,%40,%41,%42,%43,%44,%45,%46,%47,"
      "%48,%49,%50,%51,%52,%53,%54,%55,%56,%57,%58,%59,%60,%61,%62,%63,"
      "%64,%65,%66,%67,%68,%69,%70,%71,%72,%73,%74,%75,%76,%77,%78,%79,"
      "%80,%81,%82,%83,%84,%85,%86,%87,%88,%89,%90,%91,%92,%93,%94,%95}, "
      "%96, %97, p, 1, 1, 0, 0;\n}\n"
      : "+f"(d[OFF + 0]), "+f"(d[OFF + 1]), "+f"(d[OFF + 2]), "+f"(d[OFF + 3]), "+f"(d[OFF + 4]), "+f"(d[OFF + 5]),
        "+f"(d[OFF + 6]), "+f"(d[OFF + 7]), "+f"(d[OFF + 8]), "+f"(d[OFF + 9]), "+f"(d[OFF + 10]), "+f"(d[OFF + 11]),
        "+f"(d[OFF + 12]), "+f"(d[OFF + 13]), "+f"(d[OFF + 14]), "+f"(d[OFF + 15]), "+f"(d[OFF + 16]), "+f"(d[OFF + 17]),
        "+f"(d[OFF + 18]), "+f"(d[OFF + 19]), "+f"(d[OFF + 20]), "+f"(d[OFF + 21]), "+f"(d[OFF + 22]), "+f"(d[OFF + 23]),
        "+f"(d[OFF + 24]), "+f"(d[OFF + 25]), "+f"(d[OFF + 26]), "+f"(d[OFF + 27]), "+f"(d[OFF + 28]), "+f"(d[OFF + 29]),
        "+f"(d[OFF + 30]), "+f"(d[OFF + 31]), "+f"(d[OFF + 32]), "+f"(d[OFF + 33]), "+f"(d[OFF + 34]), "+f"(d[OFF + 35]),
        "+f"(d[OFF + 36]), "+f"(d[OFF + 37]), "+f"(d[OFF + 38]), "+f"(d[OFF + 39]), "+f"(d[OFF + 40]), "+f"(d[OFF + 41]),
        "+f"(d[OFF + 42]), "+f"(d[OFF + 43]), "+f"(d[OFF + 44]), "+f"(d[OFF + 45]), "+f"(d[OFF + 46]), "+f"(d[OFF + 47]),
        "+f"(d[OFF + 48]), "+f"(d[OFF + 49]), "+f"(d[OFF + 50]), "+f"(d[OFF + 51]), "+f"(d[OFF + 52]), "+f"(d[OFF + 53]),
        "+f"(d[OFF + 54]), "+f"(d[OFF + 55]), "+f"(d[OFF + 56]), "+f"(d[OFF + 57]), "+f"(d[OFF + 58]), "+f"(d[OFF + 59]),
        "+f"(d[OFF + 60]), "+f"(d[OFF + 61]), "+f"(d[OFF + 62]), "+f"(d[OFF + 63]), "+f"(d[OFF + 64]), "+f"(d[OFF + 65]),
        "+f"(d[OFF + 66]), "+f"(d[OFF + 67]), "+f"(d[OFF + 68]), "+f"(d[OFF + 69]), "+f"(d[OFF + 70]), "+f"(d[OFF + 71]),
        "+f"(d[OFF + 72]), "+f"(d[OFF + 73]), "+f"(d[OFF + 74]), "+f"(d[OFF + 75]), "+f"(d[OFF + 76]), "+f"(d[OFF + 77]),
        "+f"(d[OFF + 78]), "+f"(d[OFF + 79]), "+f"(d[OFF + 80]), "+f"(d[OFF + 81]), "+f"(d[OFF + 82]), "+f"(d[OFF + 83]),
        "+f"(d[OFF + 84]), "+f"(d[OFF + 85]), "+f"(d[OFF + 86]), "+f"(d[OFF + 87]), "+f"(d[OFF + 88]), "+f"(d[OFF + 89]),
        "+f"(d[OFF + 90]), "+f"(d[OFF + 91]), "+f"(d[OFF + 92]), "+f"(d[OFF + 93]), "+f"(d[OFF + 94]), "+f"(d[OFF + 95])
      : "l"(desc_a), "l"(desc_b), "r"(scale_d));
}

template <int OFF, int NN>
__device__ __forceinline__ void wg_m192z(float (&d)[NN], uint64_t desc_a, uint64_t desc_b, int scale_d) {
  asm volatile(
      "{\n.reg .pred p;\nsetp.ne.b32 p, %98, 0;\n"
      "wgmma.mma_async.sync.aligned.m64n192k16.f32.bf16.bf16 "
      "{%0,%1,%2,%3,%4,%5,%6,%7,%8,%9,%10,%11,%12,%13,%14,%15,"
      "%16,%17,%18,%19,%20,%21,%22,%23,%24,%25,%26,%27,%28,%29,%30,%31,"
      "%32,%33,%34,%35,%36,%37,%38,%39,%40,%41,%42,%43,%44,%45,%46,%47,"
      "%48,%49,%50,%51,%52,%53,%54,%55,%56,%57,%58,%59,%60,%61,%62,%63,"
      "%64,%65,%66,%67,%68,%69,%70,%71,%72,%73,%74,%75,%76,%77,%78,%79,"
      "%80,%81,%82,%83,%84,%85,%86,%87,%88,%89,%90,%91,%92,%93,%94,%95}, "
      "%96, %97, p, 1, 1, 0, 0;\n}\n"
      : "=f"(d[OFF + 0]), "=f"(d[OFF + 1]), "=f"(d[OFF + 2]), "=f"(d[OFF + 3]), "=f"(d[OFF + 4]), "=f"(d[OFF + 5]),
        "=f"(d[OFF + 6]), "=f"(d[OFF + 7]), "=f"(d[OFF + 8]), "=f"(d[OFF + 9]), "=f"(d[OFF + 10]), "=f"(d[OFF + 11]),
        "=f"(d[OFF + 12]), "=f"(d[OFF + 13]), "=f"(d[OFF + 14]), "=f"(d[OFF + 15]), "=f"(d[OFF + 16]), "=f"(d[OFF + 17]),
        "=f"(d[OFF + 18]), "=f"(d[OFF + 19]), "=f"(d[OFF + 20]), "=f"(d[OFF + 21]), "=f"(d[OFF + 22]), "=f"(d[OFF + 23]),
        "=f"(d[OFF + 24]), "=f"(d[OFF + 25]), "=f"(d[OFF + 26]), "=f"(d[OFF + 27]), "=f"(d[OFF + 28]), "=f"(d[OFF + 29]),
        "=f"(d[OFF + 30]), "=f"(d[OFF + 31]), "=f"(d[OFF + 32]), "=f"(d[OFF + 33]), "=f"(d[OFF + 34]), "=f"(d[OFF + 35]),
        "=f"(d[OFF + 36]), "=f"(d[OFF + 37]), "=f"(d[OFF + 38]), "=f"(d[OFF + 39]), "=f"(d[OFF + 40]), "=f"(d[OFF + 41]),
        "=f"(d[OFF + 42]), "=f"(d[OFF + 43]), "=f"(d[OFF + 44]), "=f"(d[OFF + 45]), "=f"(d[OFF + 46]), "=f"(d[OFF + 47]),
        "=f"(d[OFF + 48]), "=f"(d[OFF + 49]), "=f"(d[OFF + 50]), "=f"(d[OFF + 51]), "=f"(d[OFF + 52]), "=f"(d[OFF + 53]),
        "=f"(d[OFF + 54]), "=f"(d[OFF + 55]), "=f"(d[OFF + 56]), "=f"(d[OFF + 57]), "=f"(d[OFF + 58]), "=f"(d[OFF + 59]),
        "=f"(d[OFF + 60]), "=f"(d[OFF + 61]), "=f"(d[OFF + 62]), "=f"(d[OFF + 63]), "=f"(d[OFF + 64]), "=f"(d[OFF + 65]),
        "=f"(d[OFF + 66]), "=f"(d[OFF + 67]), "=f"(d[OFF + 68]), "=f"(d[OFF + 69]), "=f"(d[OFF + 70]), "=f"(d[OFF + 71]),
        "=f"(d[OFF + 72]), "=f"(d[OFF + 73]), "=f"(d[OFF + 74]), "=f"(d[OFF + 75]), "=f"(d[OFF + 76]), "=f"(d[OFF + 77]),
        "=f"(d[OFF + 78]), "=f"(d[OFF + 79]), "=f"(d[OFF + 80]), "=f"(d[OFF + 81]), "=f"(d[OFF + 82]), "=f"(d[OFF + 83]),
        "=f"(d[OFF + 84]), "=f"(d[OFF + 85]), "=f"(d[OFF + 86]), "=f"(d[OFF + 87]), "=f"(d[OFF + 88]), "=f"(d[OFF + 89]),
        "=f"(d[OFF + 90]), "=f"(d[OFF + 91]), "=f"(d[OFF + 92]), "=f"(d[OFF + 93]), "=f"(d[OFF + 94]), "=f"(d[OFF + 95])
      : "l"(desc_a), "l"(desc_b), "r"(scale_d));
}

template <int OFF, int NN>
__device__ __forceinline__ void wg_m96t(float (&d)[NN], uint64_t desc_a, uint64_t desc_b, int scale_d) {
  asm volatile(
      "{\n.reg .pred p;\nsetp.ne.b32 p, %50, 0;\n"
      "wgmma.mma_async.sync.aligned.m64n96k16.f32.bf16.bf16 "
      "{%0,%1,%2,%3,%4,%5,%6,%7,%8,%9,%10,%11,%12,%13,%14,%15,"
      "%16,%17,%18,%19,%20,%21,%22,%23,%24,%25,%26,%27,%28,%29,%30,%31,"
      "%32,%33,%34,%35,%36,%37,%38,%39,%40,%41,%42,%43,%44,%45,%46,%47}, "
      "%48, %49, p, 1, 1, 0, 1;\n}\n"
      : "+f"(d[OFF + 0]), "+f"(d[OFF + 1]), "+f"(d[OFF + 2]), "+f"(d[OFF + 3]), "+f"(d[OFF + 4]), "+f"(d[OFF + 5]),
        "+f"(d[OFF + 6]), "+f"(d[OFF + 7]), "+f"(d[OFF + 8]), "+f"(d[OFF + 9]), "+f"(d[OFF + 10]), "+f"(d[OFF + 11]),
        "+f"(d[OFF + 12]), "+f"(d[OFF + 13]), "+f"(d[OFF + 14]), "+f"(d[OFF + 15]), "+f"(d[OFF + 16]), "+f"(d[OFF + 17]),
        "+f"(d[OFF + 18]), "+f"(d[OFF + 19]), "+f"(d[OFF + 20]), "+f"(d[OFF + 21]), "+f"(d[OFF + 22]), "+f"(d[OFF + 23]),
        "+f"(d[OFF + 24]), "+f"(d[OFF + 25]), "+f"(d[OFF + 26]), "+f"(d[OFF + 27]), "+f"(d[OFF + 28]), "+f"(d[OFF + 29]),
        "+f"(d[OFF + 30]), "+f"(d[OFF + 31]), "+f"(d[OFF + 32]), "+f"(d[OFF + 33]), "+f"(d[OFF + 34]), "+f"(d[OFF + 35]),
        "+f"(d[OFF + 36]), "+f"(d[OFF + 37]), "+f"(d[OFF + 38]), "+f"(d[OFF + 39]), "+f"(d[OFF + 40]), "+f"(d[OFF + 41]),
        "+f"(d[OFF + 42]), "+f"(d[OFF + 43]), "+f"(d[OFF + 44]), "+f"(d[OFF + 45]), "+f"(d[OFF + 46]), "+f"(d[OFF + 47])
      : "l"(desc_a), "l"(desc_b), "r"(scale_d));
}

template <int OFF, int NN>
__device__ __forceinline__ void wg_m96tz(float (&d)[NN], uint64_t desc_a, uint64_t desc_b, int scale_d) {
  asm volatile(
      "{\n.reg .pred p;\nsetp.ne.b32 p, %50, 0;\n"
      "wgmma.mma_async.sync.aligned.m64n96k16.f32.bf16.bf16 "
      "{%0,%1,%2,%3,%4,%5,%6,%7,%8,%9,%10,%11,%12,%13,%14,%15,"
      "%16,%17,%18,%19,%20,%21,%22,%23,%24,%25,%26,%27,%28,%29,%30,%31,"
      "%32,%33,%34,%35,%36,%37,%38,%39,%40,%41,%42,%43,%44,%45,%46,%47}, "
      "%48, %49, p, 1, 1, 0, 1;\n}\n"
      : "=f"(d[OFF + 0]), "=f"(d[OFF + 1]), "=f"(d[OFF + 2]), "=f"(d[OFF + 3]), "=f"(d[OFF + 4]), "=f"(d[OFF + 5]),
        "=f"(d[OFF + 6]), "=f"(d[OFF + 7]), "=f"(d[OFF + 8]), "=f"(d[OFF + 9]), "=f"(d[OFF + 10]), "=f"(d[OFF + 11]),
        "=f"(d[OFF + 12]), "=f"(d[OFF + 13]), "=f"(d[OFF + 14]), "=f"(d[OFF + 15]), "=f"(d[OFF + 16]), "=f"(d[OFF + 17]),
        "=f"(d[OFF + 18]), "=f"(d[OFF + 19]), "=f"(d[OFF + 20]), "=f"(d[OFF + 21]), "=f"(d[OFF + 22]), "=f"(d[OFF + 23]),
        "=f"(d[OFF + 24]), "=f"(d[OFF + 25]), "=f"(d[OFF + 26]), "=f"(d[OFF + 27]), "=f"(d[OFF + 28]), "=f"(d[OFF + 29]),
        "=f"(d[OFF + 30]), "=f"(d[OFF + 31]), "=f"(d[OFF + 32]), "=f"(d[OFF + 33]), "=f"(d[OFF + 34]), "=f"(d[OFF + 35]),
        "=f"(d[OFF + 36]), "=f"(d[OFF + 37]), "=f"(d[OFF + 38]), "=f"(d[OFF + 39]), "=f"(d[OFF + 40]), "=f"(d[OFF + 41]),
        "=f"(d[OFF + 42]), "=f"(d[OFF + 43]), "=f"(d[OFF + 44]), "=f"(d[OFF + 45]), "=f"(d[OFF + 46]), "=f"(d[OFF + 47])
      : "l"(desc_a), "l"(desc_b), "r"(scale_d));
}

template <int OFF, int NN>
__device__ __forceinline__ void wg_d96(float (&d)[NN], uint32_t a0, uint32_t a1, uint32_t a2, uint32_t a3,
                                       uint64_t desc_b, int scale_d) {
  asm volatile(
      "{\n.reg .pred p;\nsetp.ne.b32 p, %53, 0;\n"
      "wgmma.mma_async.sync.aligned.m64n96k16.f32.bf16.bf16 "
      "{%0,%1,%2,%3,%4,%5,%6,%7,%8,%9,%10,%11,%12,%13,%14,%15,"
      "%16,%17,%18,%19,%20,%21,%22,%23,%24,%25,%26,%27,%28,%29,%30,%31,"
      "%32,%33,%34,%35,%36,%37,%38,%39,%40,%41,%42,%43,%44,%45,%46,%47}, "
      "{%48,%49,%50,%51}, %52, p, 1, 1, 0;\n}\n"
      : "+f"(d[OFF + 0]), "+f"(d[OFF + 1]), "+f"(d[OFF + 2]), "+f"(d[OFF + 3]), "+f"(d[OFF + 4]), "+f"(d[OFF + 5]),
        "+f"(d[OFF + 6]), "+f"(d[OFF + 7]), "+f"(d[OFF + 8]), "+f"(d[OFF + 9]), "+f"(d[OFF + 10]), "+f"(d[OFF + 11]),
        "+f"(d[OFF + 12]), "+f"(d[OFF + 13]), "+f"(d[OFF + 14]), "+f"(d[OFF + 15]), "+f"(d[OFF + 16]), "+f"(d[OFF + 17]),
        "+f"(d[OFF + 18]), "+f"(d[OFF + 19]), "+f"(d[OFF + 20]), "+f"(d[OFF + 21]), "+f"(d[OFF + 22]), "+f"(d[OFF + 23]),
        "+f"(d[OFF + 24]), "+f"(d[OFF + 25]), "+f"(d[OFF + 26]), "+f"(d[OFF + 27]), "+f"(d[OFF + 28]), "+f"(d[OFF + 29]),
        "+f"(d[OFF + 30]), "+f"(d[OFF + 31]), "+f"(d[OFF + 32]), "+f"(d[OFF + 33]), "+f"(d[OFF + 34]), "+f"(d[OFF + 35]),
        "+f"(d[OFF + 36]), "+f"(d[OFF + 37]), "+f"(d[OFF + 38]), "+f"(d[OFF + 39]), "+f"(d[OFF + 40]), "+f"(d[OFF + 41]),
        "+f"(d[OFF + 42]), "+f"(d[OFF + 43]), "+f"(d[OFF + 44]), "+f"(d[OFF + 45]), "+f"(d[OFF + 46]), "+f"(d[OFF + 47])
      : "r"(a0), "r"(a1), "r"(a2), "r"(a3), "l"(desc_b), "r"(scale_d));
}

template <int OFF, int NN>
__device__ __forceinline__ void wg_d96z(float (&d)[NN], uint32_t a0, uint32_t a1, uint32_t a2, uint32_t a3,
                                       uint64_t desc_b, int scale_d) {
  asm volatile(
      "{\n.reg .pred p;\nsetp.ne.b32 p, %53, 0;\n"
      "wgmma.mma_async.sync.aligned.m64n96k16.f32.bf16.bf16 "
      "{%0,%1,%2,%3,%4,%5,%6,%7,%8,%9,%10,%11,%12,%13,%14,%15,"
      "%16,%17,%18,%19,%20,%21,%22,%23,%24,%25,%26,%27,%28,%29,%30,%31,"
      "%32,%33,%34,%35,%36,%37,%38,%39,%40,%41,%42,%43,%44,%45,%46,%47}, "
      "{%48,%49,%50,%51}, %52, p, 1, 1, 0;\n}\n"
      : "=f"(d[OFF + 0]), "=f"(d[OFF + 1]), "=f"(d[OFF + 2]), "=f"(d[OFF + 3]), "=f"(d[OFF + 4]), "=f"(d[OFF + 5]),
        "=f"(d[OFF + 6]), "=f"(d[OFF + 7]), "=f"(d[OFF + 8]), "=f"(d[OFF + 9]), "=f"(d[OFF + 10]), "=f"(d[OFF + 11]),
        "=f"(d[OFF + 12]), "=f"(d[OFF + 13]), "=f"(d[OFF + 14]), "=f"(d[OFF + 15]), "=f"(d[OFF + 16]), "=f"(d[OFF + 17]),
        "=f"(d[OFF + 18]), "=f"(d[OFF + 19]), "=f"(d[OFF + 20]), "=f"(d[OFF + 21]), "=f"(d[OFF + 22]), "=f"(d[OFF + 23]),
        "=f"(d[OFF + 24]), "=f"(d[OFF + 25]), "=f"(d[OFF + 26]), "=f"(d[OFF + 27]), "=f"(d[OFF + 28]), "=f"(d[OFF + 29]),
        "=f"(d[OFF + 30]), "=f"(d[OFF + 31]), "=f"(d[OFF + 32]), "=f"(d[OFF + 33]), "=f"(d[OFF + 34]), "=f"(d[OFF + 35]),
        "=f"(d[OFF + 36]), "=f"(d[OFF + 37]), "=f"(d[OFF + 38]), "=f"(d[OFF + 39]), "=f"(d[OFF + 40]), "=f"(d[OFF + 41]),
        "=f"(d[OFF + 42]), "=f"(d[OFF + 43]), "=f"(d[OFF + 44]), "=f"(d[OFF + 45]), "=f"(d[OFF + 46]), "=f"(d[OFF + 47])
      : "r"(a0), "r"(a1), "r"(a2), "r"(a3), "l"(desc_b), "r"(scale_d));
}

template <int OFF, int NN>
__device__ __forceinline__ void wg_s104(float (&d)[NN], uint32_t a0, uint32_t a1, uint32_t a2, uint32_t a3,
                                       uint64_t desc_b, int scale_d, uint32_t meta) {
  asm volatile(
      "{\n.reg .pred p;\nsetp.ne.b32 p, %57, 0;\n"
      "wgmma.mma_async.sp.sync.aligned.m64n104k32.f32.bf16.bf16 "
      "{%0,%1,%2,%3,%4,%5,%6,%7,%8,%9,%10,%11,%12,%13,%14,%15,"
      "%16,%17,%18,%19,%20,%21,%22,%23,%24,%25,%26,%27,%28,%29,%30,%31,"
      "%32,%33,%34,%35,%36,%37,%38,%39,%40,%41,%42,%43,%44,%45,%46,%47,"
      "%48,%49,%50,%51}, "
      "{%52,%53,%54,%55}, %56, %58, 0, p, 1, 1, 0;\n}\n"
      : "+f"(d[OFF + 0]), "+f"(d[OFF + 1]), "+f"(d[OFF + 2]), "+f"(d[OFF + 3]), "+f"(d[OFF + 4]), "+f"(d[OFF + 5]),
        "+f"(d[OFF + 6]), "+f"(d[OFF + 7]), "+f"(d[OFF + 8]), "+f"(d[OFF + 9]), "+f"(d[OFF + 10]), "+f"(d[OFF + 11]),
        "+f"(d[OFF + 12]), "+f"(d[OFF + 13]), "+f"(d[OFF + 14]), "+f"(d[OFF + 15]), "+f"(d[OFF + 16]), "+f"(d[OFF + 17]),
        "+f"(d[OFF + 18]), "+f"(d[OFF + 19]), "+f"(d[OFF + 20]), "+f"(d[OFF + 21]), "+f"(d[OFF + 22]), "+f"(d[OFF + 23]),
        "+f"(d[OFF + 24]), "+f"(d[OFF + 25]), "+f"(d[OFF + 26]), "+f"(d[OFF + 27]), "+f"(d[OFF + 28]), "+f"(d[OFF + 29]),
        "+f"(d[OFF + 30]), "+f"(d[OFF + 31]), "+f"(d[OFF + 32]), "+f"(d[OFF + 33]), "+f"(d[OFF + 34]), "+f"(d[OFF + 35]),
        "+f"(d[OFF + 36]), "+f"(d[OFF + 37]), "+f"(d[OFF + 38]), "+f"(d[OFF + 39]), "+f"(d[OFF + 40]), "+f"(d[OFF + 41]),
        "+f"(d[OFF + 42]), "+f"(d[OFF + 43]), "+f"(d[OFF + 44]), "+f"(d[OFF + 45]), "+f"(d[OFF + 46]), "+f"(d[OFF + 47]),
        "+f"(d[OFF + 48]), "+f"(d[OFF + 49]), "+f"(d[OFF + 50]), "+f"(d[OFF + 51])
      : "r"(a0), "r"(a1), "r"(a2), "r"(a3), "l"(desc_b), "r"(scale_d), "r"(meta));
}

template <int OFF, int NN>
__device__ __forceinline__ void wg_s104z(float (&d)[NN], uint32_t a0, uint32_t a1, uint32_t a2, uint32_t a3,
                                       uint64_t desc_b, int scale_d, uint32_t meta) {
  asm volatile(
      "{\n.reg .pred p;\nsetp.ne.b32 p, %57, 0;\n"
      "wgmma.mma_async.sp.sync.aligned.m64n104k32.f32.bf16.bf16 "
      "{%0,%1,%2,%3,%4,%5,%6,%7,%8,%9,%10,%11,%12,%13,%14,%15,"
      "%16,%17,%18,%19,%20,%21,%22,%23,%24,%25,%26,%27,%28,%29,%30,%31,"
      "%32,%33,%34,%35,%36,%37,%38,%39,%40,%41,%42,%43,%44,%45,%46,%47,"
      "%48,%49,%50,%51}, "
      "{%52,%53,%54,%55}, %56, %58, 0, p, 1, 1, 0;\n}\n"
      : "=f"(d[OFF + 0]), "=f"(d[OFF + 1]), "=f"(d[OFF + 2]), "=f"(d[OFF + 3]), "=f"(d[OFF + 4]), "=f"(d[OFF + 5]),
        "=f"(d[OFF + 6]), "=f"(d[OFF + 7]), "=f"(d[OFF + 8]), "=f"(d[OFF + 9]), "=f"(d[OFF + 10]), "=f"(d[OFF + 11]),
        "=f"(d[OFF + 12]), "=f"(d[OFF + 13]), "=f"(d[OFF + 14]), "=f"(d[OFF + 15]), "=f"(d[OFF + 16]), "=f"(d[OFF + 17]),
        "=f"(d[OFF + 18]), "=f"(d[OFF + 19]), "=f"(d[OFF + 20]), "=f"(d[OFF + 21]), "=f"(d[OFF + 22]), "=f"(d[OFF + 23]),
        "=f"(d[OFF + 24]), "=f"(d[OFF + 25]), "=f"(d[OFF + 26]), "=f"(d[OFF + 27]), "=f"(d[OFF + 28]), "=f"(d[OFF + 29]),
        "=f"(d[OFF + 30]), "=f"(d[OFF + 31]), "=f"(d[OFF + 32]), "=f"(d[OFF + 33]), "=f"(d[OFF + 34]), "=f"(d[OFF + 35]),
        "=f"(d[OFF + 36]), "=f"(d[OFF + 37]), "=f"(d[OFF + 38]), "=f"(d[OFF + 39]), "=f"(d[OFF + 40]), "=f"(d[OFF + 41]),
        "=f"(d[OFF + 42]), "=f"(d[OFF + 43]), "=f"(d[OFF + 44]), "=f"(d[OFF + 45]), "=f"(d[OFF + 46]), "=f"(d[OFF + 47]),
        "=f"(d[OFF + 48]), "=f"(d[OFF + 49]), "=f"(d[OFF + 50]), "=f"(d[OFF + 51])
      : "r"(a0), "r"(a1), "r"(a2), "r"(a3), "l"(desc_b), "r"(scale_d), "r"(meta));
}

template <int OFF, int NN>
__device__ __forceinline__ void wg_s48(float (&d)[NN], uint32_t a0, uint32_t a1, uint32_t a2, uint32_t a3,
                                       uint64_t desc_b, int scale_d, uint32_t meta) {
  asm volatile(
      "{\n.reg .pred p;\nsetp.ne.b32 p, %29, 0;\n"
      "wgmma.mma_async.sp.sync.aligned.m64n48k32.f32.bf16.bf16 "
      "{%0,%1,%2,%3,%4,%5,%6,%7,%8,%9,%10,%11,%12,%13,%14,%15,"
      "%16,%17,%18,%19,%20,%21,%22,%23}, "
      "{%24,%25,%26,%27}, %28, %30, 0, p, 1, 1, 0;\n}\n"
      : "+f"(d[OFF + 0]), "+f"(d[OFF + 1]), "+f"(d[OFF + 2]), "+f"(d[OFF + 3]), "+f"(d[OFF + 4]), "+f"(d[OFF + 5]),
        "+f"(d[OFF + 6]), "+f"(d[OFF + 7]), "+f"(d[OFF + 8]), "+f"(d[OFF + 9]), "+f"(d[OFF + 10]), "+f"(d[OFF + 11]),
        "+f"(d[OFF + 12]), "+f"(d[OFF + 13]), "+f"(d[OFF + 14]), "+f"(d[OFF + 15]), "+f"(d[OFF + 16]), "+f"(d[OFF + 17]),
        "+f"(d[OFF + 18]), "+f"(d[OFF + 19]), "+f"(d[OFF + 20]), "+f"(d[OFF + 21]), "+f"(d[OFF + 22]), "+f"(d[OFF + 23])
      : "r"(a0), "r"(a1), "r"(a2), "r"(a3), "l"(desc_b), "r"(scale_d), "r"(meta));
}

template <int OFF, int NN>
__device__ __forceinline__ void wg_s48z(float (&d)[NN], uint32_t a0, uint32_t a1, uint32_t a2, uint32_t a3,
                                       uint64_t desc_b, int scale_d, uint32_t meta) {
  asm volatile(
      "{\n.reg .pred p;\nsetp.ne.b32 p, %29, 0;\n"
      "wgmma.mma_async.sp.sync.aligned.m64n48k32.f32.bf16.bf16 "
      "{%0,%1,%2,%3,%4,%5,%6,%7,%8,%9,%10,%11,%12,%13,%14,%15,"
      "%16,%17,%18,%19,%20,%21,%22,%23}, "
      "{%24,%25,%26,%27}, %28, %30, 0, p, 1, 1, 0;\n}\n"
      : "=f"(d[OFF + 0]), "=f"(d[OFF + 1]), "=f"(d[OFF + 2]), "=f"(d[OFF + 3]), "=f"(d[OFF + 4]), "=f"(d[OFF + 5]),
        "=f"(d[OFF + 6]), "=f"(d[OFF + 7]), "=f"(d[OFF + 8]), "=f"(d[OFF + 9]), "=f"(d[OFF + 10]), "=f"(d[OFF + 11]),
        "=f"(d[OFF + 12]), "=f"(d[OFF + 13]), "=f"(d[OFF + 14]), "=f"(d[OFF + 15]), "=f"(d[OFF + 16]), "=f"(d[OFF + 17]),
        "=f"(d[OFF + 18]), "=f"(d[OFF + 19]), "=f"(d[OFF + 20]), "=f"(d[OFF + 21]), "=f"(d[OFF + 22]), "=f"(d[OFF + 23])
      : "r"(a0), "r"(a1), "r"(a2), "r"(a3), "l"(desc_b), "r"(scale_d), "r"(meta));
}

template <int OFF, int NN>
__device__ __forceinline__ void wg_s56(float (&d)[NN], uint32_t a0, uint32_t a1, uint32_t a2, uint32_t a3,
                                       uint64_t desc_b, int scale_d, uint32_t meta) {
  asm volatile(
      "{\n.reg .pred p;\nsetp.ne.b32 p, %33, 0;\n"
      "wgmma.mma_async.sp.sync.aligned.m64n56k32.f32.bf16.bf16 "
      "{%0,%1,%2,%3,%4,%5,%6,%7,%8,%9,%10,%11,%12,%13,%14,%15,"
      "%16,%17,%18,%19,%20,%21,%22,%23,%24,%25,%26,%27}, "
      "{%28,%29,%30,%31}, %32, %34, 0, p, 1, 1, 0;\n}\n"
      : "+f"(d[OFF + 0]), "+f"(d[OFF + 1]), "+f"(d[OFF + 2]), "+f"(d[OFF + 3]), "+f"(d[OFF + 4]), "+f"(d[OFF + 5]),
        "+f"(d[OFF + 6]), "+f"(d[OFF + 7]), "+f"(d[OFF + 8]), "+f"(d[OFF + 9]), "+f"(d[OFF + 10]), "+f"(d[OFF + 11]),
        "+f"(d[OFF + 12]), "+f"(d[OFF + 13]), "+f"(d[OFF + 14]), "+f"(d[OFF + 15]), "+f"(d[OFF + 16]), "+f"(d[OFF + 17]),
        "+f"(d[OFF + 18]), "+f"(d[OFF + 19]), "+f"(d[OFF + 20]), "+f"(d[OFF + 21]), "+f"(d[OFF + 22]), "+f"(d[OFF + 23]),
        "+f"(d[OFF + 24]), "+f"(d[OFF + 25]), "+f"(d[OFF + 26]), "+f"(d[OFF + 27])
      : "r"(a0), "r"(a1), "r"(a2), "r"(a3), "l"(desc_b), "r"(scale_d), "r"(meta));
}

template <int OFF, int NN>
__device__ __forceinline__ void wg_s56z(float (&d)[NN], uint32_t a0, uint32_t a1, uint32_t a2, uint32_t a3,
                                       uint64_t desc_b, int scale_d, uint32_t meta) {
  asm volatile(
      "{\n.reg .pred p;\nsetp.ne.b32 p, %33, 0;\n"
      "wgmma.mma_async.sp.sync.aligned.m64n56k32.f32.bf16.bf16 "
      "{%0,%1,%2,%3,%4,%5,%6,%7,%8,%9,%10,%11,%12,%13,%14,%15,"
      "%16,%17,%18,%19,%20,%21,%22,%23,%24,%25,%26,%27}, "
      "{%28,%29,%30,%31}, %32, %34, 0, p, 1, 1, 0;\n}\n"
      : "=f"(d[OFF + 0]), "=f"(d[OFF + 1]), "=f"(d[OFF + 2]), "=f"(d[OFF + 3]), "=f"(d[OFF + 4]), "=f"(d[OFF + 5]),
        "=f"(d[OFF + 6]), "=f"(d[OFF + 7]), "=f"(d[OFF + 8]), "=f"(d[OFF + 9]), "=f"(d[OFF + 10]), "=f"(d[OFF + 11]),
        "=f"(d[OFF + 12]), "=f"(d[OFF + 13]), "=f"(d[OFF + 14]), "=f"(d[OFF + 15]), "=f"(d[OFF + 16]), "=f"(d[OFF + 17]),
        "=f"(d[OFF + 18]), "=f"(d[OFF + 19]), "=f"(d[OFF + 20]), "=f"(d[OFF + 21]), "=f"(d[OFF + 22]), "=f"(d[OFF + 23]),
        "=f"(d[OFF + 24]), "=f"(d[OFF + 25]), "=f"(d[OFF + 26]), "=f"(d[OFF + 27])
      : "r"(a0), "r"(a1), "r"(a2), "r"(a3), "l"(desc_b), "r"(scale_d), "r"(meta));
}

template <int OFF, int NN>
__device__ __forceinline__ void wg_s64t(float (&d)[NN], uint32_t a0, uint32_t a1, uint32_t a2, uint32_t a3,
                                       uint64_t desc_b, int scale_d, uint32_t meta) {
  asm volatile(
      "{\n.reg .pred p;\nsetp.ne.b32 p, %37, 0;\n"
      "wgmma.mma_async.sp.sync.aligned.m64n64k32.f32.bf16.bf16 "
      "{%0,%1,%2,%3,%4,%5,%6,%7,%8,%9,%10,%11,%12,%13,%14,%15,"
      "%16,%17,%18,%19,%20,%21,%22,%23,%24,%25,%26,%27,%28,%29,%30,%31}, "
      "{%32,%33,%34,%35}, %36, %38, 0, p, 1, 1, 1;\n}\n"
      : "+f"(d[OFF + 0]), "+f"(d[OFF + 1]), "+f"(d[OFF + 2]), "+f"(d[OFF + 3]), "+f"(d[OFF + 4]), "+f"(d[OFF + 5]),
        "+f"(d[OFF + 6]), "+f"(d[OFF + 7]), "+f"(d[OFF + 8]), "+f"(d[OFF + 9]), "+f"(d[OFF + 10]), "+f"(d[OFF + 11]),
        "+f"(d[OFF + 12]), "+f"(d[OFF + 13]), "+f"(d[OFF + 14]), "+f"(d[OFF + 15]), "+f"(d[OFF + 16]), "+f"(d[OFF + 17]),
        "+f"(d[OFF + 18]), "+f"(d[OFF + 19]), "+f"(d[OFF + 20]), "+f"(d[OFF + 21]), "+f"(d[OFF + 22]), "+f"(d[OFF + 23]),
        "+f"(d[OFF + 24]), "+f"(d[OFF + 25]), "+f"(d[OFF + 26]), "+f"(d[OFF + 27]), "+f"(d[OFF + 28]), "+f"(d[OFF + 29]),
        "+f"(d[OFF + 30]), "+f"(d[OFF + 31])
      : "r"(a0), "r"(a1), "r"(a2), "r"(a3), "l"(desc_b), "r"(scale_d), "r"(meta));
}

template <int OFF, int NN>
__device__ __forceinline__ void wg_s64t1(float (&d)[NN], uint32_t a0, uint32_t a1, uint32_t a2, uint32_t a3,
                                       uint64_t desc_b, int scale_d, uint32_t meta) {
  asm volatile(
      "{\n.reg .pred p;\nsetp.ne.b32 p, %37, 0;\n"
      "wgmma.mma_async.sp.sync.aligned.m64n64k32.f32.bf16.bf16 "
      "{%0,%1,%2,%3,%4,%5,%6,%7,%8,%9,%10,%11,%12,%13,%14,%15,"
      "%16,%17,%18,%19,%20,%21,%22,%23,%24,%25,%26,%27,%28,%29,%30,%31}, "
      "{%32,%33,%34,%35}, %36, %38, 1, p, 1, 1, 1;\n}\n"
      : "+f"(d[OFF + 0]), "+f"(d[OFF + 1]), "+f"(d[OFF + 2]), "+f"(d[OFF + 3]), "+f"(d[OFF + 4]), "+f"(d[OFF + 5]),
        "+f"(d[OFF + 6]), "+f"(d[OFF + 7]), "+f"(d[OFF + 8]), "+f"(d[OFF + 9]), "+f"(d[OFF + 10]), "+f"(d[OFF + 11]),
        "+f"(d[OFF + 12]), "+f"(d[OFF + 13]), "+f"(d[OFF + 14]), "+f"(d[OFF + 15]), "+f"(d[OFF + 16]), "+f"(d[OFF + 17]),
        "+f"(d[OFF + 18]), "+f"(d[OFF + 19]), "+f"(d[OFF + 20]), "+f"(d[OFF + 21]), "+f"(d[OFF + 22]), "+f"(d[OFF + 23]),
        "+f"(d[OFF + 24]), "+f"(d[OFF + 25]), "+f"(d[OFF + 26]), "+f"(d[OFF + 27]), "+f"(d[OFF + 28]), "+f"(d[OFF + 29]),
        "+f"(d[OFF + 30]), "+f"(d[OFF + 31])
      : "r"(a0), "r"(a1), "r"(a2), "r"(a3), "l"(desc_b), "r"(scale_d), "r"(meta));
}

template <int OFF, int NN>
__device__ __forceinline__ void wg_s64tz(float (&d)[NN], uint32_t a0, uint32_t a1, uint32_t a2, uint32_t a3,
                                       uint64_t desc_b, int scale_d, uint32_t meta) {
  asm volatile(
      "{\n.reg .pred p;\nsetp.ne.b32 p, %37, 0;\n"
      "wgmma.mma_async.sp.sync.aligned.m64n64k32.f32.bf16.bf16 "
      "{%0,%1,%2,%3,%4,%5,%6,%7,%8,%9,%10,%11,%12,%13,%14,%15,"
      "%16,%17,%18,%19,%20,%21,%22,%23,%24,%25,%26,%27,%28,%29,%30,%31}, "
      "{%32,%33,%34,%35}, %36, %38, 0, p, 1, 1, 1;\n}\n"
      : "=f"(d[OFF + 0]), "=f"(d[OFF + 1]), "=f"(d[OFF + 2]), "=f"(d[OFF + 3]), "=f"(d[OFF + 4]), "=f"(d[OFF + 5]),
        "=f"(d[OFF + 6]), "=f"(d[OFF + 7]), "=f"(d[OFF + 8]), "=f"(d[OFF + 9]), "=f"(d[OFF + 10]), "=f"(d[OFF + 11]),
        "=f"(d[OFF + 12]), "=f"(d[OFF + 13]), "=f"(d[OFF + 14]), "=f"(d[OFF + 15]), "=f"(d[OFF + 16]), "=f"(d[OFF + 17]),
        "=f"(d[OFF + 18]), "=f"(d[OFF + 19]), "=f"(d[OFF + 20]), "=f"(d[OFF + 21]), "=f"(d[OFF + 22]), "=f"(d[OFF + 23]),
        "=f"(d[OFF + 24]), "=f"(d[OFF + 25]), "=f"(d[OFF + 26]), "=f"(d[OFF + 27]), "=f"(d[OFF + 28]), "=f"(d[OFF + 29]),
        "=f"(d[OFF + 30]), "=f"(d[OFF + 31])
      : "r"(a0), "r"(a1), "r"(a2), "r"(a3), "l"(desc_b), "r"(scale_d), "r"(meta));
}

__device__ __forceinline__ int g2_inv(int ch) { return 32 * (ch >> 5) + 8 * ((ch >> 1) & 3) + 2 * ((ch >> 3) & 3) + (ch & 1); }
__host__ __device__ __forceinline__ uint32_t wimg_off(int n, int k) {
  return (uint32_t)(k >> 6) * kWChunk + (uint32_t)n * 128 + (uint32_t)((((k & 63) >> 3) ^ (n & 7)) << 4) + (k & 7) * 2;
}
__host__ __device__ constexpr int w2piece(int h, int c) { return c == 2 ? 2 + h : 4 * h + c; }
__device__ __forceinline__ uint32_t w2img_off(int n, int k) { return wimg_off(n % 96, k & 63) + w2piece(n >= 96, k >> 6) * (kWChunk / 2); }
__device__ __forceinline__ int qpix(int par, int t) {
  const int a = 2 * t + 13 * par - 6, b = t + 112 * par;
  return par ? min(a, b) : max(a, b);
}
__device__ __forceinline__ int woff(int par, int i, int r) {
  const int a = 99 * par + 6 - 8 * i;
  return par ? min(r, a) : max(r, a);
}

__device__ __forceinline__ void mma16816(float (&c)[4], uint32_t a0, uint32_t a1, uint32_t a2, uint32_t a3, uint32_t b0,
                                         uint32_t b1) {
  asm volatile(
      "mma.sync.aligned.m16n8k16.row.col.f32.bf16.bf16.f32 {%0,%1,%2,%3}, {%4,%5,%6,%7}, {%8,%9}, {%0,%1,%2,%3};"
      : "+f"(c[0]), "+f"(c[1]), "+f"(c[2]), "+f"(c[3])
      : "r"(a0), "r"(a1), "r"(a2), "r"(a3), "r"(b0), "r"(b1));
}

__device__ __forceinline__ void fold_w1(const uint32_t u, const __nv_bfloat16* __restrict__ wqkv, uint8_t* wimg) {
  const uint32_t g = (threadIdx.x >> 2) & 7, l = threadIdx.x & 3;
  const uint32_t m0 = (u * 171 >> 11) * 16, s = u - (u * 171 >> 11) * 12;
  uint4 A[12], B[12];
  const __nv_bfloat16* arow = wqkv + (m0 + 4 * (g >> 1) + (g & 1)) * 576 + 192 + 8 * l;
  const __nv_bfloat16* brow = wqkv + (16 * s + 4 * (g >> 1) + (g & 1)) * 576 + 8 * l;
#pragma unroll
  for (int i = 0; i < 12; i++) {
    A[i] = ldg128_nc(arow + (i & 1) * 2 * 576 + 32 * (i >> 1));
    B[i] = ldg128_nc(brow + (i & 1) * 2 * 576 + 32 * (i >> 1));
  }
  uint8_t* dst = wimg + wimg_off(m0 + g, 16 * s + 4 * l);
  uint32_t zero = (uint32_t)(uint64_t)wimg & 15u, one = zero + 1;
  asm volatile("" : "+l"(dst), "+r"(zero), "+r"(one));
  sched_fence();
  float acc[4][4];
#pragma unroll
  for (int j = 0; j < 16; j++) acc[j >> 2][j & 3] = 0.f;
#pragma unroll
  for (int i = 0; i < 6; i++) {
    const uint4 &a0 = A[2 * i], &a1 = A[2 * i + 1];
    const uint32_t f[8] = {a0.x | zero, a1.x * one, a0.y | zero, a1.y * one, a0.z | zero, a1.z * one, a0.w | zero, a1.w * one};
#pragma unroll
    for (int nb = 0; nb < 2; nb++) {
      mma16816(acc[2 * nb], f[0], f[1], f[2], f[3], B[2 * i + nb].x, B[2 * i + nb].y);
      mma16816(acc[2 * nb + 1], f[4], f[5], f[6], f[7], B[2 * i + nb].z, B[2 * i + nb].w);
    }
  }
#pragma unroll
  for (int j = 0; j < 2; j++) {
    const uint2 v = make_uint2(pack_bf16((acc[0][2 * j] + acc[1][2 * j]) * kAlpha, (acc[0][2 * j + 1] + acc[1][2 * j + 1]) * kAlpha),
                               pack_bf16((acc[2][2 * j] + acc[3][2 * j]) * kAlpha, (acc[2][2 * j + 1] + acc[3][2 * j + 1]) * kAlpha));
    asm volatile("st.relaxed.gpu.global.v2.u32 [%0], {%1,%2};" ::"l"(dst + j * 1024), "r"(v.x), "r"(v.y) : "memory");
  }
}
__device__ __forceinline__ void fold_w2(const int u, const __nv_bfloat16* __restrict__ wqkv, const __nv_bfloat16* __restrict__ wo,
                                        uint8_t* wimg) {
  const int g = (threadIdx.x >> 2) & 7, l = threadIdx.x & 3;
  const int m0 = (u / 12) * 32, n0 = (u % 12) * 16;
  uint4 S[12];
  uint32_t L[96];
  const __nv_bfloat16* brow = wqkv + (n0 + 4 * (g >> 1) + (g & 1)) * 576 + 384 + 8 * l;
#pragma unroll
  for (int i = 0; i < 12; i++) S[i] = ldg128_nc(brow + (i & 1) * 2 * 576 + 32 * (i >> 1));
  const __nv_bfloat16* acol = wo + (8 * l) * 192 + m0 + 4 * g;
#pragma unroll
  for (int c = 0; c < 48; c++)
    asm volatile("ld.global.nc.v2.u32 {%0,%1}, [%2];" : "=r"(L[2 * c]), "=r"(L[2 * c + 1]) : "l"(acol + (32 * (c >> 3) + (c & 7)) * 192));
  const uint32_t off = w2_offset();
  sched_fence();
  uint8_t* img = wimg + off;
  float acc[4][4];
#pragma unroll
  for (int j = 0; j < 16; j++) acc[j >> 2][j & 3] = 0.f;
#pragma unroll
  for (int i = 0; i < 6; i++) {
#pragma unroll
    for (int h = 0; h < 2; h++) {
      const uint4 &s0 = S[2 * i], &s1 = S[2 * i + 1];
#pragma unroll
      for (int mt = 0; mt < 2; mt++) {
        const uint32_t* a = L + 16 * i + 8 * h + mt;
        const uint32_t a0 = __byte_perm(a[0], a[2], 0x5410), a1 = __byte_perm(a[0], a[2], 0x7632);
        const uint32_t a2 = __byte_perm(a[4], a[6], 0x5410), a3 = __byte_perm(a[4], a[6], 0x7632);
        mma16816(acc[2 * mt], a0, a1, a2, a3, h ? s0.z : s0.x, h ? s0.w : s0.y);
        mma16816(acc[2 * mt + 1], a0, a1, a2, a3, h ? s1.z : s1.x, h ? s1.w : s1.y);
      }
    }
  }
#pragma unroll
  for (int j = 0; j < 4; j++) {
    const float(&c0)[4] = acc[j & 2];
    const float(&c1)[4] = acc[(j & 2) + 1];
    asm volatile("st.relaxed.gpu.global.v2.u32 [%0], {%1,%2};" ::"l"(img + w2img_off(g2_inv(m0 + 4 * g + j), n0 + 4 * l)),
                 "r"(pack_bf16(c0[2 * (j & 1)], c0[2 * (j & 1) + 1])), "r"(pack_bf16(c1[2 * (j & 1)], c1[2 * (j & 1) + 1])) : "memory");
  }
}

__global__ void __launch_bounds__(256) fold_kernel(const __nv_bfloat16* __restrict__ wqkv,
                                                   const __nv_bfloat16* __restrict__ wo, uint8_t* wimg) {
  const int u = blockIdx.x * 8 + (threadIdx.x >> 5);
  if (u < 144) fold_w1(u, wqkv, wimg);
  else fold_w2(u - 144, wqkv, wo, wimg);
}

struct TileCoord { int pr, pc, I, J, up, kind; };
struct TileTable { uint16_t e[kCtas * 6], g[5][8][2], b[5][2][4]; };
inline void make_tiles(TileTable& tt) {
  for (int tile = 0; tile < kCtas * 6; tile++) {
    const int b = tile / 6, k = tile - 6 * b;
    const int p = b < 128 ? (tile - 672) >> 1 : b - 80;
    const int strip = b < 112 ? b >> 1 : b >= 128 && k >= 2 ? (b & 1) * 27 + (b & 2) * 14 : p + (p < 26 ? 1 : 3);
    const int pr = strip >= 28, J = (strip - pr * 28) >> 1, pc = strip & 1, up = b < 112 ? b & 1 : pr;
    const int first = b < 112 ? 8 - 2 * pr - up : 13 * pr, step = b < 112 ? k : k & 1;
    const int I = up ? first - step : first + step;
    const int kind = I == 13 * pr ? 3 + pr : J == 13 * pc ? 1 + pc : 0;
    tt.e[tile] = (uint16_t)(I | J << 4 | pr << 8 | pc << 9 | up << 10 | kind << 11);
  }
  for (int kind = 0; kind < 5; kind++) {
    const bool col = kind == 1 || kind == 2;
    auto off = [kind](int t) { return kind == 0 ? 2 * t : kind & 1 ? t + (t == 7) : t + (t > 0); };
    for (int j = 0; j < 8; j++) {
      const int w = j >> 1, h = j & 1;
      tt.g[kind][j][0] = (uint16_t)(col ? 3 * off(w + 4 * h) : 3 * (kW * off(2 * w) + 8 * h));
      tt.g[kind][j][1] = (uint16_t)(128 * (col ? 5 : 5 + off(2 * w + 1) - off(2 * w)));
    }
    for (int i = 0; i < 2; i++) {
      const int w = kind == 0 ? 0 : kind & 1 ? 3 * i : 1 - i;
      tt.b[kind][i][0] = tt.g[kind][2 * w][0];
      tt.b[kind][i][1] = (uint16_t)(128 * (kind == 0 ? 0 : (col ? 3 : 1) + i));
      tt.b[kind][i][2] = (uint16_t)(2048 * w);
      tt.b[kind][i][3] = 0;
    }
  }
}
__device__ __forceinline__ int num_tiles() { return blockIdx.x < 128 ? 6 : 4; }
__device__ __forceinline__ TileCoord decode_tile(const TileTable& tt, int tile) {
  const uint32_t e = tt.e[tile];
  return TileCoord{(int)(e >> 8) & 1, (int)(e >> 9) & 1, (int)e & 15, (int)(e >> 4) & 15, (int)(e >> 10) & 1, (int)(e >> 11)};
}
__device__ __forceinline__ int halo_r0(const TileCoord& t) { return 8 * t.I + 6 * t.pr - 6; }
__device__ __forceinline__ int halo_c0(const TileCoord& t) { return min(max(8 * t.J + 6 * t.pc - 6, -3), 102); }

__device__ __forceinline__ uint32_t bar_full(uint32_t bars, int wg, int c) { return bars + (wg * 3 + c) * 8; }
__device__ __forceinline__ uint32_t bar_w1c(uint32_t bars, int c) { return bars + (6 + c) * 8; }
__device__ __forceinline__ uint32_t bar_w2(uint32_t bars) { return bars + 9 * 8; }
__device__ __forceinline__ uint32_t bar_x(uint32_t bars, int j, int c) { return bars + (j == 0 ? 10 : c ? 17 + c : 11) * 8; }
__device__ __forceinline__ uint32_t bar_w1q(uint32_t bars) { return bars + 12 * 8; }
__device__ __forceinline__ uint32_t bar_xf(uint32_t bars) { return bars + 13 * 8; }
__device__ __forceinline__ uint32_t bar_w2m(uint32_t bars) { return bars + 14 * 8; }
__device__ __forceinline__ uint32_t bar_redo(uint32_t bars) { return bars + 15 * 8; }
__device__ __forceinline__ uint32_t bar_wok(uint32_t bars) { return bars + 16 * 8; }
__device__ __forceinline__ uint32_t bar_go(uint32_t bars) { return bars + 17 * 8; }
__device__ __forceinline__ uint32_t bar_raw(uint32_t bars, int j = 0) { return bars + (21 + j) * 8; }
__device__ __forceinline__ uint32_t bar_w2a(uint32_t bars) { return bars + 20 * 8; }
constexpr int kNumBars = 22;

__device__ __forceinline__ uint64_t wdesc(uint64_t d0, int s) { return d0 + (((s >> 2) * kWChunk + (s & 3) * 32) >> 4); }

__device__ __forceinline__ uint32_t x_chunk(int k, int c) { return kXOff + (k == 0 ? kWChunk : 0) + (k & 1 ? 2 - c : c) * 8192; }
__device__ __forceinline__ uint32_t out_slot(int k, int nt) { return k + 1 < nt ? kW2Off + (~k & 1) * 2 * kWChunk : kW1Off + kWChunk; }
template <int I0, int I1>
__device__ __forceinline__ void store_rows(bool on, __nv_bfloat16* pA, __nv_bfloat16* pB, const uint32_t (&a)[24], const uint32_t (&b)[24]) {
#pragma unroll
  for (int i = 2 * I0; i < 2 * I1; i++) {
    const uint32_t* v = (i & 1 ? b : a) + 4 * (i >> 1);
    asm volatile("{\n.reg .pred p;\nsetp.ne.u32 p, %5, 0;\n@p st.global.v4.u32 [%0], {%1,%2,%3,%4};\n}\n" ::"l"((i & 1 ? pB : pA) + 32 * (i >> 1)),
                 "r"(v[0]), "r"(v[1]), "r"(v[2]), "r"(v[3]), "r"((uint32_t)on) : "memory");
  }
}
template <int I0, int I1>
__device__ __forceinline__ void stage_out(const uint32_t (&ad)[4], const uint32_t (&a)[24], const uint32_t (&b)[24]) {
#pragma unroll
  for (int i = I0; i < I1; i++) {
    const uint32_t* v = (i < 6 ? a : b) + 4 * (i % 6);
    asm volatile("st.shared.v4.u32 [%0], {%1,%2,%3,%4};" ::"r"(ad[i % 6 / 3 * 2 + (i % 3 == 1)] + (i % 3 == 2) * 1024 + (i / 6) * 12288),
                 "r"(v[0]), "r"(v[1]), "r"(v[2]), "r"(v[3]) : "memory");
  }
}
__device__ __forceinline__ uint32_t now_ns() {
  uint32_t t;
  asm volatile("mov.u32 %0, %globaltimer_lo;" : "=r"(t)::"memory");
  return t;
}
__device__ __forceinline__ void wait_clock(uint32_t t_start, uint32_t t) {
  while (now_ns() - t_start < t) { }
}
__device__ __forceinline__ void sleep_clock(uint32_t t_start, uint32_t t) {
  while (now_ns() - t_start < t) __nanosleep(100);
}
#define NAT_PRED(f, m) ".reg .pred p;\n.reg .b32 t;\nand.b32 t, " f ", " m ";\nsetp.ne.u32 p, t, 0;\n"
constexpr uint32_t kHiV = 1, kHiU = 8, kColB = 0x20, kInV = 0x100, kInU = 0x1000, kColA = 0x10000;
template <uint32_t M>
__device__ __forceinline__ float pick(const float* a, const float* b, uint32_t f) {
  float d;
  asm("{\n" NAT_PRED("%5", "%6") "add.f32 %0, %1, %2;\n@p add.f32 %0, %3, %4;\n}\n"
      : "=&f"(d) : "f"(a[0]), "f"(a[2]), "f"(b[0]), "f"(b[2]), "r"(f), "n"(M));
  return d;
}
template <uint32_t M>
__device__ __forceinline__ float sel(float a, float b, uint32_t f) {
  float d;
  asm("{\n" NAT_PRED("%3", "%4") "selp.f32 %0, %1, %2, p;\n}\n" : "=f"(d) : "f"(a), "f"(b), "r"(f), "n"(M));
  return d;
}
template <uint32_t M>
__device__ __forceinline__ void max_if(float& m, float v, uint32_t f) {
  asm("{\n" NAT_PRED("%2", "%3") "@p max.f32 %0, %0, %1;\n}\n" : "+f"(m) : "f"(v), "r"(f), "n"(M));
}
template <uint32_t M>
__device__ __forceinline__ void add_if(float& m, float v, uint32_t f) {
  asm("{\n" NAT_PRED("%2", "%3") "@p add.f32 %0, %0, %1;\n}\n" : "+f"(m) : "f"(v), "r"(f), "n"(M));
}
__device__ __forceinline__ void pick_v(const float* a, float* v, uint32_t f) {
  v[0] = pick<kHiV>(a, a + 16, f), v[1] = pick<kHiV>(a + 1, a + 17, f);
  v[2] = pick<kHiV * 2>(a + 4, a + 20, f), v[3] = pick<kHiV * 2>(a + 5, a + 21, f);
  v[4] = pick<kHiV * 4>(a + 8, a + 24, f), v[5] = pick<kHiV * 4>(a + 9, a + 25, f);
  v[6] = a[12] + a[14], v[7] = a[13] + a[15];
}
__device__ __forceinline__ void pick_u(const float* a, float* v, uint32_t f) {
#pragma unroll
  for (int c = 0; c < 3; c++) v[2 * c] = pick<kHiU>(a + 4 * c, a + 4 * c + 12, f), v[2 * c + 1] = pick<kHiU * 2>(a + 4 * c + 1, a + 4 * c + 13, f);
}
__device__ __forceinline__ uint32_t sign_bytes(uint32_t v, uint32_t sel) {
  uint32_t d;
  asm("prmt.b32 %0, %1, %1, %2;" : "=r"(d) : "r"(v), "r"(sel));
  return d;
}
__device__ __forceinline__ float own_max(const float (&v)[14], uint32_t f) {
  float m = sel<kInV>(fmaxf(v[0], v[1]), -INFINITY, f), m2 = sel<kInV * 2>(fmaxf(v[2], v[3]), -INFINITY, f);
  max_if<kInV * 4>(m, fmaxf(v[4], v[5]), f);
  max_if<kInV * 8>(m2, fmaxf(v[6], v[7]), f);
  max_if<kInU>(m, fmaxf(fmaxf(v[8], v[10]), v[12]), f);
  max_if<kInU * 2>(m2, fmaxf(fmaxf(v[9], v[11]), v[13]), f);
  return fmaxf(m, m2);
}
__device__ __forceinline__ float quad_max(float m) {
  const float a = __shfl_xor_sync(0xffffffffu, m, 1), b = __shfl_xor_sync(0xffffffffu, m, 2), c = __shfl_xor_sync(0xffffffffu, m, 3);
  return fmaxf(fmaxf(m, a), fmaxf(b, c));
}
__device__ __forceinline__ float row_rcp(const float (&v)[14], uint32_t f) {
  float s = sel<kInV>(v[0] + v[1], 0.f, f), s2 = sel<kInV * 2>(v[2] + v[3], 0.f, f);
  add_if<kInV * 4>(s, v[4] + v[5], f);
  add_if<kInV * 8>(s2, v[6] + v[7], f);
  add_if<kInU>(s, v[8] + v[10] + v[12], f);
  add_if<kInU * 2>(s2, v[9] + v[11] + v[13], f);
  s += s2;
  const float a = __shfl_xor_sync(0xffffffffu, s, 1), b = __shfl_xor_sync(0xffffffffu, s, 2), c = __shfl_xor_sync(0xffffffffu, s, 3);
  return rcp_approx((s + a) + (b + c));
}
__device__ __forceinline__ void route(const float (&v)[14], float s, const uint32_t (&rt)[9], uint32_t (&p)[14]) {
#pragma unroll
  for (int i = 0; i < 7; i++) {
    const uint32_t u = pack_bf16(v[2 * i] * s, v[2 * i + 1] * s);
    if (i < 4) p[i] = u & rt[i];
    if (i < 3) p[i + 4] = u & rt[i + 4];
    if (i >= 4) {
      p[i + 3] = u & rt[7];
      p[i + 6] = u & rt[8];
    }
  }
}

template <int C, int T0 = 0, int T1 = 7>
__device__ __forceinline__ void pv_chunk(float (&z)[32], const uint32_t (&pa)[14], const uint32_t (&pb)[14],
                                         const uint32_t (&meta)[4], uint64_t dV) {
#pragma unroll
  for (int t = T0; t < T1; t++) {
    if (t & 1)
      wg_s64t1<0, 32>(z, pa[2 * t], pb[2 * t], pa[2 * t + 1], pb[2 * t + 1], dV + ((2 * C * kChunkBytes + t * 2048) >> 4), 1,
                      meta[t >> 1]);
    else if (t > 0)
      wg_s64t<0, 32>(z, pa[2 * t], pb[2 * t], pa[2 * t + 1], pb[2 * t + 1], dV + ((2 * C * kChunkBytes + t * 2048) >> 4), 1,
                     meta[t >> 1]);
    else
      wg_s64tz<0, 32>(z, pa[0], pb[0], pa[1], pb[1], dV + ((2 * C * kChunkBytes) >> 4), 0, meta[0]);
  }
}
template <int C>
__device__ __forceinline__ void pack_z(const float (&z)[32], uint32_t (&za)[24], uint32_t (&zb)[24]) {
#pragma unroll
  for (int j = 0; j < 8; j++) {
    za[8 * C + j] = pack_bf16(z[4 * j], z[4 * j + 1]);
    zb[8 * C + j] = pack_bf16(z[4 * j + 2], z[4 * j + 3]);
  }
}

template <int H>
__device__ __forceinline__ void pack_out(const float (&ac)[48], uint32_t (&oa)[24], uint32_t (&ob)[24]) {
#pragma unroll
  for (int j = 0; j < 12; j++) {
    oa[12 * H + j] = pack_bf16(ac[4 * j], ac[4 * j + 1]);
    ob[12 * H + j] = pack_bf16(ac[4 * j + 2], ac[4 * j + 3]);
  }
}
struct Maps { CUtensorMap v6, v2, v14, u8, px[8], wv, wo; };
__device__ __forceinline__ void tma_prefetch_5d(const CUtensorMap* map, int c0, int c1, int c2, int c3, int c4) {
  asm volatile("cp.async.bulk.prefetch.tensor.5d.L2.global.tile [%0, {%1, %2, %3, %4, %5}];" ::"l"((uint64_t)map), "r"(c0), "r"(c1),
               "r"(c2), "r"(c3), "r"(c4) : "memory");
}
__device__ __forceinline__ int first_line(const TileCoord tc) { return 3 * (qpix(tc.pr, 8 * tc.I) * kW + qpix(tc.pc, 8 * tc.J)); }
__device__ __forceinline__ void load_px(const Maps& tm, const TileTable& tt, uint32_t dst, uint32_t bar, int line, int kind) {
#pragma unroll
  for (int i = 0; i < 2; i++) {
    if (i == 0 || kind != 0) {
      const CUtensorMap* map = (const CUtensorMap*)((const char*)tm.px + tt.b[kind][i][1]);
      if (bar) tma_load_5d(dst + tt.b[kind][i][2], map, bar, 0, 0, 0, 0, line + tt.b[kind][i][0]);
      else tma_prefetch_5d(map, 0, 0, 0, 0, line + tt.b[kind][i][0]);
    }
  }
}
__device__ __forceinline__ void store_px(const Maps& tm, const TileTable& tt, uint32_t buf, int line, int kind) {
#pragma unroll
  for (int i = 0; i < 8; i++) {
    const int j = 2 * (i & 3) + (i >> 2);
    asm volatile("cp.async.bulk.tensor.5d.global.shared::cta.tile.bulk_group [%0, {%2, %2, %2, %2, %3}], [%1];" ::"l"(
                     (uint64_t)tm.px + tt.g[kind][j][1]), "r"(buf + i * 3072), "r"(0), "r"(line + tt.g[kind][j][0]) : "memory");
  }
  asm volatile("cp.async.bulk.commit_group;" ::: "memory");
}
__device__ __noinline__ bool refetch(uint32_t base, const uint8_t* src, bool gap) {
  constexpr uint32_t bars = 1024 + kBarOff, cnt = bars + 192;
#pragma unroll 1
  for (uint32_t o = 0; o < kWBytes && !gap; o += 2048) {
    uint32_t mx = 0;
#pragma unroll
    for (int i = 0; i < 4; i++) {
      uint4 v;
      asm volatile("ld.shared.v4.u32 {%0,%1,%2,%3}, [%4];" : "=r"(v.x), "=r"(v.y), "=r"(v.z), "=r"(v.w)
                   : "r"(base + o + i * 512 + (threadIdx.x & 31) * 16));
      mx = __vimax3_u32(__vimax3_u32(mx, v.x, v.y), v.z, v.w);
    }
    gap = __any_sync(0xffffffffu, mx == kEmpty);
  }
  uint32_t n;
  asm volatile("ld.shared.u32 %0, [%1];" : "=r"(n) : "r"(cnt) : "memory");
  if (!gap || __any_sync(0xffffffffu, n > (1u << 12))) return false;
  asm volatile("bar.sync 15, 128;" ::: "memory");
  if (threadIdx.x == 0) {
    asm volatile("st.shared.u32 [%0], %1;" ::"r"(cnt), "r"(n + 1) : "memory");
    mbar_arrive_expect_tx(bar_redo(bars), kWBytes);
    bulk_load(base, src, kWBytes, bar_redo(bars));
  }
  __syncwarp();
  mbar_wait(bar_redo(bars), n & 1);
  return true;
}
__device__ __forceinline__ bool any_nan(const uint32_t (&a)[24]) {
  uint32_t m[2] = {a[0], a[1]}, nan;
#pragma unroll
  for (int i = 2; i < 24; i++) asm("max.NaN.bf16x2 %0, %0, %1;" : "+r"(m[i & 1]) : "r"(a[i]));
  asm("max.NaN.bf16x2 %0, %0, %1;" : "+r"(m[0]) : "r"(m[1]));
  asm volatile("{\n.reg .pred p;\nsetp.ne.u32 p, %1, 0;\nbar.red.or.pred p, 15, 128, p;\nselp.u32 %0, 1, 0, p;\n}\n"
               : "=r"(nan) : "r"(((m[0] & 0x7FFF7FFFu) + 0x007F007Fu) & 0x80008000u) : "memory");
  return __any_sync(0xffffffffu, nan);
}
template <int S0, int S1, int Z>
__device__ __forceinline__ void g2_steps(float (&ac)[48], const uint32_t (&za)[24], const uint32_t (&zb)[24], uint64_t d) {
#pragma unroll
  for (int s = S0; s < S1; s++) {
    const uint64_t ds = d + (((s >> 2 & 1) * (kWChunk / 2) + (s & 3) * 32) >> 4);
    if (s == Z) wg_d96z<0, 48>(ac, za[2 * s], zb[2 * s], za[2 * s + 1], zb[2 * s + 1], ds, 0);
    else wg_d96<0, 48>(ac, za[2 * s], zb[2 * s], za[2 * s + 1], zb[2 * s + 1], ds, 1);
  }
}

__device__ __forceinline__ void consumer(const int wg, __nv_bfloat16* out, const uint8_t* wimg, const uint32_t sbase,
                                         const uint32_t zero, const Maps& tm, const TileTable& tt) {
  const int tid = threadIdx.x & 127;
  const int w = __shfl_sync(0xffffffffu, tid >> 5, 0), lane = tid & 31;
  const uint64_t dK = make_desc(sbase, 16, 1024);
  const uint64_t dV = make_desc(sbase, kChunkBytes, 512, 2);
  const uint64_t dW1 = make_desc(sbase + kW1Off, 16, 1024);
  const uint64_t dX0 = make_desc(sbase + kW2Off + wg * 2 * kWChunk, 16, 1024), dY0 = make_desc(sbase + kW2Off + (1 - wg) * 2 * kWChunk, 16, 1024);
  const uint64_t dX2 = make_desc(sbase + kXOff + wg * (kWChunk / 2), 16, 1024), dY2 = make_desc(sbase + kXOff + (1 - wg) * (kWChunk / 2), 16, 1024);
  const uint32_t bars = sbase + kBarOff;
  int tile0 = blockIdx.x * kTilesPerCta;
  asm volatile("" : "+r"(tile0));
  const int nt = num_tiles();

  uint32_t pix = 0, geo[6] = {};
  const int l = lane & 3;
#pragma unroll 1
  for (int j = 4; j >= 0; j -= 2) {
    const TileCoord tc = decode_tile(tt, tile0 + wg + j);
    const bool col = tc.kind == 1 || tc.kind == 2;
    const int g = col ? lane >> 2 : 2 * w + ((lane >> 2) & 1), qc = col ? w : lane >> 3;
    const uint32_t pr = qpix(tc.pr, 8 * tc.I + g) * kW;
    if (j == nt - 2) pix = (pr + qpix(tc.pc, 8 * tc.J + qc)) | (pr + qpix(tc.pc, 8 * tc.J + qc + 4)) << 16;
    const int d = 8 * tc.J + 6 * tc.pc - 6 - halo_c0(tc);
    const int ro = woff(tc.pr, tc.I, g), coA = woff(tc.pc, tc.J, qc) + d, coB = woff(tc.pc, tc.J, qc + 4) + d - 3;
#pragma unroll
    for (int i = 5; i >= 2; i--) geo[i] = geo[i - 2];
    const uint32_t lr = 0x1FCu << ro;
    const uint32_t lv = lr >> (2 + (l >> 1)), lu = lr >> (2 * l + 2 * tc.up);
    const uint32_t t = __byte_perm(lv, lu, wg ? 0x4501 : 0x5410);
    geo[0] = (((t & 0x15u) | (lv & 0x40u)) * 0x02082080u & 0x80808080u) | (((t >> 8) & 0x15u) * 0x01041040u & 0x40404040u) |
             (__byte_perm(t << 5, t << 4, 0x7362) & 0x20202020u) | (nt == 6);
    const int dr = (ro - 1) & 7;
    const uint32_t hiv = (((1u << ((ro - (l >> 1) + 1) >> 1)) - 1u) ^ (wg ? 7u : 0u)) & 7u, hiu = (t >> 24) & 3u;
    const uint32_t ca = (1u << coA) - 1u;
    geo[1] = hiv * kHiV | hiu * kHiU | ((((1u << coB) - 1u) >> (2 * (l & 1))) & 3u) * kColB |
             (15u & ~((uint32_t)((dr & 1) == (l >> 1)) << (dr >> 1))) * kInV | ((t >> 16 | t >> 24) & 3u) * kInU | ca * kColA |
             (ca >> ((0x49 >> (2 * l)) & 3) & 1u) << 19 | (uint32_t)(l == 3) << 20 | (0x55u & ((1u << (2 * coB)) - 1u)) << 24;
  }
  keep_regs(geo);
  const int so = (lane >> 3) | (lane & 4);
  uint32_t sts = sbase + w * 3072 + so * 128 + (((lane & 3) ^ so) << 4);
  __nv_bfloat16* poA = out + 8 * l + (pix & 0xFFFFu) * kC + 96 * wg;
  __nv_bfloat16* poB = out + 8 * l + (pix >> 16) * kC + 96 * wg;
  asm volatile("" : "+l"(poA), "+l"(poB), "+r"(sts));
  uint32_t oa[24], ob[24];
#pragma unroll
  for (int j = 0; j < 24; j++) oa[j] = ob[j] = 0u;
  keep_regs(oa);
  keep_regs(ob);
  PROF(wg, 0);
  if (threadIdx.x == 0) GT(1);

  for (int k = wg; k < nt; k += 2) {
    const uint32_t ph = (k >> 1) & 1;
    const int it = k >> 1;
    uint32_t qa[24], qb[24], hok[3];
    uint32_t fl = geo[1];
    {
      float acc[96];
      const uint32_t xp = (k + (k > 0)) & 1;
      if (k > 0) nb_sync(1 + (1 - wg));
#pragma unroll
      for (int s = 0; s < 12; s++) {
        if (s == 0) mbar_wait(bar_x(bars, k > 0, 0), xp);
        if (s == 0 && k < 2) PROF(wg, 1);
        if (s == 0) PROFS(2, wg, 2 + it * 12);
        if (s == 0 && w == 0 && k < 2) GT(20 + wg);
        if (s == 4) wg_wait<1>();
        if ((s & 3) == 0 && (k == 0 || s > 0)) {
          mbar_wait(k == 0 ? bar_w1c(bars, s >> 2) : bar_x(bars, 1, s >> 2), xp);
          PROFS(17, wg, 50 + (s >> 2));
        }
        if ((s & 3) == 0) wg_fence();
        const uint64_t dX = make_desc(sbase + x_chunk(k, s >> 2), 16, 1024) + 2 * (s & 3);
        if (s == 0) wg_m192z<0, 96>(acc, dX, dW1, 0);
        else wg_m192<0, 96>(acc, dX, wdesc(dW1, s), 1);
        if ((s & 3) == 3 || s == 0) wg_commit();
      }
      PROFS(13, wg, 13 + it * 12);
      const uint32_t e = sts + out_slot(k, nt), o = e ^ 64;
      uint32_t ad[4] = {wg ? o + 1024 : e, wg ? e + 2048 : o, wg ? e : o + 1024, wg ? o : e + 2048};
      keep_regs(ad);
      wg_wait<2>();
      if (k > 0) nb_arrive_p(0);
      wg_wait<1>();
      if (k > 0) nb_arrive_p(14);
      wg_wait<0>();
      if (k > 0) {
        nb_arrive_p(6);
        sched_fence();
      }
      fence_regs(acc);
      PROFS(3, wg, 3 + it * 12);
#pragma unroll
      for (int j = 0; j < 24; j++) {
        qa[j] = pack_bf16(acc[4 * j], acc[4 * j + 1]);
        qb[j] = pack_bf16(acc[4 * j + 2], acc[4 * j + 3]);
      }
      keep_regs(qa);
      keep_regs(qb);
      sched_fence();
      if (k >= 2) {
        nb_sync(11);
        stage_out<0, 6>(ad, oa, ob);
        nb_sync(12);
        stage_out<6, 12>(ad, oa, ob);
      }
#pragma unroll
      for (int c = 0; c < 3; c++) hok[c] = mbar_test(bar_full(bars, wg, c), ph);
      if (k >= 2) {
        fence_proxy_async();
        nb_arrive_p(10);
      }
    }

    float aE[52], aO[24], bO[52], bE[28];
    const uint32_t mq = 0xEEEE4444u | zero;
    PROFS(4, wg, 4 + it * 12);

    mbar_wait_if(hok[0], bar_full(bars, wg, 0), ph);
    PROFS(14, wg, 40 + it * 3);
    if (w == 0 && k < 2) GT(22 + wg);
    if (k > 0) nb_sync(3 + (1 - wg));
    wg_fence();
#pragma unroll
    for (int ks = 0; ks < 6; ks++) {
      if (ks == 2) {
        mbar_wait_if(hok[1], bar_full(bars, wg, 1), ph);
        PROFS(14, wg, 41 + it * 3);
        wg_fence();
      }
      if (ks == 4) {
        mbar_wait_if(hok[2], bar_full(bars, wg, 2), ph);
        PROFS(14, wg, 42 + it * 3);
        wg_fence();
      }
      const uint64_t d = dK + ((ks * kChunkBytes) >> 4);
      if (ks == 0) wg_s104z<0, 52>(aE, qa[0], qa[1], qa[2], qa[3], d, 0, mq);
      else wg_s104<0, 52>(aE, qa[4 * ks], qa[4 * ks + 1], qa[4 * ks + 2], qa[4 * ks + 3], d, 1, mq);
      if (ks == 0) wg_s48z<0, 24>(aO, qa[0], qa[1], qa[2], qa[3], d + ((7 * 1024 + 64) >> 4), 0, mq);
    }
    wg_commit();
#pragma unroll
    for (int ks = 1; ks < 6; ks++)
      wg_s48<0, 24>(aO, qa[4 * ks], qa[4 * ks + 1], qa[4 * ks + 2], qa[4 * ks + 3], dK + ((ks * kChunkBytes + 7 * 1024 + 64) >> 4), 1, mq);
    wg_commit();
    wg_s56z<0, 28>(bE, qb[0], qb[1], qb[2], qb[3], dK, 0, mq);
#pragma unroll
    for (int ks = 1; ks < 6; ks++) wg_s56<0, 28>(bE, qb[4 * ks], qb[4 * ks + 1], qb[4 * ks + 2], qb[4 * ks + 3], dK + ((ks * kChunkBytes) >> 4), 1, mq);
    wg_commit();
    wg_wait<2>();
    fence_regs(aE);
    PROFS(5, wg, 5 + it * 12);

    uint32_t pa[14], pb[14], meta[4];
    {
      float vA[14], vB[14];
      pick_v(aE, vA, fl);
      pick_u(aE + 28, vA + 8, fl);
      fence_regs(vA);
      if (k == 0) {
        if (__builtin_expect(__any_sync(0xffffffffu, vA[6] != vA[6]), 0)) {
          wg_wait<0>();
          fence_regs(aO);
          fence_regs(bE);
          if (refetch(sbase + kW1Off, wimg, false)) {
#pragma unroll
            for (int j = 0; j < 24; j++) oa[j] = ob[j] = 0u;
            k -= 2;
            continue;
          }
        }
        if (elect_one()) mbar_arrive(bar_xf(bars));
      }
      wg_fence();
      wg_s104z<0, 52>(bO, qb[0], qb[1], qb[2], qb[3], dK + 4, 0, mq);
#pragma unroll
      for (int ks = 1; ks < 6; ks++)
        wg_s104<0, 52>(bO, qb[4 * ks], qb[4 * ks + 1], qb[4 * ks + 2], qb[4 * ks + 3], dK + ((ks * kChunkBytes + 64) >> 4), 1, mq);
      wg_commit();
      if (k + 1 < nt) nb_arrive(1 + wg);
      uint32_t rt[9];
#pragma unroll
      for (int i = 0; i < 7; i++) rt[i] = sign_bytes(geo[0] << (i >> 2), 0x8888u + 0x1111u * (i & 3));
      rt[7] = sign_bytes(geo[0] << 2, 0x9988u);
      rt[8] = sign_bytes(geo[0] << 2, 0xBBAAu);
      keep_regs(rt);
      pa[13] = geo[0] & zero, pb[13] = geo[1] & zero;
      wg_wait<2>();
      keep_regs(qa);
      fence_regs(aO);
      float oA[6], eB[8];
      pick_u(aO, oA, fl);
      wg_wait<1>();
      fence_regs(bE);
      pick_v(bE, eB, fl);
      vA[8] = sel<kColA>(oA[0], vA[8], fl), vA[9] = sel<kColA>(oA[1], vA[9], fl);
      vA[10] = sel<kColA * 2>(oA[2], vA[10], fl), vA[11] = sel<kColA * 2>(oA[3], vA[11], fl);
      vA[12] = sel<kColA * 4>(oA[4], vA[12], fl), vA[13] = sel<kColA * 4>(oA[5], vA[13], fl);
      {
        const float m1 = __uint_as_float(0x88DD88DDu), m0 = __uint_as_float(0x88DDDD88u);
        meta[0] = 0xDD88DD88u ^ __byte_perm(fl, 0u, 0x3344);
        meta[1] = __float_as_uint(sel<kColA * 16>(sel<kColA>(m1, m0, fl), __uint_as_float(meta[0]), fl));
        meta[2] = __float_as_uint(sel<kColA * 8>(m1, m0, fl));
        meta[3] = __float_as_uint(sel<kColA * 4>(m1, m0, fl));
        keep_regs(meta);
      }
      float mA = own_max(vA, fl);
      fl |= __float_as_uint(eB[7]) & zero;
      fence_regs(eB);
      fence_regs(vA);
      asm volatile("" : "+f"(mA), "+r"(fl));
      sched_fence();
      wg_wait<0>();
      sched_fence();
      keep_regs(qb);
      fence_regs(bO);
      PROFS(6, wg, 6 + it * 12);
      if (w == 0) GT(24 + k);
      mA = quad_max(mA);
      pick_v(bO, vB, fl);
      pick_u(bO + 28, vB + 8, fl);
#pragma unroll
      for (int i = 0; i < 8; i += 2) vB[i] = sel<kColB>(vB[i], eB[i], fl), vB[i + 1] = sel<kColB * 2>(vB[i + 1], eB[i + 1], fl);
#pragma unroll
      for (int i = 0; i < 14; i++) vA[i] = i < 3 ? ex2(vA[i] - mA) : vA[i] - mA;
      fence_regs(vA);
      fence_regs(vB);
      sched_fence();
#pragma unroll
      for (int i = 3; i < 14; i++) vA[i] = ex2(vA[i]);
      const float mB = quad_max(own_max(vB, fl));
      PROFS(7, wg, 7 + it * 12);
#pragma unroll
      for (int i = 0; i < 14; i++) vB[i] = i < 1 ? ex2(vB[i] - mB) : vB[i] - mB;
      fence_regs(vA);
      fence_regs(vB);
      sched_fence();
#pragma unroll
      for (int i = 1; i < 14; i++) vB[i] = ex2(vB[i]);
      route(vA, row_rcp(vA, fl), rt, pa);
      route(vB, row_rcp(vB, fl), rt, pb);
    }
    PROFS(8, wg, 8 + it * 12);
    if (k == NAT_PK) PROFS(18, wg, 53);
    sched_fence();

    float ac0[48], ac1[48];
    {
      float z0[32], z1[32], z2[32];
      uint32_t za[24], zb[24];
      wg_fence();
      pv_chunk<0>(z0, pa, pb, meta, dV);
      wg_commit();
      pv_chunk<1>(z1, pa, pb, meta, dV);
      wg_commit();
      wg_wait<1>();
      if (k == NAT_PK) PROFS(18, wg, 54);
      if (k + 1 < nt) nb_arrive_p(7);
      pv_chunk<2, 0, 3>(z2, pa, pb, meta, dV);
      wg_commit();
      sched_fence();
      fence_regs(z0);
      pack_z<0>(z0, za, zb);
      sched_fence();
      wg_fence();
      pv_chunk<2, 3, 7>(z2, pa, pb, meta, dV);
      wg_commit();
      wg_wait<2>();
      if (k == NAT_PK) PROFS(19, wg, 55);
      if (k + 1 < nt) nb_arrive_p(8);
      if (k < 2) mbar_wait(k == 1 ? bar_wok(bars) : bar_w2a(bars), 0);
      wg_fence();
      g2_steps<0, 3, 0>(ac0, za, zb, dX0);
      wg_commit();
      sched_fence();
      fence_regs(z1);
      pack_z<1>(z1, za, zb);
      sched_fence();
      wg_fence();
      g2_steps<3, 4, 0>(ac0, za, zb, dX0);
      wg_commit();
      g2_steps<4, 8, 0>(ac0, za, zb, dX0);
      wg_commit();
      wg_wait<3>();
      if (k + 1 < nt) nb_arrive_p(9);
      else nb_arrive(11);
      if (k == NAT_PK) PROFS(20, wg, 56);
      keep_regs(pa);
      keep_regs(pb);
      keep_regs(meta);
      sched_fence();
      const uint32_t mok = mbar_test(bar_w2m(bars), k + 1 < nt ? k & 1 : ~k & 1);
      const uint32_t wp = k < 2 ? 0 : k + 1 < nt ? ~k & 1 : k & 1, wok = mbar_test(bar_w2(bars), wp);
      fence_regs(z2);
      pack_z<2>(z2, za, zb);
      keep_regs(za);
      keep_regs(zb);
      sched_fence();
      PROFS(9, wg, 9 + it * 12);
      wg_wait<1>();
      if (k > 0 && k + 1 < nt) nb_arrive(11);
      mbar_wait_if(mok, bar_w2m(bars), k & 1);
      wg_fence();
      g2_steps<8, 12, 0>(ac0, za, zb, dX2);
      wg_commit();
      g2_steps<8, 12, 8>(ac1, za, zb, dY2);
      wg_commit();
      wg_wait<2>();
      if (k > 0 && k + 1 < nt) nb_arrive(12);
      mbar_wait_if(wok, bar_w2(bars), wp);
      wg_fence();
      g2_steps<0, 4, 8>(ac1, za, zb, dY0);
      wg_commit();
      wg_wait<2>();
      if (k + 2 < nt) nb_arrive_p(13);
      const bool direct = k + 2 >= nt;
      sched_fence();
      fence_regs(ac0);
      pack_out<0>(ac0, oa, ob);
      store_rows<0, 1>(direct, poA, poB, oa, ob);
      sched_fence();
      wg_fence();
      g2_steps<4, 8, 8>(ac1, za, zb, dY0);
      wg_commit();
      if (k + 1 < nt) nb_arrive(3 + wg);
      PROFS(10, wg, 10 + it * 12);
      wg_wait<2>();
      if (k + 2 < nt && (k > 0 || nt == 6)) nb_arrive_p(5);
      store_rows<1, 3>(direct, poA, poB, oa, ob);
      __nv_bfloat16 *qA = poA - 192 * wg, *qB = poB - 192 * wg;
      if (k + 2 == nt) nb_sync(11);
      sched_fence();
      wg_wait<0>();
      fence_regs(ac1);
      if (direct) {
        pack_out<1>(ac1, oa, ob);
        asm volatile("" : "+l"(qA), "+l"(qB));
        store_rows<3, 6>(true, qA, qB, oa, ob);
        break;
      }
      sched_fence();
      pack_out<1>(ac1, oa, ob);
      if (k == 0) {
        if (any_nan(oa)) {
          for (int c = 0; c < 3 && __any_sync(0xffffffffu, geo[2] & 1u); c++) mbar_wait(bar_x(bars, 1, c), 1);
          bool first = true;
          do {
            if (!__any_sync(0xffffffffu, refetch(sbase + kW2Off, wimg + w2_offset(), first))) break;
            first = false;
            wg_fence();
            g2_steps<0, 8, 0>(ac0, za, zb, dX0);
            g2_steps<8, 12, 0>(ac0, za, zb, dX2);
            g2_steps<8, 12, 8>(ac1, za, zb, dY2);
            g2_steps<0, 8, 8>(ac1, za, zb, dY0);
            wg_commit();
            wg_wait<0>();
            fence_regs(ac0);
            fence_regs(ac1);
            pack_out<0>(ac0, oa, ob);
            pack_out<1>(ac1, oa, ob);
          } while (any_nan(oa));
          if (__any_sync(0xffffffffu, geo[2] & 1u)) {
            asm volatile("bar.sync 15, 128;" ::: "memory");
            if (w == 0 && elect_one()) {
              const TileCoord tc = decode_tile(tt, tile0 + 2);
              mbar_arrive_expect_tx(bar_raw(bars), kWChunk);
#pragma unroll 1
              for (int c = 0; c < 3; c++) load_px(tm, tt, sbase + x_chunk(2, c), bar_raw(bars), first_line(tc) + c, tc.kind);
            }
            __syncwarp();
            mbar_wait(bar_raw(bars), 0);
          }
        }
        if (nt < 6) nb_arrive_p(5);
        if (elect_one()) mbar_arrive(bar_wok(bars));
      }
      keep_regs(za);
      keep_regs(zb);
#pragma unroll
      for (int i = 0; i < 4; i++) geo[i] = geo[i + 2];
      keep_regs(oa);
      keep_regs(ob);
      PROFS(12, wg, 12 + it * 12);
      sched_fence();
    }
  }
  PROF(wg, 38);
  GT_DUMP();
  PROF_DUMP(wg);
}

struct HaloCols { int vj, vc, uj, uc; };
__device__ __forceinline__ HaloCols halo_cols(const TileCoord& tc) {
  const int c0 = halo_c0(tc);
  return HaloCols{c0 > 98, c0 > 98 ? 98 : c0 + 3, c0 < 0 ? -1 : 0, c0 < 0 ? 4 : c0};
}
__device__ __forceinline__ void first_halo(const Maps& tm, uint32_t sbase, const TileCoord tc, int i) {
  const HaloCols hc = halo_cols(tc);
  const uint32_t dst = sbase + i * kChunkBytes, bar = bar_full(sbase + kBarOff, 0, i >> 1);
  const int h0 = halo_r0(tc), ch = 24 * tc.pc + 4 * i;
  tma_load_5d(dst, &tm.v14, bar, ch, hc.vj, hc.vc, tc.pr, h0);
  tma_load_5d(dst + 7 * 1024, &tm.u8, bar, ch, hc.uj, h0 + (tc.up ? 0 : -2), tc.pr, hc.uc);
  tma_load_5d(dst + 10 * 1024, &tm.u8, bar, ch, hc.uj, h0 + (tc.up ? 8 : 6), tc.pr, hc.uc);
}
__device__ __forceinline__ void load_halo(const Maps& tm, uint32_t sbase, uint32_t bars, const TileCoord tc, int k, int c) {
  const HaloCols hc = halo_cols(tc);
  const int h6 = halo_r0(tc) + (tc.up ? 0 : 8), h2 = halo_r0(tc) + 6, h8 = halo_r0(tc) + (tc.up ? 0 : 6), ch = 24 * tc.pc + 8 * c;
  uint32_t dv = sbase + 2 * c * kChunkBytes, du = dv + 7 * 1024;
  if (((k ^ tc.up) & 1) == 0) dv += 4 * 1024, du += 3 * 1024;
  const uint32_t bar = bar_full(bars, k & 1, c);
  mbar_arrive_expect_tx(bar, 14 * 1024);
  nb_sync_p(7 + c);
#pragma unroll
  for (int h = 0; h < 2; h++) {
    tma_load_5d(dv + h * kChunkBytes, &tm.v6, bar, ch + 4 * h, hc.vj, hc.vc, tc.pr, h6);
    tma_load_5d(du + h * kChunkBytes, &tm.u8, bar, ch + 4 * h, hc.uj, h8, tc.pr, hc.uc);
    tma_load_5d(sbase + (2 * c + h) * kChunkBytes + 3 * 1024, &tm.v2, bar, ch + 4 * h, hc.vj, hc.vc, tc.pr, h2);
  }
  PROFS(15, 2, k * 4 + c);
}
__device__ __forceinline__ void gather_px(const __nv_bfloat16* __restrict__ x, uint32_t sbase, const TileCoord tc) {
  const int lane = threadIdx.x & 31, g = lane >> 3;
  uint32_t ro[4], co[4];
#pragma unroll
  for (int i = 0; i < 4; i++) {
    ro[i] = qpix(tc.pr, 8 * tc.I + 2 * i + (g & 1)) * (kW * kC * 2) + 16 * (lane & 7);
    co[i] = qpix(tc.pc, 8 * tc.J + 2 * i + (g >> 1)) * (kC * 2);
  }
  const uint32_t dst = sbase + kXOff + g * 128 + (((lane & 7) ^ g) << 4);
  if (lane < 8)
    asm volatile("cp.async.bulk.prefetch.L2.global [%0], 3456;" ::"l"(x + (qpix(tc.pr, 8 * tc.I + lane) * kW + 215 * tc.pc) * kC) : "memory");
  __syncwarp();
  keep_regs(ro);
  keep_regs(co);
  sched_fence();
  nb_sync_p(13);
  nb_sync_p(5);
#pragma unroll
  for (int i = 0; i < 16; i++) {
    const char* src = (const char*)x + (ro[i >> 2] + co[i & 3]);
#pragma unroll
    for (int q = 0; q < 3; q++)
      asm volatile("cp.async.cg.shared.global [%0], [%1], 16;" ::"r"((dst ^ ((i & 1) * 576)) + (i >> 1) * 1024 + q * 8192), "l"(src + 128 * q) : "memory");
  }
  asm volatile("cp.async.wait_all;" ::: "memory");
  fence_proxy_async();
  __syncwarp();
  if (lane < 3) mbar_arrive(bar_x(sbase + kBarOff, 1, lane));
  __syncwarp();
}

__global__ void __launch_bounds__(384, 1)
nat_kernel(const __nv_bfloat16* __restrict__ x, __nv_bfloat16* out, const __nv_bfloat16* __restrict__ wqkv,
           const __nv_bfloat16* __restrict__ wo, uint8_t* wimg, const uint32_t zero,
           const __grid_constant__ Maps tm, const __grid_constant__ TileTable tt) {
  extern __shared__ uint8_t smem_raw[];
  constexpr uint32_t sbase = 1024;
  constexpr uint32_t bars = sbase + kBarOff;
  const int tid = threadIdx.x;
  const uint32_t t_start = now_ns();
  if (tid == 0) GT(0);
  const int role = __shfl_sync(0xffffffffu, blockIdx.x + 8 * (tid & ~31), 0), wid = role >> 8;
  const bool w2cta = blockIdx.x - 128 < 3 && wqkv != nullptr;
  if (wid >= 8) {
    asm volatile("setmaxnreg.dec.sync.aligned.u32 24;");
    if (smem_u32(smem_raw) != sbase) __trap();
    const int c = wid & 3, lane = tid & 31;
    const int tile0 = blockIdx.x * kTilesPerCta, nt = num_tiles();
    uint32_t w2o = 0;
    if (c == 3) {
      if (elect_one()) wait_clock(t_start, NAT_TM);
      __syncwarp();
      asm volatile("prefetch.tensormap [%0];" ::"l"((uint64_t)(tm.px + (blockIdx.x < 112 ? 2 : 0))) : "memory");
      asm volatile("prefetch.tensormap [%0];" ::"l"((uint64_t)&tm.v6) : "memory");
      asm volatile("prefetch.tensormap [%0];" ::"l"((uint64_t)&tm.v2) : "memory");
      asm volatile("prefetch.tensormap [%0];" ::"l"((uint64_t)(tm.px + (blockIdx.x < 112 ? 5 : 6))) : "memory");
      asm volatile("prefetch.tensormap [%0];" ::"l"((uint64_t)(tm.px + 7)) : "memory");
      if (nt < 6) {
        asm volatile("prefetch.tensormap [%0];" ::"l"((uint64_t)(tm.px + 1)) : "memory");
        asm volatile("prefetch.tensormap [%0];" ::"l"((uint64_t)(tm.px + 2)) : "memory");
        asm volatile("prefetch.tensormap [%0];" ::"l"((uint64_t)&tm.v14) : "memory");
        asm volatile("prefetch.tensormap [%0];" ::"l"((uint64_t)&tm.u8) : "memory");
      }
      __nanosleep(1600);
      asm volatile("bar.sync 4, 64;" ::: "memory");
      w2o = w2_offset();
      if (elect_one()) {
        mbar_arrive_expect_tx(bar_w2a(bars), kWChunk);
        mbar_arrive_expect_tx(bar_w2(bars), kWChunk);
        sleep_clock(t_start, NAT_TW2);
        bulk_load(sbase + kW2Off, wimg + w2o, kWChunk, bar_w2a(bars));
        mbar_wait(bar_xf(bars), 0);
        bulk_load(sbase + kW2Off + 2 * kWChunk, wimg + (w2o + 2 * kWChunk), kWChunk, bar_w2(bars));
      }
      __syncwarp();
      if (nt < 6) gather_px(x, sbase, decode_tile(tt, tile0 + 2));
      if (wqkv == nullptr) return;
      __nanosleep(2500);
      mbar_wait(bar_wok(bars), 0);
      if (lane == 0) asm volatile("red.relaxed.gpu.global.add.u32 [%0], 1;" ::"l"(g_flag) : "memory");
      if (blockIdx.x != kCtas - 1) return;
#pragma unroll
      for (int i = 0; i < 8; i++) asm volatile("st.shared.v4.u32 [%0], {%1,%1,%1,%1};" ::"r"(bars + 1024 + i * 512 + lane * 16), "r"(kEmpty) : "memory");
      fence_proxy_async();
      __syncwarp();
      if (elect_one()) {
#pragma unroll 1
        for (int i = 0; i < 36; i++) {
          if (i == 18) {
            uint32_t v, it = 0;
            do {
              __nanosleep(500);
              asm volatile("ld.relaxed.gpu.global.u32 %0, [%1];" : "=r"(v) : "l"(g_flag) : "memory");
            } while (v < gridDim.x && ++it < (1u << 18));
          }
          asm volatile("cp.async.bulk.global.shared::cta.bulk_group [%0], [%1], 4096;" ::"l"(
                           wimg + (i < 18 ? 3 * kWBytes - w2o + i * 4096 : (i - 18) * 4096)), "r"(bars + 1024) : "memory");
          asm volatile("cp.async.bulk.commit_group;" ::: "memory");
          asm volatile("cp.async.bulk.wait_group.read 1;" ::: "memory");
        }
        asm volatile("cp.async.bulk.wait_group 0;" ::: "memory");
        g_flag[0] = 0;
        g_flag[32] = w2o == kWBytes;
      }
      return;
    }
    if (!elect_one()) return;
    if (c == 0) {
      for (int i = 0; i < kNumBars; i++)
        if ((i != 0 && i != 10 || nt < 6) && (i != 21 || !w2cta)) mbar_init(bars + i * 8, i == 13 || i == 16 ? 4 : 1);
      asm volatile("st.shared.v2.u32 [%0], {%1,%1};" ::"r"(bars + 192), "r"(0) : "memory");
      asm volatile("fence.mbarrier_init.release.cluster;" ::: "memory");
      if (w2cta) asm volatile("bar.sync 10, 64;" ::: "memory");
      asm volatile("bar.arrive 0, 160;" ::: "memory");
      asm volatile("bar.arrive 14, 160;" ::: "memory");
      asm volatile("bar.arrive 13, 96;" ::: "memory");
      asm volatile("bar.arrive 4, 64;" ::: "memory");
      const TileCoord tc0 = decode_tile(tt, tile0);
      const HaloCols hc = halo_cols(tc0);
      const int h0 = halo_r0(tc0);
#pragma unroll
      for (int j = 0; j < 3; j++)
        if (j > 0 || nt < 6) mbar_arrive_expect_tx(bar_full(bars, 0, j), 2 * kChunkBytes);
      wait_clock(t_start, NAT_HP);
#pragma unroll
      for (int q = 8; q < 24 && !w2cta; q += 8) {
        if (tc0.kind == 0) {
          const int ln = first_line(tc0) + (tc0.up ? -8 : 16) * 3 * kW + (q >> 3);
          tma_prefetch_5d(tm.px + 2, 0, 0, 0, 0, ln);
          tma_prefetch_5d(tm.px + 2, 0, 0, 0, 0, ln + 12 * kW);
          continue;
        }
        tma_prefetch_5d(blockIdx.x < 112 ? &tm.v6 : &tm.v14, 24 * tc0.pc + q, hc.vj, hc.vc, tc0.pr, h0 + (tc0.up || blockIdx.x >= 112 ? 0 : 8));
        tma_prefetch_5d(&tm.u8, 24 * tc0.pc + q, hc.uj, h0 + (tc0.up ? 0 : 6), tc0.pr, hc.uc);
      }
#pragma unroll 1
      for (int i = nt < 6 ? 0 : 2; i < 6; i++) {
        if (i == 2) mbar_wait(bar_w1q(bars), 0);
        first_halo(tm, sbase, tc0, i);
      }
      mbar_arrive(bar_go(bars));
      w2o = w2_offset();
    } else {
      asm volatile("bar.sync 13, 96;" ::: "memory");
      if (c == 2) {
        if (wqkv != nullptr && blockIdx.x < 131) asm volatile("bar.sync 12, 64;" ::: "memory");
        const uint32_t c0 = clock();
        while ((uint32_t)clock() - c0 < NAT_TD && nt == 6) { }
        wait_clock(t_start, NAT_T0);
#pragma unroll
        for (int j = 0; j < 3; j++) {
          mbar_arrive_expect_tx(bar_w1c(bars, j), kWChunk);
          bulk_load(sbase + kW1Off + j * kWChunk, wimg + j * kWChunk, kWChunk, bar_w1c(bars, j));
        }
        mbar_arrive(bar_w1q(bars));
        GT(2);
      } else {
#pragma unroll 1
        for (int j = nt == 6; j < 2; j++) {
          const TileCoord tc = decode_tile(tt, tile0 + j);
          const int line = first_line(tc);
          if (j == 1) mbar_wait(bar_go(bars), 0);
          if (j == 0) GT(15);
#pragma unroll 1
          for (int q = 0; q < 3; q++) {
            load_px(tm, tt, sbase + x_chunk(j, q), bar_x(bars, j, q), line + q, tc.kind);
            if (j == 1 || q == 0) mbar_arrive_expect_tx(bar_x(bars, j, q), j ? 8192 : kWChunk);
          }
          if (j == 0) GT(16);
        }
        w2o = w2_offset();
        sleep_clock(t_start, NAT_TW2);
        mbar_wait(bar_xf(bars), 0);
      }
    }
#pragma unroll 1
    for (int k = 1; k < nt; k++) {
      const TileCoord tn = decode_tile(tt, tile0 + k + 1);
      const int line = first_line(tn);
      const bool more = k + 1 < nt && (k > 1 || nt == 6);
      if (c == 1) {
#pragma unroll
        for (int q = 0; q < 3; q++) {
          nb_sync_p(q == 0 ? 0 : q == 1 ? 14 : 6);
          bulk_load(sbase + x_chunk(k, q), wimg + (w2o + x_chunk(k, q) - kW2Off), 8192, bar_w2m(bars));
        }
        mbar_arrive_expect_tx(bar_w2m(bars), kWChunk);
      }
      if (c == 2) {
        if (k == 1) sleep_clock(t_start, NAT_TX2);
        else __nanosleep(NAT_PFD);
#pragma unroll 1
        for (int q = 0; q < 3 && more; q++) load_px(tm, tt, 0, 0, line + q, tn.kind);
      }
      if (c == 2 && (blockIdx.x >= 112 || k == 5)) {
        const TileCoord tc = decode_tile(tt, tile0 + k);
        const HaloCols hc = halo_cols(tc);
        const int h8 = halo_r0(tc) + (tc.up ? 0 : 6);
#pragma unroll 1
        for (int q = 0; q < 24; q += 8) {
          tma_prefetch_5d(&tm.v6, 24 * tc.pc + q, hc.vj, hc.vc, tc.pr, h8);
          tma_prefetch_5d(&tm.v2, 24 * tc.pc + q, hc.vj, hc.vc, tc.pr, h8 + 6);
          tma_prefetch_5d(&tm.u8, 24 * tc.pc + q, hc.uj, h8, tc.pr, hc.uc);
        }
      }
      load_halo(tm, sbase, bars, decode_tile(tt, tile0 + k), k, c);
      if (c == 0 && more) {
        if (nt < 6) mbar_wait(bar_x(bars, 1, 0), 1);
#pragma unroll
        for (int q = 0; q < 3; q++) {
          if (q < 2) nb_sync_p(q ? 5 : 13);
          load_px(tm, tt, sbase + x_chunk(k + 1, q), bar_x(bars, 1, q), line + q, tn.kind);
          if (q != 1) mbar_arrive_expect_tx(bar_x(bars, 1, q), 8192);
        }
        mbar_arrive_expect_tx(bar_x(bars, 1, 1), 8192);
        PROFS(16, 2, k * 4 + 3);
      }
      if (c == 0 && k >= 2) {
        const TileCoord tp = decode_tile(tt, tile0 + k - 2);
        const int lp = first_line(tp);
        nb_sync_p(10);
        __nanosleep(NAT_XW);
        store_px(tm, tt, sbase + out_slot(k, nt), lp, tp.kind);
        if (k + 1 < nt) {
          asm volatile("cp.async.bulk.wait_group.read 0;" ::: "memory");
          bulk_load(sbase + out_slot(k, nt), wimg + (w2o + out_slot(k, nt) - kW2Off), kWChunk, bar_w2(bars));
          mbar_arrive_expect_tx(bar_w2(bars), kWChunk);
        }
      }
    }
    asm volatile("cp.async.bulk.wait_group 0;" ::: "memory");
  } else {
    if ((role & 128) == 0) {
      if ((uint32_t)role - 1024u < 272u && wqkv != nullptr) {
        fold_w1(min(2 * (role & 127) + (wid & 1), (role & 127) + 16), wqkv, wimg);
        if (wid == 4) asm volatile("bar.arrive 12, 64;" ::: "memory");
        if (tid == 128) GT(7);
      }
      sched_fence();
      if (wid == 1 && elect_one()) {
        mbar_init(bar_x(bars, 0, 0), 1);
        asm volatile("fence.mbarrier_init.release.cluster;" ::: "memory");
        GT(15);
        const int b = role & 127, ext = b >= 112, strip = ext ? 3 * b - (b < 121 ? 335 : 333) : b >> 1;
        const int pr = strip >= 28, st = strip - 28 * pr, edge = st - 1u >= 26u, end = ext ? pr : edge & st;
        const int line = 3 * ((ext ? 215 * pr : 122 - 19 * pr - 16 * (b & 1)) * kW + max(8 * st + 5 * (st & 1) - 6, 0));
        const CUtensorMap* map = tm.px + ext + 3 * edge;
        if (ext | edge) asm volatile("prefetch.tensormap [%0];" ::"l"((uint64_t)(map + 1)) : "memory");
#pragma unroll
        for (int q = 0; q < 3; q++)
          tma_load_5d(sbase + x_chunk(0, q) + 2048 * end, map, bar_x(bars, 0, 0), 0, 0, 0, 0, line + q + end * (ext ? 9 * kW : 6));
        if (ext | edge) {
#pragma unroll
          for (int q = 0; q < 3; q++)
            tma_load_5d(sbase + x_chunk(0, q) + 6144 * (1 - end), map + 1, bar_x(bars, 0, 0), 0, 0, 0, 0, line + q + (1 - end) * (ext ? 18 * kW : 9));
        }
        mbar_arrive_expect_tx(bar_x(bars, 0, 0), kWChunk);
        GT(16);
      }
      __syncwarp();
      sched_fence();
      if (wid == 2 && elect_one()) {
        const int b = role & 127, ext = b >= 112, strip = ext ? 3 * b - (b < 121 ? 335 : 333) : b >> 1, pr = strip >= 28, up = ext ? pr : b & 1;
        const TileCoord tc{pr, strip & 1, ext ? 13 * pr : 8 - 2 * pr - up, (strip - 28 * pr) >> 1, up, 0};
        mbar_init(bar_full(bars, 0, 0), 1);
        asm volatile("fence.mbarrier_init.release.cluster;" ::: "memory");
        mbar_arrive_expect_tx(bar_full(bars, 0, 0), 2 * kChunkBytes);
        asm volatile("prefetch.tensormap [%0];" ::"l"((uint64_t)&tm.u8) : "memory");
        GT(17);
        first_halo(tm, sbase, tc, 0);
        first_halo(tm, sbase, tc, 1);
      }
      __syncwarp();
    }
    sched_fence();
    {
      if (blockIdx.x >= 128 && wqkv != nullptr && (wid | 2) == 2 && elect_one())
        asm volatile("cp.async.bulk.prefetch.L2.global [%0], %1;" ::"l"(wid ? wo + (blockIdx.x & 3) * 48 * 192 : wqkv + (blockIdx.x & 3) * 48 * 576),
                     "r"(wid ? 48 * 384 : 48 * 1152) : "memory");
      __syncwarp();
      if (w2cta) {
        const int q = blockIdx.x & 3, h = wid >> 2;
        uint32_t w2o = 0;
        if (wid == 1 && elect_one()) {
          asm volatile("prefetch.tensormap [%0];" ::"l"((uint64_t)&tm.wo) : "memory");
          mbar_init(bar_raw(bars, 0), 1);
          mbar_init(bar_raw(bars, 1), 1);
          asm volatile("fence.mbarrier_init.release.cluster;" ::: "memory");
#pragma unroll
          for (int j = 0; j < 3; j++)
            asm volatile("cp.async.bulk.tensor.3d.shared::cluster.global.tile.mbarrier::complete_tx::bytes [%0], [%1, {%3, %4, %5}], [%2];" ::"r"(
                             j ? sbase + kW2Off + (j - 1) * (kWBytes / 2) : sbase),
                         "l"((uint64_t)(j ? &tm.wo : &tm.wv)), "r"(bar_raw(bars, j >> 1)), "r"(0), "r"(j ? 0 : 64 * q), "r"(j ? 3 * j - 3 : 6) : "memory");
          mbar_arrive_expect_tx(bar_raw(bars, 0), kWChunk + kWBytes / 2);
          mbar_arrive_expect_tx(bar_raw(bars, 1), kWBytes / 2);
          w2o = w2_offset();
        }
        __syncwarp();
#pragma unroll 1
        for (int r = 1 - h;; r++) {
          if (r > 0) asm volatile("bar.sync 11, 256;" ::: "memory");
          if (r == 2) break;
          if (r > 0) {
            mbar_wait(bar_raw(bars, 0), 0);
            mbar_wait(bar_raw(bars, h), 0);
          }
          if (tid == 0) GT(7);
          float acc[48];
          const uint64_t db = make_desc(sbase + kW2Off + h * (kWBytes / 2), kWChunk / 2, 512, 2);
          wg_fence();
          wg_m96tz<0, 48>(acc, make_desc(sbase, 16, 1024), db, 0);
#pragma unroll
          for (int s = 1; s < 12; s++) wg_m96t<0, 48>(acc, make_desc(sbase + (s >> 2) * 8192 + (s & 3) * 32, 16, 1024), db + s * 64, 1);
          wg_commit();
          wg_wait<0>();
          fence_regs(acc);
          if (tid == 0) GT(19);
          const int m = (tid >> 3) & 3;
#pragma unroll
          for (int j = 0; j < 12; j += 2) {
            const int n = g2_inv(8 * (j + (m >> 1)) + (tid & 7));
            asm volatile("stmatrix.sync.aligned.m8n8.x4.trans.shared.b16 [%0], {%1,%2,%3,%4};" ::"r"(
                             sbase + kW1Off + h * (kWChunk / 2) + n * 128 + (((2 * (wid & 3) + (m & 1)) ^ (n & 7)) << 4)),
                         "r"(pack_bf16(acc[4 * j], acc[4 * j + 1])), "r"(pack_bf16(acc[4 * j + 2], acc[4 * j + 3])),
                         "r"(pack_bf16(acc[4 * j + 4], acc[4 * j + 5])), "r"(pack_bf16(acc[4 * j + 6], acc[4 * j + 7])) : "memory");
          }
          fence_proxy_async();
        }
        if (tid == 0) GT(18);
        if (wid == 1) {
          if (elect_one()) {
#pragma unroll
            for (int i = 0; i < 2; i++)
              asm volatile("cp.async.bulk.global.shared::cta.bulk_group [%0], [%1], %2;" ::"l"(wimg + (w2o + w2piece(i, q) * (kWChunk / 2))),
                           "r"(sbase + kW1Off + i * (kWChunk / 2)), "r"(kWChunk / 2) : "memory");
            asm volatile("cp.async.bulk.commit_group;" ::: "memory");
          }
          __syncwarp();
          asm volatile("bar.arrive 10, 64;" ::: "memory");
          if (elect_one()) asm volatile("cp.async.bulk.wait_group.read 0;" ::: "memory");
          if (tid == 32) GT(31);
          __syncwarp();
          asm volatile("bar.arrive 12, 64;" ::: "memory");
        }
      }
    }
    __syncwarp();
    if (wid < 4) asm volatile("bar.sync 0, 160;" ::: "memory");
    else asm volatile("bar.sync 14, 160;" ::: "memory");
    asm volatile("setmaxnreg.inc.sync.aligned.u32 240;");
    consumer(wid >> 2, out, wimg, sbase, zero, tm, tt);
  }
}

}

typedef CUresult (*PFN_encodeTiled)(CUtensorMap*, CUtensorMapDataType, cuuint32_t, void*, const cuuint64_t*,
                                    const cuuint64_t*, const cuuint32_t*, const cuuint32_t*, CUtensorMapInterleave,
                                    CUtensorMapSwizzle, CUtensorMapL2promotion, CUtensorMapFloatOOBfill);

extern "C" void kernel_launch(void* const* d_in, const int* in_sizes, int n_in, void* d_out, int out_size) {
  const __nv_bfloat16* x = (const __nv_bfloat16*)d_in[0];
  const __nv_bfloat16* wqkv = (const __nv_bfloat16*)d_in[1];
  const __nv_bfloat16* wo = (const __nv_bfloat16*)d_in[2];
  __nv_bfloat16* out = (__nv_bfloat16*)d_out;

  static PFN_encodeTiled encode = nullptr;
  static int num_sms = 0;
  static uint8_t* wimg = nullptr;
  if (!encode) {
    void* fn = nullptr;
    cudaDriverEntryPointQueryResult qres;
    cudaGetDriverEntryPoint("cuTensorMapEncodeTiled", &fn, cudaEnableDefault, &qres);
    encode = (PFN_encodeTiled)fn;
    cudaFuncSetAttribute(nat::nat_kernel, cudaFuncAttributeMaxDynamicSharedMemorySize, nat::kSmemBytes);
    cudaGetSymbolAddress((void**)&wimg, nat::g_wimg32);
    int dev = 0;
    cudaGetDevice(&dev);
    cudaDeviceGetAttribute(&num_sms, cudaDevAttrMultiProcessorCount, dev);
  }
  nat::Maps tm;
  cuuint32_t estr[5] = {1, 1, 1, 1, 1};
  {
    cuuint64_t vdim[5] = {48, 2, 105, 2, 112}, udim[5] = {48, 2, 112, 2, 105};
    cuuint64_t vstr[4] = {7 * 768, 768, 224 * 384, 2 * 224 * 384}, ustr[4] = {7 * 768, 2 * 224 * 384, 224 * 384, 768};
    CUtensorMap* maps[4] = {&tm.v6, &tm.v2, &tm.v14, &tm.u8};
    for (int i = 0; i < 4; i++) {
      cuuint32_t box[5] = {4, 2, i < 3 ? 4u : 8u, 1, i == 0 ? 6u : i == 1 ? 2u : i == 2 ? 14u : 3u};
      encode(maps[i], CU_TENSOR_MAP_DATA_TYPE_UINT32, 5, (void*)x, i < 3 ? vdim : udim, i < 3 ? vstr : ustr, box, estr,
             CU_TENSOR_MAP_INTERLEAVE_16B, CU_TENSOR_MAP_SWIZZLE_128B, CU_TENSOR_MAP_L2_PROMOTION_L2_128B, CU_TENSOR_MAP_FLOAT_OOB_FILL_NONE);
    }
  }
  for (int i = 0; i < 8; i++) {
    const cuuint32_t row = 224 * 384;
    const cuuint32_t shape[8][6] = {{2, 8, 4, 2 * row, 768, 4 * row}, {2, 8, 3, row, 768, 2 * row},     {2, 8, 1, 2 * row, 768, 4 * row},
                                    {8, 2, 3, 2 * row, 4 * 384, 384}, {8, 2, 1, 2 * row, 5 * 384, 384}, {4, 2, 3, 4 * row, 2 * row, 128},
                                    {4, 2, 3, 768, row, 128},         {4, 2, 3, 768, 2 * row, 128}};
    const cuuint32_t* sh = shape[i];
    cuuint64_t dim[5] = {64, sh[0], sh[1], sh[2], 224 * 224 * 3};
    cuuint64_t str[4] = {sh[3], sh[4], sh[5], 128};
    cuuint32_t box[5] = {64, sh[0], sh[1], sh[2], 1};
    encode(tm.px + i, CU_TENSOR_MAP_DATA_TYPE_BFLOAT16, 5, i < 5 ? (void*)x : (void*)out, dim, str, box, estr, CU_TENSOR_MAP_INTERLEAVE_NONE,
           CU_TENSOR_MAP_SWIZZLE_128B, i < 5 ? CU_TENSOR_MAP_L2_PROMOTION_L2_128B : CU_TENSOR_MAP_L2_PROMOTION_NONE,
           CU_TENSOR_MAP_FLOAT_OOB_FILL_NONE);
  }
  for (int i = 0; i < 2; i++) {
    cuuint64_t dim[3] = {i ? 32u : 64u, 192, i ? 6u : 9u}, str[2] = {i ? 384u : 1152u, i ? 64u : 128u};
    cuuint32_t box[3] = {i ? 32u : 64u, i ? 192u : 64u, 3};
    encode(i ? &tm.wo : &tm.wv, CU_TENSOR_MAP_DATA_TYPE_BFLOAT16, 3, i ? (void*)wo : (void*)wqkv, dim, str, box, estr,
           CU_TENSOR_MAP_INTERLEAVE_NONE, i ? CU_TENSOR_MAP_SWIZZLE_64B : CU_TENSOR_MAP_SWIZZLE_128B, CU_TENSOR_MAP_L2_PROMOTION_L2_256B,
           CU_TENSOR_MAP_FLOAT_OOB_FILL_NONE);
  }
  nat::TileTable tt;
  nat::make_tiles(tt);
  const int grid = nat::kCtas;
  if (num_sms >= grid) {
    nat::nat_kernel<<<grid, 384, nat::kSmemBytes>>>(x, out, wqkv, wo, wimg, 0u, tm, tt);
  } else {
    nat::fold_kernel<<<27, 256>>>(wqkv, wo, wimg);
    nat::nat_kernel<<<grid, 384, nat::kSmemBytes>>>(x, out, nullptr, nullptr, wimg, 0u, tm, tt);
  }
}
```
